```python
import torch

def _softmax(x, axis=-1):
    return torch.softmax(x, dim=axis)

def _gelu(x):
    return torch.nn.functional.gelu(x, approximate='tanh')

def _silu(x):
    return torch.nn.functional.silu(x)

def _sigmoid(x):
    return torch.sigmoid(x)

def _layernorm(x, axis=-1, eps=1e-05):
    m = x.mean(dim=axis, keepdim=True)
    v = x.var(dim=axis, keepdim=True, unbiased=False)
    return (x - m) / torch.sqrt(v + eps)

def _scatter_add(tgt, idx, src, axis=0):
    return tgt.clone().index_add_(axis, idx, src)

def _segment_sum(src, seg, n):
    out = torch.zeros((n,) + src.shape[1:], dtype=src.dtype)
    return out.index_add_(0, seg, src)

def _pad(x, pw):
    flat = tuple((v for pair in reversed(pw) for v in pair))
    return torch.nn.functional.pad(x, flat)
kernel_name = 'adaLN_cond__memory_aug_recurrent_mem_tr__dense_activation_gelu__prompt'

def setup_inputs():

    _w = lambda a: (lambda t: t.to(torch.bfloat16) if t.is_floating_point() else t)(torch.as_tensor(a))

    def _A_setup():
        B, S, Dm = (1, 2048, 1024)
        H, Dh = (32, 128)
        M, seg = (8, 32)
        seg = min(seg, S)
        S = S // seg * seg
        return {'x': _w((lambda *s: torch.randn(*s, dtype=torch.bfloat16) * 0.05)(B, S, Dm)), 'mem0': _w((lambda *s: torch.randn(*s, dtype=torch.bfloat16) * 0.8)(B, M, Dm)), 'Wq': _w((lambda *s: torch.randn(*s, dtype=torch.bfloat16) * 1.6)(Dm, H, Dh) * Dm ** (-0.5)), 'Wk': _w((lambda *s: torch.randn(*s, dtype=torch.bfloat16) * 1.6)(Dm, H, Dh) * Dm ** (-0.5)), 'Wv': _w((lambda *s: torch.randn(*s, dtype=torch.bfloat16) * 0.8)(Dm, H, Dh) * Dm ** (-0.5)), 'Wo': _w((lambda *s: torch.randn(*s, dtype=torch.bfloat16) * 0.8)(H, Dh, Dm) * (H * Dh) ** (-0.5)), 'seg_len': seg}
    _A_in = _A_setup()

    def _B_setup():
        B, S, D, F = (1, 2048, 1024, 3584)
        return {'x': _w((lambda *s: torch.randn(*s, dtype=torch.bfloat16) * 0.05)(B, S, D)), 'w1': _w((lambda *s: torch.randn(*s, dtype=torch.bfloat16) * 1.6)(D, F) * D ** (-0.5)), 'b1': _w((lambda *s: torch.randn(*s, dtype=torch.bfloat16) * 1.6)(F) * 0.01), 'w2': _w((lambda *s: torch.randn(*s, dtype=torch.bfloat16) * 0.2)(F, D) * F ** (-0.5)), 'b2': _w((lambda *s: torch.randn(*s, dtype=torch.bfloat16) * 0.2)(D) * 0.01)}
    _B_in = _B_setup()
    return {'A_x': _A_in['x'], 'A_mem0': _A_in['mem0'], 'A_Wq': _A_in['Wq'], 'A_Wk': _A_in['Wk'], 'A_Wv': _A_in['Wv'], 'A_Wo': _A_in['Wo'], 'A_seg_len': _A_in['seg_len'], 'B_x': _B_in['x'], 'B_w1': _B_in['w1'], 'B_b1': _B_in['b1'], 'B_w2': _B_in['w2'], 'B_b2': _B_in['b2'], 'c': _w((lambda *s: torch.randn(*s, dtype=torch.bfloat16) * 0.05)(1, 1024) * 8.0), 'w_mod': _w((lambda *s: torch.randn(*s, dtype=torch.bfloat16) * 0.05)(1024, 6 * 1024) * 1024 ** (-0.5) * 8.0)}

def reference(A_x, A_mem0, A_Wq, A_Wk, A_Wv, A_Wo, A_seg_len, B_x, B_w1, B_b1, B_w2, B_b2, c, w_mod):

    def _A_ref(x, mem0, Wq, Wk, Wv, Wo, seg_len):
        B, S, Dm = x.shape
        H, Dh = (Wq.shape[1], Wq.shape[2])
        M = mem0.shape[1]
        scale = Dh ** (-0.5)
        n_seg = S // seg_len
        L = M + seg_len
        idx = torch.arange(L)
        mask = (idx[:, None] < M) | (idx[:, None] >= idx[None, :])
        mem = mem0
        outs = []
        for s in range(n_seg):
            xs = x[:, s * seg_len:(s + 1) * seg_len, :].clone()
            h = torch.concatenate([mem, xs], axis=1)
            q = torch.einsum('btd,dhe->bhte', h, Wq)
            k = torch.einsum('btd,dhe->bhte', h, Wk)
            v = torch.einsum('btd,dhe->bhte', h, Wv)
            scores = torch.einsum('bhqe,bhke->bhqk', q, k) * scale
            scores = torch.where(mask[None, None], scores, -1000000000.0)
            p = _softmax(scores, axis=-1)
            o = torch.einsum('bhqk,bhke->bhqe', p, v)
            o = torch.einsum('bhte,hed->btd', o, Wo)
            mem = o[:, :M, :].clone()
            outs.append(o[:, M:, :])
        return torch.concatenate(outs, axis=1)

    def _B_ref(x, w1, b1, w2, b2):
        h = torch.einsum('bsd,df->bsf', x, w1) + b1
        h = _gelu(h)
        return torch.einsum('bsf,fd->bsd', h, w2) + b2
    x = A_x
    mod = (_silu(c) @ w_mod).reshape(c.shape[0], 6, 1, -1)
    sa, ca, ga, sb, cb, gb = (mod[:, 0].clone(), mod[:, 1].clone(), mod[:, 2].clone(), mod[:, 3].clone(), mod[:, 4].clone(), mod[:, 5].clone())
    h = _layernorm(x, axis=-1) * (1 + ca) + sa
    x = x + ga * _A_ref(h, A_mem0, A_Wq, A_Wk, A_Wv, A_Wo, A_seg_len)
    h = _layernorm(x, axis=-1) * (1 + cb) + sb
    x = x + gb * _B_ref(h, B_w1, B_b1, B_w2, B_b2)
    return x
```

```cpp
#include <cuda_runtime.h>
#include <cuda.h>
#include <cuda_bf16.h>
#include <stdint.h>

typedef __nv_bfloat16 bf16;

__device__ __align__(16) float g_mod[6144];
__device__ __align__(1024) uint4 g_modp[4 * 512];
__device__ unsigned g_hcnt;
__device__ __align__(1024) uint4 g_h[2048 * 1024 / 8];
__device__ __align__(1024) uint4 g_O[2048 * 4096 / 8];
__device__ __align__(1024) uint4 g_h2[2048 * 1024 / 8];
__device__ __align__(1024) uint4 g_x1[2048 * 1024 / 8];
__device__ __align__(1024) uint4 g_U[2048 * 3584 / 8];
__device__ __align__(1024) uint4 g_stat[2048 * 4];
__device__ __align__(1024) unsigned g_cnt[16 * 4 * 32];
__device__ unsigned g_mcnt;
__device__ unsigned g_slot[256];
__device__ unsigned g_fin;
__device__ __align__(16) uint4 g_cc[224 * 4];
__device__ __align__(1024) uint4 g_ar[160 * 64];
__device__ __align__(1024) uint4 g_xc[33 * 16384];
__device__ __align__(1024) unsigned g_tm[4 * 256];
#define FT(i)
#define FTP(i)
#define PH(i)
#define RP(i)
#define RPN(i, s)
#define TSV(i, v)
#define TS(i)

#define WIN 2
#define FRC "232"
#define FRP "40"
#define YR 1
#define XPK 0
#define NFA 1
#define PINM 1
#define FMAP (((g & 3) * 4 + m) * 8 + (g >> 2) * 2 + (blockIdx.x & 1))
#define DBG 0
#define MC 0
#define ALIAS 3
#define EF 0
#define XDL 6
#define QW 0
#define PDS 61
#define P_NVR 5
#define P_NVP 2
#define P_NWP 9
#define P_NW1 7
#define RF_ 208
#define PSV 1
#define RA_ (488 - 2 * RF_)
#define XI 5
#define XL 1
#define WCH 2
#define HX 0
#define VB 1
#define HU_ 32
#define HP 2
#define HS 1
constexpr int HU = HU_;
#define TP 0
#define CKI 0
#define NOP_ 2
#define KVO 0
#define NDL 3
#define AM 0
#define XM 3
#define XP 0
#define SPIN_LIMIT (1 << 20)
__device__ __forceinline__ uint64_t mkdesc(uint32_t addr, uint32_t lbo, uint32_t sbo) {
  return (uint64_t)((addr & 0x3FFFF) >> 4) | ((uint64_t)(lbo >> 4) << 16) | ((uint64_t)(sbo >> 4) << 32) | (1ull << 62);
}
__device__ __forceinline__ void mbar_init(uint32_t a, int c) { asm volatile("mbarrier.init.shared.b64 [%0],%1;" ::"r"(a), "r"(c) : "memory"); }
__device__ __forceinline__ void mbar_wait(uint32_t a, uint32_t par) {
  asm volatile(
      "{.reg .pred p; .reg .u32 n;\n"
      "mov.u32 n, 0;\n"
      "W: mbarrier.try_wait.parity.shared.b64 p,[%0],%1;\n"
      "@p bra D;\n"
      "add.u32 n, n, 1;\n"
      "setp.lt.u32 p, n, %2;\n"
      "@p bra W;\n"
      "trap;\n"
      "D:}" ::"r"(a), "r"(par), "n"(SPIN_LIMIT) : "memory");
}
__device__ __forceinline__ void mbar_wait_q(uint32_t a, uint32_t par) {
  asm volatile(
      "{.reg .pred p; .reg .u32 n;\n"
      "mov.u32 n, 0;\n"
      "W: mbarrier.try_wait.parity.shared.b64 p,[%0],%1,4000;\n"
      "@p bra D;\n"
      "add.u32 n, n, 1;\n"
      "setp.lt.u32 p, n, %2;\n"
      "@p bra W;\n"
      "trap;\n"
      "D:}" ::"r"(a), "r"(par), "n"(SPIN_LIMIT / 16) : "memory");
}
__device__ __forceinline__ void mbar_expect(uint32_t a, uint32_t b) { asm volatile("mbarrier.arrive.expect_tx.shared.b64 _,[%0],%1;" ::"r"(a), "r"(b) : "memory"); }
__device__ __forceinline__ void mbar_arrive(uint32_t a) { asm volatile("mbarrier.arrive.shared.b64 _,[%0];" ::"r"(a) : "memory"); }
__device__ __forceinline__ uint32_t mapa(uint32_t a, uint32_t cta) { uint32_t r; asm("mapa.shared::cluster.u32 %0,%1,%2;" : "=r"(r) : "r"(a), "r"(cta)); return r; }
__device__ __forceinline__ void mbar_arrive_cl(uint32_t a) { asm volatile("mbarrier.arrive.shared::cluster.b64 _,[%0];" ::"r"(a) : "memory"); }
__device__ __forceinline__ void tma2d(uint32_t dst, const CUtensorMap* m, int c0, int c1, uint32_t mb) {
  asm volatile("cp.async.bulk.tensor.2d.shared::cluster.global.mbarrier::complete_tx::bytes [%0],[%1,{%2,%3}],[%4];" ::"r"(dst), "l"(m), "r"(c0), "r"(c1), "r"(mb) : "memory");
}
__device__ __forceinline__ void tma2d_pf(const CUtensorMap* m, int c0, int c1) {
  asm volatile("cp.async.bulk.prefetch.tensor.2d.L2.global [%0,{%1,%2}];" ::"l"(m), "r"(c0), "r"(c1) : "memory");
}
__device__ __forceinline__ void tma3d(uint32_t dst, const CUtensorMap* m, int c1, int c2, uint32_t mb) {
  asm volatile("cp.async.bulk.tensor.3d.shared::cluster.global.mbarrier::complete_tx::bytes [%0],[%1,{0,%2,%3}],[%4];" ::"r"(dst), "l"(m), "r"(c1), "r"(c2), "r"(mb) : "memory");
}
__device__ __forceinline__ void tma2d_st(const CUtensorMap* m, int c0, int c1, uint32_t src) {
  asm volatile("cp.async.bulk.tensor.2d.global.shared::cta.bulk_group [%0,{%1,%2}],[%3];" ::"l"(m), "r"(c0), "r"(c1), "r"(src) : "memory");
}
__device__ __forceinline__ void bulk_ld(uint32_t dst, const void* src, uint32_t n, uint32_t mb) {
  asm volatile("cp.async.bulk.shared::cluster.global.mbarrier::complete_tx::bytes [%0],[%1],%2,[%3];" ::"r"(dst), "l"(src), "r"(n), "r"(mb) : "memory");
}
__device__ __forceinline__ void bulk_ld_mc(uint32_t dst, const void* src, uint32_t n, uint32_t mb) {
  asm volatile("cp.async.bulk.shared::cluster.global.mbarrier::complete_tx::bytes.multicast::cluster [%0],[%1],%2,[%3],%4;" ::"r"(dst), "l"(src), "r"(n), "r"(mb), "h"((uint16_t)3) : "memory");
}
__device__ __forceinline__ void bulk_st(void* dst, uint32_t src, uint32_t n) {
  asm volatile("cp.async.bulk.global.shared::cta.bulk_group [%0],[%1],%2;" ::"l"(dst), "r"(src), "r"(n) : "memory");
}
__device__ __forceinline__ void e_expect_tma3d(uint32_t dst, const CUtensorMap* m, int c1, int c2, uint32_t mb, uint32_t bytes) {
  asm volatile("{.reg .pred p; elect.sync _|p, 0xffffffff; @p mbarrier.arrive.expect_tx.shared.b64 _,[%4],%5;\n"
               "@p cp.async.bulk.tensor.3d.shared::cluster.global.mbarrier::complete_tx::bytes [%0],[%1,{0,%2,%3}],[%4];}" ::"r"(dst), "l"(m), "r"(c1), "r"(c2), "r"(mb), "r"(bytes) : "memory");
}
__device__ __forceinline__ void e_bulk_ld(uint32_t dst, const void* src, uint32_t n, uint32_t mb) {
  asm volatile("{.reg .pred p; elect.sync _|p, 0xffffffff; @p cp.async.bulk.shared::cluster.global.mbarrier::complete_tx::bytes [%0],[%1],%2,[%3];}" ::"r"(dst), "l"(src), "r"(n), "r"(mb) : "memory");
}
__device__ __forceinline__ void e_bulk_ld_ef(uint32_t dst, const void* src, uint32_t n, uint32_t mb) {
  asm volatile("{.reg .pred p; .reg .b64 c; createpolicy.fractional.L2::evict_first.b64 c,1.0; elect.sync _|p, 0xffffffff;"
               " @p cp.async.bulk.shared::cluster.global.mbarrier::complete_tx::bytes.L2::cache_hint [%0],[%1],%2,[%3],c;}" ::"r"(dst), "l"(src), "r"(n), "r"(mb) : "memory");
}
__device__ __forceinline__ void e_bulk_ld_mc(uint32_t dst, const void* src, uint32_t n, uint32_t mb) {
  asm volatile("{.reg .pred p; elect.sync _|p, 0xffffffff; @p cp.async.bulk.shared::cluster.global.mbarrier::complete_tx::bytes.multicast::cluster [%0],[%1],%2,[%3],%4;}" ::"r"(dst), "l"(src), "r"(n), "r"(mb), "h"((uint16_t)3) : "memory");
}
#define BULK_COMMIT() asm volatile("cp.async.bulk.commit_group;" ::: "memory")
#define BULK_WAIT_READ(n) asm volatile("cp.async.bulk.wait_group.read " #n ";" ::: "memory")
#define BULK_WAIT(n) asm volatile("cp.async.bulk.wait_group " #n ";" ::: "memory")
#define FENCE_ASYNC_SMEM() asm volatile("fence.proxy.async.shared::cta;" ::: "memory")
#define FENCE_ASYNC() asm volatile("fence.proxy.async;" ::: "memory")
#define WG_FENCE() asm volatile("wgmma.fence.sync.aligned;" ::: "memory")
#define WG_COMMIT() asm volatile("wgmma.commit_group.sync.aligned;" ::: "memory")
#define WG_WAIT(n) asm volatile("wgmma.wait_group.sync.aligned " #n ";" ::: "memory")
#define BAR_SYNC(id, n) asm volatile("bar.sync %0,%1;" ::"n"(id), "n"(n) : "memory")
#define BAR_ARRIVE(id, n) asm volatile("bar.arrive %0,%1;" ::"n"(id), "n"(n) : "memory")
#define SCHED_FENCE(k) asm volatile("{.reg .pred p; setp.ne.u32 p,%0,0; @p trap;}" ::"r"(mp.zero[(k) - 46]) : "memory")
#define CLUSTER_SYNC() asm volatile("barrier.cluster.arrive.aligned; barrier.cluster.wait.aligned;" ::: "memory")
__device__ __forceinline__ uint32_t pk(float lo, float hi) { uint32_t r; asm("cvt.rn.bf16x2.f32 %0,%1,%2;" : "=r"(r) : "f"(hi), "f"(lo)); return r; }
__device__ __forceinline__ float blo(uint32_t v) { return __uint_as_float(v << 16); }
__device__ __forceinline__ float bhi(uint32_t v) { return __uint_as_float(v & 0xffff0000u); }
__device__ __forceinline__ void ldsm4(uint32_t* r, uint32_t a) {
  asm volatile("ldmatrix.sync.aligned.m8n8.x4.shared.b16 {%0,%1,%2,%3},[%4];" : "=r"(r[0]), "=r"(r[1]), "=r"(r[2]), "=r"(r[3]) : "r"(a) : "memory");
}
__device__ __forceinline__ void ldsm4t(uint32_t* r, uint32_t a) {
  asm volatile("ldmatrix.sync.aligned.m8n8.x4.trans.shared.b16 {%0,%1,%2,%3},[%4];" : "=r"(r[0]), "=r"(r[1]), "=r"(r[2]), "=r"(r[3]) : "r"(a) : "memory");
}
__device__ __forceinline__ void stsm4(uint32_t a, uint32_t r0, uint32_t r1, uint32_t r2, uint32_t r3) {
  asm volatile("stmatrix.sync.aligned.m8n8.x4.shared.b16 [%0],{%1,%2,%3,%4};" ::"r"(a), "r"(r0), "r"(r1), "r"(r2), "r"(r3) : "memory");
}
__device__ __forceinline__ void mma16(float* d, uint32_t a0, uint32_t a1, uint32_t a2, uint32_t a3, uint32_t b0, uint32_t b1) {
  asm volatile("mma.sync.aligned.m16n8k16.row.col.f32.bf16.bf16.f32 {%0,%1,%2,%3},{%4,%5,%6,%7},{%8,%9},{%0,%1,%2,%3};"
               : "+f"(d[0]), "+f"(d[1]), "+f"(d[2]), "+f"(d[3]) : "r"(a0), "r"(a1), "r"(a2), "r"(a3), "r"(b0), "r"(b1));
}
__device__ __forceinline__ void mma8(float* d, uint32_t a0, uint32_t a1, uint32_t b0) {
  asm volatile("mma.sync.aligned.m16n8k8.row.col.f32.bf16.bf16.f32 {%0,%1,%2,%3},{%4,%5},{%6},{%0,%1,%2,%3};"
               : "+f"(d[0]), "+f"(d[1]), "+f"(d[2]), "+f"(d[3]) : "r"(a0), "r"(a1), "r"(b0));
}
__device__ __forceinline__ float4 lds4f(uint32_t a) { float4 v; asm volatile("ld.shared.v4.f32 {%0,%1,%2,%3},[%4];" : "=f"(v.x), "=f"(v.y), "=f"(v.z), "=f"(v.w) : "r"(a) : "memory"); return v; }
__device__ __forceinline__ float2 lds2f(uint32_t a) { float2 v; asm volatile("ld.shared.v2.f32 {%0,%1},[%2];" : "=f"(v.x), "=f"(v.y) : "r"(a) : "memory"); return v; }
__device__ __forceinline__ uint4 lds4(uint32_t a) { uint4 v; asm volatile("ld.shared.v4.u32 {%0,%1,%2,%3},[%4];" : "=r"(v.x), "=r"(v.y), "=r"(v.z), "=r"(v.w) : "r"(a) : "memory"); return v; }
__device__ __forceinline__ uint2 lds2u(uint32_t a) { uint2 v; asm volatile("ld.shared.v2.u32 {%0,%1},[%2];" : "=r"(v.x), "=r"(v.y) : "r"(a) : "memory"); return v; }
__device__ __forceinline__ uint32_t lds1(uint32_t a) { uint32_t v; asm volatile("ld.shared.u32 %0,[%1];" : "=r"(v) : "r"(a) : "memory"); return v; }
__device__ __forceinline__ void sts4(uint32_t a, uint32_t x, uint32_t y, uint32_t z, uint32_t w) { asm volatile("st.shared.v4.u32 [%0],{%1,%2,%3,%4};" ::"r"(a), "r"(x), "r"(y), "r"(z), "r"(w) : "memory"); }
__device__ __forceinline__ void sts2(uint32_t a, uint32_t x, uint32_t y) { asm volatile("st.shared.v2.u32 [%0],{%1,%2};" ::"r"(a), "r"(x), "r"(y) : "memory"); }
__device__ __forceinline__ void sts1(uint32_t a, uint32_t x) { asm volatile("st.shared.u32 [%0],%1;" ::"r"(a), "r"(x) : "memory"); }
__device__ __forceinline__ void sta4(uint32_t a, const uint32_t* v, uint32_t mb) {
  asm volatile("st.async.shared::cluster.mbarrier::complete_tx::bytes.v4.b32 [%0],{%1,%2,%3,%4},[%5];" ::"r"(a), "r"(v[0]), "r"(v[1]), "r"(v[2]), "r"(v[3]), "r"(mb) : "memory");
}
__device__ __forceinline__ uint4 ldg_rlx4(const void* p) { uint4 v; asm volatile("ld.relaxed.gpu.global.v4.u32 {%0,%1,%2,%3},[%4];" : "=r"(v.x), "=r"(v.y), "=r"(v.z), "=r"(v.w) : "l"(p) : "memory"); return v; }
__device__ __forceinline__ uint32_t ldg_rlx1(const void* p) { uint32_t v; asm volatile("ld.relaxed.gpu.global.u32 %0,[%1];" : "=r"(v) : "l"(p) : "memory"); return v; }
__device__ __forceinline__ uint2 ldg_rlx2(const void* p) { uint2 v; asm volatile("ld.relaxed.gpu.global.v2.u32 {%0,%1},[%2];" : "=r"(v.x), "=r"(v.y) : "l"(p) : "memory"); return v; }
__device__ __forceinline__ uint4 ldg_b128(const void* p) {
  uint4 v;
  asm volatile("{.reg .b128 t; .reg .b64 a,b; ld.relaxed.gpu.global.b128 t,[%4]; mov.b128 {a,b},t; mov.b64 {%0,%1},a; mov.b64 {%2,%3},b;}" : "=r"(v.x), "=r"(v.y), "=r"(v.z), "=r"(v.w) : "l"(p) : "memory");
  return v;
}
__device__ __forceinline__ void stg_b128(void* p, uint32_t x, uint32_t y, uint32_t z, uint32_t w) {
  asm volatile("{.reg .b128 t; .reg .b64 a,b; mov.b64 a,{%1,%2}; mov.b64 b,{%3,%4}; mov.b128 t,{a,b}; st.relaxed.gpu.global.b128 [%0],t;}" ::"l"(p), "r"(x), "r"(y), "r"(z), "r"(w) : "memory");
}
__device__ __forceinline__ void st_b128(void* p, uint32_t x, uint32_t y, uint32_t z, uint32_t w) {
  asm volatile("{.reg .b128 t; .reg .b64 a,b; mov.b64 a,{%1,%2}; mov.b64 b,{%3,%4}; mov.b128 t,{a,b}; st.relaxed.gpu.b128 [%0],t;}" ::"l"(p), "r"(x), "r"(y), "r"(z), "r"(w) : "memory");
}
__device__ __forceinline__ void stg_rlx4(void* p, uint32_t x, uint32_t y, uint32_t z, uint32_t w) { asm volatile("st.relaxed.gpu.global.v4.u32 [%0],{%1,%2,%3,%4};" ::"l"(p), "r"(x), "r"(y), "r"(z), "r"(w) : "memory"); }
__device__ __forceinline__ void stg_rlx2(void* p, uint32_t x, uint32_t y) { asm volatile("st.relaxed.gpu.global.v2.u32 [%0],{%1,%2};" ::"l"(p), "r"(x), "r"(y) : "memory"); }
__device__ __forceinline__ void red4(void* p, float a, float b, float c, float d) { asm volatile("red.relaxed.gpu.global.add.v4.f32 [%0],{%1,%2,%3,%4};" ::"l"(p), "f"(a), "f"(b), "f"(c), "f"(d) : "memory"); }
__device__ __forceinline__ unsigned ld_acq(const unsigned* p) { unsigned v; asm volatile("ld.acquire.gpu.global.u32 %0,[%1];" : "=r"(v) : "l"(p) : "memory"); return v; }
__device__ __forceinline__ void red_rel(unsigned* p) { asm volatile("red.release.gpu.global.add.u32 [%0],1;" ::"l"(p) : "memory"); }
__device__ __forceinline__ void wait_cnt(const unsigned* p, unsigned n) { int it = 0; while (ld_acq(p) < n) { if (++it > SPIN_LIMIT) __trap(); } }
__device__ __forceinline__ uint32_t clk() { uint32_t c; asm volatile("mov.u32 %0,%%clock;" : "=r"(c)); return c; }
__device__ __forceinline__ uint32_t gtime() { uint32_t c; asm volatile("mov.u32 %0,%%globaltimer_lo;" : "=r"(c)); return c; }
__device__ __forceinline__ void wait_until(uint32_t t0, uint32_t d) { while (clk() - t0 < d) {} }
__device__ __forceinline__ float ex2(float x) { float r; asm("ex2.approx.ftz.f32 %0,%1;" : "=f"(r) : "f"(x)); return r; }
__device__ __forceinline__ float silu(float x) { return x * __frcp_rn(1.f + __expf(-x)); }
__device__ __forceinline__ float rbf(float x) { return __bfloat162float(__float2bfloat16_rn(x)); }

__device__ __forceinline__ void wgmma_ss_n128(float* d, uint64_t a, uint64_t b, int sd) {
  asm volatile("{.reg .pred p; setp.ne.b32 p, %66, 0;\n"
    "wgmma.mma_async.sync.aligned.m64n128k16.f32.bf16.bf16 {%0,%1,%2,%3,%4,%5,%6,%7,%8,%9,%10,%11,%12,%13,%14,%15,%16,%17,%18,%19,%20,%21,%22,%23,%24,%25,%26,%27,%28,%29,%30,%31,%32,%33,%34,%35,%36,%37,%38,%39,%40,%41,%42,%43,%44,%45,%46,%47,%48,%49,%50,%51,%52,%53,%54,%55,%56,%57,%58,%59,%60,%61,%62,%63}, %64, %65, p, 1, 1, 0, 1;}\n"
    : "+f"(d[0]),"+f"(d[1]),"+f"(d[2]),"+f"(d[3]),"+f"(d[4]),"+f"(d[5]),"+f"(d[6]),"+f"(d[7]),
      "+f"(d[8]),"+f"(d[9]),"+f"(d[10]),"+f"(d[11]),"+f"(d[12]),"+f"(d[13]),"+f"(d[14]),"+f"(d[15]),
      "+f"(d[16]),"+f"(d[17]),"+f"(d[18]),"+f"(d[19]),"+f"(d[20]),"+f"(d[21]),"+f"(d[22]),"+f"(d[23]),
      "+f"(d[24]),"+f"(d[25]),"+f"(d[26]),"+f"(d[27]),"+f"(d[28]),"+f"(d[29]),"+f"(d[30]),"+f"(d[31]),
      "+f"(d[32]),"+f"(d[33]),"+f"(d[34]),"+f"(d[35]),"+f"(d[36]),"+f"(d[37]),"+f"(d[38]),"+f"(d[39]),
      "+f"(d[40]),"+f"(d[41]),"+f"(d[42]),"+f"(d[43]),"+f"(d[44]),"+f"(d[45]),"+f"(d[46]),"+f"(d[47]),
      "+f"(d[48]),"+f"(d[49]),"+f"(d[50]),"+f"(d[51]),"+f"(d[52]),"+f"(d[53]),"+f"(d[54]),"+f"(d[55]),
      "+f"(d[56]),"+f"(d[57]),"+f"(d[58]),"+f"(d[59]),"+f"(d[60]),"+f"(d[61]),"+f"(d[62]),"+f"(d[63])
    : "l"(a), "l"(b), "r"(sd));
}
__device__ __forceinline__ void wgmma_ss_n192(float* d, uint64_t a, uint64_t b, int sd) {
  asm volatile("{.reg .pred p; setp.ne.b32 p, %98, 0;\n"
    "wgmma.mma_async.sync.aligned.m64n192k16.f32.bf16.bf16 {%0,%1,%2,%3,%4,%5,%6,%7,%8,%9,%10,%11,%12,%13,%14,%15,%16,%17,%18,%19,%20,%21,%22,%23,%24,%25,%26,%27,%28,%29,%30,%31,%32,%33,%34,%35,%36,%37,%38,%39,%40,%41,%42,%43,%44,%45,%46,%47,%48,%49,%50,%51,%52,%53,%54,%55,%56,%57,%58,%59,%60,%61,%62,%63,%64,%65,%66,%67,%68,%69,%70,%71,%72,%73,%74,%75,%76,%77,%78,%79,%80,%81,%82,%83,%84,%85,%86,%87,%88,%89,%90,%91,%92,%93,%94,%95}, %96, %97, p, 1, 1, 0, 1;}\n"
    : "+f"(d[0]),"+f"(d[1]),"+f"(d[2]),"+f"(d[3]),"+f"(d[4]),"+f"(d[5]),"+f"(d[6]),"+f"(d[7]),
      "+f"(d[8]),"+f"(d[9]),"+f"(d[10]),"+f"(d[11]),"+f"(d[12]),"+f"(d[13]),"+f"(d[14]),"+f"(d[15]),
      "+f"(d[16]),"+f"(d[17]),"+f"(d[18]),"+f"(d[19]),"+f"(d[20]),"+f"(d[21]),"+f"(d[22]),"+f"(d[23]),
      "+f"(d[24]),"+f"(d[25]),"+f"(d[26]),"+f"(d[27]),"+f"(d[28]),"+f"(d[29]),"+f"(d[30]),"+f"(d[31]),
      "+f"(d[32]),"+f"(d[33]),"+f"(d[34]),"+f"(d[35]),"+f"(d[36]),"+f"(d[37]),"+f"(d[38]),"+f"(d[39]),
      "+f"(d[40]),"+f"(d[41]),"+f"(d[42]),"+f"(d[43]),"+f"(d[44]),"+f"(d[45]),"+f"(d[46]),"+f"(d[47]),
      "+f"(d[48]),"+f"(d[49]),"+f"(d[50]),"+f"(d[51]),"+f"(d[52]),"+f"(d[53]),"+f"(d[54]),"+f"(d[55]),
      "+f"(d[56]),"+f"(d[57]),"+f"(d[58]),"+f"(d[59]),"+f"(d[60]),"+f"(d[61]),"+f"(d[62]),"+f"(d[63]),
      "+f"(d[64]),"+f"(d[65]),"+f"(d[66]),"+f"(d[67]),"+f"(d[68]),"+f"(d[69]),"+f"(d[70]),"+f"(d[71]),
      "+f"(d[72]),"+f"(d[73]),"+f"(d[74]),"+f"(d[75]),"+f"(d[76]),"+f"(d[77]),"+f"(d[78]),"+f"(d[79]),
      "+f"(d[80]),"+f"(d[81]),"+f"(d[82]),"+f"(d[83]),"+f"(d[84]),"+f"(d[85]),"+f"(d[86]),"+f"(d[87]),
      "+f"(d[88]),"+f"(d[89]),"+f"(d[90]),"+f"(d[91]),"+f"(d[92]),"+f"(d[93]),"+f"(d[94]),"+f"(d[95])
    : "l"(a), "l"(b), "r"(sd));
}
__device__ __forceinline__ void wgmma_ss_n256(float* d, uint64_t a, uint64_t b, int sd) {
  asm volatile("{.reg .pred p; setp.ne.b32 p, %130, 0;\n"
    "wgmma.mma_async.sync.aligned.m64n256k16.f32.bf16.bf16 {%0,%1,%2,%3,%4,%5,%6,%7,%8,%9,%10,%11,%12,%13,%14,%15,%16,%17,%18,%19,%20,%21,%22,%23,%24,%25,%26,%27,%28,%29,%30,%31,%32,%33,%34,%35,%36,%37,%38,%39,%40,%41,%42,%43,%44,%45,%46,%47,%48,%49,%50,%51,%52,%53,%54,%55,%56,%57,%58,%59,%60,%61,%62,%63,%64,%65,%66,%67,%68,%69,%70,%71,%72,%73,%74,%75,%76,%77,%78,%79,%80,%81,%82,%83,%84,%85,%86,%87,%88,%89,%90,%91,%92,%93,%94,%95,%96,%97,%98,%99,%100,%101,%102,%103,%104,%105,%106,%107,%108,%109,%110,%111,%112,%113,%114,%115,%116,%117,%118,%119,%120,%121,%122,%123,%124,%125,%126,%127}, %128, %129, p, 1, 1, 0, 1;}\n"
    : "+f"(d[0]),"+f"(d[1]),"+f"(d[2]),"+f"(d[3]),"+f"(d[4]),"+f"(d[5]),"+f"(d[6]),"+f"(d[7]),
      "+f"(d[8]),"+f"(d[9]),"+f"(d[10]),"+f"(d[11]),"+f"(d[12]),"+f"(d[13]),"+f"(d[14]),"+f"(d[15]),
      "+f"(d[16]),"+f"(d[17]),"+f"(d[18]),"+f"(d[19]),"+f"(d[20]),"+f"(d[21]),"+f"(d[22]),"+f"(d[23]),
      "+f"(d[24]),"+f"(d[25]),"+f"(d[26]),"+f"(d[27]),"+f"(d[28]),"+f"(d[29]),"+f"(d[30]),"+f"(d[31]),
      "+f"(d[32]),"+f"(d[33]),"+f"(d[34]),"+f"(d[35]),"+f"(d[36]),"+f"(d[37]),"+f"(d[38]),"+f"(d[39]),
      "+f"(d[40]),"+f"(d[41]),"+f"(d[42]),"+f"(d[43]),"+f"(d[44]),"+f"(d[45]),"+f"(d[46]),"+f"(d[47]),
      "+f"(d[48]),"+f"(d[49]),"+f"(d[50]),"+f"(d[51]),"+f"(d[52]),"+f"(d[53]),"+f"(d[54]),"+f"(d[55]),
      "+f"(d[56]),"+f"(d[57]),"+f"(d[58]),"+f"(d[59]),"+f"(d[60]),"+f"(d[61]),"+f"(d[62]),"+f"(d[63]),
      "+f"(d[64]),"+f"(d[65]),"+f"(d[66]),"+f"(d[67]),"+f"(d[68]),"+f"(d[69]),"+f"(d[70]),"+f"(d[71]),
      "+f"(d[72]),"+f"(d[73]),"+f"(d[74]),"+f"(d[75]),"+f"(d[76]),"+f"(d[77]),"+f"(d[78]),"+f"(d[79]),
      "+f"(d[80]),"+f"(d[81]),"+f"(d[82]),"+f"(d[83]),"+f"(d[84]),"+f"(d[85]),"+f"(d[86]),"+f"(d[87]),
      "+f"(d[88]),"+f"(d[89]),"+f"(d[90]),"+f"(d[91]),"+f"(d[92]),"+f"(d[93]),"+f"(d[94]),"+f"(d[95]),
      "+f"(d[96]),"+f"(d[97]),"+f"(d[98]),"+f"(d[99]),"+f"(d[100]),"+f"(d[101]),"+f"(d[102]),"+f"(d[103]),
      "+f"(d[104]),"+f"(d[105]),"+f"(d[106]),"+f"(d[107]),"+f"(d[108]),"+f"(d[109]),"+f"(d[110]),"+f"(d[111]),
      "+f"(d[112]),"+f"(d[113]),"+f"(d[114]),"+f"(d[115]),"+f"(d[116]),"+f"(d[117]),"+f"(d[118]),"+f"(d[119]),
      "+f"(d[120]),"+f"(d[121]),"+f"(d[122]),"+f"(d[123]),"+f"(d[124]),"+f"(d[125]),"+f"(d[126]),"+f"(d[127])
    : "l"(a), "l"(b), "r"(sd));
}
__device__ __forceinline__ void wgmma_rs_n32(float* d, const uint32_t* a, uint64_t b, int sd) {
  asm volatile("{.reg .pred p; setp.ne.b32 p, %21, 0;\n"
    "wgmma.mma_async.sync.aligned.m64n32k16.f32.bf16.bf16 {%0,%1,%2,%3,%4,%5,%6,%7,%8,%9,%10,%11,%12,%13,%14,%15}, {%16,%17,%18,%19}, %20, p, 1, 1, 0;}\n"
    : "+f"(d[0]),"+f"(d[1]),"+f"(d[2]),"+f"(d[3]),"+f"(d[4]),"+f"(d[5]),"+f"(d[6]),"+f"(d[7]),
      "+f"(d[8]),"+f"(d[9]),"+f"(d[10]),"+f"(d[11]),"+f"(d[12]),"+f"(d[13]),"+f"(d[14]),"+f"(d[15])
    : "r"(a[0]), "r"(a[1]), "r"(a[2]), "r"(a[3]), "l"(b), "r"(sd));
}
__device__ __forceinline__ void wgmma_ssT_n32(float* d, uint64_t a, uint64_t b, int sd) {
  asm volatile("{.reg .pred p; setp.ne.b32 p, %18, 0;\n"
    "wgmma.mma_async.sync.aligned.m64n32k16.f32.bf16.bf16 {%0,%1,%2,%3,%4,%5,%6,%7,%8,%9,%10,%11,%12,%13,%14,%15}, %16, %17, p, 1, 1, 1, 0;}\n"
    : "+f"(d[0]),"+f"(d[1]),"+f"(d[2]),"+f"(d[3]),"+f"(d[4]),"+f"(d[5]),"+f"(d[6]),"+f"(d[7]),
      "+f"(d[8]),"+f"(d[9]),"+f"(d[10]),"+f"(d[11]),"+f"(d[12]),"+f"(d[13]),"+f"(d[14]),"+f"(d[15])
    : "l"(a), "l"(b), "r"(sd));
}

__device__ __forceinline__ void wgmma_rs_n32_z(float* d, const uint32_t* a, uint64_t b) {
  asm volatile("{.reg .pred p; setp.ne.b32 p, 0, 0;\n"
    "wgmma.mma_async.sync.aligned.m64n32k16.f32.bf16.bf16 {%0,%1,%2,%3,%4,%5,%6,%7,%8,%9,%10,%11,%12,%13,%14,%15}, {%16,%17,%18,%19}, %20, p, 1, 1, 0;}\n"
    : "=f"(d[0]),"=f"(d[1]),"=f"(d[2]),"=f"(d[3]),"=f"(d[4]),"=f"(d[5]),"=f"(d[6]),"=f"(d[7]),
      "=f"(d[8]),"=f"(d[9]),"=f"(d[10]),"=f"(d[11]),"=f"(d[12]),"=f"(d[13]),"=f"(d[14]),"=f"(d[15])
    : "r"(a[0]), "r"(a[1]), "r"(a[2]), "r"(a[3]), "l"(b));
}

namespace rec {
constexpr int NVR = P_NVR;
constexpr int NVS = 16 - NVR;
constexpr int NVP = P_NVP;
constexpr int NWP = P_NWP;
constexpr uint32_t WO = 0;
constexpr uint32_t XB = 65536;
constexpr uint32_t PK = XB + 32768;
constexpr uint32_t VN = PK + 24576;
constexpr uint32_t VX0 = VN + 4096;
constexpr uint32_t WVS = 131072;
constexpr uint32_t MEM = WVS + 2 * NVS * 2048;
constexpr uint32_t ARO = MEM + 10240;
constexpr uint32_t OB = ARO + 5120;
constexpr uint32_t QT = OB + 2048;
constexpr uint32_t KT = QT + 2048;
constexpr uint32_t RQ = KT + 6144;
constexpr uint32_t RK = RQ + 2048;
constexpr uint32_t SC = RK + 2048;
constexpr uint32_t OT = OB;
constexpr uint32_t TF = SC + 2048;
constexpr uint32_t PRE = MEM + 2 * NVR * 2048;
constexpr uint32_t TA = TF + 8192;
constexpr uint32_t RX = TA + 6144;
constexpr uint32_t VX1 = RX + 2048;
constexpr uint32_t BARS = VX1 + 4096;
constexpr uint32_t PACE = BARS + 18 * 8;
constexpr uint32_t SMEM = BARS + 512;
static_assert(PRE + 14336 <= BARS, "staging");
constexpr int NW1 = P_NW1;
static_assert(SMEM <= 232448, "smem");
constexpr int B_E = 2, B_SC = 3, B_S = 4, B_O = 5, B_F = 6, B_W = 7, B_C = 9, B_K = 10, B_H = 15, B_Q = 1, B_S2 = 6, B_T2 = 9, B_P = 13, B_T = 14, B_R = 11, B_X = 12, B_V = 8;
constexpr int XC = 16384, X_RING = 131072, X_PT = 4096, X_SC = 65536, X_TOK = 4096;
#define X_VX(i) (((i) >> 1) * 2048 + ((i) & 1) * 512)
#define X_VM(i) (X_VX(i) + 1024)
}
struct RecMaps { CUtensorMap wq, wk, wv, wo, ari; int zero[40]; };

#define F_(x) __uint_as_float(x)
#define U_(x) __float_as_uint(x)
__device__ __forceinline__ void ar_fetch(uint32_t dst, const CUtensorMap* m, int slot, int half, uint32_t mb) {
  asm volatile("{.reg .pred p; elect.sync _|p, 0xffffffff; @p mbarrier.arrive.expect_tx.shared.b64 _,[%4],10240;\n"
               "@p cp.async.bulk.tensor.2d.shared::cluster.global.mbarrier::complete_tx::bytes [%0],[%1,{%2,%3}],[%4];\n"
               "@p cp.async.bulk.tensor.2d.shared::cluster.global.mbarrier::complete_tx::bytes [%0+5120],[%1,{%2,%5}],[%4];}"
               ::"r"(dst), "l"(m), "r"(slot * 64), "r"(half * 80), "r"(mb), "r"(half * 80 + 40) : "memory");
}
__device__ __forceinline__ void ar_fetch1(uint32_t dst, const CUtensorMap* m, int slot, int quarter, uint32_t mb) {
  asm volatile("{.reg .pred p; elect.sync _|p, 0xffffffff; @p mbarrier.arrive.expect_tx.shared.b64 _,[%4],5120;\n"
               "@p cp.async.bulk.tensor.2d.shared::cluster.global.mbarrier::complete_tx::bytes [%0],[%1,{%2,%3}],[%4];}"
               ::"r"(dst), "l"(m), "r"(slot * 64), "r"(quarter * 40), "r"(mb) : "memory");
}
__device__ __forceinline__ uint4 exch_b128(void* p, uint32_t x, uint32_t y, uint32_t z, uint32_t w) {
  uint4 v;
  asm volatile("{.reg .b128 s, t; .reg .b64 a,b; mov.b64 a,{%5,%6}; mov.b64 b,{%7,%8}; mov.b128 s,{a,b}; atom.relaxed.gpu.global.exch.b128 t,[%4],s;"
               " mov.b128 {a,b},t; mov.b64 {%0,%1},a; mov.b64 {%2,%3},b;}" : "=r"(v.x), "=r"(v.y), "=r"(v.z), "=r"(v.w) : "l"(p), "r"(x), "r"(y), "r"(z), "r"(w) : "memory");
  return v;
}
#define CONSUME(v) do { if ((v) == 0x7fc12345u) sts1(sb + rec::BARS + 96, 0); } while (0)
__device__ __forceinline__ uint32_t tagf(float v, uint32_t tag) { return (__float_as_uint(v) & ~1u) | tag; }
__device__ __forceinline__ uint2 ldg_b64(const void* p) { uint2 v; asm volatile("{.reg .b64 t; ld.relaxed.gpu.global.b64 t,[%2]; mov.b64 {%0,%1},t;}" : "=r"(v.x), "=r"(v.y) : "l"(p) : "memory"); return v; }
__device__ __forceinline__ void stg_b64(void* p, uint32_t x, uint32_t y) { asm volatile("{.reg .b64 t; mov.b64 t,{%1,%2}; st.relaxed.gpu.global.b64 [%0],t;}" ::"l"(p), "r"(x), "r"(y) : "memory"); }
__device__ __forceinline__ uint32_t tagbad(uint32_t x, uint32_t y, uint32_t tag) { uint32_t r; asm("lop3.b32 %0,%1,%2,%3,0x7e;" : "=r"(r) : "r"(x), "r"(y), "r"(tag)); return r; }

__device__ __forceinline__ bool anybad(uint32_t a, uint32_t b, uint32_t c, uint32_t d, uint32_t e, uint32_t f, uint32_t g, uint32_t h, uint32_t tag) {
  uint32_t r;
  asm volatile("{.reg .b32 t,u,v,w; .reg .pred p; lop3.b32 t,%1,%2,%9,0x7e; lop3.b32 u,%3,%4,%9,0x7e; lop3.b32 v,%5,%6,%9,0x7e; lop3.b32 w,%7,%8,%9,0x7e;"
               " lop3.b32 t,t,u,v,0xfe; lop3.b32 t,t,w,1,0xa8; setp.ne.u32 p,t,0; vote.sync.any.pred p,p,0xffffffff; selp.u32 %0,1,0,p;}"
               : "=r"(r) : "r"(a), "r"(b), "r"(c), "r"(d), "r"(e), "r"(f), "r"(g), "r"(h), "r"(tag));
  return r;
}
__device__ __forceinline__ bool anybad(uint32_t a, uint32_t b, uint32_t c, uint32_t d, uint32_t tag) {
  uint32_t r;
  asm volatile("{.reg .b32 t,u; .reg .pred p; lop3.b32 t,%1,%2,%5,0x7e; lop3.b32 u,%3,%4,%5,0x7e;"
               " lop3.b32 t,t,u,1,0xa8; setp.ne.u32 p,t,0; vote.sync.any.pred p,p,0xffffffff; selp.u32 %0,1,0,p;}"
               : "=r"(r) : "r"(a), "r"(b), "r"(c), "r"(d), "r"(tag));
  return r;
}
#define BAD8(r) anybad(r[0].x, r[0].z, r[1].x, r[1].z, r[2].x, r[2].z, r[3].x, r[3].z, tag)
#define BADS(r) anybad(r[0].x, r[0].y, r[1].x, r[1].y, r[2].x, r[2].y, r[3].x, r[3].y, tag)
constexpr float SCS = 0.08838834764831845f * 1.4426950408889634f / 16.f;
__device__ __forceinline__ uint32_t pkh(float lo, float hi, uint32_t tag) {
  uint32_t r;
  asm("{.reg .b32 t; cvt.rn.satfinite.f16x2.f32 t,%1,%2; lop3.b32 %0,t,0xfffffffe,%3,0xea;}" : "=r"(r) : "f"(hi), "f"(lo), "r"(tag));
  return r;
}
__device__ __forceinline__ uint32_t addh(uint32_t a, uint32_t b) { uint32_t r; asm("add.rn.f16x2 %0,%1,%2;" : "=r"(r) : "r"(a), "r"(b)); return r; }
__device__ __forceinline__ float hlo(uint32_t v) { float r; asm("{.reg .b16 a,b; mov.b32 {a,b},%1; cvt.f32.f16 %0,a;}" : "=f"(r) : "r"(v)); return r; }
__device__ __forceinline__ float hhi(uint32_t v) { float r; asm("{.reg .b16 a,b; mov.b32 {a,b},%1; cvt.f32.f16 %0,b;}" : "=f"(r) : "r"(v)); return r; }
__device__ __forceinline__ uint32_t ordh(uint32_t v) {
  uint32_t r;
  asm("{.reg .b32 m; prmt.b32 m,%1,0,0xbb99; lop3.b32 %0,%1,m,0x7fff7fff,0x78;}" : "=r"(r) : "r"(v));
  return r;
}
template <bool MASK>
__device__ __forceinline__ float4 softmax2(const uint2 (&r)[4], uint32_t mx, uint32_t my) {
  uint32_t x = addh(addh(r[0].x, r[1].x), addh(r[2].x, r[3].x)), y = addh(addh(r[0].y, r[1].y), addh(r[2].y, r[3].y)), k;
  if (MASK) x = addh(x, mx);
  y = addh(y, my);
  asm("max.f16x2 %0,%1,%2;" : "=r"(k) : "r"(x), "r"(y));
  k = ordh(k);
  const int k0 = __reduce_max_sync(~0u, (int)(k << 16)), k1 = __reduce_max_sync(~0u, (int)k);
  k = ordh(__byte_perm(k0, k1, 0x7632));
  const float m0 = hlo(k) * -16.f, m1 = hhi(k) * -16.f;
  return make_float4(ex2(fmaf(hlo(x), 16.f, m0)), ex2(fmaf(hhi(x), 16.f, m1)), ex2(fmaf(hlo(y), 16.f, m0)), ex2(fmaf(hhi(y), 16.f, m1)));
}
__device__ __forceinline__ char* mkp(uint32_t lo, uint32_t hi) { uint64_t r; asm("mov.b64 %0,{%1,%2};" : "=l"(r) : "r"(lo), "r"(hi)); return (char*)r; }
#define LO(p) ((uint32_t)(uint64_t)(p))
#define HI(p) ((uint32_t)((uint64_t)(p) >> 32))
__device__ __forceinline__ void cp16(uint32_t dst, const void* src) { asm volatile("cp.async.cg.shared.global [%0],[%1],16;" ::"r"(dst), "l"(src) : "memory"); }
__device__ __forceinline__ uint32_t xor3(uint32_t a, uint32_t b, uint32_t c) { uint32_t r; asm volatile("lop3.b32 %0,%1,%2,%3,0x96;" : "=r"(r) : "r"(a), "r"(b), "r"(c)); return r; }
__device__ __forceinline__ uint32_t mulbf(uint32_t a, uint32_t b) { uint32_t r; asm("mul.rn.bf16x2 %0,%1,%2;" : "=r"(r) : "r"(a), "r"(b)); return r; }
__device__ __forceinline__ uint32_t addbf(uint32_t a, uint32_t b) { uint32_t r; asm("add.rn.bf16x2 %0,%1,%2;" : "=r"(r) : "r"(a), "r"(b)); return r; }
__device__ __forceinline__ void pv_mem(const uint32_t (&p)[4], uint32_t pm, const uint4 (&v)[4], const uint4 (&vn)[2], uint32_t (&O)[4]) {
  float o[4][4] = {{0, 0, 0, 0}, {0, 0, 0, 0}, {0, 0, 0, 0}, {0, 0, 0, 0}};
  mma16(o[0], v[0].x, v[0].y, v[0].z, v[0].w, p[0], p[1]);
  mma16(o[1], v[2].x, v[2].y, v[2].z, v[2].w, p[0], p[1]);
  mma16(o[2], v[1].x, v[1].y, v[1].z, v[1].w, p[2], p[3]);
  mma16(o[3], v[3].x, v[3].y, v[3].z, v[3].w, p[2], p[3]);
  mma16(o[0], vn[0].x, vn[0].y, vn[0].z, vn[0].w, pm, pm);
  mma16(o[1], vn[1].x, vn[1].y, vn[1].z, vn[1].w, pm, pm);
  O[0] = pk(o[0][0] + o[2][0], o[0][1] + o[2][1]); O[1] = pk(o[0][2] + o[2][2], o[0][3] + o[2][3]);
  O[2] = pk(o[1][0] + o[3][0], o[1][1] + o[3][1]); O[3] = pk(o[1][2] + o[3][2], o[1][3] + o[3][3]);
}
__device__ __forceinline__ void pv_tok(const uint32_t (&p)[4], uint32_t pm, const uint4 (&v)[4], const uint32_t (&vm)[4], uint32_t (&O)[4]) {
  float o[2][4] = {{0, 0, 0, 0}, {0, 0, 0, 0}}, sum[4] = {0, 0, 0, 0};
  const uint32_t one = 0x3f803f80u;
  mma16(sum, one, one, one, one, p[0], p[1]);
  mma16(o[0], v[0].x, v[0].y, v[0].z, v[0].w, p[0], p[1]);
  mma16(o[1], v[2].x, v[2].y, v[2].z, v[2].w, p[0], p[1]);
  mma16(sum, one, one, one, one, p[2], p[3]);
  mma16(o[0], v[1].x, v[1].y, v[1].z, v[1].w, p[2], p[3]);
  mma16(o[1], v[3].x, v[3].y, v[3].z, v[3].w, p[2], p[3]);
  mma8(sum, one, one, pm);
  mma8(o[0], vm[0], vm[1], pm);
  mma8(o[1], vm[2], vm[3], pm);
  float i0, i1;
  asm("rcp.approx.ftz.f32 %0,%1;" : "=f"(i0) : "f"(sum[0]));
  asm("rcp.approx.ftz.f32 %0,%1;" : "=f"(i1) : "f"(sum[1]));
  O[0] = pk(o[0][0] * i0, o[0][1] * i1); O[1] = pk(o[0][2] * i0, o[0][3] * i1);
  O[2] = pk(o[1][0] * i0, o[1][1] * i1); O[3] = pk(o[1][2] * i0, o[1][3] * i1);
}
__device__ __forceinline__ uint32_t sum4bf(uint32_t a, uint32_t b, uint32_t c, uint32_t d) { return addbf(addbf(a, b), addbf(c, d)); }
template <int OFF>
__device__ __forceinline__ void sta1(uint32_t a, uint32_t v, uint32_t mb) {
  asm volatile("st.async.shared::cluster.mbarrier::complete_tx::bytes.b32 [%0+%3],%1,[%2];" ::"r"(a), "r"(v), "r"(mb), "n"(OFF) : "memory");
}

__device__ __forceinline__ void rec_helper(char* smem, const bf16* cvec, const bf16* wmod, const char* w1, const bf16* b1) {
  const int tid = threadIdx.x, hb = blockIdx.x - 128;
  float* sc = (float*)smem;
  float* red = sc + 1024;
  for (int i = tid; i < 1024; i += 256) { const float v = __bfloat162float(cvec[i]); sc[i] = rbf(silu(v)); }
  for (int i = tid; i < 2048; i += 256) g_stat[hb * 2048 + i] = make_uint4(~0u, ~0u, ~0u, ~0u);
  for (int i = tid; i < 512; i += 256) g_cnt[hb * 512 + i] = 0;
  if (tid == 0) {
    wait_cnt(&g_hcnt, 128);
    if (HP)
      for (int r = 0; r < 1024; r++) {
        asm volatile("cp.async.bulk.prefetch.L2.global [%0], 2048;" ::"l"(wmod + (size_t)r * 6144 + 2048 + hb * 1024) : "memory");
        if ((r & 7) == 7) __nanosleep(250);
      }
  }
  BAR_SYNC(rec::B_F, 256);
  const int rg = tid >> 7, cg = tid & 127;
  float acc[8] = {0, 0, 0, 0, 0, 0, 0, 0};
  const uint4* p = (const uint4*)(wmod + 2048 + hb * 1024) + cg;
#pragma unroll 1
  for (int r0 = 0; r0 < 1024; r0 += 2 * HU) {
    __nanosleep(HS);
#pragma unroll
  for (int r = r0 + rg; r < r0 + 2 * HU; r += 2) {
    const uint4 v = HP == 2 ? __ldcg(p + (size_t)r * 768) : __ldcs(p + (size_t)r * 768);
    const float f = sc[r];
    acc[0] += f * blo(v.x); acc[1] += f * bhi(v.x); acc[2] += f * blo(v.y); acc[3] += f * bhi(v.y);
    acc[4] += f * blo(v.z); acc[5] += f * bhi(v.z); acc[6] += f * blo(v.w); acc[7] += f * bhi(v.w);
  }
  }
#pragma unroll
  for (int i = 0; i < 8; i++) red[rg * 1024 + cg * 8 + i] = acc[i];
  BAR_SYNC(rec::B_F, 256);
  for (int i = tid; i < 1024; i += 256) g_mod[2048 + hb * 1024 + i] = rbf(red[i] + red[1024 + i]);
  BAR_SYNC(rec::B_F, 256);
  if (tid == 0) {
    red_rel(&g_mcnt);
    for (int r = 0; r < 1024; r++) {
      asm volatile("cp.async.bulk.prefetch.L2.global [%0], 1792;" ::"l"(w1 + (size_t)r * 7168 + hb * 1792) : "memory");
      if ((r & 7) == 7) __nanosleep(250);
    }
    wait_cnt(&g_mcnt, 4);
  }
  BAR_SYNC(rec::B_F, 256);
  float2* m2 = (float2*)smem;
  for (int i = tid; i < 1024; i += 256) m2[i] = make_float2(rbf(1.f + __ldcg(g_mod + 4096 + i)), __ldcg(g_mod + 3072 + i));
  BAR_SYNC(rec::B_F, 256);
  float* rd = (float*)(smem + 8192);
  if (tid < 224) {
    const int r2 = tid >= 112, c2 = tid - r2 * 112;
    float a1[8] = {0, 0, 0, 0, 0, 0, 0, 0}, a2[8] = {0, 0, 0, 0, 0, 0, 0, 0};
    const uint4* q = (const uint4*)(w1 + hb * 1792) + c2;
#pragma unroll 1
    for (int r0 = 0; r0 < 1024; r0 += 32) {
      __nanosleep(HS);
#pragma unroll
      for (int r = r0 + r2; r < r0 + 32; r += 2) {
        const uint4 v = __ldcg(q + (size_t)r * 448);
        const float2 f = m2[r];
        const float w[8] = {blo(v.x), bhi(v.x), blo(v.y), bhi(v.y), blo(v.z), bhi(v.z), blo(v.w), bhi(v.w)};
#pragma unroll
        for (int i = 0; i < 8; i++) { a1[i] += f.x * w[i]; a2[i] += f.y * w[i]; }
      }
    }
#pragma unroll
    for (int i = 0; i < 8; i++) { rd[r2 * 1792 + c2 * 8 + i] = a1[i]; rd[r2 * 1792 + 896 + c2 * 8 + i] = a2[i]; }
  }
  BAR_SYNC(rec::B_F, 256);
  for (int i = tid; i < 448; i += 256) {
    const int n = i * 2, gn = hb * 896 + n;
    const uint32_t bb = *(const uint32_t*)(b1 + gn);
    ((uint2*)g_cc)[(gn >> 4) * 8 + ((gn >> 1) & 3) * 2 + ((gn >> 3) & 1)] =
        make_uint2(pk(rd[n] + rd[1792 + n], rd[n + 1] + rd[1793 + n]), pk(0.5f * (rd[896 + n] + rd[2688 + n] + blo(bb)), 0.5f * (rd[897 + n] + rd[2689 + n] + bhi(bb))));
  }
}

__global__ void __cluster_dims__(2, 1, 1) __launch_bounds__(512, 1)
k_rec(const __grid_constant__ RecMaps mp, const bf16* __restrict__ mem0, const bf16* __restrict__ x, const bf16* __restrict__ cvec,
      const bf16* __restrict__ wmod, const char* __restrict__ w1, const bf16* __restrict__ b1, char* xc, int dF, int dA, int dS, int dM, int dG, int dP, int dX, int dD, int dZ, int dZ2, int dV, int dX2) {
  using namespace rec;
  extern __shared__ __align__(1024) char smem[];
  const uint32_t sb = (uint32_t)__cvta_generic_to_shared(smem);
  if ((sb & 0x3FFFF) != 1024) __trap();
  PH(0);
  if (threadIdx.x == 0) {
    int b = blockIdx.x;
    if (b >= 8 && b < 128) {
      const int t = (b >> 1) - 4, u = t - 32;
      b = 2 * (t < 32 ? 4 + (t & 16) + (t & 7) * 2 + ((t >> 3) & 1) : 36 + (u / 14) * 14 + (u % 7) * 2 + ((u / 7) & 1)) + (b & 1);
    }
    sts1(sb + rec::PACE + 24, b);
    const int c = blockIdx.x >> 1, l = c < 36 ? (c - 4) & 7 : (c - 36) % 7, m = c < 4 ? c : c < 36 ? (c - 4) >> 3 : (c - 36) / 7;
    const int g = c < 4 ? 15 : (l >> 1) * 4 + (l & 1) + (c < 36 ? 0 : 2);
    unsigned sm;
    asm("mov.u32 %0,%%smid;" : "=r"(sm));
    if (c < 64 && !(MC & blockIdx.x)) g_slot[(sm >> MC) & 255] = 1 + FMAP;
  }
#define ROLE_REFRESH { asm volatile("mov.u32 %0,%%tid.x;" : "=r"(tid)); wid = __shfl_sync(~0u, tid >> 5, 0); b = __shfl_sync(~0u, lds1(sb + PACE + 24), 0); }
#define ROLE_VARS int tid; asm volatile("mov.u32 %0,%%tid.x;" : "=r"(tid)); \
    int wid = __shfl_sync(~0u, tid >> 5, 0), b = __shfl_sync(~0u, lds1(sb + PACE + 24), 0);
#define wg (wid >> 2)
#define iw (wid & 3)
#define h (b >> 2)
#define j (b & 3)
#define a (b & 1)
#define bb ((b >> 1) & 1)
  const uint32_t wbar = sb + BARS + 48, obar = wbar + 8;
  if (threadIdx.x == 256) {
    for (int i = 0; i < 18; i++) if (i != 12) mbar_init(sb + BARS + i * 8, i == 3 || i == 8 || i == 9 || i == 10 ? 2 : 1);
    for (int i = 0; i < 3; i++) mbar_init(sb + PACE + i * 8, 1);
    asm volatile("fence.mbarrier_init.release.cluster;" ::: "memory");
    FENCE_ASYNC_SMEM();
    mbar_expect(sb + BARS, 2048);
    mbar_expect(sb + BARS + 16, 4096);
    mbar_expect(sb + BARS + 32, 4096);
    mbar_expect(sb + BARS + 40, 4096);
  }
  __syncthreads();
#define lane ((int)(l16 >> 4))
#define l16 (L16 & 0x1f0)
#define is7 ((L16 & 112) == 112)
#define PIN(x) __shfl_xor_sync(~0u, (uint32_t)(x), 0)
#define REFRESH() L16 = __shfl_xor_sync(~0u, L16, 0)
#define lar ((L16 & 0x180) * 8 + (L16 & 0x70))
#define X_LOAD(n, w, u) \
        asm volatile("{.reg .pred p; elect.sync _|p, 0xffffffff; @p mbarrier.arrive.expect_tx.shared.b64 _,[%2],8192;\n" \
                     "@p cp.async.bulk.shared::cluster.global.mbarrier::complete_tx::bytes [%0],[%1],8192,[%2];}" ::"r"(sb + XB + (w) * 16384 + (u) * 8192), \
                     "l"(g_h + (n) * 4096 + a * 2048 + (w) * 1024 + (u) * 512), "r"(sb + BARS + 64 + (w) * 8) : "memory")
#define lpub ((L16 & 0x30) * 64 + ((L16 >> 3) & 0x38))
#define lrow ((L16 & 0x70) + (((L16 >> 3) ^ L16) & 0x70 & ~((L16 >> 3) & 0x40) ? L16 & 0x180 : 512))

  const int role = __shfl_sync(~0u, threadIdx.x >> 7, 0);
  if (role < 2) {
    asm volatile("setmaxnreg.inc.sync.aligned.u32 %0;" ::"n"(RF_));
    if (blockIdx.x >= 128) { rec_helper(smem, cvec, wmod, w1, b1); return; }
    ROLE_VARS
    uint32_t L16 = __shfl_sync(~0u, sb + (tid & 31) * 16, tid & 31);
    {
      uint4 wm[8], xr[8];
      const uint4* pw = (const uint4*)(wmod + (size_t)((b >> 5) * 256 + (tid >> 3)) * 6144 + (b & 31) * 64) + (tid & 7);
      const float cs = __bfloat162float(cvec[(b >> 5) * 256 + tid]);
#pragma unroll
      for (int i = 0; i < 8; i++) wm[i] = __ldcs(pw + (size_t)i * 32 * 768);
#pragma unroll
      for (int i = 0; i < 8; i++) xr[i] = __ldg((const uint4*)(x + (size_t)(b * 16 + (tid >> 5) * 2) * 1024) + i * 32 + (tid & 31));
      float* sc = (float*)(smem + PRE);
      sc[tid] = rbf(silu(cs));
      if (tid < 80) g_ar[b * 80 + tid] = make_uint4(0, 0, 0, 0);
      if (tid == 80 && b == 0) g_fin = 0;
      BAR_SYNC(B_F, 256);
      float acc[8] = {0, 0, 0, 0, 0, 0, 0, 0};
#pragma unroll
      for (int i = 0; i < 8; i++) {
        const float f = sc[i * 32 + (tid >> 3)];
        acc[0] += f * blo(wm[i].x); acc[1] += f * bhi(wm[i].x); acc[2] += f * blo(wm[i].y); acc[3] += f * bhi(wm[i].y);
        acc[4] += f * blo(wm[i].z); acc[5] += f * bhi(wm[i].z); acc[6] += f * blo(wm[i].w); acc[7] += f * bhi(wm[i].w);
      }
#pragma unroll
      for (int i = 0; i < 8; i++) { acc[i] += __shfl_xor_sync(~0u, acc[i], 8); acc[i] += __shfl_xor_sync(~0u, acc[i], 16); }
      float* red = sc + 1024;
      if ((tid & 31) < 8) {
#pragma unroll
        for (int i = 0; i < 8; i++) red[(tid >> 5) * 64 + (tid & 7) * 8 + i] = acc[i];
      }
      BAR_SYNC(B_F, 256);
      if (tid < 64) {
        float t = 0;
#pragma unroll
        for (int i = 0; i < 8; i++) t += red[i * 64 + tid];
        asm volatile("st.relaxed.gpu.global.u32 [%0],%1;" ::"l"((unsigned*)g_modp + (b >> 5) * 2048 + (b & 31) * 64 + tid), "r"(U_(t) | 1u) : "memory");
      }
      float v[2][32], rstd[2];
#pragma unroll
      for (int r = 0; r < 2; r++) {
        float t = 0, q = 0;
#pragma unroll
        for (int i = 0; i < 4; i++) {
          const uint4 u = xr[r * 4 + i];
          float* w = v[r] + i * 8;
          w[0] = blo(u.x); w[1] = bhi(u.x); w[2] = blo(u.y); w[3] = bhi(u.y); w[4] = blo(u.z); w[5] = bhi(u.z); w[6] = blo(u.w); w[7] = bhi(u.w);
        }
#pragma unroll
        for (int i = 0; i < 32; i++) t += v[r][i];
#pragma unroll
        for (int o = 16; o; o >>= 1) t += __shfl_xor_sync(~0u, t, o);
        t *= 1.f / 1024;
#pragma unroll
        for (int i = 0; i < 32; i++) { v[r][i] -= t; q += v[r][i] * v[r][i]; }
#pragma unroll
        for (int o = 16; o; o >>= 1) q += __shfl_xor_sync(~0u, q, o);
        rstd[r] = rsqrtf(q * (1.f / 1024) + 1e-5f);
      }
      float4* md = (float4*)(sc + 1536);
#pragma unroll
      for (int i = 0; i < 2; i++) {
        uint4 p[4];
        int it = 0;
        while (true) {
#pragma unroll
          for (int u = 0; u < 4; u++) p[u] = ldg_rlx4(g_modp + u * 512 + i * 256 + tid);
          uint32_t ok = 1;
#pragma unroll
          for (int u = 0; u < 4; u++) ok &= p[u].x & p[u].y & p[u].z & p[u].w;
          if (__all_sync(~0u, ok)) break;
          if (++it > SPIN_LIMIT) __trap();
          __nanosleep(100);
        }
        md[i * 256 + tid] = make_float4(i + rbf((F_(p[0].x) + F_(p[1].x)) + (F_(p[2].x) + F_(p[3].x))), i + rbf((F_(p[0].y) + F_(p[1].y)) + (F_(p[2].y) + F_(p[3].y))),
                                        i + rbf((F_(p[0].z) + F_(p[1].z)) + (F_(p[2].z) + F_(p[3].z))), i + rbf((F_(p[0].w) + F_(p[1].w)) + (F_(p[2].w) + F_(p[3].w))));
      }
      BAR_SYNC(B_F, 256);
#pragma unroll
      for (int i = 0; i < 4; i++) {
        const int ch = i * 32 + (tid & 31);
        const float4 s0 = md[ch * 2], s1 = md[ch * 2 + 1], c0 = md[256 + ch * 2], c1 = md[256 + ch * 2 + 1];
#pragma unroll
        for (int r = 0; r < 2; r++) {
          const int row = b * 16 + (tid >> 5) * 2 + r;
          const float* w = v[r] + i * 8;
          g_h[((row >> 5) * 16 + (ch >> 3)) * 256 + (row & 31) * 8 + ((ch & 7) ^ (row & 7))] =
              make_uint4(pk(w[0] * rstd[r] * c0.x + s0.x, w[1] * rstd[r] * c0.y + s0.y), pk(w[2] * rstd[r] * c0.z + s0.z, w[3] * rstd[r] * c0.w + s0.w),
                         pk(w[4] * rstd[r] * c1.x + s1.x, w[5] * rstd[r] * c1.y + s1.y), pk(w[6] * rstd[r] * c1.z + s1.z, w[7] * rstd[r] * c1.w + s1.w));
        }
      }
      FENCE_ASYNC();
      BAR_SYNC(B_F, 256);
      if (tid == 0) red_rel(&g_hcnt);
      PH(1);
    }
    uint32_t m0[2][4];
#pragma unroll
    for (int i = 0; i < 2; i++)
#pragma unroll
      for (int r = 0; r < 4; r++)
        m0[i][r] = (uint32_t)__bfloat16_as_ushort(mem0[(2 * r) * 1024 + a * 512 + tid * 2 + i]) | ((uint32_t)__bfloat16_as_ushort(mem0[(2 * r + 1) * 1024 + a * 512 + tid * 2 + i]) << 16);
    if (iw == 0) { wait_cnt(&g_hcnt, 128); FENCE_ASYNC(); }
    __syncwarp();
    PH(2);
    ROLE_REFRESH
    uint32_t wQ[16][4], wK[16][4], wV[NVR][4];
    uint32_t frag = sb + ((lane & 7) + (lane >> 4) * 8) * 128 + (((iw * 2 + ((lane >> 3) & 1)) ^ (lane & 7)) << 4);
    mbar_wait(wbar, 0);
#pragma unroll
    for (int i = 0; i < 16; i++) { ldsm4t(wQ[i], frag + WO + wg * 32768 + i * 2048); ldsm4t(wK[i], frag + XB + wg * 32768 + i * 2048); }
#pragma unroll
    for (int i = 0; i < NVR; i++) ldsm4t(wV[i], frag + MEM + (wg * NVR + i) * 2048);
    FENCE_ASYNC_SMEM();
    PH(3);
    CLUSTER_SYNC();
#define xbar (sb + BARS + 64 + wg * 8)
    auto x_load = [&](int n) { if (iw == 0) { X_LOAD(n, wg, 0); X_LOAD(n, wg, 1); } };
    x_load(0);
    if (tid == 0) {
      mbar_expect(obar, 65536);
      for (int i = 0; i < 4; i++) tma2d(sb + WO + i * 16384, &mp.wo, j * 256 + i * 64, h * 128, obar);
    }
#pragma unroll
    for (int i = 0; i < 2; i++) {
      const int k = tid * 2 + i, m = (k >> 3) & 3, r = k & 7;
      sts4(sb + MEM + (k >> 5) * 640 + (r == m ? 512 : m * 128) + r * 16, m0[i][0], m0[i][1], m0[i][2], m0[i][3]);
    }
    if (lane < 8) {
      sts4(sb + ARO + wid * 640 + (lane < 4 ? lane * 144 : 512 + l16), 0x3f803f80, 0x3f803f80, 0x3f803f80, 0x3f803f80);
#pragma unroll
      for (int i = 0; i < 2; i++) sts4(sb + MEM + (wid * 2 + i) * 640 + (lane < 4 ? lane * 144 : 512 + l16), 0x42004200, 0x42004200, 0x42004200, 0x42004200);
    }
#define owner ((iw >> 1) == a)
#define vfin ((wid >> 1) == a)
#define oi (wid & 1)
    frag += wg * NVS * 2048;
    {
      const uint32_t rsb = mapa(sb, iw >> 1);
      const uint32_t pp = rsb + PK + (owner ? 0 : 12288) + (oi * 2048 + wg * 1024) + l16;
      const uint32_t mb = sb + MEM + wg * 5120;
      sts4(L16 + TF + wid * 512, mb + lrow, owner ? L16 + (lane >> 4) * (RK - RQ - 256) + RQ + oi * 1024 + wg * 256 : rsb + RQ + oi * 1024 + 512 + wg * 256 + (l16 >> 2),
           L16 + OB, frag);
      sts4(L16 + TF + 4096 + wid * 512, sb + WO + (wid >> 1) * 16384 + ((lane & 7) + (lane >> 4) * 8) * 128 + ((((wid & 1) * 4 + ((lane >> 3) & 1)) ^ (lane & 7)) << 4),
           sb + ARO + wid * 640 + lrow, pp, LO(xc) + h * 262144 + (bb * 2 + (iw >> 1)) * XC + X_VM(0) + oi * 2048 + a * 256 + (l16 >> 1));
    }
    uint32_t tp = L16 + TF + wid * 512;
    auto park_ptr = [&]() { return lds1(tp + 4096 + 8); };
    auto park = [&](const float* f, int m, int n, uint32_t d) {
      uint32_t w[8];
#pragma unroll
      for (int i = 0; i < 8; i++) w[i] = pk(f[2 * i], f[2 * i + 1]);
      if (owner) {
        sts4(d + m * 4096, w[0], w[1], w[2], w[3]); sts4(d + m * 4096 + 512, w[4], w[5], w[6], w[7]);
      } else {
        const uint32_t pb = mapa(sb, a ^ 1) + BARS + (m ? 24 + m * 8 : 16);
        sta4(d + m * 4096, w, pb); sta4(d + m * 4096 + 512, w + 4, pb);
      }
    };
    auto xdesc = [&](int n) { return mkdesc(__shfl_sync(~0u, 1024 + XB + wg * 16384, 0), 16, 1024); };
    auto rs_issue = [&](float* acc, const uint32_t (&w)[16][4], int n, bool fence) {
      const uint64_t x = xdesc(n);
      if (fence) WG_FENCE();
      wgmma_rs_n32_z(acc, w[0], x);
#pragma unroll
      for (int i = 1; i < 16; i++) wgmma_rs_n32(acc, w[i], x + (i >> 2) * 256 + (i & 3) * 2, 1);
      WG_COMMIT();
    };
    auto v_issue = [&](float* acc, int n, bool fence) {
      const uint64_t dv = mkdesc(__shfl_sync(~0u, 1024 + WVS + wg * NVS * 2048, 0), 16, 1024), x = xdesc(n);
      if (fence) WG_FENCE();
      wgmma_rs_n32_z(acc, wV[0], x);
#pragma unroll
      for (int i = 1; i < (KVO == 2 ? NVR : 0); i++) wgmma_rs_n32(acc, wV[i], x + (i >> 2) * 256 + (i & 3) * 2, 1);
#pragma unroll
      for (int i = NVR; i < 16; i++) wgmma_ssT_n32(acc, dv + (i - NVR) * 128, x + (i >> 2) * 256 + (i & 3) * 2, 1);
#pragma unroll
      for (int i = 1; i < (KVO == 2 ? 0 : NVR); i++) wgmma_rs_n32(acc, wV[i], x + (i >> 2) * 256 + (i & 3) * 2, 1);
      WG_COMMIT();
    };
    uint32_t mA;
    auto vk_pass = [&](int n, uint32_t d) {
      float acc[16], acc2[16];
      v_issue(acc, n, true);
      rs_issue(acc2, wK, n, false);
      if (n) mbar_wait(sb + BARS + 80, (n - 1) & 1);
      WG_WAIT(1);
      park(acc, 2 - !!KVO, n, d);
      mA = lds1(tp);
      if (n > 1) BAR_ARRIVE(B_K, 320);
      WG_WAIT(0);
      park(acc2, 1 + !!KVO, n, d);
    };
    {
      float acc[16];
      mbar_wait(xbar, 0);
      rs_issue(acc, wQ, 0, true); WG_WAIT(0); park(acc, 0, 0, park_ptr());
      vk_pass(0, park_ptr());
      BAR_SYNC(B_C, 320);
      x_load(1);
      BAR_SYNC(B_C, 320);
      asm volatile("" : "+r"(wid));
      mbar_wait(xbar, 1);
      rs_issue(acc, wQ, 1, true); mbar_wait(sb + BARS + 24, 0); WG_WAIT(0); park(acc, 0, 1, park_ptr());
      vk_pass(1, park_ptr());
      BAR_ARRIVE(B_P, 384); if (!HX) BAR_ARRIVE(B_X, 320); BAR_ARRIVE(B_Q, 288);
    }
    mbar_wait(obar, 0);
    PH(4);
    ROLE_REFRESH
    for (int s = 0; s < 64; s++) {
      asm volatile("" : "+r"(tp), "+r"(wid));
      asm volatile("mov.u32 %0,%%cluster_ctarank;" : "=r"(b));
      uint32_t vS[NVS][4], bf[8][4], rm;
      const uint32_t mm = mapa(sb, a ^ 1) + BARS;
      if (s > 0) BAR_SYNC(B_R, 320);
#define VMMA(c, w, i) mma16(c, (w)[0], (w)[1], (w)[2], (w)[3], bf[(i) >> 1][((i) & 1) * 2], bf[(i) >> 1][((i) & 1) * 2 + 1])
      {
        float cQ[4] = {0, 0, 0, 0}, cK[4] = {0, 0, 0, 0};
#pragma unroll
        for (int t = 7; t >= 3; t--) ldsm4t(bf[t], mA + t * 640);
        SCHED_FENCE(47);
#pragma unroll
        for (int i = 15; i >= 0; i--) {
          VMMA(cQ, wQ[i], i); VMMA(cK, wK[i], i);
          if (i == XI && HX) BAR_ARRIVE(B_X, 320);
          if (i == 12) {
            SCHED_FENCE(51);
#pragma unroll
            for (int t = 2; t >= 0; t--) ldsm4t(bf[t], mA + t * 640);
            rm = lds1(tp + 4); frag = lds1(tp + 12);
          }
          if (i == 4 && NVP) {
            SCHED_FENCE(48);
#pragma unroll
            for (int u = 0; u < NVP; u++) ldsm4t(vS[NVS - 1 - u], frag + WVS + (NVS - 1 - u) * 2048);
          }
        }
        const uint32_t w0 = pk(cQ[0] * SCS, cQ[1] * SCS), w1 = pk(cQ[2] * SCS, cQ[3] * SCS), w2 = pk(cK[0], cK[1]), w3 = pk(cK[2], cK[3]);
        if (owner) {
          stsm4(rm, w0, w1, w2, w3);
          BAR_ARRIVE(B_E, 256);
        } else {
          sta1<0>(rm, w0, mm); sta1<128>(rm, w1, mm);
          sta1<RK - RQ>(rm, w2, mm); sta1<RK - RQ + 128>(rm, w3, mm);
        }
        if (wid == 2) TS(0);
      }
      uint4 t1;
      uint32_t oA;
      {
        float cV[4] = {0, 0, 0, 0}, cW[4] = {0, 0, 0, 0};
        static_assert(NVP == 2 && NVR == 5, "schedule");
#define VLD(k) ldsm4t(vS[(k) - NVR], frag + WVS + ((k) - NVR) * 2048)
#define VS_(c, k) VMMA(c, vS[(k) - NVR], k)
        VLD(13); VLD(12);
        VS_(cW, 15); VS_(cV, 14); VLD(11); VMMA(cW, wV[0], 0); VLD(10); VMMA(cV, wV[1], 1); VLD(9);
        VMMA(cW, wV[2], 2); VLD(8); VMMA(cV, wV[3], 3); VLD(7); VMMA(cW, wV[4], 4); VS_(cV, 13); VLD(6); VS_(cW, 12); VLD(5);
        VS_(cV, 11); VS_(cW, 10); VS_(cV, 9); VS_(cW, 8); VS_(cV, 7); VS_(cW, 6); VS_(cV, 5);
#pragma unroll
        for (int e = 0; e < 4; e++) cV[e] += cW[e];
        const uint32_t ex = tp + (RX - TF) - wg * 2048;
        t1 = lds4(tp + 4096);
        oA = lds1(tp + 8 + (s & dZ));
        if (wg) {
          sts4(ex, U_(cV[0]), U_(cV[1]), U_(cV[2]), U_(cV[3]));
          BAR_ARRIVE(B_T2, 256);
        } else {
          BAR_SYNC(B_T2, 256);
          const float4 u = lds4f(ex);
          stg_b64(mkp(t1.w ^ ((s & 1) * X_RING), HI(xc)), (pk(cV[0] + u.x, cV[1] + u.y) & ~1u) | (((s >> 1) + 1) & 1), pk(cV[2] + u.z, cV[3] + u.w));
        }
      }
      if (s == 63) break;
      {
        const uint32_t woA = t1.x, woB = woA ^ 32;
        uint32_t wo[16][4];
#pragma unroll
        for (int i = 0; i < NW1; i++) ldsm4t(wo[i], ((i & 1) ? woB : woA) + (i >= WCH ? wo[(i - WCH + NWP) % NWP][0] & dZ : 0) + (i >> 1) * 2048);
        BAR_SYNC(B_S, 416);
        if (s < 62) {
          float acc[16];
          rs_issue(acc, wQ, s + 2, true);
          mbar_wait(sb + BARS + 24, (s + 1) & 1);
          WG_WAIT(0);
          BAR_SYNC(B_V, 512);
          park(acc, 0, s + 2, t1.z);
        } else {
          BAR_SYNC(B_V, 512);
        }
#pragma unroll
        for (int i = NW1; i < NWP; i++) ldsm4t(wo[i], ((i & 1) ? woB : woA) + (i >> 1) * 2048);
        float inv0, inv1;
        {
          uint32_t p[4], pm;
          const uint32_t pa = oA + (SC - OB), one = 0x3f803f80u;
          float sum[4] = {0, 0, 0, 0}, su2[4] = {0, 0, 0, 0};
          ldsm4t(p, pa);
          asm volatile("ldmatrix.sync.aligned.m8n8.x1.trans.shared.b16 {%0},[%1];" : "=r"(pm) : "r"(pa + 512) : "memory");
          mma16(sum, one, one, one, one, p[0], p[1]);
          mma16(su2, one, one, one, one, p[2], p[3]);
          mma8(sum, one, one, pm);
          inv0 = sum[0] + su2[0]; inv1 = sum[1] + su2[1];
          SCHED_FENCE(57);
        }
        BAR_SYNC(B_O, 416);
        float c[2][4] = {{0, 0, 0, 0}, {0, 0, 0, 0}};
        uint32_t o[4][4];
#pragma unroll
        for (int i = 0; i < NOP_; i++) ldsm4t(o[i], oA + i * 512);
        SCHED_FENCE(46);
        asm("rcp.approx.ftz.f32 %0,%0;" : "+f"(inv0));
        asm("rcp.approx.ftz.f32 %0,%0;" : "+f"(inv1));
#pragma unroll
        for (int i = 0; i < 16; i++) {
          mma16(c[i & 1], wo[i][0], wo[i][1], wo[i][2], wo[i][3], o[i >> 2][i & 2], o[i >> 2][(i & 2) + 1]);
          if (i == 1 && NOP_ < 3) ldsm4t(o[2], oA + 1024);
          if (i == 3 && NOP_ < 4) ldsm4t(o[3], oA + 1536);
          if (i + NWP < 16) ldsm4t(wo[(i + NWP) & 15], (((i + NWP) & 1) ? woB : woA) + ((i + NWP) >> 1) * 2048);
        }
        stsm4(t1.y, pk(c[0][0] * inv0, c[0][1] * inv1), pk(c[0][2] * inv0, c[0][3] * inv1), pk(c[1][0] * inv0, c[1][1] * inv1), pk(c[1][2] * inv0, c[1][3] * inv1));
      }
      const uint32_t d = park_ptr();
      BAR_SYNC(B_W, 384);
      if (s < 62) {
        vk_pass(s + 2, d);
        BAR_ARRIVE(B_P, 384); if (!HX) BAR_ARRIVE(B_X, 320);
        TS(10);
      } else {
        mA = lds1(tp);
      }
    }
  } else if (role == 3) {
    asm volatile("setmaxnreg.dec.sync.aligned.u32 24;");
    if (blockIdx.x >= 128) return;
    ROLE_VARS
    const uint32_t L16 = sb + (tid & 31) * 16;
    CLUSTER_SYNC();
    sts1(sb + PACE + 36, LO(xc) + h * 262144 + X_VM(0));
    auto vm_stage = [&](int s) {
      const uint32_t tag = ((s >> 1) + 1) & 1;
      const char* xm = mkp(lds1(sb + PACE + 36) + (s & 1) * X_RING + iw * XC + (l16 >> 1), HI(xc));
      uint2 m[4];
      CONSUME(LO(xm));
      BAR_SYNC(B_S2, 256);
      if (dZ2 > 1) { const uint32_t c = clk(); while (clk() - c < (uint32_t)dZ2) {} }
      int it = 0;
      while (true) {
#pragma unroll
        for (int i = 0; i < 4; i++) m[i] = ldg_b64(xm + (i >> 1) * 2048 + (i & 1) * 256);
        sts4(L16 + VN + iw * 512, m[0].x, m[0].y, m[1].x, m[1].y);
        sts4(L16 + VN + iw * 512 + 2048, m[2].x, m[2].y, m[3].x, m[3].y);
        if (!anybad(m[0].x, m[1].x, m[2].x, m[3].x, tag)) break;
        RP(2);
        if (++it > SPIN_LIMIT) __trap();
      }
      if (s < 63) BAR_ARRIVE(B_V, 512); else BAR_ARRIVE(B_V, 256);
    };
    if (iw == 0) {
#pragma unroll 1
      for (int s = 0; s < 63; s++) {
        if (s) BAR_SYNC(B_R, 320); else BAR_SYNC(B_Q, 288);
        if (s < 62) { X_LOAD(s + 2, 0, 0); X_LOAD(s + 2, 1, 0); X_LOAD(s + 2, 0, 1); X_LOAD(s + 2, 1, 1); }
        if (s >= 7) {
          const uint32_t zo = b * 160 + l16;
          if (l16 < 160) CONSUME(exch_b128((char*)g_ar + (zo >> 7) * 1024 + (zo & 127) + ((s + 1) & 7) * 128, 0, 0, 0, 0).x);
          __syncwarp();
        }
        if (s < 62) { mbar_wait(sb + BARS + 64, s & 1); mbar_wait(sb + BARS + 72, s & 1); }
        BAR_ARRIVE(B_S, 416);
        vm_stage(s);
        BAR_ARRIVE(B_O, 416);
        BAR_SYNC(B_W, 384);
        FENCE_ASYNC_SMEM();
        asm volatile("{.reg .pred p; elect.sync _|p, 0xffffffff; @p cp.reduce.async.bulk.tensor.2d.global.shared::cta.add.bulk_group [%0,{%1,%2}],[%3];}"
                     ::"l"(&mp.ari), "r"((s & 7) * 64), "r"(j * 40), "r"(sb + ARO) : "memory");
        BULK_COMMIT();
        asm volatile("st.relaxed.gpu.global.u32 [%0],%1;" ::"l"(g_tm + (s & 1) * 128 + b), "r"(gtime()) : "memory");
        TS(3);
        BULK_WAIT_READ(0);
      }
      BAR_ARRIVE(B_R, 320);
      vm_stage(63);
    } else if (iw == 1) {
      const uint32_t pc = sb + MEM + (lane >> 2) * 640 + (lane & 3) * 144 + (lane & 12), pd = sb + MEM + (lane & 15) * 640 + 576 + (lane & 3) * 16 + (lane & 12);
      uint32_t T = 0, par = 0;
      int est = dA;
#pragma unroll 1
      for (int s = 0; s < 63; s++) {
        if (s) {
          const uint4 tm = ldg_rlx4((const char*)g_tm + ((s + 1) & 1) * 512 + l16);
          const int t0 = tm.x - T, t1 = tm.y - T, t2 = tm.z - T, t3 = tm.w - T;
          const int e = max(dF + (__reduce_add_sync(~0u, (t0 + t1) + (t2 + t3)) >> 7), dV + __reduce_max_sync(~0u, max(max(t0, t1), max(t2, t3))));
          if (s > 1) est += max(min(e >> 2, dP), -dP);
          T += (s == 1 || e > dM ? e : 0) + est;
        }
        vm_stage(s);
        BAR_SYNC(B_W, 384);
        SCHED_FENCE(70);
        const uint32_t tW = gtime();
        if (s == 0) T = tW + 800;
        const uint32_t te = tW + min(max((int)(T - tW), dD), 2000);
        while ((int)(gtime() - te) < 0) {}
        TS(7);
        int it = 0;
        while (true) {
          ar_fetch(sb + MEM, &mp.ari, s & 7, a, sb + BARS + 112);
          mbar_wait(sb + BARS + 112, par);
          par ^= 1;
          const uint32_t n0 = lds1(pc), n1 = lds1(pc + 5120), n2 = lds1(pd);
          if (!__any_sync(~0u, (tagbad(n0, n1, 0x42004200) | (n2 ^ 0x42004200)) != 0)) break;
          RP(0);
          if (++it > SPIN_LIMIT) __trap();
        }
        BAR_ARRIVE(B_R, 320);
        TS(11);
      }
      vm_stage(63);
    } else {
#define V_LOAD(n) do { if (lane == 0) mbar_expect(sb + BARS + 8, 8192); __syncwarp(); \
        if (lane < 16) bulk_ld(sb + ((lane & 2) ? VX1 : VX0) + (lane & 1) * 2048 + (lane >> 2) * 512, \
                               xc + h * 262144 + ((n) & 1) * X_RING + (lane >> 2) * XC + X_VX(lane & 3), 512, sb + BARS + 8); __syncwarp(); } while (0)
      uint32_t src = L16 + PK + (iw & 1) * 2048;
#define qd (L16 + (lane >> 4) * 256 + QT + (iw & 1) * 1024)
#define vd (LO(xc) + h * 262144 + j * XC + (iw & 1) * 2048 + l16)
#define FINISH [&](int n, int m) { \
_Pragma("unroll") \
        for (int i = 1; i >= 0; i--) { \
          const uint32_t p = src + m * 4096 + i * 512; \
          uint4 u = lds4(p); \
          const uint4 w = lds4(p + 1024), y = lds4(p + 12288), z = lds4(p + 13312); \
          u = make_uint4(sum4bf(u.x, w.x, y.x, z.x), sum4bf(u.y, w.y, y.y, z.y), sum4bf(u.z, w.z, y.z, z.z), sum4bf(u.w, w.w, y.w, z.w)); \
          if (m == 2) stg_b128(mkp(vd ^ ((n & 1) * X_RING), HI(xc)) + i * 512, (u.x & ~1u) | (((n >> 1) + 1) & 1), u.y, u.z, u.w); \
          else stsm4(qd + (n & 1) * 4096 + m * 2048 + i * 256, u.x, u.z, u.y, u.w); \
          SCHED_FENCE(71 + m * 2 + i); \
        } \
      }
#pragma unroll 1
      for (int n = 0; n < 64; n++) {
        src = PIN(src);
        b = __shfl_sync(~0u, lds1(sb + PACE + 24), 0);
        const uint32_t L16 = src - PK - (iw & 1) * 2048;
        auto finish = FINISH;
        if (n < 2) { if (n) BAR_SYNC(B_X, 320); else BAR_SYNC(B_C, 320); }
        mbar_wait(sb + BARS + 16, n & 1);
        finish(n, 0);
        __syncwarp();
        if (lane == 0) mbar_arrive_cl(mapa(sb, a ^ 1) + BARS + 24);
        if (n > 1) BAR_SYNC(B_K, 320);
        mbar_wait(sb + BARS + (KVO ? 32 : 40), n & 1);
        finish(n, 2 - !!KVO);
        if (n > 1) BAR_SYNC(B_X, 320);
        mbar_wait(sb + BARS + (KVO ? 40 : 32), n & 1);
        finish(n, 1 + !!KVO);
        BAR_SYNC(B_T, 64);
        if (lane == 0) {
          if (iw == 2 && n < 63) { mbar_expect(sb + BARS + 16, 4096); mbar_expect(sb + BARS + 32, 4096); mbar_expect(sb + BARS + 40, 4096); }
          mbar_arrive_cl(mapa(sb, a ^ 1) + BARS + 80);
        }
        __syncwarp();
        if (n) {
          vm_stage(n - 1);
          BAR_SYNC(B_W, 384);
        } else {
          BAR_SYNC(B_C, 320);
        }
        if (iw == 2) V_LOAD(n);
      }
      if (HX) BAR_ARRIVE(B_X, 320);
      vm_stage(63);
#undef qd
#undef vd
    }
  } else {
    asm volatile("setmaxnreg.dec.sync.aligned.u32 %0;" ::"n"(RA_));
    if (blockIdx.x >= 128) return;
    ROLE_VARS
    uint32_t L16 = __shfl_sync(~0u, sb + (tid & 31) * 16, tid & 31);
    if (tid == 256) {
      const int col = h * 128 + bb * 64;
      for (int c = 0; c < 12 + WIN; c++) {
        const uint32_t mb = sb + PACE + (c % WIN) * 8;
        if (c >= WIN) mbar_wait(mb, (c / WIN - 1) & 1);
        if (c >= 12) { tma2d_pf(&mp.wo, j * 256 + (c - 12) * 64, h * 128); continue; }
        mbar_expect(mb, 16384);
        if (c < 8) tma2d(sb + (c & 1) * XB + (c >> 1) * 16384, (c & 1) ? &mp.wk : &mp.wq, col, a * 512 + (c >> 1) * 128, mb);
        else
          for (int i = (c & 1) * 8; i < (c & 1) * 8 + 8; i++) {
            const int w = (c - 8) >> 1;
            tma2d(i < NVR ? sb + MEM + (w * NVR + i) * 2048 : sb + WVS + (w * NVS + i - NVR) * 2048, &mp.wv, col, a * 512 + w * 256 + i * 16, mb);
          }
      }
      asm volatile("mbarrier.arrive.shared.b64 _,[%0];" ::"r"(wbar) : "memory");
      for (int c = WIN; c < 4; c++) tma2d_pf(&mp.wo, j * 256 + c * 64, h * 128);
      for (int i = 0; i < 3; i++) asm volatile("mbarrier.inval.shared.b64 [%0];" ::"r"(sb + PACE + i * 8) : "memory");
    }
    __syncwarp();
    CLUSTER_SYNC();
#define pr (L16 + SC)
    {
      const int lim = j * 8 + iw * 2 - (lane & 7) - (lane & 8) * 2;
      const bool mk = L16 & 256;
      const int rw = lane >> 2;
      sts4(L16 + TA + iw * 512,
           iw != 2 ? L16 + KT + (iw & 1) * 256 + (lane >> 4) * 256 : sb + RK + (L16 & 0x80) * 2 + ((L16 >> 1) & 0x80) + (L16 & 0x70),
           L16 + QT + (lane >> 3) * 384, sb + SC + min(lane >> 3, 2) * 256 + (L16 & 0x70) + iw * 4, L16 + (lane >> 4) * 256 + QT + (iw >> 1) * 1024 + (iw & 1) * 256);
      sts4(L16 + TA + 2048 + iw * 512, mk ? 0u : (lim < 0 ? 0xfc00u : 0u) | (lim < -1 ? 0xfc000000u : 0u),
           mk ? 0xfc00fc00u : (lim < 8 ? 0xfc00u : 0u) | (lim < 7 ? 0xfc000000u : 0u),
           ((h * 2 + (iw >> 1)) * 1024 + (j * 8 + rw) * 8 + (((iw & 1) * 4 + (lane & 3)) ^ rw)) * 16, sb + OT + iw * 512 + (L16 & 0x70) * 4 + ((L16 >> 3) & 0x30));
    }
    {
      const uint32_t xh = LO(xc) + h * 262144, xs = xh + X_SC + iw * 1024 + min(lane, 16 + (lane & 7)) * 8;
      sts4(L16 + TA + 4096 + iw * 512, xh + X_SC + j * 256 + iw * 64 + lpub, xs, dS, iw != 2 ? 0 : U_(SCS));
      sts1(L16 + TA + 12 + iw * 512, xs + X_TOK + j * 4096);
    }
    uint32_t tA = L16 + TA + iw * 512;
#define tw (tA - L16 != TA + 1024)
#define XP_(lo) mkp(lo, HI(xc))
    auto publish = [&](char* d, const uint2& w) { stg_b64(d, w.x, w.y); };
    BAR_SYNC(B_P, 384);
    for (int s = 0; s < 64; s++) {
      asm volatile("" : "+r"(L16), "+r"(tA));
      const uint32_t tag = ((s >> 1) + 1) & 1, ring = (s & 1) * X_RING;
      const uint4 t0 = lds4(tA);
      const uint4 tx = lds4(tA + 4096);
      const uint32_t xo = tx.x ^ ring, xs = tx.y ^ ring;
      const float gm = F_(tx.w);
      const uint32_t qA = t0.y + (ring >> 5);
      uint32_t c0;
      uint2 ts[4];
      uint4 v[4];
      uint32_t af[2][4], qt[4][4];
      {
        const uint32_t aA = t0.x + (tw ? ring >> 5 : 0);
        uint32_t ql[2][4], qr[2][4];
        uint2 pw_;
        float c[4] = {0, 0, 0, 0}, d[4] = {0, 0, 0, 0};
        if (s == PDS) asm volatile("griddepcontrol.launch_dependents;");
#pragma unroll
        for (int i = 0; i < 4; i++) ldsm4t(qt[i], qA + i * 128);
        mbar_wait(sb + BARS + 8, s & 1);
        TS(4);
        BAR_SYNC(B_E, 256);
#define PACK(c) make_uint2(pkh(fmaf(c[2], gm, c[0] * SCS), fmaf(c[3], gm, c[1] * SCS), tag), pkh(c[2] * SCS, c[3] * SCS, tag))
#define SMMA(x, t, q, i) mma16(x, af[t][0], af[t][1], af[t][2], af[t][3], q[t][i], q[t][i + 1])
        ldsm4t(ql[0], L16 + RQ); ldsm4t(ql[1], L16 + RQ + 1024); ldsm4t(af[0], aA); ldsm4t(af[1], aA + 1024);
        CONSUME(xo);
#define QSUM(t, i) addbf(addbf(ql[t][i], ql[t][i + 2]), addbf(qr[t][i], qr[t][i + 2]))
#define STAIL mma16(c, af[0][0], af[0][1], af[0][2], af[0][3], QSUM(0, 0), QSUM(0, 1)); mma16(d, af[1][0], af[1][1], af[1][2], af[1][3], QSUM(1, 0), QSUM(1, 1));
        if (tw) {
          mbar_wait(sb + BARS, s & 1);
          TS(8);
          ldsm4t(qr[0], L16 + RQ + 512); ldsm4t(qr[1], L16 + RQ + 1536);
          STAIL
          pw_ = make_uint2(pkh(c[0] + d[0], c[1] + d[1], tag), pkh(c[2] + d[2], c[3] + d[3], tag));
        } else {
          uint32_t ar[2][4];
          mbar_wait(sb + BARS, s & 1);
          ldsm4t(qr[0], L16 + RQ + 512); ldsm4t(ar[0], aA + 512); ldsm4t(qr[1], L16 + RQ + 1536); ldsm4t(ar[1], aA + 1536);
#pragma unroll
          for (int i = 0; i < 8; i++) af[i >> 2][i & 3] = addbf(af[i >> 2][i & 3], ar[i >> 2][i & 3]);
          STAIL
          pw_.x = pw_.y = pkh((c[0] + c[2]) + (d[0] + d[2]), (c[1] + c[3]) + (d[1] + d[3]), tag);
        }
        publish(XP_(xo), pw_);
        c0 = clk() + tx.z;
        TS(1);
      }
      uint2 r[4];
#define TOKS(i) { float e0[4] = {0, 0, 0, 0}, e1[4] = {0, 0, 0, 0}; \
        mma16(e0, af[0][0], af[0][1], af[0][2], af[0][3], qt[i][0], qt[i][1]); mma16(e1, af[0][0], af[0][1], af[0][2], af[0][3], qt[i + 1][0], qt[i + 1][1]); \
        mma16(e0, af[1][0], af[1][1], af[1][2], af[1][3], qt[i][2], qt[i][3]); mma16(e1, af[1][0], af[1][1], af[1][2], af[1][3], qt[i + 1][2], qt[i + 1][3]); \
        ts[i] = PACK(e0); ts[i + 1] = PACK(e1); }
      {
        float e[4][4];
#pragma unroll
        for (int i = 0; i < 4; i++) {
          e[i][0] = e[i][1] = e[i][2] = e[i][3] = 0.f;
          mma16(e[i], af[0][0], af[0][1], af[0][2], af[0][3], qt[i][0], qt[i][1]);
        }
#pragma unroll
        for (int i = 0; i < 4; i++) mma16(e[i], af[1][0], af[1][1], af[1][2], af[1][3], qt[i][2], qt[i][3]);
        SCHED_FENCE(55);
        if (s < 63) BAR_ARRIVE(B_S, 416);
        SCHED_FENCE(58);
        v[0] = lds4(tA + (VX0 - TA)); v[1] = lds4(tA + (VX0 - TA) + 2048); v[2] = lds4(tA + (VX1 - TA)); v[3] = lds4(tA + (VX1 - TA) + 2048);
#pragma unroll
        for (int i = 0; i < 4; i++) ts[i] = PACK(e[i]);
        while ((int)(clk() - c0) < 0) {}
        TS(5);
#pragma unroll
        for (int u = 0; u < 4; u++) r[u] = ldg_b64(XP_(xs) + u * 256);
        BAR_ARRIVE(B_S2, 256);
      }
      const uint32_t fn = (L16 & 256) ? 0xfc00fc00u : 0u;
      SCHED_FENCE(56);
      float4 e = softmax2<false>(r, 0, fn);
      const bool vbad = anybad(v[0].x, v[1].x, v[2].x, v[3].x, tag);
      if (BADS(r)) {
        int it = 0;
        if (s > 8) sts1(tA + 4096 + 8, min(lds1(tA + 4096 + 8) + dX, 500));
        do {
          RP(1);
          if (++it > SPIN_LIMIT) __trap();
#pragma unroll
          for (int u = 0; u < 4; u++) r[u] = ldg_b64(XP_(xs) + u * 256);
        } while (BADS(r));
        e = softmax2<false>(r, 0, fn);
      }
      sts1(t0.z, pk(e.x, e.y)); sts1(t0.z + 128, pk(e.z, e.w));
#pragma unroll
      for (int i = 0; i < 4; i++) publish(XP_(xo) + X_TOK + i * 4096, ts[i]);
      TS(6);
      if (s < 63) BAR_SYNC(B_V, 512); else BAR_SYNC(B_V, 256);
      uint32_t O[4];
      uint4 vn[2];
      {
        uint32_t p[4], pm;
        ldsm4t(p, pr);
        asm volatile("ldmatrix.sync.aligned.m8n8.x1.trans.shared.b16 {%0},[%1];" : "=r"(pm) : "r"(pr + 512) : "memory");
        vn[0] = lds4(tA + (VN - TA)); vn[1] = lds4(tA + (VN - TA) + 2048);
        pv_mem(p, pm, v, vn, O);
        if (vbad) {
          int it = 0;
          do {
            if (++it > SPIN_LIMIT) __trap();
#pragma unroll
            for (int u = 0; u < 4; u++) v[u] = ldg_b128(XP_((LO(xc) + (lds1(sb + PACE + 24) >> 2) * 262144 + ((tA - L16 - TA) >> 9) * XC + l16) ^ ring) + X_VX(u));
          } while (anybad(v[0].x, v[1].x, v[2].x, v[3].x, tag));
          pv_mem(p, pm, v, vn, O);
        }
      }
      stsm4(tA + (OB - TA), O[0], O[1], O[2], O[3]);
      if (s < 63) BAR_ARRIVE(B_O, 416);
      TS(2);
      c0 = clk() + dG;
      SCHED_FENCE(60);
      if (tA == sb + TA) mbar_expect(sb + BARS, 2048);
      const uint32_t vs[4] = {addbf(vn[0].x, vn[0].z), addbf(vn[0].y, vn[0].w), addbf(vn[1].x, vn[1].z), addbf(vn[1].y, vn[1].w)};
      {
        const char* xt = XP_(lds1(tA + 12) ^ ring);
        const uint2 t1 = lds2u(tA + 2048);
        const uint32_t pw = lds1(tA + 8);
        uint2 rt[4];
        CONSUME(LO(xt) ^ t1.x ^ pw);
        while ((int)(clk() - c0) < 0) {}
        int it = 0;
        do {
          if (++it > SPIN_LIMIT) __trap();
#pragma unroll
          for (int u = 0; u < 4; u++) rt[u] = ldg_b64(xt + u * 256);
        } while (BADS(rt));
        const float4 et = softmax2<true>(rt, t1.x, t1.y);
        sts1(pw + 1024, pk(et.x, et.y)); sts1(pw + 1024 + 128, pk(et.z, et.w));
      }
      s = PIN(s);
      BAR_SYNC(B_SC, 128);
      {
        uint32_t Ot[4], p[4], pm;
        const uint2 t2 = lds2u(tA + 2048 + 8);
        ldsm4t(p, pr + 1024);
        asm volatile("ldmatrix.sync.aligned.m8n8.x1.trans.shared.b16 {%0},[%1];" : "=r"(pm) : "r"(pr + 1024 + 512) : "memory");
        char* od = (char*)g_O + ((s >> 2) * 1048576 + (s & 3) * 4096) + t2.x;
        CONSUME(LO(od) ^ HI(od) ^ pm ^ p[3]);
        TS(9);
        if (s < 62) BAR_SYNC(B_P, 384);
        pv_tok(p, pm, v, vs, Ot);
        asm volatile("stmatrix.sync.aligned.m8n8.x4.trans.shared.b16 [%0],{%1,%2,%3,%4};" ::"r"(t2.y), "r"(Ot[0]), "r"(Ot[1]), "r"(Ot[2]), "r"(Ot[3]) : "memory");
        __syncwarp();
        *(uint4*)od = lds4(tA + (OT - TA));
      }
    }
    FENCE_ASYNC();
    BAR_SYNC(B_SC, 128);
    if (tA == sb + TA) red_rel(&g_fin);
  }
  __syncwarp();
  CLUSTER_SYNC();
  PH(5);
}
#undef wg
#undef iw
#undef h
#undef j
#undef a
#undef bb
#undef oi
#undef owner
#undef vfin
#undef xbar
#undef pr
#undef PIN
#undef XP_
#undef tw
#undef is7
#undef REFRESH
#undef lane
#undef l16
#undef lrow
#undef lar
#undef lpub

namespace ffn {
constexpr uint32_t BR = 98304;
constexpr uint32_t STG = 196608;
constexpr uint32_t PRM = 229376;
constexpr uint32_t BARS = PRM + 2816;
constexpr uint32_t SMEM = BARS + 19 * 8;
}
#define Y_TILE(rb, kt) (((ALIAS & 1) ? g_h : g_h2) + ((rb) * 16 + (kt)) * 1024)
#define U_TILE(rb, kt) ((ALIAS & 2) ? g_O + ((rb) * 64 + (kt)) * 1024 : g_U + ((rb) * 56 + (kt)) * 1024)
struct FfnMaps { CUtensorMap wo, w1a, w1b, w2, x, out; };

template <int N>
__device__ __forceinline__ void wg_ss(float* d, uint64_t a, uint64_t b, int sd) {
  if (N == 128) wgmma_ss_n128(d, a, b, sd);
  if (N == 192) wgmma_ss_n192(d, a, b, sd);
}
template <int N>
__device__ __forceinline__ void acc_fence(float* d) {
#pragma unroll
  for (int i = 0; i < N; i++) asm volatile("" : "+f"(d[i])::"memory");
}
struct FfnPipe {
  uint32_t full, emp, emp1, ph, aoff;
  int st, sB, prev;
  bool leader;
  template <int N>
  __device__ __forceinline__ void issue(float* acc, bool first, uint32_t a = 0) {
    mbar_wait(full + st * 8, ph);
    const uint64_t da = mkdesc((a ? a : 1024 + st * 16384) + aoff, 16, 1024), db = mkdesc(1024 + ffn::BR + sB * (N * 128), 8192, 1024);
    WG_FENCE();
#pragma unroll
    for (int j = 0; j < ((DBG & 1) ? 1 : 4); j++) wg_ss<N>(acc, da + j * 2, db + j * 128, j || !first);
    WG_COMMIT();
    if (++sB == 768 / N) sB = 0;
  }
  __device__ __forceinline__ void release() {
    if (leader) { mbar_arrive(emp + prev * 8); if (MC) mbar_arrive_cl(emp1 + prev * 8); }
  }
  __device__ __forceinline__ void next() { prev = st; if (++st == 6) { st = 0; ph ^= 1; } }
  __device__ __forceinline__ void retire() { WG_WAIT(1); release(); next(); }
};
__device__ __forceinline__ float gelu_h(float hx) {
  float u = hx * fmaf(hx * hx, 8.f * 0.0356774081f, 2.f * 0.7978845608f), t;
  asm("tanh.approx.f32 %0,%1;" : "=f"(t) : "f"(u));
  return fmaf(hx, t, hx);
}
struct FfnEpi {
  uint32_t stw, cc, flip, staged, par;
  uint4 c;
  float n0, n1;
  bool l0;
  __device__ __forceinline__ void acquire() { mbar_wait(staged + 16 + (flip >> 11), par); }
  __device__ __forceinline__ void flush() {
    __syncwarp();
    if (l0) mbar_arrive(staged + (flip >> 11));
    par ^= flip >> 14;
    flip ^= 16384;
  }
  __device__ __forceinline__ void slice(const float* d, int J) {
    asm volatile("{.reg .pred p; setp.ne.u32 p,%2,0; vote.sync.any.pred p,p,0xffffffff; selp.f32 %0,%0,0f00000000,p; selp.f32 %1,%1,0f00000000,p;}" : "+f"(n0), "+f"(n1) : "r"(cc) : "memory");
#define PRE(v, r, n, c1, c2) gelu_h(v + fmaf(n, c1, c2))
    stsm4((stw ^ ((J & 3) * 32)) + flip,
          pk(PRE(d[0], r0, n0, blo(c.x), blo(c.y)), PRE(d[1], r0, n0, bhi(c.x), bhi(c.y))), pk(PRE(d[2], r1, n1, blo(c.x), blo(c.y)), PRE(d[3], r1, n1, bhi(c.x), bhi(c.y))),
          pk(PRE(d[4], r0, n0, blo(c.z), blo(c.w)), PRE(d[5], r0, n0, bhi(c.z), bhi(c.w))), pk(PRE(d[6], r1, n1, blo(c.z), blo(c.w)), PRE(d[7], r1, n1, bhi(c.z), bhi(c.w))));
#undef PRE
    if ((J & 3) == 3) flush();
    cc += 64;
    c = lds4(cc);
  }
};

__global__ void
__launch_bounds__(384, 1)
k_ffn(const __grid_constant__ FfnMaps mp, const bf16* __restrict__ b2) {
  using namespace ffn;
  extern __shared__ __align__(1024) char smem[];
  const uint32_t sb = (uint32_t)__cvta_generic_to_shared(smem);
  if ((sb & 0x3FFFF) != 1024) __trap();
  const int tid = threadIdx.x, lane = tid & 31, wg = __shfl_sync(~0u, tid >> 7, 0);
  const uint32_t full = sb + BARS, emp = full + 48, xbar = full + 96, staged = full + 104, tile = full + 136;
  const uint32_t rank = MC ? blockIdx.x & 1 : 0;
  uint32_t fin = 0;
  if (tid >= 288 && tid < 320) fin = ld_acq(&g_fin);
  if (tid < 32) {
    unsigned sm, v = 0;
    asm("mov.u32 %0,%%smid;" : "=r"(sm));
    if (tid == 0) {
      if (!rank) v = atomicExch(&g_slot[(sm >> MC) & 255], 0);
      for (int i = 0; i < 6; i++) { mbar_init(full + i * 8, 1); mbar_init(emp + i * 8, 2 << MC); }
      mbar_init(xbar, 2);
      for (int i = 0; i < 2; i++) { mbar_init(staged + i * 8, 8); mbar_init(staged + 16 + i * 8, 1); }
      mbar_init(tile, 1);
      if (rank) mbar_expect(tile, 4);
      asm volatile("fence.mbarrier_init.release.cluster;" ::: "memory");
      FENCE_ASYNC_SMEM();
    }
    __syncwarp();
    if (MC) asm volatile("barrier.cluster.arrive.relaxed.aligned; barrier.cluster.wait.aligned;" ::: "memory");
    v = __shfl_sync(~0u, v, 0);
    if (rank) {
      mbar_wait(tile, 0);
    } else if (!v) {
      wait_cnt(&g_fin, 128);
      for (int it = 0; !v; it++) {
        const uint4 a = ldg_rlx4(g_slot + tid * 8), b = ldg_rlx4(g_slot + tid * 8 + 4);
        const uint32_t open = __ballot_sync(~0u, a.x | a.y | a.z | a.w | b.x | b.y | b.z | b.w);
        if (!open) break;
        if (it < 16) { __nanosleep(500); continue; }
        if (tid == __ffs(open) - 1) v = atomicExch(&g_slot[tid * 8 + (a.x ? 0 : a.y ? 1 : a.z ? 2 : a.w ? 3 : b.x ? 4 : b.y ? 5 : b.z ? 6 : 7)], 0);
        v = __shfl_sync(~0u, v, __ffs(open) - 1);
      }
    }
    if (tid == 0 && !rank) {
      sts1(tile + 8, v);
      if (MC) sta1<0>(mapa(tile + 8, 1), v ? v + 1 : 0, mapa(tile, 1));
    }
  } else if (MC) {
    asm volatile("barrier.cluster.arrive.relaxed.aligned; barrier.cluster.wait.aligned;" ::: "memory");
  }
  if (tid == 256) asm volatile("prefetch.tensormap [%0];" ::"l"(&mp.wo) : "memory");
  __syncthreads();
  const int bid = __shfl_sync(~0u, lds1(tile + 8), 0) - 1;
  if (bid < 0) return;
  PH(6);
  FT(1);
  const int rb = bid >> 3, nb = bid & 7;
  unsigned* cnt = g_cnt + rb * 128;
  if (wg == 2) {
    asm volatile("setmaxnreg.dec.sync.aligned.u32 " FRP ";");
    const int pw = __shfl_sync(~0u, (tid >> 5) & 3, 0);
    uint32_t ws = emp, wp = 1, fs = full;
    auto wait_free = [&]() { mbar_wait_q(ws, wp); ws += 8; if (ws == emp + 48) { ws = emp; wp ^= 1; } };
    auto step = [&]() { fs += 8; if (fs == full + 48) fs = full; };
    const int k4 = (nb >> 1) * 4;
    if (pw == 0) {
      uint32_t d = sb + BR + 32768;
      auto put = [&](const CUtensorMap* m, int k, int c) {
        e_expect_tma3d(d, m, k * 64, c, fs, 32768);
        step();
        d += 16384;
        if (d == sb + STG) d = sb + BR;
      };
      FTP(3);
#pragma unroll 1
      for (int k = 0; k < 64; k++) { wait_free(); put(&mp.wo, k, nb * 2); }
      wait_free(); wait_free();
#pragma unroll 1
      for (int k = 0; k < 16; k++) {
        wait_free();
        e_expect_tma3d(sb + BR + (k & 3) * 24576, &mp.w1b, (k < 4 ? (nb * 2) ^ k : (k4 + k) & 15) * 64, nb * 7, fs, k < 2 ? 24576 : 40960);
        step();
      }
#pragma unroll 1
      for (int k = 0; k < 32; k++) { if (k != 5 && k != 6) wait_free(); put(&mp.w1a, (k4 + k) & 15, nb * 7 + 3 + (k >> 4) * 2); }
#pragma unroll 1
      for (int c = 0; c < 3; c++)
#pragma unroll 1
        for (int k = c ? 2 * c + 1 : 0; k < 56; k += 7) {
          wait_free(); put(&mp.w2, k, nb * 2);
          wait_free(); put(&mp.w2, k + 1, nb * 2);
          if (!c) { wait_free(); put(&mp.w2, k + 2, nb * 2); }
        }
    } else if (pw == 1) {
      FTP(5);
      if (fin < 128) wait_cnt(&g_fin, 128);
      FTP(6);
      uint32_t d = sb;
      auto skip = [&]() { step(); d += 16384; if (d == sb + BR) d = sb; };
      auto put = [&](const uint4* A) {
        wait_free();
        if (MC) e_bulk_ld_mc(d + rank * 8192, A + rank * 512, 8192, fs); else e_bulk_ld(d, A, 16384, fs);
        skip();
      };
      const uint4* A = g_O + rb * 65536;
#pragma unroll 1
      for (int k = 0; k < 64; k++) put(A + k * 1024);
      wait_free(); skip(); wait_free(); skip();
      A = Y_TILE(rb, 0);
      uint32_t ready = 0;
#pragma unroll 1
      for (int k = 2; k < 16; k += 2) {
        const int kt = k == 2 ? (nb * 2) ^ 2 : (k4 + k) & 15;
        for (int it = 0; !(ready >> (kt >> 1) & 1); it++) {
          ready = __ballot_sync(~0u, (YR ? ldg_rlx1(cnt + (lane & 7)) : ld_acq(cnt + (lane & 7))) != 0);
          if (it > SPIN_LIMIT) __trap();
        }
        if (k == 2) FTP(75);
        if (MC && k == 2) {
          wait_free(); e_bulk_ld(d, A + kt * 1024, 16384, fs); skip();
          wait_free(); e_bulk_ld(d, A + kt * 1024 + 1024, 16384, fs); skip();
        } else {
          put(A + kt * 1024); put(A + kt * 1024 + 1024);
        }
      }
      if (!(ready >> nb & 1)) wait_cnt(cnt + nb, 1);
#pragma unroll 1
      for (int k = 0; k < 32; k++) put(A + ((k4 + k) & 15) * 1024);
      A = U_TILE(rb, 0);
#pragma unroll 1
      for (int c = 0; c < 3; c++) {
        wait_cnt(cnt + 32 + c * 32, 8);
#pragma unroll 1
        for (int k = c ? 2 * c + 1 : 0; k < 56; k += 7) {
          put(A + k * 1024); put(A + k * 1024 + 1024);
          if (!c) put(A + k * 1024 + 2048);
        }
      }
    } else if (pw == 2) {
      asm volatile("griddepcontrol.wait;" ::: "memory");
      for (int i = 0; i < XDL; i++) {
        mbar_wait_q(emp, i & 1);
        if (i == 1 && lane < 2) tma2d_pf(&mp.x, nb * 128 + lane * 64, rb * 128);
      }
      if (lane == 0) {
        mbar_expect(xbar, 32768);
        tma2d(sb + STG, &mp.x, nb * 128, rb * 128, xbar);
        tma2d(sb + STG + 16384, &mp.x, nb * 128 + 64, rb * 128, xbar);
      }
      if (lane < 16) g_modp[bid * 16 + lane] = make_uint4(0, 0, 0, 0);
      if (lane == 16 && bid == 0) { g_hcnt = 0; g_mcnt = 0; }
      if (lane == 0) {
        uint4* dst = Y_TILE(rb, nb * 2);
#pragma unroll 1
        for (int g = 0; g < 9; g++) {
          if (g < 2) mbar_wait(staged + g * 8, 0); else mbar_wait_q(staged + (g & 1) * 8, (g >> 1) & 1);
          FENCE_ASYNC_SMEM();
          bulk_st(dst, sb + STG + (g & 1) * 16384, 16384);
          BULK_COMMIT();
          dst = g == 1 ? U_TILE(rb, nb * 7) : dst + 1024;
          if (g == 0) continue;
          if (g == 1 || (g >= 4 && !(g & 1))) {
            BULK_WAIT(0);
            unsigned* f = g == 1 ? cnt + nb : cnt + (g - 2) * 16;
            if (YR) asm volatile("red.relaxed.gpu.global.add.u32 [%0],1;" ::"l"(f) : "memory"); else red_rel(f);
          }
          BULK_WAIT_READ(0);
          if (g == 1) mbar_arrive(staged + 16);
          mbar_arrive(staged + 16 + (g & 1) * 8);
        }
      }
    } else {
      const uint32_t prm = sb + PRM;
      const uint2 v2 = ((const uint2*)(b2 + nb * 128))[lane];
      sts2(prm + 768 + lane * 8, v2.x, v2.y);
      asm volatile("griddepcontrol.wait;" ::: "memory");
      const float4* md = (const float4*)(g_mod + nb * 128) + lane;
      { const float4 ga = md[512]; sts2(prm + lane * 8, pk(ga.x, ga.y), pk(ga.z, ga.w)); }
      { const float4 cb = md[1024]; sts2(prm + 256 + lane * 8, pk(1.f + cb.x, 1.f + cb.y), pk(1.f + cb.z, 1.f + cb.w)); }
      { const float4 gb = md[1280]; sts2(prm + 512 + lane * 8, pk(gb.x, gb.y), pk(gb.z, gb.w)); }
#pragma unroll 1
      for (int i = lane; i < 112; i += 32) { const uint4 c = g_cc[nb * 112 + i]; sts4(prm + 1024 + i * 16, c.x, c.y, c.z, c.w); }
      __syncwarp();
      if (lane == 0) mbar_arrive(xbar);
    }
    __syncwarp();
    if (MC) asm volatile("barrier.cluster.arrive.relaxed.aligned;" ::: "memory");
  } else {
    asm volatile("setmaxnreg.inc.sync.aligned.u32 " FRC ";");
    const int w = (tid >> 5) & 3, q = lane & 3;
    const uint32_t prm = sb + PRM + q * 4;
    const int row0 = wg * 64 + w * 16;
    FfnPipe p;
    p.full = full; p.emp = emp; p.emp1 = mapa(emp, rank ^ 1); p.ph = 0; p.aoff = wg * 8192; p.st = 0; p.sB = 2; p.prev = 0; p.leader = (tid & 127) == 0;
    FfnEpi e;
    const uint32_t stg = sb + STG + row0 * 128;
    e.stw = stg + (lane & 15) * 128 + (((lane >> 4) ^ (lane & 7)) << 4);
    e.cc = sb + PRM + 1024 + q * 16; e.flip = 0; e.staged = staged; e.par = 1; e.l0 = lane == 0;
    const uint32_t stw = e.stw;
    uint32_t x1[32];
    uint4* xp = g_x1 + bid * 2048 + tid;
    uint4* sp = g_stat + (rb * 128 + row0 + (lane >> 2)) * 4;
    float old[96], r0_, r1_;
    {
      float acc[64];
      p.issue<128>(acc, true); FT(8); p.next();
#pragma unroll 1
      for (int k = 1; k < 64; k++) { p.issue<128>(acc, false); FT(8 + k); p.retire(); }
      WG_WAIT(0);
      p.release();
      acc_fence<64>(acc);
      PH(7); FT(72);
      mbar_wait(xbar, 0);
#pragma unroll
      for (int j = 0; j < 8; j++) {
        uint32_t xv[4];
        const uint32_t ad = (stw ^ ((j & 3) * 32)) + (j >> 2) * 16384;
        ldsm4(xv, ad);
        const uint32_t g0 = lds1(prm + j * 32), g1 = lds1(prm + j * 32 + 16), c0 = lds1(prm + 256 + j * 32), c1 = lds1(prm + 256 + j * 32 + 16);
        const float* d = acc + j * 8;
        uint32_t* o = x1 + j * 4;
        o[0] = pk(blo(xv[0]) + blo(g0) * d[0], bhi(xv[0]) + bhi(g0) * d[1]);
        o[1] = pk(blo(xv[1]) + blo(g0) * d[2], bhi(xv[1]) + bhi(g0) * d[3]);
        o[2] = pk(blo(xv[2]) + blo(g1) * d[4], bhi(xv[2]) + bhi(g1) * d[5]);
        o[3] = pk(blo(xv[3]) + blo(g1) * d[6], bhi(xv[3]) + bhi(g1) * d[7]);
        stsm4(ad, mulbf(o[0], c0), mulbf(o[1], c0), mulbf(o[2], c1), mulbf(o[3], c1));
        if ((j & 3) == 3) e.flush();
      }
      FENCE_ASYNC_SMEM();
      if (wg) BAR_SYNC(2, 128); else BAR_SYNC(3, 128);
    }
    PH(8); FT(73);
    float acc[64];
    {
      float accC[96];
      p.sB = 0;
      p.issue<192>(accC, true, 1024 + STG); FT(80); p.next();
      p.issue<192>(accC, false, 1024 + STG + 16384); FT(81);
      FT(78);
      float s0 = 0, s1 = 0;
#define X1_FENCE _Pragma("unroll") for (int j = 0; j < 32; j++) asm volatile("" : "+r"(x1[j]));
      X1_FENCE
#pragma unroll
      for (int j = 0; j < 16; j++) { s0 += blo(x1[j * 2]) + bhi(x1[j * 2]); s1 += blo(x1[j * 2 + 1]) + bhi(x1[j * 2 + 1]); }
      s0 += __shfl_xor_sync(~0u, s0, 1); s1 += __shfl_xor_sync(~0u, s1, 1);
      s0 += __shfl_xor_sync(~0u, s0, 2); s1 += __shfl_xor_sync(~0u, s1, 2);
      s0 *= 1.f / 128; s1 *= 1.f / 128;
      float q0 = 0, q1 = 0;
      X1_FENCE
#pragma unroll
      for (int j = 0; j < 16; j++) {
        const float a = blo(x1[j * 2]) - s0, b = bhi(x1[j * 2]) - s0, c = blo(x1[j * 2 + 1]) - s1, d = bhi(x1[j * 2 + 1]) - s1;
        q0 += a * a + b * b; q1 += c * c + d * d;
      }
      q0 += __shfl_xor_sync(~0u, q0, 1); q1 += __shfl_xor_sync(~0u, q1, 1);
      q0 += __shfl_xor_sync(~0u, q0, 2); q1 += __shfl_xor_sync(~0u, q1, 2);
      if (q < 2) {
        uint32_t m = __float_as_uint(q ? s1 : s0), v = __float_as_uint(q ? q1 : q0);
        if (m == ~0u) m = 0x7fffffffu;
        if (v == ~0u) v = 0x7fffffffu;
        stg_rlx2((uint2*)(sp + q * 32) + nb, m, v);
      }
#pragma unroll
      for (int j = 0; j < XPK; j++) __stcg(xp + j * 256, make_uint4(x1[j * 4], x1[j * 4 + 1], x1[j * 4 + 2], x1[j * 4 + 3]));
      X1_FENCE
      p.retire();
#pragma unroll 1
      for (int k = 2; k < 16; k++) { p.issue<192>(accC, false); FT(80 + k); p.retire(); }
      p.issue<128>(acc, true); FT(96);
      {
          uint4 r0, r1;
          int it = 0;
          while (true) {
            r0 = ldg_rlx4(sp + q); r1 = ldg_rlx4(sp + 32 + q);
            const bool ok = r0.x != ~0u && r0.y != ~0u && r0.z != ~0u && r0.w != ~0u && r1.x != ~0u && r1.y != ~0u && r1.z != ~0u && r1.w != ~0u;
            if (__all_sync(~0u, ok)) break;
            if (++it > SPIN_LIMIT) __trap();
          }
          float m0 = __uint_as_float(r0.x) + __uint_as_float(r0.z), m1 = __uint_as_float(r1.x) + __uint_as_float(r1.z);
          m0 += __shfl_xor_sync(~0u, m0, 1); m1 += __shfl_xor_sync(~0u, m1, 1);
          m0 += __shfl_xor_sync(~0u, m0, 2); m1 += __shfl_xor_sync(~0u, m1, 2);
          m0 *= 0.125f; m1 *= 0.125f;
          const float a = __uint_as_float(r0.x) - m0, b = __uint_as_float(r0.z) - m0, c = __uint_as_float(r1.x) - m1, d = __uint_as_float(r1.z) - m1;
          float v0 = __uint_as_float(r0.y) + __uint_as_float(r0.w) + 128.f * (a * a + b * b);
          float v1 = __uint_as_float(r1.y) + __uint_as_float(r1.w) + 128.f * (c * c + d * d);
          v0 += __shfl_xor_sync(~0u, v0, 1); v1 += __shfl_xor_sync(~0u, v1, 1);
          v0 += __shfl_xor_sync(~0u, v0, 2); v1 += __shfl_xor_sync(~0u, v1, 2);
          r0_ = 0.5f * rsqrtf(v0 * (1.f / 1024) + 1e-5f); r1_ = 0.5f * rsqrtf(v1 * (1.f / 1024) + 1e-5f);
          e.n0 = -m0 * r0_; e.n1 = -m1 * r1_;
          e.c = lds4(e.cc);
        }
      p.retire();
      acc_fence<96>(accC);
#pragma unroll
      for (int k = 0; k < 96; k++) old[k] = accC[k] * ((k & 2) ? r1_ : r0_);
      acc_fence<96>(old);
    }
    PH(9);
    {
#define FFN_FENCE(k) do { if (e.l0) BULK_WAIT_READ(1); __syncwarp(); } while (0)
#pragma unroll 1
      for (int i = 0; i < 3; i++) {
#pragma unroll
        for (int k = 0; k < 8; k++) {
          p.issue<128>(acc, false); FT(97 + i * 16 + k);
          if ((k & 3) == 0) e.acquire(); else FFN_FENCE(k);
          e.slice(old + k * 8, k);
          p.retire();
        }
        if (i == 0) {
#pragma unroll
          for (int k = 8; k < 12; k++) {
            p.issue<128>(acc, false); FT(97 + k);
            if ((k & 3) == 0) e.acquire(); else FFN_FENCE(k);
            e.slice(old + k * 8, k);
            p.retire();
          }
        }
        const int k0 = i ? 9 : 13;
#pragma unroll 1
        for (int k = k0; k < 16; k++) {
          p.issue<128>(acc, false); FT(96 + i * 16 + k);
          p.retire();
        }
        if (i == 2) break;
        WG_WAIT(0);
        acc_fence<64>(acc);
#pragma unroll
        for (int k = 0; k < 64; k++) old[k] = acc[k] * ((k & 2) ? r1_ : r0_);
        acc_fence<64>(old);
        p.issue<128>(acc, true); FT(112 + i * 16);
        p.retire();
        PH(10 + i);
      }
#pragma unroll
      for (int j = 0; j < XPK; j++) { const uint4 v = ldg_rlx4(xp + j * 256); x1[j * 4] = v.x; x1[j * 4 + 1] = v.y; x1[j * 4 + 2] = v.z; x1[j * 4 + 3] = v.w; }
#pragma unroll 1
      for (int k = 16; k < 56; k++) { p.issue<128>(acc, false); FT(128 + k); p.retire(); }
      e.acquire();
      mbar_wait(staged + 16, 0);
      WG_WAIT(0);
      if (MC) asm volatile("barrier.cluster.arrive.relaxed.aligned;" ::: "memory");
      acc_fence<64>(acc);
      PH(13); FT(184);
#pragma unroll
      for (int j = 0; j < 8; j++) {
        const uint32_t g0 = lds1(prm + 512 + j * 32), g1 = lds1(prm + 512 + j * 32 + 16);
        const uint32_t h0 = lds1(prm + 768 + j * 32), h1 = lds1(prm + 768 + j * 32 + 16);
        const float* d = acc + j * 8;
        const uint32_t* xv = x1 + j * 4;
        stsm4((stw ^ ((j & 3) * 32)) + (j >> 2) * 16384,
              pk(blo(xv[0]) + blo(g0) * (d[0] + blo(h0)), bhi(xv[0]) + bhi(g0) * (d[1] + bhi(h0))),
              pk(blo(xv[1]) + blo(g0) * (d[2] + blo(h0)), bhi(xv[1]) + bhi(g0) * (d[3] + bhi(h0))),
              pk(blo(xv[2]) + blo(g1) * (d[4] + blo(h1)), bhi(xv[2]) + bhi(g1) * (d[5] + bhi(h1))),
              pk(blo(xv[3]) + blo(g1) * (d[6] + blo(h1)), bhi(xv[3]) + bhi(g1) * (d[7] + bhi(h1))));
        if ((j & 3) == 3) {
          FENCE_ASYNC_SMEM();
          __syncwarp();
          if (lane == 0) { tma2d_st(&mp.out, nb * 128 + (j >> 2) * 64, rb * 128 + row0, stg + (j >> 2) * 16384); BULK_COMMIT(); }
        }
      }
      if (lane == 0) BULK_WAIT_READ(0);
      __syncwarp();
    }
  }
  if (MC) asm volatile("barrier.cluster.wait.aligned;" ::: "memory");
  PH(14); FT(185);
}

typedef CUresult (*EncFn)(CUtensorMap*, CUtensorMapDataType, cuuint32_t, void*, const cuuint64_t*, const cuuint64_t*, const cuuint32_t*,
                          const cuuint32_t*, CUtensorMapInterleave, CUtensorMapSwizzle, CUtensorMapL2promotion, CUtensorMapFloatOOBfill);
static void map2d(EncFn enc, CUtensorMap* m, const void* p, int rows, int cols, int boxRows) {
  cuuint64_t d[2] = {(cuuint64_t)cols, (cuuint64_t)rows}, s[1] = {(cuuint64_t)cols * 2};
  cuuint32_t b[2] = {64, (cuuint32_t)boxRows}, e[2] = {1, 1};
  enc(m, CU_TENSOR_MAP_DATA_TYPE_BFLOAT16, 2, (void*)p, d, s, b, e, CU_TENSOR_MAP_INTERLEAVE_NONE, CU_TENSOR_MAP_SWIZZLE_128B,
      CU_TENSOR_MAP_L2_PROMOTION_L2_128B, CU_TENSOR_MAP_FLOAT_OOB_FILL_NONE);
}
static void map3d(EncFn enc, CUtensorMap* m, const void* p, int rows, int cols, int nch) {
  cuuint64_t d[3] = {64, (cuuint64_t)rows, (cuuint64_t)(cols / 64)}, s[2] = {(cuuint64_t)cols * 2, 128};
  cuuint32_t b[3] = {64, 64, (cuuint32_t)nch}, e[3] = {1, 1, 1};
  enc(m, CU_TENSOR_MAP_DATA_TYPE_BFLOAT16, 3, (void*)p, d, s, b, e, CU_TENSOR_MAP_INTERLEAVE_NONE, CU_TENSOR_MAP_SWIZZLE_128B,
      CU_TENSOR_MAP_L2_PROMOTION_L2_128B, CU_TENSOR_MAP_FLOAT_OOB_FILL_NONE);
}

extern "C" void kernel_launch(void* const* d_in, const int* in_sizes, int n_in, void* d_out, int out_size) {
  const bf16* x = (const bf16*)d_in[0];
  const bf16* mem0 = (const bf16*)d_in[1];
  void* fn = nullptr;
  cudaDriverEntryPointQueryResult qr;
  cudaGetDriverEntryPoint("cuTensorMapEncodeTiled", &fn, cudaEnableDefault, &qr);
  EncFn enc = (EncFn)fn;
  FfnMaps fm = {};
  map3d(enc, &fm.wo, d_in[5], 4096, 1024, 2);
  map3d(enc, &fm.w1a, d_in[8], 1024, 3584, 2);
  map3d(enc, &fm.w1b, d_in[8], 1024, 3584, 3);
  map3d(enc, &fm.w2, d_in[10], 3584, 1024, 2);
  map2d(enc, &fm.x, x, 2048, 1024, 128);
  map2d(enc, &fm.out, d_out, 2048, 1024, 16);
  RecMaps rm = {};
  map2d(enc, &rm.wq, d_in[2], 1024, 4096, 128);
  map2d(enc, &rm.wk, d_in[3], 1024, 4096, 128);
  map2d(enc, &rm.wv, d_in[4], 1024, 4096, 16);
  map2d(enc, &rm.wo, d_in[5], 4096, 1024, 128);
  {
    void* ar = nullptr;
    cudaGetSymbolAddress(&ar, g_ar);
    cuuint64_t d[2] = {512, 160}, sd[1] = {1024};
    cuuint32_t bi[2] = {64, 40}, e[2] = {1, 1};
    enc(&rm.ari, CU_TENSOR_MAP_DATA_TYPE_BFLOAT16, 2, ar, d, sd, bi, e, CU_TENSOR_MAP_INTERLEAVE_NONE, CU_TENSOR_MAP_SWIZZLE_NONE,
        CU_TENSOR_MAP_L2_PROMOTION_NONE, CU_TENSOR_MAP_FLOAT_OOB_FILL_NONE);
  }
  cudaFuncSetAttribute(k_ffn, cudaFuncAttributeMaxDynamicSharedMemorySize, ffn::SMEM);
  cudaFuncSetAttribute(k_rec, cudaFuncAttributeMaxDynamicSharedMemorySize, rec::SMEM);
  char* xc = nullptr;
  cudaGetSymbolAddress((void**)&xc, g_xc);
  xc += (0 - (uintptr_t)xc) & 0x3FFFF;
  cudaStream_t st = cudaStreamPerThread;
  int dF = 450, dA = 2700, dS = 300, dM = 120, dG = 350, dP = 24, dX = 48, dD = 350, dZ = 0, dZ2 = 1, dV = 370, dX2 = 0;
  k_rec<<<132, 512, rec::SMEM, st>>>(rm, mem0, x, (const bf16*)d_in[12], (const bf16*)d_in[13], (const char*)d_in[8], (const bf16*)d_in[9],
                                     xc, dF, dA, dS, dM, dG, dP, dX, dD, dZ, dZ2, dV, dX2);
  cudaLaunchConfig_t cfg = {};
  cfg.gridDim = dim3(132); cfg.blockDim = dim3(384); cfg.dynamicSmemBytes = ffn::SMEM; cfg.stream = st;
  cudaLaunchAttribute at[1];
  at[0].id = cudaLaunchAttributeProgrammaticStreamSerialization;
  at[0].val.programmaticStreamSerializationAllowed = 1;
  cfg.attrs = at; cfg.numAttrs = 1;
  cudaLaunchKernelEx(&cfg, k_ffn, fm, (const bf16*)d_in[11]);
}
```

```cpp
#include <cuda_runtime.h>
#include <cuda.h>
#include <cuda_bf16.h>
#include <stdint.h>

typedef __nv_bfloat16 bf16;

__device__ __align__(16) float g_mod[6144];
__device__ __align__(1024) uint4 g_modp[4 * 512];
__device__ unsigned g_hcnt;
__device__ __align__(1024) uint4 g_h[2048 * 1024 / 8];
__device__ __align__(1024) uint4 g_O[2048 * 4096 / 8];
__device__ __align__(1024) uint4 g_h2[2048 * 1024 / 8];
__device__ __align__(1024) uint4 g_U[2048 * 3584 / 8];
__device__ __align__(1024) uint4 g_stat[2048 * 4];
__device__ __align__(1024) unsigned g_cnt[16 * 4 * 32];
__device__ unsigned g_mcnt;
__device__ unsigned g_slot[256];
__device__ unsigned g_fin;
__device__ __align__(16) uint4 g_cc[224 * 4];
__device__ __align__(1024) uint4 g_ar[160 * 64];
__device__ __align__(1024) uint4 g_xc[33 * 16384];
__device__ __align__(1024) unsigned g_tm[4 * 256];
#define FT(i)
#define FTP(i)
#define PH(i)
#define RP(i)
#define RPN(i, s)
#define TSV(i, v)
#define TS(i)

#define WIN 2
#define FRC "232"
#define FRP "40"
#define YR 1
#define XPK 0
#define NFA 1
#define PINM 1
#define FMAP (((g >> 2) * 4 + m) * 8 + (g & 3) * 2 + (blockIdx.x & 1))
#define DBG 0
#define ALIAS 3
#define EF 0
#define XPF 0
#define PFT 150000
#define PFS 100
#define XDL 6
#define QW 0
#define PDS 61
#define P_NVR 5
#define P_NVP 2
#define P_NWP 9
#define P_NW1 7
#define RF_ 208
#define PSV 1
#define RA_ (488 - 2 * RF_)
#define XI 5
#define XL 1
#define WCH 2
#define HX 0
#define VB 1
#define HU_ 32
#define HP 2
#define HS 1
constexpr int HU = HU_;
#define TP 0
#define CKI 0
#define NOP_ 2
#define KVO 0
#define NDL 3
#define AM 0
#define XM 3
#define XP 0
#define SPIN_LIMIT (1 << 20)
__device__ __forceinline__ uint64_t mkdesc(uint32_t addr, uint32_t lbo, uint32_t sbo) {
  return (uint64_t)((addr & 0x3FFFF) >> 4) | ((uint64_t)(lbo >> 4) << 16) | ((uint64_t)(sbo >> 4) << 32) | (1ull << 62);
}
__device__ __forceinline__ void mbar_init(uint32_t a, int c) { asm volatile("mbarrier.init.shared.b64 [%0],%1;" ::"r"(a), "r"(c) : "memory"); }
__device__ __forceinline__ void mbar_wait(uint32_t a, uint32_t par) {
  asm volatile(
      "{.reg .pred p; .reg .u32 n;\n"
      "mov.u32 n, 0;\n"
      "W: mbarrier.try_wait.parity.shared.b64 p,[%0],%1;\n"
      "@p bra D;\n"
      "add.u32 n, n, 1;\n"
      "setp.lt.u32 p, n, %2;\n"
      "@p bra W;\n"
      "trap;\n"
      "D:}" ::"r"(a), "r"(par), "n"(SPIN_LIMIT) : "memory");
}
__device__ __forceinline__ void mbar_wait_q(uint32_t a, uint32_t par) {
  asm volatile(
      "{.reg .pred p; .reg .u32 n;\n"
      "mov.u32 n, 0;\n"
      "W: mbarrier.try_wait.parity.shared.b64 p,[%0],%1,4000;\n"
      "@p bra D;\n"
      "add.u32 n, n, 1;\n"
      "setp.lt.u32 p, n, %2;\n"
      "@p bra W;\n"
      "trap;\n"
      "D:}" ::"r"(a), "r"(par), "n"(SPIN_LIMIT / 16) : "memory");
}
__device__ __forceinline__ void mbar_expect(uint32_t a, uint32_t b) { asm volatile("mbarrier.arrive.expect_tx.shared.b64 _,[%0],%1;" ::"r"(a), "r"(b) : "memory"); }
__device__ __forceinline__ void mbar_arrive(uint32_t a) { asm volatile("mbarrier.arrive.shared.b64 _,[%0];" ::"r"(a) : "memory"); }
__device__ __forceinline__ uint32_t mapa(uint32_t a, uint32_t cta) { uint32_t r; asm("mapa.shared::cluster.u32 %0,%1,%2;" : "=r"(r) : "r"(a), "r"(cta)); return r; }
__device__ __forceinline__ void mbar_arrive_cl(uint32_t a) { asm volatile("mbarrier.arrive.shared::cluster.b64 _,[%0];" ::"r"(a) : "memory"); }
__device__ __forceinline__ void tma2d(uint32_t dst, const CUtensorMap* m, int c0, int c1, uint32_t mb) {
  asm volatile("cp.async.bulk.tensor.2d.shared::cluster.global.mbarrier::complete_tx::bytes [%0],[%1,{%2,%3}],[%4];" ::"r"(dst), "l"(m), "r"(c0), "r"(c1), "r"(mb) : "memory");
}
__device__ __forceinline__ void tma2d_pf(const CUtensorMap* m, int c0, int c1) {
  asm volatile("cp.async.bulk.prefetch.tensor.2d.L2.global [%0,{%1,%2}];" ::"l"(m), "r"(c0), "r"(c1) : "memory");
}
__device__ __forceinline__ void tma3d(uint32_t dst, const CUtensorMap* m, int c1, int c2, uint32_t mb) {
  asm volatile("cp.async.bulk.tensor.3d.shared::cluster.global.mbarrier::complete_tx::bytes [%0],[%1,{0,%2,%3}],[%4];" ::"r"(dst), "l"(m), "r"(c1), "r"(c2), "r"(mb) : "memory");
}
__device__ __forceinline__ void tma2d_st(const CUtensorMap* m, int c0, int c1, uint32_t src) {
  asm volatile("cp.async.bulk.tensor.2d.global.shared::cta.bulk_group [%0,{%1,%2}],[%3];" ::"l"(m), "r"(c0), "r"(c1), "r"(src) : "memory");
}
__device__ __forceinline__ void bulk_ld(uint32_t dst, const void* src, uint32_t n, uint32_t mb) {
  asm volatile("cp.async.bulk.shared::cluster.global.mbarrier::complete_tx::bytes [%0],[%1],%2,[%3];" ::"r"(dst), "l"(src), "r"(n), "r"(mb) : "memory");
}
__device__ __forceinline__ void bulk_ld_mc(uint32_t dst, const void* src, uint32_t n, uint32_t mb) {
  asm volatile("cp.async.bulk.shared::cluster.global.mbarrier::complete_tx::bytes.multicast::cluster [%0],[%1],%2,[%3],%4;" ::"r"(dst), "l"(src), "r"(n), "r"(mb), "h"((uint16_t)3) : "memory");
}
__device__ __forceinline__ void bulk_st(void* dst, uint32_t src, uint32_t n) {
  asm volatile("cp.async.bulk.global.shared::cta.bulk_group [%0],[%1],%2;" ::"l"(dst), "r"(src), "r"(n) : "memory");
}
__device__ __forceinline__ void e_expect_tma3d(uint32_t dst, const CUtensorMap* m, int c1, int c2, uint32_t mb, uint32_t bytes) {
  asm volatile("{.reg .pred p; elect.sync _|p, 0xffffffff; @p mbarrier.arrive.expect_tx.shared.b64 _,[%4],%5;\n"
               "@p cp.async.bulk.tensor.3d.shared::cluster.global.mbarrier::complete_tx::bytes [%0],[%1,{0,%2,%3}],[%4];}" ::"r"(dst), "l"(m), "r"(c1), "r"(c2), "r"(mb), "r"(bytes) : "memory");
}
__device__ __forceinline__ void e_bulk_ld(uint32_t dst, const void* src, uint32_t n, uint32_t mb) {
  asm volatile("{.reg .pred p; elect.sync _|p, 0xffffffff; @p cp.async.bulk.shared::cluster.global.mbarrier::complete_tx::bytes [%0],[%1],%2,[%3];}" ::"r"(dst), "l"(src), "r"(n), "r"(mb) : "memory");
}
__device__ __forceinline__ void e_bulk_ld_ef(uint32_t dst, const void* src, uint32_t n, uint32_t mb) {
  asm volatile("{.reg .pred p; .reg .b64 c; createpolicy.fractional.L2::evict_first.b64 c,1.0; elect.sync _|p, 0xffffffff;"
               " @p cp.async.bulk.shared::cluster.global.mbarrier::complete_tx::bytes.L2::cache_hint [%0],[%1],%2,[%3],c;}" ::"r"(dst), "l"(src), "r"(n), "r"(mb) : "memory");
}
__device__ __forceinline__ void e_bulk_ld_mc(uint32_t dst, const void* src, uint32_t n, uint32_t mb) {
  asm volatile("{.reg .pred p; elect.sync _|p, 0xffffffff; @p cp.async.bulk.shared::cluster.global.mbarrier::complete_tx::bytes.multicast::cluster [%0],[%1],%2,[%3],%4;}" ::"r"(dst), "l"(src), "r"(n), "r"(mb), "h"((uint16_t)3) : "memory");
}
#define BULK_COMMIT() asm volatile("cp.async.bulk.commit_group;" ::: "memory")
#define BULK_WAIT_READ(n) asm volatile("cp.async.bulk.wait_group.read " #n ";" ::: "memory")
#define BULK_WAIT(n) asm volatile("cp.async.bulk.wait_group " #n ";" ::: "memory")
#define FENCE_ASYNC_SMEM() asm volatile("fence.proxy.async.shared::cta;" ::: "memory")
#define FENCE_ASYNC() asm volatile("fence.proxy.async;" ::: "memory")
#define WG_FENCE() asm volatile("wgmma.fence.sync.aligned;" ::: "memory")
#define WG_COMMIT() asm volatile("wgmma.commit_group.sync.aligned;" ::: "memory")
#define WG_WAIT(n) asm volatile("wgmma.wait_group.sync.aligned " #n ";" ::: "memory")
#define BAR_SYNC(id, n) asm volatile("bar.sync %0,%1;" ::"n"(id), "n"(n) : "memory")
#define BAR_ARRIVE(id, n) asm volatile("bar.arrive %0,%1;" ::"n"(id), "n"(n) : "memory")
#define SCHED_FENCE(k) asm volatile("{.reg .pred p; setp.ne.u32 p,%0,0; @p trap;}" ::"r"(mp.zero[(k) - 46]) : "memory")
#define CLUSTER_SYNC() asm volatile("barrier.cluster.arrive.aligned; barrier.cluster.wait.aligned;" ::: "memory")
__device__ __forceinline__ uint32_t pk(float lo, float hi) { uint32_t r; asm("cvt.rn.bf16x2.f32 %0,%1,%2;" : "=r"(r) : "f"(hi), "f"(lo)); return r; }
__device__ __forceinline__ float blo(uint32_t v) { return __uint_as_float(v << 16); }
__device__ __forceinline__ float bhi(uint32_t v) { return __uint_as_float(v & 0xffff0000u); }
__device__ __forceinline__ void ldsm4(uint32_t* r, uint32_t a) {
  asm volatile("ldmatrix.sync.aligned.m8n8.x4.shared.b16 {%0,%1,%2,%3},[%4];" : "=r"(r[0]), "=r"(r[1]), "=r"(r[2]), "=r"(r[3]) : "r"(a) : "memory");
}
__device__ __forceinline__ void ldsm4t(uint32_t* r, uint32_t a) {
  asm volatile("ldmatrix.sync.aligned.m8n8.x4.trans.shared.b16 {%0,%1,%2,%3},[%4];" : "=r"(r[0]), "=r"(r[1]), "=r"(r[2]), "=r"(r[3]) : "r"(a) : "memory");
}
__device__ __forceinline__ void stsm4(uint32_t a, uint32_t r0, uint32_t r1, uint32_t r2, uint32_t r3) {
  asm volatile("stmatrix.sync.aligned.m8n8.x4.shared.b16 [%0],{%1,%2,%3,%4};" ::"r"(a), "r"(r0), "r"(r1), "r"(r2), "r"(r3) : "memory");
}
__device__ __forceinline__ void mma16(float* d, uint32_t a0, uint32_t a1, uint32_t a2, uint32_t a3, uint32_t b0, uint32_t b1) {
  asm volatile("mma.sync.aligned.m16n8k16.row.col.f32.bf16.bf16.f32 {%0,%1,%2,%3},{%4,%5,%6,%7},{%8,%9},{%0,%1,%2,%3};"
               : "+f"(d[0]), "+f"(d[1]), "+f"(d[2]), "+f"(d[3]) : "r"(a0), "r"(a1), "r"(a2), "r"(a3), "r"(b0), "r"(b1));
}
__device__ __forceinline__ void mma8(float* d, uint32_t a0, uint32_t a1, uint32_t b0) {
  asm volatile("mma.sync.aligned.m16n8k8.row.col.f32.bf16.bf16.f32 {%0,%1,%2,%3},{%4,%5},{%6},{%0,%1,%2,%3};"
               : "+f"(d[0]), "+f"(d[1]), "+f"(d[2]), "+f"(d[3]) : "r"(a0), "r"(a1), "r"(b0));
}
__device__ __forceinline__ float4 lds4f(uint32_t a) { float4 v; asm volatile("ld.shared.v4.f32 {%0,%1,%2,%3},[%4];" : "=f"(v.x), "=f"(v.y), "=f"(v.z), "=f"(v.w) : "r"(a) : "memory"); return v; }
__device__ __forceinline__ float2 lds2f(uint32_t a) { float2 v; asm volatile("ld.shared.v2.f32 {%0,%1},[%2];" : "=f"(v.x), "=f"(v.y) : "r"(a) : "memory"); return v; }
__device__ __forceinline__ uint4 lds4(uint32_t a) { uint4 v; asm volatile("ld.shared.v4.u32 {%0,%1,%2,%3},[%4];" : "=r"(v.x), "=r"(v.y), "=r"(v.z), "=r"(v.w) : "r"(a) : "memory"); return v; }
__device__ __forceinline__ uint2 lds2u(uint32_t a) { uint2 v; asm volatile("ld.shared.v2.u32 {%0,%1},[%2];" : "=r"(v.x), "=r"(v.y) : "r"(a) : "memory"); return v; }
__device__ __forceinline__ uint32_t lds1(uint32_t a) { uint32_t v; asm volatile("ld.shared.u32 %0,[%1];" : "=r"(v) : "r"(a) : "memory"); return v; }
__device__ __forceinline__ void sts4(uint32_t a, uint32_t x, uint32_t y, uint32_t z, uint32_t w) { asm volatile("st.shared.v4.u32 [%0],{%1,%2,%3,%4};" ::"r"(a), "r"(x), "r"(y), "r"(z), "r"(w) : "memory"); }
__device__ __forceinline__ void sts2(uint32_t a, uint32_t x, uint32_t y) { asm volatile("st.shared.v2.u32 [%0],{%1,%2};" ::"r"(a), "r"(x), "r"(y) : "memory"); }
__device__ __forceinline__ void sts1(uint32_t a, uint32_t x) { asm volatile("st.shared.u32 [%0],%1;" ::"r"(a), "r"(x) : "memory"); }
__device__ __forceinline__ void sta4(uint32_t a, const uint32_t* v, uint32_t mb) {
  asm volatile("st.async.shared::cluster.mbarrier::complete_tx::bytes.v4.b32 [%0],{%1,%2,%3,%4},[%5];" ::"r"(a), "r"(v[0]), "r"(v[1]), "r"(v[2]), "r"(v[3]), "r"(mb) : "memory");
}
__device__ __forceinline__ uint4 ldg_rlx4(const void* p) { uint4 v; asm volatile("ld.relaxed.gpu.global.v4.u32 {%0,%1,%2,%3},[%4];" : "=r"(v.x), "=r"(v.y), "=r"(v.z), "=r"(v.w) : "l"(p) : "memory"); return v; }
__device__ __forceinline__ uint32_t ldg_rlx1(const void* p) { uint32_t v; asm volatile("ld.relaxed.gpu.global.u32 %0,[%1];" : "=r"(v) : "l"(p) : "memory"); return v; }
__device__ __forceinline__ uint2 ldg_rlx2(const void* p) { uint2 v; asm volatile("ld.relaxed.gpu.global.v2.u32 {%0,%1},[%2];" : "=r"(v.x), "=r"(v.y) : "l"(p) : "memory"); return v; }
__device__ __forceinline__ uint4 ldg_b128(const void* p) {
  uint4 v;
  asm volatile("{.reg .b128 t; .reg .b64 a,b; ld.relaxed.gpu.global.b128 t,[%4]; mov.b128 {a,b},t; mov.b64 {%0,%1},a; mov.b64 {%2,%3},b;}" : "=r"(v.x), "=r"(v.y), "=r"(v.z), "=r"(v.w) : "l"(p) : "memory");
  return v;
}
__device__ __forceinline__ void stg_b128(void* p, uint32_t x, uint32_t y, uint32_t z, uint32_t w) {
  asm volatile("{.reg .b128 t; .reg .b64 a,b; mov.b64 a,{%1,%2}; mov.b64 b,{%3,%4}; mov.b128 t,{a,b}; st.relaxed.gpu.global.b128 [%0],t;}" ::"l"(p), "r"(x), "r"(y), "r"(z), "r"(w) : "memory");
}
__device__ __forceinline__ void st_b128(void* p, uint32_t x, uint32_t y, uint32_t z, uint32_t w) {
  asm volatile("{.reg .b128 t; .reg .b64 a,b; mov.b64 a,{%1,%2}; mov.b64 b,{%3,%4}; mov.b128 t,{a,b}; st.relaxed.gpu.b128 [%0],t;}" ::"l"(p), "r"(x), "r"(y), "r"(z), "r"(w) : "memory");
}
__device__ __forceinline__ void stg_rlx4(void* p, uint32_t x, uint32_t y, uint32_t z, uint32_t w) { asm volatile("st.relaxed.gpu.global.v4.u32 [%0],{%1,%2,%3,%4};" ::"l"(p), "r"(x), "r"(y), "r"(z), "r"(w) : "memory"); }
__device__ __forceinline__ void stg_rlx2(void* p, uint32_t x, uint32_t y) { asm volatile("st.relaxed.gpu.global.v2.u32 [%0],{%1,%2};" ::"l"(p), "r"(x), "r"(y) : "memory"); }
__device__ __forceinline__ void red4(void* p, float a, float b, float c, float d) { asm volatile("red.relaxed.gpu.global.add.v4.f32 [%0],{%1,%2,%3,%4};" ::"l"(p), "f"(a), "f"(b), "f"(c), "f"(d) : "memory"); }
__device__ __forceinline__ unsigned ld_acq(const unsigned* p) { unsigned v; asm volatile("ld.acquire.gpu.global.u32 %0,[%1];" : "=r"(v) : "l"(p) : "memory"); return v; }
__device__ __forceinline__ void red_rel(unsigned* p) { asm volatile("red.release.gpu.global.add.u32 [%0],1;" ::"l"(p) : "memory"); }
__device__ __forceinline__ void red_rlx(unsigned* p) { asm volatile("red.relaxed.gpu.global.add.u32 [%0],1;" ::"l"(p) : "memory"); }
__device__ __forceinline__ void wait_cnt(const unsigned* p, unsigned n) { int it = 0; while (ld_acq(p) < n) { if (++it > SPIN_LIMIT) __trap(); } }
__device__ __forceinline__ uint32_t clk() { uint32_t c; asm volatile("mov.u32 %0,%%clock;" : "=r"(c)); return c; }
__device__ __forceinline__ uint32_t gtime() { uint32_t c; asm volatile("mov.u32 %0,%%globaltimer_lo;" : "=r"(c)); return c; }
__device__ __forceinline__ void wait_until(uint32_t t0, uint32_t d) { while (clk() - t0 < d) {} }
__device__ __forceinline__ float ex2(float x) { float r; asm("ex2.approx.ftz.f32 %0,%1;" : "=f"(r) : "f"(x)); return r; }
__device__ __forceinline__ float silu(float x) { return x * __frcp_rn(1.f + __expf(-x)); }
__device__ __forceinline__ float rbf(float x) { return __bfloat162float(__float2bfloat16_rn(x)); }

__device__ __forceinline__ void wgmma_ss_n128(float* d, uint64_t a, uint64_t b, int sd) {
  asm volatile("{.reg .pred p; setp.ne.b32 p, %66, 0;\n"
    "wgmma.mma_async.sync.aligned.m64n128k16.f32.bf16.bf16 {%0,%1,%2,%3,%4,%5,%6,%7,%8,%9,%10,%11,%12,%13,%14,%15,%16,%17,%18,%19,%20,%21,%22,%23,%24,%25,%26,%27,%28,%29,%30,%31,%32,%33,%34,%35,%36,%37,%38,%39,%40,%41,%42,%43,%44,%45,%46,%47,%48,%49,%50,%51,%52,%53,%54,%55,%56,%57,%58,%59,%60,%61,%62,%63}, %64, %65, p, 1, 1, 0, 1;}\n"
    : "+f"(d[0]),"+f"(d[1]),"+f"(d[2]),"+f"(d[3]),"+f"(d[4]),"+f"(d[5]),"+f"(d[6]),"+f"(d[7]),
      "+f"(d[8]),"+f"(d[9]),"+f"(d[10]),"+f"(d[11]),"+f"(d[12]),"+f"(d[13]),"+f"(d[14]),"+f"(d[15]),
      "+f"(d[16]),"+f"(d[17]),"+f"(d[18]),"+f"(d[19]),"+f"(d[20]),"+f"(d[21]),"+f"(d[22]),"+f"(d[23]),
      "+f"(d[24]),"+f"(d[25]),"+f"(d[26]),"+f"(d[27]),"+f"(d[28]),"+f"(d[29]),"+f"(d[30]),"+f"(d[31]),
      "+f"(d[32]),"+f"(d[33]),"+f"(d[34]),"+f"(d[35]),"+f"(d[36]),"+f"(d[37]),"+f"(d[38]),"+f"(d[39]),
      "+f"(d[40]),"+f"(d[41]),"+f"(d[42]),"+f"(d[43]),"+f"(d[44]),"+f"(d[45]),"+f"(d[46]),"+f"(d[47]),
      "+f"(d[48]),"+f"(d[49]),"+f"(d[50]),"+f"(d[51]),"+f"(d[52]),"+f"(d[53]),"+f"(d[54]),"+f"(d[55]),
      "+f"(d[56]),"+f"(d[57]),"+f"(d[58]),"+f"(d[59]),"+f"(d[60]),"+f"(d[61]),"+f"(d[62]),"+f"(d[63])
    : "l"(a), "l"(b), "r"(sd));
}
__device__ __forceinline__ void wgmma_ss_n192(float* d, uint64_t a, uint64_t b, int sd) {
  asm volatile("{.reg .pred p; setp.ne.b32 p, %98, 0;\n"
    "wgmma.mma_async.sync.aligned.m64n192k16.f32.bf16.bf16 {%0,%1,%2,%3,%4,%5,%6,%7,%8,%9,%10,%11,%12,%13,%14,%15,%16,%17,%18,%19,%20,%21,%22,%23,%24,%25,%26,%27,%28,%29,%30,%31,%32,%33,%34,%35,%36,%37,%38,%39,%40,%41,%42,%43,%44,%45,%46,%47,%48,%49,%50,%51,%52,%53,%54,%55,%56,%57,%58,%59,%60,%61,%62,%63,%64,%65,%66,%67,%68,%69,%70,%71,%72,%73,%74,%75,%76,%77,%78,%79,%80,%81,%82,%83,%84,%85,%86,%87,%88,%89,%90,%91,%92,%93,%94,%95}, %96, %97, p, 1, 1, 0, 1;}\n"
    : "+f"(d[0]),"+f"(d[1]),"+f"(d[2]),"+f"(d[3]),"+f"(d[4]),"+f"(d[5]),"+f"(d[6]),"+f"(d[7]),
      "+f"(d[8]),"+f"(d[9]),"+f"(d[10]),"+f"(d[11]),"+f"(d[12]),"+f"(d[13]),"+f"(d[14]),"+f"(d[15]),
      "+f"(d[16]),"+f"(d[17]),"+f"(d[18]),"+f"(d[19]),"+f"(d[20]),"+f"(d[21]),"+f"(d[22]),"+f"(d[23]),
      "+f"(d[24]),"+f"(d[25]),"+f"(d[26]),"+f"(d[27]),"+f"(d[28]),"+f"(d[29]),"+f"(d[30]),"+f"(d[31]),
      "+f"(d[32]),"+f"(d[33]),"+f"(d[34]),"+f"(d[35]),"+f"(d[36]),"+f"(d[37]),"+f"(d[38]),"+f"(d[39]),
      "+f"(d[40]),"+f"(d[41]),"+f"(d[42]),"+f"(d[43]),"+f"(d[44]),"+f"(d[45]),"+f"(d[46]),"+f"(d[47]),
      "+f"(d[48]),"+f"(d[49]),"+f"(d[50]),"+f"(d[51]),"+f"(d[52]),"+f"(d[53]),"+f"(d[54]),"+f"(d[55]),
      "+f"(d[56]),"+f"(d[57]),"+f"(d[58]),"+f"(d[59]),"+f"(d[60]),"+f"(d[61]),"+f"(d[62]),"+f"(d[63]),
      "+f"(d[64]),"+f"(d[65]),"+f"(d[66]),"+f"(d[67]),"+f"(d[68]),"+f"(d[69]),"+f"(d[70]),"+f"(d[71]),
      "+f"(d[72]),"+f"(d[73]),"+f"(d[74]),"+f"(d[75]),"+f"(d[76]),"+f"(d[77]),"+f"(d[78]),"+f"(d[79]),
      "+f"(d[80]),"+f"(d[81]),"+f"(d[82]),"+f"(d[83]),"+f"(d[84]),"+f"(d[85]),"+f"(d[86]),"+f"(d[87]),
      "+f"(d[88]),"+f"(d[89]),"+f"(d[90]),"+f"(d[91]),"+f"(d[92]),"+f"(d[93]),"+f"(d[94]),"+f"(d[95])
    : "l"(a), "l"(b), "r"(sd));
}
__device__ __forceinline__ void wgmma_ss_n256(float* d, uint64_t a, uint64_t b, int sd) {
  asm volatile("{.reg .pred p; setp.ne.b32 p, %130, 0;\n"
    "wgmma.mma_async.sync.aligned.m64n256k16.f32.bf16.bf16 {%0,%1,%2,%3,%4,%5,%6,%7,%8,%9,%10,%11,%12,%13,%14,%15,%16,%17,%18,%19,%20,%21,%22,%23,%24,%25,%26,%27,%28,%29,%30,%31,%32,%33,%34,%35,%36,%37,%38,%39,%40,%41,%42,%43,%44,%45,%46,%47,%48,%49,%50,%51,%52,%53,%54,%55,%56,%57,%58,%59,%60,%61,%62,%63,%64,%65,%66,%67,%68,%69,%70,%71,%72,%73,%74,%75,%76,%77,%78,%79,%80,%81,%82,%83,%84,%85,%86,%87,%88,%89,%90,%91,%92,%93,%94,%95,%96,%97,%98,%99,%100,%101,%102,%103,%104,%105,%106,%107,%108,%109,%110,%111,%112,%113,%114,%115,%116,%117,%118,%119,%120,%121,%122,%123,%124,%125,%126,%127}, %128, %129, p, 1, 1, 0, 1;}\n"
    : "+f"(d[0]),"+f"(d[1]),"+f"(d[2]),"+f"(d[3]),"+f"(d[4]),"+f"(d[5]),"+f"(d[6]),"+f"(d[7]),
      "+f"(d[8]),"+f"(d[9]),"+f"(d[10]),"+f"(d[11]),"+f"(d[12]),"+f"(d[13]),"+f"(d[14]),"+f"(d[15]),
      "+f"(d[16]),"+f"(d[17]),"+f"(d[18]),"+f"(d[19]),"+f"(d[20]),"+f"(d[21]),"+f"(d[22]),"+f"(d[23]),
      "+f"(d[24]),"+f"(d[25]),"+f"(d[26]),"+f"(d[27]),"+f"(d[28]),"+f"(d[29]),"+f"(d[30]),"+f"(d[31]),
      "+f"(d[32]),"+f"(d[33]),"+f"(d[34]),"+f"(d[35]),"+f"(d[36]),"+f"(d[37]),"+f"(d[38]),"+f"(d[39]),
      "+f"(d[40]),"+f"(d[41]),"+f"(d[42]),"+f"(d[43]),"+f"(d[44]),"+f"(d[45]),"+f"(d[46]),"+f"(d[47]),
      "+f"(d[48]),"+f"(d[49]),"+f"(d[50]),"+f"(d[51]),"+f"(d[52]),"+f"(d[53]),"+f"(d[54]),"+f"(d[55]),
      "+f"(d[56]),"+f"(d[57]),"+f"(d[58]),"+f"(d[59]),"+f"(d[60]),"+f"(d[61]),"+f"(d[62]),"+f"(d[63]),
      "+f"(d[64]),"+f"(d[65]),"+f"(d[66]),"+f"(d[67]),"+f"(d[68]),"+f"(d[69]),"+f"(d[70]),"+f"(d[71]),
      "+f"(d[72]),"+f"(d[73]),"+f"(d[74]),"+f"(d[75]),"+f"(d[76]),"+f"(d[77]),"+f"(d[78]),"+f"(d[79]),
      "+f"(d[80]),"+f"(d[81]),"+f"(d[82]),"+f"(d[83]),"+f"(d[84]),"+f"(d[85]),"+f"(d[86]),"+f"(d[87]),
      "+f"(d[88]),"+f"(d[89]),"+f"(d[90]),"+f"(d[91]),"+f"(d[92]),"+f"(d[93]),"+f"(d[94]),"+f"(d[95]),
      "+f"(d[96]),"+f"(d[97]),"+f"(d[98]),"+f"(d[99]),"+f"(d[100]),"+f"(d[101]),"+f"(d[102]),"+f"(d[103]),
      "+f"(d[104]),"+f"(d[105]),"+f"(d[106]),"+f"(d[107]),"+f"(d[108]),"+f"(d[109]),"+f"(d[110]),"+f"(d[111]),
      "+f"(d[112]),"+f"(d[113]),"+f"(d[114]),"+f"(d[115]),"+f"(d[116]),"+f"(d[117]),"+f"(d[118]),"+f"(d[119]),
      "+f"(d[120]),"+f"(d[121]),"+f"(d[122]),"+f"(d[123]),"+f"(d[124]),"+f"(d[125]),"+f"(d[126]),"+f"(d[127])
    : "l"(a), "l"(b), "r"(sd));
}
__device__ __forceinline__ void wgmma_rs_n32(float* d, const uint32_t* a, uint64_t b, int sd) {
  asm volatile("{.reg .pred p; setp.ne.b32 p, %21, 0;\n"
    "wgmma.mma_async.sync.aligned.m64n32k16.f32.bf16.bf16 {%0,%1,%2,%3,%4,%5,%6,%7,%8,%9,%10,%11,%12,%13,%14,%15}, {%16,%17,%18,%19}, %20, p, 1, 1, 0;}\n"
    : "+f"(d[0]),"+f"(d[1]),"+f"(d[2]),"+f"(d[3]),"+f"(d[4]),"+f"(d[5]),"+f"(d[6]),"+f"(d[7]),
      "+f"(d[8]),"+f"(d[9]),"+f"(d[10]),"+f"(d[11]),"+f"(d[12]),"+f"(d[13]),"+f"(d[14]),"+f"(d[15])
    : "r"(a[0]), "r"(a[1]), "r"(a[2]), "r"(a[3]), "l"(b), "r"(sd));
}
__device__ __forceinline__ void wgmma_ssT_n32(float* d, uint64_t a, uint64_t b, int sd) {
  asm volatile("{.reg .pred p; setp.ne.b32 p, %18, 0;\n"
    "wgmma.mma_async.sync.aligned.m64n32k16.f32.bf16.bf16 {%0,%1,%2,%3,%4,%5,%6,%7,%8,%9,%10,%11,%12,%13,%14,%15}, %16, %17, p, 1, 1, 1, 0;}\n"
    : "+f"(d[0]),"+f"(d[1]),"+f"(d[2]),"+f"(d[3]),"+f"(d[4]),"+f"(d[5]),"+f"(d[6]),"+f"(d[7]),
      "+f"(d[8]),"+f"(d[9]),"+f"(d[10]),"+f"(d[11]),"+f"(d[12]),"+f"(d[13]),"+f"(d[14]),"+f"(d[15])
    : "l"(a), "l"(b), "r"(sd));
}

__device__ __forceinline__ void wgmma_rs_n32_z(float* d, const uint32_t* a, uint64_t b) {
  asm volatile("{.reg .pred p; setp.ne.b32 p, 0, 0;\n"
    "wgmma.mma_async.sync.aligned.m64n32k16.f32.bf16.bf16 {%0,%1,%2,%3,%4,%5,%6,%7,%8,%9,%10,%11,%12,%13,%14,%15}, {%16,%17,%18,%19}, %20, p, 1, 1, 0;}\n"
    : "=f"(d[0]),"=f"(d[1]),"=f"(d[2]),"=f"(d[3]),"=f"(d[4]),"=f"(d[5]),"=f"(d[6]),"=f"(d[7]),
      "=f"(d[8]),"=f"(d[9]),"=f"(d[10]),"=f"(d[11]),"=f"(d[12]),"=f"(d[13]),"=f"(d[14]),"=f"(d[15])
    : "r"(a[0]), "r"(a[1]), "r"(a[2]), "r"(a[3]), "l"(b));
}

namespace rec {
constexpr int NVR = P_NVR;
constexpr int NVS = 16 - NVR;
constexpr int NVP = P_NVP;
constexpr int NWP = P_NWP;
constexpr uint32_t WO = 0;
constexpr uint32_t XB = 65536;
constexpr uint32_t PK = XB + 32768;
constexpr uint32_t VN = PK + 24576;
constexpr uint32_t VX0 = VN + 4096;
constexpr uint32_t WVS = 131072;
constexpr uint32_t MEM = WVS + 2 * NVS * 2048;
constexpr uint32_t ARO = MEM + 10240;
constexpr uint32_t OB = ARO + 5120;
constexpr uint32_t QT = OB + 2048;
constexpr uint32_t KT = QT + 2048;
constexpr uint32_t RQ = KT + 6144;
constexpr uint32_t RK = RQ + 2048;
constexpr uint32_t SC = RK + 2048;
constexpr uint32_t OT = OB;
constexpr uint32_t TF = SC + 2048;
constexpr uint32_t PRE = MEM + 2 * NVR * 2048;
constexpr uint32_t TA = TF + 8192;
constexpr uint32_t RX = TA + 6144;
constexpr uint32_t VX1 = RX + 2048;
constexpr uint32_t BARS = VX1 + 4096;
constexpr uint32_t PACE = BARS + 18 * 8;
constexpr uint32_t SMEM = BARS + 512;
static_assert(PRE + 14336 <= BARS, "staging");
constexpr int NW1 = P_NW1;
static_assert(SMEM <= 232448, "smem");
constexpr int B_E = 2, B_SC = 3, B_S = 4, B_O = 5, B_F = 6, B_W = 7, B_C = 9, B_K = 10, B_H = 15, B_Q = 1, B_S2 = 6, B_T2 = 9, B_P = 13, B_T = 14, B_R = 11, B_X = 12, B_V = 8;
constexpr int XC = 16384, X_RING = 131072, X_PT = 4096, X_SC = 65536, X_TOK = 4096;
#define X_VX(i) (((i) >> 1) * 2048 + ((i) & 1) * 512)
#define X_VM(i) (X_VX(i) + 1024)
}
struct RecMaps { CUtensorMap wq, wk, wv, wo, ari; int zero[40]; };

#define F_(x) __uint_as_float(x)
#define U_(x) __float_as_uint(x)
__device__ __forceinline__ void ar_fetch(uint32_t dst, const CUtensorMap* m, int slot, int half, uint32_t mb) {
  asm volatile("{.reg .pred p; elect.sync _|p, 0xffffffff; @p mbarrier.arrive.expect_tx.shared.b64 _,[%4],10240;\n"
               "@p cp.async.bulk.tensor.2d.shared::cluster.global.mbarrier::complete_tx::bytes [%0],[%1,{%2,%3}],[%4];\n"
               "@p cp.async.bulk.tensor.2d.shared::cluster.global.mbarrier::complete_tx::bytes [%0+5120],[%1,{%2,%5}],[%4];}"
               ::"r"(dst), "l"(m), "r"(slot * 64), "r"(half * 80), "r"(mb), "r"(half * 80 + 40) : "memory");
}
__device__ __forceinline__ void ar_fetch1(uint32_t dst, const CUtensorMap* m, int slot, int quarter, uint32_t mb) {
  asm volatile("{.reg .pred p; elect.sync _|p, 0xffffffff; @p mbarrier.arrive.expect_tx.shared.b64 _,[%4],5120;\n"
               "@p cp.async.bulk.tensor.2d.shared::cluster.global.mbarrier::complete_tx::bytes [%0],[%1,{%2,%3}],[%4];}"
               ::"r"(dst), "l"(m), "r"(slot * 64), "r"(quarter * 40), "r"(mb) : "memory");
}
__device__ __forceinline__ uint4 exch_b128(void* p, uint32_t x, uint32_t y, uint32_t z, uint32_t w) {
  uint4 v;
  asm volatile("{.reg .b128 s, t; .reg .b64 a,b; mov.b64 a,{%5,%6}; mov.b64 b,{%7,%8}; mov.b128 s,{a,b}; atom.relaxed.gpu.global.exch.b128 t,[%4],s;"
               " mov.b128 {a,b},t; mov.b64 {%0,%1},a; mov.b64 {%2,%3},b;}" : "=r"(v.x), "=r"(v.y), "=r"(v.z), "=r"(v.w) : "l"(p), "r"(x), "r"(y), "r"(z), "r"(w) : "memory");
  return v;
}
#define CONSUME(v) do { if ((v) == 0x7fc12345u) sts1(sb + rec::BARS + 96, 0); } while (0)
__device__ __forceinline__ uint32_t tagf(float v, uint32_t tag) { return (__float_as_uint(v) & ~1u) | tag; }
__device__ __forceinline__ uint2 ldg_b64(const void* p) { uint2 v; asm volatile("{.reg .b64 t; ld.relaxed.gpu.global.b64 t,[%2]; mov.b64 {%0,%1},t;}" : "=r"(v.x), "=r"(v.y) : "l"(p) : "memory"); return v; }
__device__ __forceinline__ void stg_b64(void* p, uint32_t x, uint32_t y) { asm volatile("{.reg .b64 t; mov.b64 t,{%1,%2}; st.relaxed.gpu.global.b64 [%0],t;}" ::"l"(p), "r"(x), "r"(y) : "memory"); }
__device__ __forceinline__ uint32_t tagbad(uint32_t x, uint32_t y, uint32_t tag) { uint32_t r; asm("lop3.b32 %0,%1,%2,%3,0x7e;" : "=r"(r) : "r"(x), "r"(y), "r"(tag)); return r; }

__device__ __forceinline__ bool anybad(uint32_t a, uint32_t b, uint32_t c, uint32_t d, uint32_t e, uint32_t f, uint32_t g, uint32_t h, uint32_t tag) {
  uint32_t r;
  asm volatile("{.reg .b32 t,u,v,w; .reg .pred p; lop3.b32 t,%1,%2,%9,0x7e; lop3.b32 u,%3,%4,%9,0x7e; lop3.b32 v,%5,%6,%9,0x7e; lop3.b32 w,%7,%8,%9,0x7e;"
               " lop3.b32 t,t,u,v,0xfe; lop3.b32 t,t,w,1,0xa8; setp.ne.u32 p,t,0; vote.sync.any.pred p,p,0xffffffff; selp.u32 %0,1,0,p;}"
               : "=r"(r) : "r"(a), "r"(b), "r"(c), "r"(d), "r"(e), "r"(f), "r"(g), "r"(h), "r"(tag));
  return r;
}
__device__ __forceinline__ bool anybad(uint32_t a, uint32_t b, uint32_t c, uint32_t d, uint32_t tag) {
  uint32_t r;
  asm volatile("{.reg .b32 t,u; .reg .pred p; lop3.b32 t,%1,%2,%5,0x7e; lop3.b32 u,%3,%4,%5,0x7e;"
               " lop3.b32 t,t,u,1,0xa8; setp.ne.u32 p,t,0; vote.sync.any.pred p,p,0xffffffff; selp.u32 %0,1,0,p;}"
               : "=r"(r) : "r"(a), "r"(b), "r"(c), "r"(d), "r"(tag));
  return r;
}
#define BAD8(r) anybad(r[0].x, r[0].z, r[1].x, r[1].z, r[2].x, r[2].z, r[3].x, r[3].z, tag)
#define BADS(r) anybad(r[0].x, r[0].y, r[1].x, r[1].y, r[2].x, r[2].y, r[3].x, r[3].y, tag)
constexpr float SCS = 0.08838834764831845f * 1.4426950408889634f / 16.f;
__device__ __forceinline__ uint32_t pkh(float lo, float hi, uint32_t tag) {
  uint32_t r;
  asm("{.reg .b32 t; cvt.rn.satfinite.f16x2.f32 t,%1,%2; lop3.b32 %0,t,0xfffffffe,%3,0xea;}" : "=r"(r) : "f"(hi), "f"(lo), "r"(tag));
  return r;
}
__device__ __forceinline__ uint32_t addh(uint32_t a, uint32_t b) { uint32_t r; asm("add.rn.f16x2 %0,%1,%2;" : "=r"(r) : "r"(a), "r"(b)); return r; }
__device__ __forceinline__ float hlo(uint32_t v) { float r; asm("{.reg .b16 a,b; mov.b32 {a,b},%1; cvt.f32.f16 %0,a;}" : "=f"(r) : "r"(v)); return r; }
__device__ __forceinline__ float hhi(uint32_t v) { float r; asm("{.reg .b16 a,b; mov.b32 {a,b},%1; cvt.f32.f16 %0,b;}" : "=f"(r) : "r"(v)); return r; }
__device__ __forceinline__ uint32_t ordh(uint32_t v) {
  uint32_t r;
  asm("{.reg .b32 m; prmt.b32 m,%1,0,0xbb99; lop3.b32 %0,%1,m,0x7fff7fff,0x78;}" : "=r"(r) : "r"(v));
  return r;
}
template <bool MASK>
__device__ __forceinline__ float4 softmax2(const uint2 (&r)[4], uint32_t mx, uint32_t my) {
  uint32_t x = addh(addh(r[0].x, r[1].x), addh(r[2].x, r[3].x)), y = addh(addh(r[0].y, r[1].y), addh(r[2].y, r[3].y)), k;
  if (MASK) x = addh(x, mx);
  y = addh(y, my);
  asm("max.f16x2 %0,%1,%2;" : "=r"(k) : "r"(x), "r"(y));
  k = ordh(k);
  const int k0 = __reduce_max_sync(~0u, (int)(k << 16)), k1 = __reduce_max_sync(~0u, (int)k);
  k = ordh(__byte_perm(k0, k1, 0x7632));
  const float m0 = hlo(k) * -16.f, m1 = hhi(k) * -16.f;
  return make_float4(ex2(fmaf(hlo(x), 16.f, m0)), ex2(fmaf(hhi(x), 16.f, m1)), ex2(fmaf(hlo(y), 16.f, m0)), ex2(fmaf(hhi(y), 16.f, m1)));
}
__device__ __forceinline__ char* mkp(uint32_t lo, uint32_t hi) { uint64_t r; asm("mov.b64 %0,{%1,%2};" : "=l"(r) : "r"(lo), "r"(hi)); return (char*)r; }
#define LO(p) ((uint32_t)(uint64_t)(p))
#define HI(p) ((uint32_t)((uint64_t)(p) >> 32))
__device__ __forceinline__ void cp16(uint32_t dst, const void* src) { asm volatile("cp.async.cg.shared.global [%0],[%1],16;" ::"r"(dst), "l"(src) : "memory"); }
__device__ __forceinline__ uint32_t xor3(uint32_t a, uint32_t b, uint32_t c) { uint32_t r; asm volatile("lop3.b32 %0,%1,%2,%3,0x96;" : "=r"(r) : "r"(a), "r"(b), "r"(c)); return r; }
__device__ __forceinline__ uint32_t mulbf(uint32_t a, uint32_t b) { uint32_t r; asm("mul.rn.bf16x2 %0,%1,%2;" : "=r"(r) : "r"(a), "r"(b)); return r; }
__device__ __forceinline__ uint32_t addbf(uint32_t a, uint32_t b) { uint32_t r; asm("add.rn.bf16x2 %0,%1,%2;" : "=r"(r) : "r"(a), "r"(b)); return r; }
__device__ __forceinline__ void pv_mem(const uint32_t (&p)[4], uint32_t pm, const uint4 (&v)[4], const uint4 (&vn)[2], uint32_t (&O)[4]) {
  float o[4][4] = {{0, 0, 0, 0}, {0, 0, 0, 0}, {0, 0, 0, 0}, {0, 0, 0, 0}};
  mma16(o[0], v[0].x, v[0].y, v[0].z, v[0].w, p[0], p[1]);
  mma16(o[1], v[2].x, v[2].y, v[2].z, v[2].w, p[0], p[1]);
  mma16(o[2], v[1].x, v[1].y, v[1].z, v[1].w, p[2], p[3]);
  mma16(o[3], v[3].x, v[3].y, v[3].z, v[3].w, p[2], p[3]);
  mma16(o[0], vn[0].x, vn[0].y, vn[0].z, vn[0].w, pm, pm);
  mma16(o[1], vn[1].x, vn[1].y, vn[1].z, vn[1].w, pm, pm);
  O[0] = pk(o[0][0] + o[2][0], o[0][1] + o[2][1]); O[1] = pk(o[0][2] + o[2][2], o[0][3] + o[2][3]);
  O[2] = pk(o[1][0] + o[3][0], o[1][1] + o[3][1]); O[3] = pk(o[1][2] + o[3][2], o[1][3] + o[3][3]);
}
__device__ __forceinline__ void pv_tok(const uint32_t (&p)[4], uint32_t pm, const uint4 (&v)[4], const uint32_t (&vm)[4], uint32_t (&O)[4]) {
  float o[2][4] = {{0, 0, 0, 0}, {0, 0, 0, 0}}, sum[4] = {0, 0, 0, 0};
  const uint32_t one = 0x3f803f80u;
  mma16(sum, one, one, one, one, p[0], p[1]);
  mma16(o[0], v[0].x, v[0].y, v[0].z, v[0].w, p[0], p[1]);
  mma16(o[1], v[2].x, v[2].y, v[2].z, v[2].w, p[0], p[1]);
  mma16(sum, one, one, one, one, p[2], p[3]);
  mma16(o[0], v[1].x, v[1].y, v[1].z, v[1].w, p[2], p[3]);
  mma16(o[1], v[3].x, v[3].y, v[3].z, v[3].w, p[2], p[3]);
  mma8(sum, one, one, pm);
  mma8(o[0], vm[0], vm[1], pm);
  mma8(o[1], vm[2], vm[3], pm);
  float i0, i1;
  asm("rcp.approx.ftz.f32 %0,%1;" : "=f"(i0) : "f"(sum[0]));
  asm("rcp.approx.ftz.f32 %0,%1;" : "=f"(i1) : "f"(sum[1]));
  O[0] = pk(o[0][0] * i0, o[0][1] * i1); O[1] = pk(o[0][2] * i0, o[0][3] * i1);
  O[2] = pk(o[1][0] * i0, o[1][1] * i1); O[3] = pk(o[1][2] * i0, o[1][3] * i1);
}
__device__ __forceinline__ uint32_t sum4bf(uint32_t a, uint32_t b, uint32_t c, uint32_t d) { return addbf(addbf(a, b), addbf(c, d)); }
template <int OFF>
__device__ __forceinline__ void sta1(uint32_t a, uint32_t v, uint32_t mb) {
  asm volatile("st.async.shared::cluster.mbarrier::complete_tx::bytes.b32 [%0+%3],%1,[%2];" ::"r"(a), "r"(v), "r"(mb), "n"(OFF) : "memory");
}

__device__ __forceinline__ void rec_helper(char* smem, const bf16* cvec, const bf16* wmod, const char* w1, const bf16* b1, const char* x, const char* wo) {
  const int tid = threadIdx.x, hb = blockIdx.x - 128;
  const uint32_t t0 = gtime();
  float* sc = (float*)smem;
  float* red = sc + 1024;
  for (int i = tid; i < 1024; i += 256) { const float v = __bfloat162float(cvec[i]); sc[i] = rbf(silu(v)); }
  for (int i = tid; i < 2048; i += 256) g_stat[hb * 2048 + i] = make_uint4(~0u, ~0u, ~0u, ~0u);
  for (int i = tid; i < 512; i += 256) g_cnt[hb * 512 + i] = 0;
  if (tid == 0) {
    wait_cnt(&g_hcnt, 128);
    if (HP)
      for (int r = 0; r < 1024; r++) {
        asm volatile("cp.async.bulk.prefetch.L2.global [%0], 2048;" ::"l"(wmod + (size_t)r * 6144 + 2048 + hb * 1024) : "memory");
        if ((r & 7) == 7) __nanosleep(250);
      }
  }
  BAR_SYNC(rec::B_F, 256);
  const int rg = tid >> 7, cg = tid & 127;
  float acc[8] = {0, 0, 0, 0, 0, 0, 0, 0};
  const uint4* p = (const uint4*)(wmod + 2048 + hb * 1024) + cg;
#pragma unroll 1
  for (int r0 = 0; r0 < 1024; r0 += 2 * HU) {
    __nanosleep(HS);
#pragma unroll
  for (int r = r0 + rg; r < r0 + 2 * HU; r += 2) {
    const uint4 v = HP == 2 ? __ldcg(p + (size_t)r * 768) : __ldcs(p + (size_t)r * 768);
    const float f = sc[r];
    acc[0] += f * blo(v.x); acc[1] += f * bhi(v.x); acc[2] += f * blo(v.y); acc[3] += f * bhi(v.y);
    acc[4] += f * blo(v.z); acc[5] += f * bhi(v.z); acc[6] += f * blo(v.w); acc[7] += f * bhi(v.w);
  }
  }
#pragma unroll
  for (int i = 0; i < 8; i++) red[rg * 1024 + cg * 8 + i] = acc[i];
  BAR_SYNC(rec::B_F, 256);
  for (int i = tid; i < 1024; i += 256) g_mod[2048 + hb * 1024 + i] = rbf(red[i] + red[1024 + i]);
  BAR_SYNC(rec::B_F, 256);
  if (tid == 0) {
    red_rel(&g_mcnt);
    for (int r = 0; r < 1024; r++) {
      asm volatile("cp.async.bulk.prefetch.L2.global [%0], 1792;" ::"l"(w1 + (size_t)r * 7168 + hb * 1792) : "memory");
      if ((r & 7) == 7) __nanosleep(250);
    }
    wait_cnt(&g_mcnt, 4);
  }
  BAR_SYNC(rec::B_F, 256);
  float2* m2 = (float2*)smem;
  for (int i = tid; i < 1024; i += 256) m2[i] = make_float2(rbf(1.f + __ldcg(g_mod + 4096 + i)), __ldcg(g_mod + 3072 + i));
  BAR_SYNC(rec::B_F, 256);
  float* rd = (float*)(smem + 8192);
  if (tid < 224) {
    const int r2 = tid >= 112, c2 = tid - r2 * 112;
    float a1[8] = {0, 0, 0, 0, 0, 0, 0, 0}, a2[8] = {0, 0, 0, 0, 0, 0, 0, 0};
    const uint4* q = (const uint4*)(w1 + hb * 1792) + c2;
#pragma unroll 1
    for (int r0 = 0; r0 < 1024; r0 += 32) {
      __nanosleep(HS);
#pragma unroll
      for (int r = r0 + r2; r < r0 + 32; r += 2) {
        const uint4 v = __ldcg(q + (size_t)r * 448);
        const float2 f = m2[r];
        const float w[8] = {blo(v.x), bhi(v.x), blo(v.y), bhi(v.y), blo(v.z), bhi(v.z), blo(v.w), bhi(v.w)};
#pragma unroll
        for (int i = 0; i < 8; i++) { a1[i] += f.x * w[i]; a2[i] += f.y * w[i]; }
      }
    }
#pragma unroll
    for (int i = 0; i < 8; i++) { rd[r2 * 1792 + c2 * 8 + i] = a1[i]; rd[r2 * 1792 + 896 + c2 * 8 + i] = a2[i]; }
  }
  BAR_SYNC(rec::B_F, 256);
  for (int i = tid; i < 448; i += 256) {
    const int n = i * 2, gn = hb * 896 + n;
    const uint32_t bb = *(const uint32_t*)(b1 + gn);
    ((uint2*)g_cc)[(gn >> 4) * 8 + ((gn >> 1) & 3) * 2 + ((gn >> 3) & 1)] =
        make_uint2(pk(rd[n] + rd[1792 + n], rd[n + 1] + rd[1793 + n]), pk(0.5f * (rd[896 + n] + rd[2688 + n] + blo(bb)), 0.5f * (rd[897 + n] + rd[2689 + n] + bhi(bb))));
  }
  if (tid == 0 && PFT) {
    asm volatile("griddepcontrol.launch_dependents;");
    while (gtime() - t0 < PFT) __nanosleep(1000);
    for (int r = 0; r < 1536; r++) {
      asm volatile("cp.async.bulk.prefetch.L2.global [%0], 2048;" ::"l"(r < 512 ? x + (hb * 512 + r) * 2048 : wo + ((1535 - r) * 4 + hb) * 2048) : "memory");
      if ((r & 7) == 7) { __nanosleep(PFS); if (ldg_rlx1(&g_fin)) break; }
    }
  }
}

__global__ void __cluster_dims__(2, 1, 1) __launch_bounds__(512, 1)
k_rec(const __grid_constant__ RecMaps mp, const bf16* __restrict__ mem0, const bf16* __restrict__ x, const bf16* __restrict__ cvec,
      const bf16* __restrict__ wmod, const char* __restrict__ w1, const bf16* __restrict__ b1, const char* __restrict__ wo, char* xc, int dF, int dA, int dS, int dM, int dG, int dP, int dX, int dD, int dZ, int dZ2, int dV, int dX2) {
  using namespace rec;
  extern __shared__ __align__(1024) char smem[];
  const uint32_t sb = (uint32_t)__cvta_generic_to_shared(smem);
  if ((sb & 0x3FFFF) != 1024) __trap();
  PH(0);
  if (threadIdx.x == 0) {
    int b = blockIdx.x;
    if (b >= 8 && b < 128) {
      const int t = (b >> 1) - 4, u = t - 32;
      b = 2 * (t < 32 ? 4 + (t & 16) + (t & 7) * 2 + ((t >> 3) & 1) : 36 + (u / 14) * 14 + (u % 7) * 2 + ((u / 7) & 1)) + (b & 1);
    }
    sts1(sb + rec::PACE + 24, b);
    const int c = blockIdx.x >> 1, l = c < 36 ? (c - 4) & 7 : (c - 36) % 7, m = c < 4 ? c : c < 36 ? (c - 4) >> 3 : (c - 36) / 7;
    const int g = c < 4 ? 15 : (l >> 1) * 4 + (l & 1) + (c < 36 ? 0 : 2);
    unsigned sm;
    asm("mov.u32 %0,%%smid;" : "=r"(sm));
    if (c < 64) g_slot[sm & 255] = 1 + FMAP;
  }
#define ROLE_REFRESH { asm volatile("mov.u32 %0,%%tid.x;" : "=r"(tid)); wid = __shfl_sync(~0u, tid >> 5, 0); b = __shfl_sync(~0u, lds1(sb + PACE + 24), 0); }
#define ROLE_VARS int tid; asm volatile("mov.u32 %0,%%tid.x;" : "=r"(tid)); \
    int wid = __shfl_sync(~0u, tid >> 5, 0), b = __shfl_sync(~0u, lds1(sb + PACE + 24), 0);
#define wg (wid >> 2)
#define iw (wid & 3)
#define h (b >> 2)
#define j (b & 3)
#define a (b & 1)
#define bb ((b >> 1) & 1)
  const uint32_t wbar = sb + BARS + 48, obar = wbar + 8;
  if (threadIdx.x == 256) {
    for (int i = 0; i < 18; i++) if (i != 12) mbar_init(sb + BARS + i * 8, i == 3 || i == 8 || i == 9 || i == 10 ? 2 : 1);
    for (int i = 0; i < 3; i++) mbar_init(sb + PACE + i * 8, 1);
    asm volatile("fence.mbarrier_init.release.cluster;" ::: "memory");
    FENCE_ASYNC_SMEM();
    mbar_expect(sb + BARS, 2048);
    mbar_expect(sb + BARS + 16, 4096);
    mbar_expect(sb + BARS + 32, 4096);
    mbar_expect(sb + BARS + 40, 4096);
  }
  __syncthreads();
#define lane ((int)(l16 >> 4))
#define l16 (L16 & 0x1f0)
#define is7 ((L16 & 112) == 112)
#define PIN(x) __shfl_xor_sync(~0u, (uint32_t)(x), 0)
#define REFRESH() L16 = __shfl_xor_sync(~0u, L16, 0)
#define lar ((L16 & 0x180) * 8 + (L16 & 0x70))
#define X_LOAD(n, w, u) \
        asm volatile("{.reg .pred p; elect.sync _|p, 0xffffffff; @p mbarrier.arrive.expect_tx.shared.b64 _,[%2],8192;\n" \
                     "@p cp.async.bulk.shared::cluster.global.mbarrier::complete_tx::bytes [%0],[%1],8192,[%2];}" ::"r"(sb + XB + (w) * 16384 + (u) * 8192), \
                     "l"(g_h + (n) * 4096 + a * 2048 + (w) * 1024 + (u) * 512), "r"(sb + BARS + 64 + (w) * 8) : "memory")
#define lpub ((L16 & 0x30) * 64 + ((L16 >> 3) & 0x38))
#define lrow ((L16 & 0x70) + (((L16 >> 3) ^ L16) & 0x70 & ~((L16 >> 3) & 0x40) ? L16 & 0x180 : 512))

  const int role = __shfl_sync(~0u, threadIdx.x >> 7, 0);
  if (role < 2) {
    asm volatile("setmaxnreg.inc.sync.aligned.u32 %0;" ::"n"(RF_));
    if (blockIdx.x >= 128) { rec_helper(smem, cvec, wmod, w1, b1, (const char*)x, wo); return; }
    ROLE_VARS
    uint32_t L16 = __shfl_sync(~0u, sb + (tid & 31) * 16, tid & 31);
    {
      uint4 wm[8], xr[8];
      const uint4* pw = (const uint4*)(wmod + (size_t)((b >> 5) * 256 + (tid >> 3)) * 6144 + (b & 31) * 64) + (tid & 7);
      const float cs = __bfloat162float(cvec[(b >> 5) * 256 + tid]);
#pragma unroll
      for (int i = 0; i < 8; i++) wm[i] = __ldcs(pw + (size_t)i * 32 * 768);
#pragma unroll
      for (int i = 0; i < 8; i++) xr[i] = __ldg((const uint4*)(x + (size_t)(b * 16 + (tid >> 5) * 2) * 1024) + i * 32 + (tid & 31));
      float* sc = (float*)(smem + PRE);
      sc[tid] = rbf(silu(cs));
      if (tid < 80) g_ar[b * 80 + tid] = make_uint4(0, 0, 0, 0);
      if (tid == 80 && b == 0) g_fin = 0;
      BAR_SYNC(B_F, 256);
      float acc[8] = {0, 0, 0, 0, 0, 0, 0, 0};
#pragma unroll
      for (int i = 0; i < 8; i++) {
        const float f = sc[i * 32 + (tid >> 3)];
        acc[0] += f * blo(wm[i].x); acc[1] += f * bhi(wm[i].x); acc[2] += f * blo(wm[i].y); acc[3] += f * bhi(wm[i].y);
        acc[4] += f * blo(wm[i].z); acc[5] += f * bhi(wm[i].z); acc[6] += f * blo(wm[i].w); acc[7] += f * bhi(wm[i].w);
      }
#pragma unroll
      for (int i = 0; i < 8; i++) { acc[i] += __shfl_xor_sync(~0u, acc[i], 8); acc[i] += __shfl_xor_sync(~0u, acc[i], 16); }
      float* red = sc + 1024;
      if ((tid & 31) < 8) {
#pragma unroll
        for (int i = 0; i < 8; i++) red[(tid >> 5) * 64 + (tid & 7) * 8 + i] = acc[i];
      }
      BAR_SYNC(B_F, 256);
      if (tid < 64) {
        float t = 0;
#pragma unroll
        for (int i = 0; i < 8; i++) t += red[i * 64 + tid];
        asm volatile("st.relaxed.gpu.global.u32 [%0],%1;" ::"l"((unsigned*)g_modp + (b >> 5) * 2048 + (b & 31) * 64 + tid), "r"(U_(t) | 1u) : "memory");
      }
      float v[2][32], rstd[2];
#pragma unroll
      for (int r = 0; r < 2; r++) {
        float t = 0, q = 0;
#pragma unroll
        for (int i = 0; i < 4; i++) {
          const uint4 u = xr[r * 4 + i];
          float* w = v[r] + i * 8;
          w[0] = blo(u.x); w[1] = bhi(u.x); w[2] = blo(u.y); w[3] = bhi(u.y); w[4] = blo(u.z); w[5] = bhi(u.z); w[6] = blo(u.w); w[7] = bhi(u.w);
        }
#pragma unroll
        for (int i = 0; i < 32; i++) t += v[r][i];
#pragma unroll
        for (int o = 16; o; o >>= 1) t += __shfl_xor_sync(~0u, t, o);
        t *= 1.f / 1024;
#pragma unroll
        for (int i = 0; i < 32; i++) { v[r][i] -= t; q += v[r][i] * v[r][i]; }
#pragma unroll
        for (int o = 16; o; o >>= 1) q += __shfl_xor_sync(~0u, q, o);
        rstd[r] = rsqrtf(q * (1.f / 1024) + 1e-5f);
      }
      float4* md = (float4*)(sc + 1536);
#pragma unroll
      for (int i = 0; i < 2; i++) {
        uint4 p[4];
        int it = 0;
        while (true) {
#pragma unroll
          for (int u = 0; u < 4; u++) p[u] = ldg_rlx4(g_modp + u * 512 + i * 256 + tid);
          uint32_t ok = 1;
#pragma unroll
          for (int u = 0; u < 4; u++) ok &= p[u].x & p[u].y & p[u].z & p[u].w;
          if (__all_sync(~0u, ok)) break;
          if (++it > SPIN_LIMIT) __trap();
          __nanosleep(100);
        }
        md[i * 256 + tid] = make_float4(i + rbf((F_(p[0].x) + F_(p[1].x)) + (F_(p[2].x) + F_(p[3].x))), i + rbf((F_(p[0].y) + F_(p[1].y)) + (F_(p[2].y) + F_(p[3].y))),
                                        i + rbf((F_(p[0].z) + F_(p[1].z)) + (F_(p[2].z) + F_(p[3].z))), i + rbf((F_(p[0].w) + F_(p[1].w)) + (F_(p[2].w) + F_(p[3].w))));
      }
      BAR_SYNC(B_F, 256);
#pragma unroll
      for (int i = 0; i < 4; i++) {
        const int ch = i * 32 + (tid & 31);
        const float4 s0 = md[ch * 2], s1 = md[ch * 2 + 1], c0 = md[256 + ch * 2], c1 = md[256 + ch * 2 + 1];
#pragma unroll
        for (int r = 0; r < 2; r++) {
          const int row = b * 16 + (tid >> 5) * 2 + r;
          const float* w = v[r] + i * 8;
          g_h[((row >> 5) * 16 + (ch >> 3)) * 256 + (row & 31) * 8 + ((ch & 7) ^ (row & 7))] =
              make_uint4(pk(w[0] * rstd[r] * c0.x + s0.x, w[1] * rstd[r] * c0.y + s0.y), pk(w[2] * rstd[r] * c0.z + s0.z, w[3] * rstd[r] * c0.w + s0.w),
                         pk(w[4] * rstd[r] * c1.x + s1.x, w[5] * rstd[r] * c1.y + s1.y), pk(w[6] * rstd[r] * c1.z + s1.z, w[7] * rstd[r] * c1.w + s1.w));
        }
      }
      FENCE_ASYNC();
      BAR_SYNC(B_F, 256);
      if (tid == 0) red_rel(&g_hcnt);
      PH(1);
    }
    uint32_t m0[2][4];
#pragma unroll
    for (int i = 0; i < 2; i++)
#pragma unroll
      for (int r = 0; r < 4; r++)
        m0[i][r] = (uint32_t)__bfloat16_as_ushort(mem0[(2 * r) * 1024 + a * 512 + tid * 2 + i]) | ((uint32_t)__bfloat16_as_ushort(mem0[(2 * r + 1) * 1024 + a * 512 + tid * 2 + i]) << 16);
    if (iw == 0) { wait_cnt(&g_hcnt, 128); FENCE_ASYNC(); }
    __syncwarp();
    PH(2);
    ROLE_REFRESH
    uint32_t wQ[16][4], wK[16][4], wV[NVR][4];
    uint32_t frag = sb + ((lane & 7) + (lane >> 4) * 8) * 128 + (((iw * 2 + ((lane >> 3) & 1)) ^ (lane & 7)) << 4);
    mbar_wait(wbar, 0);
#pragma unroll
    for (int i = 0; i < 16; i++) { ldsm4t(wQ[i], frag + WO + wg * 32768 + i * 2048); ldsm4t(wK[i], frag + XB + wg * 32768 + i * 2048); }
#pragma unroll
    for (int i = 0; i < NVR; i++) ldsm4t(wV[i], frag + MEM + (wg * NVR + i) * 2048);
    FENCE_ASYNC_SMEM();
    PH(3);
    CLUSTER_SYNC();
#define xbar (sb + BARS + 64 + wg * 8)
    auto x_load = [&](int n) { if (iw == 0) { X_LOAD(n, wg, 0); X_LOAD(n, wg, 1); } };
    x_load(0);
    if (tid == 0) {
      mbar_expect(obar, 65536);
      for (int i = 0; i < 4; i++) tma2d(sb + WO + i * 16384, &mp.wo, j * 256 + i * 64, h * 128, obar);
    }
#pragma unroll
    for (int i = 0; i < 2; i++) {
      const int k = tid * 2 + i, m = (k >> 3) & 3, r = k & 7;
      sts4(sb + MEM + (k >> 5) * 640 + (r == m ? 512 : m * 128) + r * 16, m0[i][0], m0[i][1], m0[i][2], m0[i][3]);
    }
    if (lane < 8) {
      sts4(sb + ARO + wid * 640 + (lane < 4 ? lane * 144 : 512 + l16), 0x3f803f80, 0x3f803f80, 0x3f803f80, 0x3f803f80);
#pragma unroll
      for (int i = 0; i < 2; i++) sts4(sb + MEM + (wid * 2 + i) * 640 + (lane < 4 ? lane * 144 : 512 + l16), 0x42004200, 0x42004200, 0x42004200, 0x42004200);
    }
#define owner ((iw >> 1) == a)
#define vfin ((wid >> 1) == a)
#define oi (wid & 1)
    frag += wg * NVS * 2048;
    {
      const uint32_t rsb = mapa(sb, iw >> 1);
      const uint32_t pp = rsb + PK + (owner ? 0 : 12288) + (oi * 2048 + wg * 1024) + l16;
      const uint32_t mb = sb + MEM + wg * 5120;
      sts4(L16 + TF + wid * 512, mb + lrow, owner ? L16 + (lane >> 4) * (RK - RQ - 256) + RQ + oi * 1024 + wg * 256 : rsb + RQ + oi * 1024 + 512 + wg * 256 + (l16 >> 2),
           L16 + OB, frag);
      sts4(L16 + TF + 4096 + wid * 512, sb + WO + (wid >> 1) * 16384 + ((lane & 7) + (lane >> 4) * 8) * 128 + ((((wid & 1) * 4 + ((lane >> 3) & 1)) ^ (lane & 7)) << 4),
           sb + ARO + wid * 640 + lrow, pp, LO(xc) + h * 262144 + (bb * 2 + (iw >> 1)) * XC + X_VM(0) + oi * 2048 + a * 256 + (l16 >> 1));
    }
    uint32_t tp = L16 + TF + wid * 512;
    auto park_ptr = [&]() { return lds1(tp + 4096 + 8); };
    auto park = [&](const float* f, int m, int n, uint32_t d) {
      uint32_t w[8];
#pragma unroll
      for (int i = 0; i < 8; i++) w[i] = pk(f[2 * i], f[2 * i + 1]);
      if (owner) {
        sts4(d + m * 4096, w[0], w[1], w[2], w[3]); sts4(d + m * 4096 + 512, w[4], w[5], w[6], w[7]);
      } else {
        const uint32_t pb = mapa(sb, a ^ 1) + BARS + (m ? 24 + m * 8 : 16);
        sta4(d + m * 4096, w, pb); sta4(d + m * 4096 + 512, w + 4, pb);
      }
    };
    auto xdesc = [&](int n) { return mkdesc(__shfl_sync(~0u, 1024 + XB + wg * 16384, 0), 16, 1024); };
    auto rs_issue = [&](float* acc, const uint32_t (&w)[16][4], int n, bool fence) {
      const uint64_t x = xdesc(n);
      if (fence) WG_FENCE();
      wgmma_rs_n32_z(acc, w[0], x);
#pragma unroll
      for (int i = 1; i < 16; i++) wgmma_rs_n32(acc, w[i], x + (i >> 2) * 256 + (i & 3) * 2, 1);
      WG_COMMIT();
    };
    auto v_issue = [&](float* acc, int n, bool fence) {
      const uint64_t dv = mkdesc(__shfl_sync(~0u, 1024 + WVS + wg * NVS * 2048, 0), 16, 1024), x = xdesc(n);
      if (fence) WG_FENCE();
      wgmma_rs_n32_z(acc, wV[0], x);
#pragma unroll
      for (int i = 1; i < (KVO == 2 ? NVR : 0); i++) wgmma_rs_n32(acc, wV[i], x + (i >> 2) * 256 + (i & 3) * 2, 1);
#pragma unroll
      for (int i = NVR; i < 16; i++) wgmma_ssT_n32(acc, dv + (i - NVR) * 128, x + (i >> 2) * 256 + (i & 3) * 2, 1);
#pragma unroll
      for (int i = 1; i < (KVO == 2 ? 0 : NVR); i++) wgmma_rs_n32(acc, wV[i], x + (i >> 2) * 256 + (i & 3) * 2, 1);
      WG_COMMIT();
    };
    uint32_t mA;
    auto vk_pass = [&](int n, uint32_t d) {
      float acc[16], acc2[16];
      v_issue(acc, n, true);
      rs_issue(acc2, wK, n, false);
      if (n) mbar_wait(sb + BARS + 80, (n - 1) & 1);
      WG_WAIT(1);
      park(acc, 2 - !!KVO, n, d);
      mA = lds1(tp);
      if (n > 1) BAR_ARRIVE(B_K, 320);
      WG_WAIT(0);
      park(acc2, 1 + !!KVO, n, d);
    };
    {
      float acc[16];
      mbar_wait(xbar, 0);
      rs_issue(acc, wQ, 0, true); WG_WAIT(0); park(acc, 0, 0, park_ptr());
      vk_pass(0, park_ptr());
      BAR_SYNC(B_C, 320);
      x_load(1);
      BAR_SYNC(B_C, 320);
      asm volatile("" : "+r"(wid));
      mbar_wait(xbar, 1);
      rs_issue(acc, wQ, 1, true); mbar_wait(sb + BARS + 24, 0); WG_WAIT(0); park(acc, 0, 1, park_ptr());
      vk_pass(1, park_ptr());
      BAR_ARRIVE(B_P, 384); if (!HX) BAR_ARRIVE(B_X, 320); BAR_ARRIVE(B_Q, 288);
    }
    mbar_wait(obar, 0);
    PH(4);
    ROLE_REFRESH
    for (int s = 0; s < 64; s++) {
      asm volatile("" : "+r"(tp), "+r"(wid));
      asm volatile("mov.u32 %0,%%cluster_ctarank;" : "=r"(b));
      uint32_t vS[NVS][4], bf[8][4], rm;
      const uint32_t mm = mapa(sb, a ^ 1) + BARS;
      if (s > 0) BAR_SYNC(B_R, 320);
#define VMMA(c, w, i) mma16(c, (w)[0], (w)[1], (w)[2], (w)[3], bf[(i) >> 1][((i) & 1) * 2], bf[(i) >> 1][((i) & 1) * 2 + 1])
      {
        float cQ[4] = {0, 0, 0, 0}, cK[4] = {0, 0, 0, 0};
#pragma unroll
        for (int t = 7; t >= 3; t--) ldsm4t(bf[t], mA + t * 640);
        SCHED_FENCE(47);
#pragma unroll
        for (int i = 15; i >= 0; i--) {
          VMMA(cQ, wQ[i], i); VMMA(cK, wK[i], i);
          if (i == XI && HX) BAR_ARRIVE(B_X, 320);
          if (i == 12) {
            SCHED_FENCE(51);
#pragma unroll
            for (int t = 2; t >= 0; t--) ldsm4t(bf[t], mA + t * 640);
            rm = lds1(tp + 4); frag = lds1(tp + 12);
          }
          if (i == 4 && NVP) {
            SCHED_FENCE(48);
#pragma unroll
            for (int u = 0; u < NVP; u++) ldsm4t(vS[NVS - 1 - u], frag + WVS + (NVS - 1 - u) * 2048);
          }
        }
        const uint32_t w0 = pk(cQ[0] * SCS, cQ[1] * SCS), w1 = pk(cQ[2] * SCS, cQ[3] * SCS), w2 = pk(cK[0], cK[1]), w3 = pk(cK[2], cK[3]);
        if (owner) {
          stsm4(rm, w0, w1, w2, w3);
          BAR_ARRIVE(B_E, 256);
        } else {
          sta1<0>(rm, w0, mm); sta1<128>(rm, w1, mm);
          sta1<RK - RQ>(rm, w2, mm); sta1<RK - RQ + 128>(rm, w3, mm);
        }
        if (wid == 2) TS(0);
      }
      uint4 t1;
      uint32_t oA;
      {
        float cV[4] = {0, 0, 0, 0}, cW[4] = {0, 0, 0, 0};
        static_assert(NVP == 2 && NVR == 5, "schedule");
#define VLD(k) ldsm4t(vS[(k) - NVR], frag + WVS + ((k) - NVR) * 2048)
#define VS_(c, k) VMMA(c, vS[(k) - NVR], k)
        VLD(13); VLD(12);
        VS_(cW, 15); VS_(cV, 14); VLD(11); VMMA(cW, wV[0], 0); VLD(10); VMMA(cV, wV[1], 1); VLD(9);
        VMMA(cW, wV[2], 2); VLD(8); VMMA(cV, wV[3], 3); VLD(7); VMMA(cW, wV[4], 4); VS_(cV, 13); VLD(6); VS_(cW, 12); VLD(5);
        VS_(cV, 11); VS_(cW, 10); VS_(cV, 9); VS_(cW, 8); VS_(cV, 7); VS_(cW, 6); VS_(cV, 5);
#pragma unroll
        for (int e = 0; e < 4; e++) cV[e] += cW[e];
        const uint32_t ex = tp + (RX - TF) - wg * 2048;
        t1 = lds4(tp + 4096);
        oA = lds1(tp + 8 + (s & dZ));
        if (wg) {
          sts4(ex, U_(cV[0]), U_(cV[1]), U_(cV[2]), U_(cV[3]));
          BAR_ARRIVE(B_T2, 256);
        } else {
          BAR_SYNC(B_T2, 256);
          const float4 u = lds4f(ex);
          stg_b64(mkp(t1.w ^ ((s & 1) * X_RING), HI(xc)), (pk(cV[0] + u.x, cV[1] + u.y) & ~1u) | (((s >> 1) + 1) & 1), pk(cV[2] + u.z, cV[3] + u.w));
        }
      }
      if (s == 63) break;
      {
        const uint32_t woA = t1.x, woB = woA ^ 32;
        uint32_t wo[16][4];
#pragma unroll
        for (int i = 0; i < NW1; i++) ldsm4t(wo[i], ((i & 1) ? woB : woA) + (i >= WCH ? wo[(i - WCH + NWP) % NWP][0] & dZ : 0) + (i >> 1) * 2048);
        BAR_SYNC(B_S, 416);
        if (s < 62) {
          float acc[16];
          rs_issue(acc, wQ, s + 2, true);
          mbar_wait(sb + BARS + 24, (s + 1) & 1);
          WG_WAIT(0);
          BAR_SYNC(B_V, 512);
          park(acc, 0, s + 2, t1.z);
        } else {
          BAR_SYNC(B_V, 512);
        }
#pragma unroll
        for (int i = NW1; i < NWP; i++) ldsm4t(wo[i], ((i & 1) ? woB : woA) + (i >> 1) * 2048);
        float inv0, inv1;
        {
          uint32_t p[4], pm;
          const uint32_t pa = oA + (SC - OB), one = 0x3f803f80u;
          float sum[4] = {0, 0, 0, 0}, su2[4] = {0, 0, 0, 0};
          ldsm4t(p, pa);
          asm volatile("ldmatrix.sync.aligned.m8n8.x1.trans.shared.b16 {%0},[%1];" : "=r"(pm) : "r"(pa + 512) : "memory");
          mma16(sum, one, one, one, one, p[0], p[1]);
          mma16(su2, one, one, one, one, p[2], p[3]);
          mma8(sum, one, one, pm);
          inv0 = sum[0] + su2[0]; inv1 = sum[1] + su2[1];
          SCHED_FENCE(57);
        }
        BAR_SYNC(B_O, 416);
        float c[2][4] = {{0, 0, 0, 0}, {0, 0, 0, 0}};
        uint32_t o[4][4];
#pragma unroll
        for (int i = 0; i < NOP_; i++) ldsm4t(o[i], oA + i * 512);
        SCHED_FENCE(46);
        asm("rcp.approx.ftz.f32 %0,%0;" : "+f"(inv0));
        asm("rcp.approx.ftz.f32 %0,%0;" : "+f"(inv1));
#pragma unroll
        for (int i = 0; i < 16; i++) {
          mma16(c[i & 1], wo[i][0], wo[i][1], wo[i][2], wo[i][3], o[i >> 2][i & 2], o[i >> 2][(i & 2) + 1]);
          if (i == 1 && NOP_ < 3) ldsm4t(o[2], oA + 1024);
          if (i == 3 && NOP_ < 4) ldsm4t(o[3], oA + 1536);
          if (i + NWP < 16) ldsm4t(wo[(i + NWP) & 15], (((i + NWP) & 1) ? woB : woA) + ((i + NWP) >> 1) * 2048);
        }
        stsm4(t1.y, pk(c[0][0] * inv0, c[0][1] * inv1), pk(c[0][2] * inv0, c[0][3] * inv1), pk(c[1][0] * inv0, c[1][1] * inv1), pk(c[1][2] * inv0, c[1][3] * inv1));
      }
      const uint32_t d = park_ptr();
      BAR_SYNC(B_W, 384);
      if (s < 62) {
        vk_pass(s + 2, d);
        BAR_ARRIVE(B_P, 384); if (!HX) BAR_ARRIVE(B_X, 320);
        TS(10);
      } else {
        mA = lds1(tp);
      }
    }
  } else if (role == 3) {
    asm volatile("setmaxnreg.dec.sync.aligned.u32 24;");
    if (blockIdx.x >= 128) return;
    ROLE_VARS
    const uint32_t L16 = sb + (tid & 31) * 16;
    CLUSTER_SYNC();
    sts1(sb + PACE + 36, LO(xc) + h * 262144 + X_VM(0));
    auto vm_stage = [&](int s) {
      const uint32_t tag = ((s >> 1) + 1) & 1;
      const char* xm = mkp(lds1(sb + PACE + 36) + (s & 1) * X_RING + iw * XC + (l16 >> 1), HI(xc));
      uint2 m[4];
      CONSUME(LO(xm));
      BAR_SYNC(B_S2, 256);
      if (dZ2 > 1) { const uint32_t c = clk(); while (clk() - c < (uint32_t)dZ2) {} }
      int it = 0;
      while (true) {
#pragma unroll
        for (int i = 0; i < 4; i++) m[i] = ldg_b64(xm + (i >> 1) * 2048 + (i & 1) * 256);
        sts4(L16 + VN + iw * 512, m[0].x, m[0].y, m[1].x, m[1].y);
        sts4(L16 + VN + iw * 512 + 2048, m[2].x, m[2].y, m[3].x, m[3].y);
        if (!anybad(m[0].x, m[1].x, m[2].x, m[3].x, tag)) break;
        RP(2);
        if (++it > SPIN_LIMIT) __trap();
      }
      if (s < 63) BAR_ARRIVE(B_V, 512); else BAR_ARRIVE(B_V, 256);
    };
    if (iw == 0) {
#pragma unroll 1
      for (int s = 0; s < 63; s++) {
        if (s) BAR_SYNC(B_R, 320); else BAR_SYNC(B_Q, 288);
        if (s < 62) { X_LOAD(s + 2, 0, 0); X_LOAD(s + 2, 1, 0); X_LOAD(s + 2, 0, 1); X_LOAD(s + 2, 1, 1); }
        if (s >= 7) {
          const uint32_t zo = b * 160 + l16;
          if (l16 < 160) CONSUME(exch_b128((char*)g_ar + (zo >> 7) * 1024 + (zo & 127) + ((s + 1) & 7) * 128, 0, 0, 0, 0).x);
          __syncwarp();
        }
        if (s < 62) { mbar_wait(sb + BARS + 64, s & 1); mbar_wait(sb + BARS + 72, s & 1); }
        BAR_ARRIVE(B_S, 416);
        vm_stage(s);
        BAR_ARRIVE(B_O, 416);
        BAR_SYNC(B_W, 384);
        FENCE_ASYNC_SMEM();
        asm volatile("{.reg .pred p; elect.sync _|p, 0xffffffff; @p cp.reduce.async.bulk.tensor.2d.global.shared::cta.add.bulk_group [%0,{%1,%2}],[%3];}"
                     ::"l"(&mp.ari), "r"((s & 7) * 64), "r"(j * 40), "r"(sb + ARO) : "memory");
        BULK_COMMIT();
        asm volatile("st.relaxed.gpu.global.u32 [%0],%1;" ::"l"(g_tm + (s & 1) * 128 + b), "r"(gtime()) : "memory");
        TS(3);
        BULK_WAIT_READ(0);
      }
      BAR_ARRIVE(B_R, 320);
      vm_stage(63);
    } else if (iw == 1) {
      const uint32_t pc = sb + MEM + (lane >> 2) * 640 + (lane & 3) * 144 + (lane & 12), pd = sb + MEM + (lane & 15) * 640 + 576 + (lane & 3) * 16 + (lane & 12);
      uint32_t T = 0, par = 0;
      int est = dA;
#pragma unroll 1
      for (int s = 0; s < 63; s++) {
        if (s) {
          const uint4 tm = ldg_rlx4((const char*)g_tm + ((s + 1) & 1) * 512 + l16);
          const int t0 = tm.x - T, t1 = tm.y - T, t2 = tm.z - T, t3 = tm.w - T;
          const int e = max(dF + (__reduce_add_sync(~0u, (t0 + t1) + (t2 + t3)) >> 7), dV + __reduce_max_sync(~0u, max(max(t0, t1), max(t2, t3))));
          if (s > 1) est += max(min(e >> 2, dP), -dP);
          T += (s == 1 || e > dM ? e : 0) + est;
        }
        vm_stage(s);
        BAR_SYNC(B_W, 384);
        SCHED_FENCE(70);
        const uint32_t tW = gtime();
        if (s == 0) T = tW + 800;
        const uint32_t te = tW + min(max((int)(T - tW), dD), 2000);
        while ((int)(gtime() - te) < 0) {}
        TS(7);
        int it = 0;
        while (true) {
          ar_fetch(sb + MEM, &mp.ari, s & 7, a, sb + BARS + 112);
          mbar_wait(sb + BARS + 112, par);
          par ^= 1;
          const uint32_t n0 = lds1(pc), n1 = lds1(pc + 5120), n2 = lds1(pd);
          if (!__any_sync(~0u, (tagbad(n0, n1, 0x42004200) | (n2 ^ 0x42004200)) != 0)) break;
          RP(0);
          if (++it > SPIN_LIMIT) __trap();
        }
        BAR_ARRIVE(B_R, 320);
        TS(11);
      }
      vm_stage(63);
    } else {
#define V_LOAD(n) do { if (lane == 0) mbar_expect(sb + BARS + 8, 8192); __syncwarp(); \
        if (lane < 16) bulk_ld(sb + ((lane & 2) ? VX1 : VX0) + (lane & 1) * 2048 + (lane >> 2) * 512, \
                               xc + h * 262144 + ((n) & 1) * X_RING + (lane >> 2) * XC + X_VX(lane & 3), 512, sb + BARS + 8); __syncwarp(); } while (0)
      uint32_t src = L16 + PK + (iw & 1) * 2048;
#define qd (L16 + (lane >> 4) * 256 + QT + (iw & 1) * 1024)
#define vd (LO(xc) + h * 262144 + j * XC + (iw & 1) * 2048 + l16)
#define FINISH [&](int n, int m) { \
_Pragma("unroll") \
        for (int i = 1; i >= 0; i--) { \
          const uint32_t p = src + m * 4096 + i * 512; \
          uint4 u = lds4(p); \
          const uint4 w = lds4(p + 1024), y = lds4(p + 12288), z = lds4(p + 13312); \
          u = make_uint4(sum4bf(u.x, w.x, y.x, z.x), sum4bf(u.y, w.y, y.y, z.y), sum4bf(u.z, w.z, y.z, z.z), sum4bf(u.w, w.w, y.w, z.w)); \
          if (m == 2) stg_b128(mkp(vd ^ ((n & 1) * X_RING), HI(xc)) + i * 512, (u.x & ~1u) | (((n >> 1) + 1) & 1), u.y, u.z, u.w); \
          else stsm4(qd + (n & 1) * 4096 + m * 2048 + i * 256, u.x, u.z, u.y, u.w); \
          SCHED_FENCE(71 + m * 2 + i); \
        } \
      }
#pragma unroll 1
      for (int n = 0; n < 64; n++) {
        src = PIN(src);
        b = __shfl_sync(~0u, lds1(sb + PACE + 24), 0);
        const uint32_t L16 = src - PK - (iw & 1) * 2048;
        auto finish = FINISH;
        if (n < 2) { if (n) BAR_SYNC(B_X, 320); else BAR_SYNC(B_C, 320); }
        mbar_wait(sb + BARS + 16, n & 1);
        finish(n, 0);
        __syncwarp();
        if (lane == 0) mbar_arrive_cl(mapa(sb, a ^ 1) + BARS + 24);
        if (n > 1) BAR_SYNC(B_K, 320);
        mbar_wait(sb + BARS + (KVO ? 32 : 40), n & 1);
        finish(n, 2 - !!KVO);
        if (n > 1) BAR_SYNC(B_X, 320);
        mbar_wait(sb + BARS + (KVO ? 40 : 32), n & 1);
        finish(n, 1 + !!KVO);
        BAR_SYNC(B_T, 64);
        if (lane == 0) {
          if (iw == 2 && n < 63) { mbar_expect(sb + BARS + 16, 4096); mbar_expect(sb + BARS + 32, 4096); mbar_expect(sb + BARS + 40, 4096); }
          mbar_arrive_cl(mapa(sb, a ^ 1) + BARS + 80);
        }
        __syncwarp();
        if (n) {
          vm_stage(n - 1);
          BAR_SYNC(B_W, 384);
        } else {
          BAR_SYNC(B_C, 320);
        }
        if (iw == 2) V_LOAD(n);
      }
      if (HX) BAR_ARRIVE(B_X, 320);
      vm_stage(63);
#undef qd
#undef vd
    }
  } else {
    asm volatile("setmaxnreg.dec.sync.aligned.u32 %0;" ::"n"(RA_));
    if (blockIdx.x >= 128) return;
    ROLE_VARS
    uint32_t L16 = __shfl_sync(~0u, sb + (tid & 31) * 16, tid & 31);
    if (tid == 256) {
      const int col = h * 128 + bb * 64;
      for (int c = 0; c < 12 + WIN; c++) {
        const uint32_t mb = sb + PACE + (c % WIN) * 8;
        if (c >= WIN) mbar_wait(mb, (c / WIN - 1) & 1);
        if (c >= 12) { tma2d_pf(&mp.wo, j * 256 + (c - 12) * 64, h * 128); continue; }
        mbar_expect(mb, 16384);
        if (c < 8) tma2d(sb + (c & 1) * XB + (c >> 1) * 16384, (c & 1) ? &mp.wk : &mp.wq, col, a * 512 + (c >> 1) * 128, mb);
        else
          for (int i = (c & 1) * 8; i < (c & 1) * 8 + 8; i++) {
            const int w = (c - 8) >> 1;
            tma2d(i < NVR ? sb + MEM + (w * NVR + i) * 2048 : sb + WVS + (w * NVS + i - NVR) * 2048, &mp.wv, col, a * 512 + w * 256 + i * 16, mb);
          }
      }
      asm volatile("mbarrier.arrive.shared.b64 _,[%0];" ::"r"(wbar) : "memory");
      for (int c = WIN; c < 4; c++) tma2d_pf(&mp.wo, j * 256 + c * 64, h * 128);
      for (int i = 0; i < 3; i++) asm volatile("mbarrier.inval.shared.b64 [%0];" ::"r"(sb + PACE + i * 8) : "memory");
    }
    __syncwarp();
    CLUSTER_SYNC();
#define pr (L16 + SC)
    {
      const int lim = j * 8 + iw * 2 - (lane & 7) - (lane & 8) * 2;
      const bool mk = L16 & 256;
      const int rw = lane >> 2;
      sts4(L16 + TA + iw * 512,
           iw != 2 ? L16 + KT + (iw & 1) * 256 + (lane >> 4) * 256 : sb + RK + (L16 & 0x80) * 2 + ((L16 >> 1) & 0x80) + (L16 & 0x70),
           L16 + QT + (lane >> 3) * 384, sb + SC + min(lane >> 3, 2) * 256 + (L16 & 0x70) + iw * 4, L16 + (lane >> 4) * 256 + QT + (iw >> 1) * 1024 + (iw & 1) * 256);
      sts4(L16 + TA + 2048 + iw * 512, mk ? 0u : (lim < 0 ? 0xfc00u : 0u) | (lim < -1 ? 0xfc000000u : 0u),
           mk ? 0xfc00fc00u : (lim < 8 ? 0xfc00u : 0u) | (lim < 7 ? 0xfc000000u : 0u),
           ((h * 2 + (iw >> 1)) * 1024 + (j * 8 + rw) * 8 + (((iw & 1) * 4 + (lane & 3)) ^ rw)) * 16, sb + OT + iw * 512 + (L16 & 0x70) * 4 + ((L16 >> 3) & 0x30));
    }
    {
      const uint32_t xh = LO(xc) + h * 262144, xs = xh + X_SC + iw * 1024 + min(lane, 16 + (lane & 7)) * 8;
      sts4(L16 + TA + 4096 + iw * 512, xh + X_SC + j * 256 + iw * 64 + lpub, xs, dS, iw != 2 ? 0 : U_(SCS));
      sts1(L16 + TA + 12 + iw * 512, xs + X_TOK + j * 4096);
    }
    uint32_t tA = L16 + TA + iw * 512;
#define tw (tA - L16 != TA + 1024)
#define XP_(lo) mkp(lo, HI(xc))
    auto publish = [&](char* d, const uint2& w) { stg_b64(d, w.x, w.y); };
    BAR_SYNC(B_P, 384);
    for (int s = 0; s < 64; s++) {
      asm volatile("" : "+r"(L16), "+r"(tA));
      const uint32_t tag = ((s >> 1) + 1) & 1, ring = (s & 1) * X_RING;
      const uint4 t0 = lds4(tA);
      const uint4 tx = lds4(tA + 4096);
      const uint32_t xo = tx.x ^ ring, xs = tx.y ^ ring;
      const float gm = F_(tx.w);
      const uint32_t qA = t0.y + (ring >> 5);
      uint32_t c0;
      uint2 ts[4];
      uint4 v[4];
      uint32_t af[2][4], qt[4][4];
      {
        const uint32_t aA = t0.x + (tw ? ring >> 5 : 0);
        uint32_t ql[2][4], qr[2][4];
        uint2 pw_;
        float c[4] = {0, 0, 0, 0}, d[4] = {0, 0, 0, 0};
        if (s == PDS) asm volatile("griddepcontrol.launch_dependents;");
#pragma unroll
        for (int i = 0; i < 4; i++) ldsm4t(qt[i], qA + i * 128);
        mbar_wait(sb + BARS + 8, s & 1);
        TS(4);
        BAR_SYNC(B_E, 256);
#define PACK(c) make_uint2(pkh(fmaf(c[2], gm, c[0] * SCS), fmaf(c[3], gm, c[1] * SCS), tag), pkh(c[2] * SCS, c[3] * SCS, tag))
#define SMMA(x, t, q, i) mma16(x, af[t][0], af[t][1], af[t][2], af[t][3], q[t][i], q[t][i + 1])
        ldsm4t(ql[0], L16 + RQ); ldsm4t(ql[1], L16 + RQ + 1024); ldsm4t(af[0], aA); ldsm4t(af[1], aA + 1024);
        CONSUME(xo);
#define QSUM(t, i) addbf(addbf(ql[t][i], ql[t][i + 2]), addbf(qr[t][i], qr[t][i + 2]))
#define STAIL mma16(c, af[0][0], af[0][1], af[0][2], af[0][3], QSUM(0, 0), QSUM(0, 1)); mma16(d, af[1][0], af[1][1], af[1][2], af[1][3], QSUM(1, 0), QSUM(1, 1));
        if (tw) {
          mbar_wait(sb + BARS, s & 1);
          TS(8);
          ldsm4t(qr[0], L16 + RQ + 512); ldsm4t(qr[1], L16 + RQ + 1536);
          STAIL
          pw_ = make_uint2(pkh(c[0] + d[0], c[1] + d[1], tag), pkh(c[2] + d[2], c[3] + d[3], tag));
        } else {
          uint32_t ar[2][4];
          mbar_wait(sb + BARS, s & 1);
          ldsm4t(qr[0], L16 + RQ + 512); ldsm4t(ar[0], aA + 512); ldsm4t(qr[1], L16 + RQ + 1536); ldsm4t(ar[1], aA + 1536);
#pragma unroll
          for (int i = 0; i < 8; i++) af[i >> 2][i & 3] = addbf(af[i >> 2][i & 3], ar[i >> 2][i & 3]);
          STAIL
          pw_.x = pw_.y = pkh((c[0] + c[2]) + (d[0] + d[2]), (c[1] + c[3]) + (d[1] + d[3]), tag);
        }
        publish(XP_(xo), pw_);
        c0 = clk() + tx.z;
        TS(1);
      }
      uint2 r[4];
#define TOKS(i) { float e0[4] = {0, 0, 0, 0}, e1[4] = {0, 0, 0, 0}; \
        mma16(e0, af[0][0], af[0][1], af[0][2], af[0][3], qt[i][0], qt[i][1]); mma16(e1, af[0][0], af[0][1], af[0][2], af[0][3], qt[i + 1][0], qt[i + 1][1]); \
        mma16(e0, af[1][0], af[1][1], af[1][2], af[1][3], qt[i][2], qt[i][3]); mma16(e1, af[1][0], af[1][1], af[1][2], af[1][3], qt[i + 1][2], qt[i + 1][3]); \
        ts[i] = PACK(e0); ts[i + 1] = PACK(e1); }
      {
        float e[4][4];
#pragma unroll
        for (int i = 0; i < 4; i++) {
          e[i][0] = e[i][1] = e[i][2] = e[i][3] = 0.f;
          mma16(e[i], af[0][0], af[0][1], af[0][2], af[0][3], qt[i][0], qt[i][1]);
        }
#pragma unroll
        for (int i = 0; i < 4; i++) mma16(e[i], af[1][0], af[1][1], af[1][2], af[1][3], qt[i][2], qt[i][3]);
        SCHED_FENCE(55);
        if (s < 63) BAR_ARRIVE(B_S, 416);
        SCHED_FENCE(58);
        v[0] = lds4(tA + (VX0 - TA)); v[1] = lds4(tA + (VX0 - TA) + 2048); v[2] = lds4(tA + (VX1 - TA)); v[3] = lds4(tA + (VX1 - TA) + 2048);
#pragma unroll
        for (int i = 0; i < 4; i++) ts[i] = PACK(e[i]);
        while ((int)(clk() - c0) < 0) {}
        TS(5);
#pragma unroll
        for (int u = 0; u < 4; u++) r[u] = ldg_b64(XP_(xs) + u * 256);
        BAR_ARRIVE(B_S2, 256);
      }
      const uint32_t fn = (L16 & 256) ? 0xfc00fc00u : 0u;
      SCHED_FENCE(56);
      float4 e = softmax2<false>(r, 0, fn);
      const bool vbad = anybad(v[0].x, v[1].x, v[2].x, v[3].x, tag);
      if (BADS(r)) {
        int it = 0;
        if (s > 8) sts1(tA + 4096 + 8, min(lds1(tA + 4096 + 8) + dX, 500));
        do {
          RP(1);
          if (++it > SPIN_LIMIT) __trap();
#pragma unroll
          for (int u = 0; u < 4; u++) r[u] = ldg_b64(XP_(xs) + u * 256);
        } while (BADS(r));
        e = softmax2<false>(r, 0, fn);
      }
      sts1(t0.z, pk(e.x, e.y)); sts1(t0.z + 128, pk(e.z, e.w));
#pragma unroll
      for (int i = 0; i < 4; i++) publish(XP_(xo) + X_TOK + i * 4096, ts[i]);
      TS(6);
      if (s < 63) BAR_SYNC(B_V, 512); else BAR_SYNC(B_V, 256);
      uint32_t O[4];
      uint4 vn[2];
      {
        uint32_t p[4], pm;
        ldsm4t(p, pr);
        asm volatile("ldmatrix.sync.aligned.m8n8.x1.trans.shared.b16 {%0},[%1];" : "=r"(pm) : "r"(pr + 512) : "memory");
        vn[0] = lds4(tA + (VN - TA)); vn[1] = lds4(tA + (VN - TA) + 2048);
        pv_mem(p, pm, v, vn, O);
        if (vbad) {
          int it = 0;
          do {
            if (++it > SPIN_LIMIT) __trap();
#pragma unroll
            for (int u = 0; u < 4; u++) v[u] = ldg_b128(XP_((LO(xc) + (lds1(sb + PACE + 24) >> 2) * 262144 + ((tA - L16 - TA) >> 9) * XC + l16) ^ ring) + X_VX(u));
          } while (anybad(v[0].x, v[1].x, v[2].x, v[3].x, tag));
          pv_mem(p, pm, v, vn, O);
        }
      }
      stsm4(tA + (OB - TA), O[0], O[1], O[2], O[3]);
      if (s < 63) BAR_ARRIVE(B_O, 416);
      TS(2);
      c0 = clk() + dG;
      SCHED_FENCE(60);
      if (tA == sb + TA) mbar_expect(sb + BARS, 2048);
      const uint32_t vs[4] = {addbf(vn[0].x, vn[0].z), addbf(vn[0].y, vn[0].w), addbf(vn[1].x, vn[1].z), addbf(vn[1].y, vn[1].w)};
      {
        const char* xt = XP_(lds1(tA + 12) ^ ring);
        const uint2 t1 = lds2u(tA + 2048);
        const uint32_t pw = lds1(tA + 8);
        uint2 rt[4];
        CONSUME(LO(xt) ^ t1.x ^ pw);
        while ((int)(clk() - c0) < 0) {}
        int it = 0;
        do {
          if (++it > SPIN_LIMIT) __trap();
#pragma unroll
          for (int u = 0; u < 4; u++) rt[u] = ldg_b64(xt + u * 256);
        } while (BADS(rt));
        const float4 et = softmax2<true>(rt, t1.x, t1.y);
        sts1(pw + 1024, pk(et.x, et.y)); sts1(pw + 1024 + 128, pk(et.z, et.w));
      }
      s = PIN(s);
      BAR_SYNC(B_SC, 128);
      {
        uint32_t Ot[4], p[4], pm;
        const uint2 t2 = lds2u(tA + 2048 + 8);
        ldsm4t(p, pr + 1024);
        asm volatile("ldmatrix.sync.aligned.m8n8.x1.trans.shared.b16 {%0},[%1];" : "=r"(pm) : "r"(pr + 1024 + 512) : "memory");
        char* od = (char*)g_O + ((s >> 2) * 1048576 + (s & 3) * 4096) + t2.x;
        CONSUME(LO(od) ^ HI(od) ^ pm ^ p[3]);
        TS(9);
        if (s < 62) BAR_SYNC(B_P, 384);
        pv_tok(p, pm, v, vs, Ot);
        asm volatile("stmatrix.sync.aligned.m8n8.x4.trans.shared.b16 [%0],{%1,%2,%3,%4};" ::"r"(t2.y), "r"(Ot[0]), "r"(Ot[1]), "r"(Ot[2]), "r"(Ot[3]) : "memory");
        __syncwarp();
        *(uint4*)od = lds4(tA + (OT - TA));
      }
    }
    FENCE_ASYNC();
    BAR_SYNC(B_SC, 128);
    if (tA == sb + TA) red_rel(&g_fin);
  }
  __syncwarp();
  CLUSTER_SYNC();
  PH(5);
}
#undef wg
#undef iw
#undef h
#undef j
#undef a
#undef bb
#undef oi
#undef owner
#undef vfin
#undef xbar
#undef pr
#undef PIN
#undef XP_
#undef tw
#undef is7
#undef REFRESH
#undef lane
#undef l16
#undef lrow
#undef lar
#undef lpub

namespace ffn {
constexpr uint32_t BR = 98304;
constexpr uint32_t STG = 196608;
constexpr uint32_t PRM = 229376;
constexpr uint32_t BARS = PRM + 2816;
constexpr uint32_t SMEM = BARS + 18 * 8;
}
#define Y_TILE(rb, kt) (((ALIAS & 1) ? g_h : g_h2) + ((rb) * 16 + (kt)) * 1024)
#define U_TILE(rb, kt) ((ALIAS & 2) ? g_O + ((rb) * 64 + (kt)) * 1024 : g_U + ((rb) * 56 + (kt)) * 1024)
struct FfnMaps { CUtensorMap wo, w1a, w1b, w2, x, out; };

template <int N>
__device__ __forceinline__ void wg_ss(float* d, uint64_t a, uint64_t b, int sd) {
  if (N == 128) wgmma_ss_n128(d, a, b, sd);
  if (N == 192) wgmma_ss_n192(d, a, b, sd);
}
template <int N>
__device__ __forceinline__ void acc_fence(float* d) {
#pragma unroll
  for (int i = 0; i < N; i++) asm volatile("" : "+f"(d[i])::"memory");
}
#define UNPK8(d, v) do { (d)[0] = blo(v.x); (d)[1] = bhi(v.x); (d)[2] = blo(v.y); (d)[3] = bhi(v.y); (d)[4] = blo(v.z); (d)[5] = bhi(v.z); (d)[6] = blo(v.w); (d)[7] = bhi(v.w); } while (0)
struct FfnPipe {
  uint32_t full, emp, ph, aoff;
  int st, sB, prev;
  bool leader;
  template <int N>
  __device__ __forceinline__ void issue(float* acc, bool first, uint32_t a = 0) {
    mbar_wait(full + st * 8, ph);
    const uint64_t da = mkdesc((a ? a : 1024 + st * 16384) + aoff, 16, 1024), db = mkdesc(1024 + ffn::BR + sB * (N * 128), 8192, 1024);
    WG_FENCE();
#pragma unroll
    for (int j = 0; j < ((DBG & 1) ? 1 : 4); j++) wg_ss<N>(acc, da + j * 2, db + j * 128, j || !first);
    WG_COMMIT();
    if (++sB == 768 / N) sB = 0;
  }
  __device__ __forceinline__ void release() { if (leader) mbar_arrive(emp + prev * 8); }
  __device__ __forceinline__ void next() { prev = st; if (++st == 6) { st = 0; ph ^= 1; } }
  __device__ __forceinline__ void retire() { WG_WAIT(1); release(); next(); }
};
__device__ __forceinline__ float gelu_h(float hx) {
  float u = hx * fmaf(hx * hx, 8.f * 0.0356774081f, 2.f * 0.7978845608f), t;
  if (DBG & 4) return hx;
  if (DBG & 2) t = u; else
  asm("tanh.approx.f32 %0,%1;" : "=f"(t) : "f"(u));
  return fmaf(hx, t, hx);
}
struct FfnEpi {
  uint32_t st2, cc, flip, staged, l0;
  uint2 c;
  float n0, n1, s0, s1;
  __device__ __forceinline__ void flush(uint32_t r) {
    __syncwarp();
    asm volatile("{.reg .pred p; setp.ne.u32 p,%1,0; @p mbarrier.arrive.shared.b64 _,[%0];}" ::"r"(staged + (flip >> 11)), "r"(l0 & r) : "memory");
    flip ^= r << 14;
  }
  __device__ __forceinline__ void half(const float* d, int J, int r) {
#define PRE(i, n, c1, c2) gelu_h(fmaf(r ? d[4 + i] : d[i], i < 2 ? s0 : s1, fmaf(n, c1, c2)))
    asm volatile("stmatrix.sync.aligned.m8n8.x2.shared.b16 [%0],{%1,%2};" ::"r"((st2 ^ ((J & 3) * 32 + r * 16)) + flip),
                 "r"(pk(PRE(0, n0, blo(c.x), blo(c.y)), PRE(1, n0, bhi(c.x), bhi(c.y)))), "r"(pk(PRE(2, n1, blo(c.x), blo(c.y)), PRE(3, n1, bhi(c.x), bhi(c.y)))) : "memory");
#undef PRE
    if ((J & 3) == 3) flush(r);
    cc += r ? 56 : 8;
    c = lds2u(cc);
  }
};

__global__ void __launch_bounds__(384, 1)
k_ffn(const __grid_constant__ FfnMaps mp, const bf16* __restrict__ b2) {
  using namespace ffn;
  extern __shared__ __align__(1024) char smem[];
  const uint32_t sb = (uint32_t)__cvta_generic_to_shared(smem);
  if (sb != 1024) __trap();
  const int tid = threadIdx.x, lane = tid & 31, wg = __shfl_sync(~0u, tid >> 7, 0);
  const uint32_t full = sb + BARS, emp = full + 48, xbar = full + 96, staged = full + 104, tile = full + 136;
  uint32_t fin = 0;
  if (tid >= 288 && tid < 320) fin = ld_acq(&g_fin);
  if (tid < 32) {
    unsigned sm, v = 0;
    asm("mov.u32 %0,%%smid;" : "=r"(sm));
    if (tid == 0) {
      v = atomicExch(&g_slot[sm & 255], 0);
      for (int i = 0; i < 6; i++) { mbar_init(full + i * 8, 1); mbar_init(emp + i * 8, 2); }
      mbar_init(xbar, 2);
      for (int i = 0; i < 2; i++) { mbar_init(staged + i * 8, 8); mbar_init(staged + 16 + i * 8, 1); }
      FENCE_ASYNC_SMEM();
    }
    v = __shfl_sync(~0u, v, 0);
    if (!v) {
      wait_cnt(&g_fin, 128);
      for (int it = 0; !v; it++) {
        const uint4 a = ldg_rlx4(g_slot + tid * 8), b = ldg_rlx4(g_slot + tid * 8 + 4);
        const uint32_t open = __ballot_sync(~0u, a.x | a.y | a.z | a.w | b.x | b.y | b.z | b.w);
        if (!open) break;
        if (it < 16) { __nanosleep(500); continue; }
        if (tid == __ffs(open) - 1) v = atomicExch(&g_slot[tid * 8 + (a.x ? 0 : a.y ? 1 : a.z ? 2 : a.w ? 3 : b.x ? 4 : b.y ? 5 : b.z ? 6 : 7)], 0);
        v = __shfl_sync(~0u, v, __ffs(open) - 1);
      }
    }
    if (tid == 0) sts1(tile, v);
  }
  if (tid == 256) asm volatile("prefetch.tensormap [%0];" ::"l"(&mp.wo) : "memory");
  __syncthreads();
  const int bid = __shfl_sync(~0u, lds1(tile), 0) - 1;
  if (bid < 0) return;
  PH(6);
  FT(1);
  const int rb = bid >> 3, nb = bid & 7;
  unsigned* cnt = g_cnt + rb * 128;
  if (wg == 2) {
    asm volatile("setmaxnreg.dec.sync.aligned.u32 " FRP ";");
    const int pw = __shfl_sync(~0u, (tid >> 5) & 3, 0);
    uint32_t ws = emp, wp = 1, fs = full;
    auto wait_free = [&]() { mbar_wait_q(ws, wp); ws += 8; if (ws == emp + 48) { ws = emp; wp ^= 1; } };
    auto step = [&]() { fs += 8; if (fs == full + 48) fs = full; };
#define K3(c) ((0x65230 >> (c) * 4) & 7)
#define KC(k) ((k) < 2 ? nb * 2 + (k) : (k) < 9 ? ((k) - 2 + ((k) - 2 >= nb)) * 2 : ((k) - 9 + ((k) - 9 >= nb)) * 2 + 1)
    if (pw == 0) {
      uint32_t d = sb + BR + 32768;
      auto put = [&](const CUtensorMap* m, int k, int c) {
        e_expect_tma3d(d, m, k * 64, c, fs, 32768);
        step();
        d += 16384;
        if (d == sb + STG) d = sb + BR;
      };
      int n = 0;
      auto stage_free = [&]() { if (!(n & 7) && n < 56) mbar_wait_q(staged + 16 + (n & 8), (n >> 4) & 1); n++; };
      FTP(3);
#pragma unroll 1
      for (int k = 0; k < 66; k++) { wait_free(); if (k < 64) put(&mp.wo, k, nb * 2); }
#pragma unroll 1
      for (int k = 0; k < 16; k++) {
        const int kt = KC(k);
        wait_free();
        e_expect_tma3d(sb + BR + (k & 3) * 24576, &mp.w1b, kt * 64, nb * 7, fs, k < 2 ? 24576 : 40960);
        step();
      }
#pragma unroll 1
      for (int k = 0; k < 32; k++) { stage_free(); if (k != 5 && k != 6) wait_free(); put(&mp.w1a, k & 15, nb * 7 + 3 + (k >> 4) * 2); }
#pragma unroll 1
      for (int c = 0; c < 5; c++)
#pragma unroll 1
        for (int k = K3(c), i = 0; k < 56; k += c < 2 && (i ^= 1) ? 1 : c < 2 ? 6 : 7) { stage_free(); wait_free(); put(&mp.w2, k, nb * 2); }
    } else if (pw == 1) {
      FTP(5);
      if (fin < 128) wait_cnt(&g_fin, 128);
      FTP(6);
      uint32_t d = sb;
      auto put = [&](const uint4* A, bool ld) {
        wait_free();
        if (ld) e_bulk_ld(d, A, 16384, fs);
        step();
        d += 16384;
        if (d == sb + BR) d = sb;
      };
      const uint4* A = g_O + rb * 65536;
#pragma unroll 1
      for (int k = 0; k < 66; k++) put(A + k * 1024, k < 64);
      A = Y_TILE(rb, 0);
      uint32_t ready = 0;
#pragma unroll 1
      for (int k = 2; k < 48; k++) {
        const int kt = k < 16 ? KC(k) : k & 15;
        for (int it = 0; !(ready >> ((kt >> 1) + (kt & 1) * 8) & 1); it++) {
          ready = __ballot_sync(~0u, ldg_rlx1(cnt + (lane & 7)) & ((lane & 8) ? 1 : 0x10000));
          if (it > SPIN_LIMIT) __trap();
        }
        if (k == 2) FTP(75);
        put(A + kt * 1024, true);
      }
      A = U_TILE(rb, 0);
#pragma unroll 1
      for (int c = 0; c < 5; c++) {
        for (int it = 0; ldg_rlx1(cnt + 32 + c) < 8; it++) if (it > SPIN_LIMIT) __trap();
#pragma unroll 1
        for (int k = K3(c), i = 0; k < 56; k += c < 2 && (i ^= 1) ? 1 : c < 2 ? 6 : 7) put(A + k * 1024, true);
      }
    } else if (pw == 2) {
      for (int i = 0; i < XDL; i++) {
        mbar_wait_q(emp, i & 1);
        if (XPF && i == 1 && lane < 2) tma2d_pf(&mp.x, nb * 128 + lane * 64, rb * 128);
      }
      if (lane == 0) {
        mbar_expect(xbar, 32768);
        tma2d(sb + STG, &mp.x, nb * 128, rb * 128, xbar);
        tma2d(sb + STG + 16384, &mp.x, nb * 128 + 64, rb * 128, xbar);
      }
      asm volatile("griddepcontrol.wait;" ::: "memory");
      if (lane < 16) g_modp[bid * 16 + lane] = make_uint4(0, 0, 0, 0);
      if (lane == 16 && bid == 0) { g_hcnt = 0; g_mcnt = 0; }
      if (lane == 0) {
#pragma unroll 1
        for (int g = 1; g < 9; g++) {
          if (g == 1) mbar_wait(staged + 8, 0); else { mbar_wait_q(staged + (g & 1) * 8, (g >> 1) & 1); FENCE_ASYNC_SMEM(); }
          bulk_st(g == 1 ? Y_TILE(rb, nb * 2 + 1) : U_TILE(rb, nb * 7 + ((0x652431000ull >> g * 4) & 7)), sb + STG + (g & 1) * 16384, 16384);
          BULK_COMMIT();
          if (g != 2 && g != 4) { BULK_WAIT(0); red_rlx(g == 1 ? cnt + nb : cnt + 32 + (g < 6 ? g >> 2 : g - 4)); }
          BULK_WAIT_READ(0);
          mbar_arrive(staged + 16 + (g & 1) * 8);
        }
      }
    } else {
      const uint32_t prm = sb + PRM, pp = prm + (lane >> 3) * 64 + (lane & 1) * 32 + (lane & 6) * 2;
      const uint2 v2 = ((const uint2*)(b2 + nb * 128))[lane];
      sts1(pp + 768, v2.x); sts1(pp + 784, v2.y);
      asm volatile("griddepcontrol.wait;" ::: "memory");
      const float4* md = (const float4*)(g_mod + nb * 128) + lane;
      { const float4 ga = md[512]; sts1(pp, pk(ga.x, ga.y)); sts1(pp + 16, pk(ga.z, ga.w)); }
      { const float4 cb = md[1024]; sts1(pp + 256, pk(1.f + cb.x, 1.f + cb.y)); sts1(pp + 272, pk(1.f + cb.z, 1.f + cb.w)); }
      { const float4 gb = md[1280]; sts1(pp + 512, pk(gb.x, gb.y)); sts1(pp + 528, pk(gb.z, gb.w)); }
#pragma unroll 1
      for (int i = lane; i < 112; i += 32) { const uint4 c = g_cc[nb * 112 + i]; sts4(prm + 1024 + i * 16, c.x, c.y, c.z, c.w); }
      __syncwarp();
      if (lane == 0) {
        mbar_arrive(xbar);
        mbar_wait(staged, 0);
        bulk_st(Y_TILE(rb, nb * 2), sb + STG, 16384);
        BULK_COMMIT(); BULK_WAIT(0);
        asm volatile("red.relaxed.gpu.global.add.u32 [%0],0x10000;" ::"l"(cnt + nb) : "memory");
        mbar_arrive(staged + 16);
      }
      __syncwarp();
      mbar_wait_q(staged + 24, 0);
      mbar_wait_q(emp + 40, 0);
#pragma unroll 1
      for (int i = 0; i < 4; i++) {
        const uint4* sp = g_stat + (rb * 128 + i * 32 + lane) * 4;
        uint4 v[4];
        for (int it = 0;; it++) {
          uint32_t m = 0;
#pragma unroll
          for (int u = 0; u < 4; u++) { v[u] = ldg_rlx4(sp + u); m = max(max(m, max(v[u].x, v[u].y)), max(v[u].z, v[u].w)); }
          if (!__any_sync(~0u, m == ~0u)) break;
          if (it > SPIN_LIMIT) __trap();
        }
        float m = 0, q = 0;
#pragma unroll
        for (int u = 0; u < 4; u++) m += F_(v[u].x) + F_(v[u].z);
        m *= 0.125f;
#pragma unroll
        for (int u = 0; u < 4; u++) { const float a = F_(v[u].x) - m, b = F_(v[u].z) - m; q += F_(v[u].y) + F_(v[u].w) + 128.f * (a * a + b * b); }
        const float r = 0.5f * rsqrtf(q * (1.f / 1024) + 1e-5f);
        sts2(sb + STG + 16384 + (i * 32 + lane) * 8, U_(r), U_(-m * r));
      }
      __syncwarp();
      if (lane < 2) mbar_arrive(xbar);
    }
  } else {
    asm volatile("setmaxnreg.inc.sync.aligned.u32 " FRC ";");
    const int w = (tid >> 5) & 3, q = lane & 3;
    const uint32_t prm = sb + PRM + q * 16;
    const int row0 = wg * 64 + w * 16;
    FfnPipe p;
    p.full = full; p.emp = emp; p.ph = 0; p.aoff = wg * 8192; p.st = 0; p.sB = 2; p.prev = 0; p.leader = (tid & 127) == 0;
    FfnEpi e;
    const uint32_t stg = sb + STG + row0 * 128;
    e.st2 = stg + (lane & 15) * 128 + ((lane & 7) << 4);
    e.cc = sb + PRM + 1024 + q * 16; e.flip = 0; e.staged = staged; e.l0 = lane == 0;
    const uint32_t stw = e.st2 ^ (lane & 16);
    uint32_t x1[32];
    uint4* sp = g_stat + (rb * 128 + row0 + (lane >> 2)) * 4;
    float old[96], r0_, r1_;
    {
      float acc[64];
      p.issue<128>(acc, true); FT(8); p.next();
#pragma unroll 1
      for (int k = 1; k < 64; k++) { p.issue<128>(acc, false); FT(8 + k); p.retire(); }
      float xf[64], gf[32];
      uint32_t cb[16];
      mbar_wait(xbar, 0);
#pragma unroll
      for (int j = 0; j < 8; j++) {
        uint32_t xv[4];
        ldsm4(xv, (stw ^ ((j & 3) * 32)) + (j >> 2) * 16384);
#pragma unroll
        for (int i = 0; i < 4; i++) { xf[j * 8 + i * 2] = blo(xv[i]); xf[j * 8 + i * 2 + 1] = bhi(xv[i]); }
      }
#pragma unroll
      for (int i = 0; i < 4; i++) {
        const uint4 g = lds4(prm + i * 64), c = lds4(prm + 256 + i * 64);
        UNPK8(gf + i * 8, g);
        cb[i * 4] = c.x; cb[i * 4 + 1] = c.y; cb[i * 4 + 2] = c.z; cb[i * 4 + 3] = c.w;
      }
      acc_fence<64>(xf); acc_fence<32>(gf);
      WG_WAIT(0);
      p.release();
      acc_fence<64>(acc);
      PH(7); FT(72);
#pragma unroll
      for (int j = 0; j < 8; j++) {
        uint32_t* o = x1 + j * 4;
#pragma unroll
        for (int i = 0; i < 4; i++)
          o[i] = pk(fmaf(acc[j * 8 + i * 2], gf[j * 4 + (i & 2)], xf[j * 8 + i * 2]), fmaf(acc[j * 8 + i * 2 + 1], gf[j * 4 + (i & 2) + 1], xf[j * 8 + i * 2 + 1]));
        stsm4((stw ^ ((j & 3) * 32)) + (j >> 2) * 16384, mulbf(o[0], cb[j * 2]), mulbf(o[1], cb[j * 2]), mulbf(o[2], cb[j * 2 + 1]), mulbf(o[3], cb[j * 2 + 1]));
        if ((j & 3) == 3) { FENCE_ASYNC_SMEM(); e.flush(1); }
      }
      if (wg) BAR_SYNC(2, 128); else BAR_SYNC(3, 128);
    }
    PH(8); FT(73);
    float acc[64];
    {
      float* accC = old;
      p.sB = 0;
      p.issue<192>(accC, true, 1024 + STG); FT(80); p.next();
      p.issue<192>(accC, false, 1024 + STG + 16384); FT(81);
      FT(78);
      float s0 = 0, s1 = 0;
#define X1_FENCE _Pragma("unroll") for (int j = 0; j < 32; j++) asm volatile("" : "+r"(x1[j]));
      X1_FENCE
#pragma unroll
      for (int j = 0; j < 16; j++) { s0 += blo(x1[j * 2]) + bhi(x1[j * 2]); s1 += blo(x1[j * 2 + 1]) + bhi(x1[j * 2 + 1]); }
      s0 += __shfl_xor_sync(~0u, s0, 1); s1 += __shfl_xor_sync(~0u, s1, 1);
      s0 += __shfl_xor_sync(~0u, s0, 2); s1 += __shfl_xor_sync(~0u, s1, 2);
      s0 *= 1.f / 128; s1 *= 1.f / 128;
      float q0 = 0, q1 = 0;
      X1_FENCE
#pragma unroll
      for (int j = 0; j < 16; j++) {
        const float a = blo(x1[j * 2]) - s0, b = bhi(x1[j * 2]) - s0, c = blo(x1[j * 2 + 1]) - s1, d = bhi(x1[j * 2 + 1]) - s1;
        q0 += a * a + b * b; q1 += c * c + d * d;
      }
      q0 += __shfl_xor_sync(~0u, q0, 1); q1 += __shfl_xor_sync(~0u, q1, 1);
      q0 += __shfl_xor_sync(~0u, q0, 2); q1 += __shfl_xor_sync(~0u, q1, 2);
      if (q < 2) {
        uint32_t m = __float_as_uint(q ? s1 : s0), v = __float_as_uint(q ? q1 : q0);
        if (m == ~0u) m = 0x7fffffffu;
        if (v == ~0u) v = 0x7fffffffu;
        stg_rlx2((uint2*)(sp + q * 32) + nb, m, v);
      }
      X1_FENCE
      p.retire();
#pragma unroll 1
      for (int k = 2; k < 15; k++) { p.issue<192>(accC, false); FT(80 + k); p.retire(); }
      p.issue<192>(accC, false); FT(95);
      mbar_wait(xbar, 1);
      const float2 u0 = lds2f(sb + STG + 16384 + (row0 + (lane >> 2)) * 8), u1 = lds2f(sb + STG + 16384 + (row0 + (lane >> 2)) * 8 + 64);
      r0_ = u0.x; e.n0 = u0.y; r1_ = u1.x; e.n1 = u1.y;
      e.c = lds2u(e.cc);
      p.retire();
      e.s0 = r0_; e.s1 = r1_;
    }
    PH(9);
    {
      auto pair = [&](int J, bool first, int fo) {
#pragma unroll 1
        for (int r = 0; r < 2; r++) { p.issue<128>(acc, first && !r); FT(fo + r); p.retire(); acc_fence<8>(old + J * 8); e.half(old + J * 8, J, r); }
      };
#pragma unroll 1
      for (int i = 0; i < 3; i++) {
        if (i == 2) {
          e.s0 = r0_; e.s1 = r1_;
#pragma unroll
          for (int J = 8; J < 12; J++) pair(J, J == 8, 128 + (J - 8) * 2);
          e.cc += 512; e.c = lds2u(e.cc);
          e.s0 = e.s1 = 1.f;
        }
#pragma unroll
        for (int J = 0; J < 8; J++) pair(J, J == 0 && i < 2, 96 + i * 16 + (i >> 1) * 8 + J * 2);
        if (i == 2) break;
        e.cc += i ? -768 : 256; e.c = lds2u(e.cc);
        WG_WAIT(0);
        acc_fence<64>(acc);
#pragma unroll
        for (int k = 0; k < 64; k++) old[k] = acc[k] * ((k & 2) ? r1_ : r0_);
        acc_fence<64>(old);
        e.s0 = e.s1 = 1.f;
        PH(10 + i);
      }
#pragma unroll 1
      for (int k = 24; k < 56; k++) { p.issue<128>(acc, false); FT(128 + k); p.retire(); }
      float xf[64], gf[32];
#pragma unroll
      for (int i = 0; i < 4; i++) {
        const uint4 g = lds4(prm + 512 + i * 64), h = lds4(prm + 768 + i * 64);
        float hf[8];
        UNPK8(gf + i * 8, g); UNPK8(hf, h);
#pragma unroll
        for (int u = 0; u < 8; u++) {
          const int c = (u >> 2) * 4 + (u & 2);
          xf[i * 16 + u * 2] = fmaf(gf[i * 8 + c], hf[c], blo(x1[i * 8 + u])); xf[i * 16 + u * 2 + 1] = fmaf(gf[i * 8 + c + 1], hf[c + 1], bhi(x1[i * 8 + u]));
        }
      }
      acc_fence<64>(xf); acc_fence<32>(gf);
      mbar_wait(staged + 24, 1);
      mbar_wait(staged + 16, 0);
      WG_WAIT(0);
      acc_fence<64>(acc);
      PH(13); FT(184);
#pragma unroll
      for (int j = 0; j < 8; j++) {
        uint32_t o[4];
#pragma unroll
        for (int i = 0; i < 4; i++)
          o[i] = pk(fmaf(acc[j * 8 + i * 2], gf[j * 4 + (i & 2)], xf[j * 8 + i * 2]), fmaf(acc[j * 8 + i * 2 + 1], gf[j * 4 + (i & 2) + 1], xf[j * 8 + i * 2 + 1]));
        stsm4((stw ^ ((j & 3) * 32)) + (j >> 2) * 16384, o[0], o[1], o[2], o[3]);
        if ((j & 3) == 3) {
          FENCE_ASYNC_SMEM();
          __syncwarp();
          if (lane == 0) { tma2d_st(&mp.out, nb * 128 + (j >> 2) * 64, rb * 128 + row0, stg + (j >> 2) * 16384); BULK_COMMIT(); }
        }
      }
      if (lane == 0) BULK_WAIT_READ(0);
      __syncwarp();
    }
  }
  PH(14); FT(185);
}

typedef CUresult (*EncFn)(CUtensorMap*, CUtensorMapDataType, cuuint32_t, void*, const cuuint64_t*, const cuuint64_t*, const cuuint32_t*,
                          const cuuint32_t*, CUtensorMapInterleave, CUtensorMapSwizzle, CUtensorMapL2promotion, CUtensorMapFloatOOBfill);
static void map2d(EncFn enc, CUtensorMap* m, const void* p, int rows, int cols, int boxRows) {
  cuuint64_t d[2] = {(cuuint64_t)cols, (cuuint64_t)rows}, s[1] = {(cuuint64_t)cols * 2};
  cuuint32_t b[2] = {64, (cuuint32_t)boxRows}, e[2] = {1, 1};
  enc(m, CU_TENSOR_MAP_DATA_TYPE_BFLOAT16, 2, (void*)p, d, s, b, e, CU_TENSOR_MAP_INTERLEAVE_NONE, CU_TENSOR_MAP_SWIZZLE_128B,
      CU_TENSOR_MAP_L2_PROMOTION_L2_128B, CU_TENSOR_MAP_FLOAT_OOB_FILL_NONE);
}
static void map3d(EncFn enc, CUtensorMap* m, const void* p, int rows, int cols, int nch) {
  cuuint64_t d[3] = {64, (cuuint64_t)rows, (cuuint64_t)(cols / 64)}, s[2] = {(cuuint64_t)cols * 2, 128};
  cuuint32_t b[3] = {64, 64, (cuuint32_t)nch}, e[3] = {1, 1, 1};
  enc(m, CU_TENSOR_MAP_DATA_TYPE_BFLOAT16, 3, (void*)p, d, s, b, e, CU_TENSOR_MAP_INTERLEAVE_NONE, CU_TENSOR_MAP_SWIZZLE_128B,
      CU_TENSOR_MAP_L2_PROMOTION_L2_128B, CU_TENSOR_MAP_FLOAT_OOB_FILL_NONE);
}

extern "C" void kernel_launch(void* const* d_in, const int* in_sizes, int n_in, void* d_out, int out_size) {
  const bf16* x = (const bf16*)d_in[0];
  const bf16* mem0 = (const bf16*)d_in[1];
  void* fn = nullptr;
  cudaDriverEntryPointQueryResult qr;
  cudaGetDriverEntryPoint("cuTensorMapEncodeTiled", &fn, cudaEnableDefault, &qr);
  EncFn enc = (EncFn)fn;
  FfnMaps fm = {};
  map3d(enc, &fm.wo, d_in[5], 4096, 1024, 2);
  map3d(enc, &fm.w1a, d_in[8], 1024, 3584, 2);
  map3d(enc, &fm.w1b, d_in[8], 1024, 3584, 3);
  map3d(enc, &fm.w2, d_in[10], 3584, 1024, 2);
  map2d(enc, &fm.x, x, 2048, 1024, 128);
  map2d(enc, &fm.out, d_out, 2048, 1024, 16);
  RecMaps rm = {};
  map2d(enc, &rm.wq, d_in[2], 1024, 4096, 128);
  map2d(enc, &rm.wk, d_in[3], 1024, 4096, 128);
  map2d(enc, &rm.wv, d_in[4], 1024, 4096, 16);
  map2d(enc, &rm.wo, d_in[5], 4096, 1024, 128);
  {
    void* ar = nullptr;
    cudaGetSymbolAddress(&ar, g_ar);
    cuuint64_t d[2] = {512, 160}, sd[1] = {1024};
    cuuint32_t bi[2] = {64, 40}, e[2] = {1, 1};
    enc(&rm.ari, CU_TENSOR_MAP_DATA_TYPE_BFLOAT16, 2, ar, d, sd, bi, e, CU_TENSOR_MAP_INTERLEAVE_NONE, CU_TENSOR_MAP_SWIZZLE_NONE,
        CU_TENSOR_MAP_L2_PROMOTION_NONE, CU_TENSOR_MAP_FLOAT_OOB_FILL_NONE);
  }
  cudaFuncSetAttribute(k_ffn, cudaFuncAttributeMaxDynamicSharedMemorySize, ffn::SMEM);
  cudaFuncSetAttribute(k_rec, cudaFuncAttributeMaxDynamicSharedMemorySize, rec::SMEM);
  char* xc = nullptr;
  cudaGetSymbolAddress((void**)&xc, g_xc);
  xc += (0 - (uintptr_t)xc) & 0x3FFFF;
  cudaStream_t st = cudaStreamPerThread;
  int dF = 450, dA = 2700, dS = 300, dM = 120, dG = 350, dP = 24, dX = 48, dD = 350, dZ = 0, dZ2 = 1, dV = 370, dX2 = 0;
  k_rec<<<132, 512, rec::SMEM, st>>>(rm, mem0, x, (const bf16*)d_in[12], (const bf16*)d_in[13], (const char*)d_in[8], (const bf16*)d_in[9],
                                     (const char*)d_in[5], xc, dF, dA, dS, dM, dG, dP, dX, dD, dZ, dZ2, dV, dX2);
  cudaLaunchConfig_t cfg = {};
  cfg.gridDim = dim3(132); cfg.blockDim = dim3(384); cfg.dynamicSmemBytes = ffn::SMEM; cfg.stream = st;
  cudaLaunchAttribute at[1];
  at[0].id = cudaLaunchAttributeProgrammaticStreamSerialization;
  at[0].val.programmaticStreamSerializationAllowed = 1;
  cfg.attrs = at; cfg.numAttrs = 1;
  cudaLaunchKernelEx(&cfg, k_ffn, fm, (const bf16*)d_in[11]);
}
```

```cpp
#include <cuda_runtime.h>
#include <cuda.h>
#include <cuda_bf16.h>
#include <stdint.h>

typedef __nv_bfloat16 bf16;

__device__ __align__(16) float g_mod[6144];
__device__ __align__(1024) uint4 g_modp[4 * 512];
__device__ unsigned g_hcnt;
__device__ __align__(1024) uint4 g_h[2048 * 1024 / 8];
__device__ __align__(1024) uint4 g_O[2048 * 4096 / 8];
__device__ __align__(1024) uint4 g_h2[2048 * 1024 / 8];
__device__ __align__(1024) uint4 g_U[2048 * 3584 / 8];
__device__ __align__(1024) uint4 g_stat[2048 * 4];
__device__ __align__(1024) unsigned g_cnt[16 * 4 * 32];
__device__ unsigned g_mcnt;
__device__ unsigned g_slot[256];
__device__ unsigned g_fin;
__device__ __align__(16) uint4 g_cc[224 * 4];
__device__ __align__(1024) uint4 g_ar[160 * 64];
__device__ __align__(1024) uint4 g_xc[33 * 16384];
__device__ __align__(1024) unsigned g_tm[4 * 256];
#define FT(i)
#define FTP(i)
#define PT(i)
#define PH(i)
#define RP(i)
#define RPN(i, s)
#define TSV(i, v)
#define TS(i)

#define WIN 2
#define FRC "232"
#define FRP "40"
#define YR 1
#define XPK 0
#define NFA 1
#define PINM 1
#define FMAP (((g >> 2) * 4 + m) * 8 + (g & 3) * 2 + (blockIdx.x & 1))
#define DBG 0
#define ALIAS 3
#define EF 0
#define XPF 0
#define PFT 150000
#define PFS 100
#define XDL 6
#define QW 0
#define PDS 61
#define P_NVR 5
#define P_NVP 2
#define P_NWP 9
#define P_NW1 7
#define RF_ 208
#define PSV 1
#define RA_ (488 - 2 * RF_)
#define XI 5
#define XL 1
#define WCH 2
#define HX 0
#define VB 1
#define HU_ 32
#define HP 2
#define HS 1
constexpr int HU = HU_;
#define TP 0
#define CKI 0
#define NOP_ 2
#define KVO 0
#define NDL 3
#define AM 0
#define XM 3
#define XP 0
#define SPIN_LIMIT (1 << 20)
__device__ __forceinline__ uint64_t mkdesc(uint32_t addr, uint32_t lbo, uint32_t sbo) {
  return (uint64_t)((addr & 0x3FFFF) >> 4) | ((uint64_t)(lbo >> 4) << 16) | ((uint64_t)(sbo >> 4) << 32) | (1ull << 62);
}
__device__ __forceinline__ void mbar_init(uint32_t a, int c) { asm volatile("mbarrier.init.shared.b64 [%0],%1;" ::"r"(a), "r"(c) : "memory"); }
__device__ __forceinline__ void mbar_wait(uint32_t a, uint32_t par) {
  asm volatile(
      "{.reg .pred p; .reg .u32 n;\n"
      "mov.u32 n, 0;\n"
      "W: mbarrier.try_wait.parity.shared.b64 p,[%0],%1;\n"
      "@p bra D;\n"
      "add.u32 n, n, 1;\n"
      "setp.lt.u32 p, n, %2;\n"
      "@p bra W;\n"
      "trap;\n"
      "D:}" ::"r"(a), "r"(par), "n"(SPIN_LIMIT) : "memory");
}
__device__ __forceinline__ void mbar_wait_q(uint32_t a, uint32_t par) {
  asm volatile(
      "{.reg .pred p; .reg .u32 n;\n"
      "mov.u32 n, 0;\n"
      "W: mbarrier.try_wait.parity.shared.b64 p,[%0],%1,4000;\n"
      "@p bra D;\n"
      "add.u32 n, n, 1;\n"
      "setp.lt.u32 p, n, %2;\n"
      "@p bra W;\n"
      "trap;\n"
      "D:}" ::"r"(a), "r"(par), "n"(SPIN_LIMIT / 16) : "memory");
}
__device__ __forceinline__ void mbar_expect(uint32_t a, uint32_t b) { asm volatile("mbarrier.arrive.expect_tx.shared.b64 _,[%0],%1;" ::"r"(a), "r"(b) : "memory"); }
__device__ __forceinline__ void mbar_arrive(uint32_t a) { asm volatile("mbarrier.arrive.shared.b64 _,[%0];" ::"r"(a) : "memory"); }
__device__ __forceinline__ uint32_t mapa(uint32_t a, uint32_t cta) { uint32_t r; asm("mapa.shared::cluster.u32 %0,%1,%2;" : "=r"(r) : "r"(a), "r"(cta)); return r; }
__device__ __forceinline__ void mbar_arrive_cl(uint32_t a) { asm volatile("mbarrier.arrive.shared::cluster.b64 _,[%0];" ::"r"(a) : "memory"); }
__device__ __forceinline__ void tma2d(uint32_t dst, const CUtensorMap* m, int c0, int c1, uint32_t mb) {
  asm volatile("cp.async.bulk.tensor.2d.shared::cluster.global.mbarrier::complete_tx::bytes [%0],[%1,{%2,%3}],[%4];" ::"r"(dst), "l"(m), "r"(c0), "r"(c1), "r"(mb) : "memory");
}
__device__ __forceinline__ void tma2d_pf(const CUtensorMap* m, int c0, int c1) {
  asm volatile("cp.async.bulk.prefetch.tensor.2d.L2.global [%0,{%1,%2}];" ::"l"(m), "r"(c0), "r"(c1) : "memory");
}
__device__ __forceinline__ void tma3d(uint32_t dst, const CUtensorMap* m, int c1, int c2, uint32_t mb) {
  asm volatile("cp.async.bulk.tensor.3d.shared::cluster.global.mbarrier::complete_tx::bytes [%0],[%1,{0,%2,%3}],[%4];" ::"r"(dst), "l"(m), "r"(c1), "r"(c2), "r"(mb) : "memory");
}
__device__ __forceinline__ void tma2d_st(const CUtensorMap* m, int c0, int c1, uint32_t src) {
  asm volatile("cp.async.bulk.tensor.2d.global.shared::cta.bulk_group [%0,{%1,%2}],[%3];" ::"l"(m), "r"(c0), "r"(c1), "r"(src) : "memory");
}
__device__ __forceinline__ void bulk_ld(uint32_t dst, const void* src, uint32_t n, uint32_t mb) {
  asm volatile("cp.async.bulk.shared::cluster.global.mbarrier::complete_tx::bytes [%0],[%1],%2,[%3];" ::"r"(dst), "l"(src), "r"(n), "r"(mb) : "memory");
}
__device__ __forceinline__ void bulk_ld_mc(uint32_t dst, const void* src, uint32_t n, uint32_t mb) {
  asm volatile("cp.async.bulk.shared::cluster.global.mbarrier::complete_tx::bytes.multicast::cluster [%0],[%1],%2,[%3],%4;" ::"r"(dst), "l"(src), "r"(n), "r"(mb), "h"((uint16_t)3) : "memory");
}
__device__ __forceinline__ void bulk_st(void* dst, uint32_t src, uint32_t n) {
  asm volatile("cp.async.bulk.global.shared::cta.bulk_group [%0],[%1],%2;" ::"l"(dst), "r"(src), "r"(n) : "memory");
}
__device__ __forceinline__ void e_expect_tma3d(uint32_t dst, const CUtensorMap* m, int c1, int c2, uint32_t mb, uint32_t bytes) {
  asm volatile("{.reg .pred p; elect.sync _|p, 0xffffffff; @p mbarrier.arrive.expect_tx.shared.b64 _,[%4],%5;\n"
               "@p cp.async.bulk.tensor.3d.shared::cluster.global.mbarrier::complete_tx::bytes [%0],[%1,{0,%2,%3}],[%4];}" ::"r"(dst), "l"(m), "r"(c1), "r"(c2), "r"(mb), "r"(bytes) : "memory");
}
__device__ __forceinline__ void e_bulk_ld(uint32_t dst, const void* src, uint32_t n, uint32_t mb) {
  asm volatile("{.reg .pred p; elect.sync _|p, 0xffffffff; @p cp.async.bulk.shared::cluster.global.mbarrier::complete_tx::bytes [%0],[%1],%2,[%3];}" ::"r"(dst), "l"(src), "r"(n), "r"(mb) : "memory");
}
__device__ __forceinline__ void e_bulk_ld_ef(uint32_t dst, const void* src, uint32_t n, uint32_t mb) {
  asm volatile("{.reg .pred p; .reg .b64 c; createpolicy.fractional.L2::evict_first.b64 c,1.0; elect.sync _|p, 0xffffffff;"
               " @p cp.async.bulk.shared::cluster.global.mbarrier::complete_tx::bytes.L2::cache_hint [%0],[%1],%2,[%3],c;}" ::"r"(dst), "l"(src), "r"(n), "r"(mb) : "memory");
}
__device__ __forceinline__ void e_bulk_ld_mc(uint32_t dst, const void* src, uint32_t n, uint32_t mb) {
  asm volatile("{.reg .pred p; elect.sync _|p, 0xffffffff; @p cp.async.bulk.shared::cluster.global.mbarrier::complete_tx::bytes.multicast::cluster [%0],[%1],%2,[%3],%4;}" ::"r"(dst), "l"(src), "r"(n), "r"(mb), "h"((uint16_t)3) : "memory");
}
#define BULK_COMMIT() asm volatile("cp.async.bulk.commit_group;" ::: "memory")
#define BULK_WAIT_READ(n) asm volatile("cp.async.bulk.wait_group.read " #n ";" ::: "memory")
#define BULK_WAIT(n) asm volatile("cp.async.bulk.wait_group " #n ";" ::: "memory")
#define FENCE_ASYNC_SMEM() asm volatile("fence.proxy.async.shared::cta;" ::: "memory")
#define FENCE_ASYNC() asm volatile("fence.proxy.async;" ::: "memory")
#define WG_FENCE() asm volatile("wgmma.fence.sync.aligned;" ::: "memory")
#define WG_COMMIT() asm volatile("wgmma.commit_group.sync.aligned;" ::: "memory")
#define WG_WAIT(n) asm volatile("wgmma.wait_group.sync.aligned " #n ";" ::: "memory")
#define BAR_SYNC(id, n) asm volatile("bar.sync %0,%1;" ::"n"(id), "n"(n) : "memory")
#define BAR_ARRIVE(id, n) asm volatile("bar.arrive %0,%1;" ::"n"(id), "n"(n) : "memory")
#define SCHED_FENCE(k) asm volatile("{.reg .pred p; setp.ne.u32 p,%0,0; @p trap;}" ::"r"(mp.zero[(k) - 46]) : "memory")
#define CLUSTER_SYNC() asm volatile("barrier.cluster.arrive.relaxed.aligned; barrier.cluster.wait.aligned;" ::: "memory")
__device__ __forceinline__ uint32_t pk(float lo, float hi) { uint32_t r; asm("cvt.rn.bf16x2.f32 %0,%1,%2;" : "=r"(r) : "f"(hi), "f"(lo)); return r; }
__device__ __forceinline__ float blo(uint32_t v) { return __uint_as_float(v << 16); }
__device__ __forceinline__ float bhi(uint32_t v) { return __uint_as_float(v & 0xffff0000u); }
__device__ __forceinline__ void ldsm4(uint32_t* r, uint32_t a) {
  asm volatile("ldmatrix.sync.aligned.m8n8.x4.shared.b16 {%0,%1,%2,%3},[%4];" : "=r"(r[0]), "=r"(r[1]), "=r"(r[2]), "=r"(r[3]) : "r"(a) : "memory");
}
__device__ __forceinline__ void ldsm4t(uint32_t* r, uint32_t a) {
  asm volatile("ldmatrix.sync.aligned.m8n8.x4.trans.shared.b16 {%0,%1,%2,%3},[%4];" : "=r"(r[0]), "=r"(r[1]), "=r"(r[2]), "=r"(r[3]) : "r"(a) : "memory");
}
__device__ __forceinline__ void stsm4(uint32_t a, uint32_t r0, uint32_t r1, uint32_t r2, uint32_t r3) {
  asm volatile("stmatrix.sync.aligned.m8n8.x4.shared.b16 [%0],{%1,%2,%3,%4};" ::"r"(a), "r"(r0), "r"(r1), "r"(r2), "r"(r3) : "memory");
}
__device__ __forceinline__ void mma16(float* d, uint32_t a0, uint32_t a1, uint32_t a2, uint32_t a3, uint32_t b0, uint32_t b1) {
  asm volatile("mma.sync.aligned.m16n8k16.row.col.f32.bf16.bf16.f32 {%0,%1,%2,%3},{%4,%5,%6,%7},{%8,%9},{%0,%1,%2,%3};"
               : "+f"(d[0]), "+f"(d[1]), "+f"(d[2]), "+f"(d[3]) : "r"(a0), "r"(a1), "r"(a2), "r"(a3), "r"(b0), "r"(b1));
}
__device__ __forceinline__ void mma8(float* d, uint32_t a0, uint32_t a1, uint32_t b0) {
  asm volatile("mma.sync.aligned.m16n8k8.row.col.f32.bf16.bf16.f32 {%0,%1,%2,%3},{%4,%5},{%6},{%0,%1,%2,%3};"
               : "+f"(d[0]), "+f"(d[1]), "+f"(d[2]), "+f"(d[3]) : "r"(a0), "r"(a1), "r"(b0));
}
__device__ __forceinline__ float4 lds4f(uint32_t a) { float4 v; asm volatile("ld.shared.v4.f32 {%0,%1,%2,%3},[%4];" : "=f"(v.x), "=f"(v.y), "=f"(v.z), "=f"(v.w) : "r"(a) : "memory"); return v; }
__device__ __forceinline__ float2 lds2f(uint32_t a) { float2 v; asm volatile("ld.shared.v2.f32 {%0,%1},[%2];" : "=f"(v.x), "=f"(v.y) : "r"(a) : "memory"); return v; }
__device__ __forceinline__ uint4 lds4(uint32_t a) { uint4 v; asm volatile("ld.shared.v4.u32 {%0,%1,%2,%3},[%4];" : "=r"(v.x), "=r"(v.y), "=r"(v.z), "=r"(v.w) : "r"(a) : "memory"); return v; }
__device__ __forceinline__ uint2 lds2u(uint32_t a) { uint2 v; asm volatile("ld.shared.v2.u32 {%0,%1},[%2];" : "=r"(v.x), "=r"(v.y) : "r"(a) : "memory"); return v; }
__device__ __forceinline__ uint32_t lds1(uint32_t a) { uint32_t v; asm volatile("ld.shared.u32 %0,[%1];" : "=r"(v) : "r"(a) : "memory"); return v; }
__device__ __forceinline__ void sts4(uint32_t a, uint32_t x, uint32_t y, uint32_t z, uint32_t w) { asm volatile("st.shared.v4.u32 [%0],{%1,%2,%3,%4};" ::"r"(a), "r"(x), "r"(y), "r"(z), "r"(w) : "memory"); }
__device__ __forceinline__ void sts2(uint32_t a, uint32_t x, uint32_t y) { asm volatile("st.shared.v2.u32 [%0],{%1,%2};" ::"r"(a), "r"(x), "r"(y) : "memory"); }
__device__ __forceinline__ void sts1(uint32_t a, uint32_t x) { asm volatile("st.shared.u32 [%0],%1;" ::"r"(a), "r"(x) : "memory"); }
__device__ __forceinline__ void sta4(uint32_t a, const uint32_t* v, uint32_t mb) {
  asm volatile("st.async.shared::cluster.mbarrier::complete_tx::bytes.v4.b32 [%0],{%1,%2,%3,%4},[%5];" ::"r"(a), "r"(v[0]), "r"(v[1]), "r"(v[2]), "r"(v[3]), "r"(mb) : "memory");
}
__device__ __forceinline__ uint4 ldg_rlx4(const void* p) { uint4 v; asm volatile("ld.relaxed.gpu.global.v4.u32 {%0,%1,%2,%3},[%4];" : "=r"(v.x), "=r"(v.y), "=r"(v.z), "=r"(v.w) : "l"(p) : "memory"); return v; }
__device__ __forceinline__ uint32_t ldg_rlx1(const void* p) { uint32_t v; asm volatile("ld.relaxed.gpu.global.u32 %0,[%1];" : "=r"(v) : "l"(p) : "memory"); return v; }
__device__ __forceinline__ uint2 ldg_rlx2(const void* p) { uint2 v; asm volatile("ld.relaxed.gpu.global.v2.u32 {%0,%1},[%2];" : "=r"(v.x), "=r"(v.y) : "l"(p) : "memory"); return v; }
__device__ __forceinline__ uint4 ldg_b128(const void* p) {
  uint4 v;
  asm volatile("{.reg .b128 t; .reg .b64 a,b; ld.relaxed.gpu.global.b128 t,[%4]; mov.b128 {a,b},t; mov.b64 {%0,%1},a; mov.b64 {%2,%3},b;}" : "=r"(v.x), "=r"(v.y), "=r"(v.z), "=r"(v.w) : "l"(p) : "memory");
  return v;
}
__device__ __forceinline__ void stg_b128(void* p, uint32_t x, uint32_t y, uint32_t z, uint32_t w) {
  asm volatile("{.reg .b128 t; .reg .b64 a,b; mov.b64 a,{%1,%2}; mov.b64 b,{%3,%4}; mov.b128 t,{a,b}; st.relaxed.gpu.global.b128 [%0],t;}" ::"l"(p), "r"(x), "r"(y), "r"(z), "r"(w) : "memory");
}
__device__ __forceinline__ void st_b128(void* p, uint32_t x, uint32_t y, uint32_t z, uint32_t w) {
  asm volatile("{.reg .b128 t; .reg .b64 a,b; mov.b64 a,{%1,%2}; mov.b64 b,{%3,%4}; mov.b128 t,{a,b}; st.relaxed.gpu.b128 [%0],t;}" ::"l"(p), "r"(x), "r"(y), "r"(z), "r"(w) : "memory");
}
__device__ __forceinline__ void stg_rlx4(void* p, uint32_t x, uint32_t y, uint32_t z, uint32_t w) { asm volatile("st.relaxed.gpu.global.v4.u32 [%0],{%1,%2,%3,%4};" ::"l"(p), "r"(x), "r"(y), "r"(z), "r"(w) : "memory"); }
__device__ __forceinline__ void stg_rlx2(void* p, uint32_t x, uint32_t y) { asm volatile("st.relaxed.gpu.global.v2.u32 [%0],{%1,%2};" ::"l"(p), "r"(x), "r"(y) : "memory"); }
__device__ __forceinline__ void red4(void* p, float a, float b, float c, float d) { asm volatile("red.relaxed.gpu.global.add.v4.f32 [%0],{%1,%2,%3,%4};" ::"l"(p), "f"(a), "f"(b), "f"(c), "f"(d) : "memory"); }
__device__ __forceinline__ unsigned ld_acq(const unsigned* p) { unsigned v; asm volatile("ld.acquire.gpu.global.u32 %0,[%1];" : "=r"(v) : "l"(p) : "memory"); return v; }
__device__ __forceinline__ void red_rel(unsigned* p) { asm volatile("red.release.gpu.global.add.u32 [%0],1;" ::"l"(p) : "memory"); }
__device__ __forceinline__ void red_rlx(unsigned* p) { asm volatile("red.relaxed.gpu.global.add.u32 [%0],1;" ::"l"(p) : "memory"); }
__device__ __forceinline__ void wait_cnt(const unsigned* p, unsigned n) { int it = 0; while (ld_acq(p) < n) { if (++it > SPIN_LIMIT) __trap(); } }
__device__ __forceinline__ uint32_t clk() { uint32_t c; asm volatile("mov.u32 %0,%%clock;" : "=r"(c)); return c; }
__device__ __forceinline__ uint32_t gtime() { uint32_t c; asm volatile("mov.u32 %0,%%globaltimer_lo;" : "=r"(c)); return c; }
__device__ __forceinline__ void wait_until(uint32_t t0, uint32_t d) { while (clk() - t0 < d) {} }
__device__ __forceinline__ float ex2(float x) { float r; asm("ex2.approx.ftz.f32 %0,%1;" : "=f"(r) : "f"(x)); return r; }
__device__ __forceinline__ float silu(float x) { return x * __frcp_rn(1.f + __expf(-x)); }
__device__ __forceinline__ float rbf(float x) { return __bfloat162float(__float2bfloat16_rn(x)); }

__device__ __forceinline__ void wgmma_ss_n128(float* d, uint64_t a, uint64_t b, int sd) {
  asm volatile("{.reg .pred p; setp.ne.b32 p, %66, 0;\n"
    "wgmma.mma_async.sync.aligned.m64n128k16.f32.bf16.bf16 {%0,%1,%2,%3,%4,%5,%6,%7,%8,%9,%10,%11,%12,%13,%14,%15,%16,%17,%18,%19,%20,%21,%22,%23,%24,%25,%26,%27,%28,%29,%30,%31,%32,%33,%34,%35,%36,%37,%38,%39,%40,%41,%42,%43,%44,%45,%46,%47,%48,%49,%50,%51,%52,%53,%54,%55,%56,%57,%58,%59,%60,%61,%62,%63}, %64, %65, p, 1, 1, 0, 1;}\n"
    : "+f"(d[0]),"+f"(d[1]),"+f"(d[2]),"+f"(d[3]),"+f"(d[4]),"+f"(d[5]),"+f"(d[6]),"+f"(d[7]),
      "+f"(d[8]),"+f"(d[9]),"+f"(d[10]),"+f"(d[11]),"+f"(d[12]),"+f"(d[13]),"+f"(d[14]),"+f"(d[15]),
      "+f"(d[16]),"+f"(d[17]),"+f"(d[18]),"+f"(d[19]),"+f"(d[20]),"+f"(d[21]),"+f"(d[22]),"+f"(d[23]),
      "+f"(d[24]),"+f"(d[25]),"+f"(d[26]),"+f"(d[27]),"+f"(d[28]),"+f"(d[29]),"+f"(d[30]),"+f"(d[31]),
      "+f"(d[32]),"+f"(d[33]),"+f"(d[34]),"+f"(d[35]),"+f"(d[36]),"+f"(d[37]),"+f"(d[38]),"+f"(d[39]),
      "+f"(d[40]),"+f"(d[41]),"+f"(d[42]),"+f"(d[43]),"+f"(d[44]),"+f"(d[45]),"+f"(d[46]),"+f"(d[47]),
      "+f"(d[48]),"+f"(d[49]),"+f"(d[50]),"+f"(d[51]),"+f"(d[52]),"+f"(d[53]),"+f"(d[54]),"+f"(d[55]),
      "+f"(d[56]),"+f"(d[57]),"+f"(d[58]),"+f"(d[59]),"+f"(d[60]),"+f"(d[61]),"+f"(d[62]),"+f"(d[63])
    : "l"(a), "l"(b), "r"(sd));
}
__device__ __forceinline__ void wgmma_ss_n192(float* d, uint64_t a, uint64_t b, int sd) {
  asm volatile("{.reg .pred p; setp.ne.b32 p, %98, 0;\n"
    "wgmma.mma_async.sync.aligned.m64n192k16.f32.bf16.bf16 {%0,%1,%2,%3,%4,%5,%6,%7,%8,%9,%10,%11,%12,%13,%14,%15,%16,%17,%18,%19,%20,%21,%22,%23,%24,%25,%26,%27,%28,%29,%30,%31,%32,%33,%34,%35,%36,%37,%38,%39,%40,%41,%42,%43,%44,%45,%46,%47,%48,%49,%50,%51,%52,%53,%54,%55,%56,%57,%58,%59,%60,%61,%62,%63,%64,%65,%66,%67,%68,%69,%70,%71,%72,%73,%74,%75,%76,%77,%78,%79,%80,%81,%82,%83,%84,%85,%86,%87,%88,%89,%90,%91,%92,%93,%94,%95}, %96, %97, p, 1, 1, 0, 1;}\n"
    : "+f"(d[0]),"+f"(d[1]),"+f"(d[2]),"+f"(d[3]),"+f"(d[4]),"+f"(d[5]),"+f"(d[6]),"+f"(d[7]),
      "+f"(d[8]),"+f"(d[9]),"+f"(d[10]),"+f"(d[11]),"+f"(d[12]),"+f"(d[13]),"+f"(d[14]),"+f"(d[15]),
      "+f"(d[16]),"+f"(d[17]),"+f"(d[18]),"+f"(d[19]),"+f"(d[20]),"+f"(d[21]),"+f"(d[22]),"+f"(d[23]),
      "+f"(d[24]),"+f"(d[25]),"+f"(d[26]),"+f"(d[27]),"+f"(d[28]),"+f"(d[29]),"+f"(d[30]),"+f"(d[31]),
      "+f"(d[32]),"+f"(d[33]),"+f"(d[34]),"+f"(d[35]),"+f"(d[36]),"+f"(d[37]),"+f"(d[38]),"+f"(d[39]),
      "+f"(d[40]),"+f"(d[41]),"+f"(d[42]),"+f"(d[43]),"+f"(d[44]),"+f"(d[45]),"+f"(d[46]),"+f"(d[47]),
      "+f"(d[48]),"+f"(d[49]),"+f"(d[50]),"+f"(d[51]),"+f"(d[52]),"+f"(d[53]),"+f"(d[54]),"+f"(d[55]),
      "+f"(d[56]),"+f"(d[57]),"+f"(d[58]),"+f"(d[59]),"+f"(d[60]),"+f"(d[61]),"+f"(d[62]),"+f"(d[63]),
      "+f"(d[64]),"+f"(d[65]),"+f"(d[66]),"+f"(d[67]),"+f"(d[68]),"+f"(d[69]),"+f"(d[70]),"+f"(d[71]),
      "+f"(d[72]),"+f"(d[73]),"+f"(d[74]),"+f"(d[75]),"+f"(d[76]),"+f"(d[77]),"+f"(d[78]),"+f"(d[79]),
      "+f"(d[80]),"+f"(d[81]),"+f"(d[82]),"+f"(d[83]),"+f"(d[84]),"+f"(d[85]),"+f"(d[86]),"+f"(d[87]),
      "+f"(d[88]),"+f"(d[89]),"+f"(d[90]),"+f"(d[91]),"+f"(d[92]),"+f"(d[93]),"+f"(d[94]),"+f"(d[95])
    : "l"(a), "l"(b), "r"(sd));
}
__device__ __forceinline__ void wgmma_ss_n256(float* d, uint64_t a, uint64_t b, int sd) {
  asm volatile("{.reg .pred p; setp.ne.b32 p, %130, 0;\n"
    "wgmma.mma_async.sync.aligned.m64n256k16.f32.bf16.bf16 {%0,%1,%2,%3,%4,%5,%6,%7,%8,%9,%10,%11,%12,%13,%14,%15,%16,%17,%18,%19,%20,%21,%22,%23,%24,%25,%26,%27,%28,%29,%30,%31,%32,%33,%34,%35,%36,%37,%38,%39,%40,%41,%42,%43,%44,%45,%46,%47,%48,%49,%50,%51,%52,%53,%54,%55,%56,%57,%58,%59,%60,%61,%62,%63,%64,%65,%66,%67,%68,%69,%70,%71,%72,%73,%74,%75,%76,%77,%78,%79,%80,%81,%82,%83,%84,%85,%86,%87,%88,%89,%90,%91,%92,%93,%94,%95,%96,%97,%98,%99,%100,%101,%102,%103,%104,%105,%106,%107,%108,%109,%110,%111,%112,%113,%114,%115,%116,%117,%118,%119,%120,%121,%122,%123,%124,%125,%126,%127}, %128, %129, p, 1, 1, 0, 1;}\n"
    : "+f"(d[0]),"+f"(d[1]),"+f"(d[2]),"+f"(d[3]),"+f"(d[4]),"+f"(d[5]),"+f"(d[6]),"+f"(d[7]),
      "+f"(d[8]),"+f"(d[9]),"+f"(d[10]),"+f"(d[11]),"+f"(d[12]),"+f"(d[13]),"+f"(d[14]),"+f"(d[15]),
      "+f"(d[16]),"+f"(d[17]),"+f"(d[18]),"+f"(d[19]),"+f"(d[20]),"+f"(d[21]),"+f"(d[22]),"+f"(d[23]),
      "+f"(d[24]),"+f"(d[25]),"+f"(d[26]),"+f"(d[27]),"+f"(d[28]),"+f"(d[29]),"+f"(d[30]),"+f"(d[31]),
      "+f"(d[32]),"+f"(d[33]),"+f"(d[34]),"+f"(d[35]),"+f"(d[36]),"+f"(d[37]),"+f"(d[38]),"+f"(d[39]),
      "+f"(d[40]),"+f"(d[41]),"+f"(d[42]),"+f"(d[43]),"+f"(d[44]),"+f"(d[45]),"+f"(d[46]),"+f"(d[47]),
      "+f"(d[48]),"+f"(d[49]),"+f"(d[50]),"+f"(d[51]),"+f"(d[52]),"+f"(d[53]),"+f"(d[54]),"+f"(d[55]),
      "+f"(d[56]),"+f"(d[57]),"+f"(d[58]),"+f"(d[59]),"+f"(d[60]),"+f"(d[61]),"+f"(d[62]),"+f"(d[63]),
      "+f"(d[64]),"+f"(d[65]),"+f"(d[66]),"+f"(d[67]),"+f"(d[68]),"+f"(d[69]),"+f"(d[70]),"+f"(d[71]),
      "+f"(d[72]),"+f"(d[73]),"+f"(d[74]),"+f"(d[75]),"+f"(d[76]),"+f"(d[77]),"+f"(d[78]),"+f"(d[79]),
      "+f"(d[80]),"+f"(d[81]),"+f"(d[82]),"+f"(d[83]),"+f"(d[84]),"+f"(d[85]),"+f"(d[86]),"+f"(d[87]),
      "+f"(d[88]),"+f"(d[89]),"+f"(d[90]),"+f"(d[91]),"+f"(d[92]),"+f"(d[93]),"+f"(d[94]),"+f"(d[95]),
      "+f"(d[96]),"+f"(d[97]),"+f"(d[98]),"+f"(d[99]),"+f"(d[100]),"+f"(d[101]),"+f"(d[102]),"+f"(d[103]),
      "+f"(d[104]),"+f"(d[105]),"+f"(d[106]),"+f"(d[107]),"+f"(d[108]),"+f"(d[109]),"+f"(d[110]),"+f"(d[111]),
      "+f"(d[112]),"+f"(d[113]),"+f"(d[114]),"+f"(d[115]),"+f"(d[116]),"+f"(d[117]),"+f"(d[118]),"+f"(d[119]),
      "+f"(d[120]),"+f"(d[121]),"+f"(d[122]),"+f"(d[123]),"+f"(d[124]),"+f"(d[125]),"+f"(d[126]),"+f"(d[127])
    : "l"(a), "l"(b), "r"(sd));
}
__device__ __forceinline__ void wgmma_rs_n32(float* d, const uint32_t* a, uint64_t b, int sd) {
  asm volatile("{.reg .pred p; setp.ne.b32 p, %21, 0;\n"
    "wgmma.mma_async.sync.aligned.m64n32k16.f32.bf16.bf16 {%0,%1,%2,%3,%4,%5,%6,%7,%8,%9,%10,%11,%12,%13,%14,%15}, {%16,%17,%18,%19}, %20, p, 1, 1, 0;}\n"
    : "+f"(d[0]),"+f"(d[1]),"+f"(d[2]),"+f"(d[3]),"+f"(d[4]),"+f"(d[5]),"+f"(d[6]),"+f"(d[7]),
      "+f"(d[8]),"+f"(d[9]),"+f"(d[10]),"+f"(d[11]),"+f"(d[12]),"+f"(d[13]),"+f"(d[14]),"+f"(d[15])
    : "r"(a[0]), "r"(a[1]), "r"(a[2]), "r"(a[3]), "l"(b), "r"(sd));
}
__device__ __forceinline__ void wgmma_ssT_n32(float* d, uint64_t a, uint64_t b, int sd) {
  asm volatile("{.reg .pred p; setp.ne.b32 p, %18, 0;\n"
    "wgmma.mma_async.sync.aligned.m64n32k16.f32.bf16.bf16 {%0,%1,%2,%3,%4,%5,%6,%7,%8,%9,%10,%11,%12,%13,%14,%15}, %16, %17, p, 1, 1, 1, 0;}\n"
    : "+f"(d[0]),"+f"(d[1]),"+f"(d[2]),"+f"(d[3]),"+f"(d[4]),"+f"(d[5]),"+f"(d[6]),"+f"(d[7]),
      "+f"(d[8]),"+f"(d[9]),"+f"(d[10]),"+f"(d[11]),"+f"(d[12]),"+f"(d[13]),"+f"(d[14]),"+f"(d[15])
    : "l"(a), "l"(b), "r"(sd));
}

__device__ __forceinline__ void wgmma_rs_n32_z(float* d, const uint32_t* a, uint64_t b) {
  asm volatile("{.reg .pred p; setp.ne.b32 p, 0, 0;\n"
    "wgmma.mma_async.sync.aligned.m64n32k16.f32.bf16.bf16 {%0,%1,%2,%3,%4,%5,%6,%7,%8,%9,%10,%11,%12,%13,%14,%15}, {%16,%17,%18,%19}, %20, p, 1, 1, 0;}\n"
    : "=f"(d[0]),"=f"(d[1]),"=f"(d[2]),"=f"(d[3]),"=f"(d[4]),"=f"(d[5]),"=f"(d[6]),"=f"(d[7]),
      "=f"(d[8]),"=f"(d[9]),"=f"(d[10]),"=f"(d[11]),"=f"(d[12]),"=f"(d[13]),"=f"(d[14]),"=f"(d[15])
    : "r"(a[0]), "r"(a[1]), "r"(a[2]), "r"(a[3]), "l"(b));
}

namespace rec {
constexpr int NVR = P_NVR;
constexpr int NVS = 16 - NVR;
constexpr int NVP = P_NVP;
constexpr int NWP = P_NWP;
constexpr uint32_t WO = 0;
constexpr uint32_t XB = 65536;
constexpr uint32_t PK = XB + 32768;
constexpr uint32_t VN = PK + 24576;
constexpr uint32_t VX0 = VN + 4096;
constexpr uint32_t WVS = 131072;
constexpr uint32_t MEM = WVS + 2 * NVS * 2048;
constexpr uint32_t ARO = MEM + 10240;
constexpr uint32_t OB = ARO + 5120;
constexpr uint32_t QT = OB + 2048;
constexpr uint32_t KT = QT + 2048;
constexpr uint32_t RQ = KT + 6144;
constexpr uint32_t RK = RQ + 2048;
constexpr uint32_t SC = RK + 2048;
constexpr uint32_t OT = OB;
constexpr uint32_t TF = SC + 2048;
constexpr uint32_t PRE = MEM + 2 * NVR * 2048;
constexpr uint32_t TA = TF + 8192;
constexpr uint32_t RX = TA + 6144;
constexpr uint32_t VX1 = RX + 2048;
constexpr uint32_t BARS = VX1 + 4096;
constexpr uint32_t PACE = BARS + 18 * 8;
constexpr uint32_t SMEM = BARS + 512;
static_assert(PRE + 14336 <= BARS, "staging");
constexpr int NW1 = P_NW1;
static_assert(SMEM <= 232448, "smem");
constexpr int B_E = 2, B_SC = 3, B_S = 4, B_O = 5, B_F = 6, B_W = 7, B_C = 9, B_K = 10, B_H = 15, B_Q = 1, B_S2 = 6, B_T2 = 9, B_P = 13, B_T = 14, B_R = 11, B_X = 12, B_V = 8;
constexpr int XC = 16384, X_RING = 131072, X_PT = 4096, X_SC = 65536, X_TOK = 4096;
#define X_VX(i) (((i) >> 1) * 2048 + ((i) & 1) * 512)
#define X_VM(i) (X_VX(i) + 1024)
}
struct RecMaps { CUtensorMap wq, wk, wv, wo, ari; int zero[40]; };

#define F_(x) __uint_as_float(x)
#define U_(x) __float_as_uint(x)
__device__ __forceinline__ void ar_fetch(uint32_t dst, const CUtensorMap* m, int slot, int half, uint32_t mb) {
  asm volatile("{.reg .pred p; elect.sync _|p, 0xffffffff; @p mbarrier.arrive.expect_tx.shared.b64 _,[%4],10240;\n"
               "@p cp.async.bulk.tensor.2d.shared::cluster.global.mbarrier::complete_tx::bytes [%0],[%1,{%2,%3}],[%4];\n"
               "@p cp.async.bulk.tensor.2d.shared::cluster.global.mbarrier::complete_tx::bytes [%0+5120],[%1,{%2,%5}],[%4];}"
               ::"r"(dst), "l"(m), "r"(slot * 64), "r"(half * 80), "r"(mb), "r"(half * 80 + 40) : "memory");
}
__device__ __forceinline__ void ar_fetch1(uint32_t dst, const CUtensorMap* m, int slot, int quarter, uint32_t mb) {
  asm volatile("{.reg .pred p; elect.sync _|p, 0xffffffff; @p mbarrier.arrive.expect_tx.shared.b64 _,[%4],5120;\n"
               "@p cp.async.bulk.tensor.2d.shared::cluster.global.mbarrier::complete_tx::bytes [%0],[%1,{%2,%3}],[%4];}"
               ::"r"(dst), "l"(m), "r"(slot * 64), "r"(quarter * 40), "r"(mb) : "memory");
}
__device__ __forceinline__ uint4 exch_b128(void* p, uint32_t x, uint32_t y, uint32_t z, uint32_t w) {
  uint4 v;
  asm volatile("{.reg .b128 s, t; .reg .b64 a,b; mov.b64 a,{%5,%6}; mov.b64 b,{%7,%8}; mov.b128 s,{a,b}; atom.relaxed.gpu.global.exch.b128 t,[%4],s;"
               " mov.b128 {a,b},t; mov.b64 {%0,%1},a; mov.b64 {%2,%3},b;}" : "=r"(v.x), "=r"(v.y), "=r"(v.z), "=r"(v.w) : "l"(p), "r"(x), "r"(y), "r"(z), "r"(w) : "memory");
  return v;
}
#define CONSUME(v) do { if ((v) == 0x7fc12345u) sts1(sb + rec::BARS + 96, 0); } while (0)
__device__ __forceinline__ uint32_t tagf(float v, uint32_t tag) { return (__float_as_uint(v) & ~1u) | tag; }
__device__ __forceinline__ uint2 ldg_b64(const void* p) { uint2 v; asm volatile("{.reg .b64 t; ld.relaxed.gpu.global.b64 t,[%2]; mov.b64 {%0,%1},t;}" : "=r"(v.x), "=r"(v.y) : "l"(p) : "memory"); return v; }
__device__ __forceinline__ void stg_b64(void* p, uint32_t x, uint32_t y) { asm volatile("{.reg .b64 t; mov.b64 t,{%1,%2}; st.relaxed.gpu.global.b64 [%0],t;}" ::"l"(p), "r"(x), "r"(y) : "memory"); }
__device__ __forceinline__ uint32_t tagbad(uint32_t x, uint32_t y, uint32_t tag) { uint32_t r; asm("lop3.b32 %0,%1,%2,%3,0x7e;" : "=r"(r) : "r"(x), "r"(y), "r"(tag)); return r; }

__device__ __forceinline__ bool anybad(uint32_t a, uint32_t b, uint32_t c, uint32_t d, uint32_t e, uint32_t f, uint32_t g, uint32_t h, uint32_t tag) {
  uint32_t r;
  asm volatile("{.reg .b32 t,u,v,w; .reg .pred p; lop3.b32 t,%1,%2,%9,0x7e; lop3.b32 u,%3,%4,%9,0x7e; lop3.b32 v,%5,%6,%9,0x7e; lop3.b32 w,%7,%8,%9,0x7e;"
               " lop3.b32 t,t,u,v,0xfe; lop3.b32 t,t,w,1,0xa8; setp.ne.u32 p,t,0; vote.sync.any.pred p,p,0xffffffff; selp.u32 %0,1,0,p;}"
               : "=r"(r) : "r"(a), "r"(b), "r"(c), "r"(d), "r"(e), "r"(f), "r"(g), "r"(h), "r"(tag));
  return r;
}
__device__ __forceinline__ bool anybad(uint32_t a, uint32_t b, uint32_t c, uint32_t d, uint32_t tag) {
  uint32_t r;
  asm volatile("{.reg .b32 t,u; .reg .pred p; lop3.b32 t,%1,%2,%5,0x7e; lop3.b32 u,%3,%4,%5,0x7e;"
               " lop3.b32 t,t,u,1,0xa8; setp.ne.u32 p,t,0; vote.sync.any.pred p,p,0xffffffff; selp.u32 %0,1,0,p;}"
               : "=r"(r) : "r"(a), "r"(b), "r"(c), "r"(d), "r"(tag));
  return r;
}
#define BAD8(r) anybad(r[0].x, r[0].z, r[1].x, r[1].z, r[2].x, r[2].z, r[3].x, r[3].z, tag)
#define BADS(r) anybad(r[0].x, r[0].y, r[1].x, r[1].y, r[2].x, r[2].y, r[3].x, r[3].y, tag)
constexpr float SCS = 0.08838834764831845f * 1.4426950408889634f / 16.f;
__device__ __forceinline__ uint32_t pkh(float lo, float hi, uint32_t tag) {
  uint32_t r;
  asm("{.reg .b32 t; cvt.rn.satfinite.f16x2.f32 t,%1,%2; lop3.b32 %0,t,0xfffffffe,%3,0xea;}" : "=r"(r) : "f"(hi), "f"(lo), "r"(tag));
  return r;
}
__device__ __forceinline__ uint32_t addh(uint32_t a, uint32_t b) { uint32_t r; asm("add.rn.f16x2 %0,%1,%2;" : "=r"(r) : "r"(a), "r"(b)); return r; }
__device__ __forceinline__ float hlo(uint32_t v) { float r; asm("{.reg .b16 a,b; mov.b32 {a,b},%1; cvt.f32.f16 %0,a;}" : "=f"(r) : "r"(v)); return r; }
__device__ __forceinline__ float hhi(uint32_t v) { float r; asm("{.reg .b16 a,b; mov.b32 {a,b},%1; cvt.f32.f16 %0,b;}" : "=f"(r) : "r"(v)); return r; }
__device__ __forceinline__ uint32_t ordh(uint32_t v) {
  uint32_t r;
  asm("{.reg .b32 m; prmt.b32 m,%1,0,0xbb99; lop3.b32 %0,%1,m,0x7fff7fff,0x78;}" : "=r"(r) : "r"(v));
  return r;
}
template <bool MASK>
__device__ __forceinline__ float4 softmax2(const uint2 (&r)[4], uint32_t mx, uint32_t my) {
  uint32_t x = addh(addh(r[0].x, r[1].x), addh(r[2].x, r[3].x)), y = addh(addh(r[0].y, r[1].y), addh(r[2].y, r[3].y)), k;
  if (MASK) x = addh(x, mx);
  y = addh(y, my);
  asm("max.f16x2 %0,%1,%2;" : "=r"(k) : "r"(x), "r"(y));
  k = ordh(k);
  const int k0 = __reduce_max_sync(~0u, (int)(k << 16)), k1 = __reduce_max_sync(~0u, (int)k);
  k = ordh(__byte_perm(k0, k1, 0x7632));
  const float m0 = hlo(k) * -16.f, m1 = hhi(k) * -16.f;
  return make_float4(ex2(fmaf(hlo(x), 16.f, m0)), ex2(fmaf(hhi(x), 16.f, m1)), ex2(fmaf(hlo(y), 16.f, m0)), ex2(fmaf(hhi(y), 16.f, m1)));
}
__device__ __forceinline__ char* mkp(uint32_t lo, uint32_t hi) { uint64_t r; asm("mov.b64 %0,{%1,%2};" : "=l"(r) : "r"(lo), "r"(hi)); return (char*)r; }
#define LO(p) ((uint32_t)(uint64_t)(p))
#define HI(p) ((uint32_t)((uint64_t)(p) >> 32))
__device__ __forceinline__ void cp16(uint32_t dst, const void* src) { asm volatile("cp.async.cg.shared.global [%0],[%1],16;" ::"r"(dst), "l"(src) : "memory"); }
__device__ __forceinline__ uint32_t xor3(uint32_t a, uint32_t b, uint32_t c) { uint32_t r; asm volatile("lop3.b32 %0,%1,%2,%3,0x96;" : "=r"(r) : "r"(a), "r"(b), "r"(c)); return r; }
__device__ __forceinline__ uint32_t mulbf(uint32_t a, uint32_t b) { uint32_t r; asm("mul.rn.bf16x2 %0,%1,%2;" : "=r"(r) : "r"(a), "r"(b)); return r; }
__device__ __forceinline__ uint32_t addbf(uint32_t a, uint32_t b) { uint32_t r; asm("add.rn.bf16x2 %0,%1,%2;" : "=r"(r) : "r"(a), "r"(b)); return r; }
__device__ __forceinline__ void pv_mem(const uint32_t (&p)[4], uint32_t pm, const uint4 (&v)[4], const uint4 (&vn)[2], uint32_t (&O)[4]) {
  float o[4][4] = {{0, 0, 0, 0}, {0, 0, 0, 0}, {0, 0, 0, 0}, {0, 0, 0, 0}};
  mma16(o[0], v[0].x, v[0].y, v[0].z, v[0].w, p[0], p[1]);
  mma16(o[1], v[2].x, v[2].y, v[2].z, v[2].w, p[0], p[1]);
  mma16(o[2], v[1].x, v[1].y, v[1].z, v[1].w, p[2], p[3]);
  mma16(o[3], v[3].x, v[3].y, v[3].z, v[3].w, p[2], p[3]);
  mma16(o[0], vn[0].x, vn[0].y, vn[0].z, vn[0].w, pm, pm);
  mma16(o[1], vn[1].x, vn[1].y, vn[1].z, vn[1].w, pm, pm);
  O[0] = pk(o[0][0] + o[2][0], o[0][1] + o[2][1]); O[1] = pk(o[0][2] + o[2][2], o[0][3] + o[2][3]);
  O[2] = pk(o[1][0] + o[3][0], o[1][1] + o[3][1]); O[3] = pk(o[1][2] + o[3][2], o[1][3] + o[3][3]);
}
__device__ __forceinline__ void pv_tok(const uint32_t (&p)[4], uint32_t pm, const uint4 (&v)[4], const uint32_t (&vm)[4], uint32_t (&O)[4]) {
  float o[2][4] = {{0, 0, 0, 0}, {0, 0, 0, 0}}, sum[4] = {0, 0, 0, 0};
  const uint32_t one = 0x3f803f80u;
  mma16(sum, one, one, one, one, p[0], p[1]);
  mma16(o[0], v[0].x, v[0].y, v[0].z, v[0].w, p[0], p[1]);
  mma16(o[1], v[2].x, v[2].y, v[2].z, v[2].w, p[0], p[1]);
  mma16(sum, one, one, one, one, p[2], p[3]);
  mma16(o[0], v[1].x, v[1].y, v[1].z, v[1].w, p[2], p[3]);
  mma16(o[1], v[3].x, v[3].y, v[3].z, v[3].w, p[2], p[3]);
  mma8(sum, one, one, pm);
  mma8(o[0], vm[0], vm[1], pm);
  mma8(o[1], vm[2], vm[3], pm);
  float i0, i1;
  asm("rcp.approx.ftz.f32 %0,%1;" : "=f"(i0) : "f"(sum[0]));
  asm("rcp.approx.ftz.f32 %0,%1;" : "=f"(i1) : "f"(sum[1]));
  O[0] = pk(o[0][0] * i0, o[0][1] * i1); O[1] = pk(o[0][2] * i0, o[0][3] * i1);
  O[2] = pk(o[1][0] * i0, o[1][1] * i1); O[3] = pk(o[1][2] * i0, o[1][3] * i1);
}
__device__ __forceinline__ uint32_t sum4bf(uint32_t a, uint32_t b, uint32_t c, uint32_t d) { return addbf(addbf(a, b), addbf(c, d)); }
template <int OFF>
__device__ __forceinline__ void sta1(uint32_t a, uint32_t v, uint32_t mb) {
  asm volatile("st.async.shared::cluster.mbarrier::complete_tx::bytes.b32 [%0+%3],%1,[%2];" ::"r"(a), "r"(v), "r"(mb), "n"(OFF) : "memory");
}

__device__ __forceinline__ void rec_helper(char* smem, const bf16* cvec, const bf16* wmod, const char* w1, const bf16* b1, const char* x, const char* wo) {
  const int tid = threadIdx.x, hb = blockIdx.x - 128;
  const uint32_t t0 = gtime();
  float* sc = (float*)smem;
  float* red = sc + 1024;
  for (int i = tid; i < 1024; i += 256) { const float v = __bfloat162float(cvec[i]); sc[i] = rbf(silu(v)); }
  for (int i = tid; i < 2048; i += 256) g_stat[hb * 2048 + i] = make_uint4(~0u, ~0u, ~0u, ~0u);
  for (int i = tid; i < 512; i += 256) g_cnt[hb * 512 + i] = 0;
  if (tid == 0) {
    wait_cnt(&g_hcnt, 128);
    if (HP)
      for (int r = 0; r < 1024; r++) {
        asm volatile("cp.async.bulk.prefetch.L2.global [%0], 2048;" ::"l"(wmod + (size_t)r * 6144 + 2048 + hb * 1024) : "memory");
        if ((r & 7) == 7) __nanosleep(250);
      }
  }
  BAR_SYNC(rec::B_F, 256);
  const int rg = tid >> 7, cg = tid & 127;
  float acc[8] = {0, 0, 0, 0, 0, 0, 0, 0};
  const uint4* p = (const uint4*)(wmod + 2048 + hb * 1024) + cg;
#pragma unroll 1
  for (int r0 = 0; r0 < 1024; r0 += 2 * HU) {
    __nanosleep(HS);
#pragma unroll
  for (int r = r0 + rg; r < r0 + 2 * HU; r += 2) {
    const uint4 v = HP == 2 ? __ldcg(p + (size_t)r * 768) : __ldcs(p + (size_t)r * 768);
    const float f = sc[r];
    acc[0] += f * blo(v.x); acc[1] += f * bhi(v.x); acc[2] += f * blo(v.y); acc[3] += f * bhi(v.y);
    acc[4] += f * blo(v.z); acc[5] += f * bhi(v.z); acc[6] += f * blo(v.w); acc[7] += f * bhi(v.w);
  }
  }
#pragma unroll
  for (int i = 0; i < 8; i++) red[rg * 1024 + cg * 8 + i] = acc[i];
  BAR_SYNC(rec::B_F, 256);
  for (int i = tid; i < 1024; i += 256) g_mod[2048 + hb * 1024 + i] = rbf(red[i] + red[1024 + i]);
  BAR_SYNC(rec::B_F, 256);
  if (tid == 0) {
    red_rel(&g_mcnt);
    for (int r = 0; r < 1024; r++) {
      asm volatile("cp.async.bulk.prefetch.L2.global [%0], 1792;" ::"l"(w1 + (size_t)r * 7168 + hb * 1792) : "memory");
      if ((r & 7) == 7) __nanosleep(250);
    }
    wait_cnt(&g_mcnt, 4);
  }
  BAR_SYNC(rec::B_F, 256);
  float2* m2 = (float2*)smem;
  for (int i = tid; i < 1024; i += 256) m2[i] = make_float2(rbf(1.f + __ldcg(g_mod + 4096 + i)), __ldcg(g_mod + 3072 + i));
  BAR_SYNC(rec::B_F, 256);
  float* rd = (float*)(smem + 8192);
  if (tid < 224) {
    const int r2 = tid >= 112, c2 = tid - r2 * 112;
    float a1[8] = {0, 0, 0, 0, 0, 0, 0, 0}, a2[8] = {0, 0, 0, 0, 0, 0, 0, 0};
    const uint4* q = (const uint4*)(w1 + hb * 1792) + c2;
#pragma unroll 1
    for (int r0 = 0; r0 < 1024; r0 += 32) {
      __nanosleep(HS);
#pragma unroll
      for (int r = r0 + r2; r < r0 + 32; r += 2) {
        const uint4 v = __ldcg(q + (size_t)r * 448);
        const float2 f = m2[r];
        const float w[8] = {blo(v.x), bhi(v.x), blo(v.y), bhi(v.y), blo(v.z), bhi(v.z), blo(v.w), bhi(v.w)};
#pragma unroll
        for (int i = 0; i < 8; i++) { a1[i] += f.x * w[i]; a2[i] += f.y * w[i]; }
      }
    }
#pragma unroll
    for (int i = 0; i < 8; i++) { rd[r2 * 1792 + c2 * 8 + i] = a1[i]; rd[r2 * 1792 + 896 + c2 * 8 + i] = a2[i]; }
  }
  BAR_SYNC(rec::B_F, 256);
  for (int i = tid; i < 448; i += 256) {
    const int n = i * 2, gn = hb * 896 + n;
    const uint32_t bb = *(const uint32_t*)(b1 + gn);
    ((uint2*)g_cc)[(gn >> 4) * 8 + ((gn >> 1) & 3) * 2 + ((gn >> 3) & 1)] =
        make_uint2(pk(rd[n] + rd[1792 + n], rd[n + 1] + rd[1793 + n]), pk(0.5f * (rd[896 + n] + rd[2688 + n] + blo(bb)), 0.5f * (rd[897 + n] + rd[2689 + n] + bhi(bb))));
  }
  if (tid == 0 && PFT) {
    asm volatile("griddepcontrol.launch_dependents;");
    while (gtime() - t0 < PFT) __nanosleep(1000);
    for (int r = 0; r < 1536; r++) {
      asm volatile("cp.async.bulk.prefetch.L2.global [%0], 2048;" ::"l"(r < 512 ? x + (hb * 512 + r) * 2048 : wo + ((1535 - r) * 4 + hb) * 2048) : "memory");
      if ((r & 7) == 7) { __nanosleep(PFS); if (ldg_rlx1(&g_fin)) break; }
    }
  }
}

__global__ void __cluster_dims__(2, 1, 1) __launch_bounds__(512, 1)
k_rec(const __grid_constant__ RecMaps mp, const bf16* __restrict__ mem0, const bf16* __restrict__ x, const bf16* __restrict__ cvec,
      const bf16* __restrict__ wmod, const char* __restrict__ w1, const bf16* __restrict__ b1, const char* __restrict__ wo, char* xc, int dF, int dA, int dS, int dM, int dG, int dP, int dX, int dD, int dZ, int dZ2, int dV, int dX2) {
  using namespace rec;
  extern __shared__ __align__(1024) char smem[];
  const uint32_t sb = (uint32_t)__cvta_generic_to_shared(smem);
  if ((sb & 0x3FFFF) != 1024) __trap();
  PH(0); if (threadIdx.x == 0) PT(0);
  if (threadIdx.x == 0) {
    int b = blockIdx.x;
    if (b >= 8 && b < 128) {
      const int t = (b >> 1) - 4, u = t - 32;
      b = 2 * (t < 32 ? 4 + (t & 16) + (t & 7) * 2 + ((t >> 3) & 1) : 36 + (u / 14) * 14 + (u % 7) * 2 + ((u / 7) & 1)) + (b & 1);
    }
    sts1(sb + rec::PACE + 24, b);
    const int c = blockIdx.x >> 1, l = c < 36 ? (c - 4) & 7 : (c - 36) % 7, m = c < 4 ? c : c < 36 ? (c - 4) >> 3 : (c - 36) / 7;
    const int g = c < 4 ? 15 : (l >> 1) * 4 + (l & 1) + (c < 36 ? 0 : 2);
    unsigned sm;
    asm("mov.u32 %0,%%smid;" : "=r"(sm));
    if (c < 64) g_slot[sm & 255] = 1 + FMAP;
  }
#define ROLE_REFRESH { asm volatile("mov.u32 %0,%%tid.x;" : "=r"(tid)); wid = __shfl_sync(~0u, tid >> 5, 0); b = __shfl_sync(~0u, lds1(sb + PACE + 24), 0); }
#define ROLE_VARS int tid; asm volatile("mov.u32 %0,%%tid.x;" : "=r"(tid)); \
    int wid = __shfl_sync(~0u, tid >> 5, 0), b = __shfl_sync(~0u, lds1(sb + PACE + 24), 0);
#define wg (wid >> 2)
#define iw (wid & 3)
#define h (b >> 2)
#define j (b & 3)
#define a (b & 1)
#define bb ((b >> 1) & 1)
  const uint32_t wbar = sb + BARS + 48, obar = wbar + 8;
  if (threadIdx.x == 256) {
    for (int i = 0; i < 18; i++) if (i != 12) mbar_init(sb + BARS + i * 8, i == 3 || i == 8 || i == 9 || i == 10 ? 2 : 1);
    for (int i = 0; i < 3; i++) mbar_init(sb + PACE + i * 8, 1);
    asm volatile("fence.mbarrier_init.release.cluster;" ::: "memory");
    FENCE_ASYNC_SMEM();
    mbar_expect(sb + BARS, 2048);
    mbar_expect(sb + BARS + 16, 4096);
    mbar_expect(sb + BARS + 32, 4096);
    mbar_expect(sb + BARS + 40, 4096);
  }
  __syncthreads();
#define lane ((int)(l16 >> 4))
#define l16 (L16 & 0x1f0)
#define is7 ((L16 & 112) == 112)
#define PIN(x) __shfl_xor_sync(~0u, (uint32_t)(x), 0)
#define REFRESH() L16 = __shfl_xor_sync(~0u, L16, 0)
#define lar ((L16 & 0x180) * 8 + (L16 & 0x70))
#define X_LOAD(n, w, u) \
        asm volatile("{.reg .pred p; elect.sync _|p, 0xffffffff; @p mbarrier.arrive.expect_tx.shared.b64 _,[%2],8192;\n" \
                     "@p cp.async.bulk.shared::cluster.global.mbarrier::complete_tx::bytes [%0],[%1],8192,[%2];}" ::"r"(sb + XB + (w) * 16384 + (u) * 8192), \
                     "l"(g_h + (n) * 4096 + a * 2048 + (w) * 1024 + (u) * 512), "r"(sb + BARS + 64 + (w) * 8) : "memory")
#define lpub ((L16 & 0x30) * 64 + ((L16 >> 3) & 0x38))
#define lrow ((L16 & 0x70) + (((L16 >> 3) ^ L16) & 0x70 & ~((L16 >> 3) & 0x40) ? L16 & 0x180 : 512))

  const int role = __shfl_sync(~0u, threadIdx.x >> 7, 0);
  if (role < 2) {
    asm volatile("setmaxnreg.inc.sync.aligned.u32 %0;" ::"n"(RF_));
    if (blockIdx.x >= 128) { rec_helper(smem, cvec, wmod, w1, b1, (const char*)x, wo); return; }
    ROLE_VARS
    uint32_t L16 = __shfl_sync(~0u, sb + (tid & 31) * 16, tid & 31);
    {
      uint4 wm[8], xr[8];
      const uint4* pw = (const uint4*)(wmod + (size_t)((b >> 5) * 256 + (tid >> 3)) * 6144 + (b & 31) * 64) + (tid & 7);
      const float cs = __bfloat162float(cvec[(b >> 5) * 256 + tid]);
#pragma unroll
      for (int i = 0; i < 8; i++) wm[i] = __ldcs(pw + (size_t)i * 32 * 768);
#pragma unroll
      for (int i = 0; i < 8; i++) xr[i] = __ldg((const uint4*)(x + (size_t)(b * 16 + (tid >> 5) * 2) * 1024) + i * 32 + (tid & 31));
      float* sc = (float*)(smem + PRE);
      sc[tid] = rbf(silu(cs));
      if (tid < 80) g_ar[b * 80 + tid] = make_uint4(0, 0, 0, 0);
      if (tid == 80 && b == 0) g_fin = 0;
      PT(1);
      BAR_SYNC(B_F, 256);
      float acc[8] = {0, 0, 0, 0, 0, 0, 0, 0};
#pragma unroll
      for (int i = 0; i < 8; i++) {
        const float f = sc[i * 32 + (tid >> 3)];
        acc[0] += f * blo(wm[i].x); acc[1] += f * bhi(wm[i].x); acc[2] += f * blo(wm[i].y); acc[3] += f * bhi(wm[i].y);
        acc[4] += f * blo(wm[i].z); acc[5] += f * bhi(wm[i].z); acc[6] += f * blo(wm[i].w); acc[7] += f * bhi(wm[i].w);
      }
#pragma unroll
      for (int i = 0; i < 8; i++) { acc[i] += __shfl_xor_sync(~0u, acc[i], 8); acc[i] += __shfl_xor_sync(~0u, acc[i], 16); }
      float* red = sc + 1024;
      if ((tid & 31) < 8) {
#pragma unroll
        for (int i = 0; i < 8; i++) red[(tid >> 5) * 64 + (tid & 7) * 8 + i] = acc[i];
      }
      BAR_SYNC(B_F, 256);
      PT(2);
      if (tid < 64) {
        float t = 0;
#pragma unroll
        for (int i = 0; i < 8; i++) t += red[i * 64 + tid];
        asm volatile("st.relaxed.gpu.global.u32 [%0],%1;" ::"l"((unsigned*)g_modp + (b >> 5) * 2048 + (b & 31) * 64 + tid), "r"(U_(t) | 1u) : "memory");
      }
      float v[2][32], rstd[2];
#pragma unroll
      for (int r = 0; r < 2; r++) {
        float t = 0, q = 0;
#pragma unroll
        for (int i = 0; i < 4; i++) {
          const uint4 u = xr[r * 4 + i];
          float* w = v[r] + i * 8;
          w[0] = blo(u.x); w[1] = bhi(u.x); w[2] = blo(u.y); w[3] = bhi(u.y); w[4] = blo(u.z); w[5] = bhi(u.z); w[6] = blo(u.w); w[7] = bhi(u.w);
        }
#pragma unroll
        for (int i = 0; i < 32; i++) t += v[r][i];
#pragma unroll
        for (int o = 16; o; o >>= 1) t += __shfl_xor_sync(~0u, t, o);
        t *= 1.f / 1024;
#pragma unroll
        for (int i = 0; i < 32; i++) { v[r][i] -= t; q += v[r][i] * v[r][i]; }
#pragma unroll
        for (int o = 16; o; o >>= 1) q += __shfl_xor_sync(~0u, q, o);
        rstd[r] = rsqrtf(q * (1.f / 1024) + 1e-5f);
      }
      PT(3);
      float4* md = (float4*)(sc + 1536);
#pragma unroll
      for (int i = 0; i < 2; i++) {
        uint4 p[4];
        int it = 0;
        while (true) {
#pragma unroll
          for (int u = 0; u < 4; u++) p[u] = ldg_rlx4(g_modp + u * 512 + i * 256 + tid);
          uint32_t ok = 1;
#pragma unroll
          for (int u = 0; u < 4; u++) ok &= p[u].x & p[u].y & p[u].z & p[u].w;
          if (__all_sync(~0u, ok)) break;
          if (++it > SPIN_LIMIT) __trap();
          __nanosleep(100);
        }
        md[i * 256 + tid] = make_float4(i + rbf((F_(p[0].x) + F_(p[1].x)) + (F_(p[2].x) + F_(p[3].x))), i + rbf((F_(p[0].y) + F_(p[1].y)) + (F_(p[2].y) + F_(p[3].y))),
                                        i + rbf((F_(p[0].z) + F_(p[1].z)) + (F_(p[2].z) + F_(p[3].z))), i + rbf((F_(p[0].w) + F_(p[1].w)) + (F_(p[2].w) + F_(p[3].w))));
      }
      BAR_SYNC(B_F, 256);
      PT(4);
#pragma unroll
      for (int i = 0; i < 4; i++) {
        const int ch = i * 32 + (tid & 31);
        const float4 s0 = md[ch * 2], s1 = md[ch * 2 + 1], c0 = md[256 + ch * 2], c1 = md[256 + ch * 2 + 1];
#pragma unroll
        for (int r = 0; r < 2; r++) {
          const int row = b * 16 + (tid >> 5) * 2 + r;
          const float* w = v[r] + i * 8;
          g_h[((row >> 5) * 16 + (ch >> 3)) * 256 + (row & 31) * 8 + ((ch & 7) ^ (row & 7))] =
              make_uint4(pk(w[0] * rstd[r] * c0.x + s0.x, w[1] * rstd[r] * c0.y + s0.y), pk(w[2] * rstd[r] * c0.z + s0.z, w[3] * rstd[r] * c0.w + s0.w),
                         pk(w[4] * rstd[r] * c1.x + s1.x, w[5] * rstd[r] * c1.y + s1.y), pk(w[6] * rstd[r] * c1.z + s1.z, w[7] * rstd[r] * c1.w + s1.w));
        }
      }
      PT(30);
      FENCE_ASYNC();
      PT(31);
      BAR_SYNC(B_F, 256);
      PT(15);
      if (tid == 0) red_rlx(&g_hcnt);
      PH(1); PT(5);
    }
    uint32_t m0[2][4];
#pragma unroll
    for (int i = 0; i < 2; i++)
#pragma unroll
      for (int r = 0; r < 4; r++)
        m0[i][r] = (uint32_t)__bfloat16_as_ushort(mem0[(2 * r) * 1024 + a * 512 + tid * 2 + i]) | ((uint32_t)__bfloat16_as_ushort(mem0[(2 * r + 1) * 1024 + a * 512 + tid * 2 + i]) << 16);
    if (iw == 0) wait_cnt(&g_hcnt, 128);
    __syncwarp();
    PH(2); PT(6);
    ROLE_REFRESH
    uint32_t wQ[16][4], wK[16][4], wV[NVR][4];
    uint32_t frag = sb + ((lane & 7) + (lane >> 4) * 8) * 128 + (((iw * 2 + ((lane >> 3) & 1)) ^ (lane & 7)) << 4);
    mbar_wait(wbar, 0);
    PT(7);
#pragma unroll
    for (int i = 0; i < 16; i++) { ldsm4t(wQ[i], frag + WO + wg * 32768 + i * 2048); ldsm4t(wK[i], frag + XB + wg * 32768 + i * 2048); }
#pragma unroll
    for (int i = 0; i < NVR; i++) ldsm4t(wV[i], frag + MEM + (wg * NVR + i) * 2048);
    FENCE_ASYNC_SMEM();
    PH(3); PT(8);
    CLUSTER_SYNC();
    PT(9);
#define xbar (sb + BARS + 64 + wg * 8)
    auto x_load = [&](int n) { if (iw == 0) { X_LOAD(n, wg, 0); X_LOAD(n, wg, 1); } };
    x_load(0);
    if (tid == 0) {
      mbar_expect(obar, 65536);
      for (int i = 0; i < 4; i++) tma2d(sb + WO + i * 16384, &mp.wo, j * 256 + i * 64, h * 128, obar);
    }
#pragma unroll
    for (int i = 0; i < 2; i++) {
      const int k = tid * 2 + i, m = (k >> 3) & 3, r = k & 7;
      sts4(sb + MEM + (k >> 5) * 640 + (r == m ? 512 : m * 128) + r * 16, m0[i][0], m0[i][1], m0[i][2], m0[i][3]);
    }
    if (lane < 8) {
      sts4(sb + ARO + wid * 640 + (lane < 4 ? lane * 144 : 512 + l16), 0x3f803f80, 0x3f803f80, 0x3f803f80, 0x3f803f80);
#pragma unroll
      for (int i = 0; i < 2; i++) sts4(sb + MEM + (wid * 2 + i) * 640 + (lane < 4 ? lane * 144 : 512 + l16), 0x42004200, 0x42004200, 0x42004200, 0x42004200);
    }
#define owner ((iw >> 1) == a)
#define vfin ((wid >> 1) == a)
#define oi (wid & 1)
    frag += wg * NVS * 2048;
    {
      const uint32_t rsb = mapa(sb, iw >> 1);
      const uint32_t pp = rsb + PK + (owner ? 0 : 12288) + (oi * 2048 + wg * 1024) + l16;
      const uint32_t mb = sb + MEM + wg * 5120;
      sts4(L16 + TF + wid * 512, mb + lrow, owner ? L16 + (lane >> 4) * (RK - RQ - 256) + RQ + oi * 1024 + wg * 256 : rsb + RQ + oi * 1024 + 512 + wg * 256 + (l16 >> 2),
           L16 + OB, frag);
      sts4(L16 + TF + 4096 + wid * 512, sb + WO + (wid >> 1) * 16384 + ((lane & 7) + (lane >> 4) * 8) * 128 + ((((wid & 1) * 4 + ((lane >> 3) & 1)) ^ (lane & 7)) << 4),
           sb + ARO + wid * 640 + lrow, pp, LO(xc) + h * 262144 + (bb * 2 + (iw >> 1)) * XC + X_VM(0) + oi * 2048 + a * 256 + (l16 >> 1));
    }
    uint32_t tp = L16 + TF + wid * 512;
    auto park_ptr = [&]() { return lds1(tp + 4096 + 8); };
    auto park = [&](const float* f, int m, int n, uint32_t d) {
      uint32_t w[8];
#pragma unroll
      for (int i = 0; i < 8; i++) w[i] = pk(f[2 * i], f[2 * i + 1]);
      if (owner) {
        sts4(d + m * 4096, w[0], w[1], w[2], w[3]); sts4(d + m * 4096 + 512, w[4], w[5], w[6], w[7]);
      } else {
        const uint32_t pb = mapa(sb, a ^ 1) + BARS + (m ? 24 + m * 8 : 16);
        sta4(d + m * 4096, w, pb); sta4(d + m * 4096 + 512, w + 4, pb);
      }
    };
    auto xdesc = [&](int n) { return mkdesc(__shfl_sync(~0u, 1024 + XB + wg * 16384, 0), 16, 1024); };
    auto rs_issue = [&](float* acc, const uint32_t (&w)[16][4], int n, bool fence) {
      const uint64_t x = xdesc(n);
      if (fence) WG_FENCE();
      wgmma_rs_n32_z(acc, w[0], x);
#pragma unroll
      for (int i = 1; i < 16; i++) wgmma_rs_n32(acc, w[i], x + (i >> 2) * 256 + (i & 3) * 2, 1);
      WG_COMMIT();
    };
    auto v_issue = [&](float* acc, int n, bool fence) {
      const uint64_t dv = mkdesc(__shfl_sync(~0u, 1024 + WVS + wg * NVS * 2048, 0), 16, 1024), x = xdesc(n);
      if (fence) WG_FENCE();
      wgmma_rs_n32_z(acc, wV[0], x);
#pragma unroll
      for (int i = 1; i < (KVO == 2 ? NVR : 0); i++) wgmma_rs_n32(acc, wV[i], x + (i >> 2) * 256 + (i & 3) * 2, 1);
#pragma unroll
      for (int i = NVR; i < 16; i++) wgmma_ssT_n32(acc, dv + (i - NVR) * 128, x + (i >> 2) * 256 + (i & 3) * 2, 1);
#pragma unroll
      for (int i = 1; i < (KVO == 2 ? 0 : NVR); i++) wgmma_rs_n32(acc, wV[i], x + (i >> 2) * 256 + (i & 3) * 2, 1);
      WG_COMMIT();
    };
    uint32_t mA;
    auto vk_pass = [&](int n, uint32_t d) {
      float acc[16], acc2[16];
      v_issue(acc, n, true);
      rs_issue(acc2, wK, n, false);
      if (n) mbar_wait(sb + BARS + 80, (n - 1) & 1);
      WG_WAIT(1);
      park(acc, 2 - !!KVO, n, d);
      mA = lds1(tp);
      if (n > 1) BAR_ARRIVE(B_K, 320);
      WG_WAIT(0);
      park(acc2, 1 + !!KVO, n, d);
    };
    {
      float acc[16];
      mbar_wait(xbar, 0);
      PT(10);
      rs_issue(acc, wQ, 0, true); WG_WAIT(0); park(acc, 0, 0, park_ptr());
      vk_pass(0, park_ptr());
      PT(11);
      BAR_SYNC(B_C, 320);
      x_load(1);
      BAR_SYNC(B_C, 320);
      asm volatile("" : "+r"(wid));
      mbar_wait(xbar, 1);
      PT(12);
      rs_issue(acc, wQ, 1, true); mbar_wait(sb + BARS + 24, 0); WG_WAIT(0); park(acc, 0, 1, park_ptr());
      vk_pass(1, park_ptr());
      BAR_ARRIVE(B_P, 384); if (!HX) BAR_ARRIVE(B_X, 320); BAR_ARRIVE(B_Q, 288);
    }
    PT(13);
    mbar_wait(obar, 0);
    PH(4); PT(14);
    ROLE_REFRESH
    for (int s = 0; s < 64; s++) {
      asm volatile("" : "+r"(tp), "+r"(wid));
      asm volatile("mov.u32 %0,%%cluster_ctarank;" : "=r"(b));
      uint32_t vS[NVS][4], bf[8][4], rm;
      const uint32_t mm = mapa(sb, a ^ 1) + BARS;
      if (s > 0) BAR_SYNC(B_R, 320);
#define VMMA(c, w, i) mma16(c, (w)[0], (w)[1], (w)[2], (w)[3], bf[(i) >> 1][((i) & 1) * 2], bf[(i) >> 1][((i) & 1) * 2 + 1])
      {
        float cQ[4] = {0, 0, 0, 0}, cK[4] = {0, 0, 0, 0};
#pragma unroll
        for (int t = 7; t >= 3; t--) ldsm4t(bf[t], mA + t * 640);
        SCHED_FENCE(47);
#pragma unroll
        for (int i = 15; i >= 0; i--) {
          VMMA(cQ, wQ[i], i); VMMA(cK, wK[i], i);
          if (i == XI && HX) BAR_ARRIVE(B_X, 320);
          if (i == 12) {
            SCHED_FENCE(51);
#pragma unroll
            for (int t = 2; t >= 0; t--) ldsm4t(bf[t], mA + t * 640);
            rm = lds1(tp + 4); frag = lds1(tp + 12);
          }
          if (i == 4 && NVP) {
            SCHED_FENCE(48);
#pragma unroll
            for (int u = 0; u < NVP; u++) ldsm4t(vS[NVS - 1 - u], frag + WVS + (NVS - 1 - u) * 2048);
          }
        }
        const uint32_t w0 = pk(cQ[0] * SCS, cQ[1] * SCS), w1 = pk(cQ[2] * SCS, cQ[3] * SCS), w2 = pk(cK[0], cK[1]), w3 = pk(cK[2], cK[3]);
        if (owner) {
          stsm4(rm, w0, w1, w2, w3);
          BAR_ARRIVE(B_E, 256);
        } else {
          sta1<0>(rm, w0, mm); sta1<128>(rm, w1, mm);
          sta1<RK - RQ>(rm, w2, mm); sta1<RK - RQ + 128>(rm, w3, mm);
        }
        if (wid == 2) TS(0);
      }
      uint4 t1;
      uint32_t oA;
      {
        float cV[4] = {0, 0, 0, 0}, cW[4] = {0, 0, 0, 0};
        static_assert(NVP == 2 && NVR == 5, "schedule");
#define VLD(k) ldsm4t(vS[(k) - NVR], frag + WVS + ((k) - NVR) * 2048)
#define VS_(c, k) VMMA(c, vS[(k) - NVR], k)
        VLD(13); VLD(12);
        VS_(cW, 15); VS_(cV, 14); VLD(11); VMMA(cW, wV[0], 0); VLD(10); VMMA(cV, wV[1], 1); VLD(9);
        VMMA(cW, wV[2], 2); VLD(8); VMMA(cV, wV[3], 3); VLD(7); VMMA(cW, wV[4], 4); VS_(cV, 13); VLD(6); VS_(cW, 12); VLD(5);
        VS_(cV, 11); VS_(cW, 10); VS_(cV, 9); VS_(cW, 8); VS_(cV, 7); VS_(cW, 6); VS_(cV, 5);
#pragma unroll
        for (int e = 0; e < 4; e++) cV[e] += cW[e];
        const uint32_t ex = tp + (RX - TF) - wg * 2048;
        t1 = lds4(tp + 4096);
        oA = lds1(tp + 8 + (s & dZ));
        if (wg) {
          sts4(ex, U_(cV[0]), U_(cV[1]), U_(cV[2]), U_(cV[3]));
          BAR_ARRIVE(B_T2, 256);
        } else {
          BAR_SYNC(B_T2, 256);
          const float4 u = lds4f(ex);
          stg_b64(mkp(t1.w ^ ((s & 1) * X_RING), HI(xc)), (pk(cV[0] + u.x, cV[1] + u.y) & ~1u) | (((s >> 1) + 1) & 1), pk(cV[2] + u.z, cV[3] + u.w));
        }
      }
      if (s == 63) break;
      {
        const uint32_t woA = t1.x, woB = woA ^ 32;
        uint32_t wo[16][4];
#pragma unroll
        for (int i = 0; i < NW1; i++) ldsm4t(wo[i], ((i & 1) ? woB : woA) + (i >= WCH ? wo[(i - WCH + NWP) % NWP][0] & dZ : 0) + (i >> 1) * 2048);
        BAR_SYNC(B_S, 416);
        if (s < 62) {
          float acc[16];
          rs_issue(acc, wQ, s + 2, true);
          mbar_wait(sb + BARS + 24, (s + 1) & 1);
          WG_WAIT(0);
          BAR_SYNC(B_V, 512);
          park(acc, 0, s + 2, t1.z);
        } else {
          BAR_SYNC(B_V, 512);
        }
#pragma unroll
        for (int i = NW1; i < NWP; i++) ldsm4t(wo[i], ((i & 1) ? woB : woA) + (i >> 1) * 2048);
        float inv0, inv1;
        {
          uint32_t p[4], pm;
          const uint32_t pa = oA + (SC - OB), one = 0x3f803f80u;
          float sum[4] = {0, 0, 0, 0}, su2[4] = {0, 0, 0, 0};
          ldsm4t(p, pa);
          asm volatile("ldmatrix.sync.aligned.m8n8.x1.trans.shared.b16 {%0},[%1];" : "=r"(pm) : "r"(pa + 512) : "memory");
          mma16(sum, one, one, one, one, p[0], p[1]);
          mma16(su2, one, one, one, one, p[2], p[3]);
          mma8(sum, one, one, pm);
          inv0 = sum[0] + su2[0]; inv1 = sum[1] + su2[1];
          SCHED_FENCE(57);
        }
        BAR_SYNC(B_O, 416);
        float c[2][4] = {{0, 0, 0, 0}, {0, 0, 0, 0}};
        uint32_t o[4][4];
#pragma unroll
        for (int i = 0; i < NOP_; i++) ldsm4t(o[i], oA + i * 512);
        SCHED_FENCE(46);
        asm("rcp.approx.ftz.f32 %0,%0;" : "+f"(inv0));
        asm("rcp.approx.ftz.f32 %0,%0;" : "+f"(inv1));
#pragma unroll
        for (int i = 0; i < 16; i++) {
          mma16(c[i & 1], wo[i][0], wo[i][1], wo[i][2], wo[i][3], o[i >> 2][i & 2], o[i >> 2][(i & 2) + 1]);
          if (i == 1 && NOP_ < 3) ldsm4t(o[2], oA + 1024);
          if (i == 3 && NOP_ < 4) ldsm4t(o[3], oA + 1536);
          if (i + NWP < 16) ldsm4t(wo[(i + NWP) & 15], (((i + NWP) & 1) ? woB : woA) + ((i + NWP) >> 1) * 2048);
        }
        stsm4(t1.y, pk(c[0][0] * inv0, c[0][1] * inv1), pk(c[0][2] * inv0, c[0][3] * inv1), pk(c[1][0] * inv0, c[1][1] * inv1), pk(c[1][2] * inv0, c[1][3] * inv1));
      }
      const uint32_t d = park_ptr();
      BAR_SYNC(B_W, 384);
      if (s < 62) {
        vk_pass(s + 2, d);
        BAR_ARRIVE(B_P, 384); if (!HX) BAR_ARRIVE(B_X, 320);
        TS(10);
      } else {
        mA = lds1(tp);
      }
    }
  } else if (role == 3) {
    asm volatile("setmaxnreg.dec.sync.aligned.u32 24;");
    if (blockIdx.x >= 128) return;
    ROLE_VARS
    const uint32_t L16 = sb + (tid & 31) * 16;
    CLUSTER_SYNC();
    sts1(sb + PACE + 36, LO(xc) + h * 262144 + X_VM(0));
    auto vm_stage = [&](int s) {
      const uint32_t tag = ((s >> 1) + 1) & 1;
      const char* xm = mkp(lds1(sb + PACE + 36) + (s & 1) * X_RING + iw * XC + (l16 >> 1), HI(xc));
      uint2 m[4];
      CONSUME(LO(xm));
      BAR_SYNC(B_S2, 256);
      if (dZ2 > 1) { const uint32_t c = clk(); while (clk() - c < (uint32_t)dZ2) {} }
      int it = 0;
      while (true) {
#pragma unroll
        for (int i = 0; i < 4; i++) m[i] = ldg_b64(xm + (i >> 1) * 2048 + (i & 1) * 256);
        sts4(L16 + VN + iw * 512, m[0].x, m[0].y, m[1].x, m[1].y);
        sts4(L16 + VN + iw * 512 + 2048, m[2].x, m[2].y, m[3].x, m[3].y);
        if (!anybad(m[0].x, m[1].x, m[2].x, m[3].x, tag)) break;
        RP(2);
        if (++it > SPIN_LIMIT) __trap();
      }
      if (s < 63) BAR_ARRIVE(B_V, 512); else BAR_ARRIVE(B_V, 256);
    };
    if (iw == 0) {
#pragma unroll 1
      for (int s = 0; s < 63; s++) {
        if (s) BAR_SYNC(B_R, 320); else BAR_SYNC(B_Q, 288);
        if (s < 62) { X_LOAD(s + 2, 0, 0); X_LOAD(s + 2, 1, 0); X_LOAD(s + 2, 0, 1); X_LOAD(s + 2, 1, 1); }
        if (s >= 7) {
          const uint32_t zo = b * 160 + l16;
          if (l16 < 160) CONSUME(exch_b128((char*)g_ar + (zo >> 7) * 1024 + (zo & 127) + ((s + 1) & 7) * 128, 0, 0, 0, 0).x);
          __syncwarp();
        }
        if (s < 62) { mbar_wait(sb + BARS + 64, s & 1); mbar_wait(sb + BARS + 72, s & 1); }
        BAR_ARRIVE(B_S, 416);
        vm_stage(s);
        BAR_ARRIVE(B_O, 416);
        BAR_SYNC(B_W, 384);
        FENCE_ASYNC_SMEM();
        asm volatile("{.reg .pred p; elect.sync _|p, 0xffffffff; @p cp.reduce.async.bulk.tensor.2d.global.shared::cta.add.bulk_group [%0,{%1,%2}],[%3];}"
                     ::"l"(&mp.ari), "r"((s & 7) * 64), "r"(j * 40), "r"(sb + ARO) : "memory");
        BULK_COMMIT();
        asm volatile("st.relaxed.gpu.global.u32 [%0],%1;" ::"l"(g_tm + (s & 1) * 128 + b), "r"(gtime()) : "memory");
        TS(3);
        BULK_WAIT_READ(0);
      }
      BAR_ARRIVE(B_R, 320);
      vm_stage(63);
    } else if (iw == 1) {
      const uint32_t pc = sb + MEM + (lane >> 2) * 640 + (lane & 3) * 144 + (lane & 12), pd = sb + MEM + (lane & 15) * 640 + 576 + (lane & 3) * 16 + (lane & 12);
      uint32_t T = 0, par = 0;
      int est = dA;
#pragma unroll 1
      for (int s = 0; s < 63; s++) {
        if (s) {
          const uint4 tm = ldg_rlx4((const char*)g_tm + ((s + 1) & 1) * 512 + l16);
          const int t0 = tm.x - T, t1 = tm.y - T, t2 = tm.z - T, t3 = tm.w - T;
          const int e = max(dF + (__reduce_add_sync(~0u, (t0 + t1) + (t2 + t3)) >> 7), dV + __reduce_max_sync(~0u, max(max(t0, t1), max(t2, t3))));
          if (s > 1) est += max(min(e >> 2, dP), -dP);
          T += (s == 1 || e > dM ? e : 0) + est;
        }
        vm_stage(s);
        BAR_SYNC(B_W, 384);
        SCHED_FENCE(70);
        const uint32_t tW = gtime();
        if (s == 0) T = tW + 800;
        const uint32_t te = tW + min(max((int)(T - tW), dD), 2000);
        while ((int)(gtime() - te) < 0) {}
        TS(7);
        int it = 0;
        while (true) {
          ar_fetch(sb + MEM, &mp.ari, s & 7, a, sb + BARS + 112);
          mbar_wait(sb + BARS + 112, par);
          par ^= 1;
          const uint32_t n0 = lds1(pc), n1 = lds1(pc + 5120), n2 = lds1(pd);
          if (!__any_sync(~0u, (tagbad(n0, n1, 0x42004200) | (n2 ^ 0x42004200)) != 0)) break;
          RP(0);
          if (++it > SPIN_LIMIT) __trap();
        }
        BAR_ARRIVE(B_R, 320);
        TS(11);
      }
      vm_stage(63);
    } else {
#define V_LOAD(n) do { if (lane == 0) mbar_expect(sb + BARS + 8, 8192); __syncwarp(); \
        if (lane < 16) bulk_ld(sb + ((lane & 2) ? VX1 : VX0) + (lane & 1) * 2048 + (lane >> 2) * 512, \
                               xc + h * 262144 + ((n) & 1) * X_RING + (lane >> 2) * XC + X_VX(lane & 3), 512, sb + BARS + 8); __syncwarp(); } while (0)
      uint32_t src = L16 + PK + (iw & 1) * 2048;
#define qd (L16 + (lane >> 4) * 256 + QT + (iw & 1) * 1024)
#define vd (LO(xc) + h * 262144 + j * XC + (iw & 1) * 2048 + l16)
#define FINISH [&](int n, int m) { \
_Pragma("unroll") \
        for (int i = 1; i >= 0; i--) { \
          const uint32_t p = src + m * 4096 + i * 512; \
          uint4 u = lds4(p); \
          const uint4 w = lds4(p + 1024), y = lds4(p + 12288), z = lds4(p + 13312); \
          u = make_uint4(sum4bf(u.x, w.x, y.x, z.x), sum4bf(u.y, w.y, y.y, z.y), sum4bf(u.z, w.z, y.z, z.z), sum4bf(u.w, w.w, y.w, z.w)); \
          if (m == 2) stg_b128(mkp(vd ^ ((n & 1) * X_RING), HI(xc)) + i * 512, (u.x & ~1u) | (((n >> 1) + 1) & 1), u.y, u.z, u.w); \
          else stsm4(qd + (n & 1) * 4096 + m * 2048 + i * 256, u.x, u.z, u.y, u.w); \
          SCHED_FENCE(71 + m * 2 + i); \
        } \
      }
#pragma unroll 1
      for (int n = 0; n < 64; n++) {
        src = PIN(src);
        b = __shfl_sync(~0u, lds1(sb + PACE + 24), 0);
        const uint32_t L16 = src - PK - (iw & 1) * 2048;
        auto finish = FINISH;
        if (n < 2) { if (n) BAR_SYNC(B_X, 320); else BAR_SYNC(B_C, 320); }
        mbar_wait(sb + BARS + 16, n & 1);
        finish(n, 0);
        __syncwarp();
        if (lane == 0) mbar_arrive_cl(mapa(sb, a ^ 1) + BARS + 24);
        if (n > 1) BAR_SYNC(B_K, 320);
        mbar_wait(sb + BARS + (KVO ? 32 : 40), n & 1);
        finish(n, 2 - !!KVO);
        if (n > 1) BAR_SYNC(B_X, 320);
        mbar_wait(sb + BARS + (KVO ? 40 : 32), n & 1);
        finish(n, 1 + !!KVO);
        BAR_SYNC(B_T, 64);
        if (lane == 0) {
          if (iw == 2 && n < 63) { mbar_expect(sb + BARS + 16, 4096); mbar_expect(sb + BARS + 32, 4096); mbar_expect(sb + BARS + 40, 4096); }
          mbar_arrive_cl(mapa(sb, a ^ 1) + BARS + 80);
        }
        __syncwarp();
        if (n) {
          vm_stage(n - 1);
          BAR_SYNC(B_W, 384);
        } else {
          BAR_SYNC(B_C, 320);
        }
        if (iw == 2) V_LOAD(n);
      }
      if (HX) BAR_ARRIVE(B_X, 320);
      vm_stage(63);
#undef qd
#undef vd
    }
  } else {
    asm volatile("setmaxnreg.dec.sync.aligned.u32 %0;" ::"n"(RA_));
    if (blockIdx.x >= 128) return;
    ROLE_VARS
    uint32_t L16 = __shfl_sync(~0u, sb + (tid & 31) * 16, tid & 31);
    if (tid == 256) {
      const int col = h * 128 + bb * 64;
      for (int c = 0; c < 12 + WIN; c++) {
        const uint32_t mb = sb + PACE + (c % WIN) * 8;
        if (c >= WIN) mbar_wait(mb, (c / WIN - 1) & 1);
        PT(16 + c);
        if (c >= 12) { tma2d_pf(&mp.wo, j * 256 + (c - 12) * 64, h * 128); continue; }
        mbar_expect(mb, 16384);
        if (c < 8) tma2d(sb + (c & 1) * XB + (c >> 1) * 16384, (c & 1) ? &mp.wk : &mp.wq, col, a * 512 + (c >> 1) * 128, mb);
        else
          for (int i = (c & 1) * 8; i < (c & 1) * 8 + 8; i++) {
            const int w = (c - 8) >> 1;
            tma2d(i < NVR ? sb + MEM + (w * NVR + i) * 2048 : sb + WVS + (w * NVS + i - NVR) * 2048, &mp.wv, col, a * 512 + w * 256 + i * 16, mb);
          }
      }
      asm volatile("mbarrier.arrive.shared.b64 _,[%0];" ::"r"(wbar) : "memory");
      for (int c = WIN; c < 4; c++) tma2d_pf(&mp.wo, j * 256 + c * 64, h * 128);
      for (int i = 0; i < 3; i++) asm volatile("mbarrier.inval.shared.b64 [%0];" ::"r"(sb + PACE + i * 8) : "memory");
    }
    __syncwarp();
    CLUSTER_SYNC();
#define pr (L16 + SC)
    {
      const int lim = j * 8 + iw * 2 - (lane & 7) - (lane & 8) * 2;
      const bool mk = L16 & 256;
      const int rw = lane >> 2;
      sts4(L16 + TA + iw * 512,
           iw != 2 ? L16 + KT + (iw & 1) * 256 + (lane >> 4) * 256 : sb + RK + (L16 & 0x80) * 2 + ((L16 >> 1) & 0x80) + (L16 & 0x70),
           L16 + QT + (lane >> 3) * 384, sb + SC + min(lane >> 3, 2) * 256 + (L16 & 0x70) + iw * 4, L16 + (lane >> 4) * 256 + QT + (iw >> 1) * 1024 + (iw & 1) * 256);
      sts4(L16 + TA + 2048 + iw * 512, mk ? 0u : (lim < 0 ? 0xfc00u : 0u) | (lim < -1 ? 0xfc000000u : 0u),
           mk ? 0xfc00fc00u : (lim < 8 ? 0xfc00u : 0u) | (lim < 7 ? 0xfc000000u : 0u),
           ((h * 2 + (iw >> 1)) * 1024 + (j * 8 + rw) * 8 + (((iw & 1) * 4 + (lane & 3)) ^ rw)) * 16, sb + OT + iw * 512 + (L16 & 0x70) * 4 + ((L16 >> 3) & 0x30));
    }
    {
      const uint32_t xh = LO(xc) + h * 262144, xs = xh + X_SC + iw * 1024 + min(lane, 16 + (lane & 7)) * 8;
      sts4(L16 + TA + 4096 + iw * 512, xh + X_SC + j * 256 + iw * 64 + lpub, xs, dS, iw != 2 ? 0 : U_(SCS));
      sts1(L16 + TA + 12 + iw * 512, xs + X_TOK + j * 4096);
    }
    uint32_t tA = L16 + TA + iw * 512;
#define tw (tA - L16 != TA + 1024)
#define XP_(lo) mkp(lo, HI(xc))
    auto publish = [&](char* d, const uint2& w) { stg_b64(d, w.x, w.y); };
    BAR_SYNC(B_P, 384);
    for (int s = 0; s < 64; s++) {
      asm volatile("" : "+r"(L16), "+r"(tA));
      const uint32_t tag = ((s >> 1) + 1) & 1, ring = (s & 1) * X_RING;
      const uint4 t0 = lds4(tA);
      const uint4 tx = lds4(tA + 4096);
      const uint32_t xo = tx.x ^ ring, xs = tx.y ^ ring;
      const float gm = F_(tx.w);
      const uint32_t qA = t0.y + (ring >> 5);
      uint32_t c0;
      uint2 ts[4];
      uint4 v[4];
      uint32_t af[2][4], qt[4][4];
      {
        const uint32_t aA = t0.x + (tw ? ring >> 5 : 0);
        uint32_t ql[2][4], qr[2][4];
        uint2 pw_;
        float c[4] = {0, 0, 0, 0}, d[4] = {0, 0, 0, 0};
        if (s == PDS) asm volatile("griddepcontrol.launch_dependents;");
#pragma unroll
        for (int i = 0; i < 4; i++) ldsm4t(qt[i], qA + i * 128);
        mbar_wait(sb + BARS + 8, s & 1);
        TS(4);
        BAR_SYNC(B_E, 256);
#define PACK(c) make_uint2(pkh(fmaf(c[2], gm, c[0] * SCS), fmaf(c[3], gm, c[1] * SCS), tag), pkh(c[2] * SCS, c[3] * SCS, tag))
#define SMMA(x, t, q, i) mma16(x, af[t][0], af[t][1], af[t][2], af[t][3], q[t][i], q[t][i + 1])
        ldsm4t(ql[0], L16 + RQ); ldsm4t(ql[1], L16 + RQ + 1024); ldsm4t(af[0], aA); ldsm4t(af[1], aA + 1024);
        CONSUME(xo);
#define QSUM(t, i) addbf(addbf(ql[t][i], ql[t][i + 2]), addbf(qr[t][i], qr[t][i + 2]))
#define STAIL mma16(c, af[0][0], af[0][1], af[0][2], af[0][3], QSUM(0, 0), QSUM(0, 1)); mma16(d, af[1][0], af[1][1], af[1][2], af[1][3], QSUM(1, 0), QSUM(1, 1));
        if (tw) {
          mbar_wait(sb + BARS, s & 1);
          TS(8);
          ldsm4t(qr[0], L16 + RQ + 512); ldsm4t(qr[1], L16 + RQ + 1536);
          STAIL
          pw_ = make_uint2(pkh(c[0] + d[0], c[1] + d[1], tag), pkh(c[2] + d[2], c[3] + d[3], tag));
        } else {
          uint32_t ar[2][4];
          mbar_wait(sb + BARS, s & 1);
          ldsm4t(qr[0], L16 + RQ + 512); ldsm4t(ar[0], aA + 512); ldsm4t(qr[1], L16 + RQ + 1536); ldsm4t(ar[1], aA + 1536);
#pragma unroll
          for (int i = 0; i < 8; i++) af[i >> 2][i & 3] = addbf(af[i >> 2][i & 3], ar[i >> 2][i & 3]);
          STAIL
          pw_.x = pw_.y = pkh((c[0] + c[2]) + (d[0] + d[2]), (c[1] + c[3]) + (d[1] + d[3]), tag);
        }
        publish(XP_(xo), pw_);
        c0 = clk() + tx.z;
        TS(1);
      }
      uint2 r[4];
#define TOKS(i) { float e0[4] = {0, 0, 0, 0}, e1[4] = {0, 0, 0, 0}; \
        mma16(e0, af[0][0], af[0][1], af[0][2], af[0][3], qt[i][0], qt[i][1]); mma16(e1, af[0][0], af[0][1], af[0][2], af[0][3], qt[i + 1][0], qt[i + 1][1]); \
        mma16(e0, af[1][0], af[1][1], af[1][2], af[1][3], qt[i][2], qt[i][3]); mma16(e1, af[1][0], af[1][1], af[1][2], af[1][3], qt[i + 1][2], qt[i + 1][3]); \
        ts[i] = PACK(e0); ts[i + 1] = PACK(e1); }
      {
        float e[4][4];
#pragma unroll
        for (int i = 0; i < 4; i++) {
          e[i][0] = e[i][1] = e[i][2] = e[i][3] = 0.f;
          mma16(e[i], af[0][0], af[0][1], af[0][2], af[0][3], qt[i][0], qt[i][1]);
        }
#pragma unroll
        for (int i = 0; i < 4; i++) mma16(e[i], af[1][0], af[1][1], af[1][2], af[1][3], qt[i][2], qt[i][3]);
        SCHED_FENCE(55);
        if (s < 63) BAR_ARRIVE(B_S, 416);
        SCHED_FENCE(58);
        v[0] = lds4(tA + (VX0 - TA)); v[1] = lds4(tA + (VX0 - TA) + 2048); v[2] = lds4(tA + (VX1 - TA)); v[3] = lds4(tA + (VX1 - TA) + 2048);
#pragma unroll
        for (int i = 0; i < 4; i++) ts[i] = PACK(e[i]);
        while ((int)(clk() - c0) < 0) {}
        TS(5);
#pragma unroll
        for (int u = 0; u < 4; u++) r[u] = ldg_b64(XP_(xs) + u * 256);
        BAR_ARRIVE(B_S2, 256);
      }
      const uint32_t fn = (L16 & 256) ? 0xfc00fc00u : 0u;
      SCHED_FENCE(56);
      float4 e = softmax2<false>(r, 0, fn);
      const bool vbad = anybad(v[0].x, v[1].x, v[2].x, v[3].x, tag);
      if (BADS(r)) {
        int it = 0;
        if (s > 8) sts1(tA + 4096 + 8, min(lds1(tA + 4096 + 8) + dX, 500));
        do {
          RP(1);
          if (++it > SPIN_LIMIT) __trap();
#pragma unroll
          for (int u = 0; u < 4; u++) r[u] = ldg_b64(XP_(xs) + u * 256);
        } while (BADS(r));
        e = softmax2<false>(r, 0, fn);
      }
      sts1(t0.z, pk(e.x, e.y)); sts1(t0.z + 128, pk(e.z, e.w));
#pragma unroll
      for (int i = 0; i < 4; i++) publish(XP_(xo) + X_TOK + i * 4096, ts[i]);
      TS(6);
      if (s < 63) BAR_SYNC(B_V, 512); else BAR_SYNC(B_V, 256);
      uint32_t O[4];
      uint4 vn[2];
      {
        uint32_t p[4], pm;
        ldsm4t(p, pr);
        asm volatile("ldmatrix.sync.aligned.m8n8.x1.trans.shared.b16 {%0},[%1];" : "=r"(pm) : "r"(pr + 512) : "memory");
        vn[0] = lds4(tA + (VN - TA)); vn[1] = lds4(tA + (VN - TA) + 2048);
        pv_mem(p, pm, v, vn, O);
        if (vbad) {
          int it = 0;
          do {
            if (++it > SPIN_LIMIT) __trap();
#pragma unroll
            for (int u = 0; u < 4; u++) v[u] = ldg_b128(XP_((LO(xc) + (lds1(sb + PACE + 24) >> 2) * 262144 + ((tA - L16 - TA) >> 9) * XC + l16) ^ ring) + X_VX(u));
          } while (anybad(v[0].x, v[1].x, v[2].x, v[3].x, tag));
          pv_mem(p, pm, v, vn, O);
        }
      }
      stsm4(tA + (OB - TA), O[0], O[1], O[2], O[3]);
      if (s < 63) BAR_ARRIVE(B_O, 416);
      TS(2);
      c0 = clk() + dG;
      SCHED_FENCE(60);
      if (tA == sb + TA) mbar_expect(sb + BARS, 2048);
      const uint32_t vs[4] = {addbf(vn[0].x, vn[0].z), addbf(vn[0].y, vn[0].w), addbf(vn[1].x, vn[1].z), addbf(vn[1].y, vn[1].w)};
      {
        const char* xt = XP_(lds1(tA + 12) ^ ring);
        const uint2 t1 = lds2u(tA + 2048);
        const uint32_t pw = lds1(tA + 8);
        uint2 rt[4];
        CONSUME(LO(xt) ^ t1.x ^ pw);
        while ((int)(clk() - c0) < 0) {}
        int it = 0;
        do {
          if (++it > SPIN_LIMIT) __trap();
#pragma unroll
          for (int u = 0; u < 4; u++) rt[u] = ldg_b64(xt + u * 256);
        } while (BADS(rt));
        const float4 et = softmax2<true>(rt, t1.x, t1.y);
        sts1(pw + 1024, pk(et.x, et.y)); sts1(pw + 1024 + 128, pk(et.z, et.w));
      }
      s = PIN(s);
      BAR_SYNC(B_SC, 128);
      {
        uint32_t Ot[4], p[4], pm;
        const uint2 t2 = lds2u(tA + 2048 + 8);
        ldsm4t(p, pr + 1024);
        asm volatile("ldmatrix.sync.aligned.m8n8.x1.trans.shared.b16 {%0},[%1];" : "=r"(pm) : "r"(pr + 1024 + 512) : "memory");
        char* od = (char*)g_O + ((s >> 2) * 1048576 + (s & 3) * 4096) + t2.x;
        CONSUME(LO(od) ^ HI(od) ^ pm ^ p[3]);
        TS(9);
        if (s < 62) BAR_SYNC(B_P, 384);
        pv_tok(p, pm, v, vs, Ot);
        asm volatile("stmatrix.sync.aligned.m8n8.x4.trans.shared.b16 [%0],{%1,%2,%3,%4};" ::"r"(t2.y), "r"(Ot[0]), "r"(Ot[1]), "r"(Ot[2]), "r"(Ot[3]) : "memory");
        __syncwarp();
        *(uint4*)od = lds4(tA + (OT - TA));
      }
    }
    FENCE_ASYNC();
    BAR_SYNC(B_SC, 128);
    if (tA == sb + TA) red_rlx(&g_fin);
  }
  __syncwarp();
  CLUSTER_SYNC();
  PH(5);
}
#undef wg
#undef iw
#undef h
#undef j
#undef a
#undef bb
#undef oi
#undef owner
#undef vfin
#undef xbar
#undef pr
#undef PIN
#undef XP_
#undef tw
#undef is7
#undef REFRESH
#undef lane
#undef l16
#undef lrow
#undef lar
#undef lpub

namespace ffn {
constexpr uint32_t BR = 98304;
constexpr uint32_t STG = 196608;
constexpr uint32_t PRM = 229376;
constexpr uint32_t BARS = PRM + 2816;
constexpr uint32_t SMEM = BARS + 18 * 8;
}
#define Y_TILE(rb, kt) (((ALIAS & 1) ? g_h : g_h2) + ((rb) * 16 + (kt)) * 1024)
#define U_TILE(rb, kt) ((ALIAS & 2) ? g_O + ((rb) * 64 + (kt)) * 1024 : g_U + ((rb) * 56 + (kt)) * 1024)
struct FfnMaps { CUtensorMap wo, w1a, w1b, w2, x, out; };

template <int N>
__device__ __forceinline__ void wg_ss(float* d, uint64_t a, uint64_t b, int sd) {
  if (N == 128) wgmma_ss_n128(d, a, b, sd);
  if (N == 192) wgmma_ss_n192(d, a, b, sd);
}
template <int N>
__device__ __forceinline__ void acc_fence(float* d) {
#pragma unroll
  for (int i = 0; i < N; i++) asm volatile("" : "+f"(d[i])::"memory");
}
#define UNPK8(d, v) do { (d)[0] = blo(v.x); (d)[1] = bhi(v.x); (d)[2] = blo(v.y); (d)[3] = bhi(v.y); (d)[4] = blo(v.z); (d)[5] = bhi(v.z); (d)[6] = blo(v.w); (d)[7] = bhi(v.w); } while (0)
struct FfnPipe {
  uint32_t full, emp, ph, aoff;
  int st, sB, prev;
  bool leader;
  template <int N>
  __device__ __forceinline__ void issue(float* acc, bool first, uint32_t a = 0) {
    mbar_wait(full + st * 8, ph);
    const uint64_t da = mkdesc((a ? a : 1024 + st * 16384) + aoff, 16, 1024), db = mkdesc(1024 + ffn::BR + sB * (N * 128), 8192, 1024);
    WG_FENCE();
#pragma unroll
    for (int j = 0; j < ((DBG & 1) ? 1 : 4); j++) wg_ss<N>(acc, da + j * 2, db + j * 128, j || !first);
    WG_COMMIT();
    if (++sB == 768 / N) sB = 0;
  }
  __device__ __forceinline__ void release() { if (leader) mbar_arrive(emp + prev * 8); }
  __device__ __forceinline__ void next() { prev = st; if (++st == 6) { st = 0; ph ^= 1; } }
  __device__ __forceinline__ void retire() { WG_WAIT(1); release(); next(); }
};
__device__ __forceinline__ float gelu_h(float hx) {
  float u = hx * fmaf(hx * hx, 8.f * 0.0356774081f, 2.f * 0.7978845608f), t;
  if (DBG & 4) return hx;
  if (DBG & 2) t = u; else
  asm("tanh.approx.f32 %0,%1;" : "=f"(t) : "f"(u));
  return fmaf(hx, t, hx);
}
struct FfnEpi {
  uint32_t st2, cc, flip, staged, l0;
  uint2 c;
  float n0, n1, s0, s1;
  __device__ __forceinline__ void flush(uint32_t r) {
    __syncwarp();
    asm volatile("{.reg .pred p; setp.ne.u32 p,%1,0; @p mbarrier.arrive.shared.b64 _,[%0];}" ::"r"(staged + (flip >> 11)), "r"(l0 & r) : "memory");
    flip ^= r << 14;
  }
  __device__ __forceinline__ void half(const float* d, int J, int r) {
#define PRE(i, n, c1, c2) gelu_h(fmaf(r ? d[4 + i] : d[i], i < 2 ? s0 : s1, fmaf(n, c1, c2)))
    asm volatile("stmatrix.sync.aligned.m8n8.x2.shared.b16 [%0],{%1,%2};" ::"r"((st2 ^ ((J & 3) * 32 + r * 16)) + flip),
                 "r"(pk(PRE(0, n0, blo(c.x), blo(c.y)), PRE(1, n0, bhi(c.x), bhi(c.y)))), "r"(pk(PRE(2, n1, blo(c.x), blo(c.y)), PRE(3, n1, bhi(c.x), bhi(c.y)))) : "memory");
#undef PRE
    if ((J & 3) == 3) flush(r);
    cc += r ? 56 : 8;
    c = lds2u(cc);
  }
};

__global__ void __launch_bounds__(384, 1)
k_ffn(const __grid_constant__ FfnMaps mp, const bf16* __restrict__ b2) {
  using namespace ffn;
  extern __shared__ __align__(1024) char smem[];
  const uint32_t sb = (uint32_t)__cvta_generic_to_shared(smem);
  if (sb != 1024) __trap();
  const int tid = threadIdx.x, lane = tid & 31, wg = __shfl_sync(~0u, tid >> 7, 0);
  const uint32_t full = sb + BARS, emp = full + 48, xbar = full + 96, staged = full + 104, tile = full + 136;
  uint32_t fin = 0;
  if (tid >= 288 && tid < 320) fin = ld_acq(&g_fin);
  if (tid < 32) {
    unsigned sm, v = 0;
    asm("mov.u32 %0,%%smid;" : "=r"(sm));
    if (tid == 0) {
      v = atomicExch(&g_slot[sm & 255], 0);
      for (int i = 0; i < 6; i++) { mbar_init(full + i * 8, 1); mbar_init(emp + i * 8, 2); }
      mbar_init(xbar, 2);
      for (int i = 0; i < 2; i++) { mbar_init(staged + i * 8, 8); mbar_init(staged + 16 + i * 8, 1); }
      FENCE_ASYNC_SMEM();
    }
    v = __shfl_sync(~0u, v, 0);
    if (!v) {
      wait_cnt(&g_fin, 128);
      for (int it = 0; !v; it++) {
        const uint4 a = ldg_rlx4(g_slot + tid * 8), b = ldg_rlx4(g_slot + tid * 8 + 4);
        const uint32_t open = __ballot_sync(~0u, a.x | a.y | a.z | a.w | b.x | b.y | b.z | b.w);
        if (!open) break;
        if (it < 16) { __nanosleep(500); continue; }
        if (tid == __ffs(open) - 1) v = atomicExch(&g_slot[tid * 8 + (a.x ? 0 : a.y ? 1 : a.z ? 2 : a.w ? 3 : b.x ? 4 : b.y ? 5 : b.z ? 6 : 7)], 0);
        v = __shfl_sync(~0u, v, __ffs(open) - 1);
      }
    }
    if (tid == 0) sts1(tile, v);
  }
  if (tid == 256) asm volatile("prefetch.tensormap [%0];" ::"l"(&mp.wo) : "memory");
  __syncthreads();
  const int bid = __shfl_sync(~0u, lds1(tile), 0) - 1;
  if (bid < 0) return;
  PH(6);
  FT(1);
  const int rb = bid >> 3, nb = bid & 7;
  unsigned* cnt = g_cnt + rb * 128;
  if (wg == 2) {
    asm volatile("setmaxnreg.dec.sync.aligned.u32 " FRP ";");
    const int pw = __shfl_sync(~0u, (tid >> 5) & 3, 0);
    uint32_t ws = emp, wp = 1, fs = full;
    auto wait_free = [&]() { mbar_wait_q(ws, wp); ws += 8; if (ws == emp + 48) { ws = emp; wp ^= 1; } };
    auto step = [&]() { fs += 8; if (fs == full + 48) fs = full; };
#define K3(c) ((0x65230 >> (c) * 4) & 7)
#define KC(k) ((k) < 2 ? nb * 2 + (k) : (k) < 9 ? ((k) - 2 + ((k) - 2 >= nb)) * 2 : ((k) - 9 + ((k) - 9 >= nb)) * 2 + 1)
    if (pw == 0) {
      uint32_t d = sb + BR + 32768;
      auto put = [&](const CUtensorMap* m, int k, int c) {
        e_expect_tma3d(d, m, k * 64, c, fs, 32768);
        step();
        d += 16384;
        if (d == sb + STG) d = sb + BR;
      };
      int n = 0;
      auto stage_free = [&]() { if (!(n & 7) && n < 56) mbar_wait_q(staged + 16 + (n & 8), (n >> 4) & 1); n++; };
      FTP(3);
#pragma unroll 1
      for (int k = 0; k < 66; k++) { wait_free(); if (k < 64) put(&mp.wo, k, nb * 2); }
#pragma unroll 1
      for (int k = 0; k < 16; k++) {
        const int kt = KC(k);
        wait_free();
        e_expect_tma3d(sb + BR + (k & 3) * 24576, &mp.w1b, kt * 64, nb * 7, fs, k < 2 ? 24576 : 40960);
        step();
      }
#pragma unroll 1
      for (int k = 0; k < 32; k++) { stage_free(); if (k != 5 && k != 6) wait_free(); put(&mp.w1a, k & 15, nb * 7 + 3 + (k >> 4) * 2); }
#pragma unroll 1
      for (int c = 0; c < 5; c++)
#pragma unroll 1
        for (int k = K3(c), i = 0; k < 56; k += c < 2 && (i ^= 1) ? 1 : c < 2 ? 6 : 7) { stage_free(); wait_free(); put(&mp.w2, k, nb * 2); }
    } else if (pw == 1) {
      FTP(5);
      if (fin < 128) wait_cnt(&g_fin, 128);
      FTP(6);
      uint32_t d = sb;
      auto put = [&](const uint4* A, bool ld) {
        wait_free();
        if (ld) e_bulk_ld(d, A, 16384, fs);
        step();
        d += 16384;
        if (d == sb + BR) d = sb;
      };
      const uint4* A = g_O + rb * 65536;
#pragma unroll 1
      for (int k = 0; k < 66; k++) put(A + k * 1024, k < 64);
      A = Y_TILE(rb, 0);
      uint32_t ready = 0;
#pragma unroll 1
      for (int k = 2; k < 48; k++) {
        const int kt = k < 16 ? KC(k) : k & 15;
        for (int it = 0; !(ready >> ((kt >> 1) + (kt & 1) * 8) & 1); it++) {
          ready = __ballot_sync(~0u, ldg_rlx1(cnt + (lane & 7)) & ((lane & 8) ? 1 : 0x10000));
          if (it > SPIN_LIMIT) __trap();
        }
        if (k == 2) FTP(75);
        put(A + kt * 1024, true);
      }
      A = U_TILE(rb, 0);
#pragma unroll 1
      for (int c = 0; c < 5; c++) {
        for (int it = 0; ldg_rlx1(cnt + 32 + c) < 8; it++) if (it > SPIN_LIMIT) __trap();
#pragma unroll 1
        for (int k = K3(c), i = 0; k < 56; k += c < 2 && (i ^= 1) ? 1 : c < 2 ? 6 : 7) put(A + k * 1024, true);
      }
    } else if (pw == 2) {
      for (int i = 0; i < XDL; i++) {
        mbar_wait_q(emp, i & 1);
        if (XPF && i == 1 && lane < 2) tma2d_pf(&mp.x, nb * 128 + lane * 64, rb * 128);
      }
      if (lane == 0) {
        mbar_expect(xbar, 32768);
        tma2d(sb + STG, &mp.x, nb * 128, rb * 128, xbar);
        tma2d(sb + STG + 16384, &mp.x, nb * 128 + 64, rb * 128, xbar);
      }
      asm volatile("griddepcontrol.wait;" ::: "memory");
      if (lane < 16) g_modp[bid * 16 + lane] = make_uint4(0, 0, 0, 0);
      if (lane == 16 && bid == 0) { g_hcnt = 0; g_mcnt = 0; }
      if (lane == 0) {
#pragma unroll 1
        for (int g = 1; g < 9; g++) {
          if (g == 1) mbar_wait(staged + 8, 0); else { mbar_wait_q(staged + (g & 1) * 8, (g >> 1) & 1); FENCE_ASYNC_SMEM(); }
          bulk_st(g == 1 ? Y_TILE(rb, nb * 2 + 1) : U_TILE(rb, nb * 7 + ((0x652431000ull >> g * 4) & 7)), sb + STG + (g & 1) * 16384, 16384);
          BULK_COMMIT();
          if (g != 2 && g != 4) { BULK_WAIT(0); red_rlx(g == 1 ? cnt + nb : cnt + 32 + (g < 6 ? g >> 2 : g - 4)); }
          BULK_WAIT_READ(0);
          mbar_arrive(staged + 16 + (g & 1) * 8);
        }
      }
    } else {
      const uint32_t prm = sb + PRM, pp = prm + (lane >> 3) * 64 + (lane & 1) * 32 + (lane & 6) * 2;
      const uint2 v2 = ((const uint2*)(b2 + nb * 128))[lane];
      sts1(pp + 768, v2.x); sts1(pp + 784, v2.y);
      asm volatile("griddepcontrol.wait;" ::: "memory");
      const float4* md = (const float4*)(g_mod + nb * 128) + lane;
      { const float4 ga = md[512]; sts1(pp, pk(ga.x, ga.y)); sts1(pp + 16, pk(ga.z, ga.w)); }
      { const float4 cb = md[1024]; sts1(pp + 256, pk(1.f + cb.x, 1.f + cb.y)); sts1(pp + 272, pk(1.f + cb.z, 1.f + cb.w)); }
      { const float4 gb = md[1280]; sts1(pp + 512, pk(gb.x, gb.y)); sts1(pp + 528, pk(gb.z, gb.w)); }
#pragma unroll 1
      for (int i = lane; i < 112; i += 32) { const uint4 c = g_cc[nb * 112 + i]; sts4(prm + 1024 + i * 16, c.x, c.y, c.z, c.w); }
      __syncwarp();
      if (lane == 0) {
        mbar_arrive(xbar);
        mbar_wait(staged, 0);
        bulk_st(Y_TILE(rb, nb * 2), sb + STG, 16384);
        BULK_COMMIT(); BULK_WAIT(0);
        asm volatile("red.relaxed.gpu.global.add.u32 [%0],0x10000;" ::"l"(cnt + nb) : "memory");
        mbar_arrive(staged + 16);
      }
      __syncwarp();
      mbar_wait_q(staged + 24, 0);
      mbar_wait_q(emp + 40, 0);
#pragma unroll 1
      for (int i = 0; i < 4; i++) {
        const uint4* sp = g_stat + (rb * 128 + i * 32 + lane) * 4;
        uint4 v[4];
        for (int it = 0;; it++) {
          uint32_t m = 0;
#pragma unroll
          for (int u = 0; u < 4; u++) { v[u] = ldg_rlx4(sp + u); m = max(max(m, max(v[u].x, v[u].y)), max(v[u].z, v[u].w)); }
          if (!__any_sync(~0u, m == ~0u)) break;
          if (it > SPIN_LIMIT) __trap();
        }
        float m = 0, q = 0;
#pragma unroll
        for (int u = 0; u < 4; u++) m += F_(v[u].x) + F_(v[u].z);
        m *= 0.125f;
#pragma unroll
        for (int u = 0; u < 4; u++) { const float a = F_(v[u].x) - m, b = F_(v[u].z) - m; q += F_(v[u].y) + F_(v[u].w) + 128.f * (a * a + b * b); }
        const float r = 0.5f * rsqrtf(q * (1.f / 1024) + 1e-5f);
        sts2(sb + STG + 16384 + (i * 32 + lane) * 8, U_(r), U_(-m * r));
      }
      __syncwarp();
      if (lane < 2) mbar_arrive(xbar);
    }
  } else {
    asm volatile("setmaxnreg.inc.sync.aligned.u32 " FRC ";");
    const int w = (tid >> 5) & 3, q = lane & 3;
    const uint32_t prm = sb + PRM + q * 16;
    const int row0 = wg * 64 + w * 16;
    FfnPipe p;
    p.full = full; p.emp = emp; p.ph = 0; p.aoff = wg * 8192; p.st = 0; p.sB = 2; p.prev = 0; p.leader = (tid & 127) == 0;
    FfnEpi e;
    const uint32_t stg = sb + STG + row0 * 128;
    e.st2 = stg + (lane & 15) * 128 + ((lane & 7) << 4);
    e.cc = sb + PRM + 1024 + q * 16; e.flip = 0; e.staged = staged; e.l0 = lane == 0;
    const uint32_t stw = e.st2 ^ (lane & 16);
    uint32_t x1[32];
    uint4* sp = g_stat + (rb * 128 + row0 + (lane >> 2)) * 4;
    float old[96], r0_, r1_;
    {
      float acc[64];
      p.issue<128>(acc, true); FT(8); p.next();
#pragma unroll 1
      for (int k = 1; k < 64; k++) { p.issue<128>(acc, false); FT(8 + k); p.retire(); }
      float xf[64], gf[32];
      uint32_t cb[16];
      mbar_wait(xbar, 0);
#pragma unroll
      for (int j = 0; j < 8; j++) {
        uint32_t xv[4];
        ldsm4(xv, (stw ^ ((j & 3) * 32)) + (j >> 2) * 16384);
#pragma unroll
        for (int i = 0; i < 4; i++) { xf[j * 8 + i * 2] = blo(xv[i]); xf[j * 8 + i * 2 + 1] = bhi(xv[i]); }
      }
#pragma unroll
      for (int i = 0; i < 4; i++) {
        const uint4 g = lds4(prm + i * 64), c = lds4(prm + 256 + i * 64);
        UNPK8(gf + i * 8, g);
        cb[i * 4] = c.x; cb[i * 4 + 1] = c.y; cb[i * 4 + 2] = c.z; cb[i * 4 + 3] = c.w;
      }
      acc_fence<64>(xf); acc_fence<32>(gf);
      WG_WAIT(0);
      p.release();
      acc_fence<64>(acc);
      PH(7); FT(72);
#pragma unroll
      for (int j = 0; j < 8; j++) {
        uint32_t* o = x1 + j * 4;
#pragma unroll
        for (int i = 0; i < 4; i++)
          o[i] = pk(fmaf(acc[j * 8 + i * 2], gf[j * 4 + (i & 2)], xf[j * 8 + i * 2]), fmaf(acc[j * 8 + i * 2 + 1], gf[j * 4 + (i & 2) + 1], xf[j * 8 + i * 2 + 1]));
        stsm4((stw ^ ((j & 3) * 32)) + (j >> 2) * 16384, mulbf(o[0], cb[j * 2]), mulbf(o[1], cb[j * 2]), mulbf(o[2], cb[j * 2 + 1]), mulbf(o[3], cb[j * 2 + 1]));
        if ((j & 3) == 3) { FENCE_ASYNC_SMEM(); e.flush(1); }
      }
      if (wg) BAR_SYNC(2, 128); else BAR_SYNC(3, 128);
    }
    PH(8); FT(73);
    float acc[64];
    {
      float* accC = old;
      p.sB = 0;
      p.issue<192>(accC, true, 1024 + STG); FT(80); p.next();
      p.issue<192>(accC, false, 1024 + STG + 16384); FT(81);
      FT(78);
      float s0 = 0, s1 = 0;
#define X1_FENCE _Pragma("unroll") for (int j = 0; j < 32; j++) asm volatile("" : "+r"(x1[j]));
      X1_FENCE
#pragma unroll
      for (int j = 0; j < 16; j++) { s0 += blo(x1[j * 2]) + bhi(x1[j * 2]); s1 += blo(x1[j * 2 + 1]) + bhi(x1[j * 2 + 1]); }
      s0 += __shfl_xor_sync(~0u, s0, 1); s1 += __shfl_xor_sync(~0u, s1, 1);
      s0 += __shfl_xor_sync(~0u, s0, 2); s1 += __shfl_xor_sync(~0u, s1, 2);
      s0 *= 1.f / 128; s1 *= 1.f / 128;
      float q0 = 0, q1 = 0;
      X1_FENCE
#pragma unroll
      for (int j = 0; j < 16; j++) {
        const float a = blo(x1[j * 2]) - s0, b = bhi(x1[j * 2]) - s0, c = blo(x1[j * 2 + 1]) - s1, d = bhi(x1[j * 2 + 1]) - s1;
        q0 += a * a + b * b; q1 += c * c + d * d;
      }
      q0 += __shfl_xor_sync(~0u, q0, 1); q1 += __shfl_xor_sync(~0u, q1, 1);
      q0 += __shfl_xor_sync(~0u, q0, 2); q1 += __shfl_xor_sync(~0u, q1, 2);
      if (q < 2) {
        uint32_t m = __float_as_uint(q ? s1 : s0), v = __float_as_uint(q ? q1 : q0);
        if (m == ~0u) m = 0x7fffffffu;
        if (v == ~0u) v = 0x7fffffffu;
        stg_rlx2((uint2*)(sp + q * 32) + nb, m, v);
      }
      X1_FENCE
      p.retire();
#pragma unroll 1
      for (int k = 2; k < 15; k++) { p.issue<192>(accC, false); FT(80 + k); p.retire(); }
      p.issue<192>(accC, false); FT(95);
      mbar_wait(xbar, 1);
      const float2 u0 = lds2f(sb + STG + 16384 + (row0 + (lane >> 2)) * 8), u1 = lds2f(sb + STG + 16384 + (row0 + (lane >> 2)) * 8 + 64);
      r0_ = u0.x; e.n0 = u0.y; r1_ = u1.x; e.n1 = u1.y;
      e.c = lds2u(e.cc);
      p.retire();
      e.s0 = r0_; e.s1 = r1_;
    }
    PH(9);
    {
      auto pair = [&](int J, bool first, int fo) {
#pragma unroll 1
        for (int r = 0; r < 2; r++) { p.issue<128>(acc, first && !r); FT(fo + r); p.retire(); acc_fence<8>(old + J * 8); e.half(old + J * 8, J, r); }
      };
#pragma unroll 1
      for (int i = 0; i < 3; i++) {
        if (i == 2) {
          e.s0 = r0_; e.s1 = r1_;
#pragma unroll
          for (int J = 8; J < 12; J++) pair(J, J == 8, 128 + (J - 8) * 2);
          e.cc += 512; e.c = lds2u(e.cc);
          e.s0 = e.s1 = 1.f;
        }
#pragma unroll
        for (int J = 0; J < 8; J++) pair(J, J == 0 && i < 2, 96 + i * 16 + (i >> 1) * 8 + J * 2);
        if (i == 2) break;
        e.cc += i ? -768 : 256; e.c = lds2u(e.cc);
        WG_WAIT(0);
        acc_fence<64>(acc);
#pragma unroll
        for (int k = 0; k < 64; k++) old[k] = acc[k] * ((k & 2) ? r1_ : r0_);
        acc_fence<64>(old);
        e.s0 = e.s1 = 1.f;
        PH(10 + i);
      }
#pragma unroll 1
      for (int k = 24; k < 56; k++) { p.issue<128>(acc, false); FT(128 + k); p.retire(); }
      float xf[64], gf[32];
#pragma unroll
      for (int i = 0; i < 4; i++) {
        const uint4 g = lds4(prm + 512 + i * 64), h = lds4(prm + 768 + i * 64);
        float hf[8];
        UNPK8(gf + i * 8, g); UNPK8(hf, h);
#pragma unroll
        for (int u = 0; u < 8; u++) {
          const int c = (u >> 2) * 4 + (u & 2);
          xf[i * 16 + u * 2] = fmaf(gf[i * 8 + c], hf[c], blo(x1[i * 8 + u])); xf[i * 16 + u * 2 + 1] = fmaf(gf[i * 8 + c + 1], hf[c + 1], bhi(x1[i * 8 + u]));
        }
      }
      acc_fence<64>(xf); acc_fence<32>(gf);
      mbar_wait(staged + 24, 1);
      mbar_wait(staged + 16, 0);
      WG_WAIT(0);
      acc_fence<64>(acc);
      PH(13); FT(184);
#pragma unroll
      for (int j = 0; j < 8; j++) {
        uint32_t o[4];
#pragma unroll
        for (int i = 0; i < 4; i++)
          o[i] = pk(fmaf(acc[j * 8 + i * 2], gf[j * 4 + (i & 2)], xf[j * 8 + i * 2]), fmaf(acc[j * 8 + i * 2 + 1], gf[j * 4 + (i & 2) + 1], xf[j * 8 + i * 2 + 1]));
        stsm4((stw ^ ((j & 3) * 32)) + (j >> 2) * 16384, o[0], o[1], o[2], o[3]);
        if ((j & 3) == 3) {
          FENCE_ASYNC_SMEM();
          __syncwarp();
          if (lane == 0) { tma2d_st(&mp.out, nb * 128 + (j >> 2) * 64, rb * 128 + row0, stg + (j >> 2) * 16384); BULK_COMMIT(); }
        }
      }
      if (lane == 0) BULK_WAIT_READ(0);
      __syncwarp();
    }
  }
  PH(14); FT(185);
}

typedef CUresult (*EncFn)(CUtensorMap*, CUtensorMapDataType, cuuint32_t, void*, const cuuint64_t*, const cuuint64_t*, const cuuint32_t*,
                          const cuuint32_t*, CUtensorMapInterleave, CUtensorMapSwizzle, CUtensorMapL2promotion, CUtensorMapFloatOOBfill);
static void map2d(EncFn enc, CUtensorMap* m, const void* p, int rows, int cols, int boxRows) {
  cuuint64_t d[2] = {(cuuint64_t)cols, (cuuint64_t)rows}, s[1] = {(cuuint64_t)cols * 2};
  cuuint32_t b[2] = {64, (cuuint32_t)boxRows}, e[2] = {1, 1};
  enc(m, CU_TENSOR_MAP_DATA_TYPE_BFLOAT16, 2, (void*)p, d, s, b, e, CU_TENSOR_MAP_INTERLEAVE_NONE, CU_TENSOR_MAP_SWIZZLE_128B,
      CU_TENSOR_MAP_L2_PROMOTION_L2_128B, CU_TENSOR_MAP_FLOAT_OOB_FILL_NONE);
}
static void map3d(EncFn enc, CUtensorMap* m, const void* p, int rows, int cols, int nch) {
  cuuint64_t d[3] = {64, (cuuint64_t)rows, (cuuint64_t)(cols / 64)}, s[2] = {(cuuint64_t)cols * 2, 128};
  cuuint32_t b[3] = {64, 64, (cuuint32_t)nch}, e[3] = {1, 1, 1};
  enc(m, CU_TENSOR_MAP_DATA_TYPE_BFLOAT16, 3, (void*)p, d, s, b, e, CU_TENSOR_MAP_INTERLEAVE_NONE, CU_TENSOR_MAP_SWIZZLE_128B,
      CU_TENSOR_MAP_L2_PROMOTION_L2_128B, CU_TENSOR_MAP_FLOAT_OOB_FILL_NONE);
}

extern "C" void kernel_launch(void* const* d_in, const int* in_sizes, int n_in, void* d_out, int out_size) {
  const bf16* x = (const bf16*)d_in[0];
  const bf16* mem0 = (const bf16*)d_in[1];
  void* fn = nullptr;
  cudaDriverEntryPointQueryResult qr;
  cudaGetDriverEntryPoint("cuTensorMapEncodeTiled", &fn, cudaEnableDefault, &qr);
  EncFn enc = (EncFn)fn;
  FfnMaps fm = {};
  map3d(enc, &fm.wo, d_in[5], 4096, 1024, 2);
  map3d(enc, &fm.w1a, d_in[8], 1024, 3584, 2);
  map3d(enc, &fm.w1b, d_in[8], 1024, 3584, 3);
  map3d(enc, &fm.w2, d_in[10], 3584, 1024, 2);
  map2d(enc, &fm.x, x, 2048, 1024, 128);
  map2d(enc, &fm.out, d_out, 2048, 1024, 16);
  RecMaps rm = {};
  map2d(enc, &rm.wq, d_in[2], 1024, 4096, 128);
  map2d(enc, &rm.wk, d_in[3], 1024, 4096, 128);
  map2d(enc, &rm.wv, d_in[4], 1024, 4096, 16);
  map2d(enc, &rm.wo, d_in[5], 4096, 1024, 128);
  {
    void* ar = nullptr;
    cudaGetSymbolAddress(&ar, g_ar);
    cuuint64_t d[2] = {512, 160}, sd[1] = {1024};
    cuuint32_t bi[2] = {64, 40}, e[2] = {1, 1};
    enc(&rm.ari, CU_TENSOR_MAP_DATA_TYPE_BFLOAT16, 2, ar, d, sd, bi, e, CU_TENSOR_MAP_INTERLEAVE_NONE, CU_TENSOR_MAP_SWIZZLE_NONE,
        CU_TENSOR_MAP_L2_PROMOTION_NONE, CU_TENSOR_MAP_FLOAT_OOB_FILL_NONE);
  }
  cudaFuncSetAttribute(k_ffn, cudaFuncAttributeMaxDynamicSharedMemorySize, ffn::SMEM);
  cudaFuncSetAttribute(k_rec, cudaFuncAttributeMaxDynamicSharedMemorySize, rec::SMEM);
  char* xc = nullptr;
  cudaGetSymbolAddress((void**)&xc, g_xc);
  xc += (0 - (uintptr_t)xc) & 0x3FFFF;
  cudaStream_t st = cudaStreamPerThread;
  int dF = 450, dA = 2700, dS = 300, dM = 120, dG = 350, dP = 24, dX = 48, dD = 350, dZ = 0, dZ2 = 1, dV = 370, dX2 = 0;
  k_rec<<<132, 512, rec::SMEM, st>>>(rm, mem0, x, (const bf16*)d_in[12], (const bf16*)d_in[13], (const char*)d_in[8], (const bf16*)d_in[9],
                                     (const char*)d_in[5], xc, dF, dA, dS, dM, dG, dP, dX, dD, dZ, dZ2, dV, dX2);
  cudaLaunchConfig_t cfg = {};
  cfg.gridDim = dim3(132); cfg.blockDim = dim3(384); cfg.dynamicSmemBytes = ffn::SMEM; cfg.stream = st;
  cudaLaunchAttribute at[1];
  at[0].id = cudaLaunchAttributeProgrammaticStreamSerialization;
  at[0].val.programmaticStreamSerializationAllowed = 1;
  cfg.attrs = at; cfg.numAttrs = 1;
  cudaLaunchKernelEx(&cfg, k_ffn, fm, (const bf16*)d_in[11]);
}
```

```cpp
#include <cuda_runtime.h>
#include <cuda.h>
#include <cuda_bf16.h>
#include <stdint.h>

typedef __nv_bfloat16 bf16;

__device__ __align__(16) float g_mod[6144];
__device__ __align__(1024) uint4 g_modp[4 * 512];
__device__ unsigned g_hcnt;
__device__ unsigned g_hf[4];
__device__ __align__(1024) uint4 g_h[2048 * 1024 / 8];
__device__ __align__(1024) uint4 g_O[2048 * 4096 / 8];
__device__ __align__(1024) uint4 g_h2[2048 * 1024 / 8];
__device__ __align__(1024) uint4 g_U[2048 * 3584 / 8];
__device__ __align__(1024) uint4 g_stat[2048 * 4];
__device__ __align__(1024) unsigned g_cnt[16 * 4 * 32];
__device__ unsigned g_mcnt;
__device__ unsigned g_slot[256];
__device__ unsigned g_fin;
__device__ __align__(16) uint4 g_cc[224 * 4];
__device__ __align__(1024) uint4 g_ar[160 * 64];
__device__ __align__(1024) uint4 g_xc[33 * 16384];
__device__ __align__(1024) unsigned g_tm[4 * 256];
#define FT(i)
#define FTP(i)
#define PT(i)
#define PH(i)
#define RP(i)
#define RPN(i, s)
#define TSV(i, v)
#define TS(i)

#define WIN 3
#define FRC "232"
#define FRP "40"
#define YR 1
#define XPK 0
#define NFA 1
#define PINM 1
#define FMAP (((g >> 2) * 4 + m) * 8 + (g & 3) * 2 + (blockIdx.x & 1))
#define FDB 0
#define ALIAS 3
#define EF 0
#define XPF 0
#define PFT 150000
#define PFS 104
#define PF0 13000
#define PFD 128
#define XDL 6
#define QW 0
#define PDS 61
#define P_NVR 5
#define P_NVP 2
#define P_NWP 9
#define P_NW1 7
#define RF_ 208
#define PSV 1
#define RA_ (488 - 2 * RF_)
#define XI 5
#define XL 1
#define WCH 2
#define HX 0
#define VB 1
#define TP 0
#define CKI 0
#define NOP_ 2
#define KVO 0
#define NDL 3
#define AM 0
#define XM 3
#define XP 0
#define SPIN_LIMIT (1 << 20)
__device__ __forceinline__ uint64_t mkdesc(uint32_t addr, uint32_t lbo, uint32_t sbo) {
  return (uint64_t)((addr & 0x3FFFF) >> 4) | ((uint64_t)(lbo >> 4) << 16) | ((uint64_t)(sbo >> 4) << 32) | (1ull << 62);
}
__device__ __forceinline__ void mbar_init(uint32_t a, int c) { asm volatile("mbarrier.init.shared.b64 [%0],%1;" ::"r"(a), "r"(c) : "memory"); }
__device__ __forceinline__ void mbar_wait(uint32_t a, uint32_t par) {
  asm volatile(
      "{.reg .pred p; .reg .u32 n;\n"
      "mov.u32 n, 0;\n"
      "W: mbarrier.try_wait.parity.shared.b64 p,[%0],%1;\n"
      "@p bra D;\n"
      "add.u32 n, n, 1;\n"
      "setp.lt.u32 p, n, %2;\n"
      "@p bra W;\n"
      "trap;\n"
      "D:}" ::"r"(a), "r"(par), "n"(SPIN_LIMIT) : "memory");
}
__device__ __forceinline__ void mbar_wait_q(uint32_t a, uint32_t par) {
  asm volatile(
      "{.reg .pred p; .reg .u32 n;\n"
      "mov.u32 n, 0;\n"
      "W: mbarrier.try_wait.parity.shared.b64 p,[%0],%1,4000;\n"
      "@p bra D;\n"
      "add.u32 n, n, 1;\n"
      "setp.lt.u32 p, n, %2;\n"
      "@p bra W;\n"
      "trap;\n"
      "D:}" ::"r"(a), "r"(par), "n"(SPIN_LIMIT / 16) : "memory");
}
__device__ __forceinline__ void mbar_expect(uint32_t a, uint32_t b) { asm volatile("mbarrier.arrive.expect_tx.shared.b64 _,[%0],%1;" ::"r"(a), "r"(b) : "memory"); }
__device__ __forceinline__ void mbar_arrive(uint32_t a) { asm volatile("mbarrier.arrive.shared.b64 _,[%0];" ::"r"(a) : "memory"); }
__device__ __forceinline__ uint32_t mapa(uint32_t a, uint32_t cta) { uint32_t r; asm("mapa.shared::cluster.u32 %0,%1,%2;" : "=r"(r) : "r"(a), "r"(cta)); return r; }
__device__ __forceinline__ void mbar_arrive_cl(uint32_t a) { asm volatile("mbarrier.arrive.shared::cluster.b64 _,[%0];" ::"r"(a) : "memory"); }
__device__ __forceinline__ void tma2d(uint32_t dst, const CUtensorMap* m, int c0, int c1, uint32_t mb) {
  asm volatile("cp.async.bulk.tensor.2d.shared::cluster.global.mbarrier::complete_tx::bytes [%0],[%1,{%2,%3}],[%4];" ::"r"(dst), "l"(m), "r"(c0), "r"(c1), "r"(mb) : "memory");
}
__device__ __forceinline__ void tma2d_pf(const CUtensorMap* m, int c0, int c1) {
  asm volatile("cp.async.bulk.prefetch.tensor.2d.L2.global [%0,{%1,%2}];" ::"l"(m), "r"(c0), "r"(c1) : "memory");
}
__device__ __forceinline__ void tma3d(uint32_t dst, const CUtensorMap* m, int c1, int c2, uint32_t mb) {
  asm volatile("cp.async.bulk.tensor.3d.shared::cluster.global.mbarrier::complete_tx::bytes [%0],[%1,{0,%2,%3}],[%4];" ::"r"(dst), "l"(m), "r"(c1), "r"(c2), "r"(mb) : "memory");
}
__device__ __forceinline__ void tma2d_st(const CUtensorMap* m, int c0, int c1, uint32_t src) {
  asm volatile("cp.async.bulk.tensor.2d.global.shared::cta.bulk_group [%0,{%1,%2}],[%3];" ::"l"(m), "r"(c0), "r"(c1), "r"(src) : "memory");
}
__device__ __forceinline__ void bulk_ld(uint32_t dst, const void* src, uint32_t n, uint32_t mb) {
  asm volatile("cp.async.bulk.shared::cluster.global.mbarrier::complete_tx::bytes [%0],[%1],%2,[%3];" ::"r"(dst), "l"(src), "r"(n), "r"(mb) : "memory");
}
__device__ __forceinline__ void bulk_ld_mc(uint32_t dst, const void* src, uint32_t n, uint32_t mb) {
  asm volatile("cp.async.bulk.shared::cluster.global.mbarrier::complete_tx::bytes.multicast::cluster [%0],[%1],%2,[%3],%4;" ::"r"(dst), "l"(src), "r"(n), "r"(mb), "h"((uint16_t)3) : "memory");
}
__device__ __forceinline__ void bulk_st(void* dst, uint32_t src, uint32_t n) {
  asm volatile("cp.async.bulk.global.shared::cta.bulk_group [%0],[%1],%2;" ::"l"(dst), "r"(src), "r"(n) : "memory");
}
__device__ __forceinline__ void e_expect_tma3d(uint32_t dst, const CUtensorMap* m, int c1, int c2, uint32_t mb, uint32_t bytes) {
  asm volatile("{.reg .pred p; elect.sync _|p, 0xffffffff; @p mbarrier.arrive.expect_tx.shared.b64 _,[%4],%5;\n"
               "@p cp.async.bulk.tensor.3d.shared::cluster.global.mbarrier::complete_tx::bytes [%0],[%1,{0,%2,%3}],[%4];}" ::"r"(dst), "l"(m), "r"(c1), "r"(c2), "r"(mb), "r"(bytes) : "memory");
}
__device__ __forceinline__ void e_bulk_ld(uint32_t dst, const void* src, uint32_t n, uint32_t mb) {
  asm volatile("{.reg .pred p; elect.sync _|p, 0xffffffff; @p cp.async.bulk.shared::cluster.global.mbarrier::complete_tx::bytes [%0],[%1],%2,[%3];}" ::"r"(dst), "l"(src), "r"(n), "r"(mb) : "memory");
}
__device__ __forceinline__ void e_bulk_ld_ef(uint32_t dst, const void* src, uint32_t n, uint32_t mb) {
  asm volatile("{.reg .pred p; .reg .b64 c; createpolicy.fractional.L2::evict_first.b64 c,1.0; elect.sync _|p, 0xffffffff;"
               " @p cp.async.bulk.shared::cluster.global.mbarrier::complete_tx::bytes.L2::cache_hint [%0],[%1],%2,[%3],c;}" ::"r"(dst), "l"(src), "r"(n), "r"(mb) : "memory");
}
__device__ __forceinline__ void e_bulk_ld_mc(uint32_t dst, const void* src, uint32_t n, uint32_t mb) {
  asm volatile("{.reg .pred p; elect.sync _|p, 0xffffffff; @p cp.async.bulk.shared::cluster.global.mbarrier::complete_tx::bytes.multicast::cluster [%0],[%1],%2,[%3],%4;}" ::"r"(dst), "l"(src), "r"(n), "r"(mb), "h"((uint16_t)3) : "memory");
}
#define BULK_COMMIT() asm volatile("cp.async.bulk.commit_group;" ::: "memory")
#define BULK_WAIT_READ(n) asm volatile("cp.async.bulk.wait_group.read " #n ";" ::: "memory")
#define BULK_WAIT(n) asm volatile("cp.async.bulk.wait_group " #n ";" ::: "memory")
#define FENCE_ASYNC_SMEM() asm volatile("fence.proxy.async.shared::cta;" ::: "memory")
#define FENCE_ASYNC() asm volatile("fence.proxy.async;" ::: "memory")
#define WG_FENCE() asm volatile("wgmma.fence.sync.aligned;" ::: "memory")
#define WG_COMMIT() asm volatile("wgmma.commit_group.sync.aligned;" ::: "memory")
#define WG_WAIT(n) asm volatile("wgmma.wait_group.sync.aligned " #n ";" ::: "memory")
#define BAR_SYNC(id, n) asm volatile("bar.sync %0,%1;" ::"n"(id), "n"(n) : "memory")
#define BAR_ARRIVE(id, n) asm volatile("bar.arrive %0,%1;" ::"n"(id), "n"(n) : "memory")
#define SCHED_FENCE(k) asm volatile("{.reg .pred p; setp.ne.u32 p,%0,0; @p trap;}" ::"r"(mp.zero[(k) - 46]) : "memory")
#define CLUSTER_SYNC() asm volatile("barrier.cluster.arrive.relaxed.aligned; barrier.cluster.wait.aligned;" ::: "memory")
__device__ __forceinline__ uint32_t pk(float lo, float hi) { uint32_t r; asm("cvt.rn.bf16x2.f32 %0,%1,%2;" : "=r"(r) : "f"(hi), "f"(lo)); return r; }
__device__ __forceinline__ float blo(uint32_t v) { return __uint_as_float(v << 16); }
__device__ __forceinline__ float bhi(uint32_t v) { return __uint_as_float(v & 0xffff0000u); }
__device__ __forceinline__ void ldsm4(uint32_t* r, uint32_t a) {
  asm volatile("ldmatrix.sync.aligned.m8n8.x4.shared.b16 {%0,%1,%2,%3},[%4];" : "=r"(r[0]), "=r"(r[1]), "=r"(r[2]), "=r"(r[3]) : "r"(a) : "memory");
}
__device__ __forceinline__ void ldsm4t(uint32_t* r, uint32_t a) {
  asm volatile("ldmatrix.sync.aligned.m8n8.x4.trans.shared.b16 {%0,%1,%2,%3},[%4];" : "=r"(r[0]), "=r"(r[1]), "=r"(r[2]), "=r"(r[3]) : "r"(a) : "memory");
}
__device__ __forceinline__ void stsm4(uint32_t a, uint32_t r0, uint32_t r1, uint32_t r2, uint32_t r3) {
  asm volatile("stmatrix.sync.aligned.m8n8.x4.shared.b16 [%0],{%1,%2,%3,%4};" ::"r"(a), "r"(r0), "r"(r1), "r"(r2), "r"(r3) : "memory");
}
__device__ __forceinline__ void mma16(float* d, uint32_t a0, uint32_t a1, uint32_t a2, uint32_t a3, uint32_t b0, uint32_t b1) {
  asm volatile("mma.sync.aligned.m16n8k16.row.col.f32.bf16.bf16.f32 {%0,%1,%2,%3},{%4,%5,%6,%7},{%8,%9},{%0,%1,%2,%3};"
               : "+f"(d[0]), "+f"(d[1]), "+f"(d[2]), "+f"(d[3]) : "r"(a0), "r"(a1), "r"(a2), "r"(a3), "r"(b0), "r"(b1));
}
__device__ __forceinline__ void mma8(float* d, uint32_t a0, uint32_t a1, uint32_t b0) {
  asm volatile("mma.sync.aligned.m16n8k8.row.col.f32.bf16.bf16.f32 {%0,%1,%2,%3},{%4,%5},{%6},{%0,%1,%2,%3};"
               : "+f"(d[0]), "+f"(d[1]), "+f"(d[2]), "+f"(d[3]) : "r"(a0), "r"(a1), "r"(b0));
}
__device__ __forceinline__ float4 lds4f(uint32_t a) { float4 v; asm volatile("ld.shared.v4.f32 {%0,%1,%2,%3},[%4];" : "=f"(v.x), "=f"(v.y), "=f"(v.z), "=f"(v.w) : "r"(a) : "memory"); return v; }
__device__ __forceinline__ float2 lds2f(uint32_t a) { float2 v; asm volatile("ld.shared.v2.f32 {%0,%1},[%2];" : "=f"(v.x), "=f"(v.y) : "r"(a) : "memory"); return v; }
__device__ __forceinline__ uint4 lds4(uint32_t a) { uint4 v; asm volatile("ld.shared.v4.u32 {%0,%1,%2,%3},[%4];" : "=r"(v.x), "=r"(v.y), "=r"(v.z), "=r"(v.w) : "r"(a) : "memory"); return v; }
__device__ __forceinline__ uint2 lds2u(uint32_t a) { uint2 v; asm volatile("ld.shared.v2.u32 {%0,%1},[%2];" : "=r"(v.x), "=r"(v.y) : "r"(a) : "memory"); return v; }
__device__ __forceinline__ uint32_t lds1(uint32_t a) { uint32_t v; asm volatile("ld.shared.u32 %0,[%1];" : "=r"(v) : "r"(a) : "memory"); return v; }
__device__ __forceinline__ void sts4(uint32_t a, uint32_t x, uint32_t y, uint32_t z, uint32_t w) { asm volatile("st.shared.v4.u32 [%0],{%1,%2,%3,%4};" ::"r"(a), "r"(x), "r"(y), "r"(z), "r"(w) : "memory"); }
__device__ __forceinline__ void sts2(uint32_t a, uint32_t x, uint32_t y) { asm volatile("st.shared.v2.u32 [%0],{%1,%2};" ::"r"(a), "r"(x), "r"(y) : "memory"); }
__device__ __forceinline__ void sts1(uint32_t a, uint32_t x) { asm volatile("st.shared.u32 [%0],%1;" ::"r"(a), "r"(x) : "memory"); }
__device__ __forceinline__ void sta4(uint32_t a, const uint32_t* v, uint32_t mb) {
  asm volatile("st.async.shared::cluster.mbarrier::complete_tx::bytes.v4.b32 [%0],{%1,%2,%3,%4},[%5];" ::"r"(a), "r"(v[0]), "r"(v[1]), "r"(v[2]), "r"(v[3]), "r"(mb) : "memory");
}
__device__ __forceinline__ uint4 ldg_rlx4(const void* p) { uint4 v; asm volatile("ld.relaxed.gpu.global.v4.u32 {%0,%1,%2,%3},[%4];" : "=r"(v.x), "=r"(v.y), "=r"(v.z), "=r"(v.w) : "l"(p) : "memory"); return v; }
__device__ __forceinline__ uint32_t ldg_rlx1(const void* p) { uint32_t v; asm volatile("ld.relaxed.gpu.global.u32 %0,[%1];" : "=r"(v) : "l"(p) : "memory"); return v; }
__device__ __forceinline__ uint2 ldg_rlx2(const void* p) { uint2 v; asm volatile("ld.relaxed.gpu.global.v2.u32 {%0,%1},[%2];" : "=r"(v.x), "=r"(v.y) : "l"(p) : "memory"); return v; }
__device__ __forceinline__ uint4 ldg_b128(const void* p) {
  uint4 v;
  asm volatile("{.reg .b128 t; .reg .b64 a,b; ld.relaxed.gpu.global.b128 t,[%4]; mov.b128 {a,b},t; mov.b64 {%0,%1},a; mov.b64 {%2,%3},b;}" : "=r"(v.x), "=r"(v.y), "=r"(v.z), "=r"(v.w) : "l"(p) : "memory");
  return v;
}
__device__ __forceinline__ void stg_b128(void* p, uint32_t x, uint32_t y, uint32_t z, uint32_t w) {
  asm volatile("{.reg .b128 t; .reg .b64 a,b; mov.b64 a,{%1,%2}; mov.b64 b,{%3,%4}; mov.b128 t,{a,b}; st.relaxed.gpu.global.b128 [%0],t;}" ::"l"(p), "r"(x), "r"(y), "r"(z), "r"(w) : "memory");
}
__device__ __forceinline__ void st_b128(void* p, uint32_t x, uint32_t y, uint32_t z, uint32_t w) {
  asm volatile("{.reg .b128 t; .reg .b64 a,b; mov.b64 a,{%1,%2}; mov.b64 b,{%3,%4}; mov.b128 t,{a,b}; st.relaxed.gpu.b128 [%0],t;}" ::"l"(p), "r"(x), "r"(y), "r"(z), "r"(w) : "memory");
}
__device__ __forceinline__ void stg_rlx4(void* p, uint32_t x, uint32_t y, uint32_t z, uint32_t w) { asm volatile("st.relaxed.gpu.global.v4.u32 [%0],{%1,%2,%3,%4};" ::"l"(p), "r"(x), "r"(y), "r"(z), "r"(w) : "memory"); }
__device__ __forceinline__ void stg_rlx2(void* p, uint32_t x, uint32_t y) { asm volatile("st.relaxed.gpu.global.v2.u32 [%0],{%1,%2};" ::"l"(p), "r"(x), "r"(y) : "memory"); }
__device__ __forceinline__ void red4(void* p, float a, float b, float c, float d) { asm volatile("red.relaxed.gpu.global.add.v4.f32 [%0],{%1,%2,%3,%4};" ::"l"(p), "f"(a), "f"(b), "f"(c), "f"(d) : "memory"); }
__device__ __forceinline__ unsigned ld_acq(const unsigned* p) { unsigned v; asm volatile("ld.acquire.gpu.global.u32 %0,[%1];" : "=r"(v) : "l"(p) : "memory"); return v; }
__device__ __forceinline__ void red_rel(unsigned* p) { asm volatile("red.release.gpu.global.add.u32 [%0],1;" ::"l"(p) : "memory"); }
__device__ __forceinline__ void red_rlx(unsigned* p) { asm volatile("red.relaxed.gpu.global.add.u32 [%0],1;" ::"l"(p) : "memory"); }
__device__ __forceinline__ void wait_cnt(const unsigned* p, unsigned n) { int it = 0; while (ld_acq(p) < n) { if (++it > SPIN_LIMIT) __trap(); } }
__device__ __forceinline__ uint32_t clk() { uint32_t c; asm volatile("mov.u32 %0,%%clock;" : "=r"(c)); return c; }
__device__ __forceinline__ uint32_t gtime() { uint32_t c; asm volatile("mov.u32 %0,%%globaltimer_lo;" : "=r"(c)); return c; }
__device__ __forceinline__ void wait_until(uint32_t t0, uint32_t d) { while (clk() - t0 < d) {} }
__device__ __forceinline__ float ex2(float x) { float r; asm("ex2.approx.ftz.f32 %0,%1;" : "=f"(r) : "f"(x)); return r; }
__device__ __forceinline__ float silu(float x) { return x * __frcp_rn(1.f + __expf(-x)); }
__device__ __forceinline__ float rbf(float x) { return __bfloat162float(__float2bfloat16_rn(x)); }

__device__ __forceinline__ void wgmma_ss_n128(float* d, uint64_t a, uint64_t b, int sd) {
  asm volatile("{.reg .pred p; setp.ne.b32 p, %66, 0;\n"
    "wgmma.mma_async.sync.aligned.m64n128k16.f32.bf16.bf16 {%0,%1,%2,%3,%4,%5,%6,%7,%8,%9,%10,%11,%12,%13,%14,%15,%16,%17,%18,%19,%20,%21,%22,%23,%24,%25,%26,%27,%28,%29,%30,%31,%32,%33,%34,%35,%36,%37,%38,%39,%40,%41,%42,%43,%44,%45,%46,%47,%48,%49,%50,%51,%52,%53,%54,%55,%56,%57,%58,%59,%60,%61,%62,%63}, %64, %65, p, 1, 1, 0, 1;}\n"
    : "+f"(d[0]),"+f"(d[1]),"+f"(d[2]),"+f"(d[3]),"+f"(d[4]),"+f"(d[5]),"+f"(d[6]),"+f"(d[7]),
      "+f"(d[8]),"+f"(d[9]),"+f"(d[10]),"+f"(d[11]),"+f"(d[12]),"+f"(d[13]),"+f"(d[14]),"+f"(d[15]),
      "+f"(d[16]),"+f"(d[17]),"+f"(d[18]),"+f"(d[19]),"+f"(d[20]),"+f"(d[21]),"+f"(d[22]),"+f"(d[23]),
      "+f"(d[24]),"+f"(d[25]),"+f"(d[26]),"+f"(d[27]),"+f"(d[28]),"+f"(d[29]),"+f"(d[30]),"+f"(d[31]),
      "+f"(d[32]),"+f"(d[33]),"+f"(d[34]),"+f"(d[35]),"+f"(d[36]),"+f"(d[37]),"+f"(d[38]),"+f"(d[39]),
      "+f"(d[40]),"+f"(d[41]),"+f"(d[42]),"+f"(d[43]),"+f"(d[44]),"+f"(d[45]),"+f"(d[46]),"+f"(d[47]),
      "+f"(d[48]),"+f"(d[49]),"+f"(d[50]),"+f"(d[51]),"+f"(d[52]),"+f"(d[53]),"+f"(d[54]),"+f"(d[55]),
      "+f"(d[56]),"+f"(d[57]),"+f"(d[58]),"+f"(d[59]),"+f"(d[60]),"+f"(d[61]),"+f"(d[62]),"+f"(d[63])
    : "l"(a), "l"(b), "r"(sd));
}
__device__ __forceinline__ void wgmma_ss_n192(float* d, uint64_t a, uint64_t b, int sd) {
  asm volatile("{.reg .pred p; setp.ne.b32 p, %98, 0;\n"
    "wgmma.mma_async.sync.aligned.m64n192k16.f32.bf16.bf16 {%0,%1,%2,%3,%4,%5,%6,%7,%8,%9,%10,%11,%12,%13,%14,%15,%16,%17,%18,%19,%20,%21,%22,%23,%24,%25,%26,%27,%28,%29,%30,%31,%32,%33,%34,%35,%36,%37,%38,%39,%40,%41,%42,%43,%44,%45,%46,%47,%48,%49,%50,%51,%52,%53,%54,%55,%56,%57,%58,%59,%60,%61,%62,%63,%64,%65,%66,%67,%68,%69,%70,%71,%72,%73,%74,%75,%76,%77,%78,%79,%80,%81,%82,%83,%84,%85,%86,%87,%88,%89,%90,%91,%92,%93,%94,%95}, %96, %97, p, 1, 1, 0, 1;}\n"
    : "+f"(d[0]),"+f"(d[1]),"+f"(d[2]),"+f"(d[3]),"+f"(d[4]),"+f"(d[5]),"+f"(d[6]),"+f"(d[7]),
      "+f"(d[8]),"+f"(d[9]),"+f"(d[10]),"+f"(d[11]),"+f"(d[12]),"+f"(d[13]),"+f"(d[14]),"+f"(d[15]),
      "+f"(d[16]),"+f"(d[17]),"+f"(d[18]),"+f"(d[19]),"+f"(d[20]),"+f"(d[21]),"+f"(d[22]),"+f"(d[23]),
      "+f"(d[24]),"+f"(d[25]),"+f"(d[26]),"+f"(d[27]),"+f"(d[28]),"+f"(d[29]),"+f"(d[30]),"+f"(d[31]),
      "+f"(d[32]),"+f"(d[33]),"+f"(d[34]),"+f"(d[35]),"+f"(d[36]),"+f"(d[37]),"+f"(d[38]),"+f"(d[39]),
      "+f"(d[40]),"+f"(d[41]),"+f"(d[42]),"+f"(d[43]),"+f"(d[44]),"+f"(d[45]),"+f"(d[46]),"+f"(d[47]),
      "+f"(d[48]),"+f"(d[49]),"+f"(d[50]),"+f"(d[51]),"+f"(d[52]),"+f"(d[53]),"+f"(d[54]),"+f"(d[55]),
      "+f"(d[56]),"+f"(d[57]),"+f"(d[58]),"+f"(d[59]),"+f"(d[60]),"+f"(d[61]),"+f"(d[62]),"+f"(d[63]),
      "+f"(d[64]),"+f"(d[65]),"+f"(d[66]),"+f"(d[67]),"+f"(d[68]),"+f"(d[69]),"+f"(d[70]),"+f"(d[71]),
      "+f"(d[72]),"+f"(d[73]),"+f"(d[74]),"+f"(d[75]),"+f"(d[76]),"+f"(d[77]),"+f"(d[78]),"+f"(d[79]),
      "+f"(d[80]),"+f"(d[81]),"+f"(d[82]),"+f"(d[83]),"+f"(d[84]),"+f"(d[85]),"+f"(d[86]),"+f"(d[87]),
      "+f"(d[88]),"+f"(d[89]),"+f"(d[90]),"+f"(d[91]),"+f"(d[92]),"+f"(d[93]),"+f"(d[94]),"+f"(d[95])
    : "l"(a), "l"(b), "r"(sd));
}
__device__ __forceinline__ void wgmma_ss_n256(float* d, uint64_t a, uint64_t b, int sd) {
  asm volatile("{.reg .pred p; setp.ne.b32 p, %130, 0;\n"
    "wgmma.mma_async.sync.aligned.m64n256k16.f32.bf16.bf16 {%0,%1,%2,%3,%4,%5,%6,%7,%8,%9,%10,%11,%12,%13,%14,%15,%16,%17,%18,%19,%20,%21,%22,%23,%24,%25,%26,%27,%28,%29,%30,%31,%32,%33,%34,%35,%36,%37,%38,%39,%40,%41,%42,%43,%44,%45,%46,%47,%48,%49,%50,%51,%52,%53,%54,%55,%56,%57,%58,%59,%60,%61,%62,%63,%64,%65,%66,%67,%68,%69,%70,%71,%72,%73,%74,%75,%76,%77,%78,%79,%80,%81,%82,%83,%84,%85,%86,%87,%88,%89,%90,%91,%92,%93,%94,%95,%96,%97,%98,%99,%100,%101,%102,%103,%104,%105,%106,%107,%108,%109,%110,%111,%112,%113,%114,%115,%116,%117,%118,%119,%120,%121,%122,%123,%124,%125,%126,%127}, %128, %129, p, 1, 1, 0, 1;}\n"
    : "+f"(d[0]),"+f"(d[1]),"+f"(d[2]),"+f"(d[3]),"+f"(d[4]),"+f"(d[5]),"+f"(d[6]),"+f"(d[7]),
      "+f"(d[8]),"+f"(d[9]),"+f"(d[10]),"+f"(d[11]),"+f"(d[12]),"+f"(d[13]),"+f"(d[14]),"+f"(d[15]),
      "+f"(d[16]),"+f"(d[17]),"+f"(d[18]),"+f"(d[19]),"+f"(d[20]),"+f"(d[21]),"+f"(d[22]),"+f"(d[23]),
      "+f"(d[24]),"+f"(d[25]),"+f"(d[26]),"+f"(d[27]),"+f"(d[28]),"+f"(d[29]),"+f"(d[30]),"+f"(d[31]),
      "+f"(d[32]),"+f"(d[33]),"+f"(d[34]),"+f"(d[35]),"+f"(d[36]),"+f"(d[37]),"+f"(d[38]),"+f"(d[39]),
      "+f"(d[40]),"+f"(d[41]),"+f"(d[42]),"+f"(d[43]),"+f"(d[44]),"+f"(d[45]),"+f"(d[46]),"+f"(d[47]),
      "+f"(d[48]),"+f"(d[49]),"+f"(d[50]),"+f"(d[51]),"+f"(d[52]),"+f"(d[53]),"+f"(d[54]),"+f"(d[55]),
      "+f"(d[56]),"+f"(d[57]),"+f"(d[58]),"+f"(d[59]),"+f"(d[60]),"+f"(d[61]),"+f"(d[62]),"+f"(d[63]),
      "+f"(d[64]),"+f"(d[65]),"+f"(d[66]),"+f"(d[67]),"+f"(d[68]),"+f"(d[69]),"+f"(d[70]),"+f"(d[71]),
      "+f"(d[72]),"+f"(d[73]),"+f"(d[74]),"+f"(d[75]),"+f"(d[76]),"+f"(d[77]),"+f"(d[78]),"+f"(d[79]),
      "+f"(d[80]),"+f"(d[81]),"+f"(d[82]),"+f"(d[83]),"+f"(d[84]),"+f"(d[85]),"+f"(d[86]),"+f"(d[87]),
      "+f"(d[88]),"+f"(d[89]),"+f"(d[90]),"+f"(d[91]),"+f"(d[92]),"+f"(d[93]),"+f"(d[94]),"+f"(d[95]),
      "+f"(d[96]),"+f"(d[97]),"+f"(d[98]),"+f"(d[99]),"+f"(d[100]),"+f"(d[101]),"+f"(d[102]),"+f"(d[103]),
      "+f"(d[104]),"+f"(d[105]),"+f"(d[106]),"+f"(d[107]),"+f"(d[108]),"+f"(d[109]),"+f"(d[110]),"+f"(d[111]),
      "+f"(d[112]),"+f"(d[113]),"+f"(d[114]),"+f"(d[115]),"+f"(d[116]),"+f"(d[117]),"+f"(d[118]),"+f"(d[119]),
      "+f"(d[120]),"+f"(d[121]),"+f"(d[122]),"+f"(d[123]),"+f"(d[124]),"+f"(d[125]),"+f"(d[126]),"+f"(d[127])
    : "l"(a), "l"(b), "r"(sd));
}
__device__ __forceinline__ void wgmma_rs_n32(float* d, const uint32_t* a, uint64_t b, int sd) {
  asm volatile("{.reg .pred p; setp.ne.b32 p, %21, 0;\n"
    "wgmma.mma_async.sync.aligned.m64n32k16.f32.bf16.bf16 {%0,%1,%2,%3,%4,%5,%6,%7,%8,%9,%10,%11,%12,%13,%14,%15}, {%16,%17,%18,%19}, %20, p, 1, 1, 0;}\n"
    : "+f"(d[0]),"+f"(d[1]),"+f"(d[2]),"+f"(d[3]),"+f"(d[4]),"+f"(d[5]),"+f"(d[6]),"+f"(d[7]),
      "+f"(d[8]),"+f"(d[9]),"+f"(d[10]),"+f"(d[11]),"+f"(d[12]),"+f"(d[13]),"+f"(d[14]),"+f"(d[15])
    : "r"(a[0]), "r"(a[1]), "r"(a[2]), "r"(a[3]), "l"(b), "r"(sd));
}
__device__ __forceinline__ void wgmma_ssT_n32(float* d, uint64_t a, uint64_t b, int sd) {
  asm volatile("{.reg .pred p; setp.ne.b32 p, %18, 0;\n"
    "wgmma.mma_async.sync.aligned.m64n32k16.f32.bf16.bf16 {%0,%1,%2,%3,%4,%5,%6,%7,%8,%9,%10,%11,%12,%13,%14,%15}, %16, %17, p, 1, 1, 1, 0;}\n"
    : "+f"(d[0]),"+f"(d[1]),"+f"(d[2]),"+f"(d[3]),"+f"(d[4]),"+f"(d[5]),"+f"(d[6]),"+f"(d[7]),
      "+f"(d[8]),"+f"(d[9]),"+f"(d[10]),"+f"(d[11]),"+f"(d[12]),"+f"(d[13]),"+f"(d[14]),"+f"(d[15])
    : "l"(a), "l"(b), "r"(sd));
}

__device__ __forceinline__ void wgmma_rs_n32_z(float* d, const uint32_t* a, uint64_t b) {
  asm volatile("{.reg .pred p; setp.ne.b32 p, 0, 0;\n"
    "wgmma.mma_async.sync.aligned.m64n32k16.f32.bf16.bf16 {%0,%1,%2,%3,%4,%5,%6,%7,%8,%9,%10,%11,%12,%13,%14,%15}, {%16,%17,%18,%19}, %20, p, 1, 1, 0;}\n"
    : "=f"(d[0]),"=f"(d[1]),"=f"(d[2]),"=f"(d[3]),"=f"(d[4]),"=f"(d[5]),"=f"(d[6]),"=f"(d[7]),
      "=f"(d[8]),"=f"(d[9]),"=f"(d[10]),"=f"(d[11]),"=f"(d[12]),"=f"(d[13]),"=f"(d[14]),"=f"(d[15])
    : "r"(a[0]), "r"(a[1]), "r"(a[2]), "r"(a[3]), "l"(b));
}

namespace rec {
constexpr int NVR = P_NVR;
constexpr int NVS = 16 - NVR;
constexpr int NVP = P_NVP;
constexpr int NWP = P_NWP;
constexpr uint32_t WO = 0;
constexpr uint32_t XB = 65536;
constexpr uint32_t PK = XB + 32768;
constexpr uint32_t VN = PK + 24576;
constexpr uint32_t VX0 = VN + 4096;
constexpr uint32_t WVS = 131072;
constexpr uint32_t MEM = WVS + 2 * NVS * 2048;
constexpr uint32_t ARO = MEM + 10240;
constexpr uint32_t OB = ARO + 5120;
constexpr uint32_t QT = OB + 2048;
constexpr uint32_t KT = QT + 2048;
constexpr uint32_t RQ = KT + 6144;
constexpr uint32_t RK = RQ + 2048;
constexpr uint32_t SC = RK + 2048;
constexpr uint32_t OT = OB;
constexpr uint32_t TF = SC + 2048;
constexpr uint32_t PRE = MEM + 2 * NVR * 2048;
constexpr uint32_t TA = TF + 8192;
constexpr uint32_t RX = TA + 6144;
constexpr uint32_t VX1 = RX + 2048;
constexpr uint32_t BARS = VX1 + 4096;
constexpr uint32_t PACE = BARS + 18 * 8;
constexpr uint32_t SMEM = BARS + 512;
static_assert(PRE + 14336 <= BARS, "staging");
constexpr int NW1 = P_NW1;
static_assert(SMEM <= 232448, "smem");
constexpr int B_E = 2, B_SC = 3, B_S = 4, B_O = 5, B_F = 6, B_W = 7, B_C = 9, B_K = 10, B_H = 15, B_Q = 1, B_S2 = 6, B_T2 = 9, B_P = 13, B_T = 14, B_R = 11, B_X = 12, B_V = 8;
constexpr int XC = 16384, X_RING = 131072, X_SC = 65536, X_TOK = 4096;
#define X_VX(i) (((i) >> 1) * 2048 + ((i) & 1) * 512)
#define X_VM(i) (X_VX(i) + 1024)
#define V_RING(n) (((n) & 1) * X_RING + ((n) & 2) * 2048)
#define V_TAG(n) ((~(n) >> 2) & 1)
}
struct RecMaps { CUtensorMap wq, wk, wv, wo, ari; int zero[40]; };

#define F_(x) __uint_as_float(x)
#define U_(x) __float_as_uint(x)
__device__ __forceinline__ void ar_fetch(uint32_t dst, const CUtensorMap* m, int slot, int half, uint32_t mb) {
  asm volatile("{.reg .pred p; elect.sync _|p, 0xffffffff; @p mbarrier.arrive.expect_tx.shared.b64 _,[%4],10240;\n"
               "@p cp.async.bulk.tensor.2d.shared::cluster.global.mbarrier::complete_tx::bytes [%0],[%1,{%2,%3}],[%4];\n"
               "@p cp.async.bulk.tensor.2d.shared::cluster.global.mbarrier::complete_tx::bytes [%0+5120],[%1,{%2,%5}],[%4];}"
               ::"r"(dst), "l"(m), "r"(slot * 64), "r"(half * 80), "r"(mb), "r"(half * 80 + 40) : "memory");
}
__device__ __forceinline__ void ar_fetch1(uint32_t dst, const CUtensorMap* m, int slot, int quarter, uint32_t mb) {
  asm volatile("{.reg .pred p; elect.sync _|p, 0xffffffff; @p mbarrier.arrive.expect_tx.shared.b64 _,[%4],5120;\n"
               "@p cp.async.bulk.tensor.2d.shared::cluster.global.mbarrier::complete_tx::bytes [%0],[%1,{%2,%3}],[%4];}"
               ::"r"(dst), "l"(m), "r"(slot * 64), "r"(quarter * 40), "r"(mb) : "memory");
}
__device__ __forceinline__ uint4 exch_b128(void* p, uint32_t x, uint32_t y, uint32_t z, uint32_t w) {
  uint4 v;
  asm volatile("{.reg .b128 s, t; .reg .b64 a,b; mov.b64 a,{%5,%6}; mov.b64 b,{%7,%8}; mov.b128 s,{a,b}; atom.relaxed.gpu.global.exch.b128 t,[%4],s;"
               " mov.b128 {a,b},t; mov.b64 {%0,%1},a; mov.b64 {%2,%3},b;}" : "=r"(v.x), "=r"(v.y), "=r"(v.z), "=r"(v.w) : "l"(p), "r"(x), "r"(y), "r"(z), "r"(w) : "memory");
  return v;
}
#define CONSUME(v) do { if ((v) == 0x7fc12345u) sts1(sb + rec::BARS + 96, 0); } while (0)
__device__ __forceinline__ uint32_t tagf(float v, uint32_t tag) { return (__float_as_uint(v) & ~1u) | tag; }
__device__ __forceinline__ uint2 ldg_b64(const void* p) { uint2 v; asm volatile("{.reg .b64 t; ld.relaxed.gpu.global.b64 t,[%2]; mov.b64 {%0,%1},t;}" : "=r"(v.x), "=r"(v.y) : "l"(p) : "memory"); return v; }
__device__ __forceinline__ void stg_b64(void* p, uint32_t x, uint32_t y) { asm volatile("{.reg .b64 t; mov.b64 t,{%1,%2}; st.relaxed.gpu.global.b64 [%0],t;}" ::"l"(p), "r"(x), "r"(y) : "memory"); }
__device__ __forceinline__ uint32_t tagbad(uint32_t x, uint32_t y, uint32_t tag) { uint32_t r; asm("lop3.b32 %0,%1,%2,%3,0x7e;" : "=r"(r) : "r"(x), "r"(y), "r"(tag)); return r; }

__device__ __forceinline__ bool anybad(uint32_t a, uint32_t b, uint32_t c, uint32_t d, uint32_t e, uint32_t f, uint32_t g, uint32_t h, uint32_t tag) {
  uint32_t r;
  asm volatile("{.reg .b32 t,u,v,w; .reg .pred p; lop3.b32 t,%1,%2,%9,0x7e; lop3.b32 u,%3,%4,%9,0x7e; lop3.b32 v,%5,%6,%9,0x7e; lop3.b32 w,%7,%8,%9,0x7e;"
               " lop3.b32 t,t,u,v,0xfe; lop3.b32 t,t,w,1,0xa8; setp.ne.u32 p,t,0; vote.sync.any.pred p,p,0xffffffff; selp.u32 %0,1,0,p;}"
               : "=r"(r) : "r"(a), "r"(b), "r"(c), "r"(d), "r"(e), "r"(f), "r"(g), "r"(h), "r"(tag));
  return r;
}
__device__ __forceinline__ bool anybad(uint32_t a, uint32_t b, uint32_t c, uint32_t d, uint32_t tag) {
  uint32_t r;
  asm volatile("{.reg .b32 t,u; .reg .pred p; lop3.b32 t,%1,%2,%5,0x7e; lop3.b32 u,%3,%4,%5,0x7e;"
               " lop3.b32 t,t,u,1,0xa8; setp.ne.u32 p,t,0; vote.sync.any.pred p,p,0xffffffff; selp.u32 %0,1,0,p;}"
               : "=r"(r) : "r"(a), "r"(b), "r"(c), "r"(d), "r"(tag));
  return r;
}
#define BAD8(r) anybad(r[0].x, r[0].z, r[1].x, r[1].z, r[2].x, r[2].z, r[3].x, r[3].z, tag)
#define BADS(r) anybad(r[0].x, r[0].y, r[1].x, r[1].y, r[2].x, r[2].y, r[3].x, r[3].y, tag)
constexpr float SCS = 0.08838834764831845f * 1.4426950408889634f / 16.f;
__device__ __forceinline__ uint32_t pkh(float lo, float hi, uint32_t tag) {
  uint32_t r;
  asm("{.reg .b32 t; cvt.rn.satfinite.f16x2.f32 t,%1,%2; lop3.b32 %0,t,0xfffffffe,%3,0xea;}" : "=r"(r) : "f"(hi), "f"(lo), "r"(tag));
  return r;
}
__device__ __forceinline__ uint32_t addh(uint32_t a, uint32_t b) { uint32_t r; asm("add.rn.f16x2 %0,%1,%2;" : "=r"(r) : "r"(a), "r"(b)); return r; }
__device__ __forceinline__ float hlo(uint32_t v) { float r; asm("{.reg .b16 a,b; mov.b32 {a,b},%1; cvt.f32.f16 %0,a;}" : "=f"(r) : "r"(v)); return r; }
__device__ __forceinline__ float hhi(uint32_t v) { float r; asm("{.reg .b16 a,b; mov.b32 {a,b},%1; cvt.f32.f16 %0,b;}" : "=f"(r) : "r"(v)); return r; }
__device__ __forceinline__ uint32_t ordh(uint32_t v) {
  uint32_t r;
  asm("{.reg .b32 m; prmt.b32 m,%1,0,0xbb99; lop3.b32 %0,%1,m,0x7fff7fff,0x78;}" : "=r"(r) : "r"(v));
  return r;
}
template <bool MASK>
__device__ __forceinline__ float4 softmax2(const uint2 (&r)[4], uint32_t mx, uint32_t my) {
  uint32_t x = addh(addh(r[0].x, r[1].x), addh(r[2].x, r[3].x)), y = addh(addh(r[0].y, r[1].y), addh(r[2].y, r[3].y)), k;
  if (MASK) x = addh(x, mx);
  y = addh(y, my);
  asm("max.f16x2 %0,%1,%2;" : "=r"(k) : "r"(x), "r"(y));
  k = ordh(k);
  const int k0 = __reduce_max_sync(~0u, (int)(k << 16)), k1 = __reduce_max_sync(~0u, (int)k);
  k = ordh(__byte_perm(k0, k1, 0x7632));
  const float m0 = hlo(k) * -16.f, m1 = hhi(k) * -16.f;
  return make_float4(ex2(fmaf(hlo(x), 16.f, m0)), ex2(fmaf(hhi(x), 16.f, m1)), ex2(fmaf(hlo(y), 16.f, m0)), ex2(fmaf(hhi(y), 16.f, m1)));
}
__device__ __forceinline__ char* mkp(uint32_t lo, uint32_t hi) { uint64_t r; asm("mov.b64 %0,{%1,%2};" : "=l"(r) : "r"(lo), "r"(hi)); return (char*)r; }
#define LO(p) ((uint32_t)(uint64_t)(p))
#define HI(p) ((uint32_t)((uint64_t)(p) >> 32))
__device__ __forceinline__ void cp16(uint32_t dst, const void* src) { asm volatile("cp.async.cg.shared.global [%0],[%1],16;" ::"r"(dst), "l"(src) : "memory"); }
__device__ __forceinline__ uint32_t xor3(uint32_t a, uint32_t b, uint32_t c) { uint32_t r; asm volatile("lop3.b32 %0,%1,%2,%3,0x96;" : "=r"(r) : "r"(a), "r"(b), "r"(c)); return r; }
__device__ __forceinline__ uint32_t mulbf(uint32_t a, uint32_t b) { uint32_t r; asm("mul.rn.bf16x2 %0,%1,%2;" : "=r"(r) : "r"(a), "r"(b)); return r; }
__device__ __forceinline__ uint32_t fmabf(uint32_t a, uint32_t b, uint32_t c) { uint32_t r; asm("fma.rn.bf16x2 %0,%1,%2,%3;" : "=r"(r) : "r"(a), "r"(b), "r"(c)); return r; }
__device__ __forceinline__ uint32_t addbf(uint32_t a, uint32_t b) { uint32_t r; asm("add.rn.bf16x2 %0,%1,%2;" : "=r"(r) : "r"(a), "r"(b)); return r; }
__device__ __forceinline__ void pv_mem(const uint32_t (&p)[4], uint32_t pm, const uint4 (&v)[4], const uint4 (&vn)[2], uint32_t (&O)[4]) {
  float o[4][4] = {{0, 0, 0, 0}, {0, 0, 0, 0}, {0, 0, 0, 0}, {0, 0, 0, 0}};
  mma16(o[0], v[0].x, v[0].y, v[0].z, v[0].w, p[0], p[1]);
  mma16(o[1], v[2].x, v[2].y, v[2].z, v[2].w, p[0], p[1]);
  mma16(o[2], v[1].x, v[1].y, v[1].z, v[1].w, p[2], p[3]);
  mma16(o[3], v[3].x, v[3].y, v[3].z, v[3].w, p[2], p[3]);
  mma16(o[0], vn[0].x, vn[0].y, vn[0].z, vn[0].w, pm, pm);
  mma16(o[1], vn[1].x, vn[1].y, vn[1].z, vn[1].w, pm, pm);
  O[0] = pk(o[0][0] + o[2][0], o[0][1] + o[2][1]); O[1] = pk(o[0][2] + o[2][2], o[0][3] + o[2][3]);
  O[2] = pk(o[1][0] + o[3][0], o[1][1] + o[3][1]); O[3] = pk(o[1][2] + o[3][2], o[1][3] + o[3][3]);
}
__device__ __forceinline__ void pv_tok(const uint32_t (&p)[4], uint32_t pm, const uint4 (&v)[4], const uint32_t (&vm)[4], uint32_t (&O)[4]) {
  float o[2][4] = {{0, 0, 0, 0}, {0, 0, 0, 0}}, sum[4] = {0, 0, 0, 0};
  const uint32_t one = 0x3f803f80u;
  mma16(sum, one, one, one, one, p[0], p[1]);
  mma16(o[0], v[0].x, v[0].y, v[0].z, v[0].w, p[0], p[1]);
  mma16(o[1], v[2].x, v[2].y, v[2].z, v[2].w, p[0], p[1]);
  mma16(sum, one, one, one, one, p[2], p[3]);
  mma16(o[0], v[1].x, v[1].y, v[1].z, v[1].w, p[2], p[3]);
  mma16(o[1], v[3].x, v[3].y, v[3].z, v[3].w, p[2], p[3]);
  mma8(sum, one, one, pm);
  mma8(o[0], vm[0], vm[1], pm);
  mma8(o[1], vm[2], vm[3], pm);
  float i0, i1;
  asm("rcp.approx.ftz.f32 %0,%1;" : "=f"(i0) : "f"(sum[0]));
  asm("rcp.approx.ftz.f32 %0,%1;" : "=f"(i1) : "f"(sum[1]));
  O[0] = pk(o[0][0] * i0, o[0][1] * i1); O[1] = pk(o[0][2] * i0, o[0][3] * i1);
  O[2] = pk(o[1][0] * i0, o[1][1] * i1); O[3] = pk(o[1][2] * i0, o[1][3] * i1);
}
__device__ __forceinline__ uint32_t sum4bf(uint32_t a, uint32_t b, uint32_t c, uint32_t d) { return addbf(addbf(a, b), addbf(c, d)); }
template <int OFF>
__device__ __forceinline__ void sta1(uint32_t a, uint32_t v, uint32_t mb) {
  asm volatile("st.async.shared::cluster.mbarrier::complete_tx::bytes.b32 [%0+%3],%1,[%2];" ::"r"(a), "r"(v), "r"(mb), "n"(OFF) : "memory");
}

__device__ __forceinline__ void wait_time(uint32_t t) { while ((int)(gtime() - t) < 0) __nanosleep(64); }
__device__ __noinline__ void rec_prefetch(const char* wmod, const char* w1, const char* x, const char* wo) {
  const int hb = blockIdx.x - 128;
  const uint32_t t0 = gtime();
  uint32_t t = t0 + PF0;
#pragma unroll 1
  for (int job = 0; job < (PFT ? 5 : 3); job++) {
    const char* p = job == 0 ? x + (6 + hb) * 65536 : job == 1 ? wmod + hb * 12288 + 4096 : job == 2 ? w1 + hb * 7168 : job == 3 ? x + hb * 8192 : wo + (1020 + hb) * 8192;
    const int n = job == 0 ? 120 - (hb & 2) * 4 : job == 3 ? 128 : 256, d = job == 0 ? 8192 : job == 1 ? 49152 : job == 2 ? 28672 : job == 3 ? 32768 : -32768;
    if (job == 3) t = t0 + PFT;
    PT(8 + job);
#pragma unroll 1
    for (int i = 0; i < n; i++) {
      wait_time(t);
      asm volatile("cp.async.bulk.prefetch.L2.global [%0], %1;" ::"l"(p), "r"(job == 2 ? 7168 : 8192) : "memory");
      p += !job && (i & 7) == 7 ? 204800 : d;
      t += job < 3 ? PFD : PFS;
      if (job && (i & 31) == 31 && ldg_rlx1(&g_fin)) return;
    }
  }
  PT(13);
}
__device__ __noinline__ void rec_helper(uint32_t sb, const bf16* cvec, const bf16* wmod, const char* w1, const bf16* b1, uint32_t t0) {
  const int tid = threadIdx.x, hb = blockIdx.x - 128;
  PT(1);
  for (int i = tid; i < 1024; i += 256) sts1(sb + i * 8, U_(rbf(silu(__bfloat162float(cvec[i])))));
  for (int i = tid; i < 2048; i += 256) g_stat[hb * 2048 + i] = make_uint4(~0u, ~0u, ~0u, ~0u);
  for (int i = tid; i < 512; i += 256) g_cnt[hb * 512 + i] = 0;
#pragma unroll 1
  for (int job = 0; job < 2; job++) {
    wait_time(t0 + PF0 + (job ? 600 : 350) * PFD);
    BAR_SYNC(rec::B_F, 256);
    PT(2 + job * 5);
    const int n8 = job ? 112 : 128, rg = tid >= n8, cg = tid - rg * n8, pitch = job ? 448 : 768;
    const uint4* p = (const uint4*)(job ? w1 + hb * 1792 : (const char*)(wmod + 2048 + hb * 1024)) + rg * pitch + min(cg, n8 - 1);
    float a1[8] = {0, 0, 0, 0, 0, 0, 0, 0}, a2[8] = {0, 0, 0, 0, 0, 0, 0, 0};
#pragma unroll 1
    for (int r0 = rg; r0 < 1024; r0 += 32) {
      uint4 v[16];
#pragma unroll
      for (int i = 0; i < 16; i++) { v[i] = ldg_rlx4(p); p += 2 * pitch; }
#pragma unroll
      for (int i = 0; i < 16; i++) {
        const float2 f = lds2f(sb + (r0 + 2 * i) * 8);
        const float w[8] = {blo(v[i].x), bhi(v[i].x), blo(v[i].y), bhi(v[i].y), blo(v[i].z), bhi(v[i].z), blo(v[i].w), bhi(v[i].w)};
#pragma unroll
        for (int e = 0; e < 8; e++) { a1[e] += f.x * w[e]; a2[e] += f.y * w[e]; }
      }
    }
    const uint32_t rd = sb + 8192;
    if (cg < n8) {
#pragma unroll
      for (int e = 0; e < 8; e++) sts2(rd + rg * 8192 + (cg * 8 + e) * 8, U_(a1[e]), U_(a2[e]));
    }
    BAR_SYNC(rec::B_F, 256);
    if (job == 0) {
      for (int i = tid; i < 1024; i += 256) g_mod[2048 + hb * 1024 + i] = rbf(F_(lds1(rd + i * 8)) + F_(lds1(rd + 8192 + i * 8)));
      BAR_SYNC(rec::B_F, 256);
      PT(6);
      if (tid == 0) { red_rel(&g_mcnt); wait_cnt(&g_mcnt, 4); }
      BAR_SYNC(rec::B_F, 256);
      for (int i = tid; i < 1024; i += 256) sts2(sb + i * 8, U_(rbf(1.f + __ldcg(g_mod + 4096 + i))), U_(__ldcg(g_mod + 3072 + i)));
    } else {
      for (int i = tid; i < 448; i += 256) {
        const int gn = hb * 896 + i * 2;
        const uint32_t bb = *(const uint32_t*)(b1 + gn);
        const float4 u = lds4f(rd + i * 16), w = lds4f(rd + 8192 + i * 16);
        ((uint2*)g_cc)[(gn >> 4) * 8 + ((gn >> 1) & 3) * 2 + ((gn >> 3) & 1)] = make_uint2(pk(u.x + w.x, u.z + w.z), pk(0.5f * (u.y + w.y + blo(bb)), 0.5f * (u.w + w.w + bhi(bb))));
      }
      PT(4);
    }
  }
}

__global__ void __cluster_dims__(2, 1, 1) __launch_bounds__(512, 1)
k_rec(const __grid_constant__ RecMaps mp, const bf16* __restrict__ mem0, const bf16* __restrict__ x, const bf16* __restrict__ cvec,
      const bf16* __restrict__ wmod, const char* __restrict__ w1, const bf16* __restrict__ b1, const char* __restrict__ wo, char* xc, int dF, int dA, int dS, int dM, int dG, int dP, int dX, int dD, int dZ, int dZ2, int dV, int dX2) {
  using namespace rec;
  extern __shared__ __align__(1024) char smem[];
  const uint32_t sb = (uint32_t)__cvta_generic_to_shared(smem);
  if ((sb & 0x3FFFF) != 1024) __trap();
  PH(0); if (threadIdx.x == 0) PT(0);
  if (threadIdx.x == 0) {
    int b = blockIdx.x;
    if (b >= 8 && b < 128) {
      const int t = (b >> 1) - 4, u = t - 32;
      b = 2 * (t < 32 ? 4 + (t & 16) + (t & 7) * 2 + ((t >> 3) & 1) : 36 + (u / 14) * 14 + (u % 7) * 2 + ((u / 7) & 1)) + (b & 1);
    }
    sts1(sb + rec::PACE + 24, b);
    const int c = blockIdx.x >> 1, l = c < 36 ? (c - 4) & 7 : (c - 36) % 7, m = c < 4 ? c : c < 36 ? (c - 4) >> 3 : (c - 36) / 7;
    const int g = c < 4 ? 15 : (l >> 1) * 4 + (l & 1) + (c < 36 ? 0 : 2);
    unsigned sm;
    asm("mov.u32 %0,%%smid;" : "=r"(sm));
    if (c < 64) g_slot[sm & 255] = 1 + FMAP;
  }
#define ROLE_REFRESH { asm volatile("mov.u32 %0,%%tid.x;" : "=r"(tid)); wid = __shfl_sync(~0u, tid >> 5, 0); b = __shfl_sync(~0u, lds1(sb + PACE + 24), 0); }
#define ROLE_VARS int tid; asm volatile("mov.u32 %0,%%tid.x;" : "=r"(tid)); \
    int wid = __shfl_sync(~0u, tid >> 5, 0), b = __shfl_sync(~0u, lds1(sb + PACE + 24), 0);
#define wg (wid >> 2)
#define iw (wid & 3)
#define h (b >> 2)
#define j (b & 3)
#define a (b & 1)
#define bb ((b >> 1) & 1)
  const uint32_t wbar = sb + BARS + 48, obar = wbar + 8;
  if (threadIdx.x == 256) {
    for (int i = 0; i < 18; i++) if (i != 12) mbar_init(sb + BARS + i * 8, i == 3 || i == 8 || i == 9 || i == 10 ? 2 : 1);
    for (int i = 0; i < 3; i++) mbar_init(sb + PACE + i * 8, 1);
    asm volatile("fence.mbarrier_init.release.cluster;" ::: "memory");
    FENCE_ASYNC_SMEM();
    mbar_expect(sb + BARS, 2048);
    mbar_expect(sb + BARS + 16, 4096);
    mbar_expect(sb + BARS + 32, 4096);
    mbar_expect(sb + BARS + 40, 4096);
  }
  __syncthreads();
  asm volatile("barrier.cluster.arrive.relaxed.aligned;" ::: "memory");
#define lane ((int)(l16 >> 4))
#define l16 (L16 & 0x1f0)
#define is7 ((L16 & 112) == 112)
#define PIN(x) __shfl_xor_sync(~0u, (uint32_t)(x), 0)
#define REFRESH() L16 = __shfl_xor_sync(~0u, L16, 0)
#define lar ((L16 & 0x180) * 8 + (L16 & 0x70))
#define X_LOAD(n, w, u) \
        asm volatile("{.reg .pred p; elect.sync _|p, 0xffffffff; @p mbarrier.arrive.expect_tx.shared.b64 _,[%2],8192;\n" \
                     "@p cp.async.bulk.shared::cluster.global.mbarrier::complete_tx::bytes [%0],[%1],8192,[%2];}" ::"r"(sb + XB + (w) * 16384 + (u) * 8192), \
                     "l"(g_h + (n) * 4096 + a * 2048 + (w) * 1024 + (u) * 512), "r"(sb + BARS + 64 + (w) * 8) : "memory")
#define lpub ((L16 & 0x30) * 64 + ((L16 >> 3) & 0x38))
#define lrow ((L16 & 0x70) + (((L16 >> 3) ^ L16) & 0x70 & ~((L16 >> 3) & 0x40) ? L16 & 0x180 : 512))

  const int role = __shfl_sync(~0u, threadIdx.x >> 7, 0);
  if (role < 2) {
    asm volatile("setmaxnreg.inc.sync.aligned.u32 %0;" ::"n"(RF_));
    ROLE_VARS
    uint32_t L16 = __shfl_sync(~0u, sb + (tid & 31) * 16, tid & 31);
    uint32_t wQ[16][4], wK[16][4], wV[NVR][4];
    uint32_t m0[2][4];
    uint32_t frag = sb + ((lane & 7) + (lane >> 4) * 8) * 128 + (((iw * 2 + ((lane >> 3) & 1)) ^ (lane & 7)) << 4);
    {
      const bool spare = b >= 128;
      const uint32_t t0 = gtime();
      uint4 xr[16];
      int seg = spare ? b - 126 : wg;
      const int half = spare ? wg : a;
      auto x_fetch = [&]() {
        const uint4* px = (const uint4*)x + (seg * 32 + iw * 8 + (lane >> 2)) * 128 + half * 64 + (lane & 3);
#pragma unroll
        for (int i = 0; i < 16; i++) xr[i] = __ldg(px + i * 4);
      };
      if (!spare) {
        uint4 wm[8];
        const uint4* pw = (const uint4*)(wmod + (size_t)((b >> 5) * 256 + (tid >> 3)) * 6144 + (b & 31) * 64) + (tid & 7);
        const float cs = __bfloat162float(cvec[(b >> 5) * 256 + tid]);
#pragma unroll
        for (int i = 0; i < 8; i++) wm[i] = __ldcs(pw + (size_t)i * 32 * 768);
        unsigned short mr[16];
#pragma unroll
        for (int i = 0; i < 16; i++) mr[i] = __bfloat16_as_ushort(mem0[(i & 7) * 1024 + a * 512 + tid * 2 + (i >> 3)]);
        float* sc = (float*)(smem + PRE);
        sc[tid] = rbf(silu(cs));
        PT(1);
        BAR_SYNC(B_F, 256);
        float acc[8] = {0, 0, 0, 0, 0, 0, 0, 0};
#pragma unroll
        for (int i = 0; i < 8; i++) {
          const float f = sc[i * 32 + (tid >> 3)];
          acc[0] += f * blo(wm[i].x); acc[1] += f * bhi(wm[i].x); acc[2] += f * blo(wm[i].y); acc[3] += f * bhi(wm[i].y);
          acc[4] += f * blo(wm[i].z); acc[5] += f * bhi(wm[i].z); acc[6] += f * blo(wm[i].w); acc[7] += f * bhi(wm[i].w);
        }
#pragma unroll
        for (int i = 0; i < 8; i++) { acc[i] += __shfl_xor_sync(~0u, acc[i], 8); acc[i] += __shfl_xor_sync(~0u, acc[i], 16); }
        float* red = sc + 1024;
        if ((tid & 31) < 8) {
#pragma unroll
          for (int i = 0; i < 8; i++) red[(tid >> 5) * 64 + (tid & 7) * 8 + i] = acc[i];
        }
        BAR_SYNC(B_F, 256);
        PT(2);
        if (tid < 64) {
          float t = 0;
#pragma unroll
          for (int i = 0; i < 8; i++) t += red[i * 64 + tid];
          asm volatile("st.relaxed.gpu.global.u32 [%0],%1;" ::"l"((unsigned*)g_modp + (b >> 5) * 2048 + (b & 31) * 64 + tid), "r"(U_(t) | 1u) : "memory");
        }
#pragma unroll
        for (int i = 0; i < 8; i++) m0[i >> 2][i & 3] = mr[i * 2] | ((uint32_t)mr[i * 2 + 1] << 16);
      } else {
        asm volatile("griddepcontrol.launch_dependents;");
      }
      x_fetch();
      const uint32_t md = sb + PRE + 6144, rx = mapa(sb, a ^ !spare);
      asm volatile("barrier.cluster.wait.aligned;" ::: "memory");
      if (!spare) {
        mbar_wait(sb + BARS + 88, 0);
#pragma unroll
        for (int i = 0; i < 16; i++) ldsm4t(wQ[i], frag + WO + wg * 32768 + i * 2048);
      }
      PT(4);
#pragma unroll 1
      for (int it = 0;; it++) {
        if (tid == 0) mbar_expect(sb + BARS + 104, 512);
        float c[4][4] = {{0, 0, 0, 0}, {0, 0, 0, 0}, {0, 0, 0, 0}, {0, 0, 0, 0}};
#pragma unroll
        for (int i = 0; i < 16; i++) {
          mma16(c[(i & 1) * 2], xr[i].x, 0x3f803f80u, xr[i].y, 0x3f803f80u, xr[i].x, xr[i].y);
          mma16(c[(i & 1) * 2 + 1], xr[i].z, 0x3f803f80u, xr[i].w, 0x3f803f80u, xr[i].z, xr[i].w);
        }
#pragma unroll
        for (int e = 0; e < 4; e++) c[0][e] = (c[0][e] + c[1][e]) + (c[2][e] + c[3][e]);
        const int src = (lane & 28) + (lane >> 3);
        const float sq = __shfl_sync(~0u, (lane & 4) ? c[0][1] : c[0][0], src), sm = __shfl_sync(~0u, (lane & 4) ? c[0][3] : c[0][2], src);
        if ((lane & 3) < 2) sta1<0>(rx + PRE + 10240 + (wid ^ (spare * 4)) * 64 + (lane >> 2) * 8 + (lane & 1) * 4, U_((lane & 1) ? sm : sq), rx + BARS + 104);
        mbar_wait(sb + BARS + 104, it & 1);
        const float2 ot = lds2f(sb + PRE + 10240 + wid * 64 + (lane >> 2) * 8);
        const float mean = (sm + ot.y) * (1.f / 1024);
        const float rs = rsqrtf(fmaxf((sq + ot.x) * (1.f / 1024) - mean * mean, 0.f) + 1e-5f), nm = -mean * rs;
#define NRM(v) v = pk(fmaf(blo(v), rs, nm), fmaf(bhi(v), rs, nm))
#pragma unroll
        for (int i = 0; i < 16; i++) { NRM(xr[i].x); NRM(xr[i].y); NRM(xr[i].z); NRM(xr[i].w); }
        if (!it) {
          PT(3);
#pragma unroll 1
          for (int i = 0; i < 2; i++) {
            uint4 p[4];
            for (int n = 0;; n++) {
#pragma unroll
              for (int e = 0; e < 4; e++) p[e] = ldg_rlx4(g_modp + e * 512 + i * 256 + tid);
              uint32_t ok = 1;
#pragma unroll
              for (int e = 0; e < 4; e++) ok &= p[e].x & p[e].y & p[e].z & p[e].w;
              if (__all_sync(~0u, ok) || n > SPIN_LIMIT / 16) break;
              __nanosleep(100);
            }
#define MSUM(e) (i + rbf((F_(p[0].e) + F_(p[1].e)) + (F_(p[2].e) + F_(p[3].e))))
            sts2(md + i * 2048 + tid * 8, pk(MSUM(x), MSUM(y)), pk(MSUM(z), MSUM(w)));
          }
          BAR_SYNC(B_F, 256);
          PT(5);
        }
        const int e0 = (iw * 8 + (lane >> 2)) * 8 + ((lane & 3) ^ (lane >> 2));
        uint4* dst = g_h + seg * 4096 + half * 2048;
#pragma unroll
        for (int i = 0; i < 16; i++) {
          const uint32_t ma = md + half * 1024 + (lane & 3) * 16 + i * 64;
          const uint4 sv = lds4(ma), cv = lds4(ma + 2048);
          const uint4 w = make_uint4(fmabf(xr[i].x, cv.x, sv.x), fmabf(xr[i].y, cv.y, sv.y), fmabf(xr[i].z, cv.z, sv.z), fmabf(xr[i].w, cv.w, sv.w));
          const int e = (e0 ^ ((i & 1) * 4)) + (i >> 1) * 256;
          if (spare) dst[e] = w; else sts4(sb + WO + wg * 32768 + e * 16, w.x, w.y, w.z, w.w);
        }
        if (!spare) break;
        seg += 4;
        if (seg < 64) x_fetch();
        FENCE_ASYNC();
        BAR_SYNC(B_F, 256);
        if (tid == 0) red_rlx(g_hf + b - 128);
        if (seg >= 64) break;
      }
      if (spare) { rec_helper(sb, cvec, wmod, w1, b1, t0); return; }
      PH(1); PH(2); PT(6);
    }
    ROLE_REFRESH
    mbar_wait(wbar, 0);
    PT(7);
#pragma unroll
    for (int i = 0; i < 16; i++) ldsm4t(wK[i], frag + XB + wg * 32768 + i * 2048);
#pragma unroll
    for (int i = 0; i < NVR; i++) ldsm4t(wV[i], frag + MEM + (wg * NVR + i) * 2048);
    FENCE_ASYNC_SMEM();
    PH(3); PT(8);
    CLUSTER_SYNC();
    PT(9);
#pragma unroll
    for (int i = 0; i < 2; i++) {
      const int k = tid * 2 + i, m = (k >> 3) & 3, r = k & 7;
      sts4(sb + MEM + (k >> 5) * 640 + (r == m ? 512 : m * 128) + r * 16, m0[i][0], m0[i][1], m0[i][2], m0[i][3]);
    }
    if (lane < 8) {
      sts4(sb + ARO + wid * 640 + (lane < 4 ? lane * 144 : 512 + l16), 0x3f803f80, 0x3f803f80, 0x3f803f80, 0x3f803f80);
#pragma unroll
      for (int i = 0; i < 2; i++) sts4(sb + MEM + (wid * 2 + i) * 640 + (lane < 4 ? lane * 144 : 512 + l16), 0x42004200, 0x42004200, 0x42004200, 0x42004200);
    }
#define owner ((iw >> 1) == a)
#define vfin ((wid >> 1) == a)
#define oi (wid & 1)
    frag += wg * NVS * 2048;
    {
      const uint32_t rsb = mapa(sb, iw >> 1);
      const uint32_t pp = rsb + PK + (owner ? 0 : 12288) + (oi * 2048 + wg * 1024) + l16;
      const uint32_t mb = sb + MEM + wg * 5120;
      sts4(L16 + TF + wid * 512, mb + lrow, owner ? L16 + (lane >> 4) * (RK - RQ - 256) + RQ + oi * 1024 + wg * 256 : rsb + RQ + oi * 1024 + 512 + wg * 256 + (l16 >> 2),
           L16 + OB, frag);
      sts4(L16 + TF + 4096 + wid * 512, sb + WO + (wid >> 1) * 16384 + ((lane & 7) + (lane >> 4) * 8) * 128 + ((((wid & 1) * 4 + ((lane >> 3) & 1)) ^ (lane & 7)) << 4),
           sb + ARO + wid * 640 + lrow, pp, LO(xc) + h * 262144 + (bb * 2 + (iw >> 1)) * XC + X_VM(0) + oi * 2048 + a * 256 + (l16 >> 1));
    }
    uint32_t tp = L16 + TF + wid * 512;
    auto park_ptr = [&]() { return lds1(tp + 4096 + 8); };
    auto park = [&](const float* f, int m, int n, uint32_t d) {
      uint32_t w[8];
#pragma unroll
      for (int i = 0; i < 8; i++) w[i] = pk(f[2 * i], f[2 * i + 1]);
      if (owner) {
        sts4(d + m * 4096, w[0], w[1], w[2], w[3]); sts4(d + m * 4096 + 512, w[4], w[5], w[6], w[7]);
      } else {
        const uint32_t pb = mapa(sb, a ^ 1) + BARS + (m ? 24 + m * 8 : 16);
        sta4(d + m * 4096, w, pb); sta4(d + m * 4096 + 512, w + 4, pb);
      }
    };
    auto xdesc = [&](uint32_t xb) { return mkdesc(__shfl_sync(~0u, 1024 + xb + wg * 16384, 0), 16, 1024); };
    auto rs_issue = [&](float* acc, const uint32_t (&w)[16][4], uint32_t xb, bool fence) {
      const uint64_t x = xdesc(xb);
      if (fence) WG_FENCE();
      wgmma_rs_n32_z(acc, w[0], x);
#pragma unroll
      for (int i = 1; i < 16; i++) wgmma_rs_n32(acc, w[i], x + (i >> 2) * 256 + (i & 3) * 2, 1);
      WG_COMMIT();
    };
    auto v_issue = [&](float* acc, uint32_t xb, bool fence) {
      const uint64_t dv = mkdesc(__shfl_sync(~0u, 1024 + WVS + wg * NVS * 2048, 0), 16, 1024), x = xdesc(xb);
      if (fence) WG_FENCE();
      wgmma_rs_n32_z(acc, wV[0], x);
#pragma unroll
      for (int i = 1; i < (KVO == 2 ? NVR : 0); i++) wgmma_rs_n32(acc, wV[i], x + (i >> 2) * 256 + (i & 3) * 2, 1);
#pragma unroll
      for (int i = NVR; i < 16; i++) wgmma_ssT_n32(acc, dv + (i - NVR) * 128, x + (i >> 2) * 256 + (i & 3) * 2, 1);
#pragma unroll
      for (int i = 1; i < (KVO == 2 ? 0 : NVR); i++) wgmma_rs_n32(acc, wV[i], x + (i >> 2) * 256 + (i & 3) * 2, 1);
      WG_COMMIT();
    };
    uint32_t mA;
    auto vk_pass = [&](int n, uint32_t d, uint32_t xb) {
      float acc[16], acc2[16];
      v_issue(acc, xb, true);
      rs_issue(acc2, wK, xb, false);
      if (n) mbar_wait(sb + BARS + 80, (n - 1) & 1);
      WG_WAIT(1);
      park(acc, 2 - !!KVO, n, d);
      mA = lds1(tp);
      if (n > 1) BAR_ARRIVE(B_K, 320);
      WG_WAIT(0);
      park(acc2, 1 + !!KVO, n, d);
    };
    {
      float acc[16];
      PT(10);
      rs_issue(acc, wQ, WO, true);
#pragma unroll
      for (int i = 0; i < 8; i++) {
        const uint4 v = lds4(L16 + WO + 32768 + wid * 4096 + i * 512);
        sts4(L16 + XB + wid * 4096 + i * 512, v.x, v.y, v.z, v.w);
      }
      WG_WAIT(0); park(acc, 0, 0, park_ptr());
      FENCE_ASYNC_SMEM();
      vk_pass(0, park_ptr(), WO);
      PT(11);
      BAR_SYNC(B_C, 320);
      if (tid == 0) {
        mbar_expect(obar, 65536);
        for (int i = 0; i < 4; i++) tma2d(sb + WO + i * 16384, &mp.wo, j * 256 + i * 64, h * 128, obar);
      }
      asm volatile("" : "+r"(wid));
      rs_issue(acc, wQ, XB, true);
      BAR_SYNC(B_C, 320);
      PT(12);
      mbar_wait(sb + BARS + 24, 0); WG_WAIT(0); park(acc, 0, 1, park_ptr());
      vk_pass(1, park_ptr(), XB);
      BAR_ARRIVE(B_P, 384); if (!HX) BAR_ARRIVE(B_X, 320); BAR_ARRIVE(B_Q, 288);
    }
    PT(13);
    mbar_wait(obar, 0);
    PH(4); PT(14);
    ROLE_REFRESH
    for (int s = 0; s < 64; s++) {
      asm volatile("" : "+r"(tp), "+r"(wid));
      asm volatile("mov.u32 %0,%%cluster_ctarank;" : "=r"(b));
      uint32_t vS[NVS][4], bf[8][4], rm;
      const uint32_t mm = mapa(sb, a ^ 1) + BARS;
      if (s > 0) BAR_SYNC(B_R, 320);
#define VMMA(c, w, i) mma16(c, (w)[0], (w)[1], (w)[2], (w)[3], bf[(i) >> 1][((i) & 1) * 2], bf[(i) >> 1][((i) & 1) * 2 + 1])
      {
        float cQ[4] = {0, 0, 0, 0}, cK[4] = {0, 0, 0, 0};
#pragma unroll
        for (int t = 7; t >= 3; t--) ldsm4t(bf[t], mA + t * 640);
        SCHED_FENCE(47);
#pragma unroll
        for (int i = 15; i >= 0; i--) {
          VMMA(cQ, wQ[i], i); VMMA(cK, wK[i], i);
          if (i == XI && HX) BAR_ARRIVE(B_X, 320);
          if (i == 12) {
            SCHED_FENCE(51);
#pragma unroll
            for (int t = 2; t >= 0; t--) ldsm4t(bf[t], mA + t * 640);
            rm = lds1(tp + 4); frag = lds1(tp + 12);
          }
          if (i == 4 && NVP) {
            SCHED_FENCE(48);
#pragma unroll
            for (int u = 0; u < NVP; u++) ldsm4t(vS[NVS - 1 - u], frag + WVS + (NVS - 1 - u) * 2048);
          }
        }
        const uint32_t w0 = pk(cQ[0] * SCS, cQ[1] * SCS), w1 = pk(cQ[2] * SCS, cQ[3] * SCS), w2 = pk(cK[0], cK[1]), w3 = pk(cK[2], cK[3]);
        if (owner) {
          stsm4(rm, w0, w1, w2, w3);
          BAR_ARRIVE(B_E, 256);
        } else {
          sta1<0>(rm, w0, mm); sta1<128>(rm, w1, mm);
          sta1<RK - RQ>(rm, w2, mm); sta1<RK - RQ + 128>(rm, w3, mm);
        }
        if (wid == 2) TS(0);
      }
      uint4 t1;
      uint32_t oA;
      {
        float cV[4] = {0, 0, 0, 0}, cW[4] = {0, 0, 0, 0};
        static_assert(NVP == 2 && NVR == 5, "schedule");
#define VLD(k) ldsm4t(vS[(k) - NVR], frag + WVS + ((k) - NVR) * 2048)
#define VS_(c, k) VMMA(c, vS[(k) - NVR], k)
        VLD(13); VLD(12);
        VS_(cW, 15); VS_(cV, 14); VLD(11); VMMA(cW, wV[0], 0); VLD(10); VMMA(cV, wV[1], 1); VLD(9);
        VMMA(cW, wV[2], 2); VLD(8); VMMA(cV, wV[3], 3); VLD(7); VMMA(cW, wV[4], 4); VS_(cV, 13); VLD(6); VS_(cW, 12); VLD(5);
        VS_(cV, 11); VS_(cW, 10); VS_(cV, 9); VS_(cW, 8); VS_(cV, 7); VS_(cW, 6); VS_(cV, 5);
#pragma unroll
        for (int e = 0; e < 4; e++) cV[e] += cW[e];
        const uint32_t ex = tp + (RX - TF) - wg * 2048;
        t1 = lds4(tp + 4096);
        oA = lds1(tp + 8 + (s & dZ));
        if (wg) {
          sts4(ex, U_(cV[0]), U_(cV[1]), U_(cV[2]), U_(cV[3]));
          BAR_ARRIVE(B_T2, 256);
        } else {
          BAR_SYNC(B_T2, 256);
          const float4 u = lds4f(ex);
          stg_b64(mkp(t1.w ^ ((s & 1) * X_RING), HI(xc)), (pk(cV[0] + u.x, cV[1] + u.y) & ~1u) | (((s >> 1) + 1) & 1), pk(cV[2] + u.z, cV[3] + u.w));
        }
      }
      if (s == 63) break;
      {
        const uint32_t woA = t1.x, woB = woA ^ 32;
        uint32_t wo[16][4];
#pragma unroll
        for (int i = 0; i < NW1; i++) ldsm4t(wo[i], ((i & 1) ? woB : woA) + (i >= WCH ? wo[(i - WCH + NWP) % NWP][0] & dZ : 0) + (i >> 1) * 2048);
        BAR_SYNC(B_S, 416);
        if (s < 62) {
          float acc[16];
          rs_issue(acc, wQ, XB, true);
          mbar_wait(sb + BARS + 24, (s + 1) & 1);
          WG_WAIT(0);
          BAR_SYNC(B_V, 512);
          park(acc, 0, s + 2, t1.z);
        } else {
          BAR_SYNC(B_V, 512);
        }
#pragma unroll
        for (int i = NW1; i < NWP; i++) ldsm4t(wo[i], ((i & 1) ? woB : woA) + (i >> 1) * 2048);
        float inv0, inv1;
        {
          uint32_t p[4], pm;
          const uint32_t pa = oA + (SC - OB), one = 0x3f803f80u;
          float sum[4] = {0, 0, 0, 0}, su2[4] = {0, 0, 0, 0};
          ldsm4t(p, pa);
          asm volatile("ldmatrix.sync.aligned.m8n8.x1.trans.shared.b16 {%0},[%1];" : "=r"(pm) : "r"(pa + 512) : "memory");
          mma16(sum, one, one, one, one, p[0], p[1]);
          mma16(su2, one, one, one, one, p[2], p[3]);
          mma8(sum, one, one, pm);
          inv0 = sum[0] + su2[0]; inv1 = sum[1] + su2[1];
          SCHED_FENCE(57);
        }
        BAR_SYNC(B_O, 416);
        float c[2][4] = {{0, 0, 0, 0}, {0, 0, 0, 0}};
        uint32_t o[4][4];
#pragma unroll
        for (int i = 0; i < NOP_; i++) ldsm4t(o[i], oA + i * 512);
        SCHED_FENCE(46);
        asm("rcp.approx.ftz.f32 %0,%0;" : "+f"(inv0));
        asm("rcp.approx.ftz.f32 %0,%0;" : "+f"(inv1));
#pragma unroll
        for (int i = 0; i < 16; i++) {
          mma16(c[i & 1], wo[i][0], wo[i][1], wo[i][2], wo[i][3], o[i >> 2][i & 2], o[i >> 2][(i & 2) + 1]);
          if (i == 1 && NOP_ < 3) ldsm4t(o[2], oA + 1024);
          if (i == 3 && NOP_ < 4) ldsm4t(o[3], oA + 1536);
          if (i + NWP < 16) ldsm4t(wo[(i + NWP) & 15], (((i + NWP) & 1) ? woB : woA) + ((i + NWP) >> 1) * 2048);
        }
        stsm4(t1.y, pk(c[0][0] * inv0, c[0][1] * inv1), pk(c[0][2] * inv0, c[0][3] * inv1), pk(c[1][0] * inv0, c[1][1] * inv1), pk(c[1][2] * inv0, c[1][3] * inv1));
      }
      const uint32_t d = park_ptr();
      BAR_SYNC(B_W, 384);
      if (s < 62) {
        vk_pass(s + 2, d, XB);
        BAR_ARRIVE(B_P, 384); if (!HX) BAR_ARRIVE(B_X, 320);
        TS(10);
      } else {
        mA = lds1(tp);
      }
    }
  } else if (role == 3) {
    asm volatile("setmaxnreg.dec.sync.aligned.u32 24;");
    if (blockIdx.x >= 128) return;
    ROLE_VARS
    const uint32_t L16 = sb + (tid & 31) * 16;
    asm volatile("barrier.cluster.wait.aligned;" ::: "memory");
    CLUSTER_SYNC();
    sts1(sb + PACE + 36, LO(xc) + h * 262144 + X_VM(0));
    auto vm_stage = [&](int s) {
      const uint32_t tag = ((s >> 1) + 1) & 1;
      const char* xm = mkp(lds1(sb + PACE + 36) + (s & 1) * X_RING + iw * XC + (l16 >> 1), HI(xc));
      uint2 m[4];
      CONSUME(LO(xm));
      BAR_SYNC(B_S2, 256);
      if (dZ2 > 1) { const uint32_t c = clk(); while (clk() - c < (uint32_t)dZ2) {} }
      int it = 0;
      while (true) {
#pragma unroll
        for (int i = 0; i < 4; i++) m[i] = ldg_b64(xm + (i >> 1) * 2048 + (i & 1) * 256);
        sts4(L16 + VN + iw * 512, m[0].x, m[0].y, m[1].x, m[1].y);
        sts4(L16 + VN + iw * 512 + 2048, m[2].x, m[2].y, m[3].x, m[3].y);
        if (!anybad(m[0].x, m[1].x, m[2].x, m[3].x, tag)) break;
        RP(2);
        if (++it > SPIN_LIMIT) __trap();
      }
      if (s < 63) BAR_ARRIVE(B_V, 512); else BAR_ARRIVE(B_V, 256);
    };
    if (iw == 0) {
      wait_cnt(&g_hcnt, 128);
#pragma unroll 1
      for (int s = 0; s < 63; s++) {
        if (s < 62) for (int it = 0; ldg_rlx1(g_hf + (s & 3)) <= (s >> 2); it++) if (it > SPIN_LIMIT) __trap();
        if (s) BAR_SYNC(B_R, 320); else BAR_SYNC(B_Q, 288);
        if (s < 62) { X_LOAD(s + 2, 0, 0); X_LOAD(s + 2, 1, 0); X_LOAD(s + 2, 0, 1); X_LOAD(s + 2, 1, 1); }
        if (s >= 7) {
          const uint32_t zo = b * 160 + l16;
          if (l16 < 160) CONSUME(exch_b128((char*)g_ar + (zo >> 7) * 1024 + (zo & 127) + ((s + 1) & 7) * 128, 0, 0, 0, 0).x);
          __syncwarp();
        }
        if (s < 62) { mbar_wait(sb + BARS + 64, s & 1); mbar_wait(sb + BARS + 72, s & 1); }
        BAR_ARRIVE(B_S, 416);
        vm_stage(s);
        BAR_ARRIVE(B_O, 416);
        BAR_SYNC(B_W, 384);
        FENCE_ASYNC_SMEM();
        asm volatile("{.reg .pred p; elect.sync _|p, 0xffffffff; @p cp.reduce.async.bulk.tensor.2d.global.shared::cta.add.bulk_group [%0,{%1,%2}],[%3];}"
                     ::"l"(&mp.ari), "r"((s & 7) * 64), "r"(j * 40), "r"(sb + ARO) : "memory");
        BULK_COMMIT();
        asm volatile("st.relaxed.gpu.global.u32 [%0],%1;" ::"l"(g_tm + (s & 1) * 128 + b), "r"(gtime()) : "memory");
        TS(3);
        BULK_WAIT_READ(0);
      }
      BAR_ARRIVE(B_R, 320);
      vm_stage(63);
    } else if (iw == 1) {
      const uint32_t pc = sb + MEM + (lane >> 2) * 640 + (lane & 3) * 144 + (lane & 12), pd = sb + MEM + (lane & 15) * 640 + 576 + (lane & 3) * 16 + (lane & 12);
      uint32_t T = 0, par = 0;
      int est = dA;
#pragma unroll 1
      for (int s = 0; s < 63; s++) {
        if (s) {
          const uint4 tm = ldg_rlx4((const char*)g_tm + ((s + 1) & 1) * 512 + l16);
          const int t0 = tm.x - T, t1 = tm.y - T, t2 = tm.z - T, t3 = tm.w - T;
          const int e = max(dF + (__reduce_add_sync(~0u, (t0 + t1) + (t2 + t3)) >> 7), dV + __reduce_max_sync(~0u, max(max(t0, t1), max(t2, t3))));
          if (s > 1) est += max(min(e >> 2, dP), -dP);
          T += (s == 1 || e > dM ? e : 0) + est;
        }
        vm_stage(s);
        BAR_SYNC(B_W, 384);
        SCHED_FENCE(70);
        const uint32_t tW = gtime();
        if (s == 0) T = tW + 800;
        const uint32_t te = tW + min(max((int)(T - tW), dD), 2000);
        while ((int)(gtime() - te) < 0) {}
        TS(7);
        int it = 0;
        while (true) {
          ar_fetch(sb + MEM, &mp.ari, s & 7, a, sb + BARS + 112);
          mbar_wait(sb + BARS + 112, par);
          par ^= 1;
          const uint32_t n0 = lds1(pc), n1 = lds1(pc + 5120), n2 = lds1(pd);
          if (!__any_sync(~0u, (tagbad(n0, n1, 0x42004200) | (n2 ^ 0x42004200)) != 0)) break;
          RP(0);
          if (++it > SPIN_LIMIT) __trap();
        }
        BAR_ARRIVE(B_R, 320);
        TS(11);
      }
      vm_stage(63);
    } else {
#define V_LOAD(n) do { if (lane == 0) mbar_expect(sb + BARS + 8, 8192); __syncwarp(); \
        if (lane < 16) bulk_ld(sb + ((lane & 2) ? VX1 : VX0) + (lane & 1) * 2048 + (lane >> 2) * 512, \
                               xc + h * 262144 + V_RING(n) + (lane >> 2) * XC + X_VX(lane & 3), 512, sb + BARS + 8); __syncwarp(); } while (0)
      uint32_t src = L16 + PK + (iw & 1) * 2048;
#define qd (L16 + (lane >> 4) * 256 + QT + (iw & 1) * 1024)
#define vd (LO(xc) + h * 262144 + j * XC + (iw & 1) * 2048 + l16)
#define FINISH [&](int n, int m) { \
_Pragma("unroll") \
        for (int i = 1; i >= 0; i--) { \
          const uint32_t p = src + m * 4096 + i * 512; \
          uint4 u = lds4(p); \
          const uint4 w = lds4(p + 1024), y = lds4(p + 12288), z = lds4(p + 13312); \
          u = make_uint4(sum4bf(u.x, w.x, y.x, z.x), sum4bf(u.y, w.y, y.y, z.y), sum4bf(u.z, w.z, y.z, z.z), sum4bf(u.w, w.w, y.w, z.w)); \
          if (m == 2) stg_b128(mkp(vd ^ V_RING(n), HI(xc)) + i * 512, (u.x & ~1u) | V_TAG(n), u.y, u.z, u.w); \
          else stsm4(qd + (n & 1) * 4096 + m * 2048 + i * 256, u.x, u.z, u.y, u.w); \
          SCHED_FENCE(71 + m * 2 + i); \
        } \
      }
#pragma unroll 1
      for (int n = 0; n < 64; n++) {
        src = PIN(src);
        b = __shfl_sync(~0u, lds1(sb + PACE + 24), 0);
        const uint32_t L16 = src - PK - (iw & 1) * 2048;
        auto finish = FINISH;
        if (n < 2) { if (n) BAR_SYNC(B_X, 320); else BAR_SYNC(B_C, 320); }
        mbar_wait(sb + BARS + 16, n & 1);
        finish(n, 0);
        __syncwarp();
        if (lane == 0) mbar_arrive_cl(mapa(sb, a ^ 1) + BARS + 24);
        if (n > 1) BAR_SYNC(B_K, 320);
        mbar_wait(sb + BARS + (KVO ? 32 : 40), n & 1);
        finish(n, 2 - !!KVO);
        if (n > 1) BAR_SYNC(B_X, 320);
        mbar_wait(sb + BARS + (KVO ? 40 : 32), n & 1);
        finish(n, 1 + !!KVO);
        BAR_SYNC(B_T, 64);
        if (lane == 0) {
          if (iw == 2 && n < 63) { mbar_expect(sb + BARS + 16, 4096); mbar_expect(sb + BARS + 32, 4096); mbar_expect(sb + BARS + 40, 4096); }
          mbar_arrive_cl(mapa(sb, a ^ 1) + BARS + 80);
        }
        __syncwarp();
        if (n) {
          vm_stage(n - 1);
          BAR_SYNC(B_W, 384);
        } else {
          BAR_SYNC(B_C, 320);
        }
        if (iw == 2) V_LOAD(n);
      }
      if (HX) BAR_ARRIVE(B_X, 320);
      vm_stage(63);
#undef qd
#undef vd
    }
  } else {
    asm volatile("setmaxnreg.dec.sync.aligned.u32 %0;" ::"n"(RA_));
    if (blockIdx.x >= 128) { if (threadIdx.x == 256) rec_prefetch((const char*)wmod, w1, (const char*)x, wo); return; }
    ROLE_VARS
    uint32_t L16 = __shfl_sync(~0u, sb + (tid & 31) * 16, tid & 31);
    if (wid == 9) {
      for (int i = tid & 31; i < 80; i += 32) g_ar[b * 80 + i] = make_uint4(0, 0, 0, 0);
      if (b == 0) g_fin = 0;
      FENCE_ASYNC();
      __syncwarp();
      if (tid == 288) red_rlx(&g_hcnt);
    }
    if (tid == 256) {
      const int col = h * 128 + bb * 64;
#pragma unroll 1
      for (int c = 0; c < 12 + WIN; c++) {
        const uint32_t mb = sb + PACE + (c % WIN) * 8;
        if (c >= WIN) mbar_wait(mb, (c / WIN - 1) & 1);
        PT(16 + c);
        if (c == 3 + WIN) asm volatile("mbarrier.arrive.shared.b64 _,[%0];" ::"r"(sb + BARS + 88) : "memory");
        if (c >= 12) continue;
        mbar_expect(mb, 16384);
        if (c < 8) tma2d(sb + (c >> 2) * XB + (c & 3) * 16384, (c & 4) ? &mp.wk : &mp.wq, col, a * 512 + (c & 3) * 128, mb);
        else
#pragma unroll 1
          for (int i = (c & 1) * 8; i < (c & 1) * 8 + 8; i++) {
            const int w = (c - 8) >> 1;
            tma2d(i < NVR ? sb + MEM + (w * NVR + i) * 2048 : sb + WVS + (w * NVS + i - NVR) * 2048, &mp.wv, col, a * 512 + w * 256 + i * 16, mb);
          }
      }
      asm volatile("mbarrier.arrive.shared.b64 _,[%0];" ::"r"(wbar) : "memory");
      for (int c = 0; c < 4; c++) tma2d_pf(&mp.wo, j * 256 + c * 64, h * 128);
      for (int i = 0; i < 3; i++) asm volatile("mbarrier.inval.shared.b64 [%0];" ::"r"(sb + PACE + i * 8) : "memory");
    }
    __syncwarp();
    asm volatile("barrier.cluster.wait.aligned;" ::: "memory");
    CLUSTER_SYNC();
#define pr (L16 + SC)
    {
      const int lim = j * 8 + iw * 2 - (lane & 7) - (lane & 8) * 2;
      const bool mk = L16 & 256;
      const int rw = lane >> 2;
      sts4(L16 + TA + iw * 512,
           iw != 2 ? L16 + KT + (iw & 1) * 256 + (lane >> 4) * 256 : sb + RK + (L16 & 0x80) * 2 + ((L16 >> 1) & 0x80) + (L16 & 0x70),
           L16 + QT + (lane >> 3) * 384, sb + SC + min(lane >> 3, 2) * 256 + (L16 & 0x70) + iw * 4, L16 + (lane >> 4) * 256 + QT + (iw >> 1) * 1024 + (iw & 1) * 256);
      sts4(L16 + TA + 2048 + iw * 512, mk ? 0u : (lim < 0 ? 0xfc00u : 0u) | (lim < -1 ? 0xfc000000u : 0u),
           mk ? 0xfc00fc00u : (lim < 8 ? 0xfc00u : 0u) | (lim < 7 ? 0xfc000000u : 0u),
           ((h * 2 + (iw >> 1)) * 1024 + (j * 8 + rw) * 8 + (((iw & 1) * 4 + (lane & 3)) ^ rw)) * 16, sb + OT + iw * 512 + (L16 & 0x70) * 4 + ((L16 >> 3) & 0x30));
    }
    {
      const uint32_t xh = LO(xc) + h * 262144, xs = xh + X_SC + iw * 1024 + min(lane, 16 + (lane & 7)) * 8;
      sts4(L16 + TA + 4096 + iw * 512, xh + X_SC + j * 256 + iw * 64 + lpub, xs, dS, iw != 2 ? 0 : U_(SCS));
      sts1(L16 + TA + 12 + iw * 512, xs + X_TOK + j * 4096);
    }
    uint32_t tA = L16 + TA + iw * 512;
#define tw (tA - L16 != TA + 1024)
#define XP_(lo) mkp(lo, HI(xc))
    auto publish = [&](char* d, const uint2& w) { stg_b64(d, w.x, w.y); };
    BAR_SYNC(B_P, 384);
    for (int s = 0; s < 64; s++) {
      asm volatile("" : "+r"(L16), "+r"(tA));
      const uint32_t tag = ((s >> 1) + 1) & 1, ring = (s & 1) * X_RING;
      const uint4 t0 = lds4(tA);
      const uint4 tx = lds4(tA + 4096);
      const uint32_t xo = tx.x ^ ring, xs = tx.y ^ ring;
      const float gm = F_(tx.w);
      const uint32_t qA = t0.y + (ring >> 5);
      uint32_t c0;
      uint2 ts[4];
      uint4 v[4];
      uint32_t af[2][4], qt[4][4];
      {
        const uint32_t aA = t0.x + (tw ? ring >> 5 : 0);
        uint32_t ql[2][4], qr[2][4];
        uint2 pw_;
        float c[4] = {0, 0, 0, 0}, d[4] = {0, 0, 0, 0};
        if (s == PDS) asm volatile("griddepcontrol.launch_dependents;");
#pragma unroll
        for (int i = 0; i < 4; i++) ldsm4t(qt[i], qA + i * 128);
        mbar_wait(sb + BARS + 8, s & 1);
        TS(4);
        BAR_SYNC(B_E, 256);
#define PACK(c) make_uint2(pkh(fmaf(c[2], gm, c[0] * SCS), fmaf(c[3], gm, c[1] * SCS), tag), pkh(c[2] * SCS, c[3] * SCS, tag))
#define SMMA(x, t, q, i) mma16(x, af[t][0], af[t][1], af[t][2], af[t][3], q[t][i], q[t][i + 1])
        ldsm4t(ql[0], L16 + RQ); ldsm4t(ql[1], L16 + RQ + 1024); ldsm4t(af[0], aA); ldsm4t(af[1], aA + 1024);
        CONSUME(xo);
#define QSUM(t, i) addbf(addbf(ql[t][i], ql[t][i + 2]), addbf(qr[t][i], qr[t][i + 2]))
#define STAIL mma16(c, af[0][0], af[0][1], af[0][2], af[0][3], QSUM(0, 0), QSUM(0, 1)); mma16(d, af[1][0], af[1][1], af[1][2], af[1][3], QSUM(1, 0), QSUM(1, 1));
        if (tw) {
          mbar_wait(sb + BARS, s & 1);
          TS(8);
          ldsm4t(qr[0], L16 + RQ + 512); ldsm4t(qr[1], L16 + RQ + 1536);
          STAIL
          pw_ = make_uint2(pkh(c[0] + d[0], c[1] + d[1], tag), pkh(c[2] + d[2], c[3] + d[3], tag));
        } else {
          uint32_t ar[2][4];
          mbar_wait(sb + BARS, s & 1);
          ldsm4t(qr[0], L16 + RQ + 512); ldsm4t(ar[0], aA + 512); ldsm4t(qr[1], L16 + RQ + 1536); ldsm4t(ar[1], aA + 1536);
#pragma unroll
          for (int i = 0; i < 8; i++) af[i >> 2][i & 3] = addbf(af[i >> 2][i & 3], ar[i >> 2][i & 3]);
          STAIL
          pw_.x = pw_.y = pkh((c[0] + c[2]) + (d[0] + d[2]), (c[1] + c[3]) + (d[1] + d[3]), tag);
        }
        publish(XP_(xo), pw_);
        c0 = clk() + tx.z;
        TS(1);
      }
      uint2 r[4];
#define TOKS(i) { float e0[4] = {0, 0, 0, 0}, e1[4] = {0, 0, 0, 0}; \
        mma16(e0, af[0][0], af[0][1], af[0][2], af[0][3], qt[i][0], qt[i][1]); mma16(e1, af[0][0], af[0][1], af[0][2], af[0][3], qt[i + 1][0], qt[i + 1][1]); \
        mma16(e0, af[1][0], af[1][1], af[1][2], af[1][3], qt[i][2], qt[i][3]); mma16(e1, af[1][0], af[1][1], af[1][2], af[1][3], qt[i + 1][2], qt[i + 1][3]); \
        ts[i] = PACK(e0); ts[i + 1] = PACK(e1); }
      {
        float e[4][4];
#pragma unroll
        for (int i = 0; i < 4; i++) {
          e[i][0] = e[i][1] = e[i][2] = e[i][3] = 0.f;
          mma16(e[i], af[0][0], af[0][1], af[0][2], af[0][3], qt[i][0], qt[i][1]);
        }
#pragma unroll
        for (int i = 0; i < 4; i++) mma16(e[i], af[1][0], af[1][1], af[1][2], af[1][3], qt[i][2], qt[i][3]);
        SCHED_FENCE(55);
        if (s < 63) BAR_ARRIVE(B_S, 416);
        SCHED_FENCE(58);
        v[0] = lds4(tA + (VX0 - TA)); v[1] = lds4(tA + (VX0 - TA) + 2048); v[2] = lds4(tA + (VX1 - TA)); v[3] = lds4(tA + (VX1 - TA) + 2048);
#pragma unroll
        for (int i = 0; i < 4; i++) ts[i] = PACK(e[i]);
        while ((int)(clk() - c0) < 0) {}
        TS(5);
#pragma unroll
        for (int u = 0; u < 4; u++) r[u] = ldg_b64(XP_(xs) + u * 256);
        BAR_ARRIVE(B_S2, 256);
      }
      const uint32_t fn = (L16 & 256) ? 0xfc00fc00u : 0u;
      SCHED_FENCE(56);
      float4 e = softmax2<false>(r, 0, fn);
      const bool vbad = anybad(v[0].x, v[1].x, v[2].x, v[3].x, V_TAG(s));
      if (BADS(r)) {
        int it = 0;
        if (s > 8) sts1(tA + 4096 + 8, min(lds1(tA + 4096 + 8) + dX, 500));
        do {
          RP(1);
          if (++it > SPIN_LIMIT) __trap();
#pragma unroll
          for (int u = 0; u < 4; u++) r[u] = ldg_b64(XP_(xs) + u * 256);
        } while (BADS(r));
        e = softmax2<false>(r, 0, fn);
      }
      sts1(t0.z, pk(e.x, e.y)); sts1(t0.z + 128, pk(e.z, e.w));
#pragma unroll
      for (int i = 0; i < 4; i++) publish(XP_(xo) + X_TOK + i * 4096, ts[i]);
      TS(6);
      if (s < 63) BAR_SYNC(B_V, 512); else BAR_SYNC(B_V, 256);
      uint32_t O[4];
      uint4 vn[2];
      {
        uint32_t p[4], pm;
        ldsm4t(p, pr);
        asm volatile("ldmatrix.sync.aligned.m8n8.x1.trans.shared.b16 {%0},[%1];" : "=r"(pm) : "r"(pr + 512) : "memory");
        vn[0] = lds4(tA + (VN - TA)); vn[1] = lds4(tA + (VN - TA) + 2048);
        pv_mem(p, pm, v, vn, O);
        if (vbad) {
          int it = 0;
          do {
            if (++it > SPIN_LIMIT) __trap();
#pragma unroll
            for (int u = 0; u < 4; u++) v[u] = ldg_b128(XP_((LO(xc) + (lds1(sb + PACE + 24) >> 2) * 262144 + ((tA - L16 - TA) >> 9) * XC + l16) ^ V_RING(s)) + X_VX(u));
          } while (anybad(v[0].x, v[1].x, v[2].x, v[3].x, V_TAG(s)));
          pv_mem(p, pm, v, vn, O);
        }
      }
      stsm4(tA + (OB - TA), O[0], O[1], O[2], O[3]);
      if (s < 63) BAR_ARRIVE(B_O, 416);
      TS(2);
      c0 = clk() + dG;
      SCHED_FENCE(60);
      if (tA == sb + TA) mbar_expect(sb + BARS, 2048);
      const uint32_t vs[4] = {addbf(vn[0].x, vn[0].z), addbf(vn[0].y, vn[0].w), addbf(vn[1].x, vn[1].z), addbf(vn[1].y, vn[1].w)};
      {
        const char* xt = XP_(lds1(tA + 12) ^ ring);
        const uint2 t1 = lds2u(tA + 2048);
        const uint32_t pw = lds1(tA + 8);
        uint2 rt[4];
        CONSUME(LO(xt) ^ t1.x ^ pw);
        while ((int)(clk() - c0) < 0) {}
        int it = 0;
        do {
          if (++it > SPIN_LIMIT) __trap();
#pragma unroll
          for (int u = 0; u < 4; u++) rt[u] = ldg_b64(xt + u * 256);
        } while (BADS(rt));
        const float4 et = softmax2<true>(rt, t1.x, t1.y);
        sts1(pw + 1024, pk(et.x, et.y)); sts1(pw + 1024 + 128, pk(et.z, et.w));
      }
      s = PIN(s);
      BAR_SYNC(B_SC, 128);
      {
        uint32_t Ot[4], p[4], pm;
        const uint2 t2 = lds2u(tA + 2048 + 8);
        ldsm4t(p, pr + 1024);
        asm volatile("ldmatrix.sync.aligned.m8n8.x1.trans.shared.b16 {%0},[%1];" : "=r"(pm) : "r"(pr + 1024 + 512) : "memory");
        char* od = (char*)g_O + ((s >> 2) * 1048576 + (s & 3) * 4096) + t2.x;
        CONSUME(LO(od) ^ HI(od) ^ pm ^ p[3]);
        TS(9);
        if (s < 62) BAR_SYNC(B_P, 384);
        pv_tok(p, pm, v, vs, Ot);
        asm volatile("stmatrix.sync.aligned.m8n8.x4.trans.shared.b16 [%0],{%1,%2,%3,%4};" ::"r"(t2.y), "r"(Ot[0]), "r"(Ot[1]), "r"(Ot[2]), "r"(Ot[3]) : "memory");
        __syncwarp();
        *(uint4*)od = lds4(tA + (OT - TA));
      }
    }
    FENCE_ASYNC();
    BAR_SYNC(B_SC, 128);
    if (tA == sb + TA) red_rlx(&g_fin);
  }
  __syncwarp();
  CLUSTER_SYNC();
  PH(5);
}
#undef wg
#undef iw
#undef h
#undef j
#undef a
#undef bb
#undef oi
#undef owner
#undef vfin
#undef pr
#undef PIN
#undef XP_
#undef tw
#undef is7
#undef REFRESH
#undef lane
#undef l16
#undef lrow
#undef lar
#undef lpub

namespace ffn {
constexpr uint32_t BR = 98304;
constexpr uint32_t STG = 196608;
constexpr uint32_t PRM = 229376;
constexpr uint32_t BARS = PRM + 2816;
constexpr uint32_t SMEM = BARS + 18 * 8;
}
#define Y_TILE(rb, kt) (((ALIAS & 1) ? g_h : g_h2) + ((rb) * 16 + (kt)) * 1024)
#define U_TILE(rb, kt) ((ALIAS & 2) ? g_O + ((rb) * 64 + (kt)) * 1024 : g_U + ((rb) * 56 + (kt)) * 1024)
struct FfnMaps { CUtensorMap wo, w1a, w1b, w2, x, out; };

template <int N>
__device__ __forceinline__ void wg_ss(float* d, uint64_t a, uint64_t b, int sd) {
  if (N == 128) wgmma_ss_n128(d, a, b, sd);
  if (N == 192) wgmma_ss_n192(d, a, b, sd);
}
template <int N>
__device__ __forceinline__ void acc_fence(float* d) {
#pragma unroll
  for (int i = 0; i < N; i++) asm volatile("" : "+f"(d[i])::"memory");
}
#define UNPK8(d, v) do { (d)[0] = blo(v.x); (d)[1] = bhi(v.x); (d)[2] = blo(v.y); (d)[3] = bhi(v.y); (d)[4] = blo(v.z); (d)[5] = bhi(v.z); (d)[6] = blo(v.w); (d)[7] = bhi(v.w); } while (0)
struct FfnPipe {
  uint32_t full, emp, ph, aoff;
  int st, sB, prev;
  bool leader;
  template <int N>
  __device__ __forceinline__ void issue(float* acc, bool first, uint32_t a = 0) {
    mbar_wait(full + st * 8, ph);
    const uint64_t da = mkdesc((a ? a : 1024 + st * 16384) + aoff, 16, 1024), db = mkdesc(1024 + ffn::BR + sB * (N * 128), 8192, 1024);
    WG_FENCE();
#pragma unroll
    for (int j = 0; j < ((FDB & 1) ? 1 : 4); j++) wg_ss<N>(acc, da + j * 2, db + j * 128, j || !first);
    WG_COMMIT();
    if (++sB == 768 / N) sB = 0;
  }
  __device__ __forceinline__ void release() { if (leader) mbar_arrive(emp + prev * 8); }
  __device__ __forceinline__ void next() { prev = st; if (++st == 6) { st = 0; ph ^= 1; } }
  __device__ __forceinline__ void retire() { WG_WAIT(1); release(); next(); }
};
__device__ __forceinline__ float gelu_h(float hx) {
  float u = hx * fmaf(hx * hx, 8.f * 0.0356774081f, 2.f * 0.7978845608f), t;
  if (FDB & 4) return hx;
  if (FDB & 2) t = u; else
  asm("tanh.approx.f32 %0,%1;" : "=f"(t) : "f"(u));
  return fmaf(hx, t, hx);
}
struct FfnEpi {
  uint32_t st2, cc, flip, staged, l0;
  uint2 c;
  float n0, n1, s0, s1;
  __device__ __forceinline__ void flush(uint32_t r) {
    __syncwarp();
    asm volatile("{.reg .pred p; setp.ne.u32 p,%1,0; @p mbarrier.arrive.shared.b64 _,[%0];}" ::"r"(staged + (flip >> 11)), "r"(l0 & r) : "memory");
    flip ^= r << 14;
  }
  __device__ __forceinline__ void half(const float* d, int J, int r) {
#define PRE(i, n, c1, c2) gelu_h(fmaf(r ? d[4 + i] : d[i], i < 2 ? s0 : s1, fmaf(n, c1, c2)))
    asm volatile("stmatrix.sync.aligned.m8n8.x2.shared.b16 [%0],{%1,%2};" ::"r"((st2 ^ ((J & 3) * 32 + r * 16)) + flip),
                 "r"(pk(PRE(0, n0, blo(c.x), blo(c.y)), PRE(1, n0, bhi(c.x), bhi(c.y)))), "r"(pk(PRE(2, n1, blo(c.x), blo(c.y)), PRE(3, n1, bhi(c.x), bhi(c.y)))) : "memory");
#undef PRE
    if ((J & 3) == 3) flush(r);
    cc += r ? 56 : 8;
    c = lds2u(cc);
  }
};

__global__ void __launch_bounds__(384, 1)
k_ffn(const __grid_constant__ FfnMaps mp, const bf16* __restrict__ b2) {
  using namespace ffn;
  extern __shared__ __align__(1024) char smem[];
  const uint32_t sb = (uint32_t)__cvta_generic_to_shared(smem);
  if (sb != 1024) __trap();
  const int tid = threadIdx.x, lane = tid & 31, wg = __shfl_sync(~0u, tid >> 7, 0);
  const uint32_t full = sb + BARS, emp = full + 48, xbar = full + 96, staged = full + 104, tile = full + 136;
  uint32_t fin = 0;
  if (tid >= 288 && tid < 320) fin = ld_acq(&g_fin);
  if (tid < 32) {
    unsigned sm, v = 0;
    asm("mov.u32 %0,%%smid;" : "=r"(sm));
    if (tid == 0) {
      v = atomicExch(&g_slot[sm & 255], 0);
      for (int i = 0; i < 6; i++) { mbar_init(full + i * 8, 1); mbar_init(emp + i * 8, 2); }
      mbar_init(xbar, 2);
      for (int i = 0; i < 2; i++) { mbar_init(staged + i * 8, 8); mbar_init(staged + 16 + i * 8, 1); }
      FENCE_ASYNC_SMEM();
    }
    v = __shfl_sync(~0u, v, 0);
    if (!v) {
      wait_cnt(&g_fin, 128);
      for (int it = 0; !v; it++) {
        const uint4 a = ldg_rlx4(g_slot + tid * 8), b = ldg_rlx4(g_slot + tid * 8 + 4);
        const uint32_t open = __ballot_sync(~0u, a.x | a.y | a.z | a.w | b.x | b.y | b.z | b.w);
        if (!open) break;
        if (it < 16) { __nanosleep(500); continue; }
        if (tid == __ffs(open) - 1) v = atomicExch(&g_slot[tid * 8 + (a.x ? 0 : a.y ? 1 : a.z ? 2 : a.w ? 3 : b.x ? 4 : b.y ? 5 : b.z ? 6 : 7)], 0);
        v = __shfl_sync(~0u, v, __ffs(open) - 1);
      }
    }
    if (tid == 0) sts1(tile, v);
  }
  if (tid == 256) asm volatile("prefetch.tensormap [%0];" ::"l"(&mp.wo) : "memory");
  __syncthreads();
  const int bid = __shfl_sync(~0u, lds1(tile), 0) - 1;
  if (bid < 0) return;
  PH(6);
  FT(1);
  const int rb = bid >> 3, nb = bid & 7;
  unsigned* cnt = g_cnt + rb * 128;
  if (wg == 2) {
    asm volatile("setmaxnreg.dec.sync.aligned.u32 " FRP ";");
    const int pw = __shfl_sync(~0u, (tid >> 5) & 3, 0);
    uint32_t ws = emp, wp = 1, fs = full;
    auto wait_free = [&]() { mbar_wait_q(ws, wp); ws += 8; if (ws == emp + 48) { ws = emp; wp ^= 1; } };
    auto step = [&]() { fs += 8; if (fs == full + 48) fs = full; };
#define K3(c) ((0x65230 >> (c) * 4) & 7)
#define KC(k) ((k) < 2 ? nb * 2 + (k) : (k) < 9 ? ((k) - 2 + ((k) - 2 >= nb)) * 2 : ((k) - 9 + ((k) - 9 >= nb)) * 2 + 1)
    if (pw == 0) {
      uint32_t d = sb + BR + 32768;
      auto put = [&](const CUtensorMap* m, int k, int c) {
        e_expect_tma3d(d, m, k * 64, c, fs, 32768);
        step();
        d += 16384;
        if (d == sb + STG) d = sb + BR;
      };
      int n = 0;
      auto stage_free = [&]() { if (!(n & 7) && n < 56) mbar_wait_q(staged + 16 + (n & 8), (n >> 4) & 1); n++; };
      FTP(3);
#pragma unroll 1
      for (int k = 0; k < 66; k++) { wait_free(); if (k < 64) put(&mp.wo, k, nb * 2); }
#pragma unroll 1
      for (int k = 0; k < 16; k++) {
        const int kt = KC(k);
        wait_free();
        e_expect_tma3d(sb + BR + (k & 3) * 24576, &mp.w1b, kt * 64, nb * 7, fs, k < 2 ? 24576 : 40960);
        step();
      }
#pragma unroll 1
      for (int k = 0; k < 32; k++) { stage_free(); if (k != 5 && k != 6) wait_free(); put(&mp.w1a, k & 15, nb * 7 + 3 + (k >> 4) * 2); }
#pragma unroll 1
      for (int c = 0; c < 5; c++)
#pragma unroll 1
        for (int k = K3(c), i = 0; k < 56; k += c < 2 && (i ^= 1) ? 1 : c < 2 ? 6 : 7) { stage_free(); wait_free(); put(&mp.w2, k, nb * 2); }
    } else if (pw == 1) {
      FTP(5);
      if (fin < 128) wait_cnt(&g_fin, 128);
      FTP(6);
      uint32_t d = sb;
      auto put = [&](const uint4* A, bool ld) {
        wait_free();
        if (ld) e_bulk_ld(d, A, 16384, fs);
        step();
        d += 16384;
        if (d == sb + BR) d = sb;
      };
      const uint4* A = g_O + rb * 65536;
#pragma unroll 1
      for (int k = 0; k < 66; k++) put(A + k * 1024, k < 64);
      A = Y_TILE(rb, 0);
      uint32_t ready = 0;
#pragma unroll 1
      for (int k = 2; k < 48; k++) {
        const int kt = k < 16 ? KC(k) : k & 15;
        for (int it = 0; !(ready >> ((kt >> 1) + (kt & 1) * 8) & 1); it++) {
          ready = __ballot_sync(~0u, ldg_rlx1(cnt + (lane & 7)) & ((lane & 8) ? 1 : 0x10000));
          if (it > SPIN_LIMIT) __trap();
        }
        if (k == 2) FTP(75);
        put(A + kt * 1024, true);
      }
      A = U_TILE(rb, 0);
#pragma unroll 1
      for (int c = 0; c < 5; c++) {
        for (int it = 0; ldg_rlx1(cnt + 32 + c) < 8; it++) if (it > SPIN_LIMIT) __trap();
#pragma unroll 1
        for (int k = K3(c), i = 0; k < 56; k += c < 2 && (i ^= 1) ? 1 : c < 2 ? 6 : 7) put(A + k * 1024, true);
      }
    } else if (pw == 2) {
      for (int i = 0; i < XDL; i++) {
        mbar_wait_q(emp, i & 1);
        if (XPF && i == 1 && lane < 2) tma2d_pf(&mp.x, nb * 128 + lane * 64, rb * 128);
      }
      if (lane == 0) {
        mbar_expect(xbar, 32768);
        tma2d(sb + STG, &mp.x, nb * 128, rb * 128, xbar);
        tma2d(sb + STG + 16384, &mp.x, nb * 128 + 64, rb * 128, xbar);
      }
      asm volatile("griddepcontrol.wait;" ::: "memory");
      if (lane < 16) g_modp[bid * 16 + lane] = make_uint4(0, 0, 0, 0);
      if (lane >= 16 && bid == 0) { g_hcnt = 0; g_mcnt = 0; g_hf[lane & 3] = 0; }
      if (lane == 0) {
#pragma unroll 1
        for (int g = 1; g < 9; g++) {
          if (g == 1) mbar_wait(staged + 8, 0); else { mbar_wait_q(staged + (g & 1) * 8, (g >> 1) & 1); FENCE_ASYNC_SMEM(); }
          bulk_st(g == 1 ? Y_TILE(rb, nb * 2 + 1) : U_TILE(rb, nb * 7 + ((0x652431000ull >> g * 4) & 7)), sb + STG + (g & 1) * 16384, 16384);
          BULK_COMMIT();
          if (g != 2 && g != 4) { BULK_WAIT(0); red_rlx(g == 1 ? cnt + nb : cnt + 32 + (g < 6 ? g >> 2 : g - 4)); }
          BULK_WAIT_READ(0);
          mbar_arrive(staged + 16 + (g & 1) * 8);
        }
      }
    } else {
      const uint32_t prm = sb + PRM, pp = prm + (lane >> 3) * 64 + (lane & 1) * 32 + (lane & 6) * 2;
      const uint2 v2 = ((const uint2*)(b2 + nb * 128))[lane];
      sts1(pp + 768, v2.x); sts1(pp + 784, v2.y);
      asm volatile("griddepcontrol.wait;" ::: "memory");
      const float4* md = (const float4*)(g_mod + nb * 128) + lane;
      { const float4 ga = md[512]; sts1(pp, pk(ga.x, ga.y)); sts1(pp + 16, pk(ga.z, ga.w)); }
      { const float4 cb = md[1024]; sts1(pp + 256, pk(1.f + cb.x, 1.f + cb.y)); sts1(pp + 272, pk(1.f + cb.z, 1.f + cb.w)); }
      { const float4 gb = md[1280]; sts1(pp + 512, pk(gb.x, gb.y)); sts1(pp + 528, pk(gb.z, gb.w)); }
#pragma unroll 1
      for (int i = lane; i < 112; i += 32) { const uint4 c = g_cc[nb * 112 + i]; sts4(prm + 1024 + i * 16, c.x, c.y, c.z, c.w); }
      __syncwarp();
      if (lane == 0) {
        mbar_arrive(xbar);
        mbar_wait(staged, 0);
        bulk_st(Y_TILE(rb, nb * 2), sb + STG, 16384);
        BULK_COMMIT(); BULK_WAIT(0);
        asm volatile("red.relaxed.gpu.global.add.u32 [%0],0x10000;" ::"l"(cnt + nb) : "memory");
        mbar_arrive(staged + 16);
      }
      __syncwarp();
      mbar_wait_q(staged + 24, 0);
      mbar_wait_q(emp + 40, 0);
#pragma unroll 1
      for (int i = 0; i < 4; i++) {
        const uint4* sp = g_stat + (rb * 128 + i * 32 + lane) * 4;
        uint4 v[4];
        for (int it = 0;; it++) {
          uint32_t m = 0;
#pragma unroll
          for (int u = 0; u < 4; u++) { v[u] = ldg_rlx4(sp + u); m = max(max(m, max(v[u].x, v[u].y)), max(v[u].z, v[u].w)); }
          if (!__any_sync(~0u, m == ~0u)) break;
          if (it > SPIN_LIMIT) __trap();
        }
        float m = 0, q = 0;
#pragma unroll
        for (int u = 0; u < 4; u++) m += F_(v[u].x) + F_(v[u].z);
        m *= 0.125f;
#pragma unroll
        for (int u = 0; u < 4; u++) { const float a = F_(v[u].x) - m, b = F_(v[u].z) - m; q += F_(v[u].y) + F_(v[u].w) + 128.f * (a * a + b * b); }
        const float r = 0.5f * rsqrtf(q * (1.f / 1024) + 1e-5f);
        sts2(sb + STG + 16384 + (i * 32 + lane) * 8, U_(r), U_(-m * r));
      }
      __syncwarp();
      if (lane < 2) mbar_arrive(xbar);
    }
  } else {
    asm volatile("setmaxnreg.inc.sync.aligned.u32 " FRC ";");
    const int w = (tid >> 5) & 3, q = lane & 3;
    const uint32_t prm = sb + PRM + q * 16;
    const int row0 = wg * 64 + w * 16;
    FfnPipe p;
    p.full = full; p.emp = emp; p.ph = 0; p.aoff = wg * 8192; p.st = 0; p.sB = 2; p.prev = 0; p.leader = (tid & 127) == 0;
    FfnEpi e;
    const uint32_t stg = sb + STG + row0 * 128;
    e.st2 = stg + (lane & 15) * 128 + ((lane & 7) << 4);
    e.cc = sb + PRM + 1024 + q * 16; e.flip = 0; e.staged = staged; e.l0 = lane == 0;
    const uint32_t stw = e.st2 ^ (lane & 16);
    uint32_t x1[32];
    uint4* sp = g_stat + (rb * 128 + row0 + (lane >> 2)) * 4;
    float old[96], r0_, r1_;
    {
      float acc[64];
      p.issue<128>(acc, true); FT(8); p.next();
#pragma unroll 1
      for (int k = 1; k < 64; k++) { p.issue<128>(acc, false); FT(8 + k); p.retire(); }
      float xf[64], gf[32];
      uint32_t cb[16];
      mbar_wait(xbar, 0);
#pragma unroll
      for (int j = 0; j < 8; j++) {
        uint32_t xv[4];
        ldsm4(xv, (stw ^ ((j & 3) * 32)) + (j >> 2) * 16384);
#pragma unroll
        for (int i = 0; i < 4; i++) { xf[j * 8 + i * 2] = blo(xv[i]); xf[j * 8 + i * 2 + 1] = bhi(xv[i]); }
      }
#pragma unroll
      for (int i = 0; i < 4; i++) {
        const uint4 g = lds4(prm + i * 64), c = lds4(prm + 256 + i * 64);
        UNPK8(gf + i * 8, g);
        cb[i * 4] = c.x; cb[i * 4 + 1] = c.y; cb[i * 4 + 2] = c.z; cb[i * 4 + 3] = c.w;
      }
      acc_fence<64>(xf); acc_fence<32>(gf);
      WG_WAIT(0);
      p.release();
      acc_fence<64>(acc);
      PH(7); FT(72);
#pragma unroll
      for (int j = 0; j < 8; j++) {
        uint32_t* o = x1 + j * 4;
#pragma unroll
        for (int i = 0; i < 4; i++)
          o[i] = pk(fmaf(acc[j * 8 + i * 2], gf[j * 4 + (i & 2)], xf[j * 8 + i * 2]), fmaf(acc[j * 8 + i * 2 + 1], gf[j * 4 + (i & 2) + 1], xf[j * 8 + i * 2 + 1]));
        stsm4((stw ^ ((j & 3) * 32)) + (j >> 2) * 16384, mulbf(o[0], cb[j * 2]), mulbf(o[1], cb[j * 2]), mulbf(o[2], cb[j * 2 + 1]), mulbf(o[3], cb[j * 2 + 1]));
        if ((j & 3) == 3) { FENCE_ASYNC_SMEM(); e.flush(1); }
      }
      if (wg) BAR_SYNC(2, 128); else BAR_SYNC(3, 128);
    }
    PH(8); FT(73);
    float acc[64];
    {
      float* accC = old;
      p.sB = 0;
      p.issue<192>(accC, true, 1024 + STG); FT(80); p.next();
      p.issue<192>(accC, false, 1024 + STG + 16384); FT(81);
      FT(78);
      float s0 = 0, s1 = 0;
#define X1_FENCE _Pragma("unroll") for (int j = 0; j < 32; j++) asm volatile("" : "+r"(x1[j]));
      X1_FENCE
#pragma unroll
      for (int j = 0; j < 16; j++) { s0 += blo(x1[j * 2]) + bhi(x1[j * 2]); s1 += blo(x1[j * 2 + 1]) + bhi(x1[j * 2 + 1]); }
      s0 += __shfl_xor_sync(~0u, s0, 1); s1 += __shfl_xor_sync(~0u, s1, 1);
      s0 += __shfl_xor_sync(~0u, s0, 2); s1 += __shfl_xor_sync(~0u, s1, 2);
      s0 *= 1.f / 128; s1 *= 1.f / 128;
      float q0 = 0, q1 = 0;
      X1_FENCE
#pragma unroll
      for (int j = 0; j < 16; j++) {
        const float a = blo(x1[j * 2]) - s0, b = bhi(x1[j * 2]) - s0, c = blo(x1[j * 2 + 1]) - s1, d = bhi(x1[j * 2 + 1]) - s1;
        q0 += a * a + b * b; q1 += c * c + d * d;
      }
      q0 += __shfl_xor_sync(~0u, q0, 1); q1 += __shfl_xor_sync(~0u, q1, 1);
      q0 += __shfl_xor_sync(~0u, q0, 2); q1 += __shfl_xor_sync(~0u, q1, 2);
      if (q < 2) {
        uint32_t m = __float_as_uint(q ? s1 : s0), v = __float_as_uint(q ? q1 : q0);
        if (m == ~0u) m = 0x7fffffffu;
        if (v == ~0u) v = 0x7fffffffu;
        stg_rlx2((uint2*)(sp + q * 32) + nb, m, v);
      }
      X1_FENCE
      p.retire();
#pragma unroll 1
      for (int k = 2; k < 15; k++) { p.issue<192>(accC, false); FT(80 + k); p.retire(); }
      p.issue<192>(accC, false); FT(95);
      mbar_wait(xbar, 1);
      const float2 u0 = lds2f(sb + STG + 16384 + (row0 + (lane >> 2)) * 8), u1 = lds2f(sb + STG + 16384 + (row0 + (lane >> 2)) * 8 + 64);
      r0_ = u0.x; e.n0 = u0.y; r1_ = u1.x; e.n1 = u1.y;
      e.c = lds2u(e.cc);
      p.retire();
      e.s0 = r0_; e.s1 = r1_;
    }
    PH(9);
    {
      auto pair = [&](int J, bool first, int fo) {
#pragma unroll 1
        for (int r = 0; r < 2; r++) { p.issue<128>(acc, first && !r); FT(fo + r); p.retire(); acc_fence<8>(old + J * 8); e.half(old + J * 8, J, r); }
      };
#pragma unroll 1
      for (int i = 0; i < 3; i++) {
        if (i == 2) {
          e.s0 = r0_; e.s1 = r1_;
#pragma unroll
          for (int J = 8; J < 12; J++) pair(J, J == 8, 128 + (J - 8) * 2);
          e.cc += 512; e.c = lds2u(e.cc);
          e.s0 = e.s1 = 1.f;
        }
#pragma unroll
        for (int J = 0; J < 8; J++) pair(J, J == 0 && i < 2, 96 + i * 16 + (i >> 1) * 8 + J * 2);
        if (i == 2) break;
        e.cc += i ? -768 : 256; e.c = lds2u(e.cc);
        WG_WAIT(0);
        acc_fence<64>(acc);
#pragma unroll
        for (int k = 0; k < 64; k++) old[k] = acc[k] * ((k & 2) ? r1_ : r0_);
        acc_fence<64>(old);
        e.s0 = e.s1 = 1.f;
        PH(10 + i);
      }
#pragma unroll 1
      for (int k = 24; k < 56; k++) { p.issue<128>(acc, false); FT(128 + k); p.retire(); }
      float xf[64], gf[32];
#pragma unroll
      for (int i = 0; i < 4; i++) {
        const uint4 g = lds4(prm + 512 + i * 64), h = lds4(prm + 768 + i * 64);
        float hf[8];
        UNPK8(gf + i * 8, g); UNPK8(hf, h);
#pragma unroll
        for (int u = 0; u < 8; u++) {
          const int c = (u >> 2) * 4 + (u & 2);
          xf[i * 16 + u * 2] = fmaf(gf[i * 8 + c], hf[c], blo(x1[i * 8 + u])); xf[i * 16 + u * 2 + 1] = fmaf(gf[i * 8 + c + 1], hf[c + 1], bhi(x1[i * 8 + u]));
        }
      }
      acc_fence<64>(xf); acc_fence<32>(gf);
      mbar_wait(staged + 24, 1);
      mbar_wait(staged + 16, 0);
      WG_WAIT(0);
      acc_fence<64>(acc);
      PH(13); FT(184);
#pragma unroll
      for (int j = 0; j < 8; j++) {
        uint32_t o[4];
#pragma unroll
        for (int i = 0; i < 4; i++)
          o[i] = pk(fmaf(acc[j * 8 + i * 2], gf[j * 4 + (i & 2)], xf[j * 8 + i * 2]), fmaf(acc[j * 8 + i * 2 + 1], gf[j * 4 + (i & 2) + 1], xf[j * 8 + i * 2 + 1]));
        stsm4((stw ^ ((j & 3) * 32)) + (j >> 2) * 16384, o[0], o[1], o[2], o[3]);
        if ((j & 3) == 3) {
          FENCE_ASYNC_SMEM();
          __syncwarp();
          if (lane == 0) { tma2d_st(&mp.out, nb * 128 + (j >> 2) * 64, rb * 128 + row0, stg + (j >> 2) * 16384); BULK_COMMIT(); }
        }
      }
      if (lane == 0) BULK_WAIT_READ(0);
      __syncwarp();
    }
  }
  PH(14); FT(185);
}

typedef CUresult (*EncFn)(CUtensorMap*, CUtensorMapDataType, cuuint32_t, void*, const cuuint64_t*, const cuuint64_t*, const cuuint32_t*,
                          const cuuint32_t*, CUtensorMapInterleave, CUtensorMapSwizzle, CUtensorMapL2promotion, CUtensorMapFloatOOBfill);
static void map2d(EncFn enc, CUtensorMap* m, const void* p, int rows, int cols, int boxRows) {
  cuuint64_t d[2] = {(cuuint64_t)cols, (cuuint64_t)rows}, s[1] = {(cuuint64_t)cols * 2};
  cuuint32_t b[2] = {64, (cuuint32_t)boxRows}, e[2] = {1, 1};
  enc(m, CU_TENSOR_MAP_DATA_TYPE_BFLOAT16, 2, (void*)p, d, s, b, e, CU_TENSOR_MAP_INTERLEAVE_NONE, CU_TENSOR_MAP_SWIZZLE_128B,
      CU_TENSOR_MAP_L2_PROMOTION_L2_128B, CU_TENSOR_MAP_FLOAT_OOB_FILL_NONE);
}
static void map3d(EncFn enc, CUtensorMap* m, const void* p, int rows, int cols, int nch) {
  cuuint64_t d[3] = {64, (cuuint64_t)rows, (cuuint64_t)(cols / 64)}, s[2] = {(cuuint64_t)cols * 2, 128};
  cuuint32_t b[3] = {64, 64, (cuuint32_t)nch}, e[3] = {1, 1, 1};
  enc(m, CU_TENSOR_MAP_DATA_TYPE_BFLOAT16, 3, (void*)p, d, s, b, e, CU_TENSOR_MAP_INTERLEAVE_NONE, CU_TENSOR_MAP_SWIZZLE_128B,
      CU_TENSOR_MAP_L2_PROMOTION_L2_128B, CU_TENSOR_MAP_FLOAT_OOB_FILL_NONE);
}

extern "C" void kernel_launch(void* const* d_in, const int* in_sizes, int n_in, void* d_out, int out_size) {
  const bf16* x = (const bf16*)d_in[0];
  const bf16* mem0 = (const bf16*)d_in[1];
  void* fn = nullptr;
  cudaDriverEntryPointQueryResult qr;
  cudaGetDriverEntryPoint("cuTensorMapEncodeTiled", &fn, cudaEnableDefault, &qr);
  EncFn enc = (EncFn)fn;
  FfnMaps fm = {};
  map3d(enc, &fm.wo, d_in[5], 4096, 1024, 2);
  map3d(enc, &fm.w1a, d_in[8], 1024, 3584, 2);
  map3d(enc, &fm.w1b, d_in[8], 1024, 3584, 3);
  map3d(enc, &fm.w2, d_in[10], 3584, 1024, 2);
  map2d(enc, &fm.x, x, 2048, 1024, 128);
  map2d(enc, &fm.out, d_out, 2048, 1024, 16);
  RecMaps rm = {};
  map2d(enc, &rm.wq, d_in[2], 1024, 4096, 128);
  map2d(enc, &rm.wk, d_in[3], 1024, 4096, 128);
  map2d(enc, &rm.wv, d_in[4], 1024, 4096, 16);
  map2d(enc, &rm.wo, d_in[5], 4096, 1024, 128);
  {
    void* ar = nullptr;
    cudaGetSymbolAddress(&ar, g_ar);
    cuuint64_t d[2] = {512, 160}, sd[1] = {1024};
    cuuint32_t bi[2] = {64, 40}, e[2] = {1, 1};
    enc(&rm.ari, CU_TENSOR_MAP_DATA_TYPE_BFLOAT16, 2, ar, d, sd, bi, e, CU_TENSOR_MAP_INTERLEAVE_NONE, CU_TENSOR_MAP_SWIZZLE_NONE,
        CU_TENSOR_MAP_L2_PROMOTION_NONE, CU_TENSOR_MAP_FLOAT_OOB_FILL_NONE);
  }
  cudaFuncSetAttribute(k_ffn, cudaFuncAttributeMaxDynamicSharedMemorySize, ffn::SMEM);
  cudaFuncSetAttribute(k_rec, cudaFuncAttributeMaxDynamicSharedMemorySize, rec::SMEM);
  char* xc = nullptr;
  cudaGetSymbolAddress((void**)&xc, g_xc);
  xc += (0 - (uintptr_t)xc) & 0x3FFFF;
  cudaStream_t st = cudaStreamPerThread;
  int dF = 450, dA = 2700, dS = 300, dM = 120, dG = 350, dP = 24, dX = 48, dD = 350, dZ = 0, dZ2 = 1, dV = 370, dX2 = 0;
  k_rec<<<132, 512, rec::SMEM, st>>>(rm, mem0, x, (const bf16*)d_in[12], (const bf16*)d_in[13], (const char*)d_in[8], (const bf16*)d_in[9],
                                     (const char*)d_in[5], xc, dF, dA, dS, dM, dG, dP, dX, dD, dZ, dZ2, dV, dX2);
  cudaLaunchConfig_t cfg = {};
  cfg.gridDim = dim3(132); cfg.blockDim = dim3(384); cfg.dynamicSmemBytes = ffn::SMEM; cfg.stream = st;
  cudaLaunchAttribute at[1];
  at[0].id = cudaLaunchAttributeProgrammaticStreamSerialization;
  at[0].val.programmaticStreamSerializationAllowed = 1;
  cfg.attrs = at; cfg.numAttrs = 1;
  cudaLaunchKernelEx(&cfg, k_ffn, fm, (const bf16*)d_in[11]);
}
```

```cpp
#include <cuda_runtime.h>
#include <cuda.h>
#include <cuda_bf16.h>
#include <stdint.h>

typedef __nv_bfloat16 bf16;

__device__ __align__(16) float g_mod[6144];
__device__ __align__(1024) uint4 g_modp[4 * 512];
__device__ unsigned g_hcnt;
__device__ unsigned g_hf[4];
__device__ __align__(1024) uint4 g_h[2048 * 1024 / 8];
__device__ __align__(1024) uint4 g_O[2048 * 4096 / 8];
__device__ __align__(1024) uint4 g_h2[2048 * 1024 / 8];
__device__ __align__(1024) uint4 g_U[2048 * 3584 / 8];
__device__ __align__(1024) uint4 g_stat[2048 * 4];
__device__ __align__(1024) unsigned g_cnt[16 * 4 * 32];
__device__ unsigned g_mcnt;
__device__ unsigned g_slot[256];
__device__ unsigned g_fin;
__device__ __align__(16) uint4 g_cc[224 * 4];
__device__ __align__(1024) uint4 g_xc[44 * 16384];
__device__ __align__(1024) unsigned g_tm[4 * 256];
#define FT(i)
#define FTP(i)
#define PT(i)
#define PH(i)
#define RP(i)
#define RPN(i, s)
#define TSV(i, v)
#define TS(i)

#define WIN 3
#define FRC "232"
#define FRP "40"
#define YR 1
#define XPK 0
#define NFA 1
#define PINM 1
#define FMAP (((g >> 2) * 4 + m) * 8 + (g & 3) * 2 + (blockIdx.x & 1))
#define FDB 0
#define ALIAS 3
#define EF 0
#define XPF 0
#define PFT 150000
#define PFS 104
#define PF0 13000
#define PFD 128
#define ARV 0
#define XDL 6
#define QW 0
#define PDS 61
#define P_NVR 5
#define P_NVP 2
#define P_NWP 9
#define P_NW1 7
#define RF_ 208
#define PSV 1
#define RA_ (488 - 2 * RF_)
#define XI 5
#define XL 1
#define WCH 2
#define HX 0
#define VB 1
#define TP 0
#define CKI 0
#define NOP_ 2
#define KVO 0
#define NDL 3
#define AM 0
#define XM 3
#define XP 0
#define SPIN_LIMIT (1 << 20)
__device__ __forceinline__ uint64_t mkdesc(uint32_t addr, uint32_t lbo, uint32_t sbo) {
  return (uint64_t)((addr & 0x3FFFF) >> 4) | ((uint64_t)(lbo >> 4) << 16) | ((uint64_t)(sbo >> 4) << 32) | (1ull << 62);
}
__device__ __forceinline__ void mbar_init(uint32_t a, int c) { asm volatile("mbarrier.init.shared.b64 [%0],%1;" ::"r"(a), "r"(c) : "memory"); }
__device__ __forceinline__ void mbar_wait(uint32_t a, uint32_t par) {
  asm volatile(
      "{.reg .pred p; .reg .u32 n;\n"
      "mov.u32 n, 0;\n"
      "W: mbarrier.try_wait.parity.shared.b64 p,[%0],%1;\n"
      "@p bra D;\n"
      "add.u32 n, n, 1;\n"
      "setp.lt.u32 p, n, %2;\n"
      "@p bra W;\n"
      "trap;\n"
      "D:}" ::"r"(a), "r"(par), "n"(SPIN_LIMIT) : "memory");
}
__device__ __forceinline__ void mbar_wait_q(uint32_t a, uint32_t par) {
  asm volatile(
      "{.reg .pred p; .reg .u32 n;\n"
      "mov.u32 n, 0;\n"
      "W: mbarrier.try_wait.parity.shared.b64 p,[%0],%1,4000;\n"
      "@p bra D;\n"
      "add.u32 n, n, 1;\n"
      "setp.lt.u32 p, n, %2;\n"
      "@p bra W;\n"
      "trap;\n"
      "D:}" ::"r"(a), "r"(par), "n"(SPIN_LIMIT / 16) : "memory");
}
__device__ __forceinline__ void mbar_expect(uint32_t a, uint32_t b) { asm volatile("mbarrier.arrive.expect_tx.shared.b64 _,[%0],%1;" ::"r"(a), "r"(b) : "memory"); }
__device__ __forceinline__ void mbar_arrive(uint32_t a) { asm volatile("mbarrier.arrive.shared.b64 _,[%0];" ::"r"(a) : "memory"); }
__device__ __forceinline__ uint32_t mapa(uint32_t a, uint32_t cta) { uint32_t r; asm("mapa.shared::cluster.u32 %0,%1,%2;" : "=r"(r) : "r"(a), "r"(cta)); return r; }
__device__ __forceinline__ void mbar_arrive_cl(uint32_t a) { asm volatile("mbarrier.arrive.shared::cluster.b64 _,[%0];" ::"r"(a) : "memory"); }
__device__ __forceinline__ void tma2d(uint32_t dst, const CUtensorMap* m, int c0, int c1, uint32_t mb) {
  asm volatile("cp.async.bulk.tensor.2d.shared::cluster.global.mbarrier::complete_tx::bytes [%0],[%1,{%2,%3}],[%4];" ::"r"(dst), "l"(m), "r"(c0), "r"(c1), "r"(mb) : "memory");
}
__device__ __forceinline__ void tma2d_pf(const CUtensorMap* m, int c0, int c1) {
  asm volatile("cp.async.bulk.prefetch.tensor.2d.L2.global [%0,{%1,%2}];" ::"l"(m), "r"(c0), "r"(c1) : "memory");
}
__device__ __forceinline__ void tma3d(uint32_t dst, const CUtensorMap* m, int c1, int c2, uint32_t mb) {
  asm volatile("cp.async.bulk.tensor.3d.shared::cluster.global.mbarrier::complete_tx::bytes [%0],[%1,{0,%2,%3}],[%4];" ::"r"(dst), "l"(m), "r"(c1), "r"(c2), "r"(mb) : "memory");
}
__device__ __forceinline__ void tma2d_st(const CUtensorMap* m, int c0, int c1, uint32_t src) {
  asm volatile("cp.async.bulk.tensor.2d.global.shared::cta.bulk_group [%0,{%1,%2}],[%3];" ::"l"(m), "r"(c0), "r"(c1), "r"(src) : "memory");
}
__device__ __forceinline__ void bulk_ld(uint32_t dst, const void* src, uint32_t n, uint32_t mb) {
  asm volatile("cp.async.bulk.shared::cluster.global.mbarrier::complete_tx::bytes [%0],[%1],%2,[%3];" ::"r"(dst), "l"(src), "r"(n), "r"(mb) : "memory");
}
__device__ __forceinline__ void bulk_ld_mc(uint32_t dst, const void* src, uint32_t n, uint32_t mb) {
  asm volatile("cp.async.bulk.shared::cluster.global.mbarrier::complete_tx::bytes.multicast::cluster [%0],[%1],%2,[%3],%4;" ::"r"(dst), "l"(src), "r"(n), "r"(mb), "h"((uint16_t)3) : "memory");
}
__device__ __forceinline__ void bulk_st(void* dst, uint32_t src, uint32_t n) {
  asm volatile("cp.async.bulk.global.shared::cta.bulk_group [%0],[%1],%2;" ::"l"(dst), "r"(src), "r"(n) : "memory");
}
__device__ __forceinline__ void e_expect_tma3d(uint32_t dst, const CUtensorMap* m, int c1, int c2, uint32_t mb, uint32_t bytes) {
  asm volatile("{.reg .pred p; elect.sync _|p, 0xffffffff; @p mbarrier.arrive.expect_tx.shared.b64 _,[%4],%5;\n"
               "@p cp.async.bulk.tensor.3d.shared::cluster.global.mbarrier::complete_tx::bytes [%0],[%1,{0,%2,%3}],[%4];}" ::"r"(dst), "l"(m), "r"(c1), "r"(c2), "r"(mb), "r"(bytes) : "memory");
}
__device__ __forceinline__ void e_bulk_ld(uint32_t dst, const void* src, uint32_t n, uint32_t mb) {
  asm volatile("{.reg .pred p; elect.sync _|p, 0xffffffff; @p cp.async.bulk.shared::cluster.global.mbarrier::complete_tx::bytes [%0],[%1],%2,[%3];}" ::"r"(dst), "l"(src), "r"(n), "r"(mb) : "memory");
}
__device__ __forceinline__ void e_bulk_ld_ef(uint32_t dst, const void* src, uint32_t n, uint32_t mb) {
  asm volatile("{.reg .pred p; .reg .b64 c; createpolicy.fractional.L2::evict_first.b64 c,1.0; elect.sync _|p, 0xffffffff;"
               " @p cp.async.bulk.shared::cluster.global.mbarrier::complete_tx::bytes.L2::cache_hint [%0],[%1],%2,[%3],c;}" ::"r"(dst), "l"(src), "r"(n), "r"(mb) : "memory");
}
__device__ __forceinline__ void e_bulk_ld_mc(uint32_t dst, const void* src, uint32_t n, uint32_t mb) {
  asm volatile("{.reg .pred p; elect.sync _|p, 0xffffffff; @p cp.async.bulk.shared::cluster.global.mbarrier::complete_tx::bytes.multicast::cluster [%0],[%1],%2,[%3],%4;}" ::"r"(dst), "l"(src), "r"(n), "r"(mb), "h"((uint16_t)3) : "memory");
}
#define BULK_COMMIT() asm volatile("cp.async.bulk.commit_group;" ::: "memory")
#define BULK_WAIT_READ(n) asm volatile("cp.async.bulk.wait_group.read " #n ";" ::: "memory")
#define BULK_WAIT(n) asm volatile("cp.async.bulk.wait_group " #n ";" ::: "memory")
#define FENCE_ASYNC_SMEM() asm volatile("fence.proxy.async.shared::cta;" ::: "memory")
#define FENCE_ASYNC() asm volatile("fence.proxy.async;" ::: "memory")
#define WG_FENCE() asm volatile("wgmma.fence.sync.aligned;" ::: "memory")
#define WG_COMMIT() asm volatile("wgmma.commit_group.sync.aligned;" ::: "memory")
#define WG_WAIT(n) asm volatile("wgmma.wait_group.sync.aligned " #n ";" ::: "memory")
#define BAR_SYNC(id, n) asm volatile("bar.sync %0,%1;" ::"n"(id), "n"(n) : "memory")
#define BAR_ARRIVE(id, n) asm volatile("bar.arrive %0,%1;" ::"n"(id), "n"(n) : "memory")
#define SCHED_FENCE(k) asm volatile("{.reg .pred p; setp.ne.u32 p,%0,0; @p trap;}" ::"r"(mp.zero[(k) - 46]) : "memory")
#define CLUSTER_SYNC() asm volatile("barrier.cluster.arrive.relaxed.aligned; barrier.cluster.wait.aligned;" ::: "memory")
__device__ __forceinline__ uint32_t pk(float lo, float hi) { uint32_t r; asm("cvt.rn.bf16x2.f32 %0,%1,%2;" : "=r"(r) : "f"(hi), "f"(lo)); return r; }
__device__ __forceinline__ float blo(uint32_t v) { return __uint_as_float(v << 16); }
__device__ __forceinline__ float bhi(uint32_t v) { return __uint_as_float(v & 0xffff0000u); }
__device__ __forceinline__ void ldsm4(uint32_t* r, uint32_t a) {
  asm volatile("ldmatrix.sync.aligned.m8n8.x4.shared.b16 {%0,%1,%2,%3},[%4];" : "=r"(r[0]), "=r"(r[1]), "=r"(r[2]), "=r"(r[3]) : "r"(a) : "memory");
}
__device__ __forceinline__ void ldsm4t(uint32_t* r, uint32_t a) {
  asm volatile("ldmatrix.sync.aligned.m8n8.x4.trans.shared.b16 {%0,%1,%2,%3},[%4];" : "=r"(r[0]), "=r"(r[1]), "=r"(r[2]), "=r"(r[3]) : "r"(a) : "memory");
}
__device__ __forceinline__ void stsm4(uint32_t a, uint32_t r0, uint32_t r1, uint32_t r2, uint32_t r3) {
  asm volatile("stmatrix.sync.aligned.m8n8.x4.shared.b16 [%0],{%1,%2,%3,%4};" ::"r"(a), "r"(r0), "r"(r1), "r"(r2), "r"(r3) : "memory");
}
__device__ __forceinline__ void mma16(float* d, uint32_t a0, uint32_t a1, uint32_t a2, uint32_t a3, uint32_t b0, uint32_t b1) {
  asm volatile("mma.sync.aligned.m16n8k16.row.col.f32.bf16.bf16.f32 {%0,%1,%2,%3},{%4,%5,%6,%7},{%8,%9},{%0,%1,%2,%3};"
               : "+f"(d[0]), "+f"(d[1]), "+f"(d[2]), "+f"(d[3]) : "r"(a0), "r"(a1), "r"(a2), "r"(a3), "r"(b0), "r"(b1));
}
__device__ __forceinline__ void mma8(float* d, uint32_t a0, uint32_t a1, uint32_t b0) {
  asm volatile("mma.sync.aligned.m16n8k8.row.col.f32.bf16.bf16.f32 {%0,%1,%2,%3},{%4,%5},{%6},{%0,%1,%2,%3};"
               : "+f"(d[0]), "+f"(d[1]), "+f"(d[2]), "+f"(d[3]) : "r"(a0), "r"(a1), "r"(b0));
}
__device__ __forceinline__ float4 lds4f(uint32_t a) { float4 v; asm volatile("ld.shared.v4.f32 {%0,%1,%2,%3},[%4];" : "=f"(v.x), "=f"(v.y), "=f"(v.z), "=f"(v.w) : "r"(a) : "memory"); return v; }
__device__ __forceinline__ float2 lds2f(uint32_t a) { float2 v; asm volatile("ld.shared.v2.f32 {%0,%1},[%2];" : "=f"(v.x), "=f"(v.y) : "r"(a) : "memory"); return v; }
__device__ __forceinline__ uint4 lds4(uint32_t a) { uint4 v; asm volatile("ld.shared.v4.u32 {%0,%1,%2,%3},[%4];" : "=r"(v.x), "=r"(v.y), "=r"(v.z), "=r"(v.w) : "r"(a) : "memory"); return v; }
__device__ __forceinline__ uint2 lds2u(uint32_t a) { uint2 v; asm volatile("ld.shared.v2.u32 {%0,%1},[%2];" : "=r"(v.x), "=r"(v.y) : "r"(a) : "memory"); return v; }
__device__ __forceinline__ uint32_t lds1(uint32_t a) { uint32_t v; asm volatile("ld.shared.u32 %0,[%1];" : "=r"(v) : "r"(a) : "memory"); return v; }
__device__ __forceinline__ void sts4(uint32_t a, uint32_t x, uint32_t y, uint32_t z, uint32_t w) { asm volatile("st.shared.v4.u32 [%0],{%1,%2,%3,%4};" ::"r"(a), "r"(x), "r"(y), "r"(z), "r"(w) : "memory"); }
__device__ __forceinline__ void sts2(uint32_t a, uint32_t x, uint32_t y) { asm volatile("st.shared.v2.u32 [%0],{%1,%2};" ::"r"(a), "r"(x), "r"(y) : "memory"); }
__device__ __forceinline__ void sts1(uint32_t a, uint32_t x) { asm volatile("st.shared.u32 [%0],%1;" ::"r"(a), "r"(x) : "memory"); }
__device__ __forceinline__ void sta4(uint32_t a, const uint32_t* v, uint32_t mb) {
  asm volatile("st.async.shared::cluster.mbarrier::complete_tx::bytes.v4.b32 [%0],{%1,%2,%3,%4},[%5];" ::"r"(a), "r"(v[0]), "r"(v[1]), "r"(v[2]), "r"(v[3]), "r"(mb) : "memory");
}
__device__ __forceinline__ uint4 ldg_rlx4(const void* p) { uint4 v; asm volatile("ld.relaxed.gpu.global.v4.u32 {%0,%1,%2,%3},[%4];" : "=r"(v.x), "=r"(v.y), "=r"(v.z), "=r"(v.w) : "l"(p) : "memory"); return v; }
__device__ __forceinline__ uint32_t ldg_rlx1(const void* p) { uint32_t v; asm volatile("ld.relaxed.gpu.global.u32 %0,[%1];" : "=r"(v) : "l"(p) : "memory"); return v; }
__device__ __forceinline__ uint2 ldg_rlx2(const void* p) { uint2 v; asm volatile("ld.relaxed.gpu.global.v2.u32 {%0,%1},[%2];" : "=r"(v.x), "=r"(v.y) : "l"(p) : "memory"); return v; }
__device__ __forceinline__ uint4 ldg_b128(const void* p) {
  uint4 v;
  asm volatile("{.reg .b128 t; .reg .b64 a,b; ld.relaxed.gpu.global.b128 t,[%4]; mov.b128 {a,b},t; mov.b64 {%0,%1},a; mov.b64 {%2,%3},b;}" : "=r"(v.x), "=r"(v.y), "=r"(v.z), "=r"(v.w) : "l"(p) : "memory");
  return v;
}
__device__ __forceinline__ void stg_b128(void* p, uint32_t x, uint32_t y, uint32_t z, uint32_t w) {
  asm volatile("{.reg .b128 t; .reg .b64 a,b; mov.b64 a,{%1,%2}; mov.b64 b,{%3,%4}; mov.b128 t,{a,b}; st.relaxed.gpu.global.b128 [%0],t;}" ::"l"(p), "r"(x), "r"(y), "r"(z), "r"(w) : "memory");
}
__device__ __forceinline__ void st_b128(void* p, uint32_t x, uint32_t y, uint32_t z, uint32_t w) {
  asm volatile("{.reg .b128 t; .reg .b64 a,b; mov.b64 a,{%1,%2}; mov.b64 b,{%3,%4}; mov.b128 t,{a,b}; st.relaxed.gpu.b128 [%0],t;}" ::"l"(p), "r"(x), "r"(y), "r"(z), "r"(w) : "memory");
}
__device__ __forceinline__ void stg_rlx4(void* p, uint32_t x, uint32_t y, uint32_t z, uint32_t w) { asm volatile("st.relaxed.gpu.global.v4.u32 [%0],{%1,%2,%3,%4};" ::"l"(p), "r"(x), "r"(y), "r"(z), "r"(w) : "memory"); }
__device__ __forceinline__ void stg_rlx2(void* p, uint32_t x, uint32_t y) { asm volatile("st.relaxed.gpu.global.v2.u32 [%0],{%1,%2};" ::"l"(p), "r"(x), "r"(y) : "memory"); }
__device__ __forceinline__ void red4(void* p, float a, float b, float c, float d) { asm volatile("red.relaxed.gpu.global.add.v4.f32 [%0],{%1,%2,%3,%4};" ::"l"(p), "f"(a), "f"(b), "f"(c), "f"(d) : "memory"); }
__device__ __forceinline__ unsigned ld_acq(const unsigned* p) { unsigned v; asm volatile("ld.acquire.gpu.global.u32 %0,[%1];" : "=r"(v) : "l"(p) : "memory"); return v; }
__device__ __forceinline__ void red_rel(unsigned* p) { asm volatile("red.release.gpu.global.add.u32 [%0],1;" ::"l"(p) : "memory"); }
__device__ __forceinline__ void red_rlx(unsigned* p) { asm volatile("red.relaxed.gpu.global.add.u32 [%0],1;" ::"l"(p) : "memory"); }
__device__ __forceinline__ void wait_cnt(const unsigned* p, unsigned n) { int it = 0; while (ld_acq(p) < n) { if (++it > SPIN_LIMIT) __trap(); } }
__device__ __forceinline__ uint32_t clk() { uint32_t c; asm volatile("mov.u32 %0,%%clock;" : "=r"(c)); return c; }
__device__ __forceinline__ uint32_t gtime() { uint32_t c; asm volatile("mov.u32 %0,%%globaltimer_lo;" : "=r"(c)); return c; }
__device__ __forceinline__ void wait_until(uint32_t t0, uint32_t d) { while (clk() - t0 < d) {} }
__device__ __forceinline__ float ex2(float x) { float r; asm("ex2.approx.ftz.f32 %0,%1;" : "=f"(r) : "f"(x)); return r; }
__device__ __forceinline__ float silu(float x) { return x * __frcp_rn(1.f + __expf(-x)); }
__device__ __forceinline__ float rbf(float x) { return __bfloat162float(__float2bfloat16_rn(x)); }

__device__ __forceinline__ void wgmma_ss_n128(float* d, uint64_t a, uint64_t b, int sd) {
  asm volatile("{.reg .pred p; setp.ne.b32 p, %66, 0;\n"
    "wgmma.mma_async.sync.aligned.m64n128k16.f32.bf16.bf16 {%0,%1,%2,%3,%4,%5,%6,%7,%8,%9,%10,%11,%12,%13,%14,%15,%16,%17,%18,%19,%20,%21,%22,%23,%24,%25,%26,%27,%28,%29,%30,%31,%32,%33,%34,%35,%36,%37,%38,%39,%40,%41,%42,%43,%44,%45,%46,%47,%48,%49,%50,%51,%52,%53,%54,%55,%56,%57,%58,%59,%60,%61,%62,%63}, %64, %65, p, 1, 1, 0, 1;}\n"
    : "+f"(d[0]),"+f"(d[1]),"+f"(d[2]),"+f"(d[3]),"+f"(d[4]),"+f"(d[5]),"+f"(d[6]),"+f"(d[7]),
      "+f"(d[8]),"+f"(d[9]),"+f"(d[10]),"+f"(d[11]),"+f"(d[12]),"+f"(d[13]),"+f"(d[14]),"+f"(d[15]),
      "+f"(d[16]),"+f"(d[17]),"+f"(d[18]),"+f"(d[19]),"+f"(d[20]),"+f"(d[21]),"+f"(d[22]),"+f"(d[23]),
      "+f"(d[24]),"+f"(d[25]),"+f"(d[26]),"+f"(d[27]),"+f"(d[28]),"+f"(d[29]),"+f"(d[30]),"+f"(d[31]),
      "+f"(d[32]),"+f"(d[33]),"+f"(d[34]),"+f"(d[35]),"+f"(d[36]),"+f"(d[37]),"+f"(d[38]),"+f"(d[39]),
      "+f"(d[40]),"+f"(d[41]),"+f"(d[42]),"+f"(d[43]),"+f"(d[44]),"+f"(d[45]),"+f"(d[46]),"+f"(d[47]),
      "+f"(d[48]),"+f"(d[49]),"+f"(d[50]),"+f"(d[51]),"+f"(d[52]),"+f"(d[53]),"+f"(d[54]),"+f"(d[55]),
      "+f"(d[56]),"+f"(d[57]),"+f"(d[58]),"+f"(d[59]),"+f"(d[60]),"+f"(d[61]),"+f"(d[62]),"+f"(d[63])
    : "l"(a), "l"(b), "r"(sd));
}
__device__ __forceinline__ void wgmma_ss_n192(float* d, uint64_t a, uint64_t b, int sd) {
  asm volatile("{.reg .pred p; setp.ne.b32 p, %98, 0;\n"
    "wgmma.mma_async.sync.aligned.m64n192k16.f32.bf16.bf16 {%0,%1,%2,%3,%4,%5,%6,%7,%8,%9,%10,%11,%12,%13,%14,%15,%16,%17,%18,%19,%20,%21,%22,%23,%24,%25,%26,%27,%28,%29,%30,%31,%32,%33,%34,%35,%36,%37,%38,%39,%40,%41,%42,%43,%44,%45,%46,%47,%48,%49,%50,%51,%52,%53,%54,%55,%56,%57,%58,%59,%60,%61,%62,%63,%64,%65,%66,%67,%68,%69,%70,%71,%72,%73,%74,%75,%76,%77,%78,%79,%80,%81,%82,%83,%84,%85,%86,%87,%88,%89,%90,%91,%92,%93,%94,%95}, %96, %97, p, 1, 1, 0, 1;}\n"
    : "+f"(d[0]),"+f"(d[1]),"+f"(d[2]),"+f"(d[3]),"+f"(d[4]),"+f"(d[5]),"+f"(d[6]),"+f"(d[7]),
      "+f"(d[8]),"+f"(d[9]),"+f"(d[10]),"+f"(d[11]),"+f"(d[12]),"+f"(d[13]),"+f"(d[14]),"+f"(d[15]),
      "+f"(d[16]),"+f"(d[17]),"+f"(d[18]),"+f"(d[19]),"+f"(d[20]),"+f"(d[21]),"+f"(d[22]),"+f"(d[23]),
      "+f"(d[24]),"+f"(d[25]),"+f"(d[26]),"+f"(d[27]),"+f"(d[28]),"+f"(d[29]),"+f"(d[30]),"+f"(d[31]),
      "+f"(d[32]),"+f"(d[33]),"+f"(d[34]),"+f"(d[35]),"+f"(d[36]),"+f"(d[37]),"+f"(d[38]),"+f"(d[39]),
      "+f"(d[40]),"+f"(d[41]),"+f"(d[42]),"+f"(d[43]),"+f"(d[44]),"+f"(d[45]),"+f"(d[46]),"+f"(d[47]),
      "+f"(d[48]),"+f"(d[49]),"+f"(d[50]),"+f"(d[51]),"+f"(d[52]),"+f"(d[53]),"+f"(d[54]),"+f"(d[55]),
      "+f"(d[56]),"+f"(d[57]),"+f"(d[58]),"+f"(d[59]),"+f"(d[60]),"+f"(d[61]),"+f"(d[62]),"+f"(d[63]),
      "+f"(d[64]),"+f"(d[65]),"+f"(d[66]),"+f"(d[67]),"+f"(d[68]),"+f"(d[69]),"+f"(d[70]),"+f"(d[71]),
      "+f"(d[72]),"+f"(d[73]),"+f"(d[74]),"+f"(d[75]),"+f"(d[76]),"+f"(d[77]),"+f"(d[78]),"+f"(d[79]),
      "+f"(d[80]),"+f"(d[81]),"+f"(d[82]),"+f"(d[83]),"+f"(d[84]),"+f"(d[85]),"+f"(d[86]),"+f"(d[87]),
      "+f"(d[88]),"+f"(d[89]),"+f"(d[90]),"+f"(d[91]),"+f"(d[92]),"+f"(d[93]),"+f"(d[94]),"+f"(d[95])
    : "l"(a), "l"(b), "r"(sd));
}
__device__ __forceinline__ void wgmma_ss_n256(float* d, uint64_t a, uint64_t b, int sd) {
  asm volatile("{.reg .pred p; setp.ne.b32 p, %130, 0;\n"
    "wgmma.mma_async.sync.aligned.m64n256k16.f32.bf16.bf16 {%0,%1,%2,%3,%4,%5,%6,%7,%8,%9,%10,%11,%12,%13,%14,%15,%16,%17,%18,%19,%20,%21,%22,%23,%24,%25,%26,%27,%28,%29,%30,%31,%32,%33,%34,%35,%36,%37,%38,%39,%40,%41,%42,%43,%44,%45,%46,%47,%48,%49,%50,%51,%52,%53,%54,%55,%56,%57,%58,%59,%60,%61,%62,%63,%64,%65,%66,%67,%68,%69,%70,%71,%72,%73,%74,%75,%76,%77,%78,%79,%80,%81,%82,%83,%84,%85,%86,%87,%88,%89,%90,%91,%92,%93,%94,%95,%96,%97,%98,%99,%100,%101,%102,%103,%104,%105,%106,%107,%108,%109,%110,%111,%112,%113,%114,%115,%116,%117,%118,%119,%120,%121,%122,%123,%124,%125,%126,%127}, %128, %129, p, 1, 1, 0, 1;}\n"
    : "+f"(d[0]),"+f"(d[1]),"+f"(d[2]),"+f"(d[3]),"+f"(d[4]),"+f"(d[5]),"+f"(d[6]),"+f"(d[7]),
      "+f"(d[8]),"+f"(d[9]),"+f"(d[10]),"+f"(d[11]),"+f"(d[12]),"+f"(d[13]),"+f"(d[14]),"+f"(d[15]),
      "+f"(d[16]),"+f"(d[17]),"+f"(d[18]),"+f"(d[19]),"+f"(d[20]),"+f"(d[21]),"+f"(d[22]),"+f"(d[23]),
      "+f"(d[24]),"+f"(d[25]),"+f"(d[26]),"+f"(d[27]),"+f"(d[28]),"+f"(d[29]),"+f"(d[30]),"+f"(d[31]),
      "+f"(d[32]),"+f"(d[33]),"+f"(d[34]),"+f"(d[35]),"+f"(d[36]),"+f"(d[37]),"+f"(d[38]),"+f"(d[39]),
      "+f"(d[40]),"+f"(d[41]),"+f"(d[42]),"+f"(d[43]),"+f"(d[44]),"+f"(d[45]),"+f"(d[46]),"+f"(d[47]),
      "+f"(d[48]),"+f"(d[49]),"+f"(d[50]),"+f"(d[51]),"+f"(d[52]),"+f"(d[53]),"+f"(d[54]),"+f"(d[55]),
      "+f"(d[56]),"+f"(d[57]),"+f"(d[58]),"+f"(d[59]),"+f"(d[60]),"+f"(d[61]),"+f"(d[62]),"+f"(d[63]),
      "+f"(d[64]),"+f"(d[65]),"+f"(d[66]),"+f"(d[67]),"+f"(d[68]),"+f"(d[69]),"+f"(d[70]),"+f"(d[71]),
      "+f"(d[72]),"+f"(d[73]),"+f"(d[74]),"+f"(d[75]),"+f"(d[76]),"+f"(d[77]),"+f"(d[78]),"+f"(d[79]),
      "+f"(d[80]),"+f"(d[81]),"+f"(d[82]),"+f"(d[83]),"+f"(d[84]),"+f"(d[85]),"+f"(d[86]),"+f"(d[87]),
      "+f"(d[88]),"+f"(d[89]),"+f"(d[90]),"+f"(d[91]),"+f"(d[92]),"+f"(d[93]),"+f"(d[94]),"+f"(d[95]),
      "+f"(d[96]),"+f"(d[97]),"+f"(d[98]),"+f"(d[99]),"+f"(d[100]),"+f"(d[101]),"+f"(d[102]),"+f"(d[103]),
      "+f"(d[104]),"+f"(d[105]),"+f"(d[106]),"+f"(d[107]),"+f"(d[108]),"+f"(d[109]),"+f"(d[110]),"+f"(d[111]),
      "+f"(d[112]),"+f"(d[113]),"+f"(d[114]),"+f"(d[115]),"+f"(d[116]),"+f"(d[117]),"+f"(d[118]),"+f"(d[119]),
      "+f"(d[120]),"+f"(d[121]),"+f"(d[122]),"+f"(d[123]),"+f"(d[124]),"+f"(d[125]),"+f"(d[126]),"+f"(d[127])
    : "l"(a), "l"(b), "r"(sd));
}
__device__ __forceinline__ void wgmma_rs_n32(float* d, const uint32_t* a, uint64_t b, int sd) {
  asm volatile("{.reg .pred p; setp.ne.b32 p, %21, 0;\n"
    "wgmma.mma_async.sync.aligned.m64n32k16.f32.bf16.bf16 {%0,%1,%2,%3,%4,%5,%6,%7,%8,%9,%10,%11,%12,%13,%14,%15}, {%16,%17,%18,%19}, %20, p, 1, 1, 0;}\n"
    : "+f"(d[0]),"+f"(d[1]),"+f"(d[2]),"+f"(d[3]),"+f"(d[4]),"+f"(d[5]),"+f"(d[6]),"+f"(d[7]),
      "+f"(d[8]),"+f"(d[9]),"+f"(d[10]),"+f"(d[11]),"+f"(d[12]),"+f"(d[13]),"+f"(d[14]),"+f"(d[15])
    : "r"(a[0]), "r"(a[1]), "r"(a[2]), "r"(a[3]), "l"(b), "r"(sd));
}
__device__ __forceinline__ void wgmma_ssT_n32(float* d, uint64_t a, uint64_t b, int sd) {
  asm volatile("{.reg .pred p; setp.ne.b32 p, %18, 0;\n"
    "wgmma.mma_async.sync.aligned.m64n32k16.f32.bf16.bf16 {%0,%1,%2,%3,%4,%5,%6,%7,%8,%9,%10,%11,%12,%13,%14,%15}, %16, %17, p, 1, 1, 1, 0;}\n"
    : "+f"(d[0]),"+f"(d[1]),"+f"(d[2]),"+f"(d[3]),"+f"(d[4]),"+f"(d[5]),"+f"(d[6]),"+f"(d[7]),
      "+f"(d[8]),"+f"(d[9]),"+f"(d[10]),"+f"(d[11]),"+f"(d[12]),"+f"(d[13]),"+f"(d[14]),"+f"(d[15])
    : "l"(a), "l"(b), "r"(sd));
}

__device__ __forceinline__ void wgmma_rs_n32_z(float* d, const uint32_t* a, uint64_t b) {
  asm volatile("{.reg .pred p; setp.ne.b32 p, 0, 0;\n"
    "wgmma.mma_async.sync.aligned.m64n32k16.f32.bf16.bf16 {%0,%1,%2,%3,%4,%5,%6,%7,%8,%9,%10,%11,%12,%13,%14,%15}, {%16,%17,%18,%19}, %20, p, 1, 1, 0;}\n"
    : "=f"(d[0]),"=f"(d[1]),"=f"(d[2]),"=f"(d[3]),"=f"(d[4]),"=f"(d[5]),"=f"(d[6]),"=f"(d[7]),
      "=f"(d[8]),"=f"(d[9]),"=f"(d[10]),"=f"(d[11]),"=f"(d[12]),"=f"(d[13]),"=f"(d[14]),"=f"(d[15])
    : "r"(a[0]), "r"(a[1]), "r"(a[2]), "r"(a[3]), "l"(b));
}

namespace rec {
constexpr int NVR = P_NVR;
constexpr int NVS = 16 - NVR;
constexpr int NVP = P_NVP;
constexpr int NWP = P_NWP;
constexpr uint32_t WO = 0;
constexpr uint32_t XB = 65536;
constexpr uint32_t PK = XB + 32768;
constexpr uint32_t VN = PK + 24576;
constexpr uint32_t VX0 = VN + 4096;
constexpr uint32_t WVS = 131072;
constexpr uint32_t MEM = WVS + 2 * NVS * 2048;
constexpr uint32_t ARO = MEM + 10240;
constexpr uint32_t OB = ARO + 5120;
constexpr uint32_t QT = OB + 2048;
constexpr uint32_t KT = QT + 2048;
constexpr uint32_t RQ = KT + 6144;
constexpr uint32_t RK = RQ + 2048;
constexpr uint32_t SC = RK + 2048;
constexpr uint32_t OT = OB;
constexpr uint32_t TF = SC + 2048;
constexpr uint32_t PRE = MEM + 2 * NVR * 2048;
constexpr uint32_t TA = TF + 8192;
constexpr uint32_t RX = TA + 6144;
constexpr uint32_t VX1 = RX + 2048;
constexpr uint32_t BARS = VX1 + 4096;
constexpr uint32_t PACE = BARS + 18 * 8;
constexpr uint32_t SMEM = BARS + 512;
static_assert(PRE + 14336 <= BARS, "staging");
constexpr int NW1 = P_NW1;
static_assert(SMEM <= 232448, "smem");
constexpr int B_E = 2, B_SC = 3, B_S = 4, B_O = 5, B_F = 6, B_W = 7, B_C = 9, B_K = 10, B_H = 15, B_Q = 1, B_S2 = 6, B_T2 = 9, B_P = 13, B_T = 14, B_R = 11, B_X = 12, B_V = 8;
constexpr int XC = 16384, X_RING = 131072, X_SC = 65536, X_TOK = 4096;
#define X_VX(i) (((i) >> 1) * 2048 + ((i) & 1) * 512)
#define X_VM(i) (X_VX(i) + 1024)
#define V_RING(n) (((n) & 1) * X_RING + ((n) & 2) * 2048)
#define V_TAG(n) ((~(n) >> 2) & 1)
}
struct RecMaps { CUtensorMap wq, wk, wv, wo, ari; int zero[40]; };

#define F_(x) __uint_as_float(x)
#define U_(x) __float_as_uint(x)
#define AR_R(q) (24 + ((q) & 1) * 16 + ((q) >> 1) * 56)
#define AR_P(q) ((q) >> 1)
#define AR_ROW(i) (24 + ((i) & 1) * 16 + ((i) & 2) * 92 + (((i) >> 2) & 7) + ((i) >> 5) * 128)
constexpr size_t AR_OFF = 32 * 262144;
__device__ __forceinline__ void ar_fetch(uint32_t dst, const CUtensorMap* m, int slot, int half, uint32_t mb) {
  asm volatile("{.reg .pred p; elect.sync _|p, 0xffffffff; @p mbarrier.arrive.expect_tx.shared.b64 _,[%4],10240;\n"
               "@p cp.async.bulk.tensor.3d.shared::cluster.global.mbarrier::complete_tx::bytes [%0],[%1,{%2,%3,%6}],[%4];\n"
               "@p cp.async.bulk.tensor.3d.shared::cluster.global.mbarrier::complete_tx::bytes [%0+5120],[%1,{%2,%5,%7}],[%4];}"
               ::"r"(dst), "l"(m), "r"(slot * 64), "r"(AR_R(half * 2)), "r"(mb), "r"(AR_R(half * 2 + 1)), "r"(AR_P(half * 2)), "r"(AR_P(half * 2 + 1)) : "memory");
}
__device__ __forceinline__ uint4 exch_b128(void* p, uint32_t x, uint32_t y, uint32_t z, uint32_t w) {
  uint4 v;
  asm volatile("{.reg .b128 s, t; .reg .b64 a,b; mov.b64 a,{%5,%6}; mov.b64 b,{%7,%8}; mov.b128 s,{a,b}; atom.relaxed.gpu.global.exch.b128 t,[%4],s;"
               " mov.b128 {a,b},t; mov.b64 {%0,%1},a; mov.b64 {%2,%3},b;}" : "=r"(v.x), "=r"(v.y), "=r"(v.z), "=r"(v.w) : "l"(p), "r"(x), "r"(y), "r"(z), "r"(w) : "memory");
  return v;
}
#define CONSUME(v) do { if ((v) == 0x7fc12345u) sts1(sb + rec::BARS + 96, 0); } while (0)
__device__ __forceinline__ uint32_t tagf(float v, uint32_t tag) { return (__float_as_uint(v) & ~1u) | tag; }
__device__ __forceinline__ uint2 ldg_b64(const void* p) { uint2 v; asm volatile("{.reg .b64 t; ld.relaxed.gpu.global.b64 t,[%2]; mov.b64 {%0,%1},t;}" : "=r"(v.x), "=r"(v.y) : "l"(p) : "memory"); return v; }
__device__ __forceinline__ void stg_b64(void* p, uint32_t x, uint32_t y) { asm volatile("{.reg .b64 t; mov.b64 t,{%1,%2}; st.relaxed.gpu.global.b64 [%0],t;}" ::"l"(p), "r"(x), "r"(y) : "memory"); }
__device__ __forceinline__ uint32_t tagbad(uint32_t x, uint32_t y, uint32_t tag) { uint32_t r; asm("lop3.b32 %0,%1,%2,%3,0x7e;" : "=r"(r) : "r"(x), "r"(y), "r"(tag)); return r; }

__device__ __forceinline__ bool anybad(uint32_t a, uint32_t b, uint32_t c, uint32_t d, uint32_t e, uint32_t f, uint32_t g, uint32_t h, uint32_t tag) {
  uint32_t r;
  asm volatile("{.reg .b32 t,u,v,w; .reg .pred p; lop3.b32 t,%1,%2,%9,0x7e; lop3.b32 u,%3,%4,%9,0x7e; lop3.b32 v,%5,%6,%9,0x7e; lop3.b32 w,%7,%8,%9,0x7e;"
               " lop3.b32 t,t,u,v,0xfe; lop3.b32 t,t,w,1,0xa8; setp.ne.u32 p,t,0; vote.sync.any.pred p,p,0xffffffff; selp.u32 %0,1,0,p;}"
               : "=r"(r) : "r"(a), "r"(b), "r"(c), "r"(d), "r"(e), "r"(f), "r"(g), "r"(h), "r"(tag));
  return r;
}
__device__ __forceinline__ bool anybad(uint32_t a, uint32_t b, uint32_t c, uint32_t d, uint32_t tag) {
  uint32_t r;
  asm volatile("{.reg .b32 t,u; .reg .pred p; lop3.b32 t,%1,%2,%5,0x7e; lop3.b32 u,%3,%4,%5,0x7e;"
               " lop3.b32 t,t,u,1,0xa8; setp.ne.u32 p,t,0; vote.sync.any.pred p,p,0xffffffff; selp.u32 %0,1,0,p;}"
               : "=r"(r) : "r"(a), "r"(b), "r"(c), "r"(d), "r"(tag));
  return r;
}
#define BAD8(r) anybad(r[0].x, r[0].z, r[1].x, r[1].z, r[2].x, r[2].z, r[3].x, r[3].z, tag)
#define BADS(r) anybad(r[0].x, r[0].y, r[1].x, r[1].y, r[2].x, r[2].y, r[3].x, r[3].y, tag)
constexpr float SCS = 0.08838834764831845f * 1.4426950408889634f / 16.f;
__device__ __forceinline__ uint32_t pkh(float lo, float hi, uint32_t tag) {
  uint32_t r;
  asm("{.reg .b32 t; cvt.rn.satfinite.f16x2.f32 t,%1,%2; lop3.b32 %0,t,0xfffffffe,%3,0xea;}" : "=r"(r) : "f"(hi), "f"(lo), "r"(tag));
  return r;
}
__device__ __forceinline__ uint32_t addh(uint32_t a, uint32_t b) { uint32_t r; asm("add.rn.f16x2 %0,%1,%2;" : "=r"(r) : "r"(a), "r"(b)); return r; }
__device__ __forceinline__ float hlo(uint32_t v) { float r; asm("{.reg .b16 a,b; mov.b32 {a,b},%1; cvt.f32.f16 %0,a;}" : "=f"(r) : "r"(v)); return r; }
__device__ __forceinline__ float hhi(uint32_t v) { float r; asm("{.reg .b16 a,b; mov.b32 {a,b},%1; cvt.f32.f16 %0,b;}" : "=f"(r) : "r"(v)); return r; }
__device__ __forceinline__ uint32_t ordh(uint32_t v) {
  uint32_t r;
  asm("{.reg .b32 m; prmt.b32 m,%1,0,0xbb99; lop3.b32 %0,%1,m,0x7fff7fff,0x78;}" : "=r"(r) : "r"(v));
  return r;
}
template <bool MASK>
__device__ __forceinline__ float4 softmax2(const uint2 (&r)[4], uint32_t mx, uint32_t my) {
  uint32_t x = addh(addh(r[0].x, r[1].x), addh(r[2].x, r[3].x)), y = addh(addh(r[0].y, r[1].y), addh(r[2].y, r[3].y)), k;
  if (MASK) x = addh(x, mx);
  y = addh(y, my);
  asm("max.f16x2 %0,%1,%2;" : "=r"(k) : "r"(x), "r"(y));
  k = ordh(k);
  const int k0 = __reduce_max_sync(~0u, (int)(k << 16)), k1 = __reduce_max_sync(~0u, (int)k);
  k = ordh(__byte_perm(k0, k1, 0x7632));
  const float m0 = hlo(k) * -16.f, m1 = hhi(k) * -16.f;
  return make_float4(ex2(fmaf(hlo(x), 16.f, m0)), ex2(fmaf(hhi(x), 16.f, m1)), ex2(fmaf(hlo(y), 16.f, m0)), ex2(fmaf(hhi(y), 16.f, m1)));
}
__device__ __forceinline__ char* mkp(uint32_t lo, uint32_t hi) { uint64_t r; asm("mov.b64 %0,{%1,%2};" : "=l"(r) : "r"(lo), "r"(hi)); return (char*)r; }
#define LO(p) ((uint32_t)(uint64_t)(p))
#define HI(p) ((uint32_t)((uint64_t)(p) >> 32))
__device__ __forceinline__ void cp16(uint32_t dst, const void* src) { asm volatile("cp.async.cg.shared.global [%0],[%1],16;" ::"r"(dst), "l"(src) : "memory"); }
__device__ __forceinline__ uint32_t xor3(uint32_t a, uint32_t b, uint32_t c) { uint32_t r; asm volatile("lop3.b32 %0,%1,%2,%3,0x96;" : "=r"(r) : "r"(a), "r"(b), "r"(c)); return r; }
__device__ __forceinline__ uint32_t mulbf(uint32_t a, uint32_t b) { uint32_t r; asm("mul.rn.bf16x2 %0,%1,%2;" : "=r"(r) : "r"(a), "r"(b)); return r; }
__device__ __forceinline__ uint32_t fmabf(uint32_t a, uint32_t b, uint32_t c) { uint32_t r; asm("fma.rn.bf16x2 %0,%1,%2,%3;" : "=r"(r) : "r"(a), "r"(b), "r"(c)); return r; }
__device__ __forceinline__ uint32_t addbf(uint32_t a, uint32_t b) { uint32_t r; asm("add.rn.bf16x2 %0,%1,%2;" : "=r"(r) : "r"(a), "r"(b)); return r; }
__device__ __forceinline__ void pv_mem(const uint32_t (&p)[4], uint32_t pm, const uint4 (&v)[4], const uint4 (&vn)[2], uint32_t (&O)[4]) {
  float o[4][4] = {{0, 0, 0, 0}, {0, 0, 0, 0}, {0, 0, 0, 0}, {0, 0, 0, 0}};
  mma16(o[0], v[0].x, v[0].y, v[0].z, v[0].w, p[0], p[1]);
  mma16(o[1], v[2].x, v[2].y, v[2].z, v[2].w, p[0], p[1]);
  mma16(o[2], v[1].x, v[1].y, v[1].z, v[1].w, p[2], p[3]);
  mma16(o[3], v[3].x, v[3].y, v[3].z, v[3].w, p[2], p[3]);
  mma16(o[0], vn[0].x, vn[0].y, vn[0].z, vn[0].w, pm, pm);
  mma16(o[1], vn[1].x, vn[1].y, vn[1].z, vn[1].w, pm, pm);
  O[0] = pk(o[0][0] + o[2][0], o[0][1] + o[2][1]); O[1] = pk(o[0][2] + o[2][2], o[0][3] + o[2][3]);
  O[2] = pk(o[1][0] + o[3][0], o[1][1] + o[3][1]); O[3] = pk(o[1][2] + o[3][2], o[1][3] + o[3][3]);
}
__device__ __forceinline__ void pv_tok(const uint32_t (&p)[4], uint32_t pm, const uint4 (&v)[4], const uint32_t (&vm)[4], uint32_t (&O)[4]) {
  float o[2][4] = {{0, 0, 0, 0}, {0, 0, 0, 0}}, sum[4] = {0, 0, 0, 0};
  const uint32_t one = 0x3f803f80u;
  mma16(sum, one, one, one, one, p[0], p[1]);
  mma16(o[0], v[0].x, v[0].y, v[0].z, v[0].w, p[0], p[1]);
  mma16(o[1], v[2].x, v[2].y, v[2].z, v[2].w, p[0], p[1]);
  mma16(sum, one, one, one, one, p[2], p[3]);
  mma16(o[0], v[1].x, v[1].y, v[1].z, v[1].w, p[2], p[3]);
  mma16(o[1], v[3].x, v[3].y, v[3].z, v[3].w, p[2], p[3]);
  mma8(sum, one, one, pm);
  mma8(o[0], vm[0], vm[1], pm);
  mma8(o[1], vm[2], vm[3], pm);
  float i0, i1;
  asm("rcp.approx.ftz.f32 %0,%1;" : "=f"(i0) : "f"(sum[0]));
  asm("rcp.approx.ftz.f32 %0,%1;" : "=f"(i1) : "f"(sum[1]));
  O[0] = pk(o[0][0] * i0, o[0][1] * i1); O[1] = pk(o[0][2] * i0, o[0][3] * i1);
  O[2] = pk(o[1][0] * i0, o[1][1] * i1); O[3] = pk(o[1][2] * i0, o[1][3] * i1);
}
__device__ __forceinline__ uint32_t sum4bf(uint32_t a, uint32_t b, uint32_t c, uint32_t d) { return addbf(addbf(a, b), addbf(c, d)); }
template <int OFF>
__device__ __forceinline__ void sta1(uint32_t a, uint32_t v, uint32_t mb) {
  asm volatile("st.async.shared::cluster.mbarrier::complete_tx::bytes.b32 [%0+%3],%1,[%2];" ::"r"(a), "r"(v), "r"(mb), "n"(OFF) : "memory");
}

__device__ __forceinline__ void wait_time(uint32_t t) { while ((int)(gtime() - t) < 0) __nanosleep(64); }
__device__ __noinline__ void rec_prefetch(const char* wmod, const char* w1, const char* x, const char* wo) {
  const int hb = blockIdx.x - 128;
  const uint32_t t0 = gtime();
  uint32_t t = t0 + PF0;
#pragma unroll 1
  for (int job = 0; job < (PFT ? 5 : 3); job++) {
    const char* p = job == 0 ? x + (6 + hb) * 65536 : job == 1 ? wmod + hb * 12288 + 4096 : job == 2 ? w1 + hb * 7168 : job == 3 ? x + hb * 8192 : wo + (1020 + hb) * 8192;
    const int n = job == 0 ? 120 - (hb & 2) * 4 : job == 3 ? 128 : 256, d = job == 0 ? 8192 : job == 1 ? 49152 : job == 2 ? 28672 : job == 3 ? 32768 : -32768;
    if (job == 3) t = t0 + PFT;
    PT(8 + job);
#pragma unroll 1
    for (int i = 0; i < n; i++) {
      wait_time(t);
      asm volatile("cp.async.bulk.prefetch.L2.global [%0], %1;" ::"l"(p), "r"(job == 2 ? 7168 : 8192) : "memory");
      p += !job && (i & 7) == 7 ? 204800 : d;
      t += job < 3 ? PFD : PFS;
      if (job && (i & 31) == 31 && ldg_rlx1(&g_fin)) return;
    }
  }
  PT(13);
}
__device__ __noinline__ void rec_helper(uint32_t sb, const bf16* cvec, const bf16* wmod, const char* w1, const bf16* b1, uint32_t t0) {
  const int tid = threadIdx.x, hb = blockIdx.x - 128;
  PT(1);
  for (int i = tid; i < 1024; i += 256) sts1(sb + i * 8, U_(rbf(silu(__bfloat162float(cvec[i])))));
  for (int i = tid; i < 2048; i += 256) g_stat[hb * 2048 + i] = make_uint4(~0u, ~0u, ~0u, ~0u);
  for (int i = tid; i < 512; i += 256) g_cnt[hb * 512 + i] = 0;
#pragma unroll 1
  for (int job = 0; job < 2; job++) {
    wait_time(t0 + PF0 + (job ? 600 : 350) * PFD);
    BAR_SYNC(rec::B_F, 256);
    PT(2 + job * 5);
    const int n8 = job ? 112 : 128, rg = tid >= n8, cg = tid - rg * n8, pitch = job ? 448 : 768;
    const uint4* p = (const uint4*)(job ? w1 + hb * 1792 : (const char*)(wmod + 2048 + hb * 1024)) + rg * pitch + min(cg, n8 - 1);
    float a1[8] = {0, 0, 0, 0, 0, 0, 0, 0}, a2[8] = {0, 0, 0, 0, 0, 0, 0, 0};
#pragma unroll 1
    for (int r0 = rg; r0 < 1024; r0 += 32) {
      uint4 v[16];
#pragma unroll
      for (int i = 0; i < 16; i++) { v[i] = ldg_rlx4(p); p += 2 * pitch; }
#pragma unroll
      for (int i = 0; i < 16; i++) {
        const float2 f = lds2f(sb + (r0 + 2 * i) * 8);
        const float w[8] = {blo(v[i].x), bhi(v[i].x), blo(v[i].y), bhi(v[i].y), blo(v[i].z), bhi(v[i].z), blo(v[i].w), bhi(v[i].w)};
#pragma unroll
        for (int e = 0; e < 8; e++) { a1[e] += f.x * w[e]; a2[e] += f.y * w[e]; }
      }
    }
    const uint32_t rd = sb + 8192;
    if (cg < n8) {
#pragma unroll
      for (int e = 0; e < 8; e++) sts2(rd + rg * 8192 + (cg * 8 + e) * 8, U_(a1[e]), U_(a2[e]));
    }
    BAR_SYNC(rec::B_F, 256);
    if (job == 0) {
      for (int i = tid; i < 1024; i += 256) g_mod[2048 + hb * 1024 + i] = rbf(F_(lds1(rd + i * 8)) + F_(lds1(rd + 8192 + i * 8)));
      BAR_SYNC(rec::B_F, 256);
      PT(6);
      if (tid == 0) { red_rel(&g_mcnt); wait_cnt(&g_mcnt, 4); }
      BAR_SYNC(rec::B_F, 256);
      for (int i = tid; i < 1024; i += 256) sts2(sb + i * 8, U_(rbf(1.f + __ldcg(g_mod + 4096 + i))), U_(__ldcg(g_mod + 3072 + i)));
    } else {
      for (int i = tid; i < 448; i += 256) {
        const int gn = hb * 896 + i * 2;
        const uint32_t bb = *(const uint32_t*)(b1 + gn);
        const float4 u = lds4f(rd + i * 16), w = lds4f(rd + 8192 + i * 16);
        ((uint2*)g_cc)[(gn >> 4) * 8 + ((gn >> 1) & 3) * 2 + ((gn >> 3) & 1)] = make_uint2(pk(u.x + w.x, u.z + w.z), pk(0.5f * (u.y + w.y + blo(bb)), 0.5f * (u.w + w.w + bhi(bb))));
      }
      PT(4);
    }
  }
}

__global__ void __cluster_dims__(2, 1, 1) __launch_bounds__(512, 1)
k_rec(const __grid_constant__ RecMaps mp, const bf16* __restrict__ mem0, const bf16* __restrict__ x, const bf16* __restrict__ cvec,
      const bf16* __restrict__ wmod, const char* __restrict__ w1, const bf16* __restrict__ b1, const char* __restrict__ wo, char* xc, int dF, int dA, int dS, int dM, int dG, int dP, int dX, int dD, int dZ, int dZ2, int dV, int dX2) {
  using namespace rec;
  extern __shared__ __align__(1024) char smem[];
  const uint32_t sb = (uint32_t)__cvta_generic_to_shared(smem);
  if ((sb & 0x3FFFF) != 1024) __trap();
  PH(0); if (threadIdx.x == 0) PT(0);
  if (threadIdx.x == 0) {
    int b = blockIdx.x;
    if (b >= 8 && b < 128) {
      const int t = (b >> 1) - 4, u = t - 32;
      b = 2 * (t < 32 ? 4 + (t & 16) + (t & 7) * 2 + ((t >> 3) & 1) : 36 + (u / 14) * 14 + (u % 7) * 2 + ((u / 7) & 1)) + (b & 1);
    }
    sts1(sb + rec::PACE + 24, b);
    const int c = blockIdx.x >> 1, l = c < 36 ? (c - 4) & 7 : (c - 36) % 7, m = c < 4 ? c : c < 36 ? (c - 4) >> 3 : (c - 36) / 7;
    const int g = c < 4 ? 15 : (l >> 1) * 4 + (l & 1) + (c < 36 ? 0 : 2);
    unsigned sm;
    asm("mov.u32 %0,%%smid;" : "=r"(sm));
    if (c < 64) g_slot[sm & 255] = 1 + FMAP;
  }
#define ROLE_REFRESH { asm volatile("mov.u32 %0,%%tid.x;" : "=r"(tid)); wid = __shfl_sync(~0u, tid >> 5, 0); b = __shfl_sync(~0u, lds1(sb + PACE + 24), 0); }
#define ROLE_VARS int tid; asm volatile("mov.u32 %0,%%tid.x;" : "=r"(tid)); \
    int wid = __shfl_sync(~0u, tid >> 5, 0), b = __shfl_sync(~0u, lds1(sb + PACE + 24), 0);
#define wg (wid >> 2)
#define iw (wid & 3)
#define h (b >> 2)
#define j (b & 3)
#define a (b & 1)
#define bb ((b >> 1) & 1)
  const uint32_t wbar = sb + BARS + 48, obar = wbar + 8;
  if (threadIdx.x == 256) {
    for (int i = 0; i < 18; i++) if (i != 12) mbar_init(sb + BARS + i * 8, i == 3 || i == 8 || i == 9 || i == 10 ? 2 : 1);
    for (int i = 0; i < 3; i++) mbar_init(sb + PACE + i * 8, 1);
    asm volatile("fence.mbarrier_init.release.cluster;" ::: "memory");
    FENCE_ASYNC_SMEM();
    mbar_expect(sb + BARS, 2048);
    mbar_expect(sb + BARS + 16, 4096);
    mbar_expect(sb + BARS + 32, 4096);
    mbar_expect(sb + BARS + 40, 4096);
  }
  __syncthreads();
  asm volatile("barrier.cluster.arrive.relaxed.aligned;" ::: "memory");
#define lane ((int)(l16 >> 4))
#define l16 (L16 & 0x1f0)
#define is7 ((L16 & 112) == 112)
#define PIN(x) __shfl_xor_sync(~0u, (uint32_t)(x), 0)
#define REFRESH() L16 = __shfl_xor_sync(~0u, L16, 0)
#define lar ((L16 & 0x180) * 8 + (L16 & 0x70))
#define X_LOAD(n, w, u) \
        asm volatile("{.reg .pred p; elect.sync _|p, 0xffffffff; @p mbarrier.arrive.expect_tx.shared.b64 _,[%2],8192;\n" \
                     "@p cp.async.bulk.shared::cluster.global.mbarrier::complete_tx::bytes [%0],[%1],8192,[%2];}" ::"r"(sb + XB + (w) * 16384 + (u) * 8192), \
                     "l"(g_h + (n) * 4096 + a * 2048 + (w) * 1024 + (u) * 512), "r"(sb + BARS + 64 + (w) * 8) : "memory")
#define lpub ((L16 & 0x30) * 64 + ((L16 >> 3) & 0x38))
#define lrow ((L16 & 0x70) + (((L16 >> 3) ^ L16) & 0x70 & ~((L16 >> 3) & 0x40) ? L16 & 0x180 : 512))

  const int role = __shfl_sync(~0u, threadIdx.x >> 7, 0);
  if (role < 2) {
    asm volatile("setmaxnreg.inc.sync.aligned.u32 %0;" ::"n"(RF_));
    ROLE_VARS
    uint32_t L16 = __shfl_sync(~0u, sb + (tid & 31) * 16, tid & 31);
    uint32_t wQ[16][4], wK[16][4], wV[NVR][4];
    uint32_t m0[2][4];
    uint32_t frag = sb + ((lane & 7) + (lane >> 4) * 8) * 128 + (((iw * 2 + ((lane >> 3) & 1)) ^ (lane & 7)) << 4);
    {
      const bool spare = b >= 128;
      const uint32_t t0 = gtime();
      uint4 xr[16];
      int seg = spare ? b - 126 : wg;
      const int half = spare ? wg : a;
      auto x_fetch = [&]() {
        const uint4* px = (const uint4*)x + (seg * 32 + iw * 8 + (lane >> 2)) * 128 + half * 64 + (lane & 3);
#pragma unroll
        for (int i = 0; i < 16; i++) xr[i] = __ldg(px + i * 4);
      };
      if (!spare) {
        uint4 wm[8];
        const uint4* pw = (const uint4*)(wmod + (size_t)((b >> 5) * 256 + (tid >> 3)) * 6144 + (b & 31) * 64) + (tid & 7);
        const float cs = __bfloat162float(cvec[(b >> 5) * 256 + tid]);
#pragma unroll
        for (int i = 0; i < 8; i++) wm[i] = __ldcs(pw + (size_t)i * 32 * 768);
        unsigned short mr[16];
#pragma unroll
        for (int i = 0; i < 16; i++) mr[i] = __bfloat16_as_ushort(mem0[(i & 7) * 1024 + a * 512 + tid * 2 + (i >> 3)]);
        float* sc = (float*)(smem + PRE);
        sc[tid] = rbf(silu(cs));
        PT(1);
        BAR_SYNC(B_F, 256);
        float acc[8] = {0, 0, 0, 0, 0, 0, 0, 0};
#pragma unroll
        for (int i = 0; i < 8; i++) {
          const float f = sc[i * 32 + (tid >> 3)];
          acc[0] += f * blo(wm[i].x); acc[1] += f * bhi(wm[i].x); acc[2] += f * blo(wm[i].y); acc[3] += f * bhi(wm[i].y);
          acc[4] += f * blo(wm[i].z); acc[5] += f * bhi(wm[i].z); acc[6] += f * blo(wm[i].w); acc[7] += f * bhi(wm[i].w);
        }
#pragma unroll
        for (int i = 0; i < 8; i++) { acc[i] += __shfl_xor_sync(~0u, acc[i], 8); acc[i] += __shfl_xor_sync(~0u, acc[i], 16); }
        float* red = sc + 1024;
        if ((tid & 31) < 8) {
#pragma unroll
          for (int i = 0; i < 8; i++) red[(tid >> 5) * 64 + (tid & 7) * 8 + i] = acc[i];
        }
        BAR_SYNC(B_F, 256);
        PT(2);
        if (tid < 64) {
          float t = 0;
#pragma unroll
          for (int i = 0; i < 8; i++) t += red[i * 64 + tid];
          asm volatile("st.relaxed.gpu.global.u32 [%0],%1;" ::"l"((unsigned*)g_modp + (b >> 5) * 2048 + (b & 31) * 64 + tid), "r"(U_(t) | 1u) : "memory");
        }
#pragma unroll
        for (int i = 0; i < 8; i++) m0[i >> 2][i & 3] = mr[i * 2] | ((uint32_t)mr[i * 2 + 1] << 16);
      } else {
        asm volatile("griddepcontrol.launch_dependents;");
      }
      x_fetch();
      const uint32_t md = sb + PRE + 6144, rx = mapa(sb, a ^ !spare);
      asm volatile("barrier.cluster.wait.aligned;" ::: "memory");
      if (!spare) {
        mbar_wait(sb + BARS + 88, 0);
#pragma unroll
        for (int i = 0; i < 16; i++) ldsm4t(wQ[i], frag + WO + wg * 32768 + i * 2048);
      }
      PT(4);
#pragma unroll 1
      for (int it = 0;; it++) {
        if (tid == 0) mbar_expect(sb + BARS + 104, 512);
        float c[4][4] = {{0, 0, 0, 0}, {0, 0, 0, 0}, {0, 0, 0, 0}, {0, 0, 0, 0}};
#pragma unroll
        for (int i = 0; i < 16; i++) {
          mma16(c[(i & 1) * 2], xr[i].x, 0x3f803f80u, xr[i].y, 0x3f803f80u, xr[i].x, xr[i].y);
          mma16(c[(i & 1) * 2 + 1], xr[i].z, 0x3f803f80u, xr[i].w, 0x3f803f80u, xr[i].z, xr[i].w);
        }
#pragma unroll
        for (int e = 0; e < 4; e++) c[0][e] = (c[0][e] + c[1][e]) + (c[2][e] + c[3][e]);
        const int src = (lane & 28) + (lane >> 3);
        const float sq = __shfl_sync(~0u, (lane & 4) ? c[0][1] : c[0][0], src), sm = __shfl_sync(~0u, (lane & 4) ? c[0][3] : c[0][2], src);
        if ((lane & 3) < 2) sta1<0>(rx + PRE + 10240 + (wid ^ (spare * 4)) * 64 + (lane >> 2) * 8 + (lane & 1) * 4, U_((lane & 1) ? sm : sq), rx + BARS + 104);
        mbar_wait(sb + BARS + 104, it & 1);
        const float2 ot = lds2f(sb + PRE + 10240 + wid * 64 + (lane >> 2) * 8);
        const float mean = (sm + ot.y) * (1.f / 1024);
        const float rs = rsqrtf(fmaxf((sq + ot.x) * (1.f / 1024) - mean * mean, 0.f) + 1e-5f), nm = -mean * rs;
#define NRM(v) v = pk(fmaf(blo(v), rs, nm), fmaf(bhi(v), rs, nm))
#pragma unroll
        for (int i = 0; i < 16; i++) { NRM(xr[i].x); NRM(xr[i].y); NRM(xr[i].z); NRM(xr[i].w); }
        if (!it) {
          PT(3);
#pragma unroll 1
          for (int i = 0; i < 2; i++) {
            uint4 p[4];
            for (int n = 0;; n++) {
#pragma unroll
              for (int e = 0; e < 4; e++) p[e] = ldg_rlx4(g_modp + e * 512 + i * 256 + tid);
              uint32_t ok = 1;
#pragma unroll
              for (int e = 0; e < 4; e++) ok &= p[e].x & p[e].y & p[e].z & p[e].w;
              if (__all_sync(~0u, ok) || n > SPIN_LIMIT / 16) break;
              __nanosleep(100);
            }
#define MSUM(e) (i + rbf((F_(p[0].e) + F_(p[1].e)) + (F_(p[2].e) + F_(p[3].e))))
            sts2(md + i * 2048 + tid * 8, pk(MSUM(x), MSUM(y)), pk(MSUM(z), MSUM(w)));
          }
          BAR_SYNC(B_F, 256);
          PT(5);
        }
        const int e0 = (iw * 8 + (lane >> 2)) * 8 + ((lane & 3) ^ (lane >> 2));
        uint4* dst = g_h + seg * 4096 + half * 2048;
#pragma unroll
        for (int i = 0; i < 16; i++) {
          const uint32_t ma = md + half * 1024 + (lane & 3) * 16 + i * 64;
          const uint4 sv = lds4(ma), cv = lds4(ma + 2048);
          xr[i] = make_uint4(fmabf(xr[i].x, cv.x, sv.x), fmabf(xr[i].y, cv.y, sv.y), fmabf(xr[i].z, cv.z, sv.z), fmabf(xr[i].w, cv.w, sv.w));
        }
        if (!spare) {
#pragma unroll
          for (int i = 0; i < 16; i++) sts4(sb + WO + wg * 32768 + (e0 ^ ((i & 1) * 4)) * 16 + (i >> 1) * 4096, xr[i].x, xr[i].y, xr[i].z, xr[i].w);
          break;
        }
#pragma unroll
        for (int i = 0; i < 16; i++) dst[(e0 ^ ((i & 1) * 4)) + (i >> 1) * 256] = xr[i];
        seg += 4;
        if (seg < 64) x_fetch();
        FENCE_ASYNC();
        BAR_SYNC(B_F, 256);
        if (tid == 0) red_rlx(g_hf + b - 128);
        if (seg >= 64) break;
      }
      if (spare) { rec_helper(sb, cvec, wmod, w1, b1, t0); return; }
      PH(1); PH(2); PT(6);
    }
    ROLE_REFRESH
    mbar_wait(wbar, 0);
    PT(7);
#pragma unroll
    for (int i = 0; i < 16; i++) ldsm4t(wK[i], frag + XB + wg * 32768 + i * 2048);
#pragma unroll
    for (int i = 0; i < NVR; i++) ldsm4t(wV[i], frag + MEM + (wg * NVR + i) * 2048);
    FENCE_ASYNC_SMEM();
    PH(3); PT(8);
    CLUSTER_SYNC();
    PT(9);
#pragma unroll
    for (int i = 0; i < 2; i++) {
      const int k = tid * 2 + i, m = (k >> 3) & 3, r = k & 7;
      sts4(sb + MEM + (k >> 5) * 640 + (r == m ? 512 : m * 128) + r * 16, m0[i][0], m0[i][1], m0[i][2], m0[i][3]);
    }
    if (lane < 8) {
      sts4(sb + ARO + wid * 640 + (lane < 4 ? lane * 144 : 512 + l16), 0x3f803f80, 0x3f803f80, 0x3f803f80, 0x3f803f80);
#pragma unroll
      for (int i = 0; i < 2; i++) sts4(sb + MEM + (wid * 2 + i) * 640 + (lane < 4 ? lane * 144 : 512 + l16), 0x42004200, 0x42004200, 0x42004200, 0x42004200);
    }
#define owner ((iw >> 1) == a)
#define vfin ((wid >> 1) == a)
#define oi (wid & 1)
    frag += wg * NVS * 2048;
    {
      const uint32_t rsb = mapa(sb, iw >> 1);
      const uint32_t pp = rsb + PK + (owner ? 0 : 12288) + (oi * 2048 + wg * 1024) + l16;
      const uint32_t mb = sb + MEM + wg * 5120;
      sts4(L16 + TF + wid * 512, mb + lrow, owner ? L16 + (lane >> 4) * (RK - RQ - 256) + RQ + oi * 1024 + wg * 256 : rsb + RQ + oi * 1024 + 512 + wg * 256 + (l16 >> 2),
           L16 + OB, frag);
      sts4(L16 + TF + 4096 + wid * 512, sb + WO + (wid >> 1) * 16384 + ((lane & 7) + (lane >> 4) * 8) * 128 + ((((wid & 1) * 4 + ((lane >> 3) & 1)) ^ (lane & 7)) << 4),
           sb + ARO + wid * 640 + lrow, pp, LO(xc) + h * 262144 + (bb * 2 + (iw >> 1)) * XC + X_VM(0) + oi * 2048 + a * 256 + (l16 >> 1));
    }
    uint32_t tp = L16 + TF + wid * 512;
    auto park_ptr = [&]() { return lds1(tp + 4096 + 8); };
    auto park = [&](const float* f, int m, int n, uint32_t d) {
      uint32_t w[8];
#pragma unroll
      for (int i = 0; i < 8; i++) w[i] = pk(f[2 * i], f[2 * i + 1]);
      if (owner) {
        sts4(d + m * 4096, w[0], w[1], w[2], w[3]); sts4(d + m * 4096 + 512, w[4], w[5], w[6], w[7]);
      } else {
        const uint32_t pb = mapa(sb, a ^ 1) + BARS + (m ? 24 + m * 8 : 16);
        sta4(d + m * 4096, w, pb); sta4(d + m * 4096 + 512, w + 4, pb);
      }
    };
    auto xdesc = [&](uint32_t xb) { return mkdesc(__shfl_sync(~0u, 1024 + xb + wg * 16384, 0), 16, 1024); };
    auto rs_issue = [&](float* acc, const uint32_t (&w)[16][4], uint32_t xb, bool fence) {
      const uint64_t x = xdesc(xb);
      if (fence) WG_FENCE();
      wgmma_rs_n32_z(acc, w[0], x);
#pragma unroll
      for (int i = 1; i < 16; i++) wgmma_rs_n32(acc, w[i], x + (i >> 2) * 256 + (i & 3) * 2, 1);
      WG_COMMIT();
    };
    auto v_issue = [&](float* acc, uint32_t xb, bool fence) {
      const uint64_t dv = mkdesc(__shfl_sync(~0u, 1024 + WVS + wg * NVS * 2048, 0), 16, 1024), x = xdesc(xb);
      if (fence) WG_FENCE();
      wgmma_rs_n32_z(acc, wV[0], x);
#pragma unroll
      for (int i = 1; i < (KVO == 2 ? NVR : 0); i++) wgmma_rs_n32(acc, wV[i], x + (i >> 2) * 256 + (i & 3) * 2, 1);
#pragma unroll
      for (int i = NVR; i < 16; i++) wgmma_ssT_n32(acc, dv + (i - NVR) * 128, x + (i >> 2) * 256 + (i & 3) * 2, 1);
#pragma unroll
      for (int i = 1; i < (KVO == 2 ? 0 : NVR); i++) wgmma_rs_n32(acc, wV[i], x + (i >> 2) * 256 + (i & 3) * 2, 1);
      WG_COMMIT();
    };
    uint32_t mA;
    auto vk_pass = [&](int n, uint32_t d, uint32_t xb, bool steady) {
      float acc[16], acc2[16];
      v_issue(acc, xb, true);
      rs_issue(acc2, wK, xb, false);
      if (steady || n) mbar_wait(sb + BARS + 80, (n - 1) & 1);
      WG_WAIT(1);
      park(acc, 2 - !!KVO, n, d);
      mA = lds1(tp);
      if (steady) BAR_ARRIVE(B_K, 320);
      WG_WAIT(0);
      park(acc2, 1 + !!KVO, n, d);
    };
    PT(10);
#pragma unroll 1
    for (int n = 0; n < 2; n++) {
      float acc[16];
      asm volatile("" : "+r"(wid));
      rs_issue(acc, wQ, n * XB, true);
      if (n) {
        BAR_SYNC(B_C, 320);
        PT(12);
        mbar_wait(sb + BARS + 24, 0);
      } else {
#pragma unroll
        for (int i = 0; i < 8; i++) {
          const uint4 v = lds4(L16 + WO + 32768 + wid * 4096 + i * 512);
          sts4(L16 + XB + wid * 4096 + i * 512, v.x, v.y, v.z, v.w);
        }
      }
      WG_WAIT(0); park(acc, 0, n, park_ptr());
      FENCE_ASYNC_SMEM();
      vk_pass(n, park_ptr(), n * XB, false);
      if (n) break;
      PT(11);
      BAR_SYNC(B_C, 320);
      if (tid == 0) {
        mbar_expect(obar, 65536);
#pragma unroll 1
        for (int i = 0; i < 4; i++) tma2d(sb + WO + i * 16384, &mp.wo, j * 256 + i * 64, h * 128, obar);
      }
    }
    static_assert(WO == 0, "x");
    {
      BAR_ARRIVE(B_P, 384); if (!HX) BAR_ARRIVE(B_X, 320); BAR_ARRIVE(B_Q, 288);
    }
    PT(13);
    mbar_wait(obar, 0);
    PH(4); PT(14);
    ROLE_REFRESH
    for (int s = 0; s < 64; s++) {
      asm volatile("" : "+r"(tp), "+r"(wid));
      asm volatile("mov.u32 %0,%%cluster_ctarank;" : "=r"(b));
      uint32_t vS[NVS][4], bf[8][4], rm;
      const uint32_t mm = mapa(sb, a ^ 1) + BARS;
      if (s > 0) BAR_SYNC(B_R, 320);
#define VMMA(c, w, i) mma16(c, (w)[0], (w)[1], (w)[2], (w)[3], bf[(i) >> 1][((i) & 1) * 2], bf[(i) >> 1][((i) & 1) * 2 + 1])
      {
        float cQ[4] = {0, 0, 0, 0}, cK[4] = {0, 0, 0, 0};
#pragma unroll
        for (int t = 7; t >= 3; t--) ldsm4t(bf[t], mA + t * 640);
        SCHED_FENCE(47);
#pragma unroll
        for (int i = 15; i >= 0; i--) {
          VMMA(cQ, wQ[i], i); VMMA(cK, wK[i], i);
          if (i == XI && HX) BAR_ARRIVE(B_X, 320);
          if (i == 12) {
            SCHED_FENCE(51);
#pragma unroll
            for (int t = 2; t >= 0; t--) ldsm4t(bf[t], mA + t * 640);
            rm = lds1(tp + 4); frag = lds1(tp + 12);
          }
          if (i == 4 && NVP) {
            SCHED_FENCE(48);
#pragma unroll
            for (int u = 0; u < NVP; u++) ldsm4t(vS[NVS - 1 - u], frag + WVS + (NVS - 1 - u) * 2048);
          }
        }
        const uint32_t w0 = pk(cQ[0] * SCS, cQ[1] * SCS), w1 = pk(cQ[2] * SCS, cQ[3] * SCS), w2 = pk(cK[0], cK[1]), w3 = pk(cK[2], cK[3]);
        if (owner) {
          stsm4(rm, w0, w1, w2, w3);
          BAR_ARRIVE(B_E, 256);
        } else {
          sta1<0>(rm, w0, mm); sta1<128>(rm, w1, mm);
          sta1<RK - RQ>(rm, w2, mm); sta1<RK - RQ + 128>(rm, w3, mm);
        }
        if (wid == 2) TS(0);
      }
      uint4 t1;
      uint32_t oA;
      {
        float cV[4] = {0, 0, 0, 0}, cW[4] = {0, 0, 0, 0};
        static_assert(NVP == 2 && NVR == 5, "schedule");
#define VLD(k) ldsm4t(vS[(k) - NVR], frag + WVS + ((k) - NVR) * 2048)
#define VS_(c, k) VMMA(c, vS[(k) - NVR], k)
        VLD(13); VLD(12);
        VS_(cW, 15); VS_(cV, 14); VLD(11); VMMA(cW, wV[0], 0); VLD(10); VMMA(cV, wV[1], 1); VLD(9);
        VMMA(cW, wV[2], 2); VLD(8); VMMA(cV, wV[3], 3); VLD(7); VMMA(cW, wV[4], 4); VS_(cV, 13); VLD(6); VS_(cW, 12); VLD(5);
        VS_(cV, 11); VS_(cW, 10); VS_(cV, 9); VS_(cW, 8); VS_(cV, 7); VS_(cW, 6); VS_(cV, 5);
#pragma unroll
        for (int e = 0; e < 4; e++) cV[e] += cW[e];
        const uint32_t ex = tp + (RX - TF) - wg * 2048;
        t1 = lds4(tp + 4096);
        oA = lds1(tp + 8 + (s & dZ));
        if (wg) {
          sts4(ex, U_(cV[0]), U_(cV[1]), U_(cV[2]), U_(cV[3]));
          BAR_ARRIVE(B_T2, 256);
        } else {
          BAR_SYNC(B_T2, 256);
          const float4 u = lds4f(ex);
          stg_b64(mkp(t1.w ^ ((s & 1) * X_RING), HI(xc)), (pk(cV[0] + u.x, cV[1] + u.y) & ~1u) | (((s >> 1) + 1) & 1), pk(cV[2] + u.z, cV[3] + u.w));
        }
      }
      if (s == 63) break;
      {
        const uint32_t woA = t1.x, woB = woA ^ 32;
        uint32_t wo[16][4];
#pragma unroll
        for (int i = 0; i < NW1; i++) ldsm4t(wo[i], ((i & 1) ? woB : woA) + (i >= WCH ? wo[(i - WCH + NWP) % NWP][0] & dZ : 0) + (i >> 1) * 2048);
        BAR_SYNC(B_S, 416);
        if (s < 62) {
          float acc[16];
          rs_issue(acc, wQ, XB, true);
          mbar_wait(sb + BARS + 24, (s + 1) & 1);
          WG_WAIT(0);
          BAR_SYNC(B_V, 512);
          park(acc, 0, s + 2, t1.z);
        } else {
          BAR_SYNC(B_V, 512);
        }
#pragma unroll
        for (int i = NW1; i < NWP; i++) ldsm4t(wo[i], ((i & 1) ? woB : woA) + (i >> 1) * 2048);
        float inv0, inv1;
        {
          uint32_t p[4], pm;
          const uint32_t pa = oA + (SC - OB), one = 0x3f803f80u;
          float sum[4] = {0, 0, 0, 0}, su2[4] = {0, 0, 0, 0};
          ldsm4t(p, pa);
          asm volatile("ldmatrix.sync.aligned.m8n8.x1.trans.shared.b16 {%0},[%1];" : "=r"(pm) : "r"(pa + 512) : "memory");
          mma16(sum, one, one, one, one, p[0], p[1]);
          mma16(su2, one, one, one, one, p[2], p[3]);
          mma8(sum, one, one, pm);
          inv0 = sum[0] + su2[0]; inv1 = sum[1] + su2[1];
          SCHED_FENCE(57);
        }
        BAR_SYNC(B_O, 416);
        float c[2][4] = {{0, 0, 0, 0}, {0, 0, 0, 0}};
        uint32_t o[4][4];
#pragma unroll
        for (int i = 0; i < NOP_; i++) ldsm4t(o[i], oA + i * 512);
        SCHED_FENCE(46);
        asm("rcp.approx.ftz.f32 %0,%0;" : "+f"(inv0));
        asm("rcp.approx.ftz.f32 %0,%0;" : "+f"(inv1));
#pragma unroll
        for (int i = 0; i < 16; i++) {
          mma16(c[i & 1], wo[i][0], wo[i][1], wo[i][2], wo[i][3], o[i >> 2][i & 2], o[i >> 2][(i & 2) + 1]);
          if (i == 1 && NOP_ < 3) ldsm4t(o[2], oA + 1024);
          if (i == 3 && NOP_ < 4) ldsm4t(o[3], oA + 1536);
          if (i + NWP < 16) ldsm4t(wo[(i + NWP) & 15], (((i + NWP) & 1) ? woB : woA) + ((i + NWP) >> 1) * 2048);
        }
        stsm4(t1.y, pk(c[0][0] * inv0, c[0][1] * inv1), pk(c[0][2] * inv0, c[0][3] * inv1), pk(c[1][0] * inv0, c[1][1] * inv1), pk(c[1][2] * inv0, c[1][3] * inv1));
      }
      const uint32_t d = park_ptr();
      BAR_SYNC(B_W, 384);
      if (s < 62) {
        vk_pass(s + 2, d, XB, true);
        BAR_ARRIVE(B_P, 384); if (!HX) BAR_ARRIVE(B_X, 320);
        TS(10);
      } else {
        mA = lds1(tp);
      }
    }
  } else if (role == 3) {
    asm volatile("setmaxnreg.dec.sync.aligned.u32 24;");
    if (blockIdx.x >= 128) return;
    ROLE_VARS
    const uint32_t L16 = sb + (tid & 31) * 16;
    asm volatile("barrier.cluster.wait.aligned;" ::: "memory");
    CLUSTER_SYNC();
    sts1(sb + PACE + 36, LO(xc) + h * 262144 + X_VM(0));
    auto vm_stage = [&](int s) {
      const uint32_t tag = ((s >> 1) + 1) & 1;
      const char* xm = mkp(lds1(sb + PACE + 36) + (s & 1) * X_RING + iw * XC + (l16 >> 1), HI(xc));
      uint2 m[4];
      CONSUME(LO(xm));
      BAR_SYNC(B_S2, 256);
      if (dZ2 > 1) { const uint32_t c = clk(); while (clk() - c < (uint32_t)dZ2) {} }
      int it = 0;
      while (true) {
#pragma unroll
        for (int i = 0; i < 4; i++) m[i] = ldg_b64(xm + (i >> 1) * 2048 + (i & 1) * 256);
        sts4(L16 + VN + iw * 512, m[0].x, m[0].y, m[1].x, m[1].y);
        sts4(L16 + VN + iw * 512 + 2048, m[2].x, m[2].y, m[3].x, m[3].y);
        if (!anybad(m[0].x, m[1].x, m[2].x, m[3].x, tag)) break;
        RP(2);
        if (++it > SPIN_LIMIT) __trap();
      }
      if (s < 63) BAR_ARRIVE(B_V, 512); else BAR_ARRIVE(B_V, 256);
    };
    if (iw == 0) {
      wait_cnt(&g_hcnt, 128);
#pragma unroll 1
      for (int s = 0; s < 63; s++) {
        if (s < 62) for (int it = 0; ldg_rlx1(g_hf + (s & 3)) <= (s >> 2); it++) if (it > SPIN_LIMIT) __trap();
        if (s) BAR_SYNC(B_R, 320); else BAR_SYNC(B_Q, 288);
        if (s < 62) { X_LOAD(s + 2, 0, 0); X_LOAD(s + 2, 1, 0); X_LOAD(s + 2, 0, 1); X_LOAD(s + 2, 1, 1); }
        if (s >= 7) {
          const uint32_t zo = b * 160 + l16;
          if (l16 < 160) CONSUME(exch_b128(xc + AR_OFF + AR_ROW(zo >> 7) * 1024 + (zo & 127) + ((s + 1) & 7) * 128, 0, 0, 0, 0).x);
          __syncwarp();
        }
        if (s < 62) { mbar_wait(sb + BARS + 64, s & 1); mbar_wait(sb + BARS + 72, s & 1); }
        BAR_ARRIVE(B_S, 416);
        vm_stage(s);
        BAR_ARRIVE(B_O, 416);
        BAR_SYNC(B_W, 384);
        FENCE_ASYNC_SMEM();
        asm volatile("{.reg .pred p; elect.sync _|p, 0xffffffff; @p cp.reduce.async.bulk.tensor.3d.global.shared::cta.add.bulk_group [%0,{%1,%2,%4}],[%3];}"
                     ::"l"(&mp.ari), "r"((s & 7) * 64), "r"(AR_R(j)), "r"(sb + ARO), "r"(AR_P(j)) : "memory");
        BULK_COMMIT();
        asm volatile("st.relaxed.gpu.global.u32 [%0],%1;" ::"l"(g_tm + (s & 1) * 128 + b), "r"(gtime()) : "memory");
        TS(3);
        BULK_WAIT_READ(0);
      }
      BAR_ARRIVE(B_R, 320);
    } else if (iw == 1) {
      const uint32_t pc = sb + MEM + (lane >> 2) * 640 + (lane & 3) * 144 + (lane & 12), pd = sb + MEM + (lane & 15) * 640 + 576 + (lane & 3) * 16 + (lane & 12);
      uint32_t T = 0, par = 0;
      int est = dA;
#pragma unroll 1
      for (int s = 0; s < 63; s++) {
        if (s) {
          const uint4 tm = ldg_rlx4((const char*)g_tm + ((s + 1) & 1) * 512 + l16);
          const int t0 = tm.x - T, t1 = tm.y - T, t2 = tm.z - T, t3 = tm.w - T;
          const int e = max(dF + (__reduce_add_sync(~0u, (t0 + t1) + (t2 + t3)) >> 7), dV + __reduce_max_sync(~0u, max(max(t0, t1), max(t2, t3))));
          if (s > 1) est += max(min(e >> 2, dP), -dP);
          T += (s == 1 || e > dM ? e : 0) + est;
        }
        vm_stage(s);
        BAR_SYNC(B_W, 384);
        SCHED_FENCE(70);
        const uint32_t tW = gtime();
        if (s == 0) T = tW + 800;
        const uint32_t te = tW + min(max((int)(T - tW), dD), 2000);
        while ((int)(gtime() - te) < 0) {}
        TS(7);
        int it = 0;
        while (true) {
          ar_fetch(sb + MEM, &mp.ari, s & 7, a, sb + BARS + 112);
          mbar_wait(sb + BARS + 112, par);
          par ^= 1;
          const uint32_t n0 = lds1(pc), n1 = lds1(pc + 5120), n2 = lds1(pd);
          if (!__any_sync(~0u, (tagbad(n0, n1, 0x42004200) | (n2 ^ 0x42004200)) != 0)) break;
          RP(0);
          if (++it > SPIN_LIMIT) __trap();
        }
        BAR_ARRIVE(B_R, 320);
        TS(11);
      }
    } else {
#define V_LOAD(n) do { if (lane == 0) mbar_expect(sb + BARS + 8, 8192); __syncwarp(); \
        if (lane < 16) bulk_ld(sb + ((lane & 2) ? VX1 : VX0) + (lane & 1) * 2048 + (lane >> 2) * 512, \
                               xc + h * 262144 + V_RING(n) + (lane >> 2) * XC + X_VX(lane & 3), 512, sb + BARS + 8); __syncwarp(); } while (0)
      uint32_t src = L16 + PK + (iw & 1) * 2048;
#define qd (L16 + (lane >> 4) * 256 + QT + (iw & 1) * 1024)
#define vd (LO(xc) + h * 262144 + j * XC + (iw & 1) * 2048 + l16)
#define FINISH [&](int n, int m) { \
_Pragma("unroll") \
        for (int i = 1; i >= 0; i--) { \
          const uint32_t p = src + m * 4096 + i * 512; \
          uint4 u = lds4(p); \
          const uint4 w = lds4(p + 1024), y = lds4(p + 12288), z = lds4(p + 13312); \
          u = make_uint4(sum4bf(u.x, w.x, y.x, z.x), sum4bf(u.y, w.y, y.y, z.y), sum4bf(u.z, w.z, y.z, z.z), sum4bf(u.w, w.w, y.w, z.w)); \
          if (m == 2) stg_b128(mkp(vd ^ V_RING(n), HI(xc)) + i * 512, (u.x & ~1u) | V_TAG(n), u.y, u.z, u.w); \
          else stsm4(qd + (n & 1) * 4096 + m * 2048 + i * 256, u.x, u.z, u.y, u.w); \
          SCHED_FENCE(71 + m * 2 + i); \
        } \
      }
#pragma unroll 1
      for (int n = 0; n < 64; n++) {
        src = PIN(src);
        b = __shfl_sync(~0u, lds1(sb + PACE + 24), 0);
        const uint32_t L16 = src - PK - (iw & 1) * 2048;
        auto finish = FINISH;
        if (n < 2) { if (n) BAR_SYNC(B_X, 320); else BAR_SYNC(B_C, 320); }
        mbar_wait(sb + BARS + 16, n & 1);
        finish(n, 0);
        __syncwarp();
        if (lane == 0) mbar_arrive_cl(mapa(sb, a ^ 1) + BARS + 24);
        if (n > 1) BAR_SYNC(B_K, 320);
        mbar_wait(sb + BARS + (KVO ? 32 : 40), n & 1);
        finish(n, 2 - !!KVO);
        if (n > 1) BAR_SYNC(B_X, 320);
        mbar_wait(sb + BARS + (KVO ? 40 : 32), n & 1);
        finish(n, 1 + !!KVO);
        BAR_SYNC(B_T, 64);
        if (lane == 0) {
          if (iw == 2 && n < 63) { mbar_expect(sb + BARS + 16, 4096); mbar_expect(sb + BARS + 32, 4096); mbar_expect(sb + BARS + 40, 4096); }
          mbar_arrive_cl(mapa(sb, a ^ 1) + BARS + 80);
        }
        __syncwarp();
        if (n) {
          vm_stage(n - 1);
          BAR_SYNC(B_W, 384);
        } else {
          BAR_SYNC(B_C, 320);
        }
        if (iw == 2) V_LOAD(n);
      }
#undef qd
#undef vd
    }
    { ROLE_REFRESH }
    vm_stage(63);
  } else {
    asm volatile("setmaxnreg.dec.sync.aligned.u32 %0;" ::"n"(RA_));
    if (blockIdx.x >= 128) { if (threadIdx.x == 256) rec_prefetch((const char*)wmod, w1, (const char*)x, wo); return; }
    ROLE_VARS
    uint32_t L16 = __shfl_sync(~0u, sb + (tid & 31) * 16, tid & 31);
    if (wid == 9) {
      for (int i = b * 80 + (tid & 31); i < b * 80 + 80; i += 32) ((uint4*)(xc + AR_OFF))[AR_ROW(i >> 6) * 64 + (i & 63)] = make_uint4(0, 0, 0, 0);
      if (b == 0) g_fin = 0;
      FENCE_ASYNC();
      __syncwarp();
      if (tid == 288) red_rlx(&g_hcnt);
    }
    if (tid == 256) {
      const int col = h * 128 + bb * 64;
#pragma unroll 1
      for (int c = 0; c < 12 + WIN; c++) {
        const uint32_t mb = sb + PACE + (c % WIN) * 8;
        if (c >= WIN) mbar_wait(mb, (c / WIN - 1) & 1);
        PT(16 + c);
        if (c == 3 + WIN) asm volatile("mbarrier.arrive.shared.b64 _,[%0];" ::"r"(sb + BARS + 88) : "memory");
        if (c >= 12) continue;
        mbar_expect(mb, 16384);
        if (c < 8) tma2d(sb + (c >> 2) * XB + (c & 3) * 16384, (c & 4) ? &mp.wk : &mp.wq, col, a * 512 + (c & 3) * 128, mb);
        else
#pragma unroll 1
          for (int i = (c & 1) * 8; i < (c & 1) * 8 + 8; i++) {
            const int w = (c - 8) >> 1;
            tma2d(i < NVR ? sb + MEM + (w * NVR + i) * 2048 : sb + WVS + (w * NVS + i - NVR) * 2048, &mp.wv, col, a * 512 + w * 256 + i * 16, mb);
          }
      }
      asm volatile("mbarrier.arrive.shared.b64 _,[%0];" ::"r"(wbar) : "memory");
      for (int c = 0; c < 4; c++) tma2d_pf(&mp.wo, j * 256 + c * 64, h * 128);
      for (int i = 0; i < 3; i++) asm volatile("mbarrier.inval.shared.b64 [%0];" ::"r"(sb + PACE + i * 8) : "memory");
    }
    __syncwarp();
    asm volatile("barrier.cluster.wait.aligned;" ::: "memory");
    CLUSTER_SYNC();
#define pr (L16 + SC)
    {
      const int lim = j * 8 + iw * 2 - (lane & 7) - (lane & 8) * 2;
      const bool mk = L16 & 256;
      const int rw = lane >> 2;
      sts4(L16 + TA + iw * 512,
           iw != 2 ? L16 + KT + (iw & 1) * 256 + (lane >> 4) * 256 : sb + RK + (L16 & 0x80) * 2 + ((L16 >> 1) & 0x80) + (L16 & 0x70),
           L16 + QT + (lane >> 3) * 384, sb + SC + min(lane >> 3, 2) * 256 + (L16 & 0x70) + iw * 4, L16 + (lane >> 4) * 256 + QT + (iw >> 1) * 1024 + (iw & 1) * 256);
      sts4(L16 + TA + 2048 + iw * 512, mk ? 0u : (lim < 0 ? 0xfc00u : 0u) | (lim < -1 ? 0xfc000000u : 0u),
           mk ? 0xfc00fc00u : (lim < 8 ? 0xfc00u : 0u) | (lim < 7 ? 0xfc000000u : 0u),
           ((h * 2 + (iw >> 1)) * 1024 + (j * 8 + rw) * 8 + (((iw & 1) * 4 + (lane & 3)) ^ rw)) * 16, sb + OT + iw * 512 + (L16 & 0x70) * 4 + ((L16 >> 3) & 0x30));
    }
    {
      const uint32_t xh = LO(xc) + h * 262144, xs = xh + X_SC + iw * 1024 + min(lane, 16 + (lane & 7)) * 8;
      sts4(L16 + TA + 4096 + iw * 512, xh + X_SC + j * 256 + iw * 64 + lpub, xs, dS, iw != 2 ? 0 : U_(SCS));
      sts1(L16 + TA + 12 + iw * 512, xs + X_TOK + j * 4096);
    }
    uint32_t tA = L16 + TA + iw * 512;
#define tw (tA - L16 != TA + 1024)
#define XP_(lo) mkp(lo, HI(xc))
    auto publish = [&](char* d, const uint2& w) { stg_b64(d, w.x, w.y); };
    BAR_SYNC(B_P, 384);
    for (int s = 0; s < 64; s++) {
      asm volatile("" : "+r"(L16), "+r"(tA));
      const uint32_t tag = ((s >> 1) + 1) & 1, ring = (s & 1) * X_RING;
      const uint4 t0 = lds4(tA);
      const uint4 tx = lds4(tA + 4096);
      const uint32_t xo = tx.x ^ ring, xs = tx.y ^ ring;
      const float gm = F_(tx.w);
      const uint32_t qA = t0.y + (ring >> 5);
      uint32_t c0;
      uint2 ts[4];
      uint4 v[4];
      uint32_t af[2][4], qt[4][4];
      {
        const uint32_t aA = t0.x + (tw ? ring >> 5 : 0);
        uint32_t ql[2][4], qr[2][4];
        uint2 pw_;
        float c[4] = {0, 0, 0, 0}, d[4] = {0, 0, 0, 0};
        if (s == PDS) asm volatile("griddepcontrol.launch_dependents;");
#pragma unroll
        for (int i = 0; i < 4; i++) ldsm4t(qt[i], qA + i * 128);
        mbar_wait(sb + BARS + 8, s & 1);
        TS(4);
        BAR_SYNC(B_E, 256);
#define PACK(c) make_uint2(pkh(fmaf(c[2], gm, c[0] * SCS), fmaf(c[3], gm, c[1] * SCS), tag), pkh(c[2] * SCS, c[3] * SCS, tag))
#define SMMA(x, t, q, i) mma16(x, af[t][0], af[t][1], af[t][2], af[t][3], q[t][i], q[t][i + 1])
        ldsm4t(ql[0], L16 + RQ); ldsm4t(ql[1], L16 + RQ + 1024); ldsm4t(af[0], aA); ldsm4t(af[1], aA + 1024);
        CONSUME(xo);
#define QSUM(t, i) addbf(addbf(ql[t][i], ql[t][i + 2]), addbf(qr[t][i], qr[t][i + 2]))
#define STAIL mma16(c, af[0][0], af[0][1], af[0][2], af[0][3], QSUM(0, 0), QSUM(0, 1)); mma16(d, af[1][0], af[1][1], af[1][2], af[1][3], QSUM(1, 0), QSUM(1, 1));
        if (tw) {
          mbar_wait(sb + BARS, s & 1);
          TS(8);
          ldsm4t(qr[0], L16 + RQ + 512); ldsm4t(qr[1], L16 + RQ + 1536);
          STAIL
          pw_ = make_uint2(pkh(c[0] + d[0], c[1] + d[1], tag), pkh(c[2] + d[2], c[3] + d[3], tag));
        } else {
          uint32_t ar[2][4];
          mbar_wait(sb + BARS, s & 1);
          ldsm4t(qr[0], L16 + RQ + 512); ldsm4t(ar[0], aA + 512); ldsm4t(qr[1], L16 + RQ + 1536); ldsm4t(ar[1], aA + 1536);
#pragma unroll
          for (int i = 0; i < 8; i++) af[i >> 2][i & 3] = addbf(af[i >> 2][i & 3], ar[i >> 2][i & 3]);
          STAIL
          pw_.x = pw_.y = pkh((c[0] + c[2]) + (d[0] + d[2]), (c[1] + c[3]) + (d[1] + d[3]), tag);
        }
        publish(XP_(xo), pw_);
        c0 = clk() + tx.z;
        TS(1);
      }
      uint2 r[4];
#define TOKS(i) { float e0[4] = {0, 0, 0, 0}, e1[4] = {0, 0, 0, 0}; \
        mma16(e0, af[0][0], af[0][1], af[0][2], af[0][3], qt[i][0], qt[i][1]); mma16(e1, af[0][0], af[0][1], af[0][2], af[0][3], qt[i + 1][0], qt[i + 1][1]); \
        mma16(e0, af[1][0], af[1][1], af[1][2], af[1][3], qt[i][2], qt[i][3]); mma16(e1, af[1][0], af[1][1], af[1][2], af[1][3], qt[i + 1][2], qt[i + 1][3]); \
        ts[i] = PACK(e0); ts[i + 1] = PACK(e1); }
      {
        float e[4][4];
#pragma unroll
        for (int i = 0; i < 4; i++) {
          e[i][0] = e[i][1] = e[i][2] = e[i][3] = 0.f;
          mma16(e[i], af[0][0], af[0][1], af[0][2], af[0][3], qt[i][0], qt[i][1]);
        }
#pragma unroll
        for (int i = 0; i < 4; i++) mma16(e[i], af[1][0], af[1][1], af[1][2], af[1][3], qt[i][2], qt[i][3]);
        SCHED_FENCE(55);
        if (s < 63) BAR_ARRIVE(B_S, 416);
        SCHED_FENCE(58);
        v[0] = lds4(tA + (VX0 - TA)); v[1] = lds4(tA + (VX0 - TA) + 2048); v[2] = lds4(tA + (VX1 - TA)); v[3] = lds4(tA + (VX1 - TA) + 2048);
#pragma unroll
        for (int i = 0; i < 4; i++) ts[i] = PACK(e[i]);
        while ((int)(clk() - c0) < 0) {}
        TS(5);
#pragma unroll
        for (int u = 0; u < 4; u++) r[u] = ldg_b64(XP_(xs) + u * 256);
        BAR_ARRIVE(B_S2, 256);
      }
      const uint32_t fn = (L16 & 256) ? 0xfc00fc00u : 0u;
      SCHED_FENCE(56);
      float4 e = softmax2<false>(r, 0, fn);
      const bool vbad = anybad(v[0].x, v[1].x, v[2].x, v[3].x, V_TAG(s));
      if (BADS(r)) {
        int it = 0;
        if (s > 8) sts1(tA + 4096 + 8, min(lds1(tA + 4096 + 8) + dX, 500));
        do {
          RP(1);
          if (++it > SPIN_LIMIT) __trap();
#pragma unroll
          for (int u = 0; u < 4; u++) r[u] = ldg_b64(XP_(xs) + u * 256);
        } while (BADS(r));
        e = softmax2<false>(r, 0, fn);
      }
      sts1(t0.z, pk(e.x, e.y)); sts1(t0.z + 128, pk(e.z, e.w));
#pragma unroll
      for (int i = 0; i < 4; i++) publish(XP_(xo) + X_TOK + i * 4096, ts[i]);
      TS(6);
      if (s < 63) BAR_SYNC(B_V, 512); else BAR_SYNC(B_V, 256);
      uint32_t O[4];
      uint4 vn[2];
      {
        uint32_t p[4], pm;
        ldsm4t(p, pr);
        asm volatile("ldmatrix.sync.aligned.m8n8.x1.trans.shared.b16 {%0},[%1];" : "=r"(pm) : "r"(pr + 512) : "memory");
        vn[0] = lds4(tA + (VN - TA)); vn[1] = lds4(tA + (VN - TA) + 2048);
        pv_mem(p, pm, v, vn, O);
        if (vbad) {
          int it = 0;
          do {
            if (++it > SPIN_LIMIT) __trap();
#pragma unroll
            for (int u = 0; u < 4; u++) v[u] = ldg_b128(XP_((LO(xc) + (lds1(sb + PACE + 24) >> 2) * 262144 + ((tA - L16 - TA) >> 9) * XC + l16) ^ V_RING(s)) + X_VX(u));
          } while (anybad(v[0].x, v[1].x, v[2].x, v[3].x, V_TAG(s)));
          pv_mem(p, pm, v, vn, O);
        }
      }
      stsm4(tA + (OB - TA), O[0], O[1], O[2], O[3]);
      if (s < 63) BAR_ARRIVE(B_O, 416);
      TS(2);
      c0 = clk() + dG;
      SCHED_FENCE(60);
      if (tA == sb + TA) mbar_expect(sb + BARS, 2048);
      const uint32_t vs[4] = {addbf(vn[0].x, vn[0].z), addbf(vn[0].y, vn[0].w), addbf(vn[1].x, vn[1].z), addbf(vn[1].y, vn[1].w)};
      {
        const char* xt = XP_(lds1(tA + 12) ^ ring);
        const uint2 t1 = lds2u(tA + 2048);
        const uint32_t pw = lds1(tA + 8);
        uint2 rt[4];
        CONSUME(LO(xt) ^ t1.x ^ pw);
        while ((int)(clk() - c0) < 0) {}
        int it = 0;
        do {
          if (++it > SPIN_LIMIT) __trap();
#pragma unroll
          for (int u = 0; u < 4; u++) rt[u] = ldg_b64(xt + u * 256);
        } while (BADS(rt));
        const float4 et = softmax2<true>(rt, t1.x, t1.y);
        sts1(pw + 1024, pk(et.x, et.y)); sts1(pw + 1024 + 128, pk(et.z, et.w));
      }
      s = PIN(s);
      BAR_SYNC(B_SC, 128);
      {
        uint32_t Ot[4], p[4], pm;
        const uint2 t2 = lds2u(tA + 2048 + 8);
        ldsm4t(p, pr + 1024);
        asm volatile("ldmatrix.sync.aligned.m8n8.x1.trans.shared.b16 {%0},[%1];" : "=r"(pm) : "r"(pr + 1024 + 512) : "memory");
        char* od = (char*)g_O + ((s >> 2) * 1048576 + (s & 3) * 4096) + t2.x;
        CONSUME(LO(od) ^ HI(od) ^ pm ^ p[3]);
        TS(9);
        if (s < 62) BAR_SYNC(B_P, 384);
        pv_tok(p, pm, v, vs, Ot);
        asm volatile("stmatrix.sync.aligned.m8n8.x4.trans.shared.b16 [%0],{%1,%2,%3,%4};" ::"r"(t2.y), "r"(Ot[0]), "r"(Ot[1]), "r"(Ot[2]), "r"(Ot[3]) : "memory");
        __syncwarp();
        *(uint4*)od = lds4(tA + (OT - TA));
      }
    }
    FENCE_ASYNC();
    BAR_SYNC(B_SC, 128);
    if (tA == sb + TA) red_rlx(&g_fin);
  }
  __syncwarp();
  CLUSTER_SYNC();
  PH(5);
}
#undef wg
#undef iw
#undef h
#undef j
#undef a
#undef bb
#undef oi
#undef owner
#undef vfin
#undef pr
#undef PIN
#undef XP_
#undef tw
#undef is7
#undef REFRESH
#undef lane
#undef l16
#undef lrow
#undef lar
#undef lpub

namespace ffn {
constexpr uint32_t BR = 98304;
constexpr uint32_t STG = 196608;
constexpr uint32_t PRM = 229376;
constexpr uint32_t BARS = PRM + 2816;
constexpr uint32_t SMEM = BARS + 18 * 8;
}
#define Y_TILE(rb, kt) (((ALIAS & 1) ? g_h : g_h2) + ((rb) * 16 + (kt)) * 1024)
#define U_TILE(rb, kt) ((ALIAS & 2) ? g_O + ((rb) * 64 + (kt)) * 1024 : g_U + ((rb) * 56 + (kt)) * 1024)
struct FfnMaps { CUtensorMap wo, w1a, w1b, w2, x, out; };

template <int N>
__device__ __forceinline__ void wg_ss(float* d, uint64_t a, uint64_t b, int sd) {
  if (N == 128) wgmma_ss_n128(d, a, b, sd);
  if (N == 192) wgmma_ss_n192(d, a, b, sd);
}
template <int N>
__device__ __forceinline__ void acc_fence(float* d) {
#pragma unroll
  for (int i = 0; i < N; i++) asm volatile("" : "+f"(d[i])::"memory");
}
#define UNPK8(d, v) do { (d)[0] = blo(v.x); (d)[1] = bhi(v.x); (d)[2] = blo(v.y); (d)[3] = bhi(v.y); (d)[4] = blo(v.z); (d)[5] = bhi(v.z); (d)[6] = blo(v.w); (d)[7] = bhi(v.w); } while (0)
struct FfnPipe {
  uint32_t full, emp, ph, aoff;
  int st, sB, prev;
  bool leader;
  template <int N>
  __device__ __forceinline__ void issue(float* acc, bool first, uint32_t a = 0) {
    mbar_wait(full + st * 8, ph);
    const uint64_t da = mkdesc((a ? a : 1024 + st * 16384) + aoff, 16, 1024), db = mkdesc(1024 + ffn::BR + sB * (N * 128), 8192, 1024);
    WG_FENCE();
#pragma unroll
    for (int j = 0; j < ((FDB & 1) ? 1 : 4); j++) wg_ss<N>(acc, da + j * 2, db + j * 128, j || !first);
    WG_COMMIT();
    if (++sB == 768 / N) sB = 0;
  }
  __device__ __forceinline__ void release() { if (leader) mbar_arrive(emp + prev * 8); }
  __device__ __forceinline__ void next() { prev = st; if (++st == 6) { st = 0; ph ^= 1; } }
  __device__ __forceinline__ void retire() { WG_WAIT(1); release(); next(); }
};
__device__ __forceinline__ float gelu_h(float hx) {
  float u = hx * fmaf(hx * hx, 8.f * 0.0356774081f, 2.f * 0.7978845608f), t;
  if (FDB & 4) return hx;
  if (FDB & 2) t = u; else
  asm("tanh.approx.f32 %0,%1;" : "=f"(t) : "f"(u));
  return fmaf(hx, t, hx);
}
struct FfnEpi {
  uint32_t st2, cc, flip, staged, l0;
  uint2 c;
  float n0, n1, s0, s1;
  __device__ __forceinline__ void flush(uint32_t r) {
    __syncwarp();
    asm volatile("{.reg .pred p; setp.ne.u32 p,%1,0; @p mbarrier.arrive.shared.b64 _,[%0];}" ::"r"(staged + (flip >> 11)), "r"(l0 & r) : "memory");
    flip ^= r << 14;
  }
  __device__ __forceinline__ void half(const float* d, int J, int r) {
#define PRE(i, n, c1, c2) gelu_h(fmaf(r ? d[4 + i] : d[i], i < 2 ? s0 : s1, fmaf(n, c1, c2)))
    asm volatile("stmatrix.sync.aligned.m8n8.x2.shared.b16 [%0],{%1,%2};" ::"r"((st2 ^ ((J & 3) * 32 + r * 16)) + flip),
                 "r"(pk(PRE(0, n0, blo(c.x), blo(c.y)), PRE(1, n0, bhi(c.x), bhi(c.y)))), "r"(pk(PRE(2, n1, blo(c.x), blo(c.y)), PRE(3, n1, bhi(c.x), bhi(c.y)))) : "memory");
#undef PRE
    if ((J & 3) == 3) flush(r);
    cc += r ? 56 : 8;
    c = lds2u(cc);
  }
};

__global__ void __launch_bounds__(384, 1)
k_ffn(const __grid_constant__ FfnMaps mp, const bf16* __restrict__ b2) {
  using namespace ffn;
  extern __shared__ __align__(1024) char smem[];
  const uint32_t sb = (uint32_t)__cvta_generic_to_shared(smem);
  if (sb != 1024) __trap();
  const int tid = threadIdx.x, lane = tid & 31, wg = __shfl_sync(~0u, tid >> 7, 0);
  const uint32_t full = sb + BARS, emp = full + 48, xbar = full + 96, staged = full + 104, tile = full + 136;
  uint32_t fin = 0;
  if (tid >= 288 && tid < 320) fin = ld_acq(&g_fin);
  if (tid < 32) {
    unsigned sm, v = 0;
    asm("mov.u32 %0,%%smid;" : "=r"(sm));
    if (tid == 0) {
      v = atomicExch(&g_slot[sm & 255], 0);
      for (int i = 0; i < 6; i++) { mbar_init(full + i * 8, 1); mbar_init(emp + i * 8, 2); }
      mbar_init(xbar, 2);
      for (int i = 0; i < 2; i++) { mbar_init(staged + i * 8, 8); mbar_init(staged + 16 + i * 8, 1); }
      FENCE_ASYNC_SMEM();
    }
    v = __shfl_sync(~0u, v, 0);
    if (!v) {
      wait_cnt(&g_fin, 128);
      for (int it = 0; !v; it++) {
        const uint4 a = ldg_rlx4(g_slot + tid * 8), b = ldg_rlx4(g_slot + tid * 8 + 4);
        const uint32_t open = __ballot_sync(~0u, a.x | a.y | a.z | a.w | b.x | b.y | b.z | b.w);
        if (!open) break;
        if (it < 16) { __nanosleep(500); continue; }
        if (tid == __ffs(open) - 1) v = atomicExch(&g_slot[tid * 8 + (a.x ? 0 : a.y ? 1 : a.z ? 2 : a.w ? 3 : b.x ? 4 : b.y ? 5 : b.z ? 6 : 7)], 0);
        v = __shfl_sync(~0u, v, __ffs(open) - 1);
      }
    }
    if (tid == 0) sts1(tile, v);
  }
  if (tid == 256) asm volatile("prefetch.tensormap [%0];" ::"l"(&mp.wo) : "memory");
  __syncthreads();
  const int bid = __shfl_sync(~0u, lds1(tile), 0) - 1;
  if (bid < 0) return;
  PH(6);
  FT(1);
  const int rb = bid >> 3, nb = bid & 7;
  unsigned* cnt = g_cnt + rb * 128;
  if (wg == 2) {
    asm volatile("setmaxnreg.dec.sync.aligned.u32 " FRP ";");
    const int pw = __shfl_sync(~0u, (tid >> 5) & 3, 0);
    uint32_t ws = emp, wp = 1, fs = full;
    auto wait_free = [&]() { mbar_wait_q(ws, wp); ws += 8; if (ws == emp + 48) { ws = emp; wp ^= 1; } };
    auto step = [&]() { fs += 8; if (fs == full + 48) fs = full; };
#define K3(c) ((0x65230 >> (c) * 4) & 7)
#define KC(k) ((k) < 2 ? nb * 2 + (k) : (k) < 9 ? ((k) - 2 + ((k) - 2 >= nb)) * 2 : ((k) - 9 + ((k) - 9 >= nb)) * 2 + 1)
    if (pw == 0) {
      uint32_t d = sb + BR + 32768;
      auto put = [&](const CUtensorMap* m, int k, int c) {
        e_expect_tma3d(d, m, k * 64, c, fs, 32768);
        step();
        d += 16384;
        if (d == sb + STG) d = sb + BR;
      };
      int n = 0;
      auto stage_free = [&]() { if (!(n & 7) && n < 56) mbar_wait_q(staged + 16 + (n & 8), (n >> 4) & 1); n++; };
      FTP(3);
#pragma unroll 1
      for (int k = 0; k < 66; k++) { wait_free(); if (k < 64) put(&mp.wo, k, nb * 2); }
#pragma unroll 1
      for (int k = 0; k < 16; k++) {
        const int kt = KC(k);
        wait_free();
        e_expect_tma3d(sb + BR + (k & 3) * 24576, &mp.w1b, kt * 64, nb * 7, fs, k < 2 ? 24576 : 40960);
        step();
      }
#pragma unroll 1
      for (int k = 0; k < 32; k++) { stage_free(); if (k != 5 && k != 6) wait_free(); put(&mp.w1a, k & 15, nb * 7 + 3 + (k >> 4) * 2); }
#pragma unroll 1
      for (int c = 0; c < 5; c++)
#pragma unroll 1
        for (int k = K3(c), i = 0; k < 56; k += c < 2 && (i ^= 1) ? 1 : c < 2 ? 6 : 7) { stage_free(); wait_free(); put(&mp.w2, k, nb * 2); }
    } else if (pw == 1) {
      FTP(5);
      if (fin < 128) wait_cnt(&g_fin, 128);
      FTP(6);
      uint32_t d = sb;
      auto put = [&](const uint4* A, bool ld) {
        wait_free();
        if (ld) e_bulk_ld(d, A, 16384, fs);
        step();
        d += 16384;
        if (d == sb + BR) d = sb;
      };
      const uint4* A = g_O + rb * 65536;
#pragma unroll 1
      for (int k = 0; k < 66; k++) put(A + k * 1024, k < 64);
      A = Y_TILE(rb, 0);
      uint32_t ready = 0;
#pragma unroll 1
      for (int k = 2; k < 48; k++) {
        const int kt = k < 16 ? KC(k) : k & 15;
        for (int it = 0; !(ready >> ((kt >> 1) + (kt & 1) * 8) & 1); it++) {
          ready = __ballot_sync(~0u, ldg_rlx1(cnt + (lane & 7)) & ((lane & 8) ? 1 : 0x10000));
          if (it > SPIN_LIMIT) __trap();
        }
        if (k == 2) FTP(75);
        put(A + kt * 1024, true);
      }
      A = U_TILE(rb, 0);
#pragma unroll 1
      for (int c = 0; c < 5; c++) {
        for (int it = 0; ldg_rlx1(cnt + 32 + c) < 8; it++) if (it > SPIN_LIMIT) __trap();
#pragma unroll 1
        for (int k = K3(c), i = 0; k < 56; k += c < 2 && (i ^= 1) ? 1 : c < 2 ? 6 : 7) put(A + k * 1024, true);
      }
    } else if (pw == 2) {
      for (int i = 0; i < XDL; i++) {
        mbar_wait_q(emp, i & 1);
        if (XPF && i == 1 && lane < 2) tma2d_pf(&mp.x, nb * 128 + lane * 64, rb * 128);
      }
      if (lane == 0) {
        mbar_expect(xbar, 32768);
        tma2d(sb + STG, &mp.x, nb * 128, rb * 128, xbar);
        tma2d(sb + STG + 16384, &mp.x, nb * 128 + 64, rb * 128, xbar);
      }
      asm volatile("griddepcontrol.wait;" ::: "memory");
      if (lane < 16) g_modp[bid * 16 + lane] = make_uint4(0, 0, 0, 0);
      if (lane >= 16 && bid == 0) { g_hcnt = 0; g_mcnt = 0; g_hf[lane & 3] = 0; }
      if (lane == 0) {
#pragma unroll 1
        for (int g = 1; g < 9; g++) {
          if (g == 1) mbar_wait(staged + 8, 0); else { mbar_wait_q(staged + (g & 1) * 8, (g >> 1) & 1); FENCE_ASYNC_SMEM(); }
          bulk_st(g == 1 ? Y_TILE(rb, nb * 2 + 1) : U_TILE(rb, nb * 7 + ((0x652431000ull >> g * 4) & 7)), sb + STG + (g & 1) * 16384, 16384);
          BULK_COMMIT();
          if (g != 2 && g != 4) { BULK_WAIT(0); red_rlx(g == 1 ? cnt + nb : cnt + 32 + (g < 6 ? g >> 2 : g - 4)); }
          BULK_WAIT_READ(0);
          mbar_arrive(staged + 16 + (g & 1) * 8);
        }
      }
    } else {
      const uint32_t prm = sb + PRM, pp = prm + (lane >> 3) * 64 + (lane & 1) * 32 + (lane & 6) * 2;
      const uint2 v2 = ((const uint2*)(b2 + nb * 128))[lane];
      sts1(pp + 768, v2.x); sts1(pp + 784, v2.y);
      asm volatile("griddepcontrol.wait;" ::: "memory");
      const float4* md = (const float4*)(g_mod + nb * 128) + lane;
      { const float4 ga = md[512]; sts1(pp, pk(ga.x, ga.y)); sts1(pp + 16, pk(ga.z, ga.w)); }
      { const float4 cb = md[1024]; sts1(pp + 256, pk(1.f + cb.x, 1.f + cb.y)); sts1(pp + 272, pk(1.f + cb.z, 1.f + cb.w)); }
      { const float4 gb = md[1280]; sts1(pp + 512, pk(gb.x, gb.y)); sts1(pp + 528, pk(gb.z, gb.w)); }
#pragma unroll 1
      for (int i = lane; i < 112; i += 32) { const uint4 c = g_cc[nb * 112 + i]; sts4(prm + 1024 + i * 16, c.x, c.y, c.z, c.w); }
      __syncwarp();
      if (lane == 0) {
        mbar_arrive(xbar);
        mbar_wait(staged, 0);
        bulk_st(Y_TILE(rb, nb * 2), sb + STG, 16384);
        BULK_COMMIT(); BULK_WAIT(0);
        asm volatile("red.relaxed.gpu.global.add.u32 [%0],0x10000;" ::"l"(cnt + nb) : "memory");
        mbar_arrive(staged + 16);
      }
      __syncwarp();
      mbar_wait_q(staged + 24, 0);
      mbar_wait_q(emp + 40, 0);
#pragma unroll 1
      for (int i = 0; i < 4; i++) {
        const uint4* sp = g_stat + (rb * 128 + i * 32 + lane) * 4;
        uint4 v[4];
        for (int it = 0;; it++) {
          uint32_t m = 0;
#pragma unroll
          for (int u = 0; u < 4; u++) { v[u] = ldg_rlx4(sp + u); m = max(max(m, max(v[u].x, v[u].y)), max(v[u].z, v[u].w)); }
          if (!__any_sync(~0u, m == ~0u)) break;
          if (it > SPIN_LIMIT) __trap();
        }
        float m = 0, q = 0;
#pragma unroll
        for (int u = 0; u < 4; u++) m += F_(v[u].x) + F_(v[u].z);
        m *= 0.125f;
#pragma unroll
        for (int u = 0; u < 4; u++) { const float a = F_(v[u].x) - m, b = F_(v[u].z) - m; q += F_(v[u].y) + F_(v[u].w) + 128.f * (a * a + b * b); }
        const float r = 0.5f * rsqrtf(q * (1.f / 1024) + 1e-5f);
        sts2(sb + STG + 16384 + (i * 32 + lane) * 8, U_(r), U_(-m * r));
      }
      __syncwarp();
      if (lane < 2) mbar_arrive(xbar);
    }
  } else {
    asm volatile("setmaxnreg.inc.sync.aligned.u32 " FRC ";");
    const int w = (tid >> 5) & 3, q = lane & 3;
    const uint32_t prm = sb + PRM + q * 16;
    const int row0 = wg * 64 + w * 16;
    FfnPipe p;
    p.full = full; p.emp = emp; p.ph = 0; p.aoff = wg * 8192; p.st = 0; p.sB = 2; p.prev = 0; p.leader = (tid & 127) == 0;
    FfnEpi e;
    const uint32_t stg = sb + STG + row0 * 128;
    e.st2 = stg + (lane & 15) * 128 + ((lane & 7) << 4);
    e.cc = sb + PRM + 1024 + q * 16; e.flip = 0; e.staged = staged; e.l0 = lane == 0;
    const uint32_t stw = e.st2 ^ (lane & 16);
    uint32_t x1[32];
    uint4* sp = g_stat + (rb * 128 + row0 + (lane >> 2)) * 4;
    float old[96], r0_, r1_;
    {
      float acc[64];
      p.issue<128>(acc, true); FT(8); p.next();
#pragma unroll 1
      for (int k = 1; k < 64; k++) { p.issue<128>(acc, false); FT(8 + k); p.retire(); }
      float xf[64], gf[32];
      uint32_t cb[16];
      mbar_wait(xbar, 0);
#pragma unroll
      for (int j = 0; j < 8; j++) {
        uint32_t xv[4];
        ldsm4(xv, (stw ^ ((j & 3) * 32)) + (j >> 2) * 16384);
#pragma unroll
        for (int i = 0; i < 4; i++) { xf[j * 8 + i * 2] = blo(xv[i]); xf[j * 8 + i * 2 + 1] = bhi(xv[i]); }
      }
#pragma unroll
      for (int i = 0; i < 4; i++) {
        const uint4 g = lds4(prm + i * 64), c = lds4(prm + 256 + i * 64);
        UNPK8(gf + i * 8, g);
        cb[i * 4] = c.x; cb[i * 4 + 1] = c.y; cb[i * 4 + 2] = c.z; cb[i * 4 + 3] = c.w;
      }
      acc_fence<64>(xf); acc_fence<32>(gf);
      WG_WAIT(0);
      p.release();
      acc_fence<64>(acc);
      PH(7); FT(72);
#pragma unroll
      for (int j = 0; j < 8; j++) {
        uint32_t* o = x1 + j * 4;
#pragma unroll
        for (int i = 0; i < 4; i++)
          o[i] = pk(fmaf(acc[j * 8 + i * 2], gf[j * 4 + (i & 2)], xf[j * 8 + i * 2]), fmaf(acc[j * 8 + i * 2 + 1], gf[j * 4 + (i & 2) + 1], xf[j * 8 + i * 2 + 1]));
        stsm4((stw ^ ((j & 3) * 32)) + (j >> 2) * 16384, mulbf(o[0], cb[j * 2]), mulbf(o[1], cb[j * 2]), mulbf(o[2], cb[j * 2 + 1]), mulbf(o[3], cb[j * 2 + 1]));
        if ((j & 3) == 3) { FENCE_ASYNC_SMEM(); e.flush(1); }
      }
      if (wg) BAR_SYNC(2, 128); else BAR_SYNC(3, 128);
    }
    PH(8); FT(73);
    float acc[64];
    {
      float* accC = old;
      p.sB = 0;
      p.issue<192>(accC, true, 1024 + STG); FT(80); p.next();
      p.issue<192>(accC, false, 1024 + STG + 16384); FT(81);
      FT(78);
      float s0 = 0, s1 = 0;
#define X1_FENCE _Pragma("unroll") for (int j = 0; j < 32; j++) asm volatile("" : "+r"(x1[j]));
      X1_FENCE
#pragma unroll
      for (int j = 0; j < 16; j++) { s0 += blo(x1[j * 2]) + bhi(x1[j * 2]); s1 += blo(x1[j * 2 + 1]) + bhi(x1[j * 2 + 1]); }
      s0 += __shfl_xor_sync(~0u, s0, 1); s1 += __shfl_xor_sync(~0u, s1, 1);
      s0 += __shfl_xor_sync(~0u, s0, 2); s1 += __shfl_xor_sync(~0u, s1, 2);
      s0 *= 1.f / 128; s1 *= 1.f / 128;
      float q0 = 0, q1 = 0;
      X1_FENCE
#pragma unroll
      for (int j = 0; j < 16; j++) {
        const float a = blo(x1[j * 2]) - s0, b = bhi(x1[j * 2]) - s0, c = blo(x1[j * 2 + 1]) - s1, d = bhi(x1[j * 2 + 1]) - s1;
        q0 += a * a + b * b; q1 += c * c + d * d;
      }
      q0 += __shfl_xor_sync(~0u, q0, 1); q1 += __shfl_xor_sync(~0u, q1, 1);
      q0 += __shfl_xor_sync(~0u, q0, 2); q1 += __shfl_xor_sync(~0u, q1, 2);
      if (q < 2) {
        uint32_t m = __float_as_uint(q ? s1 : s0), v = __float_as_uint(q ? q1 : q0);
        if (m == ~0u) m = 0x7fffffffu;
        if (v == ~0u) v = 0x7fffffffu;
        stg_rlx2((uint2*)(sp + q * 32) + nb, m, v);
      }
      X1_FENCE
      p.retire();
#pragma unroll 1
      for (int k = 2; k < 15; k++) { p.issue<192>(accC, false); FT(80 + k); p.retire(); }
      p.issue<192>(accC, false); FT(95);
      mbar_wait(xbar, 1);
      const float2 u0 = lds2f(sb + STG + 16384 + (row0 + (lane >> 2)) * 8), u1 = lds2f(sb + STG + 16384 + (row0 + (lane >> 2)) * 8 + 64);
      r0_ = u0.x; e.n0 = u0.y; r1_ = u1.x; e.n1 = u1.y;
      e.c = lds2u(e.cc);
      p.retire();
      e.s0 = r0_; e.s1 = r1_;
    }
    PH(9);
    {
      auto pair = [&](int J, bool first, int fo) {
#pragma unroll 1
        for (int r = 0; r < 2; r++) { p.issue<128>(acc, first && !r); FT(fo + r); p.retire(); acc_fence<8>(old + J * 8); e.half(old + J * 8, J, r); }
      };
#pragma unroll 1
      for (int i = 0; i < 3; i++) {
        if (i == 2) {
          e.s0 = r0_; e.s1 = r1_;
#pragma unroll
          for (int J = 8; J < 12; J++) pair(J, J == 8, 128 + (J - 8) * 2);
          e.cc += 512; e.c = lds2u(e.cc);
          e.s0 = e.s1 = 1.f;
        }
#pragma unroll
        for (int J = 0; J < 8; J++) pair(J, J == 0 && i < 2, 96 + i * 16 + (i >> 1) * 8 + J * 2);
        if (i == 2) break;
        e.cc += i ? -768 : 256; e.c = lds2u(e.cc);
        WG_WAIT(0);
        acc_fence<64>(acc);
#pragma unroll
        for (int k = 0; k < 64; k++) old[k] = acc[k] * ((k & 2) ? r1_ : r0_);
        acc_fence<64>(old);
        e.s0 = e.s1 = 1.f;
        PH(10 + i);
      }
#pragma unroll 1
      for (int k = 24; k < 56; k++) { p.issue<128>(acc, false); FT(128 + k); p.retire(); }
      float xf[64], gf[32];
#pragma unroll
      for (int i = 0; i < 4; i++) {
        const uint4 g = lds4(prm + 512 + i * 64), h = lds4(prm + 768 + i * 64);
        float hf[8];
        UNPK8(gf + i * 8, g); UNPK8(hf, h);
#pragma unroll
        for (int u = 0; u < 8; u++) {
          const int c = (u >> 2) * 4 + (u & 2);
          xf[i * 16 + u * 2] = fmaf(gf[i * 8 + c], hf[c], blo(x1[i * 8 + u])); xf[i * 16 + u * 2 + 1] = fmaf(gf[i * 8 + c + 1], hf[c + 1], bhi(x1[i * 8 + u]));
        }
      }
      acc_fence<64>(xf); acc_fence<32>(gf);
      mbar_wait(staged + 24, 1);
      mbar_wait(staged + 16, 0);
      WG_WAIT(0);
      acc_fence<64>(acc);
      PH(13); FT(184);
#pragma unroll
      for (int j = 0; j < 8; j++) {
        uint32_t o[4];
#pragma unroll
        for (int i = 0; i < 4; i++)
          o[i] = pk(fmaf(acc[j * 8 + i * 2], gf[j * 4 + (i & 2)], xf[j * 8 + i * 2]), fmaf(acc[j * 8 + i * 2 + 1], gf[j * 4 + (i & 2) + 1], xf[j * 8 + i * 2 + 1]));
        stsm4((stw ^ ((j & 3) * 32)) + (j >> 2) * 16384, o[0], o[1], o[2], o[3]);
        if ((j & 3) == 3) {
          FENCE_ASYNC_SMEM();
          __syncwarp();
          if (lane == 0) { tma2d_st(&mp.out, nb * 128 + (j >> 2) * 64, rb * 128 + row0, stg + (j >> 2) * 16384); BULK_COMMIT(); }
        }
      }
      if (lane == 0) BULK_WAIT_READ(0);
      __syncwarp();
    }
  }
  PH(14); FT(185);
}

typedef CUresult (*EncFn)(CUtensorMap*, CUtensorMapDataType, cuuint32_t, void*, const cuuint64_t*, const cuuint64_t*, const cuuint32_t*,
                          const cuuint32_t*, CUtensorMapInterleave, CUtensorMapSwizzle, CUtensorMapL2promotion, CUtensorMapFloatOOBfill);
static void map2d(EncFn enc, CUtensorMap* m, const void* p, int rows, int cols, int boxRows) {
  cuuint64_t d[2] = {(cuuint64_t)cols, (cuuint64_t)rows}, s[1] = {(cuuint64_t)cols * 2};
  cuuint32_t b[2] = {64, (cuuint32_t)boxRows}, e[2] = {1, 1};
  enc(m, CU_TENSOR_MAP_DATA_TYPE_BFLOAT16, 2, (void*)p, d, s, b, e, CU_TENSOR_MAP_INTERLEAVE_NONE, CU_TENSOR_MAP_SWIZZLE_128B,
      CU_TENSOR_MAP_L2_PROMOTION_L2_128B, CU_TENSOR_MAP_FLOAT_OOB_FILL_NONE);
}
static void map3d(EncFn enc, CUtensorMap* m, const void* p, int rows, int cols, int nch) {
  cuuint64_t d[3] = {64, (cuuint64_t)rows, (cuuint64_t)(cols / 64)}, s[2] = {(cuuint64_t)cols * 2, 128};
  cuuint32_t b[3] = {64, 64, (cuuint32_t)nch}, e[3] = {1, 1, 1};
  enc(m, CU_TENSOR_MAP_DATA_TYPE_BFLOAT16, 3, (void*)p, d, s, b, e, CU_TENSOR_MAP_INTERLEAVE_NONE, CU_TENSOR_MAP_SWIZZLE_128B,
      CU_TENSOR_MAP_L2_PROMOTION_L2_128B, CU_TENSOR_MAP_FLOAT_OOB_FILL_NONE);
}

extern "C" void kernel_launch(void* const* d_in, const int* in_sizes, int n_in, void* d_out, int out_size) {
  const bf16* x = (const bf16*)d_in[0];
  const bf16* mem0 = (const bf16*)d_in[1];
  void* fn = nullptr;
  cudaDriverEntryPointQueryResult qr;
  cudaGetDriverEntryPoint("cuTensorMapEncodeTiled", &fn, cudaEnableDefault, &qr);
  EncFn enc = (EncFn)fn;
  FfnMaps fm = {};
  map3d(enc, &fm.wo, d_in[5], 4096, 1024, 2);
  map3d(enc, &fm.w1a, d_in[8], 1024, 3584, 2);
  map3d(enc, &fm.w1b, d_in[8], 1024, 3584, 3);
  map3d(enc, &fm.w2, d_in[10], 3584, 1024, 2);
  map2d(enc, &fm.x, x, 2048, 1024, 128);
  map2d(enc, &fm.out, d_out, 2048, 1024, 16);
  RecMaps rm = {};
  map2d(enc, &rm.wq, d_in[2], 1024, 4096, 128);
  map2d(enc, &rm.wk, d_in[3], 1024, 4096, 128);
  map2d(enc, &rm.wv, d_in[4], 1024, 4096, 16);
  map2d(enc, &rm.wo, d_in[5], 4096, 1024, 128);
  char* xc = nullptr;
  cudaGetSymbolAddress((void**)&xc, g_xc);
  xc += (0 - (uintptr_t)xc) & 0x1FFFFF;
  {
    cuuint64_t d[3] = {512, ARV ? 8 : 128, ARV ? 128 : 6}, sd[2] = {1024, ARV ? 8192 : 131072};
    cuuint32_t bi[3] = {64, 8, 5}, e[3] = {1, 1, 1};
    enc(&rm.ari, CU_TENSOR_MAP_DATA_TYPE_BFLOAT16, 3, xc + AR_OFF, d, sd, bi, e, CU_TENSOR_MAP_INTERLEAVE_NONE, CU_TENSOR_MAP_SWIZZLE_NONE,
        CU_TENSOR_MAP_L2_PROMOTION_NONE, CU_TENSOR_MAP_FLOAT_OOB_FILL_NONE);
  }
  cudaFuncSetAttribute(k_ffn, cudaFuncAttributeMaxDynamicSharedMemorySize, ffn::SMEM);
  cudaFuncSetAttribute(k_rec, cudaFuncAttributeMaxDynamicSharedMemorySize, rec::SMEM);
  cudaStream_t st = cudaStreamPerThread;
  int dF = 450, dA = 2700, dS = 300, dM = 120, dG = 350, dP = 24, dX = 48, dD = 350, dZ = 0, dZ2 = 1, dV = 370, dX2 = 0;
  k_rec<<<132, 512, rec::SMEM, st>>>(rm, mem0, x, (const bf16*)d_in[12], (const bf16*)d_in[13], (const char*)d_in[8], (const bf16*)d_in[9],
                                     (const char*)d_in[5], xc, dF, dA, dS, dM, dG, dP, dX, dD, dZ, dZ2, dV, dX2);
  cudaLaunchConfig_t cfg = {};
  cfg.gridDim = dim3(132); cfg.blockDim = dim3(384); cfg.dynamicSmemBytes = ffn::SMEM; cfg.stream = st;
  cudaLaunchAttribute at[1];
  at[0].id = cudaLaunchAttributeProgrammaticStreamSerialization;
  at[0].val.programmaticStreamSerializationAllowed = 1;
  cfg.attrs = at; cfg.numAttrs = 1;
  cudaLaunchKernelEx(&cfg, k_ffn, fm, (const bf16*)d_in[11]);
}
```

```cpp
#include <cuda_runtime.h>
#include <cuda.h>
#include <cuda_bf16.h>
#include <stdint.h>

typedef __nv_bfloat16 bf16;

__device__ __align__(16) float g_mod[6144];
__device__ __align__(1024) uint4 g_modp[4 * 512];
__device__ unsigned g_hcnt;
__device__ unsigned g_hf[4];
__device__ __align__(1024) uint4 g_h[2048 * 1024 / 8];
__device__ __align__(1024) uint4 g_O[2048 * 4096 / 8];
__device__ __align__(1024) uint4 g_h2[2048 * 1024 / 8];
__device__ __align__(1024) uint4 g_U[2048 * 3584 / 8];
__device__ __align__(1024) uint4 g_stat[2048 * 4];
__device__ __align__(1024) unsigned g_cnt[16 * 4 * 32];
__device__ unsigned g_mcnt;
__device__ unsigned g_slot[256];
__device__ unsigned g_fin;
__device__ __align__(16) uint4 g_cc[224 * 4];
__device__ __align__(1024) uint4 g_xc[44 * 16384];
__device__ __align__(1024) unsigned g_tm[4 * 256];
#define FT(i)
#define FTP(i)
#define PT(i)
#define PH(i)
#define RP(i)
#define RPN(i, s)
#define TSV(i, v)
#define TS(i)

#define WIN 3
#define FRC "232"
#define FRP "40"
#define YR 1
#define XPK 0
#define NFA 1
#define PINM 1
#define FMAP (((g >> 2) * 4 + m) * 8 + (g & 3) * 2 + (blockIdx.x & 1))
#define FDB 0
#define ALIAS 3
#define EF 0
#define XPF 0
#define PFT 150000
#define PFS 104
#define PF0 13000
#define PFD 128
#define ARV 0
#define HV 0
#define XE 0
#define NF 2
#define NB0 4
#define PV0 4
#define T1L 1
#define NW0 5
#define FQM 0
#define FQ(k) do { if ((FQM >> ((k) - 48)) & 1) SCHED_FENCE(k); } while (0)
#define SWP 1
#define VCO 0
#define AV 0
#define PKE 0
#define XDL 6
#define QW 0
#define PDS 61
#define P_NVR 5
#define P_NVP 2
#define P_NWP 9
#define P_NW1 7
#define RF_ 208
#define PSV 1
#define RA_ (488 - 2 * RF_)
#define XI 5
#define XL 1
#define WCH 2
#define HX 0
#define VB 1
#define TP 0
#define CKI 0
#define NOP_ 2
#define KVO 0
#define NDL 3
#define AM 0
#define XM 3
#define XP 0
#define SPIN_LIMIT (1 << 20)
__device__ __forceinline__ uint64_t mkdesc(uint32_t addr, uint32_t lbo, uint32_t sbo) {
  return (uint64_t)((addr & 0x3FFFF) >> 4) | ((uint64_t)(lbo >> 4) << 16) | ((uint64_t)(sbo >> 4) << 32) | (1ull << 62);
}
__device__ __forceinline__ void mbar_init(uint32_t a, int c) { asm volatile("mbarrier.init.shared.b64 [%0],%1;" ::"r"(a), "r"(c) : "memory"); }
__device__ __forceinline__ void mbar_wait(uint32_t a, uint32_t par) {
  asm volatile(
      "{.reg .pred p; .reg .u32 n;\n"
      "mov.u32 n, 0;\n"
      "W: mbarrier.try_wait.parity.shared.b64 p,[%0],%1;\n"
      "@p bra D;\n"
      "add.u32 n, n, 1;\n"
      "setp.lt.u32 p, n, %2;\n"
      "@p bra W;\n"
      "trap;\n"
      "D:}" ::"r"(a), "r"(par), "n"(SPIN_LIMIT) : "memory");
}
__device__ __forceinline__ void mbar_wait_q(uint32_t a, uint32_t par) {
  asm volatile(
      "{.reg .pred p; .reg .u32 n;\n"
      "mov.u32 n, 0;\n"
      "W: mbarrier.try_wait.parity.shared.b64 p,[%0],%1,4000;\n"
      "@p bra D;\n"
      "add.u32 n, n, 1;\n"
      "setp.lt.u32 p, n, %2;\n"
      "@p bra W;\n"
      "trap;\n"
      "D:}" ::"r"(a), "r"(par), "n"(SPIN_LIMIT / 16) : "memory");
}
__device__ __forceinline__ void mbar_expect(uint32_t a, uint32_t b) { asm volatile("mbarrier.arrive.expect_tx.shared.b64 _,[%0],%1;" ::"r"(a), "r"(b) : "memory"); }
__device__ __forceinline__ void mbar_arrive(uint32_t a) { asm volatile("mbarrier.arrive.shared.b64 _,[%0];" ::"r"(a) : "memory"); }
__device__ __forceinline__ uint32_t mapa(uint32_t a, uint32_t cta) { uint32_t r; asm("mapa.shared::cluster.u32 %0,%1,%2;" : "=r"(r) : "r"(a), "r"(cta)); return r; }
__device__ __forceinline__ void mbar_arrive_cl(uint32_t a) { asm volatile("mbarrier.arrive.shared::cluster.b64 _,[%0];" ::"r"(a) : "memory"); }
__device__ __forceinline__ void tma2d(uint32_t dst, const CUtensorMap* m, int c0, int c1, uint32_t mb) {
  asm volatile("cp.async.bulk.tensor.2d.shared::cluster.global.mbarrier::complete_tx::bytes [%0],[%1,{%2,%3}],[%4];" ::"r"(dst), "l"(m), "r"(c0), "r"(c1), "r"(mb) : "memory");
}
__device__ __forceinline__ void tma2d_pf(const CUtensorMap* m, int c0, int c1) {
  asm volatile("cp.async.bulk.prefetch.tensor.2d.L2.global [%0,{%1,%2}];" ::"l"(m), "r"(c0), "r"(c1) : "memory");
}
__device__ __forceinline__ void tma3d(uint32_t dst, const CUtensorMap* m, int c1, int c2, uint32_t mb) {
  asm volatile("cp.async.bulk.tensor.3d.shared::cluster.global.mbarrier::complete_tx::bytes [%0],[%1,{0,%2,%3}],[%4];" ::"r"(dst), "l"(m), "r"(c1), "r"(c2), "r"(mb) : "memory");
}
__device__ __forceinline__ void tma2d_st(const CUtensorMap* m, int c0, int c1, uint32_t src) {
  asm volatile("cp.async.bulk.tensor.2d.global.shared::cta.bulk_group [%0,{%1,%2}],[%3];" ::"l"(m), "r"(c0), "r"(c1), "r"(src) : "memory");
}
__device__ __forceinline__ void bulk_ld(uint32_t dst, const void* src, uint32_t n, uint32_t mb) {
  asm volatile("cp.async.bulk.shared::cluster.global.mbarrier::complete_tx::bytes [%0],[%1],%2,[%3];" ::"r"(dst), "l"(src), "r"(n), "r"(mb) : "memory");
}
__device__ __forceinline__ void bulk_ld_mc(uint32_t dst, const void* src, uint32_t n, uint32_t mb) {
  asm volatile("cp.async.bulk.shared::cluster.global.mbarrier::complete_tx::bytes.multicast::cluster [%0],[%1],%2,[%3],%4;" ::"r"(dst), "l"(src), "r"(n), "r"(mb), "h"((uint16_t)3) : "memory");
}
__device__ __forceinline__ void bulk_st(void* dst, uint32_t src, uint32_t n) {
  asm volatile("cp.async.bulk.global.shared::cta.bulk_group [%0],[%1],%2;" ::"l"(dst), "r"(src), "r"(n) : "memory");
}
__device__ __forceinline__ void e_expect_tma3d(uint32_t dst, const CUtensorMap* m, int c1, int c2, uint32_t mb, uint32_t bytes) {
  asm volatile("{.reg .pred p; elect.sync _|p, 0xffffffff; @p mbarrier.arrive.expect_tx.shared.b64 _,[%4],%5;\n"
               "@p cp.async.bulk.tensor.3d.shared::cluster.global.mbarrier::complete_tx::bytes [%0],[%1,{0,%2,%3}],[%4];}" ::"r"(dst), "l"(m), "r"(c1), "r"(c2), "r"(mb), "r"(bytes) : "memory");
}
__device__ __forceinline__ void e_bulk_ld(uint32_t dst, const void* src, uint32_t n, uint32_t mb) {
  asm volatile("{.reg .pred p; elect.sync _|p, 0xffffffff; @p cp.async.bulk.shared::cluster.global.mbarrier::complete_tx::bytes [%0],[%1],%2,[%3];}" ::"r"(dst), "l"(src), "r"(n), "r"(mb) : "memory");
}
__device__ __forceinline__ void e_bulk_ld_ef(uint32_t dst, const void* src, uint32_t n, uint32_t mb) {
  asm volatile("{.reg .pred p; .reg .b64 c; createpolicy.fractional.L2::evict_first.b64 c,1.0; elect.sync _|p, 0xffffffff;"
               " @p cp.async.bulk.shared::cluster.global.mbarrier::complete_tx::bytes.L2::cache_hint [%0],[%1],%2,[%3],c;}" ::"r"(dst), "l"(src), "r"(n), "r"(mb) : "memory");
}
__device__ __forceinline__ void e_bulk_ld_mc(uint32_t dst, const void* src, uint32_t n, uint32_t mb) {
  asm volatile("{.reg .pred p; elect.sync _|p, 0xffffffff; @p cp.async.bulk.shared::cluster.global.mbarrier::complete_tx::bytes.multicast::cluster [%0],[%1],%2,[%3],%4;}" ::"r"(dst), "l"(src), "r"(n), "r"(mb), "h"((uint16_t)3) : "memory");
}
#define BULK_COMMIT() asm volatile("cp.async.bulk.commit_group;" ::: "memory")
#define BULK_WAIT_READ(n) asm volatile("cp.async.bulk.wait_group.read " #n ";" ::: "memory")
#define BULK_WAIT(n) asm volatile("cp.async.bulk.wait_group " #n ";" ::: "memory")
#define FENCE_ASYNC_SMEM() asm volatile("fence.proxy.async.shared::cta;" ::: "memory")
#define FENCE_ASYNC() asm volatile("fence.proxy.async;" ::: "memory")
#define WG_FENCE() asm volatile("wgmma.fence.sync.aligned;" ::: "memory")
#define WG_COMMIT() asm volatile("wgmma.commit_group.sync.aligned;" ::: "memory")
#define WG_WAIT(n) asm volatile("wgmma.wait_group.sync.aligned " #n ";" ::: "memory")
#define BAR_SYNC(id, n) asm volatile("bar.sync %0,%1;" ::"n"(id), "n"(n) : "memory")
#define BAR_ARRIVE(id, n) asm volatile("bar.arrive %0,%1;" ::"n"(id), "n"(n) : "memory")
#define SCHED_FENCE(k) asm volatile("{.reg .pred p; setp.ne.u32 p,%0,0; @p trap;}" ::"r"(mp.zero[(k) - 46]) : "memory")
#define CLUSTER_SYNC() asm volatile("barrier.cluster.arrive.relaxed.aligned; barrier.cluster.wait.aligned;" ::: "memory")
__device__ __forceinline__ uint32_t pk(float lo, float hi) { uint32_t r; asm("cvt.rn.bf16x2.f32 %0,%1,%2;" : "=r"(r) : "f"(hi), "f"(lo)); return r; }
__device__ __forceinline__ float blo(uint32_t v) { return __uint_as_float(v << 16); }
__device__ __forceinline__ float bhi(uint32_t v) { return __uint_as_float(v & 0xffff0000u); }
__device__ __forceinline__ void ldsm4(uint32_t* r, uint32_t a) {
  asm volatile("ldmatrix.sync.aligned.m8n8.x4.shared.b16 {%0,%1,%2,%3},[%4];" : "=r"(r[0]), "=r"(r[1]), "=r"(r[2]), "=r"(r[3]) : "r"(a) : "memory");
}
__device__ __forceinline__ void ldsm4t(uint32_t* r, uint32_t a) {
  asm volatile("ldmatrix.sync.aligned.m8n8.x4.trans.shared.b16 {%0,%1,%2,%3},[%4];" : "=r"(r[0]), "=r"(r[1]), "=r"(r[2]), "=r"(r[3]) : "r"(a) : "memory");
}
__device__ __forceinline__ void stsm4(uint32_t a, uint32_t r0, uint32_t r1, uint32_t r2, uint32_t r3) {
  asm volatile("stmatrix.sync.aligned.m8n8.x4.shared.b16 [%0],{%1,%2,%3,%4};" ::"r"(a), "r"(r0), "r"(r1), "r"(r2), "r"(r3) : "memory");
}
__device__ __forceinline__ void mma16(float* d, uint32_t a0, uint32_t a1, uint32_t a2, uint32_t a3, uint32_t b0, uint32_t b1) {
  asm volatile("mma.sync.aligned.m16n8k16.row.col.f32.bf16.bf16.f32 {%0,%1,%2,%3},{%4,%5,%6,%7},{%8,%9},{%0,%1,%2,%3};"
               : "+f"(d[0]), "+f"(d[1]), "+f"(d[2]), "+f"(d[3]) : "r"(a0), "r"(a1), "r"(a2), "r"(a3), "r"(b0), "r"(b1));
}
__device__ __forceinline__ void mma8(float* d, uint32_t a0, uint32_t a1, uint32_t b0) {
  asm volatile("mma.sync.aligned.m16n8k8.row.col.f32.bf16.bf16.f32 {%0,%1,%2,%3},{%4,%5},{%6},{%0,%1,%2,%3};"
               : "+f"(d[0]), "+f"(d[1]), "+f"(d[2]), "+f"(d[3]) : "r"(a0), "r"(a1), "r"(b0));
}
__device__ __forceinline__ float4 lds4f(uint32_t a) { float4 v; asm volatile("ld.shared.v4.f32 {%0,%1,%2,%3},[%4];" : "=f"(v.x), "=f"(v.y), "=f"(v.z), "=f"(v.w) : "r"(a) : "memory"); return v; }
__device__ __forceinline__ float2 lds2f(uint32_t a) { float2 v; asm volatile("ld.shared.v2.f32 {%0,%1},[%2];" : "=f"(v.x), "=f"(v.y) : "r"(a) : "memory"); return v; }
__device__ __forceinline__ uint4 lds4(uint32_t a) { uint4 v; asm volatile("ld.shared.v4.u32 {%0,%1,%2,%3},[%4];" : "=r"(v.x), "=r"(v.y), "=r"(v.z), "=r"(v.w) : "r"(a) : "memory"); return v; }
__device__ __forceinline__ uint2 lds2u(uint32_t a) { uint2 v; asm volatile("ld.shared.v2.u32 {%0,%1},[%2];" : "=r"(v.x), "=r"(v.y) : "r"(a) : "memory"); return v; }
__device__ __forceinline__ uint32_t lds1(uint32_t a) { uint32_t v; asm volatile("ld.shared.u32 %0,[%1];" : "=r"(v) : "r"(a) : "memory"); return v; }
__device__ __forceinline__ void sts4(uint32_t a, uint32_t x, uint32_t y, uint32_t z, uint32_t w) { asm volatile("st.shared.v4.u32 [%0],{%1,%2,%3,%4};" ::"r"(a), "r"(x), "r"(y), "r"(z), "r"(w) : "memory"); }
__device__ __forceinline__ void sts2(uint32_t a, uint32_t x, uint32_t y) { asm volatile("st.shared.v2.u32 [%0],{%1,%2};" ::"r"(a), "r"(x), "r"(y) : "memory"); }
__device__ __forceinline__ void sts1(uint32_t a, uint32_t x) { asm volatile("st.shared.u32 [%0],%1;" ::"r"(a), "r"(x) : "memory"); }
__device__ __forceinline__ void sta4(uint32_t a, const uint32_t* v, uint32_t mb) {
  asm volatile("st.async.shared::cluster.mbarrier::complete_tx::bytes.v4.b32 [%0],{%1,%2,%3,%4},[%5];" ::"r"(a), "r"(v[0]), "r"(v[1]), "r"(v[2]), "r"(v[3]), "r"(mb) : "memory");
}
__device__ __forceinline__ uint4 ldg_rlx4(const void* p) { uint4 v; asm volatile("ld.relaxed.gpu.global.v4.u32 {%0,%1,%2,%3},[%4];" : "=r"(v.x), "=r"(v.y), "=r"(v.z), "=r"(v.w) : "l"(p) : "memory"); return v; }
__device__ __forceinline__ uint32_t ldg_rlx1(const void* p) { uint32_t v; asm volatile("ld.relaxed.gpu.global.u32 %0,[%1];" : "=r"(v) : "l"(p) : "memory"); return v; }
__device__ __forceinline__ uint2 ldg_rlx2(const void* p) { uint2 v; asm volatile("ld.relaxed.gpu.global.v2.u32 {%0,%1},[%2];" : "=r"(v.x), "=r"(v.y) : "l"(p) : "memory"); return v; }
__device__ __forceinline__ uint4 ldg_b128(const void* p) {
  uint4 v;
  asm volatile("{.reg .b128 t; .reg .b64 a,b; ld.relaxed.gpu.global.b128 t,[%4]; mov.b128 {a,b},t; mov.b64 {%0,%1},a; mov.b64 {%2,%3},b;}" : "=r"(v.x), "=r"(v.y), "=r"(v.z), "=r"(v.w) : "l"(p) : "memory");
  return v;
}
__device__ __forceinline__ void stg_b128(void* p, uint32_t x, uint32_t y, uint32_t z, uint32_t w) {
  asm volatile("{.reg .b128 t; .reg .b64 a,b; mov.b64 a,{%1,%2}; mov.b64 b,{%3,%4}; mov.b128 t,{a,b}; st.relaxed.gpu.global.b128 [%0],t;}" ::"l"(p), "r"(x), "r"(y), "r"(z), "r"(w) : "memory");
}
__device__ __forceinline__ void st_b128(void* p, uint32_t x, uint32_t y, uint32_t z, uint32_t w) {
  asm volatile("{.reg .b128 t; .reg .b64 a,b; mov.b64 a,{%1,%2}; mov.b64 b,{%3,%4}; mov.b128 t,{a,b}; st.relaxed.gpu.b128 [%0],t;}" ::"l"(p), "r"(x), "r"(y), "r"(z), "r"(w) : "memory");
}
__device__ __forceinline__ void stg_rlx4(void* p, uint32_t x, uint32_t y, uint32_t z, uint32_t w) { asm volatile("st.relaxed.gpu.global.v4.u32 [%0],{%1,%2,%3,%4};" ::"l"(p), "r"(x), "r"(y), "r"(z), "r"(w) : "memory"); }
__device__ __forceinline__ void stg_rlx2(void* p, uint32_t x, uint32_t y) { asm volatile("st.relaxed.gpu.global.v2.u32 [%0],{%1,%2};" ::"l"(p), "r"(x), "r"(y) : "memory"); }
__device__ __forceinline__ void red4(void* p, float a, float b, float c, float d) { asm volatile("red.relaxed.gpu.global.add.v4.f32 [%0],{%1,%2,%3,%4};" ::"l"(p), "f"(a), "f"(b), "f"(c), "f"(d) : "memory"); }
__device__ __forceinline__ unsigned ld_acq(const unsigned* p) { unsigned v; asm volatile("ld.acquire.gpu.global.u32 %0,[%1];" : "=r"(v) : "l"(p) : "memory"); return v; }
__device__ __forceinline__ void red_rel(unsigned* p) { asm volatile("red.release.gpu.global.add.u32 [%0],1;" ::"l"(p) : "memory"); }
__device__ __forceinline__ void red_rlx(unsigned* p) { asm volatile("red.relaxed.gpu.global.add.u32 [%0],1;" ::"l"(p) : "memory"); }
__device__ __forceinline__ void wait_cnt(const unsigned* p, unsigned n) { int it = 0; while (ld_acq(p) < n) { if (++it > SPIN_LIMIT) __trap(); } }
__device__ __forceinline__ uint32_t clk() { uint32_t c; asm volatile("mov.u32 %0,%%clock;" : "=r"(c)); return c; }
__device__ __forceinline__ uint32_t gtime() { uint32_t c; asm volatile("mov.u32 %0,%%globaltimer_lo;" : "=r"(c)); return c; }
__device__ __forceinline__ void wait_until(uint32_t t0, uint32_t d) { while (clk() - t0 < d) {} }
__device__ __forceinline__ float ex2(float x) { float r; asm("ex2.approx.ftz.f32 %0,%1;" : "=f"(r) : "f"(x)); return r; }
__device__ __forceinline__ float silu(float x) { return x * __frcp_rn(1.f + __expf(-x)); }
__device__ __forceinline__ float rbf(float x) { return __bfloat162float(__float2bfloat16_rn(x)); }

__device__ __forceinline__ void wgmma_ss_n128(float* d, uint64_t a, uint64_t b, int sd) {
  asm volatile("{.reg .pred p; setp.ne.b32 p, %66, 0;\n"
    "wgmma.mma_async.sync.aligned.m64n128k16.f32.bf16.bf16 {%0,%1,%2,%3,%4,%5,%6,%7,%8,%9,%10,%11,%12,%13,%14,%15,%16,%17,%18,%19,%20,%21,%22,%23,%24,%25,%26,%27,%28,%29,%30,%31,%32,%33,%34,%35,%36,%37,%38,%39,%40,%41,%42,%43,%44,%45,%46,%47,%48,%49,%50,%51,%52,%53,%54,%55,%56,%57,%58,%59,%60,%61,%62,%63}, %64, %65, p, 1, 1, 0, 1;}\n"
    : "+f"(d[0]),"+f"(d[1]),"+f"(d[2]),"+f"(d[3]),"+f"(d[4]),"+f"(d[5]),"+f"(d[6]),"+f"(d[7]),
      "+f"(d[8]),"+f"(d[9]),"+f"(d[10]),"+f"(d[11]),"+f"(d[12]),"+f"(d[13]),"+f"(d[14]),"+f"(d[15]),
      "+f"(d[16]),"+f"(d[17]),"+f"(d[18]),"+f"(d[19]),"+f"(d[20]),"+f"(d[21]),"+f"(d[22]),"+f"(d[23]),
      "+f"(d[24]),"+f"(d[25]),"+f"(d[26]),"+f"(d[27]),"+f"(d[28]),"+f"(d[29]),"+f"(d[30]),"+f"(d[31]),
      "+f"(d[32]),"+f"(d[33]),"+f"(d[34]),"+f"(d[35]),"+f"(d[36]),"+f"(d[37]),"+f"(d[38]),"+f"(d[39]),
      "+f"(d[40]),"+f"(d[41]),"+f"(d[42]),"+f"(d[43]),"+f"(d[44]),"+f"(d[45]),"+f"(d[46]),"+f"(d[47]),
      "+f"(d[48]),"+f"(d[49]),"+f"(d[50]),"+f"(d[51]),"+f"(d[52]),"+f"(d[53]),"+f"(d[54]),"+f"(d[55]),
      "+f"(d[56]),"+f"(d[57]),"+f"(d[58]),"+f"(d[59]),"+f"(d[60]),"+f"(d[61]),"+f"(d[62]),"+f"(d[63])
    : "l"(a), "l"(b), "r"(sd));
}
__device__ __forceinline__ void wgmma_ss_n192(float* d, uint64_t a, uint64_t b, int sd) {
  asm volatile("{.reg .pred p; setp.ne.b32 p, %98, 0;\n"
    "wgmma.mma_async.sync.aligned.m64n192k16.f32.bf16.bf16 {%0,%1,%2,%3,%4,%5,%6,%7,%8,%9,%10,%11,%12,%13,%14,%15,%16,%17,%18,%19,%20,%21,%22,%23,%24,%25,%26,%27,%28,%29,%30,%31,%32,%33,%34,%35,%36,%37,%38,%39,%40,%41,%42,%43,%44,%45,%46,%47,%48,%49,%50,%51,%52,%53,%54,%55,%56,%57,%58,%59,%60,%61,%62,%63,%64,%65,%66,%67,%68,%69,%70,%71,%72,%73,%74,%75,%76,%77,%78,%79,%80,%81,%82,%83,%84,%85,%86,%87,%88,%89,%90,%91,%92,%93,%94,%95}, %96, %97, p, 1, 1, 0, 1;}\n"
    : "+f"(d[0]),"+f"(d[1]),"+f"(d[2]),"+f"(d[3]),"+f"(d[4]),"+f"(d[5]),"+f"(d[6]),"+f"(d[7]),
      "+f"(d[8]),"+f"(d[9]),"+f"(d[10]),"+f"(d[11]),"+f"(d[12]),"+f"(d[13]),"+f"(d[14]),"+f"(d[15]),
      "+f"(d[16]),"+f"(d[17]),"+f"(d[18]),"+f"(d[19]),"+f"(d[20]),"+f"(d[21]),"+f"(d[22]),"+f"(d[23]),
      "+f"(d[24]),"+f"(d[25]),"+f"(d[26]),"+f"(d[27]),"+f"(d[28]),"+f"(d[29]),"+f"(d[30]),"+f"(d[31]),
      "+f"(d[32]),"+f"(d[33]),"+f"(d[34]),"+f"(d[35]),"+f"(d[36]),"+f"(d[37]),"+f"(d[38]),"+f"(d[39]),
      "+f"(d[40]),"+f"(d[41]),"+f"(d[42]),"+f"(d[43]),"+f"(d[44]),"+f"(d[45]),"+f"(d[46]),"+f"(d[47]),
      "+f"(d[48]),"+f"(d[49]),"+f"(d[50]),"+f"(d[51]),"+f"(d[52]),"+f"(d[53]),"+f"(d[54]),"+f"(d[55]),
      "+f"(d[56]),"+f"(d[57]),"+f"(d[58]),"+f"(d[59]),"+f"(d[60]),"+f"(d[61]),"+f"(d[62]),"+f"(d[63]),
      "+f"(d[64]),"+f"(d[65]),"+f"(d[66]),"+f"(d[67]),"+f"(d[68]),"+f"(d[69]),"+f"(d[70]),"+f"(d[71]),
      "+f"(d[72]),"+f"(d[73]),"+f"(d[74]),"+f"(d[75]),"+f"(d[76]),"+f"(d[77]),"+f"(d[78]),"+f"(d[79]),
      "+f"(d[80]),"+f"(d[81]),"+f"(d[82]),"+f"(d[83]),"+f"(d[84]),"+f"(d[85]),"+f"(d[86]),"+f"(d[87]),
      "+f"(d[88]),"+f"(d[89]),"+f"(d[90]),"+f"(d[91]),"+f"(d[92]),"+f"(d[93]),"+f"(d[94]),"+f"(d[95])
    : "l"(a), "l"(b), "r"(sd));
}
__device__ __forceinline__ void wgmma_ss_n256(float* d, uint64_t a, uint64_t b, int sd) {
  asm volatile("{.reg .pred p; setp.ne.b32 p, %130, 0;\n"
    "wgmma.mma_async.sync.aligned.m64n256k16.f32.bf16.bf16 {%0,%1,%2,%3,%4,%5,%6,%7,%8,%9,%10,%11,%12,%13,%14,%15,%16,%17,%18,%19,%20,%21,%22,%23,%24,%25,%26,%27,%28,%29,%30,%31,%32,%33,%34,%35,%36,%37,%38,%39,%40,%41,%42,%43,%44,%45,%46,%47,%48,%49,%50,%51,%52,%53,%54,%55,%56,%57,%58,%59,%60,%61,%62,%63,%64,%65,%66,%67,%68,%69,%70,%71,%72,%73,%74,%75,%76,%77,%78,%79,%80,%81,%82,%83,%84,%85,%86,%87,%88,%89,%90,%91,%92,%93,%94,%95,%96,%97,%98,%99,%100,%101,%102,%103,%104,%105,%106,%107,%108,%109,%110,%111,%112,%113,%114,%115,%116,%117,%118,%119,%120,%121,%122,%123,%124,%125,%126,%127}, %128, %129, p, 1, 1, 0, 1;}\n"
    : "+f"(d[0]),"+f"(d[1]),"+f"(d[2]),"+f"(d[3]),"+f"(d[4]),"+f"(d[5]),"+f"(d[6]),"+f"(d[7]),
      "+f"(d[8]),"+f"(d[9]),"+f"(d[10]),"+f"(d[11]),"+f"(d[12]),"+f"(d[13]),"+f"(d[14]),"+f"(d[15]),
      "+f"(d[16]),"+f"(d[17]),"+f"(d[18]),"+f"(d[19]),"+f"(d[20]),"+f"(d[21]),"+f"(d[22]),"+f"(d[23]),
      "+f"(d[24]),"+f"(d[25]),"+f"(d[26]),"+f"(d[27]),"+f"(d[28]),"+f"(d[29]),"+f"(d[30]),"+f"(d[31]),
      "+f"(d[32]),"+f"(d[33]),"+f"(d[34]),"+f"(d[35]),"+f"(d[36]),"+f"(d[37]),"+f"(d[38]),"+f"(d[39]),
      "+f"(d[40]),"+f"(d[41]),"+f"(d[42]),"+f"(d[43]),"+f"(d[44]),"+f"(d[45]),"+f"(d[46]),"+f"(d[47]),
      "+f"(d[48]),"+f"(d[49]),"+f"(d[50]),"+f"(d[51]),"+f"(d[52]),"+f"(d[53]),"+f"(d[54]),"+f"(d[55]),
      "+f"(d[56]),"+f"(d[57]),"+f"(d[58]),"+f"(d[59]),"+f"(d[60]),"+f"(d[61]),"+f"(d[62]),"+f"(d[63]),
      "+f"(d[64]),"+f"(d[65]),"+f"(d[66]),"+f"(d[67]),"+f"(d[68]),"+f"(d[69]),"+f"(d[70]),"+f"(d[71]),
      "+f"(d[72]),"+f"(d[73]),"+f"(d[74]),"+f"(d[75]),"+f"(d[76]),"+f"(d[77]),"+f"(d[78]),"+f"(d[79]),
      "+f"(d[80]),"+f"(d[81]),"+f"(d[82]),"+f"(d[83]),"+f"(d[84]),"+f"(d[85]),"+f"(d[86]),"+f"(d[87]),
      "+f"(d[88]),"+f"(d[89]),"+f"(d[90]),"+f"(d[91]),"+f"(d[92]),"+f"(d[93]),"+f"(d[94]),"+f"(d[95]),
      "+f"(d[96]),"+f"(d[97]),"+f"(d[98]),"+f"(d[99]),"+f"(d[100]),"+f"(d[101]),"+f"(d[102]),"+f"(d[103]),
      "+f"(d[104]),"+f"(d[105]),"+f"(d[106]),"+f"(d[107]),"+f"(d[108]),"+f"(d[109]),"+f"(d[110]),"+f"(d[111]),
      "+f"(d[112]),"+f"(d[113]),"+f"(d[114]),"+f"(d[115]),"+f"(d[116]),"+f"(d[117]),"+f"(d[118]),"+f"(d[119]),
      "+f"(d[120]),"+f"(d[121]),"+f"(d[122]),"+f"(d[123]),"+f"(d[124]),"+f"(d[125]),"+f"(d[126]),"+f"(d[127])
    : "l"(a), "l"(b), "r"(sd));
}
__device__ __forceinline__ void wgmma_rs_n32(float* d, const uint32_t* a, uint64_t b, int sd) {
  asm volatile("{.reg .pred p; setp.ne.b32 p, %21, 0;\n"
    "wgmma.mma_async.sync.aligned.m64n32k16.f32.bf16.bf16 {%0,%1,%2,%3,%4,%5,%6,%7,%8,%9,%10,%11,%12,%13,%14,%15}, {%16,%17,%18,%19}, %20, p, 1, 1, 0;}\n"
    : "+f"(d[0]),"+f"(d[1]),"+f"(d[2]),"+f"(d[3]),"+f"(d[4]),"+f"(d[5]),"+f"(d[6]),"+f"(d[7]),
      "+f"(d[8]),"+f"(d[9]),"+f"(d[10]),"+f"(d[11]),"+f"(d[12]),"+f"(d[13]),"+f"(d[14]),"+f"(d[15])
    : "r"(a[0]), "r"(a[1]), "r"(a[2]), "r"(a[3]), "l"(b), "r"(sd));
}
__device__ __forceinline__ void wgmma_ssT_n32(float* d, uint64_t a, uint64_t b, int sd) {
  asm volatile("{.reg .pred p; setp.ne.b32 p, %18, 0;\n"
    "wgmma.mma_async.sync.aligned.m64n32k16.f32.bf16.bf16 {%0,%1,%2,%3,%4,%5,%6,%7,%8,%9,%10,%11,%12,%13,%14,%15}, %16, %17, p, 1, 1, 1, 0;}\n"
    : "+f"(d[0]),"+f"(d[1]),"+f"(d[2]),"+f"(d[3]),"+f"(d[4]),"+f"(d[5]),"+f"(d[6]),"+f"(d[7]),
      "+f"(d[8]),"+f"(d[9]),"+f"(d[10]),"+f"(d[11]),"+f"(d[12]),"+f"(d[13]),"+f"(d[14]),"+f"(d[15])
    : "l"(a), "l"(b), "r"(sd));
}

__device__ __forceinline__ void wgmma_rs_n32_z(float* d, const uint32_t* a, uint64_t b) {
  asm volatile("{.reg .pred p; setp.ne.b32 p, 0, 0;\n"
    "wgmma.mma_async.sync.aligned.m64n32k16.f32.bf16.bf16 {%0,%1,%2,%3,%4,%5,%6,%7,%8,%9,%10,%11,%12,%13,%14,%15}, {%16,%17,%18,%19}, %20, p, 1, 1, 0;}\n"
    : "=f"(d[0]),"=f"(d[1]),"=f"(d[2]),"=f"(d[3]),"=f"(d[4]),"=f"(d[5]),"=f"(d[6]),"=f"(d[7]),
      "=f"(d[8]),"=f"(d[9]),"=f"(d[10]),"=f"(d[11]),"=f"(d[12]),"=f"(d[13]),"=f"(d[14]),"=f"(d[15])
    : "r"(a[0]), "r"(a[1]), "r"(a[2]), "r"(a[3]), "l"(b));
}

namespace rec {
constexpr int NVR = P_NVR;
constexpr int NVS = 16 - NVR;
constexpr int NVP = P_NVP;
constexpr int NWP = P_NWP;
constexpr uint32_t WO = 0;
constexpr uint32_t XB = 65536;
constexpr uint32_t PK = XB + 32768;
constexpr uint32_t VN = PK + 24576;
constexpr uint32_t VX0 = VN + 4096;
constexpr uint32_t WVS = 131072;
constexpr uint32_t MEM = WVS + 2 * NVS * 2048;
constexpr uint32_t ARO = MEM + 10240;
constexpr uint32_t OB = ARO + 5120;
constexpr uint32_t QT = OB + 2048;
constexpr uint32_t KT = QT + 2048;
constexpr uint32_t RQ = KT + 6144;
constexpr uint32_t RK = RQ + 2048;
constexpr uint32_t SC = RK + 2048;
constexpr uint32_t OT = OB;
constexpr uint32_t TF = SC + 2048;
constexpr uint32_t PRE = MEM + 2 * NVR * 2048;
constexpr uint32_t TA = TF + 8192;
constexpr uint32_t RX = TA + 6144;
constexpr uint32_t VX1 = RX + 2048;
constexpr uint32_t BARS = VX1 + 4096;
constexpr uint32_t PACE = BARS + 18 * 8;
constexpr uint32_t SMEM = BARS + 512;
static_assert(PRE + 14336 <= BARS, "staging");
constexpr int NW1 = P_NW1;
static_assert(SMEM <= 232448, "smem");
constexpr int B_E = 2, B_SC = 3, B_S = 4, B_O = 5, B_F = 6, B_W = 7, B_C = 9, B_K = 10, B_H = 15, B_Q = 1, B_S2 = 6, B_T2 = 9, B_P = 13, B_T = 14, B_R = 11, B_X = 12, B_V = 8;
constexpr int N_P = XE == 1 ? 416 : 384, N_R = XE ? 288 : 320, N_V = AV ? 384 : 512, N_O = AV ? 384 : 416;
constexpr int XC = 16384, X_RING = 131072, X_SC = 65536, X_TOK = 4096;
#define X_VX(i) (((i) >> 1) * 2048 + ((i) & 1) * 512)
#define X_VM(i) (X_VX(i) + 1024)
#define V_RING(n) (((n) & 1) * X_RING + ((n) & 2) * 2048)
#define V_TAG(n) ((~(n) >> 2) & 1)
}
struct RecMaps { CUtensorMap wq, wk, wv, wo, ari; int zero[40]; };

#define F_(x) __uint_as_float(x)
#define U_(x) __float_as_uint(x)
#define AR_R(q) (24 + ((q) & 1) * 16 + ((q) >> 1) * 56)
#define AR_P(q) ((q) >> 1)
#define AR_ROW(i) (24 + ((i) & 1) * 16 + ((i) & 2) * 92 + (((i) >> 2) & 7) + ((i) >> 5) * 128)
constexpr size_t AR_OFF = 32 * 262144;
__device__ __forceinline__ void ar_fetch(uint32_t dst, const CUtensorMap* m, int slot, int half, uint32_t mb) {
  asm volatile("{.reg .pred p; elect.sync _|p, 0xffffffff; @p mbarrier.arrive.expect_tx.shared.b64 _,[%4],10240;\n"
               "@p cp.async.bulk.tensor.3d.shared::cluster.global.mbarrier::complete_tx::bytes [%0],[%1,{%2,%3,%6}],[%4];\n"
               "@p cp.async.bulk.tensor.3d.shared::cluster.global.mbarrier::complete_tx::bytes [%0+5120],[%1,{%2,%5,%7}],[%4];}"
               ::"r"(dst), "l"(m), "r"(slot * 64), "r"(AR_R(half * 2)), "r"(mb), "r"(AR_R(half * 2 + 1)), "r"(AR_P(half * 2)), "r"(AR_P(half * 2 + 1)) : "memory");
}
__device__ __forceinline__ uint4 exch_b128(void* p, uint32_t x, uint32_t y, uint32_t z, uint32_t w) {
  uint4 v;
  asm volatile("{.reg .b128 s, t; .reg .b64 a,b; mov.b64 a,{%5,%6}; mov.b64 b,{%7,%8}; mov.b128 s,{a,b}; atom.relaxed.gpu.global.exch.b128 t,[%4],s;"
               " mov.b128 {a,b},t; mov.b64 {%0,%1},a; mov.b64 {%2,%3},b;}" : "=r"(v.x), "=r"(v.y), "=r"(v.z), "=r"(v.w) : "l"(p), "r"(x), "r"(y), "r"(z), "r"(w) : "memory");
  return v;
}
#define CONSUME(v) do { if ((v) == 0x7fc12345u) sts1(sb + rec::BARS + 96, 0); } while (0)
__device__ __forceinline__ uint32_t tagf(float v, uint32_t tag) { return (__float_as_uint(v) & ~1u) | tag; }
__device__ __forceinline__ uint2 ldg_b64(const void* p) { uint2 v; asm volatile("{.reg .b64 t; ld.relaxed.gpu.global.b64 t,[%2]; mov.b64 {%0,%1},t;}" : "=r"(v.x), "=r"(v.y) : "l"(p) : "memory"); return v; }
__device__ __forceinline__ void stg_b64(void* p, uint32_t x, uint32_t y) { asm volatile("{.reg .b64 t; mov.b64 t,{%1,%2}; st.relaxed.gpu.global.b64 [%0],t;}" ::"l"(p), "r"(x), "r"(y) : "memory"); }
__device__ __forceinline__ uint32_t tagbad(uint32_t x, uint32_t y, uint32_t tag) { uint32_t r; asm("lop3.b32 %0,%1,%2,%3,0x7e;" : "=r"(r) : "r"(x), "r"(y), "r"(tag)); return r; }

__device__ __forceinline__ bool anybad(uint32_t a, uint32_t b, uint32_t c, uint32_t d, uint32_t e, uint32_t f, uint32_t g, uint32_t h, uint32_t tag) {
  uint32_t r;
  asm volatile("{.reg .b32 t,u,v,w; .reg .pred p; lop3.b32 t,%1,%2,%9,0x7e; lop3.b32 u,%3,%4,%9,0x7e; lop3.b32 v,%5,%6,%9,0x7e; lop3.b32 w,%7,%8,%9,0x7e;"
               " lop3.b32 t,t,u,v,0xfe; lop3.b32 t,t,w,1,0xa8; setp.ne.u32 p,t,0; vote.sync.any.pred p,p,0xffffffff; selp.u32 %0,1,0,p;}"
               : "=r"(r) : "r"(a), "r"(b), "r"(c), "r"(d), "r"(e), "r"(f), "r"(g), "r"(h), "r"(tag));
  return r;
}
__device__ __forceinline__ bool anybad(uint32_t a, uint32_t b, uint32_t c, uint32_t d, uint32_t tag) {
  uint32_t r;
  asm volatile("{.reg .b32 t,u; .reg .pred p; lop3.b32 t,%1,%2,%5,0x7e; lop3.b32 u,%3,%4,%5,0x7e;"
               " lop3.b32 t,t,u,1,0xa8; setp.ne.u32 p,t,0; vote.sync.any.pred p,p,0xffffffff; selp.u32 %0,1,0,p;}"
               : "=r"(r) : "r"(a), "r"(b), "r"(c), "r"(d), "r"(tag));
  return r;
}
#define BAD8(r) anybad(r[0].x, r[0].z, r[1].x, r[1].z, r[2].x, r[2].z, r[3].x, r[3].z, tag)
#define BADS(r) anybad(r[0].x, r[0].y, r[1].x, r[1].y, r[2].x, r[2].y, r[3].x, r[3].y, tag)
constexpr float SCS = 0.08838834764831845f * 1.4426950408889634f / 16.f;
__device__ __forceinline__ uint32_t pkh(float lo, float hi, uint32_t tag) {
  uint32_t r;
  asm("{.reg .b32 t; cvt.rn.satfinite.f16x2.f32 t,%1,%2; lop3.b32 %0,t,0xfffffffe,%3,0xea;}" : "=r"(r) : "f"(hi), "f"(lo), "r"(tag));
  return r;
}
__device__ __forceinline__ uint32_t addh(uint32_t a, uint32_t b) { uint32_t r; asm("add.rn.f16x2 %0,%1,%2;" : "=r"(r) : "r"(a), "r"(b)); return r; }
__device__ __forceinline__ float hlo(uint32_t v) { float r; asm("{.reg .b16 a,b; mov.b32 {a,b},%1; cvt.f32.f16 %0,a;}" : "=f"(r) : "r"(v)); return r; }
__device__ __forceinline__ float hhi(uint32_t v) { float r; asm("{.reg .b16 a,b; mov.b32 {a,b},%1; cvt.f32.f16 %0,b;}" : "=f"(r) : "r"(v)); return r; }
__device__ __forceinline__ uint32_t ordh(uint32_t v) {
  uint32_t r;
  asm("{.reg .b32 m; prmt.b32 m,%1,0,0xbb99; lop3.b32 %0,%1,m,0x7fff7fff,0x78;}" : "=r"(r) : "r"(v));
  return r;
}
template <bool MASK>
__device__ __forceinline__ float4 softmax2(const uint2 (&r)[4], uint32_t mx, uint32_t my, uint32_t& k) {
  uint32_t x = addh(addh(r[0].x, r[1].x), addh(r[2].x, r[3].x)), y = addh(addh(r[0].y, r[1].y), addh(r[2].y, r[3].y));
  if (MASK) { x = addh(x, mx); y = addh(y, my); }
  asm("max.f16x2 %0,%1,%2;" : "=r"(k) : "r"(x), "r"(y));
  k = ordh(k);
  const int k0 = __reduce_max_sync(~0u, (int)(k << 16)), k1 = __reduce_max_sync(~0u, (int)k);
  const float m0 = hhi(k0 ^ ((k0 >> 31) & 0x7fff0000)) * -16.f, m1 = hhi(k1 ^ ((k1 >> 31) & 0x7fff0000)) * -16.f;
  return make_float4(ex2(fmaf(hlo(x), 16.f, m0)), ex2(fmaf(hhi(x), 16.f, m1)), ex2(fmaf(hlo(y), 16.f, m0)), ex2(fmaf(hhi(y), 16.f, m1)));
}
__device__ __forceinline__ char* mkp(uint32_t lo, uint32_t hi) { uint64_t r; asm("mov.b64 %0,{%1,%2};" : "=l"(r) : "r"(lo), "r"(hi)); return (char*)r; }
#define LO(p) ((uint32_t)(uint64_t)(p))
#define HI(p) ((uint32_t)((uint64_t)(p) >> 32))
__device__ __forceinline__ void cp16(uint32_t dst, const void* src) { asm volatile("cp.async.cg.shared.global [%0],[%1],16;" ::"r"(dst), "l"(src) : "memory"); }
__device__ __forceinline__ uint32_t xor3(uint32_t a, uint32_t b, uint32_t c) { uint32_t r; asm volatile("lop3.b32 %0,%1,%2,%3,0x96;" : "=r"(r) : "r"(a), "r"(b), "r"(c)); return r; }
__device__ __forceinline__ uint32_t mulbf(uint32_t a, uint32_t b) { uint32_t r; asm("mul.rn.bf16x2 %0,%1,%2;" : "=r"(r) : "r"(a), "r"(b)); return r; }
__device__ __forceinline__ uint32_t fmabf(uint32_t a, uint32_t b, uint32_t c) { uint32_t r; asm("fma.rn.bf16x2 %0,%1,%2,%3;" : "=r"(r) : "r"(a), "r"(b), "r"(c)); return r; }
__device__ __forceinline__ uint32_t addbf(uint32_t a, uint32_t b) { uint32_t r; asm("add.rn.bf16x2 %0,%1,%2;" : "=r"(r) : "r"(a), "r"(b)); return r; }
__device__ __forceinline__ void pv_mem(const uint32_t (&p)[4], uint32_t pm, const uint4 (&v)[4], const uint4 (&vn)[2], uint32_t (&O)[4]) {
  float o[4][4] = {{0, 0, 0, 0}, {0, 0, 0, 0}, {0, 0, 0, 0}, {0, 0, 0, 0}};
  mma16(o[0], v[0].x, v[0].y, v[0].z, v[0].w, p[0], p[1]);
  mma16(o[1], v[2].x, v[2].y, v[2].z, v[2].w, p[0], p[1]);
  mma16(o[2], v[1].x, v[1].y, v[1].z, v[1].w, p[2], p[3]);
  mma16(o[3], v[3].x, v[3].y, v[3].z, v[3].w, p[2], p[3]);
  mma16(o[0], vn[0].x, vn[0].y, vn[0].z, vn[0].w, pm, pm);
  mma16(o[1], vn[1].x, vn[1].y, vn[1].z, vn[1].w, pm, pm);
  O[0] = pk(o[0][0] + o[2][0], o[0][1] + o[2][1]); O[1] = pk(o[0][2] + o[2][2], o[0][3] + o[2][3]);
  O[2] = pk(o[1][0] + o[3][0], o[1][1] + o[3][1]); O[3] = pk(o[1][2] + o[3][2], o[1][3] + o[3][3]);
}
__device__ __forceinline__ void pv_tok(const uint32_t (&p)[4], uint32_t pm, const uint4 (&v)[4], const uint32_t (&vm)[4], uint32_t (&O)[4]) {
  float o[2][4] = {{0, 0, 0, 0}, {0, 0, 0, 0}}, sum[4] = {0, 0, 0, 0};
  const uint32_t one = 0x3f803f80u;
  mma16(sum, one, one, one, one, p[0], p[1]);
  mma16(o[0], v[0].x, v[0].y, v[0].z, v[0].w, p[0], p[1]);
  mma16(o[1], v[2].x, v[2].y, v[2].z, v[2].w, p[0], p[1]);
  mma16(sum, one, one, one, one, p[2], p[3]);
  mma16(o[0], v[1].x, v[1].y, v[1].z, v[1].w, p[2], p[3]);
  mma16(o[1], v[3].x, v[3].y, v[3].z, v[3].w, p[2], p[3]);
  mma8(sum, one, one, pm);
  mma8(o[0], vm[0], vm[1], pm);
  mma8(o[1], vm[2], vm[3], pm);
  float i0, i1;
  asm("rcp.approx.ftz.f32 %0,%1;" : "=f"(i0) : "f"(sum[0]));
  asm("rcp.approx.ftz.f32 %0,%1;" : "=f"(i1) : "f"(sum[1]));
  O[0] = pk(o[0][0] * i0, o[0][1] * i1); O[1] = pk(o[0][2] * i0, o[0][3] * i1);
  O[2] = pk(o[1][0] * i0, o[1][1] * i1); O[3] = pk(o[1][2] * i0, o[1][3] * i1);
}
__device__ __forceinline__ uint32_t sum4bf(uint32_t a, uint32_t b, uint32_t c, uint32_t d) { return addbf(addbf(a, b), addbf(c, d)); }
template <int OFF>
__device__ __forceinline__ void sta1(uint32_t a, uint32_t v, uint32_t mb) {
  asm volatile("st.async.shared::cluster.mbarrier::complete_tx::bytes.b32 [%0+%3],%1,[%2];" ::"r"(a), "r"(v), "r"(mb), "n"(OFF) : "memory");
}

__device__ __forceinline__ void wait_time(uint32_t t) { while ((int)(gtime() - t) < 0) __nanosleep(64); }
__device__ __noinline__ void rec_prefetch(const char* wmod, const char* w1, const char* x, const char* wo) {
  const int hb = blockIdx.x - 128;
  const uint32_t t0 = gtime();
  uint32_t t = t0 + PF0;
#pragma unroll 1
  for (int job = 0; job < (PFT ? 5 : 3); job++) {
    const char* p = job == 0 ? x + (6 + hb) * 65536 : job == 1 ? wmod + hb * 12288 + 4096 : job == 2 ? w1 + hb * 7168 : job == 3 ? x + hb * 8192 : wo + (1020 + hb) * 8192;
    const int n = job == 0 ? 120 - (hb & 2) * 4 : job == 3 ? 128 : 256, d = job == 0 ? 8192 : job == 1 ? 49152 : job == 2 ? 28672 : job == 3 ? 32768 : -32768;
    if (job == 3) t = t0 + PFT;
    PT(8 + job);
#pragma unroll 1
    for (int i = 0; i < n; i++) {
      wait_time(t);
      asm volatile("cp.async.bulk.prefetch.L2.global [%0], %1;" ::"l"(p), "r"(job == 2 ? 7168 : 8192) : "memory");
      p += !job && (i & 7) == 7 ? 204800 : d;
      t += job < 3 ? PFD : PFS;
      if (job && (i & 31) == 31 && ldg_rlx1(&g_fin)) return;
    }
  }
  PT(13);
}
__device__ __noinline__ void rec_helper(uint32_t sb, const bf16* cvec, const bf16* wmod, const char* w1, const bf16* b1, uint32_t t0) {
  const int tid = threadIdx.x, hb = blockIdx.x - 128;
  PT(1);
  for (int i = tid; i < 1024; i += 256) sts1(sb + i * 8, U_(rbf(silu(__bfloat162float(cvec[i])))));
  for (int i = tid; i < 2048; i += 256) g_stat[hb * 2048 + i] = make_uint4(~0u, ~0u, ~0u, ~0u);
  for (int i = tid; i < 512; i += 256) g_cnt[hb * 512 + i] = 0;
#pragma unroll 1
  for (int job = 0; job < 2; job++) {
    wait_time(t0 + PF0 + (job ? 600 : 350) * PFD);
    BAR_SYNC(rec::B_F, 256);
    PT(2 + job * 5);
    const int n8 = job ? 112 : 128, rg = tid >= n8, cg = tid - rg * n8, pitch = job ? 448 : 768;
    const uint4* p = (const uint4*)(job ? w1 + hb * 1792 : (const char*)(wmod + 2048 + hb * 1024)) + rg * pitch + min(cg, n8 - 1);
    float a1[8] = {0, 0, 0, 0, 0, 0, 0, 0}, a2[8] = {0, 0, 0, 0, 0, 0, 0, 0};
#pragma unroll 1
    for (int r0 = rg; r0 < 1024; r0 += 32) {
      uint4 v[16];
#pragma unroll
      for (int i = 0; i < 16; i++) { v[i] = ldg_rlx4(p); p += 2 * pitch; }
#pragma unroll
      for (int i = 0; i < 16; i++) {
        const float2 f = lds2f(sb + (r0 + 2 * i) * 8);
        const float w[8] = {blo(v[i].x), bhi(v[i].x), blo(v[i].y), bhi(v[i].y), blo(v[i].z), bhi(v[i].z), blo(v[i].w), bhi(v[i].w)};
#pragma unroll
        for (int e = 0; e < 8; e++) { a1[e] += f.x * w[e]; a2[e] += f.y * w[e]; }
      }
    }
    const uint32_t rd = sb + 8192;
    if (cg < n8) {
#pragma unroll
      for (int e = 0; e < 8; e++) sts2(rd + rg * 8192 + (cg * 8 + e) * 8, U_(a1[e]), U_(a2[e]));
    }
    BAR_SYNC(rec::B_F, 256);
    if (job == 0) {
      for (int i = tid; i < 1024; i += 256) g_mod[2048 + hb * 1024 + i] = rbf(F_(lds1(rd + i * 8)) + F_(lds1(rd + 8192 + i * 8)));
      BAR_SYNC(rec::B_F, 256);
      PT(6);
      if (tid == 0) { red_rel(&g_mcnt); wait_cnt(&g_mcnt, 4); }
      BAR_SYNC(rec::B_F, 256);
      for (int i = tid; i < 1024; i += 256) sts2(sb + i * 8, U_(rbf(1.f + __ldcg(g_mod + 4096 + i))), U_(__ldcg(g_mod + 3072 + i)));
    } else {
      for (int i = tid; i < 448; i += 256) {
        const int gn = hb * 896 + i * 2;
        const uint32_t bb = *(const uint32_t*)(b1 + gn);
        const float4 u = lds4f(rd + i * 16), w = lds4f(rd + 8192 + i * 16);
        ((uint2*)g_cc)[(gn >> 4) * 8 + ((gn >> 1) & 3) * 2 + ((gn >> 3) & 1)] = make_uint2(pk(u.x + w.x, u.z + w.z), pk(0.5f * (u.y + w.y + blo(bb)), 0.5f * (u.w + w.w + bhi(bb))));
      }
      PT(4);
    }
  }
}

__global__ void __cluster_dims__(2, 1, 1) __launch_bounds__(512, 1)
k_rec(const __grid_constant__ RecMaps mp, const bf16* __restrict__ mem0, const bf16* __restrict__ x, const bf16* __restrict__ cvec,
      const bf16* __restrict__ wmod, const char* __restrict__ w1, const bf16* __restrict__ b1, const char* __restrict__ wo, char* xc, int dF, int dA, int dS, int dM, int dG, int dP, int dX, int dD, int dZ, int dZ2, int dV, int dX2) {
  using namespace rec;
  extern __shared__ __align__(1024) char smem[];
  const uint32_t sb = (uint32_t)__cvta_generic_to_shared(smem);
  if ((sb & 0x3FFFF) != 1024) __trap();
  PH(0); if (threadIdx.x == 0) PT(0);
  if (threadIdx.x == 0) {
    int b = blockIdx.x;
    if (b >= 8 && b < 128) {
      const int t = (b >> 1) - 4, u = t - 32;
      b = 2 * (t < 32 ? 4 + (t & 16) + (t & 7) * 2 + ((t >> 3) & 1) : 36 + (u / 14) * 14 + (u % 7) * 2 + ((u / 7) & 1)) + (b & 1);
    }
    sts1(sb + rec::PACE + 24, b);
    const int c = blockIdx.x >> 1, l = c < 36 ? (c - 4) & 7 : (c - 36) % 7, m = c < 4 ? c : c < 36 ? (c - 4) >> 3 : (c - 36) / 7;
    const int g = c < 4 ? 15 : (l >> 1) * 4 + (l & 1) + (c < 36 ? 0 : 2);
    unsigned sm;
    asm("mov.u32 %0,%%smid;" : "=r"(sm));
    if (c < 64) g_slot[sm & 255] = 1 + FMAP;
  }
#define ROLE_REFRESH { asm volatile("mov.u32 %0,%%tid.x;" : "=r"(tid)); wid = __shfl_sync(~0u, tid >> 5, 0); b = __shfl_sync(~0u, lds1(sb + PACE + 24), 0); }
#define ROLE_VARS int tid; asm volatile("mov.u32 %0,%%tid.x;" : "=r"(tid)); \
    int wid = __shfl_sync(~0u, tid >> 5, 0), b = __shfl_sync(~0u, lds1(sb + PACE + 24), 0);
#define wg (wid >> 2)
#define iw (wid & 3)
#define h (b >> 2)
#define j (b & 3)
#define a (b & 1)
#define bb ((b >> 1) & 1)
  const uint32_t wbar = sb + BARS + 48, obar = wbar + 8;
  if (threadIdx.x == 256) {
    for (int i = 0; i < 18; i++) if (i != 12) mbar_init(sb + BARS + i * 8, i == 3 || i == 8 || i == 9 || i == 10 ? 2 : 1);
    for (int i = 0; i < 3; i++) mbar_init(sb + PACE + i * 8, 1);
    asm volatile("fence.mbarrier_init.release.cluster;" ::: "memory");
    FENCE_ASYNC_SMEM();
    mbar_expect(sb + BARS, 2048);
    mbar_expect(sb + BARS + 16, 4096);
    mbar_expect(sb + BARS + 32, 4096);
    mbar_expect(sb + BARS + 40, 4096);
  }
  __syncthreads();
  asm volatile("barrier.cluster.arrive.relaxed.aligned;" ::: "memory");
#define lane ((int)(l16 >> 4))
#define l16 (L16 & 0x1f0)
#define is7 ((L16 & 112) == 112)
#define PIN(x) __shfl_xor_sync(~0u, (uint32_t)(x), 0)
#define REFRESH() L16 = __shfl_xor_sync(~0u, L16, 0)
#define lar ((L16 & 0x180) * 8 + (L16 & 0x70))
#define X_LOAD(n, w, u) \
        asm volatile("{.reg .pred p; elect.sync _|p, 0xffffffff; @p mbarrier.arrive.expect_tx.shared.b64 _,[%2],8192;\n" \
                     "@p cp.async.bulk.shared::cluster.global.mbarrier::complete_tx::bytes [%0],[%1],8192,[%2];}" ::"r"(sb + XB + (w) * 16384 + (u) * 8192), \
                     "l"(g_h + (n) * 4096 + a * 2048 + (w) * 1024 + (u) * 512), "r"(sb + BARS + 64 + (w) * 8) : "memory")
#define lpub ((L16 & 0x30) * 64 + ((L16 >> 3) & 0x38))
#define lrow ((L16 & 0x70) + (((L16 >> 3) ^ L16) & 0x70 & ~((L16 >> 3) & 0x40) ? L16 & 0x180 : 512))

  const int role = __shfl_sync(~0u, threadIdx.x >> 7, 0);
  if (role < 2) {
    asm volatile("setmaxnreg.inc.sync.aligned.u32 %0;" ::"n"(RF_));
    ROLE_VARS
    uint32_t L16 = __shfl_sync(~0u, sb + (tid & 31) * 16, tid & 31);
    uint32_t wQ[16][4], wK[16][4], wV[NVR][4];
    uint32_t m0[2][4];
    uint32_t frag = sb + ((lane & 7) + (lane >> 4) * 8) * 128 + (((iw * 2 + ((lane >> 3) & 1)) ^ (lane & 7)) << 4);
#define QSW (SWP && !a ? 64 : 0)
    {
      const bool spare = b >= 128;
      const uint32_t t0 = gtime();
      uint4 xr[16];
      int seg = spare ? b - 126 : wg;
      const int half = spare ? wg : a;
      auto x_fetch = [&]() {
        const uint4* px = (const uint4*)x + (seg * 32 + iw * 8 + (lane >> 2)) * 128 + half * 64 + (lane & 3);
#pragma unroll
        for (int i = 0; i < 16; i++) xr[i] = __ldg(px + i * 4);
      };
      if (!spare) {
        uint4 wm[8];
        const uint4* pw = (const uint4*)(wmod + (size_t)((b >> 5) * 256 + (tid >> 3)) * 6144 + (b & 31) * 64) + (tid & 7);
        const float cs = __bfloat162float(cvec[(b >> 5) * 256 + tid]);
#pragma unroll
        for (int i = 0; i < 8; i++) wm[i] = __ldcs(pw + (size_t)i * 32 * 768);
        unsigned short mr[16];
#pragma unroll
        for (int i = 0; i < 16; i++) mr[i] = __bfloat16_as_ushort(mem0[(i & 7) * 1024 + a * 512 + tid * 2 + (i >> 3)]);
        float* sc = (float*)(smem + PRE);
        sc[tid] = rbf(silu(cs));
        PT(1);
        BAR_SYNC(B_F, 256);
        float acc[8] = {0, 0, 0, 0, 0, 0, 0, 0};
#pragma unroll
        for (int i = 0; i < 8; i++) {
          const float f = sc[i * 32 + (tid >> 3)];
          acc[0] += f * blo(wm[i].x); acc[1] += f * bhi(wm[i].x); acc[2] += f * blo(wm[i].y); acc[3] += f * bhi(wm[i].y);
          acc[4] += f * blo(wm[i].z); acc[5] += f * bhi(wm[i].z); acc[6] += f * blo(wm[i].w); acc[7] += f * bhi(wm[i].w);
        }
#pragma unroll
        for (int i = 0; i < 8; i++) { acc[i] += __shfl_xor_sync(~0u, acc[i], 8); acc[i] += __shfl_xor_sync(~0u, acc[i], 16); }
        float* red = sc + 1024;
        if ((tid & 31) < 8) {
#pragma unroll
          for (int i = 0; i < 8; i++) red[(tid >> 5) * 64 + (tid & 7) * 8 + i] = acc[i];
        }
        BAR_SYNC(B_F, 256);
        PT(2);
        if (tid < 64) {
          float t = 0;
#pragma unroll
          for (int i = 0; i < 8; i++) t += red[i * 64 + tid];
          asm volatile("st.relaxed.gpu.global.u32 [%0],%1;" ::"l"((unsigned*)g_modp + (b >> 5) * 2048 + (b & 31) * 64 + tid), "r"(U_(t) | 1u) : "memory");
        }
#pragma unroll
        for (int i = 0; i < 8; i++) m0[i >> 2][i & 3] = mr[i * 2] | ((uint32_t)mr[i * 2 + 1] << 16);
      } else {
        asm volatile("griddepcontrol.launch_dependents;");
      }
      x_fetch();
      const uint32_t md = sb + PRE + 6144, rx = mapa(sb, a ^ !spare);
      asm volatile("barrier.cluster.wait.aligned;" ::: "memory");
      if (!spare) {
        mbar_wait(sb + BARS + 88, 0);
#pragma unroll
        for (int i = 0; i < 16; i++) ldsm4t(wQ[i], (frag ^ QSW) + WO + wg * 32768 + i * 2048);
      }
      PT(4);
#pragma unroll 1
      for (int it = 0;; it++) {
        if (tid == 0) mbar_expect(sb + BARS + 104, 512);
        float c[4][4] = {{0, 0, 0, 0}, {0, 0, 0, 0}, {0, 0, 0, 0}, {0, 0, 0, 0}};
#pragma unroll
        for (int i = 0; i < 16; i++) {
          mma16(c[(i & 1) * 2], xr[i].x, 0x3f803f80u, xr[i].y, 0x3f803f80u, xr[i].x, xr[i].y);
          mma16(c[(i & 1) * 2 + 1], xr[i].z, 0x3f803f80u, xr[i].w, 0x3f803f80u, xr[i].z, xr[i].w);
        }
#pragma unroll
        for (int e = 0; e < 4; e++) c[0][e] = (c[0][e] + c[1][e]) + (c[2][e] + c[3][e]);
        const int src = (lane & 28) + (lane >> 3);
        const float sq = __shfl_sync(~0u, (lane & 4) ? c[0][1] : c[0][0], src), sm = __shfl_sync(~0u, (lane & 4) ? c[0][3] : c[0][2], src);
        if ((lane & 3) < 2) sta1<0>(rx + PRE + 10240 + (wid ^ (spare * 4)) * 64 + (lane >> 2) * 8 + (lane & 1) * 4, U_((lane & 1) ? sm : sq), rx + BARS + 104);
        mbar_wait(sb + BARS + 104, it & 1);
        const float2 ot = lds2f(sb + PRE + 10240 + wid * 64 + (lane >> 2) * 8);
        const float mean = (sm + ot.y) * (1.f / 1024);
        const float rs = rsqrtf(fmaxf((sq + ot.x) * (1.f / 1024) - mean * mean, 0.f) + 1e-5f), nm = -mean * rs;
#define NRM(v) v = pk(fmaf(blo(v), rs, nm), fmaf(bhi(v), rs, nm))
#pragma unroll
        for (int i = 0; i < 16; i++) { NRM(xr[i].x); NRM(xr[i].y); NRM(xr[i].z); NRM(xr[i].w); }
        if (!it) {
          PT(3);
#pragma unroll 1
          for (int i = 0; i < 2; i++) {
            uint4 p[4];
            for (int n = 0;; n++) {
#pragma unroll
              for (int e = 0; e < 4; e++) p[e] = ldg_rlx4(g_modp + e * 512 + i * 256 + tid);
              uint32_t ok = 1;
#pragma unroll
              for (int e = 0; e < 4; e++) ok &= p[e].x & p[e].y & p[e].z & p[e].w;
              if (__all_sync(~0u, ok) || n > SPIN_LIMIT / 16) break;
              __nanosleep(100);
            }
#define MSUM(e) (i + rbf((F_(p[0].e) + F_(p[1].e)) + (F_(p[2].e) + F_(p[3].e))))
            sts2(md + i * 2048 + tid * 8, pk(MSUM(x), MSUM(y)), pk(MSUM(z), MSUM(w)));
          }
          BAR_SYNC(B_F, 256);
          PT(5);
        }
        const int e0 = (iw * 8 + (lane >> 2)) * 8 + ((lane & 3) ^ (lane >> 2));
        uint4* dst = g_h + seg * 4096 + half * 2048;
#pragma unroll
        for (int i = 0; i < 16; i++) {
          const uint32_t ma = md + half * 1024 + (lane & 3) * 16 + i * 64;
          const uint4 sv = lds4(ma), cv = lds4(ma + 2048);
          xr[i] = make_uint4(fmabf(xr[i].x, cv.x, sv.x), fmabf(xr[i].y, cv.y, sv.y), fmabf(xr[i].z, cv.z, sv.z), fmabf(xr[i].w, cv.w, sv.w));
        }
        if (!spare) {
#pragma unroll
          for (int i = 0; i < 16; i++) sts4(sb + WO + wg * 32768 + (e0 ^ ((i & 1) * 4)) * 16 + (i >> 1) * 4096, xr[i].x, xr[i].y, xr[i].z, xr[i].w);
          break;
        }
#pragma unroll
        for (int i = 0; i < 16; i++) dst[(e0 ^ ((i & 1) * 4)) + (i >> 1) * 256] = xr[i];
        seg += 4;
        if (seg < 64) x_fetch();
        FENCE_ASYNC();
        BAR_SYNC(B_F, 256);
        if (tid == 0) red_rlx(g_hf + b - 128);
        if (seg >= 64) break;
      }
      if (spare) { rec_helper(sb, cvec, wmod, w1, b1, t0); return; }
      PH(1); PH(2); PT(6);
    }
    ROLE_REFRESH
    mbar_wait(wbar, 0);
    PT(7);
#pragma unroll
    for (int i = 0; i < 16; i++) ldsm4t(wK[i], (frag ^ QSW) + XB + wg * 32768 + i * 2048);
#pragma unroll
    for (int i = 0; i < NVR; i++) ldsm4t(wV[i], frag + MEM + (wg * NVR + i) * 2048);
    FENCE_ASYNC_SMEM();
    PH(3); PT(8);
    CLUSTER_SYNC();
    PT(9);
#pragma unroll
    for (int i = 0; i < 2; i++) {
      const int k = tid * 2 + i, m = (k >> 3) & 3, r = k & 7;
      sts4(sb + MEM + (k >> 5) * 640 + (r == m ? 512 : m * 128) + r * 16, m0[i][0], m0[i][1], m0[i][2], m0[i][3]);
    }
    if (lane < 8) {
      sts4(sb + ARO + wid * 640 + (lane < 4 ? lane * 144 : 512 + l16), 0x3f803f80, 0x3f803f80, 0x3f803f80, 0x3f803f80);
#pragma unroll
      for (int i = 0; i < 2; i++) sts4(sb + MEM + (wid * 2 + i) * 640 + (lane < 4 ? lane * 144 : 512 + l16), 0x42004200, 0x42004200, 0x42004200, 0x42004200);
    }
#define ownv ((iw >> 1) == a)
#define owner (SWP ? iw >= 2 : ownv)
#define vfin ((wid >> 1) == a)
#define oi (wid & 1)
    frag += wg * NVS * 2048;
    {
      const uint32_t rsb = mapa(sb, owner ? a : a ^ 1);
      const uint32_t pp = rsb + PK + (owner ? 0 : 12288) + (oi * 2048 + wg * 1024) + l16;
      const uint32_t mb = sb + MEM + wg * 5120;
      sts4(L16 + TF + wid * 512, mb + lrow, owner ? L16 + (lane >> 4) * (RK - RQ - 256) + RQ + oi * 1024 + wg * 256 : rsb + RQ + oi * 1024 + 512 + wg * 256 + (l16 >> 2),
           L16 + OB, frag);
      sts4(L16 + TF + 4096 + wid * 512, sb + WO + (wid >> 1) * 16384 + ((lane & 7) + (lane >> 4) * 8) * 128 + ((((wid & 1) * 4 + ((lane >> 3) & 1)) ^ (lane & 7)) << 4),
           sb + ARO + wid * 640 + lrow, pp, LO(xc) + h * 262144 + (bb * 2 + (iw >> 1)) * XC + X_VM(0) + oi * 2048 + a * 256 + (l16 >> 1));
    }
    uint32_t tp = L16 + TF + wid * 512;
    auto park_ptr = [&]() { return lds1(tp + 4096 + 8); };
    auto park = [&](const float* f, int m, int n, uint32_t d) {
      uint32_t w[8];
#pragma unroll
      for (int i = 0; i < 8; i++) w[i] = pk(f[2 * i], f[2 * i + 1]);
      if (SWP && m == 2) d += (sb & 0x1000000) ? 0 : owner ? 0x1003000 : -0x1003000;
      if (m == 2 ? ownv : owner) {
        sts4(d + m * 4096, w[0], w[1], w[2], w[3]); sts4(d + m * 4096 + 512, w[4], w[5], w[6], w[7]);
      } else {
        const uint32_t pb = (d & 0xff000000u) | (1024 + BARS + (m ? 24 + m * 8 : 16));
        sta4(d + m * 4096, w, pb); sta4(d + m * 4096 + 512, w + 4, pb);
      }
    };
    auto xdesc = [&](uint32_t xb) { return mkdesc(__shfl_sync(~0u, 1024 + xb + wg * 16384, 0), 16, 1024); };
    auto rs_issue = [&](float* acc, const uint32_t (&w)[16][4], uint32_t xb, bool fence) {
      const uint64_t x = xdesc(xb);
      if (fence) WG_FENCE();
      wgmma_rs_n32_z(acc, w[0], x);
#pragma unroll
      for (int i = 1; i < 16; i++) wgmma_rs_n32(acc, w[i], x + (i >> 2) * 256 + (i & 3) * 2, 1);
      WG_COMMIT();
    };
    auto v_issue = [&](float* acc, uint32_t xb, bool fence) {
      const uint64_t dv = mkdesc(__shfl_sync(~0u, 1024 + WVS + wg * NVS * 2048, 0), 16, 1024), x = xdesc(xb);
      if (fence) WG_FENCE();
      wgmma_rs_n32_z(acc, wV[0], x);
#pragma unroll
      for (int i = 1; i < (KVO == 2 ? NVR : 0); i++) wgmma_rs_n32(acc, wV[i], x + (i >> 2) * 256 + (i & 3) * 2, 1);
#pragma unroll
      for (int i = NVR; i < 16; i++) wgmma_ssT_n32(acc, dv + (i - NVR) * 128, x + (i >> 2) * 256 + (i & 3) * 2, 1);
#pragma unroll
      for (int i = 1; i < (KVO == 2 ? 0 : NVR); i++) wgmma_rs_n32(acc, wV[i], x + (i >> 2) * 256 + (i & 3) * 2, 1);
      WG_COMMIT();
    };
    uint32_t mA;
    auto vk_pass = [&](int n, uint32_t d, uint32_t xb, bool steady) {
      float acc[16], acc2[16];
      v_issue(acc, xb, true);
      rs_issue(acc2, wK, xb, false);
      if (steady || n) mbar_wait(sb + BARS + 80, (n - 1) & 1);
      WG_WAIT(1);
      park(acc, 2 - !!KVO, n, d);
      mA = lds1(tp); if (NF) frag = lds1(tp + 12);
      if (steady) BAR_ARRIVE(B_K, 320);
      WG_WAIT(0);
      park(acc2, 1 + !!KVO, n, d);
    };
    PT(10);
#pragma unroll 1
    for (int n = 0; n < 2; n++) {
      float acc[16];
      asm volatile("" : "+r"(wid));
      rs_issue(acc, wQ, n * XB, true);
      if (n) {
        BAR_SYNC(B_C, 320);
        PT(12);
        mbar_wait(sb + BARS + 24, 0);
      } else {
#pragma unroll
        for (int i = 0; i < 8; i++) {
          const uint4 v = lds4(L16 + WO + 32768 + wid * 4096 + i * 512);
          sts4(L16 + XB + wid * 4096 + i * 512, v.x, v.y, v.z, v.w);
        }
      }
      WG_WAIT(0); park(acc, 0, n, park_ptr());
      FENCE_ASYNC_SMEM();
      vk_pass(n, park_ptr(), n * XB, false);
      if (n) break;
      PT(11);
      BAR_SYNC(B_C, 320);
      if (tid == 0) {
        mbar_expect(obar, 65536);
#pragma unroll 1
        for (int i = 0; i < 4; i++) tma2d(sb + WO + i * 16384, &mp.wo, j * 256 + i * 64, h * 128, obar);
      }
    }
    static_assert(WO == 0, "x");
    {
      BAR_ARRIVE(B_P, N_P); if (!HX) BAR_ARRIVE(B_X, 320); if (XE != 1) BAR_ARRIVE(B_Q, 288);
    }
    PT(13);
    mbar_wait(obar, 0);
    PH(4); PT(14);
    ROLE_REFRESH
    for (int s = 0; s < 64; s++) {
      asm volatile("" : "+r"(tp), "+r"(wid));
      asm volatile("mov.u32 %0,%%cluster_ctarank;" : "=r"(b));
      uint32_t vS[NVS][4], bf[8][4];
      static_assert(NVR == 5, "schedule");
#define VLD(k) ldsm4t(vS[(k) - NVR], frag + WVS + ((k) - NVR) * 2048)
#define BLD(t) ldsm4t(bf[t], mA + (t) * 640)
#define VMMA(c, w, i) mma16(c, (w)[0], (w)[1], (w)[2], (w)[3], bf[(i) >> 1][((i) & 1) * 2], bf[(i) >> 1][((i) & 1) * 2 + 1])
#define VS_(c, k) VMMA(c, vS[(k) - NVR], k)
#define QK(i) VMMA(cQ, wQ[i], i); VMMA(cK, wK[i], i)
#define PREV if (NF) { VLD(13); VLD(12); if (NF > 2) VLD(11); } else { VLD(15); VLD(14); }
      if (NF) { VLD(15); VLD(14); }
      if (s > 0) BAR_SYNC(B_R, N_R);
      float cV[4] = {0, 0, 0, 0}, cW[4] = {0, 0, 0, 0};
      {
        float cQ[4] = {0, 0, 0, 0}, cK[4] = {0, 0, 0, 0};
        BLD(7); BLD(6); BLD(5); BLD(4); if (NB0 > 4) BLD(3);
        SCHED_FENCE(47);
        QK(15); if (NF) VS_(cV, 15);
        QK(14); if (NF) VS_(cV, 14);
        QK(13); QK(12);
        SCHED_FENCE(51);
        if (NB0 < 5) BLD(3);
        BLD(2); BLD(1); BLD(0);
        const uint32_t rm = lds1(tp + 4);
        if (!NF) frag = lds1(tp + 12);
        QK(11); QK(10); QK(9); QK(8); QK(7);
        if (PV0 == 6) { SCHED_FENCE(48); PREV }
        QK(6); QK(5);
        if (PV0 == 4) { QK(4); SCHED_FENCE(48); PREV } else { QK(4); }
        QK(3); QK(2); QK(1); QK(0);
        const uint32_t w0 = pk(cQ[0] * SCS, cQ[1] * SCS), w1 = pk(cQ[2] * SCS, cQ[3] * SCS), w2 = pk(cK[0], cK[1]), w3 = pk(cK[2], cK[3]);
        if (owner) {
          stsm4(rm, w0, w1, w2, w3);
          BAR_ARRIVE(B_E, 256);
        } else {
          const uint32_t mm = (rm & 0xff000000u) | (1024 + BARS);
          sta1<0>(rm, w0, mm); sta1<128>(rm, w1, mm);
          sta1<RK - RQ>(rm, w2, mm); sta1<RK - RQ + 128>(rm, w3, mm);
        }
        if (wid == 2) TS(0);
      }
      uint4 t1;
      uint32_t oA, wo[16][4];
      {
        if (NF == 0) {
          VLD(13); VLD(12);
          VS_(cW, 15); VS_(cV, 14); VLD(11); VMMA(cW, wV[0], 0); VLD(10); VMMA(cV, wV[1], 1); VLD(9);
          VMMA(cW, wV[2], 2); VLD(8); VMMA(cV, wV[3], 3); VLD(7); VMMA(cW, wV[4], 4); VS_(cV, 13); VLD(6); VS_(cW, 12); VLD(5);
          VS_(cV, 11);
        } else {
          if (NF < 3) VLD(11);
          VLD(10);
          VS_(cW, 13); VLD(9); VS_(cV, 12); VLD(8); VLD(7); VMMA(cW, wV[0], 0); VMMA(cV, wV[1], 1); VLD(6);
          VMMA(cW, wV[2], 2); VMMA(cV, wV[3], 3); VLD(5); VMMA(cW, wV[4], 4); VS_(cV, 11);
        }
        VS_(cW, 10); VS_(cV, 9); VS_(cW, 8); VS_(cV, 7); VS_(cW, 6); VS_(cV, 5);
#pragma unroll
        for (int e = 0; e < 4; e++) cV[e] += cW[e];
        const uint32_t ex = tp + (RX - TF) - wg * 2048;
        t1 = lds4(tp + 4096 + (T1L ? vS[3][0] & dZ : 0));
        oA = lds1(tp + 8 + (s & dZ));
        if (wg) {
          sts4(ex, U_(cV[0]), U_(cV[1]), U_(cV[2]), U_(cV[3]));
          BAR_ARRIVE(B_T2, 256);
        }
#pragma unroll
        for (int i = 0; i < VCO; i++) ldsm4t(wo[i], (t1.x ^ ((i & 1) * 32)) + (i >> 1) * 2048);
        if (!wg) {
          BAR_SYNC(B_T2, 256);
          const float4 u = lds4f(ex);
          stg_b64(mkp(t1.w ^ ((s & 1) * X_RING), HI(xc)), (pk(cV[0] + u.x, cV[1] + u.y) & ~1u) | (((s >> 1) + 1) & 1), pk(cV[2] + u.z, cV[3] + u.w));
        }
      }
      if (s == 63) break;
      {
        const uint32_t woA = t1.x, woB = woA ^ 32;
#pragma unroll
        for (int i = VCO; i < NW0; i++) ldsm4t(wo[i], ((i & 1) ? woB : woA) + (i >= WCH ? wo[(i - WCH + NWP) % NWP][0] & dZ : 0) + (i >> 1) * 2048);
        BAR_SYNC(B_S, 416);
        if (s < 62) {
          float acc[16];
          rs_issue(acc, wQ, XB, true);
          mbar_wait(sb + BARS + 24, (s + 1) & 1);
          WG_WAIT(0);
          if (PKE) park(acc, 0, s + 2, t1.z);
#pragma unroll
          for (int i = NW0; i < (PKE ? NWP : NW1); i++) ldsm4t(wo[i], ((i & 1) ? woB : woA) + (i >> 1) * 2048);
          BAR_SYNC(B_V, N_V);
          if (!PKE) park(acc, 0, s + 2, t1.z);
        } else {
#pragma unroll
          for (int i = NW0; i < (PKE ? NWP : NW1); i++) ldsm4t(wo[i], ((i & 1) ? woB : woA) + (i >> 1) * 2048);
          BAR_SYNC(B_V, N_V);
        }
#pragma unroll
        for (int i = PKE ? NWP : NW1; i < NWP; i++) ldsm4t(wo[i], ((i & 1) ? woB : woA) + (i >> 1) * 2048);
        float inv0, inv1;
        {
          uint32_t p[4], pm;
          const uint32_t pa = oA + (SC - OB), one = 0x3f803f80u;
          float sum[4] = {0, 0, 0, 0}, su2[4] = {0, 0, 0, 0};
          ldsm4t(p, pa);
          asm volatile("ldmatrix.sync.aligned.m8n8.x1.trans.shared.b16 {%0},[%1];" : "=r"(pm) : "r"(pa + 512) : "memory");
          mma16(sum, one, one, one, one, p[0], p[1]);
          mma16(su2, one, one, one, one, p[2], p[3]);
          mma8(sum, one, one, pm);
          inv0 = sum[0] + su2[0]; inv1 = sum[1] + su2[1];
          SCHED_FENCE(57);
        }
        BAR_SYNC(B_O, N_O);
        float c[2][4] = {{0, 0, 0, 0}, {0, 0, 0, 0}};
        uint32_t o[4][4];
#pragma unroll
        for (int i = 0; i < NOP_; i++) ldsm4t(o[i], oA + i * 512);
        SCHED_FENCE(46);
        asm("rcp.approx.ftz.f32 %0,%0;" : "+f"(inv0));
        asm("rcp.approx.ftz.f32 %0,%0;" : "+f"(inv1));
#pragma unroll
        for (int i = 0; i < 16; i++) {
          mma16(c[i & 1], wo[i][0], wo[i][1], wo[i][2], wo[i][3], o[i >> 2][i & 2], o[i >> 2][(i & 2) + 1]);
          if (i == 1 && NOP_ < 3) ldsm4t(o[2], oA + 1024);
          if (i == 3 && NOP_ < 4) ldsm4t(o[3], oA + 1536);
          if (i + NWP < 16) ldsm4t(wo[(i + NWP) & 15], (((i + NWP) & 1) ? woB : woA) + ((i + NWP) >> 1) * 2048);
        }
        stsm4(t1.y, pk(c[0][0] * inv0, c[0][1] * inv1), pk(c[0][2] * inv0, c[0][3] * inv1), pk(c[1][0] * inv0, c[1][1] * inv1), pk(c[1][2] * inv0, c[1][3] * inv1));
      }
      const uint32_t d = park_ptr();
      BAR_SYNC(B_W, 384);
      if (s < 62) {
        vk_pass(s + 2, d, XB, true);
        if (XE == 2) BAR_ARRIVE(B_Q, 288);
        BAR_ARRIVE(B_P, N_P); if (!HX) BAR_ARRIVE(B_X, 320);
        TS(10);
      } else {
        mA = lds1(tp); if (NF) frag = lds1(tp + 12);
      }
    }
  } else if (role == 3) {
    asm volatile("setmaxnreg.dec.sync.aligned.u32 24;");
    if (blockIdx.x >= 128) return;
    ROLE_VARS
    const uint32_t L16 = sb + (tid & 31) * 16;
    asm volatile("barrier.cluster.wait.aligned;" ::: "memory");
    CLUSTER_SYNC();
    sts1(sb + PACE + 36, LO(xc) + h * 262144 + X_VM(0));
    auto vm_stage = [&](int s) {
      if (AV) return;
      const uint32_t tag = ((s >> 1) + 1) & 1;
      const char* xm = mkp(lds1(sb + PACE + 36) + (s & 1) * X_RING + iw * XC + (l16 >> 1), HI(xc));
      uint2 m[4];
      CONSUME(LO(xm));
      BAR_SYNC(B_S2, 256);
      if (dZ2 > 1) { const uint32_t c = clk(); while (clk() - c < (uint32_t)dZ2) {} }
      int it = 0;
      while (true) {
#pragma unroll
        for (int i = 0; i < 4; i++) m[i] = ldg_b64(xm + (i >> 1) * 2048 + (i & 1) * 256);
        sts4(L16 + VN + iw * 512, m[0].x, m[0].y, m[1].x, m[1].y);
        sts4(L16 + VN + iw * 512 + 2048, m[2].x, m[2].y, m[3].x, m[3].y);
        if (HV || !anybad(m[0].x, m[1].x, m[2].x, m[3].x, tag)) break;
        RP(2);
        if (++it > SPIN_LIMIT) __trap();
      }
      if (s < 63) BAR_ARRIVE(B_V, 512); else BAR_ARRIVE(B_V, 256);
    };
    if (iw == 0) {
      wait_cnt(&g_hcnt, 128);
#pragma unroll 1
      for (int s = 0; s < 63; s++) {
        if (s < 62) for (int it = 0; ldg_rlx1(g_hf + (s & 3)) <= (s >> 2); it++) if (it > SPIN_LIMIT) __trap();
        if (XE == 1) BAR_SYNC(B_P, N_P); else if (XE == 2) BAR_SYNC(B_Q, 288); else if (s) BAR_SYNC(B_R, 320); else BAR_SYNC(B_Q, 288);
        if (s < 62) { X_LOAD(s + 2, 0, 0); X_LOAD(s + 2, 1, 0); X_LOAD(s + 2, 0, 1); X_LOAD(s + 2, 1, 1); }
        if (s >= 7) {
          const uint32_t zo = b * 160 + l16;
          if (l16 < 160) CONSUME(exch_b128(xc + AR_OFF + AR_ROW(zo >> 7) * 1024 + (zo & 127) + ((s + 1) & 7) * 128, 0, 0, 0, 0).x);
          __syncwarp();
        }
        if (s < 62) { mbar_wait(sb + BARS + 64, s & 1); mbar_wait(sb + BARS + 72, s & 1); }
        BAR_ARRIVE(B_S, 416);
        vm_stage(s);
        if (!AV) BAR_ARRIVE(B_O, 416);
        BAR_SYNC(B_W, 384);
        FENCE_ASYNC_SMEM();
        asm volatile("{.reg .pred p; elect.sync _|p, 0xffffffff; @p cp.reduce.async.bulk.tensor.3d.global.shared::cta.add.bulk_group [%0,{%1,%2,%4}],[%3];}"
                     ::"l"(&mp.ari), "r"((s & 7) * 64), "r"(AR_R(j)), "r"(sb + ARO), "r"(AR_P(j)) : "memory");
        BULK_COMMIT();
        asm volatile("st.relaxed.gpu.global.u32 [%0],%1;" ::"l"(g_tm + (s & 1) * 128 + b), "r"(gtime()) : "memory");
        TS(3);
        BULK_WAIT_READ(0);
      }
      if (!XE) BAR_ARRIVE(B_R, 320);
    } else if (iw == 1) {
      const uint32_t pc = sb + MEM + (lane >> 2) * 640 + (lane & 3) * 144 + (lane & 12), pd = sb + MEM + (lane & 15) * 640 + 576 + (lane & 3) * 16 + (lane & 12);
      uint32_t T = 0, par = 0;
      int est = dA;
#pragma unroll 1
      for (int s = 0; s < 63; s++) {
        if (s) {
          const uint4 tm = ldg_rlx4((const char*)g_tm + ((s + 1) & 1) * 512 + l16);
          const int t0 = tm.x - T, t1 = tm.y - T, t2 = tm.z - T, t3 = tm.w - T;
          const int e = max(dF + (__reduce_add_sync(~0u, (t0 + t1) + (t2 + t3)) >> 7), dV + __reduce_max_sync(~0u, max(max(t0, t1), max(t2, t3))));
          if (s > 1) est += max(min(e >> 2, dP), -dP);
          T += (s == 1 || e > dM ? e : 0) + est;
        }
        vm_stage(s);
        BAR_SYNC(B_W, 384);
        SCHED_FENCE(70);
        const uint32_t tW = gtime();
        if (s == 0) T = tW + 800;
        const uint32_t te = tW + min(max((int)(T - tW), dD), 2000);
        while ((int)(gtime() - te) < 0) {}
        TS(7);
        int it = 0;
        while (true) {
          ar_fetch(sb + MEM, &mp.ari, s & 7, a, sb + BARS + 112);
          mbar_wait(sb + BARS + 112, par);
          par ^= 1;
          const uint32_t n0 = lds1(pc), n1 = lds1(pc + 5120), n2 = lds1(pd);
          if (!__any_sync(~0u, (tagbad(n0, n1, 0x42004200) | (n2 ^ 0x42004200)) != 0)) break;
          RP(0);
          if (++it > SPIN_LIMIT) __trap();
        }
        BAR_ARRIVE(B_R, N_R);
        TS(11);
      }
    } else {
#define V_LOAD(n) do { if (lane == 0) mbar_expect(sb + BARS + 8, 8192); __syncwarp(); \
        if (lane < 16) bulk_ld(sb + ((lane & 2) ? VX1 : VX0) + (lane & 1) * 2048 + (lane >> 2) * 512, \
                               xc + h * 262144 + V_RING(n) + (lane >> 2) * XC + X_VX(lane & 3), 512, sb + BARS + 8); __syncwarp(); } while (0)
      uint32_t src = L16 + PK + (iw & 1) * 2048;
#define qd (L16 + (lane >> 4) * 256 + QT + (iw & 1) * 1024)
#define vd (LO(xc) + h * 262144 + j * XC + (iw & 1) * 2048 + l16)
#define FINISH [&](int n, int m) { \
_Pragma("unroll") \
        for (int i = 1; i >= 0; i--) { \
          const uint32_t p = src + m * 4096 + i * 512; \
          uint4 u = lds4(p); \
          const uint4 w = lds4(p + 1024), y = lds4(p + 12288), z = lds4(p + 13312); \
          u = make_uint4(sum4bf(u.x, w.x, y.x, z.x), sum4bf(u.y, w.y, y.y, z.y), sum4bf(u.z, w.z, y.z, z.z), sum4bf(u.w, w.w, y.w, z.w)); \
          if (m == 2) stg_b128(mkp(vd ^ V_RING(n), HI(xc)) + i * 512, (u.x & ~1u) | V_TAG(n), u.y, u.z, u.w); \
          else stsm4(qd + (n & 1) * 4096 + m * 2048 + i * 256, u.x, u.z, u.y, u.w); \
          SCHED_FENCE(71 + m * 2 + i); \
        } \
      }
#pragma unroll 1
      for (int n = 0; n < 64; n++) {
        src = PIN(src);
        b = __shfl_sync(~0u, lds1(sb + PACE + 24), 0);
        const uint32_t L16 = src - PK - (iw & 1) * 2048;
        auto finish = FINISH;
        if (n < 2) { if (n) BAR_SYNC(B_X, 320); else BAR_SYNC(B_C, 320); }
        mbar_wait(sb + BARS + 16, n & 1);
        finish(n, 0);
        __syncwarp();
        if (lane == 0) mbar_arrive_cl(mapa(sb, a ^ 1) + BARS + 24);
        if (n > 1) BAR_SYNC(B_K, 320);
        mbar_wait(sb + BARS + (KVO ? 32 : 40), n & 1);
        finish(n, 2 - !!KVO);
        if (n > 1) BAR_SYNC(B_X, 320);
        mbar_wait(sb + BARS + (KVO ? 40 : 32), n & 1);
        finish(n, 1 + !!KVO);
        BAR_SYNC(B_T, 64);
        if (lane == 0) {
          if (iw == 2 && n < 63) { mbar_expect(sb + BARS + 16, 4096); mbar_expect(sb + BARS + 32, 4096); mbar_expect(sb + BARS + 40, 4096); }
          mbar_arrive_cl(mapa(sb, a ^ 1) + BARS + 80);
        }
        __syncwarp();
        if (n) {
          vm_stage(n - 1);
          BAR_SYNC(B_W, 384);
        } else {
          BAR_SYNC(B_C, 320);
        }
        if (iw == 2) V_LOAD(n);
      }
#undef qd
#undef vd
    }
    { ROLE_REFRESH }
    vm_stage(63);
  } else {
    asm volatile("setmaxnreg.dec.sync.aligned.u32 %0;" ::"n"(RA_));
    if (blockIdx.x >= 128) { if (threadIdx.x == 256) rec_prefetch((const char*)wmod, w1, (const char*)x, wo); return; }
    ROLE_VARS
    uint32_t L16 = __shfl_sync(~0u, sb + (tid & 31) * 16, tid & 31);
    if (wid == 9) {
      for (int i = b * 80 + (tid & 31); i < b * 80 + 80; i += 32) ((uint4*)(xc + AR_OFF))[AR_ROW(i >> 6) * 64 + (i & 63)] = make_uint4(0, 0, 0, 0);
      if (b == 0) g_fin = 0;
      FENCE_ASYNC();
      __syncwarp();
      if (tid == 288) red_rlx(&g_hcnt);
    }
    if (tid == 256) {
      const int col = h * 128 + bb * 64;
#pragma unroll 1
      for (int c = 0; c < 12 + WIN; c++) {
        const uint32_t mb = sb + PACE + (c % WIN) * 8;
        if (c >= WIN) mbar_wait(mb, (c / WIN - 1) & 1);
        PT(16 + c);
        if (c == 3 + WIN) asm volatile("mbarrier.arrive.shared.b64 _,[%0];" ::"r"(sb + BARS + 88) : "memory");
        if (c >= 12) continue;
        mbar_expect(mb, 16384);
        if (c < 8) tma2d(sb + (c >> 2) * XB + (c & 3) * 16384, (c & 4) ? &mp.wk : &mp.wq, col, a * 512 + (c & 3) * 128, mb);
        else
#pragma unroll 1
          for (int i = (c & 1) * 8; i < (c & 1) * 8 + 8; i++) {
            const int w = (c - 8) >> 1;
            tma2d(i < NVR ? sb + MEM + (w * NVR + i) * 2048 : sb + WVS + (w * NVS + i - NVR) * 2048, &mp.wv, col, a * 512 + w * 256 + i * 16, mb);
          }
      }
      asm volatile("mbarrier.arrive.shared.b64 _,[%0];" ::"r"(wbar) : "memory");
      for (int c = 0; c < 4; c++) tma2d_pf(&mp.wo, j * 256 + c * 64, h * 128);
      for (int i = 0; i < 3; i++) asm volatile("mbarrier.inval.shared.b64 [%0];" ::"r"(sb + PACE + i * 8) : "memory");
    }
    __syncwarp();
    asm volatile("barrier.cluster.wait.aligned;" ::: "memory");
    CLUSTER_SYNC();
#define pr (L16 + SC)
    {
      const int lim = j * 8 + iw * 2 - (lane & 7) - (lane & 8) * 2;
      const bool mk = L16 & 256;
      const int rw = lane >> 2;
      sts4(L16 + TA + iw * 512,
           iw != 2 ? L16 + KT + (iw & 1) * 256 + (lane >> 4) * 256 : sb + RK + (L16 & 0x80) * 2 + ((L16 >> 1) & 0x80) + (L16 & 0x70),
           L16 + QT + (lane >> 3) * 384, sb + SC + min(lane >> 3, 2) * 256 + (L16 & 0x70) + iw * 4, L16 + (lane >> 4) * 256 + QT + (iw >> 1) * 1024 + (iw & 1) * 256);
      sts4(L16 + TA + 2048 + iw * 512, mk ? 0u : (lim < 0 ? 0xfc00u : 0u) | (lim < -1 ? 0xfc000000u : 0u),
           mk ? 0xfc00fc00u : (lim < 8 ? 0xfc00u : 0u) | (lim < 7 ? 0xfc000000u : 0u),
           ((h * 2 + (iw >> 1)) * 1024 + (j * 8 + rw) * 8 + (((iw & 1) * 4 + (lane & 3)) ^ rw)) * 16, sb + OT + iw * 512 + (L16 & 0x70) * 4 + ((L16 >> 3) & 0x30));
    }
    {
      const uint32_t xh = LO(xc) + h * 262144, xs = xh + X_SC + iw * 1024 + min(lane, 16 + (lane & 7)) * 8;
      sts4(L16 + TA + 4096 + iw * 512, xh + X_SC + j * 256 + iw * 64 + lpub, xs, dS, iw != 2 ? 0 : U_(SCS));
      sts1(L16 + TA + 12 + iw * 512, xs + X_TOK + j * 4096);
    }
    uint32_t tA = L16 + TA + iw * 512;
#define tw (tA - L16 != TA + 1024)
#define XP_(lo) mkp(lo, HI(xc))
    auto publish = [&](char* d, const uint2& w) { stg_b64(d, w.x, w.y); };
    BAR_SYNC(B_P, N_P);
    for (int s = 0; s < 64; s++) {
      asm volatile("" : "+r"(L16), "+r"(tA));
      const uint32_t tag = ((s >> 1) + 1) & 1, ring = (s & 1) * X_RING;
      const uint4 t0 = lds4(tA);
      const uint4 tx = lds4(tA + 4096);
      const uint32_t xo = tx.x ^ ring, xs = tx.y ^ ring;
      const float gm = F_(tx.w);
      const uint32_t qA = t0.y + (ring >> 5);
      uint32_t c0;
      uint2 ts[4];
      uint4 v[4];
      uint32_t af[2][4], qt[4][4];
      {
        const uint32_t aA = t0.x + (tw ? ring >> 5 : 0);
        uint32_t ql[2][4], qr[2][4];
        uint2 pw_;
        float c[4] = {0, 0, 0, 0}, d[4] = {0, 0, 0, 0};
        if (s == PDS) asm volatile("griddepcontrol.launch_dependents;");
#pragma unroll
        for (int i = 0; i < 4; i++) ldsm4t(qt[i], qA + i * 128);
        mbar_wait(sb + BARS + 8, s & 1);
        TS(4);
        BAR_SYNC(B_E, 256);
#define PACK(c) make_uint2(pkh(fmaf(c[2], gm, c[0] * SCS), fmaf(c[3], gm, c[1] * SCS), tag), pkh(c[2] * SCS, c[3] * SCS, tag))
#define SMMA(x, t, q, i) mma16(x, af[t][0], af[t][1], af[t][2], af[t][3], q[t][i], q[t][i + 1])
        ldsm4t(ql[0], L16 + RQ); ldsm4t(ql[1], L16 + RQ + 1024); ldsm4t(af[0], aA); ldsm4t(af[1], aA + 1024);
        CONSUME(xo);
#define QSUM(t, i) addbf(addbf(ql[t][i], ql[t][i + 2]), addbf(qr[t][i], qr[t][i + 2]))
#define STAIL mma16(c, af[0][0], af[0][1], af[0][2], af[0][3], QSUM(0, 0), QSUM(0, 1)); mma16(d, af[1][0], af[1][1], af[1][2], af[1][3], QSUM(1, 0), QSUM(1, 1));
        if (tw) {
          mbar_wait(sb + BARS, s & 1);
          TS(8);
          ldsm4t(qr[0], L16 + RQ + 512); ldsm4t(qr[1], L16 + RQ + 1536);
          STAIL
          pw_ = make_uint2(pkh(c[0] + d[0], c[1] + d[1], tag), pkh(c[2] + d[2], c[3] + d[3], tag));
        } else {
          uint32_t ar[2][4];
          mbar_wait(sb + BARS, s & 1);
          ldsm4t(qr[0], L16 + RQ + 512); ldsm4t(ar[0], aA + 512); ldsm4t(qr[1], L16 + RQ + 1536); ldsm4t(ar[1], aA + 1536);
#pragma unroll
          for (int i = 0; i < 8; i++) af[i >> 2][i & 3] = addbf(af[i >> 2][i & 3], ar[i >> 2][i & 3]);
          STAIL
          pw_.x = pw_.y = pkh((c[0] + c[2]) + (d[0] + d[2]), (c[1] + c[3]) + (d[1] + d[3]), tag);
        }
        publish(XP_(xo), pw_);
        c0 = clk() + tx.z;
        TS(1);
      }
      uint2 r[4];
      bool vbad;
      uint32_t xm;
      uint4 vn[2];
#define TOKS(i) { float e0[4] = {0, 0, 0, 0}, e1[4] = {0, 0, 0, 0}; \
        mma16(e0, af[0][0], af[0][1], af[0][2], af[0][3], qt[i][0], qt[i][1]); mma16(e1, af[0][0], af[0][1], af[0][2], af[0][3], qt[i + 1][0], qt[i + 1][1]); \
        mma16(e0, af[1][0], af[1][1], af[1][2], af[1][3], qt[i][2], qt[i][3]); mma16(e1, af[1][0], af[1][1], af[1][2], af[1][3], qt[i + 1][2], qt[i + 1][3]); \
        ts[i] = PACK(e0); ts[i + 1] = PACK(e1); }
      {
        float e[4][4];
#pragma unroll
        for (int i = 0; i < 4; i++) {
          e[i][0] = e[i][1] = e[i][2] = e[i][3] = 0.f;
          mma16(e[i], af[0][0], af[0][1], af[0][2], af[0][3], qt[i][0], qt[i][1]);
        }
#pragma unroll
        for (int i = 0; i < 4; i++) mma16(e[i], af[1][0], af[1][1], af[1][2], af[1][3], qt[i][2], qt[i][3]);
        SCHED_FENCE(55);
        if (s < 63) BAR_ARRIVE(B_S, 416);
        SCHED_FENCE(58);
        v[0] = lds4(tA + (VX0 - TA)); v[1] = lds4(tA + (VX0 - TA) + 2048); v[2] = lds4(tA + (VX1 - TA)); v[3] = lds4(tA + (VX1 - TA) + 2048);
#pragma unroll
        for (int i = 0; i < 4; i++) ts[i] = PACK(e[i]);
        vbad = anybad(v[0].x, v[1].x, v[2].x, v[3].x, V_TAG(s));
        if (AV) { xm = (xs & ~0x1ffffu) + X_VM(0) + ((tA - L16 - TA) << 5) + (l16 >> 1); CONSUME(xm); }
        while ((int)(clk() - c0) < 0) {}
        TS(5);
#pragma unroll
        for (int u = 0; u < 4; u++) r[u] = ldg_b64(XP_(xs) + u * 256);
        if (!AV) BAR_ARRIVE(B_S2, 256);
      }
      SCHED_FENCE(56);
      uint32_t kk;
      float4 e = softmax2<false>(r, 0, 0, kk);
      if (AV) {
        const char* pm_ = XP_(xm + (kk & dZ));
#pragma unroll
        for (int u = 0; u < 2; u++) { const uint2 m0 = ldg_b64(pm_ + u * 2048), m1 = ldg_b64(pm_ + u * 2048 + 256); vn[u] = make_uint4(m0.x, m0.y, m1.x, m1.y); }
      }
      if (__builtin_expect(anybad(r[0].x, r[0].y, r[1].x, r[1].y, r[2].x, r[2].y, r[3].x, r[3].y, tag ^ (kk & dZ)), 0)) {
        int it = 0;
        if (s > 8) sts1(tA + 4096 + 8, min(lds1(tA + 4096 + 8) + dX, 500));
        do {
          RP(1);
          if (++it > SPIN_LIMIT) __trap();
#pragma unroll
          for (int u = 0; u < 4; u++) r[u] = ldg_b64(XP_(xs) + u * 256);
        } while (BADS(r));
        e = softmax2<false>(r, 0, 0, kk);
      }
      sts1(t0.z, pk(e.x, e.y)); sts1(t0.z + 128, pk(e.z, e.w));
#pragma unroll
      for (int i = 0; i < 4; i++) publish(XP_(xo) + X_TOK + i * 4096, ts[i]);
      TS(6);
      if (s < 63) BAR_SYNC(B_V, N_V); else BAR_SYNC(B_V, N_V - 256);
      uint32_t O[4];
      {
        uint32_t p[4], pm;
        ldsm4t(p, pr);
        asm volatile("ldmatrix.sync.aligned.m8n8.x1.trans.shared.b16 {%0},[%1];" : "=r"(pm) : "r"(pr + 512) : "memory");
        if (!AV) { vn[0] = lds4(tA + (VN - TA)); vn[1] = lds4(tA + (VN - TA) + 2048); }
        pv_mem(p, pm, v, vn, O);
        if (__builtin_expect(vbad || ((HV || AV) && anybad(vn[0].x, vn[0].z, vn[1].x, vn[1].z, tag)), 0)) {
          int it = 0;
          const uint32_t xv = LO(xc) + (lds1(sb + PACE + 24) >> 2) * 262144 + ((tA - L16 - TA) >> 9) * XC;
          do {
            RP(2);
            if (++it > SPIN_LIMIT) __trap();
#pragma unroll
            for (int u = 0; u < 4; u++) v[u] = ldg_b128(XP_((xv + l16) ^ V_RING(s)) + X_VX(u));
#pragma unroll
            for (int u = 0; u < 2; u++) {
              const uint2 m0 = ldg_b64(XP_((xv + (l16 >> 1)) ^ ring) + X_VM(0) + u * 2048), m1 = ldg_b64(XP_((xv + (l16 >> 1)) ^ ring) + X_VM(0) + u * 2048 + 256);
              vn[u] = make_uint4(m0.x, m0.y, m1.x, m1.y);
            }
          } while (anybad(v[0].x, v[1].x, v[2].x, v[3].x, V_TAG(s)) || anybad(vn[0].x, vn[0].z, vn[1].x, vn[1].z, tag));
          pv_mem(p, pm, v, vn, O);
        }
      }
      stsm4(tA + (OB - TA), O[0], O[1], O[2], O[3]);
      if (s < 63) BAR_ARRIVE(B_O, N_O);
      TS(2);
      c0 = clk() + dG;
      SCHED_FENCE(60);
      if (tA == sb + TA) mbar_expect(sb + BARS, 2048);
      const uint32_t vs[4] = {addbf(vn[0].x, vn[0].z), addbf(vn[0].y, vn[0].w), addbf(vn[1].x, vn[1].z), addbf(vn[1].y, vn[1].w)};
      {
        const char* xt = XP_(lds1(tA + 12) ^ ring);
        const uint2 t1 = lds2u(tA + 2048);
        const uint32_t pw = lds1(tA + 8);
        uint2 rt[4];
        CONSUME(LO(xt) ^ t1.x ^ pw);
        while ((int)(clk() - c0) < 0) {}
        int it = 0;
        do {
          if (++it > SPIN_LIMIT) __trap();
#pragma unroll
          for (int u = 0; u < 4; u++) rt[u] = ldg_b64(xt + u * 256);
        } while (BADS(rt));
        uint32_t kt;
        const float4 et = softmax2<true>(rt, t1.x, t1.y, kt);
        sts1(pw + 1024, pk(et.x, et.y)); sts1(pw + 1024 + 128, pk(et.z, et.w));
      }
      s = PIN(s);
      BAR_SYNC(B_SC, 128);
      {
        uint32_t Ot[4], p[4], pm;
        const uint2 t2 = lds2u(tA + 2048 + 8);
        ldsm4t(p, pr + 1024);
        asm volatile("ldmatrix.sync.aligned.m8n8.x1.trans.shared.b16 {%0},[%1];" : "=r"(pm) : "r"(pr + 1024 + 512) : "memory");
        char* od = (char*)g_O + ((s >> 2) * 1048576 + (s & 3) * 4096) + t2.x;
        CONSUME(LO(od) ^ HI(od) ^ pm ^ p[3]);
        TS(9);
        if (s < 62) BAR_SYNC(B_P, N_P);
        pv_tok(p, pm, v, vs, Ot);
        asm volatile("stmatrix.sync.aligned.m8n8.x4.trans.shared.b16 [%0],{%1,%2,%3,%4};" ::"r"(t2.y), "r"(Ot[0]), "r"(Ot[1]), "r"(Ot[2]), "r"(Ot[3]) : "memory");
        __syncwarp();
        *(uint4*)od = lds4(tA + (OT - TA));
      }
    }
    FENCE_ASYNC();
    BAR_SYNC(B_SC, 128);
    if (tA == sb + TA) red_rlx(&g_fin);
  }
  __syncwarp();
  CLUSTER_SYNC();
  PH(5);
}
#undef wg
#undef iw
#undef h
#undef j
#undef a
#undef bb
#undef oi
#undef owner
#undef ownv
#undef vfin
#undef pr
#undef PIN
#undef XP_
#undef tw
#undef is7
#undef REFRESH
#undef lane
#undef l16
#undef lrow
#undef lar
#undef lpub

namespace ffn {
constexpr uint32_t BR = 98304;
constexpr uint32_t STG = 196608;
constexpr uint32_t PRM = 229376;
constexpr uint32_t BARS = PRM + 2816;
constexpr uint32_t SMEM = BARS + 18 * 8;
}
#define Y_TILE(rb, kt) (((ALIAS & 1) ? g_h : g_h2) + ((rb) * 16 + (kt)) * 1024)
#define U_TILE(rb, kt) ((ALIAS & 2) ? g_O + ((rb) * 64 + (kt)) * 1024 : g_U + ((rb) * 56 + (kt)) * 1024)
struct FfnMaps { CUtensorMap wo, w1a, w1b, w2, x, out; };

template <int N>
__device__ __forceinline__ void wg_ss(float* d, uint64_t a, uint64_t b, int sd) {
  if (N == 128) wgmma_ss_n128(d, a, b, sd);
  if (N == 192) wgmma_ss_n192(d, a, b, sd);
}
template <int N>
__device__ __forceinline__ void acc_fence(float* d) {
#pragma unroll
  for (int i = 0; i < N; i++) asm volatile("" : "+f"(d[i])::"memory");
}
#define UNPK8(d, v) do { (d)[0] = blo(v.x); (d)[1] = bhi(v.x); (d)[2] = blo(v.y); (d)[3] = bhi(v.y); (d)[4] = blo(v.z); (d)[5] = bhi(v.z); (d)[6] = blo(v.w); (d)[7] = bhi(v.w); } while (0)
struct FfnPipe {
  uint32_t full, emp, ph, aoff;
  int st, sB, prev;
  bool leader;
  template <int N>
  __device__ __forceinline__ void issue(float* acc, bool first, uint32_t a = 0) {
    mbar_wait(full + st * 8, ph);
    const uint64_t da = mkdesc((a ? a : 1024 + st * 16384) + aoff, 16, 1024), db = mkdesc(1024 + ffn::BR + sB * (N * 128), 8192, 1024);
    WG_FENCE();
#pragma unroll
    for (int j = 0; j < ((FDB & 1) ? 1 : 4); j++) wg_ss<N>(acc, da + j * 2, db + j * 128, j || !first);
    WG_COMMIT();
    if (++sB == 768 / N) sB = 0;
  }
  __device__ __forceinline__ void release() { if (leader) mbar_arrive(emp + prev * 8); }
  __device__ __forceinline__ void next() { prev = st; if (++st == 6) { st = 0; ph ^= 1; } }
  __device__ __forceinline__ void retire() { WG_WAIT(1); release(); next(); }
};
__device__ __forceinline__ float gelu_h(float hx) {
  float u = hx * fmaf(hx * hx, 8.f * 0.0356774081f, 2.f * 0.7978845608f), t;
  if (FDB & 4) return hx;
  if (FDB & 2) t = u; else
  asm("tanh.approx.f32 %0,%1;" : "=f"(t) : "f"(u));
  return fmaf(hx, t, hx);
}
struct FfnEpi {
  uint32_t st2, cc, flip, staged, l0;
  uint2 c;
  float n0, n1, s0, s1;
  __device__ __forceinline__ void flush(uint32_t r) {
    __syncwarp();
    asm volatile("{.reg .pred p; setp.ne.u32 p,%1,0; @p mbarrier.arrive.shared.b64 _,[%0];}" ::"r"(staged + (flip >> 11)), "r"(l0 & r) : "memory");
    flip ^= r << 14;
  }
  __device__ __forceinline__ void half(const float* d, int J, int r) {
#define PRE(i, n, c1, c2) gelu_h(fmaf(r ? d[4 + i] : d[i], i < 2 ? s0 : s1, fmaf(n, c1, c2)))
    asm volatile("stmatrix.sync.aligned.m8n8.x2.shared.b16 [%0],{%1,%2};" ::"r"((st2 ^ ((J & 3) * 32 + r * 16)) + flip),
                 "r"(pk(PRE(0, n0, blo(c.x), blo(c.y)), PRE(1, n0, bhi(c.x), bhi(c.y)))), "r"(pk(PRE(2, n1, blo(c.x), blo(c.y)), PRE(3, n1, bhi(c.x), bhi(c.y)))) : "memory");
#undef PRE
    if ((J & 3) == 3) flush(r);
    cc += r ? 56 : 8;
    c = lds2u(cc);
  }
};

__global__ void __launch_bounds__(384, 1)
k_ffn(const __grid_constant__ FfnMaps mp, const bf16* __restrict__ b2) {
  using namespace ffn;
  extern __shared__ __align__(1024) char smem[];
  const uint32_t sb = (uint32_t)__cvta_generic_to_shared(smem);
  if (sb != 1024) __trap();
  const int tid = threadIdx.x, lane = tid & 31, wg = __shfl_sync(~0u, tid >> 7, 0);
  const uint32_t full = sb + BARS, emp = full + 48, xbar = full + 96, staged = full + 104, tile = full + 136;
  uint32_t fin = 0;
  if (tid >= 288 && tid < 320) fin = ld_acq(&g_fin);
  if (tid < 32) {
    unsigned sm, v = 0;
    asm("mov.u32 %0,%%smid;" : "=r"(sm));
    if (tid == 0) {
      v = atomicExch(&g_slot[sm & 255], 0);
      for (int i = 0; i < 6; i++) { mbar_init(full + i * 8, 1); mbar_init(emp + i * 8, 2); }
      mbar_init(xbar, 2);
      for (int i = 0; i < 2; i++) { mbar_init(staged + i * 8, 8); mbar_init(staged + 16 + i * 8, 1); }
      FENCE_ASYNC_SMEM();
    }
    v = __shfl_sync(~0u, v, 0);
    if (!v) {
      wait_cnt(&g_fin, 128);
      for (int it = 0; !v; it++) {
        const uint4 a = ldg_rlx4(g_slot + tid * 8), b = ldg_rlx4(g_slot + tid * 8 + 4);
        const uint32_t open = __ballot_sync(~0u, a.x | a.y | a.z | a.w | b.x | b.y | b.z | b.w);
        if (!open) break;
        if (it < 16) { __nanosleep(500); continue; }
        if (tid == __ffs(open) - 1) v = atomicExch(&g_slot[tid * 8 + (a.x ? 0 : a.y ? 1 : a.z ? 2 : a.w ? 3 : b.x ? 4 : b.y ? 5 : b.z ? 6 : 7)], 0);
        v = __shfl_sync(~0u, v, __ffs(open) - 1);
      }
    }
    if (tid == 0) sts1(tile, v);
  }
  if (tid == 256) asm volatile("prefetch.tensormap [%0];" ::"l"(&mp.wo) : "memory");
  __syncthreads();
  const int bid = __shfl_sync(~0u, lds1(tile), 0) - 1;
  if (bid < 0) return;
  PH(6);
  FT(1);
  const int rb = bid >> 3, nb = bid & 7;
  unsigned* cnt = g_cnt + rb * 128;
  if (wg == 2) {
    asm volatile("setmaxnreg.dec.sync.aligned.u32 " FRP ";");
    const int pw = __shfl_sync(~0u, (tid >> 5) & 3, 0);
    uint32_t ws = emp, wp = 1, fs = full;
    auto wait_free = [&]() { mbar_wait_q(ws, wp); ws += 8; if (ws == emp + 48) { ws = emp; wp ^= 1; } };
    auto step = [&]() { fs += 8; if (fs == full + 48) fs = full; };
#define K3(c) ((0x65230 >> (c) * 4) & 7)
#define KC(k) ((k) < 2 ? nb * 2 + (k) : (k) < 9 ? ((k) - 2 + ((k) - 2 >= nb)) * 2 : ((k) - 9 + ((k) - 9 >= nb)) * 2 + 1)
    if (pw == 0) {
      uint32_t d = sb + BR + 32768;
      auto put = [&](const CUtensorMap* m, int k, int c) {
        e_expect_tma3d(d, m, k * 64, c, fs, 32768);
        step();
        d += 16384;
        if (d == sb + STG) d = sb + BR;
      };
      int n = 0;
      auto stage_free = [&]() { if (!(n & 7) && n < 56) mbar_wait_q(staged + 16 + (n & 8), (n >> 4) & 1); n++; };
      FTP(3);
#pragma unroll 1
      for (int k = 0; k < 66; k++) { wait_free(); if (k < 64) put(&mp.wo, k, nb * 2); }
#pragma unroll 1
      for (int k = 0; k < 16; k++) {
        const int kt = KC(k);
        wait_free();
        e_expect_tma3d(sb + BR + (k & 3) * 24576, &mp.w1b, kt * 64, nb * 7, fs, k < 2 ? 24576 : 40960);
        step();
      }
#pragma unroll 1
      for (int k = 0; k < 32; k++) { stage_free(); if (k != 5 && k != 6) wait_free(); put(&mp.w1a, k & 15, nb * 7 + 3 + (k >> 4) * 2); }
#pragma unroll 1
      for (int c = 0; c < 5; c++)
#pragma unroll 1
        for (int k = K3(c), i = 0; k < 56; k += c < 2 && (i ^= 1) ? 1 : c < 2 ? 6 : 7) { stage_free(); wait_free(); put(&mp.w2, k, nb * 2); }
    } else if (pw == 1) {
      FTP(5);
      if (fin < 128) wait_cnt(&g_fin, 128);
      FTP(6);
      uint32_t d = sb;
      auto put = [&](const uint4* A, bool ld) {
        wait_free();
        if (ld) e_bulk_ld(d, A, 16384, fs);
        step();
        d += 16384;
        if (d == sb + BR) d = sb;
      };
      const uint4* A = g_O + rb * 65536;
#pragma unroll 1
      for (int k = 0; k < 66; k++) put(A + k * 1024, k < 64);
      A = Y_TILE(rb, 0);
      uint32_t ready = 0;
#pragma unroll 1
      for (int k = 2; k < 48; k++) {
        const int kt = k < 16 ? KC(k) : k & 15;
        for (int it = 0; !(ready >> ((kt >> 1) + (kt & 1) * 8) & 1); it++) {
          ready = __ballot_sync(~0u, ldg_rlx1(cnt + (lane & 7)) & ((lane & 8) ? 1 : 0x10000));
          if (it > SPIN_LIMIT) __trap();
        }
        if (k == 2) FTP(75);
        put(A + kt * 1024, true);
      }
      A = U_TILE(rb, 0);
#pragma unroll 1
      for (int c = 0; c < 5; c++) {
        for (int it = 0; ldg_rlx1(cnt + 32 + c) < 8; it++) if (it > SPIN_LIMIT) __trap();
#pragma unroll 1
        for (int k = K3(c), i = 0; k < 56; k += c < 2 && (i ^= 1) ? 1 : c < 2 ? 6 : 7) put(A + k * 1024, true);
      }
    } else if (pw == 2) {
      for (int i = 0; i < XDL; i++) {
        mbar_wait_q(emp, i & 1);
        if (XPF && i == 1 && lane < 2) tma2d_pf(&mp.x, nb * 128 + lane * 64, rb * 128);
      }
      if (lane == 0) {
        mbar_expect(xbar, 32768);
        tma2d(sb + STG, &mp.x, nb * 128, rb * 128, xbar);
        tma2d(sb + STG + 16384, &mp.x, nb * 128 + 64, rb * 128, xbar);
      }
      asm volatile("griddepcontrol.wait;" ::: "memory");
      if (lane < 16) g_modp[bid * 16 + lane] = make_uint4(0, 0, 0, 0);
      if (lane >= 16 && bid == 0) { g_hcnt = 0; g_mcnt = 0; g_hf[lane & 3] = 0; }
      if (lane == 0) {
#pragma unroll 1
        for (int g = 1; g < 9; g++) {
          if (g == 1) mbar_wait(staged + 8, 0); else { mbar_wait_q(staged + (g & 1) * 8, (g >> 1) & 1); FENCE_ASYNC_SMEM(); }
          bulk_st(g == 1 ? Y_TILE(rb, nb * 2 + 1) : U_TILE(rb, nb * 7 + ((0x652431000ull >> g * 4) & 7)), sb + STG + (g & 1) * 16384, 16384);
          BULK_COMMIT();
          if (g != 2 && g != 4) { BULK_WAIT(0); red_rlx(g == 1 ? cnt + nb : cnt + 32 + (g < 6 ? g >> 2 : g - 4)); }
          BULK_WAIT_READ(0);
          mbar_arrive(staged + 16 + (g & 1) * 8);
        }
      }
    } else {
      const uint32_t prm = sb + PRM, pp = prm + (lane >> 3) * 64 + (lane & 1) * 32 + (lane & 6) * 2;
      const uint2 v2 = ((const uint2*)(b2 + nb * 128))[lane];
      sts1(pp + 768, v2.x); sts1(pp + 784, v2.y);
      asm volatile("griddepcontrol.wait;" ::: "memory");
      const float4* md = (const float4*)(g_mod + nb * 128) + lane;
      { const float4 ga = md[512]; sts1(pp, pk(ga.x, ga.y)); sts1(pp + 16, pk(ga.z, ga.w)); }
      { const float4 cb = md[1024]; sts1(pp + 256, pk(1.f + cb.x, 1.f + cb.y)); sts1(pp + 272, pk(1.f + cb.z, 1.f + cb.w)); }
      { const float4 gb = md[1280]; sts1(pp + 512, pk(gb.x, gb.y)); sts1(pp + 528, pk(gb.z, gb.w)); }
#pragma unroll 1
      for (int i = lane; i < 112; i += 32) { const uint4 c = g_cc[nb * 112 + i]; sts4(prm + 1024 + i * 16, c.x, c.y, c.z, c.w); }
      __syncwarp();
      if (lane == 0) {
        mbar_arrive(xbar);
        mbar_wait(staged, 0);
        bulk_st(Y_TILE(rb, nb * 2), sb + STG, 16384);
        BULK_COMMIT(); BULK_WAIT(0);
        asm volatile("red.relaxed.gpu.global.add.u32 [%0],0x10000;" ::"l"(cnt + nb) : "memory");
        mbar_arrive(staged + 16);
      }
      __syncwarp();
      mbar_wait_q(staged + 24, 0);
      mbar_wait_q(emp + 40, 0);
#pragma unroll 1
      for (int i = 0; i < 4; i++) {
        const uint4* sp = g_stat + (rb * 128 + i * 32 + lane) * 4;
        uint4 v[4];
        for (int it = 0;; it++) {
          uint32_t m = 0;
#pragma unroll
          for (int u = 0; u < 4; u++) { v[u] = ldg_rlx4(sp + u); m = max(max(m, max(v[u].x, v[u].y)), max(v[u].z, v[u].w)); }
          if (!__any_sync(~0u, m == ~0u)) break;
          if (it > SPIN_LIMIT) __trap();
        }
        float m = 0, q = 0;
#pragma unroll
        for (int u = 0; u < 4; u++) m += F_(v[u].x) + F_(v[u].z);
        m *= 0.125f;
#pragma unroll
        for (int u = 0; u < 4; u++) { const float a = F_(v[u].x) - m, b = F_(v[u].z) - m; q += F_(v[u].y) + F_(v[u].w) + 128.f * (a * a + b * b); }
        const float r = 0.5f * rsqrtf(q * (1.f / 1024) + 1e-5f);
        sts2(sb + STG + 16384 + (i * 32 + lane) * 8, U_(r), U_(-m * r));
      }
      __syncwarp();
      if (lane < 2) mbar_arrive(xbar);
    }
  } else {
    asm volatile("setmaxnreg.inc.sync.aligned.u32 " FRC ";");
    const int w = (tid >> 5) & 3, q = lane & 3;
    const uint32_t prm = sb + PRM + q * 16;
    const int row0 = wg * 64 + w * 16;
    FfnPipe p;
    p.full = full; p.emp = emp; p.ph = 0; p.aoff = wg * 8192; p.st = 0; p.sB = 2; p.prev = 0; p.leader = (tid & 127) == 0;
    FfnEpi e;
    const uint32_t stg = sb + STG + row0 * 128;
    e.st2 = stg + (lane & 15) * 128 + ((lane & 7) << 4);
    e.cc = sb + PRM + 1024 + q * 16; e.flip = 0; e.staged = staged; e.l0 = lane == 0;
    const uint32_t stw = e.st2 ^ (lane & 16);
    uint32_t x1[32];
    uint4* sp = g_stat + (rb * 128 + row0 + (lane >> 2)) * 4;
    float old[96], r0_, r1_;
    {
      float acc[64];
      p.issue<128>(acc, true); FT(8); p.next();
#pragma unroll 1
      for (int k = 1; k < 64; k++) { p.issue<128>(acc, false); FT(8 + k); p.retire(); }
      float xf[64], gf[32];
      uint32_t cb[16];
      mbar_wait(xbar, 0);
#pragma unroll
      for (int j = 0; j < 8; j++) {
        uint32_t xv[4];
        ldsm4(xv, (stw ^ ((j & 3) * 32)) + (j >> 2) * 16384);
#pragma unroll
        for (int i = 0; i < 4; i++) { xf[j * 8 + i * 2] = blo(xv[i]); xf[j * 8 + i * 2 + 1] = bhi(xv[i]); }
      }
#pragma unroll
      for (int i = 0; i < 4; i++) {
        const uint4 g = lds4(prm + i * 64), c = lds4(prm + 256 + i * 64);
        UNPK8(gf + i * 8, g);
        cb[i * 4] = c.x; cb[i * 4 + 1] = c.y; cb[i * 4 + 2] = c.z; cb[i * 4 + 3] = c.w;
      }
      acc_fence<64>(xf); acc_fence<32>(gf);
      WG_WAIT(0);
      p.release();
      acc_fence<64>(acc);
      PH(7); FT(72);
#pragma unroll
      for (int j = 0; j < 8; j++) {
        uint32_t* o = x1 + j * 4;
#pragma unroll
        for (int i = 0; i < 4; i++)
          o[i] = pk(fmaf(acc[j * 8 + i * 2], gf[j * 4 + (i & 2)], xf[j * 8 + i * 2]), fmaf(acc[j * 8 + i * 2 + 1], gf[j * 4 + (i & 2) + 1], xf[j * 8 + i * 2 + 1]));
        stsm4((stw ^ ((j & 3) * 32)) + (j >> 2) * 16384, mulbf(o[0], cb[j * 2]), mulbf(o[1], cb[j * 2]), mulbf(o[2], cb[j * 2 + 1]), mulbf(o[3], cb[j * 2 + 1]));
        if ((j & 3) == 3) { FENCE_ASYNC_SMEM(); e.flush(1); }
      }
      if (wg) BAR_SYNC(2, 128); else BAR_SYNC(3, 128);
    }
    PH(8); FT(73);
    float acc[64];
    {
      float* accC = old;
      p.sB = 0;
      p.issue<192>(accC, true, 1024 + STG); FT(80); p.next();
      p.issue<192>(accC, false, 1024 + STG + 16384); FT(81);
      FT(78);
      float s0 = 0, s1 = 0;
#define X1_FENCE _Pragma("unroll") for (int j = 0; j < 32; j++) asm volatile("" : "+r"(x1[j]));
      X1_FENCE
#pragma unroll
      for (int j = 0; j < 16; j++) { s0 += blo(x1[j * 2]) + bhi(x1[j * 2]); s1 += blo(x1[j * 2 + 1]) + bhi(x1[j * 2 + 1]); }
      s0 += __shfl_xor_sync(~0u, s0, 1); s1 += __shfl_xor_sync(~0u, s1, 1);
      s0 += __shfl_xor_sync(~0u, s0, 2); s1 += __shfl_xor_sync(~0u, s1, 2);
      s0 *= 1.f / 128; s1 *= 1.f / 128;
      float q0 = 0, q1 = 0;
      X1_FENCE
#pragma unroll
      for (int j = 0; j < 16; j++) {
        const float a = blo(x1[j * 2]) - s0, b = bhi(x1[j * 2]) - s0, c = blo(x1[j * 2 + 1]) - s1, d = bhi(x1[j * 2 + 1]) - s1;
        q0 += a * a + b * b; q1 += c * c + d * d;
      }
      q0 += __shfl_xor_sync(~0u, q0, 1); q1 += __shfl_xor_sync(~0u, q1, 1);
      q0 += __shfl_xor_sync(~0u, q0, 2); q1 += __shfl_xor_sync(~0u, q1, 2);
      if (q < 2) {
        uint32_t m = __float_as_uint(q ? s1 : s0), v = __float_as_uint(q ? q1 : q0);
        if (m == ~0u) m = 0x7fffffffu;
        if (v == ~0u) v = 0x7fffffffu;
        stg_rlx2((uint2*)(sp + q * 32) + nb, m, v);
      }
      X1_FENCE
      p.retire();
#pragma unroll 1
      for (int k = 2; k < 15; k++) { p.issue<192>(accC, false); FT(80 + k); p.retire(); }
      p.issue<192>(accC, false); FT(95);
      mbar_wait(xbar, 1);
      const float2 u0 = lds2f(sb + STG + 16384 + (row0 + (lane >> 2)) * 8), u1 = lds2f(sb + STG + 16384 + (row0 + (lane >> 2)) * 8 + 64);
      r0_ = u0.x; e.n0 = u0.y; r1_ = u1.x; e.n1 = u1.y;
      e.c = lds2u(e.cc);
      p.retire();
      e.s0 = r0_; e.s1 = r1_;
    }
    PH(9);
    {
      auto pair = [&](int J, bool first, int fo) {
#pragma unroll 1
        for (int r = 0; r < 2; r++) { p.issue<128>(acc, first && !r); FT(fo + r); p.retire(); acc_fence<8>(old + J * 8); e.half(old + J * 8, J, r); }
      };
#pragma unroll 1
      for (int i = 0; i < 3; i++) {
        if (i == 2) {
          e.s0 = r0_; e.s1 = r1_;
#pragma unroll
          for (int J = 8; J < 12; J++) pair(J, J == 8, 128 + (J - 8) * 2);
          e.cc += 512; e.c = lds2u(e.cc);
          e.s0 = e.s1 = 1.f;
        }
#pragma unroll
        for (int J = 0; J < 8; J++) pair(J, J == 0 && i < 2, 96 + i * 16 + (i >> 1) * 8 + J * 2);
        if (i == 2) break;
        e.cc += i ? -768 : 256; e.c = lds2u(e.cc);
        WG_WAIT(0);
        acc_fence<64>(acc);
#pragma unroll
        for (int k = 0; k < 64; k++) old[k] = acc[k] * ((k & 2) ? r1_ : r0_);
        acc_fence<64>(old);
        e.s0 = e.s1 = 1.f;
        PH(10 + i);
      }
#pragma unroll 1
      for (int k = 24; k < 56; k++) { p.issue<128>(acc, false); FT(128 + k); p.retire(); }
      float xf[64], gf[32];
#pragma unroll
      for (int i = 0; i < 4; i++) {
        const uint4 g = lds4(prm + 512 + i * 64), h = lds4(prm + 768 + i * 64);
        float hf[8];
        UNPK8(gf + i * 8, g); UNPK8(hf, h);
#pragma unroll
        for (int u = 0; u < 8; u++) {
          const int c = (u >> 2) * 4 + (u & 2);
          xf[i * 16 + u * 2] = fmaf(gf[i * 8 + c], hf[c], blo(x1[i * 8 + u])); xf[i * 16 + u * 2 + 1] = fmaf(gf[i * 8 + c + 1], hf[c + 1], bhi(x1[i * 8 + u]));
        }
      }
      acc_fence<64>(xf); acc_fence<32>(gf);
      mbar_wait(staged + 24, 1);
      mbar_wait(staged + 16, 0);
      WG_WAIT(0);
      acc_fence<64>(acc);
      PH(13); FT(184);
#pragma unroll
      for (int j = 0; j < 8; j++) {
        uint32_t o[4];
#pragma unroll
        for (int i = 0; i < 4; i++)
          o[i] = pk(fmaf(acc[j * 8 + i * 2], gf[j * 4 + (i & 2)], xf[j * 8 + i * 2]), fmaf(acc[j * 8 + i * 2 + 1], gf[j * 4 + (i & 2) + 1], xf[j * 8 + i * 2 + 1]));
        stsm4((stw ^ ((j & 3) * 32)) + (j >> 2) * 16384, o[0], o[1], o[2], o[3]);
        if ((j & 3) == 3) {
          FENCE_ASYNC_SMEM();
          __syncwarp();
          if (lane == 0) { tma2d_st(&mp.out, nb * 128 + (j >> 2) * 64, rb * 128 + row0, stg + (j >> 2) * 16384); BULK_COMMIT(); }
        }
      }
      if (lane == 0) BULK_WAIT_READ(0);
      __syncwarp();
    }
  }
  PH(14); FT(185);
}

typedef CUresult (*EncFn)(CUtensorMap*, CUtensorMapDataType, cuuint32_t, void*, const cuuint64_t*, const cuuint64_t*, const cuuint32_t*,
                          const cuuint32_t*, CUtensorMapInterleave, CUtensorMapSwizzle, CUtensorMapL2promotion, CUtensorMapFloatOOBfill);
static void map2d(EncFn enc, CUtensorMap* m, const void* p, int rows, int cols, int boxRows) {
  cuuint64_t d[2] = {(cuuint64_t)cols, (cuuint64_t)rows}, s[1] = {(cuuint64_t)cols * 2};
  cuuint32_t b[2] = {64, (cuuint32_t)boxRows}, e[2] = {1, 1};
  enc(m, CU_TENSOR_MAP_DATA_TYPE_BFLOAT16, 2, (void*)p, d, s, b, e, CU_TENSOR_MAP_INTERLEAVE_NONE, CU_TENSOR_MAP_SWIZZLE_128B,
      CU_TENSOR_MAP_L2_PROMOTION_L2_128B, CU_TENSOR_MAP_FLOAT_OOB_FILL_NONE);
}
static void map3d(EncFn enc, CUtensorMap* m, const void* p, int rows, int cols, int nch) {
  cuuint64_t d[3] = {64, (cuuint64_t)rows, (cuuint64_t)(cols / 64)}, s[2] = {(cuuint64_t)cols * 2, 128};
  cuuint32_t b[3] = {64, 64, (cuuint32_t)nch}, e[3] = {1, 1, 1};
  enc(m, CU_TENSOR_MAP_DATA_TYPE_BFLOAT16, 3, (void*)p, d, s, b, e, CU_TENSOR_MAP_INTERLEAVE_NONE, CU_TENSOR_MAP_SWIZZLE_128B,
      CU_TENSOR_MAP_L2_PROMOTION_L2_128B, CU_TENSOR_MAP_FLOAT_OOB_FILL_NONE);
}

extern "C" void kernel_launch(void* const* d_in, const int* in_sizes, int n_in, void* d_out, int out_size) {
  const bf16* x = (const bf16*)d_in[0];
  const bf16* mem0 = (const bf16*)d_in[1];
  void* fn = nullptr;
  cudaDriverEntryPointQueryResult qr;
  cudaGetDriverEntryPoint("cuTensorMapEncodeTiled", &fn, cudaEnableDefault, &qr);
  EncFn enc = (EncFn)fn;
  FfnMaps fm = {};
  map3d(enc, &fm.wo, d_in[5], 4096, 1024, 2);
  map3d(enc, &fm.w1a, d_in[8], 1024, 3584, 2);
  map3d(enc, &fm.w1b, d_in[8], 1024, 3584, 3);
  map3d(enc, &fm.w2, d_in[10], 3584, 1024, 2);
  map2d(enc, &fm.x, x, 2048, 1024, 128);
  map2d(enc, &fm.out, d_out, 2048, 1024, 16);
  RecMaps rm = {};
  map2d(enc, &rm.wq, d_in[2], 1024, 4096, 128);
  map2d(enc, &rm.wk, d_in[3], 1024, 4096, 128);
  map2d(enc, &rm.wv, d_in[4], 1024, 4096, 16);
  map2d(enc, &rm.wo, d_in[5], 4096, 1024, 128);
  char* xc = nullptr;
  cudaGetSymbolAddress((void**)&xc, g_xc);
  xc += (0 - (uintptr_t)xc) & 0x1FFFFF;
  {
    cuuint64_t d[3] = {512, ARV ? 8 : 128, ARV ? 128 : 6}, sd[2] = {1024, ARV ? 8192 : 131072};
    cuuint32_t bi[3] = {64, 8, 5}, e[3] = {1, 1, 1};
    enc(&rm.ari, CU_TENSOR_MAP_DATA_TYPE_BFLOAT16, 3, xc + AR_OFF, d, sd, bi, e, CU_TENSOR_MAP_INTERLEAVE_NONE, CU_TENSOR_MAP_SWIZZLE_NONE,
        CU_TENSOR_MAP_L2_PROMOTION_NONE, CU_TENSOR_MAP_FLOAT_OOB_FILL_NONE);
  }
  cudaFuncSetAttribute(k_ffn, cudaFuncAttributeMaxDynamicSharedMemorySize, ffn::SMEM);
  cudaFuncSetAttribute(k_rec, cudaFuncAttributeMaxDynamicSharedMemorySize, rec::SMEM);
  cudaStream_t st = cudaStreamPerThread;
  int dF = 450, dA = 2700, dS = 300, dM = 120, dG = 350, dP = 24, dX = 48, dD = 350, dZ = 0, dZ2 = 1, dV = 370, dX2 = 0;
  k_rec<<<132, 512, rec::SMEM, st>>>(rm, mem0, x, (const bf16*)d_in[12], (const bf16*)d_in[13], (const char*)d_in[8], (const bf16*)d_in[9],
                                     (const char*)d_in[5], xc, dF, dA, dS, dM, dG, dP, dX, dD, dZ, dZ2, dV, dX2);
  cudaLaunchConfig_t cfg = {};
  cfg.gridDim = dim3(132); cfg.blockDim = dim3(384); cfg.dynamicSmemBytes = ffn::SMEM; cfg.stream = st;
  cudaLaunchAttribute at[1];
  at[0].id = cudaLaunchAttributeProgrammaticStreamSerialization;
  at[0].val.programmaticStreamSerializationAllowed = 1;
  cfg.attrs = at; cfg.numAttrs = 1;
  cudaLaunchKernelEx(&cfg, k_ffn, fm, (const bf16*)d_in[11]);
}
```

```cpp
#include <cuda_runtime.h>
#include <cuda.h>
#include <cuda_bf16.h>
#include <stdint.h>

typedef __nv_bfloat16 bf16;

__device__ __align__(16) float g_mod[6144];
__device__ __align__(1024) uint4 g_modp[4 * 512];
__device__ unsigned g_hcnt;
__device__ unsigned g_hf[4];
__device__ __align__(1024) uint4 g_h[2048 * 1024 / 8];
__device__ __align__(1024) uint4 g_O[2048 * 4096 / 8];
__device__ __align__(1024) uint4 g_h2[2048 * 1024 / 8];
__device__ __align__(1024) uint4 g_U[2048 * 3584 / 8];
__device__ __align__(1024) uint4 g_stat[2048 * 4];
__device__ __align__(1024) unsigned g_cnt[16 * 4 * 32];
__device__ unsigned g_mcnt;
__device__ unsigned g_slot[256];
__device__ unsigned g_fin;
__device__ __align__(16) uint4 g_cc[224 * 4];
__device__ __align__(1024) uint4 g_xc[44 * 16384];
__device__ __align__(1024) unsigned g_tm[4 * 256];
#define FT(i)
#define FTP(i)
#define PT(i)
#define PH(i)
#define RP(i)
#define RPN(i, s)
#define TSV(i, v)
#define TS(i)

#define WIN 3
#define FRC "232"
#define FRP "40"
#define YR 1
#define XPK 0
#define NFA 1
#define PINM 1
#define FMAP (((g >> 2) * 4 + m) * 8 + (g & 3) * 2 + (blockIdx.x & 1))
#define FDB 0
#define ALIAS 3
#define EF 0
#define XPF 0
#define PFT 150000
#define PFS 104
#define PF0 13000
#define PFD 128
#define ARV 0
#define HV 0
#define XE 0
#define NF 2
#define NB0 4
#define PV0 4
#define T1L 1
#define NW0 5
#define FQM 0
#define FQ(k) do { if ((FQM >> ((k) - 48)) & 1) SCHED_FENCE(k); } while (0)
#define SWP 1
#define VCO 0
#define AV 0
#define PKE 0
#define VRF 3
#define XDL 6
#define QW 0
#define PDS 61
#define P_NVR 5
#define P_NVP 2
#define P_NWP 9
#define P_NW1 7
#define RF_ 208
#define PSV 1
#define RA_ (488 - 2 * RF_)
#define XI 5
#define XL 1
#define WCH 2
#define HX 0
#define VB 1
#define TP 0
#define CKI 0
#define NOP_ 2
#define KVO 0
#define NDL 3
#define AM 0
#define XM 3
#define XP 0
#define SPIN_LIMIT (1 << 20)
__device__ __forceinline__ uint64_t mkdesc(uint32_t addr, uint32_t lbo, uint32_t sbo) {
  return (uint64_t)((addr & 0x3FFFF) >> 4) | ((uint64_t)(lbo >> 4) << 16) | ((uint64_t)(sbo >> 4) << 32) | (1ull << 62);
}
__device__ __forceinline__ void mbar_init(uint32_t a, int c) { asm volatile("mbarrier.init.shared.b64 [%0],%1;" ::"r"(a), "r"(c) : "memory"); }
__device__ __forceinline__ void mbar_wait(uint32_t a, uint32_t par) {
  asm volatile(
      "{.reg .pred p; .reg .u32 n;\n"
      "mov.u32 n, 0;\n"
      "W: mbarrier.try_wait.parity.shared.b64 p,[%0],%1;\n"
      "@p bra D;\n"
      "add.u32 n, n, 1;\n"
      "setp.lt.u32 p, n, %2;\n"
      "@p bra W;\n"
      "trap;\n"
      "D:}" ::"r"(a), "r"(par), "n"(SPIN_LIMIT) : "memory");
}
__device__ __forceinline__ void mbar_wait_q(uint32_t a, uint32_t par) {
  asm volatile(
      "{.reg .pred p; .reg .u32 n;\n"
      "mov.u32 n, 0;\n"
      "W: mbarrier.try_wait.parity.shared.b64 p,[%0],%1,4000;\n"
      "@p bra D;\n"
      "add.u32 n, n, 1;\n"
      "setp.lt.u32 p, n, %2;\n"
      "@p bra W;\n"
      "trap;\n"
      "D:}" ::"r"(a), "r"(par), "n"(SPIN_LIMIT / 16) : "memory");
}
__device__ __forceinline__ void mbar_expect(uint32_t a, uint32_t b) { asm volatile("mbarrier.arrive.expect_tx.shared.b64 _,[%0],%1;" ::"r"(a), "r"(b) : "memory"); }
__device__ __forceinline__ void mbar_arrive(uint32_t a) { asm volatile("mbarrier.arrive.shared.b64 _,[%0];" ::"r"(a) : "memory"); }
__device__ __forceinline__ uint32_t mapa(uint32_t a, uint32_t cta) { uint32_t r; asm("mapa.shared::cluster.u32 %0,%1,%2;" : "=r"(r) : "r"(a), "r"(cta)); return r; }
__device__ __forceinline__ void mbar_arrive_cl(uint32_t a) { asm volatile("mbarrier.arrive.shared::cluster.b64 _,[%0];" ::"r"(a) : "memory"); }
__device__ __forceinline__ void tma2d(uint32_t dst, const CUtensorMap* m, int c0, int c1, uint32_t mb) {
  asm volatile("cp.async.bulk.tensor.2d.shared::cluster.global.mbarrier::complete_tx::bytes [%0],[%1,{%2,%3}],[%4];" ::"r"(dst), "l"(m), "r"(c0), "r"(c1), "r"(mb) : "memory");
}
__device__ __forceinline__ void tma2d_pf(const CUtensorMap* m, int c0, int c1) {
  asm volatile("cp.async.bulk.prefetch.tensor.2d.L2.global [%0,{%1,%2}];" ::"l"(m), "r"(c0), "r"(c1) : "memory");
}
__device__ __forceinline__ void tma3d(uint32_t dst, const CUtensorMap* m, int c1, int c2, uint32_t mb) {
  asm volatile("cp.async.bulk.tensor.3d.shared::cluster.global.mbarrier::complete_tx::bytes [%0],[%1,{0,%2,%3}],[%4];" ::"r"(dst), "l"(m), "r"(c1), "r"(c2), "r"(mb) : "memory");
}
__device__ __forceinline__ void tma2d_st(const CUtensorMap* m, int c0, int c1, uint32_t src) {
  asm volatile("cp.async.bulk.tensor.2d.global.shared::cta.bulk_group [%0,{%1,%2}],[%3];" ::"l"(m), "r"(c0), "r"(c1), "r"(src) : "memory");
}
__device__ __forceinline__ void bulk_ld(uint32_t dst, const void* src, uint32_t n, uint32_t mb) {
  asm volatile("cp.async.bulk.shared::cluster.global.mbarrier::complete_tx::bytes [%0],[%1],%2,[%3];" ::"r"(dst), "l"(src), "r"(n), "r"(mb) : "memory");
}
__device__ __forceinline__ void bulk_ld_mc(uint32_t dst, const void* src, uint32_t n, uint32_t mb) {
  asm volatile("cp.async.bulk.shared::cluster.global.mbarrier::complete_tx::bytes.multicast::cluster [%0],[%1],%2,[%3],%4;" ::"r"(dst), "l"(src), "r"(n), "r"(mb), "h"((uint16_t)3) : "memory");
}
__device__ __forceinline__ void bulk_st(void* dst, uint32_t src, uint32_t n) {
  asm volatile("cp.async.bulk.global.shared::cta.bulk_group [%0],[%1],%2;" ::"l"(dst), "r"(src), "r"(n) : "memory");
}
__device__ __forceinline__ void e_expect_tma3d(uint32_t dst, const CUtensorMap* m, int c1, int c2, uint32_t mb, uint32_t bytes) {
  asm volatile("{.reg .pred p; elect.sync _|p, 0xffffffff; @p mbarrier.arrive.expect_tx.shared.b64 _,[%4],%5;\n"
               "@p cp.async.bulk.tensor.3d.shared::cluster.global.mbarrier::complete_tx::bytes [%0],[%1,{0,%2,%3}],[%4];}" ::"r"(dst), "l"(m), "r"(c1), "r"(c2), "r"(mb), "r"(bytes) : "memory");
}
__device__ __forceinline__ void e_bulk_ld(uint32_t dst, const void* src, uint32_t n, uint32_t mb) {
  asm volatile("{.reg .pred p; elect.sync _|p, 0xffffffff; @p cp.async.bulk.shared::cluster.global.mbarrier::complete_tx::bytes [%0],[%1],%2,[%3];}" ::"r"(dst), "l"(src), "r"(n), "r"(mb) : "memory");
}
__device__ __forceinline__ void e_bulk_ld_ef(uint32_t dst, const void* src, uint32_t n, uint32_t mb) {
  asm volatile("{.reg .pred p; .reg .b64 c; createpolicy.fractional.L2::evict_first.b64 c,1.0; elect.sync _|p, 0xffffffff;"
               " @p cp.async.bulk.shared::cluster.global.mbarrier::complete_tx::bytes.L2::cache_hint [%0],[%1],%2,[%3],c;}" ::"r"(dst), "l"(src), "r"(n), "r"(mb) : "memory");
}
__device__ __forceinline__ void e_bulk_ld_mc(uint32_t dst, const void* src, uint32_t n, uint32_t mb) {
  asm volatile("{.reg .pred p; elect.sync _|p, 0xffffffff; @p cp.async.bulk.shared::cluster.global.mbarrier::complete_tx::bytes.multicast::cluster [%0],[%1],%2,[%3],%4;}" ::"r"(dst), "l"(src), "r"(n), "r"(mb), "h"((uint16_t)3) : "memory");
}
#define BULK_COMMIT() asm volatile("cp.async.bulk.commit_group;" ::: "memory")
#define BULK_WAIT_READ(n) asm volatile("cp.async.bulk.wait_group.read " #n ";" ::: "memory")
#define BULK_WAIT(n) asm volatile("cp.async.bulk.wait_group " #n ";" ::: "memory")
#define FENCE_ASYNC_SMEM() asm volatile("fence.proxy.async.shared::cta;" ::: "memory")
#define FENCE_ASYNC() asm volatile("fence.proxy.async;" ::: "memory")
#define WG_FENCE() asm volatile("wgmma.fence.sync.aligned;" ::: "memory")
#define WG_COMMIT() asm volatile("wgmma.commit_group.sync.aligned;" ::: "memory")
#define WG_WAIT(n) asm volatile("wgmma.wait_group.sync.aligned " #n ";" ::: "memory")
#define BAR_SYNC(id, n) asm volatile("bar.sync %0,%1;" ::"n"(id), "n"(n) : "memory")
#define BAR_ARRIVE(id, n) asm volatile("bar.arrive %0,%1;" ::"n"(id), "n"(n) : "memory")
#define SCHED_FENCE(k) asm volatile("{.reg .pred p; setp.ne.u32 p,%0,0; @p trap;}" ::"r"(mp.zero[(k) - 46]) : "memory")
#define CLUSTER_SYNC() asm volatile("barrier.cluster.arrive.relaxed.aligned; barrier.cluster.wait.aligned;" ::: "memory")
__device__ __forceinline__ uint32_t pk(float lo, float hi) { uint32_t r; asm("cvt.rn.bf16x2.f32 %0,%1,%2;" : "=r"(r) : "f"(hi), "f"(lo)); return r; }
__device__ __forceinline__ float blo(uint32_t v) { return __uint_as_float(v << 16); }
__device__ __forceinline__ float bhi(uint32_t v) { return __uint_as_float(v & 0xffff0000u); }
__device__ __forceinline__ void ldsm4(uint32_t* r, uint32_t a) {
  asm volatile("ldmatrix.sync.aligned.m8n8.x4.shared.b16 {%0,%1,%2,%3},[%4];" : "=r"(r[0]), "=r"(r[1]), "=r"(r[2]), "=r"(r[3]) : "r"(a) : "memory");
}
__device__ __forceinline__ void ldsm4t(uint32_t* r, uint32_t a) {
  asm volatile("ldmatrix.sync.aligned.m8n8.x4.trans.shared.b16 {%0,%1,%2,%3},[%4];" : "=r"(r[0]), "=r"(r[1]), "=r"(r[2]), "=r"(r[3]) : "r"(a) : "memory");
}
__device__ __forceinline__ void stsm4(uint32_t a, uint32_t r0, uint32_t r1, uint32_t r2, uint32_t r3) {
  asm volatile("stmatrix.sync.aligned.m8n8.x4.shared.b16 [%0],{%1,%2,%3,%4};" ::"r"(a), "r"(r0), "r"(r1), "r"(r2), "r"(r3) : "memory");
}
__device__ __forceinline__ void mma16(float* d, uint32_t a0, uint32_t a1, uint32_t a2, uint32_t a3, uint32_t b0, uint32_t b1) {
  asm volatile("mma.sync.aligned.m16n8k16.row.col.f32.bf16.bf16.f32 {%0,%1,%2,%3},{%4,%5,%6,%7},{%8,%9},{%0,%1,%2,%3};"
               : "+f"(d[0]), "+f"(d[1]), "+f"(d[2]), "+f"(d[3]) : "r"(a0), "r"(a1), "r"(a2), "r"(a3), "r"(b0), "r"(b1));
}
__device__ __forceinline__ void mma8(float* d, uint32_t a0, uint32_t a1, uint32_t b0) {
  asm volatile("mma.sync.aligned.m16n8k8.row.col.f32.bf16.bf16.f32 {%0,%1,%2,%3},{%4,%5},{%6},{%0,%1,%2,%3};"
               : "+f"(d[0]), "+f"(d[1]), "+f"(d[2]), "+f"(d[3]) : "r"(a0), "r"(a1), "r"(b0));
}
__device__ __forceinline__ float4 lds4f(uint32_t a) { float4 v; asm volatile("ld.shared.v4.f32 {%0,%1,%2,%3},[%4];" : "=f"(v.x), "=f"(v.y), "=f"(v.z), "=f"(v.w) : "r"(a) : "memory"); return v; }
__device__ __forceinline__ float2 lds2f(uint32_t a) { float2 v; asm volatile("ld.shared.v2.f32 {%0,%1},[%2];" : "=f"(v.x), "=f"(v.y) : "r"(a) : "memory"); return v; }
__device__ __forceinline__ uint4 lds4(uint32_t a) { uint4 v; asm volatile("ld.shared.v4.u32 {%0,%1,%2,%3},[%4];" : "=r"(v.x), "=r"(v.y), "=r"(v.z), "=r"(v.w) : "r"(a) : "memory"); return v; }
__device__ __forceinline__ uint2 lds2u(uint32_t a) { uint2 v; asm volatile("ld.shared.v2.u32 {%0,%1},[%2];" : "=r"(v.x), "=r"(v.y) : "r"(a) : "memory"); return v; }
__device__ __forceinline__ uint32_t lds1(uint32_t a) { uint32_t v; asm volatile("ld.shared.u32 %0,[%1];" : "=r"(v) : "r"(a) : "memory"); return v; }
__device__ __forceinline__ void sts4(uint32_t a, uint32_t x, uint32_t y, uint32_t z, uint32_t w) { asm volatile("st.shared.v4.u32 [%0],{%1,%2,%3,%4};" ::"r"(a), "r"(x), "r"(y), "r"(z), "r"(w) : "memory"); }
__device__ __forceinline__ void sts2(uint32_t a, uint32_t x, uint32_t y) { asm volatile("st.shared.v2.u32 [%0],{%1,%2};" ::"r"(a), "r"(x), "r"(y) : "memory"); }
__device__ __forceinline__ void sts1(uint32_t a, uint32_t x) { asm volatile("st.shared.u32 [%0],%1;" ::"r"(a), "r"(x) : "memory"); }
__device__ __forceinline__ void sta4(uint32_t a, const uint32_t* v, uint32_t mb) {
  asm volatile("st.async.shared::cluster.mbarrier::complete_tx::bytes.v4.b32 [%0],{%1,%2,%3,%4},[%5];" ::"r"(a), "r"(v[0]), "r"(v[1]), "r"(v[2]), "r"(v[3]), "r"(mb) : "memory");
}
__device__ __forceinline__ uint4 ldg_rlx4(const void* p) { uint4 v; asm volatile("ld.relaxed.gpu.global.v4.u32 {%0,%1,%2,%3},[%4];" : "=r"(v.x), "=r"(v.y), "=r"(v.z), "=r"(v.w) : "l"(p) : "memory"); return v; }
__device__ __forceinline__ uint32_t ldg_rlx1(const void* p) { uint32_t v; asm volatile("ld.relaxed.gpu.global.u32 %0,[%1];" : "=r"(v) : "l"(p) : "memory"); return v; }
__device__ __forceinline__ uint2 ldg_rlx2(const void* p) { uint2 v; asm volatile("ld.relaxed.gpu.global.v2.u32 {%0,%1},[%2];" : "=r"(v.x), "=r"(v.y) : "l"(p) : "memory"); return v; }
__device__ __forceinline__ uint4 ldg_b128(const void* p) {
  uint4 v;
  asm volatile("{.reg .b128 t; .reg .b64 a,b; ld.relaxed.gpu.global.b128 t,[%4]; mov.b128 {a,b},t; mov.b64 {%0,%1},a; mov.b64 {%2,%3},b;}" : "=r"(v.x), "=r"(v.y), "=r"(v.z), "=r"(v.w) : "l"(p) : "memory");
  return v;
}
__device__ __forceinline__ void stg_b128(void* p, uint32_t x, uint32_t y, uint32_t z, uint32_t w) {
  asm volatile("{.reg .b128 t; .reg .b64 a,b; mov.b64 a,{%1,%2}; mov.b64 b,{%3,%4}; mov.b128 t,{a,b}; st.relaxed.gpu.global.b128 [%0],t;}" ::"l"(p), "r"(x), "r"(y), "r"(z), "r"(w) : "memory");
}
__device__ __forceinline__ void st_b128(void* p, uint32_t x, uint32_t y, uint32_t z, uint32_t w) {
  asm volatile("{.reg .b128 t; .reg .b64 a,b; mov.b64 a,{%1,%2}; mov.b64 b,{%3,%4}; mov.b128 t,{a,b}; st.relaxed.gpu.b128 [%0],t;}" ::"l"(p), "r"(x), "r"(y), "r"(z), "r"(w) : "memory");
}
__device__ __forceinline__ void stg_rlx4(void* p, uint32_t x, uint32_t y, uint32_t z, uint32_t w) { asm volatile("st.relaxed.gpu.global.v4.u32 [%0],{%1,%2,%3,%4};" ::"l"(p), "r"(x), "r"(y), "r"(z), "r"(w) : "memory"); }
__device__ __forceinline__ void stg_rlx2(void* p, uint32_t x, uint32_t y) { asm volatile("st.relaxed.gpu.global.v2.u32 [%0],{%1,%2};" ::"l"(p), "r"(x), "r"(y) : "memory"); }
__device__ __forceinline__ void red4(void* p, float a, float b, float c, float d) { asm volatile("red.relaxed.gpu.global.add.v4.f32 [%0],{%1,%2,%3,%4};" ::"l"(p), "f"(a), "f"(b), "f"(c), "f"(d) : "memory"); }
__device__ __forceinline__ unsigned ld_acq(const unsigned* p) { unsigned v; asm volatile("ld.acquire.gpu.global.u32 %0,[%1];" : "=r"(v) : "l"(p) : "memory"); return v; }
__device__ __forceinline__ void red_rel(unsigned* p) { asm volatile("red.release.gpu.global.add.u32 [%0],1;" ::"l"(p) : "memory"); }
__device__ __forceinline__ void red_rlx(unsigned* p) { asm volatile("red.relaxed.gpu.global.add.u32 [%0],1;" ::"l"(p) : "memory"); }
__device__ __forceinline__ void wait_cnt(const unsigned* p, unsigned n) { int it = 0; while (ld_acq(p) < n) { if (++it > SPIN_LIMIT) __trap(); } }
__device__ __forceinline__ uint32_t clk() { uint32_t c; asm volatile("mov.u32 %0,%%clock;" : "=r"(c)); return c; }
__device__ __forceinline__ uint32_t gtime() { uint32_t c; asm volatile("mov.u32 %0,%%globaltimer_lo;" : "=r"(c)); return c; }
__device__ __forceinline__ void wait_until(uint32_t t0, uint32_t d) { while (clk() - t0 < d) {} }
__device__ __forceinline__ float ex2(float x) { float r; asm("ex2.approx.ftz.f32 %0,%1;" : "=f"(r) : "f"(x)); return r; }
__device__ __forceinline__ float silu(float x) { return x * __frcp_rn(1.f + __expf(-x)); }
__device__ __forceinline__ float rbf(float x) { return __bfloat162float(__float2bfloat16_rn(x)); }

__device__ __forceinline__ void wgmma_ss_n128(float* d, uint64_t a, uint64_t b, int sd) {
  asm volatile("{.reg .pred p; setp.ne.b32 p, %66, 0;\n"
    "wgmma.mma_async.sync.aligned.m64n128k16.f32.bf16.bf16 {%0,%1,%2,%3,%4,%5,%6,%7,%8,%9,%10,%11,%12,%13,%14,%15,%16,%17,%18,%19,%20,%21,%22,%23,%24,%25,%26,%27,%28,%29,%30,%31,%32,%33,%34,%35,%36,%37,%38,%39,%40,%41,%42,%43,%44,%45,%46,%47,%48,%49,%50,%51,%52,%53,%54,%55,%56,%57,%58,%59,%60,%61,%62,%63}, %64, %65, p, 1, 1, 0, 1;}\n"
    : "+f"(d[0]),"+f"(d[1]),"+f"(d[2]),"+f"(d[3]),"+f"(d[4]),"+f"(d[5]),"+f"(d[6]),"+f"(d[7]),
      "+f"(d[8]),"+f"(d[9]),"+f"(d[10]),"+f"(d[11]),"+f"(d[12]),"+f"(d[13]),"+f"(d[14]),"+f"(d[15]),
      "+f"(d[16]),"+f"(d[17]),"+f"(d[18]),"+f"(d[19]),"+f"(d[20]),"+f"(d[21]),"+f"(d[22]),"+f"(d[23]),
      "+f"(d[24]),"+f"(d[25]),"+f"(d[26]),"+f"(d[27]),"+f"(d[28]),"+f"(d[29]),"+f"(d[30]),"+f"(d[31]),
      "+f"(d[32]),"+f"(d[33]),"+f"(d[34]),"+f"(d[35]),"+f"(d[36]),"+f"(d[37]),"+f"(d[38]),"+f"(d[39]),
      "+f"(d[40]),"+f"(d[41]),"+f"(d[42]),"+f"(d[43]),"+f"(d[44]),"+f"(d[45]),"+f"(d[46]),"+f"(d[47]),
      "+f"(d[48]),"+f"(d[49]),"+f"(d[50]),"+f"(d[51]),"+f"(d[52]),"+f"(d[53]),"+f"(d[54]),"+f"(d[55]),
      "+f"(d[56]),"+f"(d[57]),"+f"(d[58]),"+f"(d[59]),"+f"(d[60]),"+f"(d[61]),"+f"(d[62]),"+f"(d[63])
    : "l"(a), "l"(b), "r"(sd));
}
__device__ __forceinline__ void wgmma_ss_n192(float* d, uint64_t a, uint64_t b, int sd) {
  asm volatile("{.reg .pred p; setp.ne.b32 p, %98, 0;\n"
    "wgmma.mma_async.sync.aligned.m64n192k16.f32.bf16.bf16 {%0,%1,%2,%3,%4,%5,%6,%7,%8,%9,%10,%11,%12,%13,%14,%15,%16,%17,%18,%19,%20,%21,%22,%23,%24,%25,%26,%27,%28,%29,%30,%31,%32,%33,%34,%35,%36,%37,%38,%39,%40,%41,%42,%43,%44,%45,%46,%47,%48,%49,%50,%51,%52,%53,%54,%55,%56,%57,%58,%59,%60,%61,%62,%63,%64,%65,%66,%67,%68,%69,%70,%71,%72,%73,%74,%75,%76,%77,%78,%79,%80,%81,%82,%83,%84,%85,%86,%87,%88,%89,%90,%91,%92,%93,%94,%95}, %96, %97, p, 1, 1, 0, 1;}\n"
    : "+f"(d[0]),"+f"(d[1]),"+f"(d[2]),"+f"(d[3]),"+f"(d[4]),"+f"(d[5]),"+f"(d[6]),"+f"(d[7]),
      "+f"(d[8]),"+f"(d[9]),"+f"(d[10]),"+f"(d[11]),"+f"(d[12]),"+f"(d[13]),"+f"(d[14]),"+f"(d[15]),
      "+f"(d[16]),"+f"(d[17]),"+f"(d[18]),"+f"(d[19]),"+f"(d[20]),"+f"(d[21]),"+f"(d[22]),"+f"(d[23]),
      "+f"(d[24]),"+f"(d[25]),"+f"(d[26]),"+f"(d[27]),"+f"(d[28]),"+f"(d[29]),"+f"(d[30]),"+f"(d[31]),
      "+f"(d[32]),"+f"(d[33]),"+f"(d[34]),"+f"(d[35]),"+f"(d[36]),"+f"(d[37]),"+f"(d[38]),"+f"(d[39]),
      "+f"(d[40]),"+f"(d[41]),"+f"(d[42]),"+f"(d[43]),"+f"(d[44]),"+f"(d[45]),"+f"(d[46]),"+f"(d[47]),
      "+f"(d[48]),"+f"(d[49]),"+f"(d[50]),"+f"(d[51]),"+f"(d[52]),"+f"(d[53]),"+f"(d[54]),"+f"(d[55]),
      "+f"(d[56]),"+f"(d[57]),"+f"(d[58]),"+f"(d[59]),"+f"(d[60]),"+f"(d[61]),"+f"(d[62]),"+f"(d[63]),
      "+f"(d[64]),"+f"(d[65]),"+f"(d[66]),"+f"(d[67]),"+f"(d[68]),"+f"(d[69]),"+f"(d[70]),"+f"(d[71]),
      "+f"(d[72]),"+f"(d[73]),"+f"(d[74]),"+f"(d[75]),"+f"(d[76]),"+f"(d[77]),"+f"(d[78]),"+f"(d[79]),
      "+f"(d[80]),"+f"(d[81]),"+f"(d[82]),"+f"(d[83]),"+f"(d[84]),"+f"(d[85]),"+f"(d[86]),"+f"(d[87]),
      "+f"(d[88]),"+f"(d[89]),"+f"(d[90]),"+f"(d[91]),"+f"(d[92]),"+f"(d[93]),"+f"(d[94]),"+f"(d[95])
    : "l"(a), "l"(b), "r"(sd));
}
__device__ __forceinline__ void wgmma_ss_n256(float* d, uint64_t a, uint64_t b, int sd) {
  asm volatile("{.reg .pred p; setp.ne.b32 p, %130, 0;\n"
    "wgmma.mma_async.sync.aligned.m64n256k16.f32.bf16.bf16 {%0,%1,%2,%3,%4,%5,%6,%7,%8,%9,%10,%11,%12,%13,%14,%15,%16,%17,%18,%19,%20,%21,%22,%23,%24,%25,%26,%27,%28,%29,%30,%31,%32,%33,%34,%35,%36,%37,%38,%39,%40,%41,%42,%43,%44,%45,%46,%47,%48,%49,%50,%51,%52,%53,%54,%55,%56,%57,%58,%59,%60,%61,%62,%63,%64,%65,%66,%67,%68,%69,%70,%71,%72,%73,%74,%75,%76,%77,%78,%79,%80,%81,%82,%83,%84,%85,%86,%87,%88,%89,%90,%91,%92,%93,%94,%95,%96,%97,%98,%99,%100,%101,%102,%103,%104,%105,%106,%107,%108,%109,%110,%111,%112,%113,%114,%115,%116,%117,%118,%119,%120,%121,%122,%123,%124,%125,%126,%127}, %128, %129, p, 1, 1, 0, 1;}\n"
    : "+f"(d[0]),"+f"(d[1]),"+f"(d[2]),"+f"(d[3]),"+f"(d[4]),"+f"(d[5]),"+f"(d[6]),"+f"(d[7]),
      "+f"(d[8]),"+f"(d[9]),"+f"(d[10]),"+f"(d[11]),"+f"(d[12]),"+f"(d[13]),"+f"(d[14]),"+f"(d[15]),
      "+f"(d[16]),"+f"(d[17]),"+f"(d[18]),"+f"(d[19]),"+f"(d[20]),"+f"(d[21]),"+f"(d[22]),"+f"(d[23]),
      "+f"(d[24]),"+f"(d[25]),"+f"(d[26]),"+f"(d[27]),"+f"(d[28]),"+f"(d[29]),"+f"(d[30]),"+f"(d[31]),
      "+f"(d[32]),"+f"(d[33]),"+f"(d[34]),"+f"(d[35]),"+f"(d[36]),"+f"(d[37]),"+f"(d[38]),"+f"(d[39]),
      "+f"(d[40]),"+f"(d[41]),"+f"(d[42]),"+f"(d[43]),"+f"(d[44]),"+f"(d[45]),"+f"(d[46]),"+f"(d[47]),
      "+f"(d[48]),"+f"(d[49]),"+f"(d[50]),"+f"(d[51]),"+f"(d[52]),"+f"(d[53]),"+f"(d[54]),"+f"(d[55]),
      "+f"(d[56]),"+f"(d[57]),"+f"(d[58]),"+f"(d[59]),"+f"(d[60]),"+f"(d[61]),"+f"(d[62]),"+f"(d[63]),
      "+f"(d[64]),"+f"(d[65]),"+f"(d[66]),"+f"(d[67]),"+f"(d[68]),"+f"(d[69]),"+f"(d[70]),"+f"(d[71]),
      "+f"(d[72]),"+f"(d[73]),"+f"(d[74]),"+f"(d[75]),"+f"(d[76]),"+f"(d[77]),"+f"(d[78]),"+f"(d[79]),
      "+f"(d[80]),"+f"(d[81]),"+f"(d[82]),"+f"(d[83]),"+f"(d[84]),"+f"(d[85]),"+f"(d[86]),"+f"(d[87]),
      "+f"(d[88]),"+f"(d[89]),"+f"(d[90]),"+f"(d[91]),"+f"(d[92]),"+f"(d[93]),"+f"(d[94]),"+f"(d[95]),
      "+f"(d[96]),"+f"(d[97]),"+f"(d[98]),"+f"(d[99]),"+f"(d[100]),"+f"(d[101]),"+f"(d[102]),"+f"(d[103]),
      "+f"(d[104]),"+f"(d[105]),"+f"(d[106]),"+f"(d[107]),"+f"(d[108]),"+f"(d[109]),"+f"(d[110]),"+f"(d[111]),
      "+f"(d[112]),"+f"(d[113]),"+f"(d[114]),"+f"(d[115]),"+f"(d[116]),"+f"(d[117]),"+f"(d[118]),"+f"(d[119]),
      "+f"(d[120]),"+f"(d[121]),"+f"(d[122]),"+f"(d[123]),"+f"(d[124]),"+f"(d[125]),"+f"(d[126]),"+f"(d[127])
    : "l"(a), "l"(b), "r"(sd));
}
__device__ __forceinline__ void wgmma_rs_n32(float* d, const uint32_t* a, uint64_t b, int sd) {
  asm volatile("{.reg .pred p; setp.ne.b32 p, %21, 0;\n"
    "wgmma.mma_async.sync.aligned.m64n32k16.f32.bf16.bf16 {%0,%1,%2,%3,%4,%5,%6,%7,%8,%9,%10,%11,%12,%13,%14,%15}, {%16,%17,%18,%19}, %20, p, 1, 1, 0;}\n"
    : "+f"(d[0]),"+f"(d[1]),"+f"(d[2]),"+f"(d[3]),"+f"(d[4]),"+f"(d[5]),"+f"(d[6]),"+f"(d[7]),
      "+f"(d[8]),"+f"(d[9]),"+f"(d[10]),"+f"(d[11]),"+f"(d[12]),"+f"(d[13]),"+f"(d[14]),"+f"(d[15])
    : "r"(a[0]), "r"(a[1]), "r"(a[2]), "r"(a[3]), "l"(b), "r"(sd));
}
__device__ __forceinline__ void wgmma_ssT_n32(float* d, uint64_t a, uint64_t b, int sd) {
  asm volatile("{.reg .pred p; setp.ne.b32 p, %18, 0;\n"
    "wgmma.mma_async.sync.aligned.m64n32k16.f32.bf16.bf16 {%0,%1,%2,%3,%4,%5,%6,%7,%8,%9,%10,%11,%12,%13,%14,%15}, %16, %17, p, 1, 1, 1, 0;}\n"
    : "+f"(d[0]),"+f"(d[1]),"+f"(d[2]),"+f"(d[3]),"+f"(d[4]),"+f"(d[5]),"+f"(d[6]),"+f"(d[7]),
      "+f"(d[8]),"+f"(d[9]),"+f"(d[10]),"+f"(d[11]),"+f"(d[12]),"+f"(d[13]),"+f"(d[14]),"+f"(d[15])
    : "l"(a), "l"(b), "r"(sd));
}

__device__ __forceinline__ void wgmma_rs_n32_z(float* d, const uint32_t* a, uint64_t b) {
  asm volatile("{.reg .pred p; setp.ne.b32 p, 0, 0;\n"
    "wgmma.mma_async.sync.aligned.m64n32k16.f32.bf16.bf16 {%0,%1,%2,%3,%4,%5,%6,%7,%8,%9,%10,%11,%12,%13,%14,%15}, {%16,%17,%18,%19}, %20, p, 1, 1, 0;}\n"
    : "=f"(d[0]),"=f"(d[1]),"=f"(d[2]),"=f"(d[3]),"=f"(d[4]),"=f"(d[5]),"=f"(d[6]),"=f"(d[7]),
      "=f"(d[8]),"=f"(d[9]),"=f"(d[10]),"=f"(d[11]),"=f"(d[12]),"=f"(d[13]),"=f"(d[14]),"=f"(d[15])
    : "r"(a[0]), "r"(a[1]), "r"(a[2]), "r"(a[3]), "l"(b));
}

namespace rec {
constexpr int NVR = P_NVR;
constexpr int NVS = 16 - NVR;
constexpr int NVP = P_NVP;
constexpr int NWP = P_NWP;
constexpr uint32_t WO = 0;
constexpr uint32_t XB = 65536;
constexpr uint32_t PK = XB + 32768;
constexpr uint32_t VN = PK + 24576;
constexpr uint32_t VX0 = VN + 4096;
constexpr uint32_t WVS = 131072;
constexpr uint32_t MEM = WVS + 2 * NVS * 2048;
constexpr uint32_t ARO = MEM + 10240;
constexpr uint32_t OB = ARO + 5120;
constexpr uint32_t QT = OB + 2048;
constexpr uint32_t KT = QT + 2048;
constexpr uint32_t RQ = KT + 6144;
constexpr uint32_t RK = RQ + 2048;
constexpr uint32_t SC = RK + 2048;
constexpr uint32_t OT = OB;
constexpr uint32_t TF = SC + 2048;
constexpr uint32_t PRE = MEM + 2 * NVR * 2048;
constexpr uint32_t TA = TF + 8192;
constexpr uint32_t RX = TA + 6144;
constexpr uint32_t VX1 = RX + 2048;
constexpr uint32_t BARS = VX1 + 4096;
constexpr uint32_t PACE = BARS + 18 * 8;
constexpr uint32_t SMEM = BARS + 512;
static_assert(PRE + 14336 <= BARS, "staging");
constexpr int NW1 = P_NW1;
static_assert(SMEM <= 232448, "smem");
constexpr int B_E = 2, B_SC = 3, B_S = 4, B_O = 5, B_F = 6, B_W = 7, B_C = 9, B_K = 10, B_H = 15, B_Q = 1, B_S2 = 6, B_T2 = 9, B_P = 13, B_T = 14, B_R = 11, B_X = 12, B_V = 8;
constexpr int N_P = XE == 1 ? 416 : 384, N_R = XE ? 288 : 320, N_V = AV ? 384 : 512, N_O = AV ? 384 : 416;
constexpr int XC = 16384, X_RING = 131072, X_SC = 65536, X_TOK = 4096;
#define X_VX(i) (((i) >> 1) * 2048 + ((i) & 1) * 512)
#define X_VM(i) (X_VX(i) + 1024)
#define V_RING(n) (((n) & 1) * X_RING + ((n) & 2) * 2048)
#define V_TAG(n) ((~(n) >> 2) & 1)
}
struct RecMaps { CUtensorMap wq, wk, wv, wo, ari; int zero[40]; };

#define F_(x) __uint_as_float(x)
#define U_(x) __float_as_uint(x)
#define AR_R(q) (24 + ((q) & 1) * 16 + ((q) >> 1) * 56)
#define AR_P(q) ((q) >> 1)
#define AR_ROW(i) (24 + ((i) & 1) * 16 + ((i) & 2) * 92 + (((i) >> 2) & 7) + ((i) >> 5) * 128)
constexpr size_t AR_OFF = 32 * 262144;
__device__ __forceinline__ void ar_fetch(uint32_t dst, const CUtensorMap* m, int slot, int half, uint32_t mb) {
  asm volatile("{.reg .pred p; elect.sync _|p, 0xffffffff; @p mbarrier.arrive.expect_tx.shared.b64 _,[%4],10240;\n"
               "@p cp.async.bulk.tensor.3d.shared::cluster.global.mbarrier::complete_tx::bytes [%0],[%1,{%2,%3,%6}],[%4];\n"
               "@p cp.async.bulk.tensor.3d.shared::cluster.global.mbarrier::complete_tx::bytes [%0+5120],[%1,{%2,%5,%7}],[%4];}"
               ::"r"(dst), "l"(m), "r"(slot * 64), "r"(AR_R(half * 2)), "r"(mb), "r"(AR_R(half * 2 + 1)), "r"(AR_P(half * 2)), "r"(AR_P(half * 2 + 1)) : "memory");
}
__device__ __forceinline__ uint4 exch_b128(void* p, uint32_t x, uint32_t y, uint32_t z, uint32_t w) {
  uint4 v;
  asm volatile("{.reg .b128 s, t; .reg .b64 a,b; mov.b64 a,{%5,%6}; mov.b64 b,{%7,%8}; mov.b128 s,{a,b}; atom.relaxed.gpu.global.exch.b128 t,[%4],s;"
               " mov.b128 {a,b},t; mov.b64 {%0,%1},a; mov.b64 {%2,%3},b;}" : "=r"(v.x), "=r"(v.y), "=r"(v.z), "=r"(v.w) : "l"(p), "r"(x), "r"(y), "r"(z), "r"(w) : "memory");
  return v;
}
#define CONSUME(v) do { if ((v) == 0x7fc12345u) sts1(sb + rec::BARS + 96, 0); } while (0)
__device__ __forceinline__ uint32_t tagf(float v, uint32_t tag) { return (__float_as_uint(v) & ~1u) | tag; }
__device__ __forceinline__ uint2 ldg_b64(const void* p) { uint2 v; asm volatile("{.reg .b64 t; ld.relaxed.gpu.global.b64 t,[%2]; mov.b64 {%0,%1},t;}" : "=r"(v.x), "=r"(v.y) : "l"(p) : "memory"); return v; }
__device__ __forceinline__ void stg_b64(void* p, uint32_t x, uint32_t y) { asm volatile("{.reg .b64 t; mov.b64 t,{%1,%2}; st.relaxed.gpu.global.b64 [%0],t;}" ::"l"(p), "r"(x), "r"(y) : "memory"); }
__device__ __forceinline__ uint32_t tagbad(uint32_t x, uint32_t y, uint32_t tag) { uint32_t r; asm("lop3.b32 %0,%1,%2,%3,0x7e;" : "=r"(r) : "r"(x), "r"(y), "r"(tag)); return r; }

__device__ __forceinline__ bool anybad(uint32_t a, uint32_t b, uint32_t c, uint32_t d, uint32_t e, uint32_t f, uint32_t g, uint32_t h, uint32_t tag) {
  uint32_t r;
  asm volatile("{.reg .b32 t,u,v,w; .reg .pred p; lop3.b32 t,%1,%2,%9,0x7e; lop3.b32 u,%3,%4,%9,0x7e; lop3.b32 v,%5,%6,%9,0x7e; lop3.b32 w,%7,%8,%9,0x7e;"
               " lop3.b32 t,t,u,v,0xfe; lop3.b32 t,t,w,1,0xa8; setp.ne.u32 p,t,0; vote.sync.any.pred p,p,0xffffffff; selp.u32 %0,1,0,p;}"
               : "=r"(r) : "r"(a), "r"(b), "r"(c), "r"(d), "r"(e), "r"(f), "r"(g), "r"(h), "r"(tag));
  return r;
}
__device__ __forceinline__ bool anybad(uint32_t a, uint32_t b, uint32_t c, uint32_t d, uint32_t tag) {
  uint32_t r;
  asm volatile("{.reg .b32 t,u; .reg .pred p; lop3.b32 t,%1,%2,%5,0x7e; lop3.b32 u,%3,%4,%5,0x7e;"
               " lop3.b32 t,t,u,1,0xa8; setp.ne.u32 p,t,0; vote.sync.any.pred p,p,0xffffffff; selp.u32 %0,1,0,p;}"
               : "=r"(r) : "r"(a), "r"(b), "r"(c), "r"(d), "r"(tag));
  return r;
}
#define BAD8(r) anybad(r[0].x, r[0].z, r[1].x, r[1].z, r[2].x, r[2].z, r[3].x, r[3].z, tag)
#define BADS(r) anybad(r[0].x, r[0].y, r[1].x, r[1].y, r[2].x, r[2].y, r[3].x, r[3].y, tag)
constexpr float SCS = 0.08838834764831845f * 1.4426950408889634f / 16.f;
__device__ __forceinline__ uint32_t pkh(float lo, float hi, uint32_t tag) {
  uint32_t r;
  asm("{.reg .b32 t; cvt.rn.satfinite.f16x2.f32 t,%1,%2; lop3.b32 %0,t,0xfffffffe,%3,0xea;}" : "=r"(r) : "f"(hi), "f"(lo), "r"(tag));
  return r;
}
__device__ __forceinline__ uint32_t addh(uint32_t a, uint32_t b) { uint32_t r; asm("add.rn.f16x2 %0,%1,%2;" : "=r"(r) : "r"(a), "r"(b)); return r; }
__device__ __forceinline__ float hlo(uint32_t v) { float r; asm("{.reg .b16 a,b; mov.b32 {a,b},%1; cvt.f32.f16 %0,a;}" : "=f"(r) : "r"(v)); return r; }
__device__ __forceinline__ float hhi(uint32_t v) { float r; asm("{.reg .b16 a,b; mov.b32 {a,b},%1; cvt.f32.f16 %0,b;}" : "=f"(r) : "r"(v)); return r; }
__device__ __forceinline__ uint32_t ordh(uint32_t v) {
  uint32_t r;
  asm("{.reg .b32 m; prmt.b32 m,%1,0,0xbb99; lop3.b32 %0,%1,m,0x7fff7fff,0x78;}" : "=r"(r) : "r"(v));
  return r;
}
template <bool MASK>
__device__ __forceinline__ float4 softmax2(const uint2 (&r)[4], uint32_t mx, uint32_t my, uint32_t& k) {
  uint32_t x = addh(addh(r[0].x, r[1].x), addh(r[2].x, r[3].x)), y = addh(addh(r[0].y, r[1].y), addh(r[2].y, r[3].y));
  if (MASK) { x = addh(x, mx); y = addh(y, my); }
  asm("max.f16x2 %0,%1,%2;" : "=r"(k) : "r"(x), "r"(y));
  k = ordh(k);
  const int k0 = __reduce_max_sync(~0u, (int)(k << 16)), k1 = __reduce_max_sync(~0u, (int)k);
  const float m0 = hhi(k0 ^ ((k0 >> 31) & 0x7fff0000)) * -16.f, m1 = hhi(k1 ^ ((k1 >> 31) & 0x7fff0000)) * -16.f;
  return make_float4(ex2(fmaf(hlo(x), 16.f, m0)), ex2(fmaf(hhi(x), 16.f, m1)), ex2(fmaf(hlo(y), 16.f, m0)), ex2(fmaf(hhi(y), 16.f, m1)));
}
__device__ __forceinline__ char* mkp(uint32_t lo, uint32_t hi) { uint64_t r; asm("mov.b64 %0,{%1,%2};" : "=l"(r) : "r"(lo), "r"(hi)); return (char*)r; }
#define LO(p) ((uint32_t)(uint64_t)(p))
#define HI(p) ((uint32_t)((uint64_t)(p) >> 32))
__device__ __forceinline__ void cp16(uint32_t dst, const void* src) { asm volatile("cp.async.cg.shared.global [%0],[%1],16;" ::"r"(dst), "l"(src) : "memory"); }
__device__ __forceinline__ uint32_t xor3(uint32_t a, uint32_t b, uint32_t c) { uint32_t r; asm volatile("lop3.b32 %0,%1,%2,%3,0x96;" : "=r"(r) : "r"(a), "r"(b), "r"(c)); return r; }
__device__ __forceinline__ uint32_t mulbf(uint32_t a, uint32_t b) { uint32_t r; asm("mul.rn.bf16x2 %0,%1,%2;" : "=r"(r) : "r"(a), "r"(b)); return r; }
__device__ __forceinline__ uint32_t fmabf(uint32_t a, uint32_t b, uint32_t c) { uint32_t r; asm("fma.rn.bf16x2 %0,%1,%2,%3;" : "=r"(r) : "r"(a), "r"(b), "r"(c)); return r; }
__device__ __forceinline__ uint32_t addbf(uint32_t a, uint32_t b) { uint32_t r; asm("add.rn.bf16x2 %0,%1,%2;" : "=r"(r) : "r"(a), "r"(b)); return r; }
__device__ __forceinline__ void pv_mem(const uint32_t (&p)[4], uint32_t pm, const uint4 (&v)[4], const uint4 (&vn)[2], uint32_t (&O)[4]) {
  float o[4][4] = {{0, 0, 0, 0}, {0, 0, 0, 0}, {0, 0, 0, 0}, {0, 0, 0, 0}};
  mma16(o[0], v[0].x, v[0].y, v[0].z, v[0].w, p[0], p[1]);
  mma16(o[1], v[2].x, v[2].y, v[2].z, v[2].w, p[0], p[1]);
  mma16(o[2], v[1].x, v[1].y, v[1].z, v[1].w, p[2], p[3]);
  mma16(o[3], v[3].x, v[3].y, v[3].z, v[3].w, p[2], p[3]);
  mma16(o[0], vn[0].x, vn[0].y, vn[0].z, vn[0].w, pm, pm);
  mma16(o[1], vn[1].x, vn[1].y, vn[1].z, vn[1].w, pm, pm);
  O[0] = pk(o[0][0] + o[2][0], o[0][1] + o[2][1]); O[1] = pk(o[0][2] + o[2][2], o[0][3] + o[2][3]);
  O[2] = pk(o[1][0] + o[3][0], o[1][1] + o[3][1]); O[3] = pk(o[1][2] + o[3][2], o[1][3] + o[3][3]);
}
__device__ __forceinline__ void pv_tok(const uint32_t (&p)[4], uint32_t pm, const uint4 (&v)[4], const uint32_t (&vm)[4], uint32_t (&O)[4]) {
  float o[2][4] = {{0, 0, 0, 0}, {0, 0, 0, 0}}, sum[4] = {0, 0, 0, 0};
  const uint32_t one = 0x3f803f80u;
  mma16(sum, one, one, one, one, p[0], p[1]);
  mma16(o[0], v[0].x, v[0].y, v[0].z, v[0].w, p[0], p[1]);
  mma16(o[1], v[2].x, v[2].y, v[2].z, v[2].w, p[0], p[1]);
  mma16(sum, one, one, one, one, p[2], p[3]);
  mma16(o[0], v[1].x, v[1].y, v[1].z, v[1].w, p[2], p[3]);
  mma16(o[1], v[3].x, v[3].y, v[3].z, v[3].w, p[2], p[3]);
  mma8(sum, one, one, pm);
  mma8(o[0], vm[0], vm[1], pm);
  mma8(o[1], vm[2], vm[3], pm);
  float i0, i1;
  asm("rcp.approx.ftz.f32 %0,%1;" : "=f"(i0) : "f"(sum[0]));
  asm("rcp.approx.ftz.f32 %0,%1;" : "=f"(i1) : "f"(sum[1]));
  O[0] = pk(o[0][0] * i0, o[0][1] * i1); O[1] = pk(o[0][2] * i0, o[0][3] * i1);
  O[2] = pk(o[1][0] * i0, o[1][1] * i1); O[3] = pk(o[1][2] * i0, o[1][3] * i1);
}
__device__ __forceinline__ uint32_t sum4bf(uint32_t a, uint32_t b, uint32_t c, uint32_t d) { return addbf(addbf(a, b), addbf(c, d)); }
template <int OFF>
__device__ __forceinline__ void sta1(uint32_t a, uint32_t v, uint32_t mb) {
  asm volatile("st.async.shared::cluster.mbarrier::complete_tx::bytes.b32 [%0+%3],%1,[%2];" ::"r"(a), "r"(v), "r"(mb), "n"(OFF) : "memory");
}

__device__ __forceinline__ void wait_time(uint32_t t) { while ((int)(gtime() - t) < 0) __nanosleep(64); }
__device__ __noinline__ void rec_prefetch(const char* wmod, const char* w1, const char* x, const char* wo) {
  const int hb = blockIdx.x - 128;
  const uint32_t t0 = gtime();
  uint32_t t = t0 + PF0;
#pragma unroll 1
  for (int job = 0; job < (PFT ? 5 : 3); job++) {
    const char* p = job == 0 ? x + (6 + hb) * 65536 : job == 1 ? wmod + hb * 12288 + 4096 : job == 2 ? w1 + hb * 7168 : job == 3 ? x + hb * 8192 : wo + (1020 + hb) * 8192;
    const int n = job == 0 ? 120 - (hb & 2) * 4 : job == 3 ? 128 : 256, d = job == 0 ? 8192 : job == 1 ? 49152 : job == 2 ? 28672 : job == 3 ? 32768 : -32768;
    if (job == 3) t = t0 + PFT;
    PT(8 + job);
#pragma unroll 1
    for (int i = 0; i < n; i++) {
      wait_time(t);
      asm volatile("cp.async.bulk.prefetch.L2.global [%0], %1;" ::"l"(p), "r"(job == 2 ? 7168 : 8192) : "memory");
      p += !job && (i & 7) == 7 ? 204800 : d;
      t += job < 3 ? PFD : PFS;
      if (job && (i & 31) == 31 && ldg_rlx1(&g_fin)) return;
    }
  }
  PT(13);
}
__device__ __noinline__ void rec_helper(uint32_t sb, const bf16* cvec, const bf16* wmod, const char* w1, const bf16* b1, uint32_t t0) {
  const int tid = threadIdx.x, hb = blockIdx.x - 128;
  PT(1);
  for (int i = tid; i < 1024; i += 256) sts1(sb + i * 8, U_(rbf(silu(__bfloat162float(cvec[i])))));
  for (int i = tid; i < 2048; i += 256) g_stat[hb * 2048 + i] = make_uint4(~0u, ~0u, ~0u, ~0u);
  for (int i = tid; i < 512; i += 256) g_cnt[hb * 512 + i] = 0;
#pragma unroll 1
  for (int job = 0; job < 2; job++) {
    wait_time(t0 + PF0 + (job ? 600 : 350) * PFD);
    BAR_SYNC(rec::B_F, 256);
    PT(2 + job * 5);
    const int n8 = job ? 112 : 128, rg = tid >= n8, cg = tid - rg * n8, pitch = job ? 448 : 768;
    const uint4* p = (const uint4*)(job ? w1 + hb * 1792 : (const char*)(wmod + 2048 + hb * 1024)) + rg * pitch + min(cg, n8 - 1);
    float a1[8] = {0, 0, 0, 0, 0, 0, 0, 0}, a2[8] = {0, 0, 0, 0, 0, 0, 0, 0};
#pragma unroll 1
    for (int r0 = rg; r0 < 1024; r0 += 32) {
      uint4 v[16];
#pragma unroll
      for (int i = 0; i < 16; i++) { v[i] = ldg_rlx4(p); p += 2 * pitch; }
#pragma unroll
      for (int i = 0; i < 16; i++) {
        const float2 f = lds2f(sb + (r0 + 2 * i) * 8);
        const float w[8] = {blo(v[i].x), bhi(v[i].x), blo(v[i].y), bhi(v[i].y), blo(v[i].z), bhi(v[i].z), blo(v[i].w), bhi(v[i].w)};
#pragma unroll
        for (int e = 0; e < 8; e++) { a1[e] += f.x * w[e]; a2[e] += f.y * w[e]; }
      }
    }
    const uint32_t rd = sb + 8192;
    if (cg < n8) {
#pragma unroll
      for (int e = 0; e < 8; e++) sts2(rd + rg * 8192 + (cg * 8 + e) * 8, U_(a1[e]), U_(a2[e]));
    }
    BAR_SYNC(rec::B_F, 256);
    if (job == 0) {
      for (int i = tid; i < 1024; i += 256) g_mod[2048 + hb * 1024 + i] = rbf(F_(lds1(rd + i * 8)) + F_(lds1(rd + 8192 + i * 8)));
      BAR_SYNC(rec::B_F, 256);
      PT(6);
      if (tid == 0) { red_rel(&g_mcnt); wait_cnt(&g_mcnt, 4); }
      BAR_SYNC(rec::B_F, 256);
      for (int i = tid; i < 1024; i += 256) sts2(sb + i * 8, U_(rbf(1.f + __ldcg(g_mod + 4096 + i))), U_(__ldcg(g_mod + 3072 + i)));
    } else {
      for (int i = tid; i < 448; i += 256) {
        const int gn = hb * 896 + i * 2;
        const uint32_t bb = *(const uint32_t*)(b1 + gn);
        const float4 u = lds4f(rd + i * 16), w = lds4f(rd + 8192 + i * 16);
        ((uint2*)g_cc)[(gn >> 4) * 8 + ((gn >> 1) & 3) * 2 + ((gn >> 3) & 1)] = make_uint2(pk(u.x + w.x, u.z + w.z), pk(0.5f * (u.y + w.y + blo(bb)), 0.5f * (u.w + w.w + bhi(bb))));
      }
      PT(4);
    }
  }
}

__global__ void __cluster_dims__(2, 1, 1) __launch_bounds__(512, 1)
k_rec(const __grid_constant__ RecMaps mp, const bf16* __restrict__ mem0, const bf16* __restrict__ x, const bf16* __restrict__ cvec,
      const bf16* __restrict__ wmod, const char* __restrict__ w1, const bf16* __restrict__ b1, const char* __restrict__ wo, char* xc, int dF, int dA, int dS, int dM, int dG, int dP, int dX, int dD, int dZ, int dZ2, int dV, int dX2) {
  using namespace rec;
  extern __shared__ __align__(1024) char smem[];
  const uint32_t sb = (uint32_t)__cvta_generic_to_shared(smem);
  if ((sb & 0x3FFFF) != 1024) __trap();
  PH(0); if (threadIdx.x == 0) PT(0);
  if (threadIdx.x == 0) {
    int b = blockIdx.x;
    if (b >= 8 && b < 128) {
      const int t = (b >> 1) - 4, u = t - 32;
      b = 2 * (t < 32 ? 4 + (t & 16) + (t & 7) * 2 + ((t >> 3) & 1) : 36 + (u / 14) * 14 + (u % 7) * 2 + ((u / 7) & 1)) + (b & 1);
    }
    sts1(sb + rec::PACE + 24, b);
    const int c = blockIdx.x >> 1, l = c < 36 ? (c - 4) & 7 : (c - 36) % 7, m = c < 4 ? c : c < 36 ? (c - 4) >> 3 : (c - 36) / 7;
    const int g = c < 4 ? 15 : (l >> 1) * 4 + (l & 1) + (c < 36 ? 0 : 2);
    unsigned sm;
    asm("mov.u32 %0,%%smid;" : "=r"(sm));
    if (c < 64) g_slot[sm & 255] = 1 + FMAP;
  }
#define ROLE_REFRESH { asm volatile("mov.u32 %0,%%tid.x;" : "=r"(tid)); wid = __shfl_sync(~0u, tid >> 5, 0); b = __shfl_sync(~0u, lds1(sb + PACE + 24), 0); }
#define ROLE_VARS int tid; asm volatile("mov.u32 %0,%%tid.x;" : "=r"(tid)); \
    int wid = __shfl_sync(~0u, tid >> 5, 0), b = __shfl_sync(~0u, lds1(sb + PACE + 24), 0);
#define wg (wid >> 2)
#define iw (wid & 3)
#define h (b >> 2)
#define j (b & 3)
#define a (b & 1)
#define bb ((b >> 1) & 1)
  const uint32_t wbar = sb + BARS + 48, obar = wbar + 8;
  if (threadIdx.x == 256) {
    for (int i = 0; i < 18; i++) if (i != 12) mbar_init(sb + BARS + i * 8, i == 3 || i == 8 || i == 9 || i == 10 ? 2 : 1);
    for (int i = 0; i < 3; i++) mbar_init(sb + PACE + i * 8, 1);
    asm volatile("fence.mbarrier_init.release.cluster;" ::: "memory");
    FENCE_ASYNC_SMEM();
    mbar_expect(sb + BARS, 2048);
    mbar_expect(sb + BARS + 16, 4096);
    mbar_expect(sb + BARS + 32, 4096);
    mbar_expect(sb + BARS + 40, 4096);
  }
  __syncthreads();
  asm volatile("barrier.cluster.arrive.relaxed.aligned;" ::: "memory");
#define lane ((int)(l16 >> 4))
#define l16 (L16 & 0x1f0)
#define is7 ((L16 & 112) == 112)
#define PIN(x) __shfl_xor_sync(~0u, (uint32_t)(x), 0)
#define REFRESH() L16 = __shfl_xor_sync(~0u, L16, 0)
#define lar ((L16 & 0x180) * 8 + (L16 & 0x70))
#define X_LOAD(n, w, u) \
        asm volatile("{.reg .pred p; elect.sync _|p, 0xffffffff; @p mbarrier.arrive.expect_tx.shared.b64 _,[%2],8192;\n" \
                     "@p cp.async.bulk.shared::cluster.global.mbarrier::complete_tx::bytes [%0],[%1],8192,[%2];}" ::"r"(sb + XB + (w) * 16384 + (u) * 8192), \
                     "l"(g_h + (n) * 4096 + a * 2048 + (w) * 1024 + (u) * 512), "r"(sb + BARS + 64 + (w) * 8) : "memory")
#define lpub ((L16 & 0x30) * 64 + ((L16 >> 3) & 0x38))
#define lrow ((L16 & 0x70) + (((L16 >> 3) ^ L16) & 0x70 & ~((L16 >> 3) & 0x40) ? L16 & 0x180 : 512))

  const int role = __shfl_sync(~0u, threadIdx.x >> 7, 0);
  if (role < 2) {
    asm volatile("setmaxnreg.inc.sync.aligned.u32 %0;" ::"n"(RF_));
    ROLE_VARS
    uint32_t L16 = __shfl_sync(~0u, sb + (tid & 31) * 16, tid & 31);
    uint32_t wQ[16][4], wK[16][4], wV[NVR][4];
    uint32_t m0[2][4];
    uint32_t frag = sb + ((lane & 7) + (lane >> 4) * 8) * 128 + (((iw * 2 + ((lane >> 3) & 1)) ^ (lane & 7)) << 4);
#define QSW (SWP && !a ? 64 : 0)
    {
      const bool spare = b >= 128;
      const uint32_t t0 = gtime();
      uint4 xr[16];
      int seg = spare ? b - 126 : wg;
      const int half = spare ? wg : a;
      auto x_fetch = [&]() {
        const uint4* px = (const uint4*)x + (seg * 32 + iw * 8 + (lane >> 2)) * 128 + half * 64 + (lane & 3);
#pragma unroll
        for (int i = 0; i < 16; i++) xr[i] = __ldg(px + i * 4);
      };
      if (!spare) {
        uint4 wm[8];
        const uint4* pw = (const uint4*)(wmod + (size_t)((b >> 5) * 256 + (tid >> 3)) * 6144 + (b & 31) * 64) + (tid & 7);
        const float cs = __bfloat162float(cvec[(b >> 5) * 256 + tid]);
#pragma unroll
        for (int i = 0; i < 8; i++) wm[i] = __ldcs(pw + (size_t)i * 32 * 768);
        unsigned short mr[16];
#pragma unroll
        for (int i = 0; i < 16; i++) mr[i] = __bfloat16_as_ushort(mem0[(i & 7) * 1024 + a * 512 + tid * 2 + (i >> 3)]);
        float* sc = (float*)(smem + PRE);
        sc[tid] = rbf(silu(cs));
        PT(1);
        BAR_SYNC(B_F, 256);
        float acc[8] = {0, 0, 0, 0, 0, 0, 0, 0};
#pragma unroll
        for (int i = 0; i < 8; i++) {
          const float f = sc[i * 32 + (tid >> 3)];
          acc[0] += f * blo(wm[i].x); acc[1] += f * bhi(wm[i].x); acc[2] += f * blo(wm[i].y); acc[3] += f * bhi(wm[i].y);
          acc[4] += f * blo(wm[i].z); acc[5] += f * bhi(wm[i].z); acc[6] += f * blo(wm[i].w); acc[7] += f * bhi(wm[i].w);
        }
#pragma unroll
        for (int i = 0; i < 8; i++) { acc[i] += __shfl_xor_sync(~0u, acc[i], 8); acc[i] += __shfl_xor_sync(~0u, acc[i], 16); }
        float* red = sc + 1024;
        if ((tid & 31) < 8) {
#pragma unroll
          for (int i = 0; i < 8; i++) red[(tid >> 5) * 64 + (tid & 7) * 8 + i] = acc[i];
        }
        BAR_SYNC(B_F, 256);
        PT(2);
        if (tid < 64) {
          float t = 0;
#pragma unroll
          for (int i = 0; i < 8; i++) t += red[i * 64 + tid];
          asm volatile("st.relaxed.gpu.global.u32 [%0],%1;" ::"l"((unsigned*)g_modp + (b >> 5) * 2048 + (b & 31) * 64 + tid), "r"(U_(t) | 1u) : "memory");
        }
#pragma unroll
        for (int i = 0; i < 8; i++) m0[i >> 2][i & 3] = mr[i * 2] | ((uint32_t)mr[i * 2 + 1] << 16);
      } else {
        asm volatile("griddepcontrol.launch_dependents;");
      }
      x_fetch();
      const uint32_t md = sb + PRE + 6144, rx = mapa(sb, a ^ !spare);
      asm volatile("barrier.cluster.wait.aligned;" ::: "memory");
      if (!spare) {
        mbar_wait(sb + BARS + 88, 0);
#pragma unroll
        for (int i = 0; i < 16; i++) ldsm4t(wQ[i], (frag ^ QSW) + WO + wg * 32768 + i * 2048);
      }
      PT(4);
#pragma unroll 1
      for (int it = 0;; it++) {
        if (tid == 0) mbar_expect(sb + BARS + 104, 512);
        float c[4][4] = {{0, 0, 0, 0}, {0, 0, 0, 0}, {0, 0, 0, 0}, {0, 0, 0, 0}};
#pragma unroll
        for (int i = 0; i < 16; i++) {
          mma16(c[(i & 1) * 2], xr[i].x, 0x3f803f80u, xr[i].y, 0x3f803f80u, xr[i].x, xr[i].y);
          mma16(c[(i & 1) * 2 + 1], xr[i].z, 0x3f803f80u, xr[i].w, 0x3f803f80u, xr[i].z, xr[i].w);
        }
#pragma unroll
        for (int e = 0; e < 4; e++) c[0][e] = (c[0][e] + c[1][e]) + (c[2][e] + c[3][e]);
        const int src = (lane & 28) + (lane >> 3);
        const float sq = __shfl_sync(~0u, (lane & 4) ? c[0][1] : c[0][0], src), sm = __shfl_sync(~0u, (lane & 4) ? c[0][3] : c[0][2], src);
        if ((lane & 3) < 2) sta1<0>(rx + PRE + 10240 + (wid ^ (spare * 4)) * 64 + (lane >> 2) * 8 + (lane & 1) * 4, U_((lane & 1) ? sm : sq), rx + BARS + 104);
        mbar_wait(sb + BARS + 104, it & 1);
        const float2 ot = lds2f(sb + PRE + 10240 + wid * 64 + (lane >> 2) * 8);
        const float mean = (sm + ot.y) * (1.f / 1024);
        const float rs = rsqrtf(fmaxf((sq + ot.x) * (1.f / 1024) - mean * mean, 0.f) + 1e-5f), nm = -mean * rs;
#define NRM(v) v = pk(fmaf(blo(v), rs, nm), fmaf(bhi(v), rs, nm))
#pragma unroll
        for (int i = 0; i < 16; i++) { NRM(xr[i].x); NRM(xr[i].y); NRM(xr[i].z); NRM(xr[i].w); }
        if (!it) {
          PT(3);
#pragma unroll 1
          for (int i = 0; i < 2; i++) {
            uint4 p[4];
            for (int n = 0;; n++) {
#pragma unroll
              for (int e = 0; e < 4; e++) p[e] = ldg_rlx4(g_modp + e * 512 + i * 256 + tid);
              uint32_t ok = 1;
#pragma unroll
              for (int e = 0; e < 4; e++) ok &= p[e].x & p[e].y & p[e].z & p[e].w;
              if (__all_sync(~0u, ok) || n > SPIN_LIMIT / 16) break;
              __nanosleep(100);
            }
#define MSUM(e) (i + rbf((F_(p[0].e) + F_(p[1].e)) + (F_(p[2].e) + F_(p[3].e))))
            sts2(md + i * 2048 + tid * 8, pk(MSUM(x), MSUM(y)), pk(MSUM(z), MSUM(w)));
          }
          BAR_SYNC(B_F, 256);
          PT(5);
        }
        const int e0 = (iw * 8 + (lane >> 2)) * 8 + ((lane & 3) ^ (lane >> 2));
        uint4* dst = g_h + seg * 4096 + half * 2048;
#pragma unroll
        for (int i = 0; i < 16; i++) {
          const uint32_t ma = md + half * 1024 + (lane & 3) * 16 + i * 64;
          const uint4 sv = lds4(ma), cv = lds4(ma + 2048);
          xr[i] = make_uint4(fmabf(xr[i].x, cv.x, sv.x), fmabf(xr[i].y, cv.y, sv.y), fmabf(xr[i].z, cv.z, sv.z), fmabf(xr[i].w, cv.w, sv.w));
        }
        if (!spare) {
#pragma unroll
          for (int i = 0; i < 16; i++) sts4(sb + WO + wg * 32768 + (e0 ^ ((i & 1) * 4)) * 16 + (i >> 1) * 4096, xr[i].x, xr[i].y, xr[i].z, xr[i].w);
          break;
        }
#pragma unroll
        for (int i = 0; i < 16; i++) dst[(e0 ^ ((i & 1) * 4)) + (i >> 1) * 256] = xr[i];
        seg += 4;
        if (seg < 64) x_fetch();
        FENCE_ASYNC();
        BAR_SYNC(B_F, 256);
        if (tid == 0) red_rlx(g_hf + b - 128);
        if (seg >= 64) break;
      }
      if (spare) { rec_helper(sb, cvec, wmod, w1, b1, t0); return; }
      PH(1); PH(2); PT(6);
    }
    ROLE_REFRESH
    mbar_wait(wbar, 0);
    PT(7);
#pragma unroll
    for (int i = 0; i < 16; i++) ldsm4t(wK[i], (frag ^ QSW) + XB + wg * 32768 + i * 2048);
#pragma unroll
    for (int i = 0; i < NVR; i++) ldsm4t(wV[i], frag + MEM + (wg * NVR + i) * 2048);
    FENCE_ASYNC_SMEM();
    PH(3); PT(8);
    CLUSTER_SYNC();
    PT(9);
#pragma unroll
    for (int i = 0; i < 2; i++) {
      const int k = tid * 2 + i, m = (k >> 3) & 3, r = k & 7;
      sts4(sb + MEM + (k >> 5) * 640 + (r == m ? 512 : m * 128) + r * 16, m0[i][0], m0[i][1], m0[i][2], m0[i][3]);
    }
    if (lane < 8) {
      sts4(sb + ARO + wid * 640 + (lane < 4 ? lane * 144 : 512 + l16), 0x3f803f80, 0x3f803f80, 0x3f803f80, 0x3f803f80);
#pragma unroll
      for (int i = 0; i < 2; i++) sts4(sb + MEM + (wid * 2 + i) * 640 + (lane < 4 ? lane * 144 : 512 + l16), 0x42004200, 0x42004200, 0x42004200, 0x42004200);
    }
#define ownv ((iw >> 1) == a)
#define owner (SWP ? iw >= 2 : ownv)
#define vfin ((wid >> 1) == a)
#define oi (wid & 1)
    frag += wg * NVS * 2048;
    {
      const uint32_t rsb = mapa(sb, owner ? a : a ^ 1);
      const uint32_t pp = rsb + PK + (owner ? 0 : 12288) + (oi * 2048 + wg * 1024) + l16;
      const uint32_t mb = sb + MEM + wg * 5120;
      sts4(L16 + TF + wid * 512, mb + lrow, owner ? L16 + (lane >> 4) * (RK - RQ - 256) + RQ + oi * 1024 + wg * 256 : rsb + RQ + oi * 1024 + 512 + wg * 256 + (l16 >> 2),
           L16 + OB, frag);
      sts4(L16 + TF + 4096 + wid * 512, sb + WO + (wid >> 1) * 16384 + ((lane & 7) + (lane >> 4) * 8) * 128 + ((((wid & 1) * 4 + ((lane >> 3) & 1)) ^ (lane & 7)) << 4),
           sb + ARO + wid * 640 + lrow, pp, LO(xc) + h * 262144 + (bb * 2 + (iw >> 1)) * XC + X_VM(0) + oi * 2048 + a * 256 + (l16 >> 1));
    }
    uint32_t tp = L16 + TF + wid * 512;
    auto park_ptr = [&]() { return lds1(tp + 4096 + 8); };
    auto park = [&](const float* f, int m, int n, uint32_t d) {
      uint32_t w[8];
#pragma unroll
      for (int i = 0; i < 8; i++) w[i] = pk(f[2 * i], f[2 * i + 1]);
      if (SWP && m == 2) d += (sb & 0x1000000) ? 0 : owner ? 0x1003000 : -0x1003000;
      if (m == 2 ? ownv : owner) {
        sts4(d + m * 4096, w[0], w[1], w[2], w[3]); sts4(d + m * 4096 + 512, w[4], w[5], w[6], w[7]);
      } else {
        const uint32_t pb = (d & 0xff000000u) | (1024 + BARS + (m ? 24 + m * 8 : 16));
        sta4(d + m * 4096, w, pb); sta4(d + m * 4096 + 512, w + 4, pb);
      }
    };
#define D64(lo) (0x4000004000000000ull | (uint32_t)(lo))
#define XD(i) D64(x | (((i) >> 2) * 256 + ((i) & 3) * 2))
    auto xdesc = [&](uint32_t xb) { return ((uint32_t)__shfl_sync(~0u, 1024 + xb + wg * 16384, 0) >> 4) | 0x10000u; };
    auto rs_issue = [&](float* acc, const uint32_t (&w)[16][4], uint32_t xb, bool fence) {
      const uint32_t x = xdesc(xb);
      if (fence) WG_FENCE();
      wgmma_rs_n32_z(acc, w[0], XD(0));
#pragma unroll
      for (int i = 1; i < 16; i++) wgmma_rs_n32(acc, w[i], XD(i), 1);
      WG_COMMIT();
    };
    auto v_issue = [&](float* acc, uint32_t xb, bool fence) {
      const uint32_t dv = ((uint32_t)__shfl_sync(~0u, 1024 + WVS + wg * NVS * 2048, 0) >> 4) | 0x10000u, x = xdesc(xb);
      if (fence) WG_FENCE();
      wgmma_rs_n32_z(acc, wV[0], XD(0));
#pragma unroll
      for (int i = 1; i < VRF; i++) wgmma_rs_n32(acc, wV[i], XD(i), 1);
#pragma unroll
      for (int i = NVR; i < 16; i++) wgmma_ssT_n32(acc, D64(dv + (i - NVR) * 128), XD(i), 1);
#pragma unroll
      for (int i = VRF; i < NVR; i++) wgmma_rs_n32(acc, wV[i], XD(i), 1);
      WG_COMMIT();
    };
    uint32_t mA;
    auto vk_pass = [&](int n, uint32_t d, uint32_t xb, bool steady) {
      float acc[16], acc2[16];
      v_issue(acc, xb, true);
      rs_issue(acc2, wK, xb, false);
      if (steady || n) mbar_wait(sb + BARS + 80, (n - 1) & 1);
      WG_WAIT(1);
      park(acc, 2 - !!KVO, n, d);
      mA = lds1(tp); if (NF) frag = lds1(tp + 12);
      if (steady) BAR_ARRIVE(B_K, 320);
      WG_WAIT(0);
      park(acc2, 1 + !!KVO, n, d);
    };
    PT(10);
#pragma unroll 1
    for (int n = 0; n < 2; n++) {
      float acc[16];
      asm volatile("" : "+r"(wid));
      rs_issue(acc, wQ, n * XB, true);
      if (n) {
        BAR_SYNC(B_C, 320);
        PT(12);
        mbar_wait(sb + BARS + 24, 0);
      } else {
#pragma unroll
        for (int i = 0; i < 8; i++) {
          const uint4 v = lds4(L16 + WO + 32768 + wid * 4096 + i * 512);
          sts4(L16 + XB + wid * 4096 + i * 512, v.x, v.y, v.z, v.w);
        }
      }
      WG_WAIT(0); park(acc, 0, n, park_ptr());
      FENCE_ASYNC_SMEM();
      vk_pass(n, park_ptr(), n * XB, false);
      if (n) break;
      PT(11);
      BAR_SYNC(B_C, 320);
      if (tid == 0) {
        mbar_expect(obar, 65536);
#pragma unroll 1
        for (int i = 0; i < 4; i++) tma2d(sb + WO + i * 16384, &mp.wo, j * 256 + i * 64, h * 128, obar);
      }
    }
    static_assert(WO == 0, "x");
    {
      BAR_ARRIVE(B_P, N_P); if (!HX) BAR_ARRIVE(B_X, 320); if (XE != 1) BAR_ARRIVE(B_Q, 288);
    }
    PT(13);
    mbar_wait(obar, 0);
    PH(4); PT(14);
    ROLE_REFRESH
    for (int s = 0; s < 64; s++) {
      asm volatile("" : "+r"(tp), "+r"(wid));
      asm volatile("mov.u32 %0,%%cluster_ctarank;" : "=r"(b));
      uint32_t vS[NVS][4], bf[8][4];
      static_assert(NVR == 5, "schedule");
#define VLD(k) ldsm4t(vS[(k) - NVR], frag + WVS + ((k) - NVR) * 2048)
#define BLD(t) ldsm4t(bf[t], mA + (t) * 640)
#define VMMA(c, w, i) mma16(c, (w)[0], (w)[1], (w)[2], (w)[3], bf[(i) >> 1][((i) & 1) * 2], bf[(i) >> 1][((i) & 1) * 2 + 1])
#define VS_(c, k) VMMA(c, vS[(k) - NVR], k)
#define QK(i) VMMA(cQ, wQ[i], i); VMMA(cK, wK[i], i)
#define PREV if (NF) { VLD(13); VLD(12); if (NF > 2) VLD(11); } else { VLD(15); VLD(14); }
      if (NF) { VLD(15); VLD(14); }
      if (s > 0) BAR_SYNC(B_R, N_R);
      float cV[4] = {0, 0, 0, 0}, cW[4] = {0, 0, 0, 0};
      {
        float cQ[4] = {0, 0, 0, 0}, cK[4] = {0, 0, 0, 0};
        BLD(7); BLD(6); BLD(5); BLD(4); if (NB0 > 4) BLD(3);
        SCHED_FENCE(47);
        QK(15); if (NF) VS_(cV, 15);
        QK(14); if (NF) VS_(cV, 14);
        QK(13); QK(12);
        SCHED_FENCE(51);
        if (NB0 < 5) BLD(3);
        BLD(2); BLD(1); BLD(0);
        const uint32_t rm = lds1(tp + 4);
        if (!NF) frag = lds1(tp + 12);
        QK(11); QK(10); QK(9); QK(8); QK(7);
        if (PV0 == 6) { SCHED_FENCE(48); PREV }
        QK(6); QK(5);
        if (PV0 == 4) { QK(4); SCHED_FENCE(48); PREV } else { QK(4); }
        QK(3); QK(2); QK(1); QK(0);
        const uint32_t w0 = pk(cQ[0] * SCS, cQ[1] * SCS), w1 = pk(cQ[2] * SCS, cQ[3] * SCS), w2 = pk(cK[0], cK[1]), w3 = pk(cK[2], cK[3]);
        if (owner) {
          stsm4(rm, w0, w1, w2, w3);
          BAR_ARRIVE(B_E, 256);
        } else {
          const uint32_t mm = (rm & 0xff000000u) | (1024 + BARS);
          sta1<0>(rm, w0, mm); sta1<128>(rm, w1, mm);
          sta1<RK - RQ>(rm, w2, mm); sta1<RK - RQ + 128>(rm, w3, mm);
        }
        if (wid == 2) TS(0);
      }
      uint4 t1;
      uint32_t oA, wo[16][4];
      {
        if (NF == 0) {
          VLD(13); VLD(12);
          VS_(cW, 15); VS_(cV, 14); VLD(11); VMMA(cW, wV[0], 0); VLD(10); VMMA(cV, wV[1], 1); VLD(9);
          VMMA(cW, wV[2], 2); VLD(8); VMMA(cV, wV[3], 3); VLD(7); VMMA(cW, wV[4], 4); VS_(cV, 13); VLD(6); VS_(cW, 12); VLD(5);
          VS_(cV, 11);
        } else {
          if (NF < 3) VLD(11);
          VLD(10);
          VS_(cW, 13); VLD(9); VS_(cV, 12); VLD(8); VLD(7); VMMA(cW, wV[0], 0); VMMA(cV, wV[1], 1); VLD(6);
          VMMA(cW, wV[2], 2); VMMA(cV, wV[3], 3); VLD(5); VMMA(cW, wV[4], 4); VS_(cV, 11);
        }
        VS_(cW, 10); VS_(cV, 9); VS_(cW, 8); VS_(cV, 7); VS_(cW, 6); VS_(cV, 5);
#pragma unroll
        for (int e = 0; e < 4; e++) cV[e] += cW[e];
        const uint32_t ex = tp + (RX - TF) - wg * 2048;
        t1 = lds4(tp + 4096 + (T1L ? vS[3][0] & dZ : 0));
        oA = lds1(tp + 8 + (s & dZ));
        if (wg) {
          sts4(ex, U_(cV[0]), U_(cV[1]), U_(cV[2]), U_(cV[3]));
          BAR_ARRIVE(B_T2, 256);
        }
#pragma unroll
        for (int i = 0; i < VCO; i++) ldsm4t(wo[i], (t1.x ^ ((i & 1) * 32)) + (i >> 1) * 2048);
        if (!wg) {
          BAR_SYNC(B_T2, 256);
          const float4 u = lds4f(ex);
          stg_b64(mkp(t1.w ^ ((s & 1) * X_RING), HI(xc)), (pk(cV[0] + u.x, cV[1] + u.y) & ~1u) | (((s >> 1) + 1) & 1), pk(cV[2] + u.z, cV[3] + u.w));
        }
      }
      if (s == 63) break;
      {
        const uint32_t woA = t1.x, woB = woA ^ 32;
#pragma unroll
        for (int i = VCO; i < NW0; i++) ldsm4t(wo[i], ((i & 1) ? woB : woA) + (i >= WCH ? wo[(i - WCH + NWP) % NWP][0] & dZ : 0) + (i >> 1) * 2048);
        BAR_SYNC(B_S, 416);
        if (s < 62) {
          float acc[16];
          rs_issue(acc, wQ, XB, true);
          mbar_wait(sb + BARS + 24, (s + 1) & 1);
          WG_WAIT(0);
          if (PKE) park(acc, 0, s + 2, t1.z);
#pragma unroll
          for (int i = NW0; i < (PKE ? NWP : NW1); i++) ldsm4t(wo[i], ((i & 1) ? woB : woA) + (i >> 1) * 2048);
          BAR_SYNC(B_V, N_V);
          if (!PKE) park(acc, 0, s + 2, t1.z);
        } else {
#pragma unroll
          for (int i = NW0; i < (PKE ? NWP : NW1); i++) ldsm4t(wo[i], ((i & 1) ? woB : woA) + (i >> 1) * 2048);
          BAR_SYNC(B_V, N_V);
        }
#pragma unroll
        for (int i = PKE ? NWP : NW1; i < NWP; i++) ldsm4t(wo[i], ((i & 1) ? woB : woA) + (i >> 1) * 2048);
        float inv0, inv1;
        {
          uint32_t p[4], pm;
          const uint32_t pa = oA + (SC - OB), one = 0x3f803f80u;
          float sum[4] = {0, 0, 0, 0}, su2[4] = {0, 0, 0, 0};
          ldsm4t(p, pa);
          asm volatile("ldmatrix.sync.aligned.m8n8.x1.trans.shared.b16 {%0},[%1];" : "=r"(pm) : "r"(pa + 512) : "memory");
          mma16(sum, one, one, one, one, p[0], p[1]);
          mma16(su2, one, one, one, one, p[2], p[3]);
          mma8(sum, one, one, pm);
          inv0 = sum[0] + su2[0]; inv1 = sum[1] + su2[1];
          SCHED_FENCE(57);
        }
        BAR_SYNC(B_O, N_O);
        float c[2][4] = {{0, 0, 0, 0}, {0, 0, 0, 0}};
        uint32_t o[4][4];
#pragma unroll
        for (int i = 0; i < NOP_; i++) ldsm4t(o[i], oA + i * 512);
        SCHED_FENCE(46);
        asm("rcp.approx.ftz.f32 %0,%0;" : "+f"(inv0));
        asm("rcp.approx.ftz.f32 %0,%0;" : "+f"(inv1));
#pragma unroll
        for (int i = 0; i < 16; i++) {
          mma16(c[i & 1], wo[i][0], wo[i][1], wo[i][2], wo[i][3], o[i >> 2][i & 2], o[i >> 2][(i & 2) + 1]);
          if (i == 1 && NOP_ < 3) ldsm4t(o[2], oA + 1024);
          if (i == 3 && NOP_ < 4) ldsm4t(o[3], oA + 1536);
          if (i + NWP < 16) ldsm4t(wo[(i + NWP) & 15], (((i + NWP) & 1) ? woB : woA) + ((i + NWP) >> 1) * 2048);
        }
        stsm4(t1.y, pk(c[0][0] * inv0, c[0][1] * inv1), pk(c[0][2] * inv0, c[0][3] * inv1), pk(c[1][0] * inv0, c[1][1] * inv1), pk(c[1][2] * inv0, c[1][3] * inv1));
      }
      const uint32_t d = park_ptr();
      BAR_SYNC(B_W, 384);
      if (s < 62) {
        vk_pass(s + 2, d, XB, true);
        if (XE == 2) BAR_ARRIVE(B_Q, 288);
        BAR_ARRIVE(B_P, N_P); if (!HX) BAR_ARRIVE(B_X, 320);
        TS(10);
      } else {
        mA = lds1(tp); if (NF) frag = lds1(tp + 12);
      }
    }
  } else if (role == 3) {
    asm volatile("setmaxnreg.dec.sync.aligned.u32 24;");
    if (blockIdx.x >= 128) return;
    ROLE_VARS
    const uint32_t L16 = sb + (tid & 31) * 16;
    asm volatile("barrier.cluster.wait.aligned;" ::: "memory");
    CLUSTER_SYNC();
    sts1(sb + PACE + 36, LO(xc) + h * 262144 + X_VM(0));
    auto vm_stage = [&](int s) {
      if (AV) return;
      const uint32_t tag = ((s >> 1) + 1) & 1;
      const char* xm = mkp(lds1(sb + PACE + 36) + (s & 1) * X_RING + iw * XC + (l16 >> 1), HI(xc));
      uint2 m[4];
      CONSUME(LO(xm));
      BAR_SYNC(B_S2, 256);
      if (dZ2 > 1) { const uint32_t c = clk(); while (clk() - c < (uint32_t)dZ2) {} }
      int it = 0;
      while (true) {
#pragma unroll
        for (int i = 0; i < 4; i++) m[i] = ldg_b64(xm + (i >> 1) * 2048 + (i & 1) * 256);
        sts4(L16 + VN + iw * 512, m[0].x, m[0].y, m[1].x, m[1].y);
        sts4(L16 + VN + iw * 512 + 2048, m[2].x, m[2].y, m[3].x, m[3].y);
        if (HV || !anybad(m[0].x, m[1].x, m[2].x, m[3].x, tag)) break;
        RP(2);
        if (++it > SPIN_LIMIT) __trap();
      }
      if (s < 63) BAR_ARRIVE(B_V, 512); else BAR_ARRIVE(B_V, 256);
    };
    if (iw == 0) {
      wait_cnt(&g_hcnt, 128);
#pragma unroll 1
      for (int s = 0; s < 63; s++) {
        if (s < 62) for (int it = 0; ldg_rlx1(g_hf + (s & 3)) <= (s >> 2); it++) if (it > SPIN_LIMIT) __trap();
        if (XE == 1) BAR_SYNC(B_P, N_P); else if (XE == 2) BAR_SYNC(B_Q, 288); else if (s) BAR_SYNC(B_R, 320); else BAR_SYNC(B_Q, 288);
        if (s < 62) { X_LOAD(s + 2, 0, 0); X_LOAD(s + 2, 1, 0); X_LOAD(s + 2, 0, 1); X_LOAD(s + 2, 1, 1); }
        if (s >= 7) {
          const uint32_t zo = b * 160 + l16;
          if (l16 < 160) CONSUME(exch_b128(xc + AR_OFF + AR_ROW(zo >> 7) * 1024 + (zo & 127) + ((s + 1) & 7) * 128, 0, 0, 0, 0).x);
          __syncwarp();
        }
        if (s < 62) { mbar_wait(sb + BARS + 64, s & 1); mbar_wait(sb + BARS + 72, s & 1); }
        BAR_ARRIVE(B_S, 416);
        vm_stage(s);
        if (!AV) BAR_ARRIVE(B_O, 416);
        BAR_SYNC(B_W, 384);
        FENCE_ASYNC_SMEM();
        asm volatile("{.reg .pred p; elect.sync _|p, 0xffffffff; @p cp.reduce.async.bulk.tensor.3d.global.shared::cta.add.bulk_group [%0,{%1,%2,%4}],[%3];}"
                     ::"l"(&mp.ari), "r"((s & 7) * 64), "r"(AR_R(j)), "r"(sb + ARO), "r"(AR_P(j)) : "memory");
        BULK_COMMIT();
        asm volatile("st.relaxed.gpu.global.u32 [%0],%1;" ::"l"(g_tm + (s & 1) * 128 + b), "r"(gtime()) : "memory");
        TS(3);
        BULK_WAIT_READ(0);
      }
      if (!XE) BAR_ARRIVE(B_R, 320);
    } else if (iw == 1) {
      const uint32_t pc = sb + MEM + (lane >> 2) * 640 + (lane & 3) * 144 + (lane & 12), pd = sb + MEM + (lane & 15) * 640 + 576 + (lane & 3) * 16 + (lane & 12);
      uint32_t T = 0, par = 0;
      int est = dA;
#pragma unroll 1
      for (int s = 0; s < 63; s++) {
        if (s) {
          const uint4 tm = ldg_rlx4((const char*)g_tm + ((s + 1) & 1) * 512 + l16);
          const int t0 = tm.x - T, t1 = tm.y - T, t2 = tm.z - T, t3 = tm.w - T;
          const int e = max(dF + (__reduce_add_sync(~0u, (t0 + t1) + (t2 + t3)) >> 7), dV + __reduce_max_sync(~0u, max(max(t0, t1), max(t2, t3))));
          if (s > 1) est += max(min(e >> 2, dP), -dP);
          T += (s == 1 || e > dM ? e : 0) + est;
        }
        vm_stage(s);
        BAR_SYNC(B_W, 384);
        SCHED_FENCE(70);
        const uint32_t tW = gtime();
        if (s == 0) T = tW + 800;
        const uint32_t te = tW + min(max((int)(T - tW), dD), 2000);
        while ((int)(gtime() - te) < 0) {}
        TS(7);
        int it = 0;
        while (true) {
          ar_fetch(sb + MEM, &mp.ari, s & 7, a, sb + BARS + 112);
          mbar_wait(sb + BARS + 112, par);
          par ^= 1;
          const uint32_t n0 = lds1(pc), n1 = lds1(pc + 5120), n2 = lds1(pd);
          if (!__any_sync(~0u, (tagbad(n0, n1, 0x42004200) | (n2 ^ 0x42004200)) != 0)) break;
          RP(0);
          if (++it > SPIN_LIMIT) __trap();
        }
        BAR_ARRIVE(B_R, N_R);
        TS(11);
      }
    } else {
#define V_LOAD(n) do { if (lane == 0) mbar_expect(sb + BARS + 8, 8192); __syncwarp(); \
        if (lane < 16) bulk_ld(sb + ((lane & 2) ? VX1 : VX0) + (lane & 1) * 2048 + (lane >> 2) * 512, \
                               xc + h * 262144 + V_RING(n) + (lane >> 2) * XC + X_VX(lane & 3), 512, sb + BARS + 8); __syncwarp(); } while (0)
      uint32_t src = L16 + PK + (iw & 1) * 2048;
#define qd (L16 + (lane >> 4) * 256 + QT + (iw & 1) * 1024)
#define vd (LO(xc) + h * 262144 + j * XC + (iw & 1) * 2048 + l16)
#define FINISH [&](int n, int m) { \
_Pragma("unroll") \
        for (int i = 1; i >= 0; i--) { \
          const uint32_t p = src + m * 4096 + i * 512; \
          uint4 u = lds4(p); \
          const uint4 w = lds4(p + 1024), y = lds4(p + 12288), z = lds4(p + 13312); \
          u = make_uint4(sum4bf(u.x, w.x, y.x, z.x), sum4bf(u.y, w.y, y.y, z.y), sum4bf(u.z, w.z, y.z, z.z), sum4bf(u.w, w.w, y.w, z.w)); \
          if (m == 2) stg_b128(mkp(vd ^ V_RING(n), HI(xc)) + i * 512, (u.x & ~1u) | V_TAG(n), u.y, u.z, u.w); \
          else stsm4(qd + (n & 1) * 4096 + m * 2048 + i * 256, u.x, u.z, u.y, u.w); \
          SCHED_FENCE(71 + m * 2 + i); \
        } \
      }
#pragma unroll 1
      for (int n = 0; n < 64; n++) {
        src = PIN(src);
        b = __shfl_sync(~0u, lds1(sb + PACE + 24), 0);
        const uint32_t L16 = src - PK - (iw & 1) * 2048;
        auto finish = FINISH;
        if (n < 2) { if (n) BAR_SYNC(B_X, 320); else BAR_SYNC(B_C, 320); }
        mbar_wait(sb + BARS + 16, n & 1);
        finish(n, 0);
        __syncwarp();
        if (lane == 0) mbar_arrive_cl(mapa(sb, a ^ 1) + BARS + 24);
        if (n > 1) BAR_SYNC(B_K, 320);
        mbar_wait(sb + BARS + (KVO ? 32 : 40), n & 1);
        finish(n, 2 - !!KVO);
        if (n > 1) BAR_SYNC(B_X, 320);
        mbar_wait(sb + BARS + (KVO ? 40 : 32), n & 1);
        finish(n, 1 + !!KVO);
        BAR_SYNC(B_T, 64);
        if (lane == 0) {
          if (iw == 2 && n < 63) { mbar_expect(sb + BARS + 16, 4096); mbar_expect(sb + BARS + 32, 4096); mbar_expect(sb + BARS + 40, 4096); }
          mbar_arrive_cl(mapa(sb, a ^ 1) + BARS + 80);
        }
        __syncwarp();
        if (n) {
          vm_stage(n - 1);
          BAR_SYNC(B_W, 384);
        } else {
          BAR_SYNC(B_C, 320);
        }
        if (iw == 2) V_LOAD(n);
      }
#undef qd
#undef vd
    }
    { ROLE_REFRESH }
    vm_stage(63);
  } else {
    asm volatile("setmaxnreg.dec.sync.aligned.u32 %0;" ::"n"(RA_));
    if (blockIdx.x >= 128) { if (threadIdx.x == 256) rec_prefetch((const char*)wmod, w1, (const char*)x, wo); return; }
    ROLE_VARS
    uint32_t L16 = __shfl_sync(~0u, sb + (tid & 31) * 16, tid & 31);
    if (wid == 9) {
      for (int i = b * 80 + (tid & 31); i < b * 80 + 80; i += 32) ((uint4*)(xc + AR_OFF))[AR_ROW(i >> 6) * 64 + (i & 63)] = make_uint4(0, 0, 0, 0);
      if (b == 0) g_fin = 0;
      FENCE_ASYNC();
      __syncwarp();
      if (tid == 288) red_rlx(&g_hcnt);
    }
    if (tid == 256) {
      const int col = h * 128 + bb * 64;
#pragma unroll 1
      for (int c = 0; c < 12 + WIN; c++) {
        const uint32_t mb = sb + PACE + (c % WIN) * 8;
        if (c >= WIN) mbar_wait(mb, (c / WIN - 1) & 1);
        PT(16 + c);
        if (c == 3 + WIN) asm volatile("mbarrier.arrive.shared.b64 _,[%0];" ::"r"(sb + BARS + 88) : "memory");
        if (c >= 12) continue;
        mbar_expect(mb, 16384);
        if (c < 8) tma2d(sb + (c >> 2) * XB + (c & 3) * 16384, (c & 4) ? &mp.wk : &mp.wq, col, a * 512 + (c & 3) * 128, mb);
        else
#pragma unroll 1
          for (int i = (c & 1) * 8; i < (c & 1) * 8 + 8; i++) {
            const int w = (c - 8) >> 1;
            tma2d(i < NVR ? sb + MEM + (w * NVR + i) * 2048 : sb + WVS + (w * NVS + i - NVR) * 2048, &mp.wv, col, a * 512 + w * 256 + i * 16, mb);
          }
      }
      asm volatile("mbarrier.arrive.shared.b64 _,[%0];" ::"r"(wbar) : "memory");
      for (int c = 0; c < 4; c++) tma2d_pf(&mp.wo, j * 256 + c * 64, h * 128);
      for (int i = 0; i < 3; i++) asm volatile("mbarrier.inval.shared.b64 [%0];" ::"r"(sb + PACE + i * 8) : "memory");
    }
    __syncwarp();
    asm volatile("barrier.cluster.wait.aligned;" ::: "memory");
    CLUSTER_SYNC();
#define pr (L16 + SC)
    {
      const int lim = j * 8 + iw * 2 - (lane & 7) - (lane & 8) * 2;
      const bool mk = L16 & 256;
      const int rw = lane >> 2;
      sts4(L16 + TA + iw * 512,
           iw != 2 ? L16 + KT + (iw & 1) * 256 + (lane >> 4) * 256 : sb + RK + (L16 & 0x80) * 2 + ((L16 >> 1) & 0x80) + (L16 & 0x70),
           L16 + QT + (lane >> 3) * 384, sb + SC + min(lane >> 3, 2) * 256 + (L16 & 0x70) + iw * 4, L16 + (lane >> 4) * 256 + QT + (iw >> 1) * 1024 + (iw & 1) * 256);
      sts4(L16 + TA + 2048 + iw * 512, mk ? 0u : (lim < 0 ? 0xfc00u : 0u) | (lim < -1 ? 0xfc000000u : 0u),
           mk ? 0xfc00fc00u : (lim < 8 ? 0xfc00u : 0u) | (lim < 7 ? 0xfc000000u : 0u),
           ((h * 2 + (iw >> 1)) * 1024 + (j * 8 + rw) * 8 + (((iw & 1) * 4 + (lane & 3)) ^ rw)) * 16, sb + OT + iw * 512 + (L16 & 0x70) * 4 + ((L16 >> 3) & 0x30));
    }
    {
      const uint32_t xh = LO(xc) + h * 262144, xs = xh + X_SC + iw * 1024 + min(lane, 16 + (lane & 7)) * 8;
      sts4(L16 + TA + 4096 + iw * 512, xh + X_SC + j * 256 + iw * 64 + lpub, xs, dS, iw != 2 ? 0 : U_(SCS));
      sts1(L16 + TA + 12 + iw * 512, xs + X_TOK + j * 4096);
    }
    uint32_t tA = L16 + TA + iw * 512;
#define tw (tA - L16 != TA + 1024)
#define XP_(lo) mkp(lo, HI(xc))
    auto publish = [&](char* d, const uint2& w) { stg_b64(d, w.x, w.y); };
    BAR_SYNC(B_P, N_P);
    for (int s = 0; s < 64; s++) {
      asm volatile("" : "+r"(L16), "+r"(tA));
      const uint32_t tag = ((s >> 1) + 1) & 1, ring = (s & 1) * X_RING;
      const uint4 t0 = lds4(tA);
      const uint4 tx = lds4(tA + 4096);
      const uint32_t xo = tx.x ^ ring, xs = tx.y ^ ring;
      const float gm = F_(tx.w);
      const uint32_t qA = t0.y + (ring >> 5);
      uint32_t c0;
      uint2 ts[4];
      uint4 v[4];
      uint32_t af[2][4], qt[4][4];
      {
        const uint32_t aA = t0.x + (tw ? ring >> 5 : 0);
        uint32_t ql[2][4], qr[2][4];
        uint2 pw_;
        float c[4] = {0, 0, 0, 0}, d[4] = {0, 0, 0, 0};
        if (s == PDS) asm volatile("griddepcontrol.launch_dependents;");
#pragma unroll
        for (int i = 0; i < 4; i++) ldsm4t(qt[i], qA + i * 128);
        mbar_wait(sb + BARS + 8, s & 1);
        TS(4);
        BAR_SYNC(B_E, 256);
#define PACK(c) make_uint2(pkh(fmaf(c[2], gm, c[0] * SCS), fmaf(c[3], gm, c[1] * SCS), tag), pkh(c[2] * SCS, c[3] * SCS, tag))
#define SMMA(x, t, q, i) mma16(x, af[t][0], af[t][1], af[t][2], af[t][3], q[t][i], q[t][i + 1])
        ldsm4t(ql[0], L16 + RQ); ldsm4t(ql[1], L16 + RQ + 1024); ldsm4t(af[0], aA); ldsm4t(af[1], aA + 1024);
        CONSUME(xo);
#define QSUM(t, i) addbf(addbf(ql[t][i], ql[t][i + 2]), addbf(qr[t][i], qr[t][i + 2]))
#define STAIL mma16(c, af[0][0], af[0][1], af[0][2], af[0][3], QSUM(0, 0), QSUM(0, 1)); mma16(d, af[1][0], af[1][1], af[1][2], af[1][3], QSUM(1, 0), QSUM(1, 1));
        if (tw) {
          mbar_wait(sb + BARS, s & 1);
          TS(8);
          ldsm4t(qr[0], L16 + RQ + 512); ldsm4t(qr[1], L16 + RQ + 1536);
          STAIL
          pw_ = make_uint2(pkh(c[0] + d[0], c[1] + d[1], tag), pkh(c[2] + d[2], c[3] + d[3], tag));
        } else {
          uint32_t ar[2][4];
          mbar_wait(sb + BARS, s & 1);
          ldsm4t(qr[0], L16 + RQ + 512); ldsm4t(ar[0], aA + 512); ldsm4t(qr[1], L16 + RQ + 1536); ldsm4t(ar[1], aA + 1536);
#pragma unroll
          for (int i = 0; i < 8; i++) af[i >> 2][i & 3] = addbf(af[i >> 2][i & 3], ar[i >> 2][i & 3]);
          STAIL
          pw_.x = pw_.y = pkh((c[0] + c[2]) + (d[0] + d[2]), (c[1] + c[3]) + (d[1] + d[3]), tag);
        }
        publish(XP_(xo), pw_);
        c0 = clk() + tx.z;
        TS(1);
      }
      uint2 r[4];
      bool vbad;
      uint32_t xm;
      uint4 vn[2];
#define TOKS(i) { float e0[4] = {0, 0, 0, 0}, e1[4] = {0, 0, 0, 0}; \
        mma16(e0, af[0][0], af[0][1], af[0][2], af[0][3], qt[i][0], qt[i][1]); mma16(e1, af[0][0], af[0][1], af[0][2], af[0][3], qt[i + 1][0], qt[i + 1][1]); \
        mma16(e0, af[1][0], af[1][1], af[1][2], af[1][3], qt[i][2], qt[i][3]); mma16(e1, af[1][0], af[1][1], af[1][2], af[1][3], qt[i + 1][2], qt[i + 1][3]); \
        ts[i] = PACK(e0); ts[i + 1] = PACK(e1); }
      {
        float e[4][4];
#pragma unroll
        for (int i = 0; i < 4; i++) {
          e[i][0] = e[i][1] = e[i][2] = e[i][3] = 0.f;
          mma16(e[i], af[0][0], af[0][1], af[0][2], af[0][3], qt[i][0], qt[i][1]);
        }
#pragma unroll
        for (int i = 0; i < 4; i++) mma16(e[i], af[1][0], af[1][1], af[1][2], af[1][3], qt[i][2], qt[i][3]);
        SCHED_FENCE(55);
        if (s < 63) BAR_ARRIVE(B_S, 416);
        SCHED_FENCE(58);
        v[0] = lds4(tA + (VX0 - TA)); v[1] = lds4(tA + (VX0 - TA) + 2048); v[2] = lds4(tA + (VX1 - TA)); v[3] = lds4(tA + (VX1 - TA) + 2048);
#pragma unroll
        for (int i = 0; i < 4; i++) ts[i] = PACK(e[i]);
        vbad = anybad(v[0].x, v[1].x, v[2].x, v[3].x, V_TAG(s));
        if (AV) { xm = (xs & ~0x1ffffu) + X_VM(0) + ((tA - L16 - TA) << 5) + (l16 >> 1); CONSUME(xm); }
        while ((int)(clk() - c0) < 0) {}
        TS(5);
#pragma unroll
        for (int u = 0; u < 4; u++) r[u] = ldg_b64(XP_(xs) + u * 256);
        if (!AV) BAR_ARRIVE(B_S2, 256);
      }
      SCHED_FENCE(56);
      uint32_t kk;
      float4 e = softmax2<false>(r, 0, 0, kk);
      if (AV) {
        const char* pm_ = XP_(xm + (kk & dZ));
#pragma unroll
        for (int u = 0; u < 2; u++) { const uint2 m0 = ldg_b64(pm_ + u * 2048), m1 = ldg_b64(pm_ + u * 2048 + 256); vn[u] = make_uint4(m0.x, m0.y, m1.x, m1.y); }
      }
      if (__builtin_expect(anybad(r[0].x, r[0].y, r[1].x, r[1].y, r[2].x, r[2].y, r[3].x, r[3].y, tag ^ (kk & dZ)), 0)) {
        int it = 0;
        if (s > 8) sts1(tA + 4096 + 8, min(lds1(tA + 4096 + 8) + dX, 500));
        do {
          RP(1);
          if (++it > SPIN_LIMIT) __trap();
#pragma unroll
          for (int u = 0; u < 4; u++) r[u] = ldg_b64(XP_(xs) + u * 256);
        } while (BADS(r));
        e = softmax2<false>(r, 0, 0, kk);
      }
      sts1(t0.z, pk(e.x, e.y)); sts1(t0.z + 128, pk(e.z, e.w));
#pragma unroll
      for (int i = 0; i < 4; i++) publish(XP_(xo) + X_TOK + i * 4096, ts[i]);
      TS(6);
      if (s < 63) BAR_SYNC(B_V, N_V); else BAR_SYNC(B_V, N_V - 256);
      uint32_t O[4];
      {
        uint32_t p[4], pm;
        ldsm4t(p, pr);
        asm volatile("ldmatrix.sync.aligned.m8n8.x1.trans.shared.b16 {%0},[%1];" : "=r"(pm) : "r"(pr + 512) : "memory");
        if (!AV) { vn[0] = lds4(tA + (VN - TA)); vn[1] = lds4(tA + (VN - TA) + 2048); }
        pv_mem(p, pm, v, vn, O);
        if (__builtin_expect(vbad || ((HV || AV) && anybad(vn[0].x, vn[0].z, vn[1].x, vn[1].z, tag)), 0)) {
          int it = 0;
          const uint32_t xv = LO(xc) + (lds1(sb + PACE + 24) >> 2) * 262144 + ((tA - L16 - TA) >> 9) * XC;
          do {
            RP(2);
            if (++it > SPIN_LIMIT) __trap();
#pragma unroll
            for (int u = 0; u < 4; u++) v[u] = ldg_b128(XP_((xv + l16) ^ V_RING(s)) + X_VX(u));
#pragma unroll
            for (int u = 0; u < 2; u++) {
              const uint2 m0 = ldg_b64(XP_((xv + (l16 >> 1)) ^ ring) + X_VM(0) + u * 2048), m1 = ldg_b64(XP_((xv + (l16 >> 1)) ^ ring) + X_VM(0) + u * 2048 + 256);
              vn[u] = make_uint4(m0.x, m0.y, m1.x, m1.y);
            }
          } while (anybad(v[0].x, v[1].x, v[2].x, v[3].x, V_TAG(s)) || anybad(vn[0].x, vn[0].z, vn[1].x, vn[1].z, tag));
          pv_mem(p, pm, v, vn, O);
        }
      }
      stsm4(tA + (OB - TA), O[0], O[1], O[2], O[3]);
      if (s < 63) BAR_ARRIVE(B_O, N_O);
      TS(2);
      c0 = clk() + dG;
      SCHED_FENCE(60);
      if (tA == sb + TA) mbar_expect(sb + BARS, 2048);
      const uint32_t vs[4] = {addbf(vn[0].x, vn[0].z), addbf(vn[0].y, vn[0].w), addbf(vn[1].x, vn[1].z), addbf(vn[1].y, vn[1].w)};
      {
        const char* xt = XP_(lds1(tA + 12) ^ ring);
        const uint2 t1 = lds2u(tA + 2048);
        const uint32_t pw = lds1(tA + 8);
        uint2 rt[4];
        CONSUME(LO(xt) ^ t1.x ^ pw);
        while ((int)(clk() - c0) < 0) {}
        int it = 0;
        do {
          if (++it > SPIN_LIMIT) __trap();
#pragma unroll
          for (int u = 0; u < 4; u++) rt[u] = ldg_b64(xt + u * 256);
        } while (BADS(rt));
        uint32_t kt;
        const float4 et = softmax2<true>(rt, t1.x, t1.y, kt);
        sts1(pw + 1024, pk(et.x, et.y)); sts1(pw + 1024 + 128, pk(et.z, et.w));
      }
      s = PIN(s);
      BAR_SYNC(B_SC, 128);
      {
        uint32_t Ot[4], p[4], pm;
        const uint2 t2 = lds2u(tA + 2048 + 8);
        ldsm4t(p, pr + 1024);
        asm volatile("ldmatrix.sync.aligned.m8n8.x1.trans.shared.b16 {%0},[%1];" : "=r"(pm) : "r"(pr + 1024 + 512) : "memory");
        char* od = (char*)g_O + ((s >> 2) * 1048576 + (s & 3) * 4096) + t2.x;
        CONSUME(LO(od) ^ HI(od) ^ pm ^ p[3]);
        TS(9);
        if (s < 62) BAR_SYNC(B_P, N_P);
        pv_tok(p, pm, v, vs, Ot);
        asm volatile("stmatrix.sync.aligned.m8n8.x4.trans.shared.b16 [%0],{%1,%2,%3,%4};" ::"r"(t2.y), "r"(Ot[0]), "r"(Ot[1]), "r"(Ot[2]), "r"(Ot[3]) : "memory");
        __syncwarp();
        *(uint4*)od = lds4(tA + (OT - TA));
      }
    }
    FENCE_ASYNC();
    BAR_SYNC(B_SC, 128);
    if (tA == sb + TA) red_rlx(&g_fin);
  }
  __syncwarp();
  CLUSTER_SYNC();
  PH(5);
}
#undef wg
#undef iw
#undef h
#undef j
#undef a
#undef bb
#undef oi
#undef owner
#undef ownv
#undef vfin
#undef pr
#undef PIN
#undef XP_
#undef tw
#undef is7
#undef REFRESH
#undef lane
#undef l16
#undef lrow
#undef lar
#undef lpub

namespace ffn {
constexpr uint32_t BR = 98304;
constexpr uint32_t STG = 196608;
constexpr uint32_t PRM = 229376;
constexpr uint32_t BARS = PRM + 2816;
constexpr uint32_t SMEM = BARS + 18 * 8;
}
#define Y_TILE(rb, kt) (((ALIAS & 1) ? g_h : g_h2) + ((rb) * 16 + (kt)) * 1024)
#define U_TILE(rb, kt) ((ALIAS & 2) ? g_O + ((rb) * 64 + (kt)) * 1024 : g_U + ((rb) * 56 + (kt)) * 1024)
struct FfnMaps { CUtensorMap wo, w1a, w1b, w2, x, out; };

template <int N>
__device__ __forceinline__ void wg_ss(float* d, uint64_t a, uint64_t b, int sd) {
  if (N == 128) wgmma_ss_n128(d, a, b, sd);
  if (N == 192) wgmma_ss_n192(d, a, b, sd);
}
template <int N>
__device__ __forceinline__ void acc_fence(float* d) {
#pragma unroll
  for (int i = 0; i < N; i++) asm volatile("" : "+f"(d[i])::"memory");
}
#define UNPK8(d, v) do { (d)[0] = blo(v.x); (d)[1] = bhi(v.x); (d)[2] = blo(v.y); (d)[3] = bhi(v.y); (d)[4] = blo(v.z); (d)[5] = bhi(v.z); (d)[6] = blo(v.w); (d)[7] = bhi(v.w); } while (0)
struct FfnPipe {
  uint32_t full, emp, ph, aoff;
  int st, sB, prev;
  bool leader;
  template <int N>
  __device__ __forceinline__ void issue(float* acc, bool first, uint32_t a = 0) {
    mbar_wait(full + st * 8, ph);
    const uint64_t da = mkdesc((a ? a : 1024 + st * 16384) + aoff, 16, 1024), db = mkdesc(1024 + ffn::BR + sB * (N * 128), 8192, 1024);
    WG_FENCE();
#pragma unroll
    for (int j = 0; j < ((FDB & 1) ? 1 : 4); j++) wg_ss<N>(acc, da + j * 2, db + j * 128, j || !first);
    WG_COMMIT();
    if (++sB == 768 / N) sB = 0;
  }
  __device__ __forceinline__ void release() { if (leader) mbar_arrive(emp + prev * 8); }
  __device__ __forceinline__ void next() { prev = st; if (++st == 6) { st = 0; ph ^= 1; } }
  __device__ __forceinline__ void retire() { WG_WAIT(1); release(); next(); }
};
__device__ __forceinline__ float gelu_h(float hx) {
  float u = hx * fmaf(hx * hx, 8.f * 0.0356774081f, 2.f * 0.7978845608f), t;
  if (FDB & 4) return hx;
  if (FDB & 2) t = u; else
  asm("tanh.approx.f32 %0,%1;" : "=f"(t) : "f"(u));
  return fmaf(hx, t, hx);
}
struct FfnEpi {
  uint32_t st2, cc, flip, staged, l0;
  uint2 c;
  float n0, n1, s0, s1;
  __device__ __forceinline__ void flush(uint32_t r) {
    __syncwarp();
    asm volatile("{.reg .pred p; setp.ne.u32 p,%1,0; @p mbarrier.arrive.shared.b64 _,[%0];}" ::"r"(staged + (flip >> 11)), "r"(l0 & r) : "memory");
    flip ^= r << 14;
  }
  __device__ __forceinline__ void half(const float* d, int J, int r) {
#define PRE(i, n, c1, c2) gelu_h(fmaf(r ? d[4 + i] : d[i], i < 2 ? s0 : s1, fmaf(n, c1, c2)))
    asm volatile("stmatrix.sync.aligned.m8n8.x2.shared.b16 [%0],{%1,%2};" ::"r"((st2 ^ ((J & 3) * 32 + r * 16)) + flip),
                 "r"(pk(PRE(0, n0, blo(c.x), blo(c.y)), PRE(1, n0, bhi(c.x), bhi(c.y)))), "r"(pk(PRE(2, n1, blo(c.x), blo(c.y)), PRE(3, n1, bhi(c.x), bhi(c.y)))) : "memory");
#undef PRE
    if ((J & 3) == 3) flush(r);
    cc += r ? 56 : 8;
    c = lds2u(cc);
  }
};

__global__ void __launch_bounds__(384, 1)
k_ffn(const __grid_constant__ FfnMaps mp, const bf16* __restrict__ b2) {
  using namespace ffn;
  extern __shared__ __align__(1024) char smem[];
  const uint32_t sb = (uint32_t)__cvta_generic_to_shared(smem);
  if (sb != 1024) __trap();
  const int tid = threadIdx.x, lane = tid & 31, wg = __shfl_sync(~0u, tid >> 7, 0);
  const uint32_t full = sb + BARS, emp = full + 48, xbar = full + 96, staged = full + 104, tile = full + 136;
  uint32_t fin = 0;
  if (tid >= 288 && tid < 320) fin = ld_acq(&g_fin);
  if (tid < 32) {
    unsigned sm, v = 0;
    asm("mov.u32 %0,%%smid;" : "=r"(sm));
    if (tid == 0) {
      v = atomicExch(&g_slot[sm & 255], 0);
      for (int i = 0; i < 6; i++) { mbar_init(full + i * 8, 1); mbar_init(emp + i * 8, 2); }
      mbar_init(xbar, 2);
      for (int i = 0; i < 2; i++) { mbar_init(staged + i * 8, 8); mbar_init(staged + 16 + i * 8, 1); }
      FENCE_ASYNC_SMEM();
    }
    v = __shfl_sync(~0u, v, 0);
    if (!v) {
      wait_cnt(&g_fin, 128);
      for (int it = 0; !v; it++) {
        const uint4 a = ldg_rlx4(g_slot + tid * 8), b = ldg_rlx4(g_slot + tid * 8 + 4);
        const uint32_t open = __ballot_sync(~0u, a.x | a.y | a.z | a.w | b.x | b.y | b.z | b.w);
        if (!open) break;
        if (it < 16) { __nanosleep(500); continue; }
        if (tid == __ffs(open) - 1) v = atomicExch(&g_slot[tid * 8 + (a.x ? 0 : a.y ? 1 : a.z ? 2 : a.w ? 3 : b.x ? 4 : b.y ? 5 : b.z ? 6 : 7)], 0);
        v = __shfl_sync(~0u, v, __ffs(open) - 1);
      }
    }
    if (tid == 0) sts1(tile, v);
  }
  if (tid == 256) asm volatile("prefetch.tensormap [%0];" ::"l"(&mp.wo) : "memory");
  __syncthreads();
  const int bid = __shfl_sync(~0u, lds1(tile), 0) - 1;
  if (bid < 0) return;
  PH(6);
  FT(1);
  const int rb = bid >> 3, nb = bid & 7;
  unsigned* cnt = g_cnt + rb * 128;
  if (wg == 2) {
    asm volatile("setmaxnreg.dec.sync.aligned.u32 " FRP ";");
    const int pw = __shfl_sync(~0u, (tid >> 5) & 3, 0);
    uint32_t ws = emp, wp = 1, fs = full;
    auto wait_free = [&]() { mbar_wait_q(ws, wp); ws += 8; if (ws == emp + 48) { ws = emp; wp ^= 1; } };
    auto step = [&]() { fs += 8; if (fs == full + 48) fs = full; };
#define K3(c) ((0x65230 >> (c) * 4) & 7)
#define KC(k) ((k) < 2 ? nb * 2 + (k) : (k) < 9 ? ((k) - 2 + ((k) - 2 >= nb)) * 2 : ((k) - 9 + ((k) - 9 >= nb)) * 2 + 1)
    if (pw == 0) {
      uint32_t d = sb + BR + 32768;
      auto put = [&](const CUtensorMap* m, int k, int c) {
        e_expect_tma3d(d, m, k * 64, c, fs, 32768);
        step();
        d += 16384;
        if (d == sb + STG) d = sb + BR;
      };
      int n = 0;
      auto stage_free = [&]() { if (!(n & 7) && n < 56) mbar_wait_q(staged + 16 + (n & 8), (n >> 4) & 1); n++; };
      FTP(3);
#pragma unroll 1
      for (int k = 0; k < 66; k++) { wait_free(); if (k < 64) put(&mp.wo, k, nb * 2); }
#pragma unroll 1
      for (int k = 0; k < 16; k++) {
        const int kt = KC(k);
        wait_free();
        e_expect_tma3d(sb + BR + (k & 3) * 24576, &mp.w1b, kt * 64, nb * 7, fs, k < 2 ? 24576 : 40960);
        step();
      }
#pragma unroll 1
      for (int k = 0; k < 32; k++) { stage_free(); if (k != 5 && k != 6) wait_free(); put(&mp.w1a, k & 15, nb * 7 + 3 + (k >> 4) * 2); }
#pragma unroll 1
      for (int c = 0; c < 5; c++)
#pragma unroll 1
        for (int k = K3(c), i = 0; k < 56; k += c < 2 && (i ^= 1) ? 1 : c < 2 ? 6 : 7) { stage_free(); wait_free(); put(&mp.w2, k, nb * 2); }
    } else if (pw == 1) {
      FTP(5);
      if (fin < 128) wait_cnt(&g_fin, 128);
      FTP(6);
      uint32_t d = sb;
      auto put = [&](const uint4* A, bool ld) {
        wait_free();
        if (ld) e_bulk_ld(d, A, 16384, fs);
        step();
        d += 16384;
        if (d == sb + BR) d = sb;
      };
      const uint4* A = g_O + rb * 65536;
#pragma unroll 1
      for (int k = 0; k < 66; k++) put(A + k * 1024, k < 64);
      A = Y_TILE(rb, 0);
      uint32_t ready = 0;
#pragma unroll 1
      for (int k = 2; k < 48; k++) {
        const int kt = k < 16 ? KC(k) : k & 15;
        for (int it = 0; !(ready >> ((kt >> 1) + (kt & 1) * 8) & 1); it++) {
          ready = __ballot_sync(~0u, ldg_rlx1(cnt + (lane & 7)) & ((lane & 8) ? 1 : 0x10000));
          if (it > SPIN_LIMIT) __trap();
        }
        if (k == 2) FTP(75);
        put(A + kt * 1024, true);
      }
      A = U_TILE(rb, 0);
#pragma unroll 1
      for (int c = 0; c < 5; c++) {
        for (int it = 0; ldg_rlx1(cnt + 32 + c) < 8; it++) if (it > SPIN_LIMIT) __trap();
#pragma unroll 1
        for (int k = K3(c), i = 0; k < 56; k += c < 2 && (i ^= 1) ? 1 : c < 2 ? 6 : 7) put(A + k * 1024, true);
      }
    } else if (pw == 2) {
      for (int i = 0; i < XDL; i++) {
        mbar_wait_q(emp, i & 1);
        if (XPF && i == 1 && lane < 2) tma2d_pf(&mp.x, nb * 128 + lane * 64, rb * 128);
      }
      if (lane == 0) {
        mbar_expect(xbar, 32768);
        tma2d(sb + STG, &mp.x, nb * 128, rb * 128, xbar);
        tma2d(sb + STG + 16384, &mp.x, nb * 128 + 64, rb * 128, xbar);
      }
      asm volatile("griddepcontrol.wait;" ::: "memory");
      if (lane < 16) g_modp[bid * 16 + lane] = make_uint4(0, 0, 0, 0);
      if (lane >= 16 && bid == 0) { g_hcnt = 0; g_mcnt = 0; g_hf[lane & 3] = 0; }
      if (lane == 0) {
#pragma unroll 1
        for (int g = 1; g < 9; g++) {
          if (g == 1) mbar_wait(staged + 8, 0); else { mbar_wait_q(staged + (g & 1) * 8, (g >> 1) & 1); FENCE_ASYNC_SMEM(); }
          bulk_st(g == 1 ? Y_TILE(rb, nb * 2 + 1) : U_TILE(rb, nb * 7 + ((0x652431000ull >> g * 4) & 7)), sb + STG + (g & 1) * 16384, 16384);
          BULK_COMMIT();
          if (g != 2 && g != 4) { BULK_WAIT(0); red_rlx(g == 1 ? cnt + nb : cnt + 32 + (g < 6 ? g >> 2 : g - 4)); }
          BULK_WAIT_READ(0);
          mbar_arrive(staged + 16 + (g & 1) * 8);
        }
      }
    } else {
      const uint32_t prm = sb + PRM, pp = prm + (lane >> 3) * 64 + (lane & 1) * 32 + (lane & 6) * 2;
      const uint2 v2 = ((const uint2*)(b2 + nb * 128))[lane];
      sts1(pp + 768, v2.x); sts1(pp + 784, v2.y);
      asm volatile("griddepcontrol.wait;" ::: "memory");
      const float4* md = (const float4*)(g_mod + nb * 128) + lane;
      { const float4 ga = md[512]; sts1(pp, pk(ga.x, ga.y)); sts1(pp + 16, pk(ga.z, ga.w)); }
      { const float4 cb = md[1024]; sts1(pp + 256, pk(1.f + cb.x, 1.f + cb.y)); sts1(pp + 272, pk(1.f + cb.z, 1.f + cb.w)); }
      { const float4 gb = md[1280]; sts1(pp + 512, pk(gb.x, gb.y)); sts1(pp + 528, pk(gb.z, gb.w)); }
#pragma unroll 1
      for (int i = lane; i < 112; i += 32) { const uint4 c = g_cc[nb * 112 + i]; sts4(prm + 1024 + i * 16, c.x, c.y, c.z, c.w); }
      __syncwarp();
      if (lane == 0) {
        mbar_arrive(xbar);
        mbar_wait(staged, 0);
        bulk_st(Y_TILE(rb, nb * 2), sb + STG, 16384);
        BULK_COMMIT(); BULK_WAIT(0);
        asm volatile("red.relaxed.gpu.global.add.u32 [%0],0x10000;" ::"l"(cnt + nb) : "memory");
        mbar_arrive(staged + 16);
      }
      __syncwarp();
      mbar_wait_q(staged + 24, 0);
      mbar_wait_q(emp + 40, 0);
#pragma unroll 1
      for (int i = 0; i < 4; i++) {
        const uint4* sp = g_stat + (rb * 128 + i * 32 + lane) * 4;
        uint4 v[4];
        for (int it = 0;; it++) {
          uint32_t m = 0;
#pragma unroll
          for (int u = 0; u < 4; u++) { v[u] = ldg_rlx4(sp + u); m = max(max(m, max(v[u].x, v[u].y)), max(v[u].z, v[u].w)); }
          if (!__any_sync(~0u, m == ~0u)) break;
          if (it > SPIN_LIMIT) __trap();
        }
        float m = 0, q = 0;
#pragma unroll
        for (int u = 0; u < 4; u++) m += F_(v[u].x) + F_(v[u].z);
        m *= 0.125f;
#pragma unroll
        for (int u = 0; u < 4; u++) { const float a = F_(v[u].x) - m, b = F_(v[u].z) - m; q += F_(v[u].y) + F_(v[u].w) + 128.f * (a * a + b * b); }
        const float r = 0.5f * rsqrtf(q * (1.f / 1024) + 1e-5f);
        sts2(sb + STG + 16384 + (i * 32 + lane) * 8, U_(r), U_(-m * r));
      }
      __syncwarp();
      if (lane < 2) mbar_arrive(xbar);
    }
  } else {
    asm volatile("setmaxnreg.inc.sync.aligned.u32 " FRC ";");
    const int w = (tid >> 5) & 3, q = lane & 3;
    const uint32_t prm = sb + PRM + q * 16;
    const int row0 = wg * 64 + w * 16;
    FfnPipe p;
    p.full = full; p.emp = emp; p.ph = 0; p.aoff = wg * 8192; p.st = 0; p.sB = 2; p.prev = 0; p.leader = (tid & 127) == 0;
    FfnEpi e;
    const uint32_t stg = sb + STG + row0 * 128;
    e.st2 = stg + (lane & 15) * 128 + ((lane & 7) << 4);
    e.cc = sb + PRM + 1024 + q * 16; e.flip = 0; e.staged = staged; e.l0 = lane == 0;
    const uint32_t stw = e.st2 ^ (lane & 16);
    uint32_t x1[32];
    uint4* sp = g_stat + (rb * 128 + row0 + (lane >> 2)) * 4;
    float old[96], r0_, r1_;
    {
      float acc[64];
      p.issue<128>(acc, true); FT(8); p.next();
#pragma unroll 1
      for (int k = 1; k < 64; k++) { p.issue<128>(acc, false); FT(8 + k); p.retire(); }
      float xf[64], gf[32];
      uint32_t cb[16];
      mbar_wait(xbar, 0);
#pragma unroll
      for (int j = 0; j < 8; j++) {
        uint32_t xv[4];
        ldsm4(xv, (stw ^ ((j & 3) * 32)) + (j >> 2) * 16384);
#pragma unroll
        for (int i = 0; i < 4; i++) { xf[j * 8 + i * 2] = blo(xv[i]); xf[j * 8 + i * 2 + 1] = bhi(xv[i]); }
      }
#pragma unroll
      for (int i = 0; i < 4; i++) {
        const uint4 g = lds4(prm + i * 64), c = lds4(prm + 256 + i * 64);
        UNPK8(gf + i * 8, g);
        cb[i * 4] = c.x; cb[i * 4 + 1] = c.y; cb[i * 4 + 2] = c.z; cb[i * 4 + 3] = c.w;
      }
      acc_fence<64>(xf); acc_fence<32>(gf);
      WG_WAIT(0);
      p.release();
      acc_fence<64>(acc);
      PH(7); FT(72);
#pragma unroll
      for (int j = 0; j < 8; j++) {
        uint32_t* o = x1 + j * 4;
#pragma unroll
        for (int i = 0; i < 4; i++)
          o[i] = pk(fmaf(acc[j * 8 + i * 2], gf[j * 4 + (i & 2)], xf[j * 8 + i * 2]), fmaf(acc[j * 8 + i * 2 + 1], gf[j * 4 + (i & 2) + 1], xf[j * 8 + i * 2 + 1]));
        stsm4((stw ^ ((j & 3) * 32)) + (j >> 2) * 16384, mulbf(o[0], cb[j * 2]), mulbf(o[1], cb[j * 2]), mulbf(o[2], cb[j * 2 + 1]), mulbf(o[3], cb[j * 2 + 1]));
        if ((j & 3) == 3) { FENCE_ASYNC_SMEM(); e.flush(1); }
      }
      if (wg) BAR_SYNC(2, 128); else BAR_SYNC(3, 128);
    }
    PH(8); FT(73);
    float acc[64];
    {
      float* accC = old;
      p.sB = 0;
      p.issue<192>(accC, true, 1024 + STG); FT(80); p.next();
      p.issue<192>(accC, false, 1024 + STG + 16384); FT(81);
      FT(78);
      float s0 = 0, s1 = 0;
#define X1_FENCE _Pragma("unroll") for (int j = 0; j < 32; j++) asm volatile("" : "+r"(x1[j]));
      X1_FENCE
#pragma unroll
      for (int j = 0; j < 16; j++) { s0 += blo(x1[j * 2]) + bhi(x1[j * 2]); s1 += blo(x1[j * 2 + 1]) + bhi(x1[j * 2 + 1]); }
      s0 += __shfl_xor_sync(~0u, s0, 1); s1 += __shfl_xor_sync(~0u, s1, 1);
      s0 += __shfl_xor_sync(~0u, s0, 2); s1 += __shfl_xor_sync(~0u, s1, 2);
      s0 *= 1.f / 128; s1 *= 1.f / 128;
      float q0 = 0, q1 = 0;
      X1_FENCE
#pragma unroll
      for (int j = 0; j < 16; j++) {
        const float a = blo(x1[j * 2]) - s0, b = bhi(x1[j * 2]) - s0, c = blo(x1[j * 2 + 1]) - s1, d = bhi(x1[j * 2 + 1]) - s1;
        q0 += a * a + b * b; q1 += c * c + d * d;
      }
      q0 += __shfl_xor_sync(~0u, q0, 1); q1 += __shfl_xor_sync(~0u, q1, 1);
      q0 += __shfl_xor_sync(~0u, q0, 2); q1 += __shfl_xor_sync(~0u, q1, 2);
      if (q < 2) {
        uint32_t m = __float_as_uint(q ? s1 : s0), v = __float_as_uint(q ? q1 : q0);
        if (m == ~0u) m = 0x7fffffffu;
        if (v == ~0u) v = 0x7fffffffu;
        stg_rlx2((uint2*)(sp + q * 32) + nb, m, v);
      }
      X1_FENCE
      p.retire();
#pragma unroll 1
      for (int k = 2; k < 15; k++) { p.issue<192>(accC, false); FT(80 + k); p.retire(); }
      p.issue<192>(accC, false); FT(95);
      mbar_wait(xbar, 1);
      const float2 u0 = lds2f(sb + STG + 16384 + (row0 + (lane >> 2)) * 8), u1 = lds2f(sb + STG + 16384 + (row0 + (lane >> 2)) * 8 + 64);
      r0_ = u0.x; e.n0 = u0.y; r1_ = u1.x; e.n1 = u1.y;
      e.c = lds2u(e.cc);
      p.retire();
      e.s0 = r0_; e.s1 = r1_;
    }
    PH(9);
    {
      auto pair = [&](int J, bool first, int fo) {
#pragma unroll 1
        for (int r = 0; r < 2; r++) { p.issue<128>(acc, first && !r); FT(fo + r); p.retire(); acc_fence<8>(old + J * 8); e.half(old + J * 8, J, r); }
      };
#pragma unroll 1
      for (int i = 0; i < 3; i++) {
        if (i == 2) {
          e.s0 = r0_; e.s1 = r1_;
#pragma unroll
          for (int J = 8; J < 12; J++) pair(J, J == 8, 128 + (J - 8) * 2);
          e.cc += 512; e.c = lds2u(e.cc);
          e.s0 = e.s1 = 1.f;
        }
#pragma unroll
        for (int J = 0; J < 8; J++) pair(J, J == 0 && i < 2, 96 + i * 16 + (i >> 1) * 8 + J * 2);
        if (i == 2) break;
        e.cc += i ? -768 : 256; e.c = lds2u(e.cc);
        WG_WAIT(0);
        acc_fence<64>(acc);
#pragma unroll
        for (int k = 0; k < 64; k++) old[k] = acc[k] * ((k & 2) ? r1_ : r0_);
        acc_fence<64>(old);
        e.s0 = e.s1 = 1.f;
        PH(10 + i);
      }
#pragma unroll 1
      for (int k = 24; k < 56; k++) { p.issue<128>(acc, false); FT(128 + k); p.retire(); }
      float xf[64], gf[32];
#pragma unroll
      for (int i = 0; i < 4; i++) {
        const uint4 g = lds4(prm + 512 + i * 64), h = lds4(prm + 768 + i * 64);
        float hf[8];
        UNPK8(gf + i * 8, g); UNPK8(hf, h);
#pragma unroll
        for (int u = 0; u < 8; u++) {
          const int c = (u >> 2) * 4 + (u & 2);
          xf[i * 16 + u * 2] = fmaf(gf[i * 8 + c], hf[c], blo(x1[i * 8 + u])); xf[i * 16 + u * 2 + 1] = fmaf(gf[i * 8 + c + 1], hf[c + 1], bhi(x1[i * 8 + u]));
        }
      }
      acc_fence<64>(xf); acc_fence<32>(gf);
      mbar_wait(staged + 24, 1);
      mbar_wait(staged + 16, 0);
      WG_WAIT(0);
      acc_fence<64>(acc);
      PH(13); FT(184);
#pragma unroll
      for (int j = 0; j < 8; j++) {
        uint32_t o[4];
#pragma unroll
        for (int i = 0; i < 4; i++)
          o[i] = pk(fmaf(acc[j * 8 + i * 2], gf[j * 4 + (i & 2)], xf[j * 8 + i * 2]), fmaf(acc[j * 8 + i * 2 + 1], gf[j * 4 + (i & 2) + 1], xf[j * 8 + i * 2 + 1]));
        stsm4((stw ^ ((j & 3) * 32)) + (j >> 2) * 16384, o[0], o[1], o[2], o[3]);
        if ((j & 3) == 3) {
          FENCE_ASYNC_SMEM();
          __syncwarp();
          if (lane == 0) { tma2d_st(&mp.out, nb * 128 + (j >> 2) * 64, rb * 128 + row0, stg + (j >> 2) * 16384); BULK_COMMIT(); }
        }
      }
      if (lane == 0) BULK_WAIT_READ(0);
      __syncwarp();
    }
  }
  PH(14); FT(185);
}

typedef CUresult (*EncFn)(CUtensorMap*, CUtensorMapDataType, cuuint32_t, void*, const cuuint64_t*, const cuuint64_t*, const cuuint32_t*,
                          const cuuint32_t*, CUtensorMapInterleave, CUtensorMapSwizzle, CUtensorMapL2promotion, CUtensorMapFloatOOBfill);
static void map2d(EncFn enc, CUtensorMap* m, const void* p, int rows, int cols, int boxRows) {
  cuuint64_t d[2] = {(cuuint64_t)cols, (cuuint64_t)rows}, s[1] = {(cuuint64_t)cols * 2};
  cuuint32_t b[2] = {64, (cuuint32_t)boxRows}, e[2] = {1, 1};
  enc(m, CU_TENSOR_MAP_DATA_TYPE_BFLOAT16, 2, (void*)p, d, s, b, e, CU_TENSOR_MAP_INTERLEAVE_NONE, CU_TENSOR_MAP_SWIZZLE_128B,
      CU_TENSOR_MAP_L2_PROMOTION_L2_128B, CU_TENSOR_MAP_FLOAT_OOB_FILL_NONE);
}
static void map3d(EncFn enc, CUtensorMap* m, const void* p, int rows, int cols, int nch) {
  cuuint64_t d[3] = {64, (cuuint64_t)rows, (cuuint64_t)(cols / 64)}, s[2] = {(cuuint64_t)cols * 2, 128};
  cuuint32_t b[3] = {64, 64, (cuuint32_t)nch}, e[3] = {1, 1, 1};
  enc(m, CU_TENSOR_MAP_DATA_TYPE_BFLOAT16, 3, (void*)p, d, s, b, e, CU_TENSOR_MAP_INTERLEAVE_NONE, CU_TENSOR_MAP_SWIZZLE_128B,
      CU_TENSOR_MAP_L2_PROMOTION_L2_128B, CU_TENSOR_MAP_FLOAT_OOB_FILL_NONE);
}

extern "C" void kernel_launch(void* const* d_in, const int* in_sizes, int n_in, void* d_out, int out_size) {
  const bf16* x = (const bf16*)d_in[0];
  const bf16* mem0 = (const bf16*)d_in[1];
  void* fn = nullptr;
  cudaDriverEntryPointQueryResult qr;
  cudaGetDriverEntryPoint("cuTensorMapEncodeTiled", &fn, cudaEnableDefault, &qr);
  EncFn enc = (EncFn)fn;
  FfnMaps fm = {};
  map3d(enc, &fm.wo, d_in[5], 4096, 1024, 2);
  map3d(enc, &fm.w1a, d_in[8], 1024, 3584, 2);
  map3d(enc, &fm.w1b, d_in[8], 1024, 3584, 3);
  map3d(enc, &fm.w2, d_in[10], 3584, 1024, 2);
  map2d(enc, &fm.x, x, 2048, 1024, 128);
  map2d(enc, &fm.out, d_out, 2048, 1024, 16);
  RecMaps rm = {};
  map2d(enc, &rm.wq, d_in[2], 1024, 4096, 128);
  map2d(enc, &rm.wk, d_in[3], 1024, 4096, 128);
  map2d(enc, &rm.wv, d_in[4], 1024, 4096, 16);
  map2d(enc, &rm.wo, d_in[5], 4096, 1024, 128);
  char* xc = nullptr;
  cudaGetSymbolAddress((void**)&xc, g_xc);
  xc += (0 - (uintptr_t)xc) & 0x1FFFFF;
  {
    cuuint64_t d[3] = {512, ARV ? 8 : 128, ARV ? 128 : 6}, sd[2] = {1024, ARV ? 8192 : 131072};
    cuuint32_t bi[3] = {64, 8, 5}, e[3] = {1, 1, 1};
    enc(&rm.ari, CU_TENSOR_MAP_DATA_TYPE_BFLOAT16, 3, xc + AR_OFF, d, sd, bi, e, CU_TENSOR_MAP_INTERLEAVE_NONE, CU_TENSOR_MAP_SWIZZLE_NONE,
        CU_TENSOR_MAP_L2_PROMOTION_NONE, CU_TENSOR_MAP_FLOAT_OOB_FILL_NONE);
  }
  cudaFuncSetAttribute(k_ffn, cudaFuncAttributeMaxDynamicSharedMemorySize, ffn::SMEM);
  cudaFuncSetAttribute(k_rec, cudaFuncAttributeMaxDynamicSharedMemorySize, rec::SMEM);
  cudaStream_t st = cudaStreamPerThread;
  int dF = 450, dA = 2700, dS = 300, dM = 120, dG = 350, dP = 24, dX = 48, dD = 350, dZ = 0, dZ2 = 1, dV = 370, dX2 = 0;
  k_rec<<<132, 512, rec::SMEM, st>>>(rm, mem0, x, (const bf16*)d_in[12], (const bf16*)d_in[13], (const char*)d_in[8], (const bf16*)d_in[9],
                                     (const char*)d_in[5], xc, dF, dA, dS, dM, dG, dP, dX, dD, dZ, dZ2, dV, dX2);
  cudaLaunchConfig_t cfg = {};
  cfg.gridDim = dim3(132); cfg.blockDim = dim3(384); cfg.dynamicSmemBytes = ffn::SMEM; cfg.stream = st;
  cudaLaunchAttribute at[1];
  at[0].id = cudaLaunchAttributeProgrammaticStreamSerialization;
  at[0].val.programmaticStreamSerializationAllowed = 1;
  cfg.attrs = at; cfg.numAttrs = 1;
  cudaLaunchKernelEx(&cfg, k_ffn, fm, (const bf16*)d_in[11]);
}
```

```cpp
#include <cuda_runtime.h>
#include <cuda.h>
#include <cuda_bf16.h>
#include <stdint.h>

typedef __nv_bfloat16 bf16;

__device__ __align__(16) float g_mod[6144];
__device__ __align__(1024) uint4 g_modp[4 * 512];
__device__ unsigned g_hcnt;
__device__ unsigned g_hf[4];
__device__ __align__(1024) uint4 g_h[2048 * 1024 / 8];
__device__ __align__(1024) uint4 g_O[2048 * 4096 / 8];
__device__ __align__(1024) uint4 g_h2[2048 * 1024 / 8];
__device__ __align__(1024) uint4 g_U[2048 * 3584 / 8];
__device__ __align__(1024) uint4 g_stat[2048 * 4];
__device__ __align__(1024) unsigned g_cnt[16 * 4 * 32];
__device__ unsigned g_mcnt;
__device__ unsigned g_slot[256];
__device__ unsigned g_fin;
__device__ __align__(16) uint4 g_cc[224 * 4];
__device__ __align__(1024) uint4 g_xc[44 * 16384];
__device__ __align__(1024) unsigned g_tm[4 * 256];
#define FT(i)
#define FTP(i)
#define PT(i)
#define PH(i)
#define RP(i)
#define RPN(i, s)
#define TSV(i, v)
#define TS(i)

#define WIN 3
#define FRC "232"
#define FRP "40"
#define YR 1
#define XPK 0
#define NFA 1
#define PINM 1
#define FMAP (((g >> 2) * 4 + m) * 8 + (g & 3) * 2 + (blockIdx.x & 1))
#define FDB 0
#define ALIAS 3
#define EF 0
#define XPF 0
#define PFT 150000
#define PFS 104
#define PF0 13000
#define PFD 128
#define ARV 0
#define HV 0
#define XE 0
#define NF 2
#define NB0 4
#define PV0 4
#define T1L 1
#define NW0 5
#define FQM 0
#define FQ(k) do { if ((FQM >> ((k) - 48)) & 1) SCHED_FENCE(k); } while (0)
#define SWP 1
#define VCO 0
#define AV 0
#define PKE 0
#define VRF 3
#define RSO 2
#define XDL 6
#define QW 0
#define PDS 61
#define P_NVR 5
#define P_NVP 2
#define P_NWP 9
#define P_NW1 7
#define RF_ 208
#define PSV 1
#define RA_ (488 - 2 * RF_)
#define XI 5
#define XL 1
#define WCH 2
#define HX 0
#define VB 1
#define TP 0
#define CKI 0
#define NOP_ 2
#define KVO 0
#define NDL 3
#define AM 0
#define XM 3
#define XP 0
#define SPIN_LIMIT (1 << 20)
__device__ __forceinline__ uint64_t mkdesc(uint32_t addr, uint32_t lbo, uint32_t sbo) {
  return (uint64_t)((addr & 0x3FFFF) >> 4) | ((uint64_t)(lbo >> 4) << 16) | ((uint64_t)(sbo >> 4) << 32) | (1ull << 62);
}
__device__ __forceinline__ void mbar_init(uint32_t a, int c) { asm volatile("mbarrier.init.shared.b64 [%0],%1;" ::"r"(a), "r"(c) : "memory"); }
__device__ __forceinline__ void mbar_wait(uint32_t a, uint32_t par) {
  asm volatile(
      "{.reg .pred p; .reg .u32 n;\n"
      "mov.u32 n, 0;\n"
      "W: mbarrier.try_wait.parity.shared.b64 p,[%0],%1;\n"
      "@p bra D;\n"
      "add.u32 n, n, 1;\n"
      "setp.lt.u32 p, n, %2;\n"
      "@p bra W;\n"
      "trap;\n"
      "D:}" ::"r"(a), "r"(par), "n"(SPIN_LIMIT) : "memory");
}
__device__ __forceinline__ void mbar_wait_q(uint32_t a, uint32_t par) {
  asm volatile(
      "{.reg .pred p; .reg .u32 n;\n"
      "mov.u32 n, 0;\n"
      "W: mbarrier.try_wait.parity.shared.b64 p,[%0],%1,4000;\n"
      "@p bra D;\n"
      "add.u32 n, n, 1;\n"
      "setp.lt.u32 p, n, %2;\n"
      "@p bra W;\n"
      "trap;\n"
      "D:}" ::"r"(a), "r"(par), "n"(SPIN_LIMIT / 16) : "memory");
}
__device__ __forceinline__ void mbar_expect(uint32_t a, uint32_t b) { asm volatile("mbarrier.arrive.expect_tx.shared.b64 _,[%0],%1;" ::"r"(a), "r"(b) : "memory"); }
__device__ __forceinline__ void mbar_arrive(uint32_t a) { asm volatile("mbarrier.arrive.shared.b64 _,[%0];" ::"r"(a) : "memory"); }
__device__ __forceinline__ uint32_t mapa(uint32_t a, uint32_t cta) { uint32_t r; asm("mapa.shared::cluster.u32 %0,%1,%2;" : "=r"(r) : "r"(a), "r"(cta)); return r; }
__device__ __forceinline__ void mbar_arrive_cl(uint32_t a) { asm volatile("mbarrier.arrive.shared::cluster.b64 _,[%0];" ::"r"(a) : "memory"); }
__device__ __forceinline__ void tma2d(uint32_t dst, const CUtensorMap* m, int c0, int c1, uint32_t mb) {
  asm volatile("cp.async.bulk.tensor.2d.shared::cluster.global.mbarrier::complete_tx::bytes [%0],[%1,{%2,%3}],[%4];" ::"r"(dst), "l"(m), "r"(c0), "r"(c1), "r"(mb) : "memory");
}
__device__ __forceinline__ void tma2d_pf(const CUtensorMap* m, int c0, int c1) {
  asm volatile("cp.async.bulk.prefetch.tensor.2d.L2.global [%0,{%1,%2}];" ::"l"(m), "r"(c0), "r"(c1) : "memory");
}
__device__ __forceinline__ void tma3d(uint32_t dst, const CUtensorMap* m, int c1, int c2, uint32_t mb) {
  asm volatile("cp.async.bulk.tensor.3d.shared::cluster.global.mbarrier::complete_tx::bytes [%0],[%1,{0,%2,%3}],[%4];" ::"r"(dst), "l"(m), "r"(c1), "r"(c2), "r"(mb) : "memory");
}
__device__ __forceinline__ void tma2d_st(const CUtensorMap* m, int c0, int c1, uint32_t src) {
  asm volatile("cp.async.bulk.tensor.2d.global.shared::cta.bulk_group [%0,{%1,%2}],[%3];" ::"l"(m), "r"(c0), "r"(c1), "r"(src) : "memory");
}
__device__ __forceinline__ void bulk_ld(uint32_t dst, const void* src, uint32_t n, uint32_t mb) {
  asm volatile("cp.async.bulk.shared::cluster.global.mbarrier::complete_tx::bytes [%0],[%1],%2,[%3];" ::"r"(dst), "l"(src), "r"(n), "r"(mb) : "memory");
}
__device__ __forceinline__ void bulk_ld_mc(uint32_t dst, const void* src, uint32_t n, uint32_t mb) {
  asm volatile("cp.async.bulk.shared::cluster.global.mbarrier::complete_tx::bytes.multicast::cluster [%0],[%1],%2,[%3],%4;" ::"r"(dst), "l"(src), "r"(n), "r"(mb), "h"((uint16_t)3) : "memory");
}
__device__ __forceinline__ void bulk_st(void* dst, uint32_t src, uint32_t n) {
  asm volatile("cp.async.bulk.global.shared::cta.bulk_group [%0],[%1],%2;" ::"l"(dst), "r"(src), "r"(n) : "memory");
}
__device__ __forceinline__ void e_expect_tma3d(uint32_t dst, const CUtensorMap* m, int c1, int c2, uint32_t mb, uint32_t bytes) {
  asm volatile("{.reg .pred p; elect.sync _|p, 0xffffffff; @p mbarrier.arrive.expect_tx.shared.b64 _,[%4],%5;\n"
               "@p cp.async.bulk.tensor.3d.shared::cluster.global.mbarrier::complete_tx::bytes [%0],[%1,{0,%2,%3}],[%4];}" ::"r"(dst), "l"(m), "r"(c1), "r"(c2), "r"(mb), "r"(bytes) : "memory");
}
__device__ __forceinline__ void e_bulk_ld(uint32_t dst, const void* src, uint32_t n, uint32_t mb) {
  asm volatile("{.reg .pred p; elect.sync _|p, 0xffffffff; @p cp.async.bulk.shared::cluster.global.mbarrier::complete_tx::bytes [%0],[%1],%2,[%3];}" ::"r"(dst), "l"(src), "r"(n), "r"(mb) : "memory");
}
__device__ __forceinline__ void e_bulk_ld_ef(uint32_t dst, const void* src, uint32_t n, uint32_t mb) {
  asm volatile("{.reg .pred p; .reg .b64 c; createpolicy.fractional.L2::evict_first.b64 c,1.0; elect.sync _|p, 0xffffffff;"
               " @p cp.async.bulk.shared::cluster.global.mbarrier::complete_tx::bytes.L2::cache_hint [%0],[%1],%2,[%3],c;}" ::"r"(dst), "l"(src), "r"(n), "r"(mb) : "memory");
}
__device__ __forceinline__ void e_bulk_ld_mc(uint32_t dst, const void* src, uint32_t n, uint32_t mb) {
  asm volatile("{.reg .pred p; elect.sync _|p, 0xffffffff; @p cp.async.bulk.shared::cluster.global.mbarrier::complete_tx::bytes.multicast::cluster [%0],[%1],%2,[%3],%4;}" ::"r"(dst), "l"(src), "r"(n), "r"(mb), "h"((uint16_t)3) : "memory");
}
#define BULK_COMMIT() asm volatile("cp.async.bulk.commit_group;" ::: "memory")
#define BULK_WAIT_READ(n) asm volatile("cp.async.bulk.wait_group.read " #n ";" ::: "memory")
#define BULK_WAIT(n) asm volatile("cp.async.bulk.wait_group " #n ";" ::: "memory")
#define FENCE_ASYNC_SMEM() asm volatile("fence.proxy.async.shared::cta;" ::: "memory")
#define FENCE_ASYNC() asm volatile("fence.proxy.async;" ::: "memory")
#define WG_FENCE() asm volatile("wgmma.fence.sync.aligned;" ::: "memory")
#define WG_COMMIT() asm volatile("wgmma.commit_group.sync.aligned;" ::: "memory")
#define WG_WAIT(n) asm volatile("wgmma.wait_group.sync.aligned " #n ";" ::: "memory")
#define BAR_SYNC(id, n) asm volatile("bar.sync %0,%1;" ::"n"(id), "n"(n) : "memory")
#define BAR_ARRIVE(id, n) asm volatile("bar.arrive %0,%1;" ::"n"(id), "n"(n) : "memory")
#define SCHED_FENCE(k) asm volatile("{.reg .pred p; setp.ne.u32 p,%0,0; @p trap;}" ::"r"(mp.zero[(k) - 46]) : "memory")
#define CLUSTER_SYNC() asm volatile("barrier.cluster.arrive.relaxed.aligned; barrier.cluster.wait.aligned;" ::: "memory")
__device__ __forceinline__ uint32_t pk(float lo, float hi) { uint32_t r; asm("cvt.rn.bf16x2.f32 %0,%1,%2;" : "=r"(r) : "f"(hi), "f"(lo)); return r; }
__device__ __forceinline__ float blo(uint32_t v) { return __uint_as_float(v << 16); }
__device__ __forceinline__ float bhi(uint32_t v) { return __uint_as_float(v & 0xffff0000u); }
__device__ __forceinline__ void ldsm4(uint32_t* r, uint32_t a) {
  asm volatile("ldmatrix.sync.aligned.m8n8.x4.shared.b16 {%0,%1,%2,%3},[%4];" : "=r"(r[0]), "=r"(r[1]), "=r"(r[2]), "=r"(r[3]) : "r"(a) : "memory");
}
__device__ __forceinline__ void ldsm4t(uint32_t* r, uint32_t a) {
  asm volatile("ldmatrix.sync.aligned.m8n8.x4.trans.shared.b16 {%0,%1,%2,%3},[%4];" : "=r"(r[0]), "=r"(r[1]), "=r"(r[2]), "=r"(r[3]) : "r"(a) : "memory");
}
__device__ __forceinline__ void stsm4(uint32_t a, uint32_t r0, uint32_t r1, uint32_t r2, uint32_t r3) {
  asm volatile("stmatrix.sync.aligned.m8n8.x4.shared.b16 [%0],{%1,%2,%3,%4};" ::"r"(a), "r"(r0), "r"(r1), "r"(r2), "r"(r3) : "memory");
}
__device__ __forceinline__ void mma16(float* d, uint32_t a0, uint32_t a1, uint32_t a2, uint32_t a3, uint32_t b0, uint32_t b1) {
  asm volatile("mma.sync.aligned.m16n8k16.row.col.f32.bf16.bf16.f32 {%0,%1,%2,%3},{%4,%5,%6,%7},{%8,%9},{%0,%1,%2,%3};"
               : "+f"(d[0]), "+f"(d[1]), "+f"(d[2]), "+f"(d[3]) : "r"(a0), "r"(a1), "r"(a2), "r"(a3), "r"(b0), "r"(b1));
}
__device__ __forceinline__ void mma8(float* d, uint32_t a0, uint32_t a1, uint32_t b0) {
  asm volatile("mma.sync.aligned.m16n8k8.row.col.f32.bf16.bf16.f32 {%0,%1,%2,%3},{%4,%5},{%6},{%0,%1,%2,%3};"
               : "+f"(d[0]), "+f"(d[1]), "+f"(d[2]), "+f"(d[3]) : "r"(a0), "r"(a1), "r"(b0));
}
__device__ __forceinline__ float4 lds4f(uint32_t a) { float4 v; asm volatile("ld.shared.v4.f32 {%0,%1,%2,%3},[%4];" : "=f"(v.x), "=f"(v.y), "=f"(v.z), "=f"(v.w) : "r"(a) : "memory"); return v; }
__device__ __forceinline__ float2 lds2f(uint32_t a) { float2 v; asm volatile("ld.shared.v2.f32 {%0,%1},[%2];" : "=f"(v.x), "=f"(v.y) : "r"(a) : "memory"); return v; }
__device__ __forceinline__ uint4 lds4(uint32_t a) { uint4 v; asm volatile("ld.shared.v4.u32 {%0,%1,%2,%3},[%4];" : "=r"(v.x), "=r"(v.y), "=r"(v.z), "=r"(v.w) : "r"(a) : "memory"); return v; }
__device__ __forceinline__ uint2 lds2u(uint32_t a) { uint2 v; asm volatile("ld.shared.v2.u32 {%0,%1},[%2];" : "=r"(v.x), "=r"(v.y) : "r"(a) : "memory"); return v; }
__device__ __forceinline__ uint32_t lds1(uint32_t a) { uint32_t v; asm volatile("ld.shared.u32 %0,[%1];" : "=r"(v) : "r"(a) : "memory"); return v; }
__device__ __forceinline__ void sts4(uint32_t a, uint32_t x, uint32_t y, uint32_t z, uint32_t w) { asm volatile("st.shared.v4.u32 [%0],{%1,%2,%3,%4};" ::"r"(a), "r"(x), "r"(y), "r"(z), "r"(w) : "memory"); }
__device__ __forceinline__ void sts2(uint32_t a, uint32_t x, uint32_t y) { asm volatile("st.shared.v2.u32 [%0],{%1,%2};" ::"r"(a), "r"(x), "r"(y) : "memory"); }
__device__ __forceinline__ void sts1(uint32_t a, uint32_t x) { asm volatile("st.shared.u32 [%0],%1;" ::"r"(a), "r"(x) : "memory"); }
__device__ __forceinline__ void sta4(uint32_t a, const uint32_t* v, uint32_t mb) {
  asm volatile("st.async.shared::cluster.mbarrier::complete_tx::bytes.v4.b32 [%0],{%1,%2,%3,%4},[%5];" ::"r"(a), "r"(v[0]), "r"(v[1]), "r"(v[2]), "r"(v[3]), "r"(mb) : "memory");
}
__device__ __forceinline__ uint4 ldg_rlx4(const void* p) { uint4 v; asm volatile("ld.relaxed.gpu.global.v4.u32 {%0,%1,%2,%3},[%4];" : "=r"(v.x), "=r"(v.y), "=r"(v.z), "=r"(v.w) : "l"(p) : "memory"); return v; }
__device__ __forceinline__ uint32_t ldg_rlx1(const void* p) { uint32_t v; asm volatile("ld.relaxed.gpu.global.u32 %0,[%1];" : "=r"(v) : "l"(p) : "memory"); return v; }
__device__ __forceinline__ uint2 ldg_rlx2(const void* p) { uint2 v; asm volatile("ld.relaxed.gpu.global.v2.u32 {%0,%1},[%2];" : "=r"(v.x), "=r"(v.y) : "l"(p) : "memory"); return v; }
__device__ __forceinline__ uint4 ldg_b128(const void* p) {
  uint4 v;
  asm volatile("{.reg .b128 t; .reg .b64 a,b; ld.relaxed.gpu.global.b128 t,[%4]; mov.b128 {a,b},t; mov.b64 {%0,%1},a; mov.b64 {%2,%3},b;}" : "=r"(v.x), "=r"(v.y), "=r"(v.z), "=r"(v.w) : "l"(p) : "memory");
  return v;
}
__device__ __forceinline__ void stg_b128(void* p, uint32_t x, uint32_t y, uint32_t z, uint32_t w) {
  asm volatile("{.reg .b128 t; .reg .b64 a,b; mov.b64 a,{%1,%2}; mov.b64 b,{%3,%4}; mov.b128 t,{a,b}; st.relaxed.gpu.global.b128 [%0],t;}" ::"l"(p), "r"(x), "r"(y), "r"(z), "r"(w) : "memory");
}
__device__ __forceinline__ void st_b128(void* p, uint32_t x, uint32_t y, uint32_t z, uint32_t w) {
  asm volatile("{.reg .b128 t; .reg .b64 a,b; mov.b64 a,{%1,%2}; mov.b64 b,{%3,%4}; mov.b128 t,{a,b}; st.relaxed.gpu.b128 [%0],t;}" ::"l"(p), "r"(x), "r"(y), "r"(z), "r"(w) : "memory");
}
__device__ __forceinline__ void stg_rlx4(void* p, uint32_t x, uint32_t y, uint32_t z, uint32_t w) { asm volatile("st.relaxed.gpu.global.v4.u32 [%0],{%1,%2,%3,%4};" ::"l"(p), "r"(x), "r"(y), "r"(z), "r"(w) : "memory"); }
__device__ __forceinline__ void stg_rlx2(void* p, uint32_t x, uint32_t y) { asm volatile("st.relaxed.gpu.global.v2.u32 [%0],{%1,%2};" ::"l"(p), "r"(x), "r"(y) : "memory"); }
__device__ __forceinline__ void red4(void* p, float a, float b, float c, float d) { asm volatile("red.relaxed.gpu.global.add.v4.f32 [%0],{%1,%2,%3,%4};" ::"l"(p), "f"(a), "f"(b), "f"(c), "f"(d) : "memory"); }
__device__ __forceinline__ unsigned ld_acq(const unsigned* p) { unsigned v; asm volatile("ld.acquire.gpu.global.u32 %0,[%1];" : "=r"(v) : "l"(p) : "memory"); return v; }
__device__ __forceinline__ void red_rel(unsigned* p) { asm volatile("red.release.gpu.global.add.u32 [%0],1;" ::"l"(p) : "memory"); }
__device__ __forceinline__ void red_rlx(unsigned* p) { asm volatile("red.relaxed.gpu.global.add.u32 [%0],1;" ::"l"(p) : "memory"); }
__device__ __forceinline__ void wait_cnt(const unsigned* p, unsigned n) { int it = 0; while (ld_acq(p) < n) { if (++it > SPIN_LIMIT) __trap(); } }
__device__ __forceinline__ uint32_t clk() { uint32_t c; asm volatile("mov.u32 %0,%%clock;" : "=r"(c)); return c; }
__device__ __forceinline__ uint32_t gtime() { uint32_t c; asm volatile("mov.u32 %0,%%globaltimer_lo;" : "=r"(c)); return c; }
__device__ __forceinline__ void wait_until(uint32_t t0, uint32_t d) { while (clk() - t0 < d) {} }
__device__ __forceinline__ float ex2(float x) { float r; asm("ex2.approx.ftz.f32 %0,%1;" : "=f"(r) : "f"(x)); return r; }
__device__ __forceinline__ float silu(float x) { return x * __frcp_rn(1.f + __expf(-x)); }
__device__ __forceinline__ float rbf(float x) { return __bfloat162float(__float2bfloat16_rn(x)); }

__device__ __forceinline__ void wgmma_ss_n128(float* d, uint64_t a, uint64_t b, int sd) {
  asm volatile("{.reg .pred p; setp.ne.b32 p, %66, 0;\n"
    "wgmma.mma_async.sync.aligned.m64n128k16.f32.bf16.bf16 {%0,%1,%2,%3,%4,%5,%6,%7,%8,%9,%10,%11,%12,%13,%14,%15,%16,%17,%18,%19,%20,%21,%22,%23,%24,%25,%26,%27,%28,%29,%30,%31,%32,%33,%34,%35,%36,%37,%38,%39,%40,%41,%42,%43,%44,%45,%46,%47,%48,%49,%50,%51,%52,%53,%54,%55,%56,%57,%58,%59,%60,%61,%62,%63}, %64, %65, p, 1, 1, 0, 1;}\n"
    : "+f"(d[0]),"+f"(d[1]),"+f"(d[2]),"+f"(d[3]),"+f"(d[4]),"+f"(d[5]),"+f"(d[6]),"+f"(d[7]),
      "+f"(d[8]),"+f"(d[9]),"+f"(d[10]),"+f"(d[11]),"+f"(d[12]),"+f"(d[13]),"+f"(d[14]),"+f"(d[15]),
      "+f"(d[16]),"+f"(d[17]),"+f"(d[18]),"+f"(d[19]),"+f"(d[20]),"+f"(d[21]),"+f"(d[22]),"+f"(d[23]),
      "+f"(d[24]),"+f"(d[25]),"+f"(d[26]),"+f"(d[27]),"+f"(d[28]),"+f"(d[29]),"+f"(d[30]),"+f"(d[31]),
      "+f"(d[32]),"+f"(d[33]),"+f"(d[34]),"+f"(d[35]),"+f"(d[36]),"+f"(d[37]),"+f"(d[38]),"+f"(d[39]),
      "+f"(d[40]),"+f"(d[41]),"+f"(d[42]),"+f"(d[43]),"+f"(d[44]),"+f"(d[45]),"+f"(d[46]),"+f"(d[47]),
      "+f"(d[48]),"+f"(d[49]),"+f"(d[50]),"+f"(d[51]),"+f"(d[52]),"+f"(d[53]),"+f"(d[54]),"+f"(d[55]),
      "+f"(d[56]),"+f"(d[57]),"+f"(d[58]),"+f"(d[59]),"+f"(d[60]),"+f"(d[61]),"+f"(d[62]),"+f"(d[63])
    : "l"(a), "l"(b), "r"(sd));
}
__device__ __forceinline__ void wgmma_ss_n192(float* d, uint64_t a, uint64_t b, int sd) {
  asm volatile("{.reg .pred p; setp.ne.b32 p, %98, 0;\n"
    "wgmma.mma_async.sync.aligned.m64n192k16.f32.bf16.bf16 {%0,%1,%2,%3,%4,%5,%6,%7,%8,%9,%10,%11,%12,%13,%14,%15,%16,%17,%18,%19,%20,%21,%22,%23,%24,%25,%26,%27,%28,%29,%30,%31,%32,%33,%34,%35,%36,%37,%38,%39,%40,%41,%42,%43,%44,%45,%46,%47,%48,%49,%50,%51,%52,%53,%54,%55,%56,%57,%58,%59,%60,%61,%62,%63,%64,%65,%66,%67,%68,%69,%70,%71,%72,%73,%74,%75,%76,%77,%78,%79,%80,%81,%82,%83,%84,%85,%86,%87,%88,%89,%90,%91,%92,%93,%94,%95}, %96, %97, p, 1, 1, 0, 1;}\n"
    : "+f"(d[0]),"+f"(d[1]),"+f"(d[2]),"+f"(d[3]),"+f"(d[4]),"+f"(d[5]),"+f"(d[6]),"+f"(d[7]),
      "+f"(d[8]),"+f"(d[9]),"+f"(d[10]),"+f"(d[11]),"+f"(d[12]),"+f"(d[13]),"+f"(d[14]),"+f"(d[15]),
      "+f"(d[16]),"+f"(d[17]),"+f"(d[18]),"+f"(d[19]),"+f"(d[20]),"+f"(d[21]),"+f"(d[22]),"+f"(d[23]),
      "+f"(d[24]),"+f"(d[25]),"+f"(d[26]),"+f"(d[27]),"+f"(d[28]),"+f"(d[29]),"+f"(d[30]),"+f"(d[31]),
      "+f"(d[32]),"+f"(d[33]),"+f"(d[34]),"+f"(d[35]),"+f"(d[36]),"+f"(d[37]),"+f"(d[38]),"+f"(d[39]),
      "+f"(d[40]),"+f"(d[41]),"+f"(d[42]),"+f"(d[43]),"+f"(d[44]),"+f"(d[45]),"+f"(d[46]),"+f"(d[47]),
      "+f"(d[48]),"+f"(d[49]),"+f"(d[50]),"+f"(d[51]),"+f"(d[52]),"+f"(d[53]),"+f"(d[54]),"+f"(d[55]),
      "+f"(d[56]),"+f"(d[57]),"+f"(d[58]),"+f"(d[59]),"+f"(d[60]),"+f"(d[61]),"+f"(d[62]),"+f"(d[63]),
      "+f"(d[64]),"+f"(d[65]),"+f"(d[66]),"+f"(d[67]),"+f"(d[68]),"+f"(d[69]),"+f"(d[70]),"+f"(d[71]),
      "+f"(d[72]),"+f"(d[73]),"+f"(d[74]),"+f"(d[75]),"+f"(d[76]),"+f"(d[77]),"+f"(d[78]),"+f"(d[79]),
      "+f"(d[80]),"+f"(d[81]),"+f"(d[82]),"+f"(d[83]),"+f"(d[84]),"+f"(d[85]),"+f"(d[86]),"+f"(d[87]),
      "+f"(d[88]),"+f"(d[89]),"+f"(d[90]),"+f"(d[91]),"+f"(d[92]),"+f"(d[93]),"+f"(d[94]),"+f"(d[95])
    : "l"(a), "l"(b), "r"(sd));
}
__device__ __forceinline__ void wgmma_ss_n256(float* d, uint64_t a, uint64_t b, int sd) {
  asm volatile("{.reg .pred p; setp.ne.b32 p, %130, 0;\n"
    "wgmma.mma_async.sync.aligned.m64n256k16.f32.bf16.bf16 {%0,%1,%2,%3,%4,%5,%6,%7,%8,%9,%10,%11,%12,%13,%14,%15,%16,%17,%18,%19,%20,%21,%22,%23,%24,%25,%26,%27,%28,%29,%30,%31,%32,%33,%34,%35,%36,%37,%38,%39,%40,%41,%42,%43,%44,%45,%46,%47,%48,%49,%50,%51,%52,%53,%54,%55,%56,%57,%58,%59,%60,%61,%62,%63,%64,%65,%66,%67,%68,%69,%70,%71,%72,%73,%74,%75,%76,%77,%78,%79,%80,%81,%82,%83,%84,%85,%86,%87,%88,%89,%90,%91,%92,%93,%94,%95,%96,%97,%98,%99,%100,%101,%102,%103,%104,%105,%106,%107,%108,%109,%110,%111,%112,%113,%114,%115,%116,%117,%118,%119,%120,%121,%122,%123,%124,%125,%126,%127}, %128, %129, p, 1, 1, 0, 1;}\n"
    : "+f"(d[0]),"+f"(d[1]),"+f"(d[2]),"+f"(d[3]),"+f"(d[4]),"+f"(d[5]),"+f"(d[6]),"+f"(d[7]),
      "+f"(d[8]),"+f"(d[9]),"+f"(d[10]),"+f"(d[11]),"+f"(d[12]),"+f"(d[13]),"+f"(d[14]),"+f"(d[15]),
      "+f"(d[16]),"+f"(d[17]),"+f"(d[18]),"+f"(d[19]),"+f"(d[20]),"+f"(d[21]),"+f"(d[22]),"+f"(d[23]),
      "+f"(d[24]),"+f"(d[25]),"+f"(d[26]),"+f"(d[27]),"+f"(d[28]),"+f"(d[29]),"+f"(d[30]),"+f"(d[31]),
      "+f"(d[32]),"+f"(d[33]),"+f"(d[34]),"+f"(d[35]),"+f"(d[36]),"+f"(d[37]),"+f"(d[38]),"+f"(d[39]),
      "+f"(d[40]),"+f"(d[41]),"+f"(d[42]),"+f"(d[43]),"+f"(d[44]),"+f"(d[45]),"+f"(d[46]),"+f"(d[47]),
      "+f"(d[48]),"+f"(d[49]),"+f"(d[50]),"+f"(d[51]),"+f"(d[52]),"+f"(d[53]),"+f"(d[54]),"+f"(d[55]),
      "+f"(d[56]),"+f"(d[57]),"+f"(d[58]),"+f"(d[59]),"+f"(d[60]),"+f"(d[61]),"+f"(d[62]),"+f"(d[63]),
      "+f"(d[64]),"+f"(d[65]),"+f"(d[66]),"+f"(d[67]),"+f"(d[68]),"+f"(d[69]),"+f"(d[70]),"+f"(d[71]),
      "+f"(d[72]),"+f"(d[73]),"+f"(d[74]),"+f"(d[75]),"+f"(d[76]),"+f"(d[77]),"+f"(d[78]),"+f"(d[79]),
      "+f"(d[80]),"+f"(d[81]),"+f"(d[82]),"+f"(d[83]),"+f"(d[84]),"+f"(d[85]),"+f"(d[86]),"+f"(d[87]),
      "+f"(d[88]),"+f"(d[89]),"+f"(d[90]),"+f"(d[91]),"+f"(d[92]),"+f"(d[93]),"+f"(d[94]),"+f"(d[95]),
      "+f"(d[96]),"+f"(d[97]),"+f"(d[98]),"+f"(d[99]),"+f"(d[100]),"+f"(d[101]),"+f"(d[102]),"+f"(d[103]),
      "+f"(d[104]),"+f"(d[105]),"+f"(d[106]),"+f"(d[107]),"+f"(d[108]),"+f"(d[109]),"+f"(d[110]),"+f"(d[111]),
      "+f"(d[112]),"+f"(d[113]),"+f"(d[114]),"+f"(d[115]),"+f"(d[116]),"+f"(d[117]),"+f"(d[118]),"+f"(d[119]),
      "+f"(d[120]),"+f"(d[121]),"+f"(d[122]),"+f"(d[123]),"+f"(d[124]),"+f"(d[125]),"+f"(d[126]),"+f"(d[127])
    : "l"(a), "l"(b), "r"(sd));
}
__device__ __forceinline__ void wgmma_rs_n32(float* d, const uint32_t* a, uint64_t b, int sd) {
  asm volatile("{.reg .pred p; setp.ne.b32 p, %21, 0;\n"
    "wgmma.mma_async.sync.aligned.m64n32k16.f32.bf16.bf16 {%0,%1,%2,%3,%4,%5,%6,%7,%8,%9,%10,%11,%12,%13,%14,%15}, {%16,%17,%18,%19}, %20, p, 1, 1, 0;}\n"
    : "+f"(d[0]),"+f"(d[1]),"+f"(d[2]),"+f"(d[3]),"+f"(d[4]),"+f"(d[5]),"+f"(d[6]),"+f"(d[7]),
      "+f"(d[8]),"+f"(d[9]),"+f"(d[10]),"+f"(d[11]),"+f"(d[12]),"+f"(d[13]),"+f"(d[14]),"+f"(d[15])
    : "r"(a[0]), "r"(a[1]), "r"(a[2]), "r"(a[3]), "l"(b), "r"(sd));
}
__device__ __forceinline__ void wgmma_ssT_n32(float* d, uint64_t a, uint64_t b, int sd) {
  asm volatile("{.reg .pred p; setp.ne.b32 p, %18, 0;\n"
    "wgmma.mma_async.sync.aligned.m64n32k16.f32.bf16.bf16 {%0,%1,%2,%3,%4,%5,%6,%7,%8,%9,%10,%11,%12,%13,%14,%15}, %16, %17, p, 1, 1, 1, 0;}\n"
    : "+f"(d[0]),"+f"(d[1]),"+f"(d[2]),"+f"(d[3]),"+f"(d[4]),"+f"(d[5]),"+f"(d[6]),"+f"(d[7]),
      "+f"(d[8]),"+f"(d[9]),"+f"(d[10]),"+f"(d[11]),"+f"(d[12]),"+f"(d[13]),"+f"(d[14]),"+f"(d[15])
    : "l"(a), "l"(b), "r"(sd));
}

__device__ __forceinline__ void wgmma_rs_n32_z(float* d, const uint32_t* a, uint64_t b) {
  asm volatile("{.reg .pred p; setp.ne.b32 p, 0, 0;\n"
    "wgmma.mma_async.sync.aligned.m64n32k16.f32.bf16.bf16 {%0,%1,%2,%3,%4,%5,%6,%7,%8,%9,%10,%11,%12,%13,%14,%15}, {%16,%17,%18,%19}, %20, p, 1, 1, 0;}\n"
    : "=f"(d[0]),"=f"(d[1]),"=f"(d[2]),"=f"(d[3]),"=f"(d[4]),"=f"(d[5]),"=f"(d[6]),"=f"(d[7]),
      "=f"(d[8]),"=f"(d[9]),"=f"(d[10]),"=f"(d[11]),"=f"(d[12]),"=f"(d[13]),"=f"(d[14]),"=f"(d[15])
    : "r"(a[0]), "r"(a[1]), "r"(a[2]), "r"(a[3]), "l"(b));
}

namespace rec {
constexpr int NVR = P_NVR;
constexpr int NVS = 16 - NVR;
constexpr int NVP = P_NVP;
constexpr int NWP = P_NWP;
constexpr uint32_t WO = 0;
constexpr uint32_t XB = 65536;
constexpr uint32_t PK = XB + 32768;
constexpr uint32_t VN = PK + 24576;
constexpr uint32_t VX0 = VN + 4096;
constexpr uint32_t WVS = 131072;
constexpr uint32_t MEM = WVS + 2 * NVS * 2048;
constexpr uint32_t ARO = MEM + 10240;
constexpr uint32_t OB = ARO + 5120;
constexpr uint32_t QT = OB + 2048;
constexpr uint32_t KT = QT + 2048;
constexpr uint32_t RQ = KT + 6144;
constexpr uint32_t RK = RQ + 2048;
constexpr uint32_t SC = RK + 2048;
constexpr uint32_t OT = OB;
constexpr uint32_t TF = SC + 2048;
constexpr uint32_t PRE = MEM + 2 * NVR * 2048;
constexpr uint32_t TA = TF + 8192;
constexpr uint32_t RX = TA + 6144;
constexpr uint32_t VX1 = RX + 2048;
constexpr uint32_t BARS = VX1 + 4096;
constexpr uint32_t PACE = BARS + 18 * 8;
constexpr uint32_t SMEM = BARS + 512;
static_assert(PRE + 14336 <= BARS, "staging");
constexpr int NW1 = P_NW1;
static_assert(SMEM <= 232448, "smem");
constexpr int B_E = 2, B_SC = 3, B_S = 4, B_O = 5, B_F = 6, B_W = 7, B_C = 9, B_K = 10, B_H = 15, B_Q = 1, B_S2 = 6, B_T2 = 9, B_P = 13, B_T = 14, B_R = 11, B_X = 12, B_V = 8;
constexpr int N_P = XE == 1 ? 416 : 384, N_R = XE ? 288 : 320, N_V = AV ? 384 : 512, N_O = AV ? 384 : 416;
constexpr int XC = 16384, X_RING = 131072, X_SC = 65536, X_TOK = 4096;
#define X_VX(i) (((i) >> 1) * 2048 + ((i) & 1) * 512)
#define X_VM(i) (X_VX(i) + 1024)
#define V_RING(n) (((n) & 1) * X_RING + ((n) & 2) * 2048)
#define V_TAG(n) ((~(n) >> 2) & 1)
}
struct RecMaps { CUtensorMap wq, wk, wv, wo, ari; int zero[40]; };

#define F_(x) __uint_as_float(x)
#define U_(x) __float_as_uint(x)
#define AR_R(q) (24 + ((q) & 1) * 16 + ((q) >> 1) * 56)
#define AR_P(q) ((q) >> 1)
#define AR_ROW(i) (24 + ((i) & 1) * 16 + ((i) & 2) * 92 + (((i) >> 2) & 7) + ((i) >> 5) * 128)
constexpr size_t AR_OFF = 32 * 262144;
__device__ __forceinline__ void ar_fetch(uint32_t dst, const CUtensorMap* m, int slot, int half, uint32_t mb) {
  asm volatile("{.reg .pred p; elect.sync _|p, 0xffffffff; @p mbarrier.arrive.expect_tx.shared.b64 _,[%4],10240;\n"
               "@p cp.async.bulk.tensor.3d.shared::cluster.global.mbarrier::complete_tx::bytes [%0],[%1,{%2,%3,%6}],[%4];\n"
               "@p cp.async.bulk.tensor.3d.shared::cluster.global.mbarrier::complete_tx::bytes [%0+5120],[%1,{%2,%5,%7}],[%4];}"
               ::"r"(dst), "l"(m), "r"(slot * 64), "r"(AR_R(half * 2)), "r"(mb), "r"(AR_R(half * 2 + 1)), "r"(AR_P(half * 2)), "r"(AR_P(half * 2 + 1)) : "memory");
}
__device__ __forceinline__ uint4 exch_b128(void* p, uint32_t x, uint32_t y, uint32_t z, uint32_t w) {
  uint4 v;
  asm volatile("{.reg .b128 s, t; .reg .b64 a,b; mov.b64 a,{%5,%6}; mov.b64 b,{%7,%8}; mov.b128 s,{a,b}; atom.relaxed.gpu.global.exch.b128 t,[%4],s;"
               " mov.b128 {a,b},t; mov.b64 {%0,%1},a; mov.b64 {%2,%3},b;}" : "=r"(v.x), "=r"(v.y), "=r"(v.z), "=r"(v.w) : "l"(p), "r"(x), "r"(y), "r"(z), "r"(w) : "memory");
  return v;
}
#define CONSUME(v) do { if ((v) == 0x7fc12345u) sts1(sb + rec::BARS + 96, 0); } while (0)
__device__ __forceinline__ uint32_t tagf(float v, uint32_t tag) { return (__float_as_uint(v) & ~1u) | tag; }
__device__ __forceinline__ uint2 ldg_b64(const void* p) { uint2 v; asm volatile("{.reg .b64 t; ld.relaxed.gpu.global.b64 t,[%2]; mov.b64 {%0,%1},t;}" : "=r"(v.x), "=r"(v.y) : "l"(p) : "memory"); return v; }
__device__ __forceinline__ void stg_b64(void* p, uint32_t x, uint32_t y) { asm volatile("{.reg .b64 t; mov.b64 t,{%1,%2}; st.relaxed.gpu.global.b64 [%0],t;}" ::"l"(p), "r"(x), "r"(y) : "memory"); }
__device__ __forceinline__ uint32_t tagbad(uint32_t x, uint32_t y, uint32_t tag) { uint32_t r; asm("lop3.b32 %0,%1,%2,%3,0x7e;" : "=r"(r) : "r"(x), "r"(y), "r"(tag)); return r; }

__device__ __forceinline__ bool anybad(uint32_t a, uint32_t b, uint32_t c, uint32_t d, uint32_t e, uint32_t f, uint32_t g, uint32_t h, uint32_t tag) {
  uint32_t r;
  asm volatile("{.reg .b32 t,u,v,w; .reg .pred p; lop3.b32 t,%1,%2,%9,0x7e; lop3.b32 u,%3,%4,%9,0x7e; lop3.b32 v,%5,%6,%9,0x7e; lop3.b32 w,%7,%8,%9,0x7e;"
               " lop3.b32 t,t,u,v,0xfe; lop3.b32 t,t,w,1,0xa8; setp.ne.u32 p,t,0; vote.sync.any.pred p,p,0xffffffff; selp.u32 %0,1,0,p;}"
               : "=r"(r) : "r"(a), "r"(b), "r"(c), "r"(d), "r"(e), "r"(f), "r"(g), "r"(h), "r"(tag));
  return r;
}
__device__ __forceinline__ bool anybad(uint32_t a, uint32_t b, uint32_t c, uint32_t d, uint32_t tag) {
  uint32_t r;
  asm volatile("{.reg .b32 t,u; .reg .pred p; lop3.b32 t,%1,%2,%5,0x7e; lop3.b32 u,%3,%4,%5,0x7e;"
               " lop3.b32 t,t,u,1,0xa8; setp.ne.u32 p,t,0; vote.sync.any.pred p,p,0xffffffff; selp.u32 %0,1,0,p;}"
               : "=r"(r) : "r"(a), "r"(b), "r"(c), "r"(d), "r"(tag));
  return r;
}
#define BAD8(r) anybad(r[0].x, r[0].z, r[1].x, r[1].z, r[2].x, r[2].z, r[3].x, r[3].z, tag)
#define BADS(r) anybad(r[0].x, r[0].y, r[1].x, r[1].y, r[2].x, r[2].y, r[3].x, r[3].y, tag)
constexpr float SCS = 0.08838834764831845f * 1.4426950408889634f / 16.f;
__device__ __forceinline__ uint32_t pkh(float lo, float hi, uint32_t tag) {
  uint32_t r;
  asm("{.reg .b32 t; cvt.rn.satfinite.f16x2.f32 t,%1,%2; lop3.b32 %0,t,0xfffffffe,%3,0xea;}" : "=r"(r) : "f"(hi), "f"(lo), "r"(tag));
  return r;
}
__device__ __forceinline__ uint32_t addh(uint32_t a, uint32_t b) { uint32_t r; asm("add.rn.f16x2 %0,%1,%2;" : "=r"(r) : "r"(a), "r"(b)); return r; }
__device__ __forceinline__ float hlo(uint32_t v) { float r; asm("{.reg .b16 a,b; mov.b32 {a,b},%1; cvt.f32.f16 %0,a;}" : "=f"(r) : "r"(v)); return r; }
__device__ __forceinline__ float hhi(uint32_t v) { float r; asm("{.reg .b16 a,b; mov.b32 {a,b},%1; cvt.f32.f16 %0,b;}" : "=f"(r) : "r"(v)); return r; }
__device__ __forceinline__ uint32_t ordh(uint32_t v) {
  uint32_t r;
  asm("{.reg .b32 m; prmt.b32 m,%1,0,0xbb99; lop3.b32 %0,%1,m,0x7fff7fff,0x78;}" : "=r"(r) : "r"(v));
  return r;
}
template <bool MASK>
__device__ __forceinline__ float4 softmax2(const uint2 (&r)[4], uint32_t mx, uint32_t my, uint32_t& k) {
  uint32_t x = addh(addh(r[0].x, r[1].x), addh(r[2].x, r[3].x)), y = addh(addh(r[0].y, r[1].y), addh(r[2].y, r[3].y));
  if (MASK) { x = addh(x, mx); y = addh(y, my); }
  asm("max.f16x2 %0,%1,%2;" : "=r"(k) : "r"(x), "r"(y));
  k = ordh(k);
  const int k0 = __reduce_max_sync(~0u, (int)(k << 16)), k1 = __reduce_max_sync(~0u, (int)k);
  const float m0 = hhi(k0 ^ ((k0 >> 31) & 0x7fff0000)) * -16.f, m1 = hhi(k1 ^ ((k1 >> 31) & 0x7fff0000)) * -16.f;
  return make_float4(ex2(fmaf(hlo(x), 16.f, m0)), ex2(fmaf(hhi(x), 16.f, m1)), ex2(fmaf(hlo(y), 16.f, m0)), ex2(fmaf(hhi(y), 16.f, m1)));
}
__device__ __forceinline__ char* mkp(uint32_t lo, uint32_t hi) { uint64_t r; asm("mov.b64 %0,{%1,%2};" : "=l"(r) : "r"(lo), "r"(hi)); return (char*)r; }
#define LO(p) ((uint32_t)(uint64_t)(p))
#define HI(p) ((uint32_t)((uint64_t)(p) >> 32))
__device__ __forceinline__ void cp16(uint32_t dst, const void* src) { asm volatile("cp.async.cg.shared.global [%0],[%1],16;" ::"r"(dst), "l"(src) : "memory"); }
__device__ __forceinline__ uint32_t xor3(uint32_t a, uint32_t b, uint32_t c) { uint32_t r; asm volatile("lop3.b32 %0,%1,%2,%3,0x96;" : "=r"(r) : "r"(a), "r"(b), "r"(c)); return r; }
__device__ __forceinline__ uint32_t mulbf(uint32_t a, uint32_t b) { uint32_t r; asm("mul.rn.bf16x2 %0,%1,%2;" : "=r"(r) : "r"(a), "r"(b)); return r; }
__device__ __forceinline__ uint32_t fmabf(uint32_t a, uint32_t b, uint32_t c) { uint32_t r; asm("fma.rn.bf16x2 %0,%1,%2,%3;" : "=r"(r) : "r"(a), "r"(b), "r"(c)); return r; }
__device__ __forceinline__ uint32_t addbf(uint32_t a, uint32_t b) { uint32_t r; asm("add.rn.bf16x2 %0,%1,%2;" : "=r"(r) : "r"(a), "r"(b)); return r; }
__device__ __forceinline__ void pv_mem(const uint32_t (&p)[4], uint32_t pm, const uint4 (&v)[4], const uint4 (&vn)[2], uint32_t (&O)[4]) {
  float o[4][4] = {{0, 0, 0, 0}, {0, 0, 0, 0}, {0, 0, 0, 0}, {0, 0, 0, 0}};
  mma16(o[0], v[0].x, v[0].y, v[0].z, v[0].w, p[0], p[1]);
  mma16(o[1], v[2].x, v[2].y, v[2].z, v[2].w, p[0], p[1]);
  mma16(o[2], v[1].x, v[1].y, v[1].z, v[1].w, p[2], p[3]);
  mma16(o[3], v[3].x, v[3].y, v[3].z, v[3].w, p[2], p[3]);
  mma16(o[0], vn[0].x, vn[0].y, vn[0].z, vn[0].w, pm, pm);
  mma16(o[1], vn[1].x, vn[1].y, vn[1].z, vn[1].w, pm, pm);
  O[0] = pk(o[0][0] + o[2][0], o[0][1] + o[2][1]); O[1] = pk(o[0][2] + o[2][2], o[0][3] + o[2][3]);
  O[2] = pk(o[1][0] + o[3][0], o[1][1] + o[3][1]); O[3] = pk(o[1][2] + o[3][2], o[1][3] + o[3][3]);
}
__device__ __forceinline__ void pv_tok(const uint32_t (&p)[4], uint32_t pm, const uint4 (&v)[4], const uint32_t (&vm)[4], uint32_t (&O)[4]) {
  float o[2][4] = {{0, 0, 0, 0}, {0, 0, 0, 0}}, sum[4] = {0, 0, 0, 0};
  const uint32_t one = 0x3f803f80u;
  mma16(sum, one, one, one, one, p[0], p[1]);
  mma16(o[0], v[0].x, v[0].y, v[0].z, v[0].w, p[0], p[1]);
  mma16(o[1], v[2].x, v[2].y, v[2].z, v[2].w, p[0], p[1]);
  mma16(sum, one, one, one, one, p[2], p[3]);
  mma16(o[0], v[1].x, v[1].y, v[1].z, v[1].w, p[2], p[3]);
  mma16(o[1], v[3].x, v[3].y, v[3].z, v[3].w, p[2], p[3]);
  mma8(sum, one, one, pm);
  mma8(o[0], vm[0], vm[1], pm);
  mma8(o[1], vm[2], vm[3], pm);
  float i0, i1;
  asm("rcp.approx.ftz.f32 %0,%1;" : "=f"(i0) : "f"(sum[0]));
  asm("rcp.approx.ftz.f32 %0,%1;" : "=f"(i1) : "f"(sum[1]));
  O[0] = pk(o[0][0] * i0, o[0][1] * i1); O[1] = pk(o[0][2] * i0, o[0][3] * i1);
  O[2] = pk(o[1][0] * i0, o[1][1] * i1); O[3] = pk(o[1][2] * i0, o[1][3] * i1);
}
__device__ __forceinline__ uint32_t sum4bf(uint32_t a, uint32_t b, uint32_t c, uint32_t d) { return addbf(addbf(a, b), addbf(c, d)); }
template <int OFF>
__device__ __forceinline__ void sta1(uint32_t a, uint32_t v, uint32_t mb) {
  asm volatile("st.async.shared::cluster.mbarrier::complete_tx::bytes.b32 [%0+%3],%1,[%2];" ::"r"(a), "r"(v), "r"(mb), "n"(OFF) : "memory");
}

__device__ __forceinline__ void wait_time(uint32_t t) { while ((int)(gtime() - t) < 0) __nanosleep(64); }
__device__ __noinline__ void rec_prefetch(const char* wmod, const char* w1, const char* x, const char* wo) {
  const int hb = blockIdx.x - 128;
  const uint32_t t0 = gtime();
  uint32_t t = t0 + PF0;
#pragma unroll 1
  for (int job = 0; job < (PFT ? 5 : 3); job++) {
    const char* p = job == 0 ? x + (6 + hb) * 65536 : job == 1 ? wmod + hb * 12288 + 4096 : job == 2 ? w1 + hb * 7168 : job == 3 ? x + hb * 8192 : wo + (1020 + hb) * 8192;
    const int n = job == 0 ? 120 - (hb & 2) * 4 : job == 3 ? 128 : 256, d = job == 0 ? 8192 : job == 1 ? 49152 : job == 2 ? 28672 : job == 3 ? 32768 : -32768;
    if (job == 3) t = t0 + PFT;
    PT(8 + job);
#pragma unroll 1
    for (int i = 0; i < n; i++) {
      wait_time(t);
      asm volatile("cp.async.bulk.prefetch.L2.global [%0], %1;" ::"l"(p), "r"(job == 2 ? 7168 : 8192) : "memory");
      p += !job && (i & 7) == 7 ? 204800 : d;
      t += job < 3 ? PFD : PFS;
      if (job && (i & 31) == 31 && ldg_rlx1(&g_fin)) return;
    }
  }
  PT(13);
}
__device__ __noinline__ void rec_helper(uint32_t sb, const bf16* cvec, const bf16* wmod, const char* w1, const bf16* b1, uint32_t t0) {
  const int tid = threadIdx.x, hb = blockIdx.x - 128;
  PT(1);
  for (int i = tid; i < 1024; i += 256) sts1(sb + i * 8, U_(rbf(silu(__bfloat162float(cvec[i])))));
  for (int i = tid; i < 2048; i += 256) g_stat[hb * 2048 + i] = make_uint4(~0u, ~0u, ~0u, ~0u);
  for (int i = tid; i < 512; i += 256) g_cnt[hb * 512 + i] = 0;
#pragma unroll 1
  for (int job = 0; job < 2; job++) {
    wait_time(t0 + PF0 + (job ? 600 : 350) * PFD);
    BAR_SYNC(rec::B_F, 256);
    PT(2 + job * 5);
    const int n8 = job ? 112 : 128, rg = tid >= n8, cg = tid - rg * n8, pitch = job ? 448 : 768;
    const uint4* p = (const uint4*)(job ? w1 + hb * 1792 : (const char*)(wmod + 2048 + hb * 1024)) + rg * pitch + min(cg, n8 - 1);
    float a1[8] = {0, 0, 0, 0, 0, 0, 0, 0}, a2[8] = {0, 0, 0, 0, 0, 0, 0, 0};
#pragma unroll 1
    for (int r0 = rg; r0 < 1024; r0 += 32) {
      uint4 v[16];
#pragma unroll
      for (int i = 0; i < 16; i++) { v[i] = ldg_rlx4(p); p += 2 * pitch; }
#pragma unroll
      for (int i = 0; i < 16; i++) {
        const float2 f = lds2f(sb + (r0 + 2 * i) * 8);
        const float w[8] = {blo(v[i].x), bhi(v[i].x), blo(v[i].y), bhi(v[i].y), blo(v[i].z), bhi(v[i].z), blo(v[i].w), bhi(v[i].w)};
#pragma unroll
        for (int e = 0; e < 8; e++) { a1[e] += f.x * w[e]; a2[e] += f.y * w[e]; }
      }
    }
    const uint32_t rd = sb + 8192;
    if (cg < n8) {
#pragma unroll
      for (int e = 0; e < 8; e++) sts2(rd + rg * 8192 + (cg * 8 + e) * 8, U_(a1[e]), U_(a2[e]));
    }
    BAR_SYNC(rec::B_F, 256);
    if (job == 0) {
      for (int i = tid; i < 1024; i += 256) g_mod[2048 + hb * 1024 + i] = rbf(F_(lds1(rd + i * 8)) + F_(lds1(rd + 8192 + i * 8)));
      BAR_SYNC(rec::B_F, 256);
      PT(6);
      if (tid == 0) { red_rel(&g_mcnt); wait_cnt(&g_mcnt, 4); }
      BAR_SYNC(rec::B_F, 256);
      for (int i = tid; i < 1024; i += 256) sts2(sb + i * 8, U_(rbf(1.f + __ldcg(g_mod + 4096 + i))), U_(__ldcg(g_mod + 3072 + i)));
    } else {
      for (int i = tid; i < 448; i += 256) {
        const int gn = hb * 896 + i * 2;
        const uint32_t bb = *(const uint32_t*)(b1 + gn);
        const float4 u = lds4f(rd + i * 16), w = lds4f(rd + 8192 + i * 16);
        ((uint2*)g_cc)[(gn >> 4) * 8 + ((gn >> 1) & 3) * 2 + ((gn >> 3) & 1)] = make_uint2(pk(u.x + w.x, u.z + w.z), pk(0.5f * (u.y + w.y + blo(bb)), 0.5f * (u.w + w.w + bhi(bb))));
      }
      PT(4);
    }
  }
}

__global__ void __cluster_dims__(2, 1, 1) __launch_bounds__(512, 1)
k_rec(const __grid_constant__ RecMaps mp, const bf16* __restrict__ mem0, const bf16* __restrict__ x, const bf16* __restrict__ cvec,
      const bf16* __restrict__ wmod, const char* __restrict__ w1, const bf16* __restrict__ b1, const char* __restrict__ wo, char* xc, int dF, int dA, int dS, int dM, int dG, int dP, int dX, int dD, int dZ, int dZ2, int dV, int dX2) {
  using namespace rec;
  extern __shared__ __align__(1024) char smem[];
  const uint32_t sb = (uint32_t)__cvta_generic_to_shared(smem);
  if ((sb & 0x3FFFF) != 1024) __trap();
  PH(0); if (threadIdx.x == 0) PT(0);
  if (threadIdx.x == 0) {
    int b = blockIdx.x;
    if (b >= 8 && b < 128) {
      const int t = (b >> 1) - 4, u = t - 32;
      b = 2 * (t < 32 ? 4 + (t & 16) + (t & 7) * 2 + ((t >> 3) & 1) : 36 + (u / 14) * 14 + (u % 7) * 2 + ((u / 7) & 1)) + (b & 1);
    }
    sts1(sb + rec::PACE + 24, b);
    const int c = blockIdx.x >> 1, l = c < 36 ? (c - 4) & 7 : (c - 36) % 7, m = c < 4 ? c : c < 36 ? (c - 4) >> 3 : (c - 36) / 7;
    const int g = c < 4 ? 15 : (l >> 1) * 4 + (l & 1) + (c < 36 ? 0 : 2);
    unsigned sm;
    asm("mov.u32 %0,%%smid;" : "=r"(sm));
    if (c < 64) g_slot[sm & 255] = 1 + FMAP;
  }
#define ROLE_REFRESH { asm volatile("mov.u32 %0,%%tid.x;" : "=r"(tid)); wid = __shfl_sync(~0u, tid >> 5, 0); b = __shfl_sync(~0u, lds1(sb + PACE + 24), 0); }
#define ROLE_VARS int tid; asm volatile("mov.u32 %0,%%tid.x;" : "=r"(tid)); \
    int wid = __shfl_sync(~0u, tid >> 5, 0), b = __shfl_sync(~0u, lds1(sb + PACE + 24), 0);
#define wg (wid >> 2)
#define iw (wid & 3)
#define h (b >> 2)
#define j (b & 3)
#define a (b & 1)
#define bb ((b >> 1) & 1)
  const uint32_t wbar = sb + BARS + 48, obar = wbar + 8;
  if (threadIdx.x == 256) {
    for (int i = 0; i < 18; i++) if (i != 12) mbar_init(sb + BARS + i * 8, i == 3 || i == 8 || i == 9 || i == 10 ? 2 : 1);
    for (int i = 0; i < 3; i++) mbar_init(sb + PACE + i * 8, 1);
    asm volatile("fence.mbarrier_init.release.cluster;" ::: "memory");
    FENCE_ASYNC_SMEM();
    mbar_expect(sb + BARS, 2048);
    mbar_expect(sb + BARS + 16, 4096);
    mbar_expect(sb + BARS + 32, 4096);
    mbar_expect(sb + BARS + 40, 4096);
  }
  __syncthreads();
  asm volatile("barrier.cluster.arrive.relaxed.aligned;" ::: "memory");
#define lane ((int)(l16 >> 4))
#define l16 (L16 & 0x1f0)
#define is7 ((L16 & 112) == 112)
#define PIN(x) __shfl_xor_sync(~0u, (uint32_t)(x), 0)
#define REFRESH() L16 = __shfl_xor_sync(~0u, L16, 0)
#define lar ((L16 & 0x180) * 8 + (L16 & 0x70))
#define X_LOAD(n, w, u) \
        asm volatile("{.reg .pred p; elect.sync _|p, 0xffffffff; @p mbarrier.arrive.expect_tx.shared.b64 _,[%2],8192;\n" \
                     "@p cp.async.bulk.shared::cluster.global.mbarrier::complete_tx::bytes [%0],[%1],8192,[%2];}" ::"r"(sb + XB + (w) * 16384 + (u) * 8192), \
                     "l"(g_h + (n) * 4096 + a * 2048 + (w) * 1024 + (u) * 512), "r"(sb + BARS + 64 + (w) * 8) : "memory")
#define lpub ((L16 & 0x30) * 64 + ((L16 >> 3) & 0x38))
#define lrow ((L16 & 0x70) + (((L16 >> 3) ^ L16) & 0x70 & ~((L16 >> 3) & 0x40) ? L16 & 0x180 : 512))

  const int role = __shfl_sync(~0u, threadIdx.x >> 7, 0);
  if (role < 2) {
    asm volatile("setmaxnreg.inc.sync.aligned.u32 %0;" ::"n"(RF_));
    ROLE_VARS
    uint32_t L16 = __shfl_sync(~0u, sb + (tid & 31) * 16, tid & 31);
    uint32_t wQ[16][4], wK[16][4], wV[NVR][4];
    uint32_t m0[2][4];
    uint32_t frag = sb + ((lane & 7) + (lane >> 4) * 8) * 128 + (((iw * 2 + ((lane >> 3) & 1)) ^ (lane & 7)) << 4);
#define QSW (SWP && !a ? 64 : 0)
    {
      const bool spare = b >= 128;
      const uint32_t t0 = gtime();
      uint4 xr[16];
      int seg = spare ? b - 126 : wg;
      const int half = spare ? wg : a;
      auto x_fetch = [&]() {
        const uint4* px = (const uint4*)x + (seg * 32 + iw * 8 + (lane >> 2)) * 128 + half * 64 + (lane & 3);
#pragma unroll
        for (int i = 0; i < 16; i++) xr[i] = __ldg(px + i * 4);
      };
      if (!spare) {
        uint4 wm[8];
        const uint4* pw = (const uint4*)(wmod + (size_t)((b >> 5) * 256 + (tid >> 3)) * 6144 + (b & 31) * 64) + (tid & 7);
        const float cs = __bfloat162float(cvec[(b >> 5) * 256 + tid]);
#pragma unroll
        for (int i = 0; i < 8; i++) wm[i] = __ldcs(pw + (size_t)i * 32 * 768);
        unsigned short mr[16];
#pragma unroll
        for (int i = 0; i < 16; i++) mr[i] = __bfloat16_as_ushort(mem0[(i & 7) * 1024 + a * 512 + tid * 2 + (i >> 3)]);
        float* sc = (float*)(smem + PRE);
        sc[tid] = rbf(silu(cs));
        PT(1);
        BAR_SYNC(B_F, 256);
        float acc[8] = {0, 0, 0, 0, 0, 0, 0, 0};
#pragma unroll
        for (int i = 0; i < 8; i++) {
          const float f = sc[i * 32 + (tid >> 3)];
          acc[0] += f * blo(wm[i].x); acc[1] += f * bhi(wm[i].x); acc[2] += f * blo(wm[i].y); acc[3] += f * bhi(wm[i].y);
          acc[4] += f * blo(wm[i].z); acc[5] += f * bhi(wm[i].z); acc[6] += f * blo(wm[i].w); acc[7] += f * bhi(wm[i].w);
        }
#pragma unroll
        for (int i = 0; i < 8; i++) { acc[i] += __shfl_xor_sync(~0u, acc[i], 8); acc[i] += __shfl_xor_sync(~0u, acc[i], 16); }
        float* red = sc + 1024;
        if ((tid & 31) < 8) {
#pragma unroll
          for (int i = 0; i < 8; i++) red[(tid >> 5) * 64 + (tid & 7) * 8 + i] = acc[i];
        }
        BAR_SYNC(B_F, 256);
        PT(2);
        if (tid < 64) {
          float t = 0;
#pragma unroll
          for (int i = 0; i < 8; i++) t += red[i * 64 + tid];
          asm volatile("st.relaxed.gpu.global.u32 [%0],%1;" ::"l"((unsigned*)g_modp + (b >> 5) * 2048 + (b & 31) * 64 + tid), "r"(U_(t) | 1u) : "memory");
        }
#pragma unroll
        for (int i = 0; i < 8; i++) m0[i >> 2][i & 3] = mr[i * 2] | ((uint32_t)mr[i * 2 + 1] << 16);
      } else {
        asm volatile("griddepcontrol.launch_dependents;");
      }
      x_fetch();
      const uint32_t md = sb + PRE + 6144, rx = mapa(sb, a ^ !spare);
      asm volatile("barrier.cluster.wait.aligned;" ::: "memory");
      if (!spare) {
        mbar_wait(sb + BARS + 88, 0);
#pragma unroll
        for (int i = 0; i < 16; i++) ldsm4t(wQ[i], (frag ^ QSW) + WO + wg * 32768 + i * 2048);
      }
      PT(4);
#pragma unroll 1
      for (int it = 0;; it++) {
        if (tid == 0) mbar_expect(sb + BARS + 104, 512);
        float c[4][4] = {{0, 0, 0, 0}, {0, 0, 0, 0}, {0, 0, 0, 0}, {0, 0, 0, 0}};
#pragma unroll
        for (int i = 0; i < 16; i++) {
          mma16(c[(i & 1) * 2], xr[i].x, 0x3f803f80u, xr[i].y, 0x3f803f80u, xr[i].x, xr[i].y);
          mma16(c[(i & 1) * 2 + 1], xr[i].z, 0x3f803f80u, xr[i].w, 0x3f803f80u, xr[i].z, xr[i].w);
        }
#pragma unroll
        for (int e = 0; e < 4; e++) c[0][e] = (c[0][e] + c[1][e]) + (c[2][e] + c[3][e]);
        const int src = (lane & 28) + (lane >> 3);
        const float sq = __shfl_sync(~0u, (lane & 4) ? c[0][1] : c[0][0], src), sm = __shfl_sync(~0u, (lane & 4) ? c[0][3] : c[0][2], src);
        if ((lane & 3) < 2) sta1<0>(rx + PRE + 10240 + (wid ^ (spare * 4)) * 64 + (lane >> 2) * 8 + (lane & 1) * 4, U_((lane & 1) ? sm : sq), rx + BARS + 104);
        mbar_wait(sb + BARS + 104, it & 1);
        const float2 ot = lds2f(sb + PRE + 10240 + wid * 64 + (lane >> 2) * 8);
        const float mean = (sm + ot.y) * (1.f / 1024);
        const float rs = rsqrtf(fmaxf((sq + ot.x) * (1.f / 1024) - mean * mean, 0.f) + 1e-5f), nm = -mean * rs;
#define NRM(v) v = pk(fmaf(blo(v), rs, nm), fmaf(bhi(v), rs, nm))
#pragma unroll
        for (int i = 0; i < 16; i++) { NRM(xr[i].x); NRM(xr[i].y); NRM(xr[i].z); NRM(xr[i].w); }
        if (!it) {
          PT(3);
#pragma unroll 1
          for (int i = 0; i < 2; i++) {
            uint4 p[4];
            for (int n = 0;; n++) {
#pragma unroll
              for (int e = 0; e < 4; e++) p[e] = ldg_rlx4(g_modp + e * 512 + i * 256 + tid);
              uint32_t ok = 1;
#pragma unroll
              for (int e = 0; e < 4; e++) ok &= p[e].x & p[e].y & p[e].z & p[e].w;
              if (__all_sync(~0u, ok) || n > SPIN_LIMIT / 16) break;
              __nanosleep(100);
            }
#define MSUM(e) (i + rbf((F_(p[0].e) + F_(p[1].e)) + (F_(p[2].e) + F_(p[3].e))))
            sts2(md + i * 2048 + tid * 8, pk(MSUM(x), MSUM(y)), pk(MSUM(z), MSUM(w)));
          }
          BAR_SYNC(B_F, 256);
          PT(5);
        }
        const int e0 = (iw * 8 + (lane >> 2)) * 8 + ((lane & 3) ^ (lane >> 2));
        uint4* dst = g_h + seg * 4096 + half * 2048;
#pragma unroll
        for (int i = 0; i < 16; i++) {
          const uint32_t ma = md + half * 1024 + (lane & 3) * 16 + i * 64;
          const uint4 sv = lds4(ma), cv = lds4(ma + 2048);
          xr[i] = make_uint4(fmabf(xr[i].x, cv.x, sv.x), fmabf(xr[i].y, cv.y, sv.y), fmabf(xr[i].z, cv.z, sv.z), fmabf(xr[i].w, cv.w, sv.w));
        }
        if (!spare) {
#pragma unroll
          for (int i = 0; i < 16; i++) sts4(sb + WO + wg * 32768 + (e0 ^ ((i & 1) * 4)) * 16 + (i >> 1) * 4096, xr[i].x, xr[i].y, xr[i].z, xr[i].w);
          break;
        }
#pragma unroll
        for (int i = 0; i < 16; i++) dst[(e0 ^ ((i & 1) * 4)) + (i >> 1) * 256] = xr[i];
        seg += 4;
        if (seg < 64) x_fetch();
        FENCE_ASYNC();
        BAR_SYNC(B_F, 256);
        if (tid == 0) red_rlx(g_hf + b - 128);
        if (seg >= 64) break;
      }
      if (spare) { rec_helper(sb, cvec, wmod, w1, b1, t0); return; }
      PH(1); PH(2); PT(6);
    }
    ROLE_REFRESH
    mbar_wait(wbar, 0);
    PT(7);
#pragma unroll
    for (int i = 0; i < 16; i++) ldsm4t(wK[i], (frag ^ QSW) + XB + wg * 32768 + i * 2048);
#pragma unroll
    for (int i = 0; i < NVR; i++) ldsm4t(wV[i], frag + MEM + (wg * NVR + i) * 2048);
    FENCE_ASYNC_SMEM();
    PH(3); PT(8);
    CLUSTER_SYNC();
    PT(9);
#pragma unroll
    for (int i = 0; i < 2; i++) {
      const int k = tid * 2 + i, m = (k >> 3) & 3, r = k & 7;
      sts4(sb + MEM + (k >> 5) * 640 + (r == m ? 512 : m * 128) + r * 16, m0[i][0], m0[i][1], m0[i][2], m0[i][3]);
    }
    if (lane < 8) {
      sts4(sb + ARO + wid * 640 + (lane < 4 ? lane * 144 : 512 + l16), 0x3f803f80, 0x3f803f80, 0x3f803f80, 0x3f803f80);
#pragma unroll
      for (int i = 0; i < 2; i++) sts4(sb + MEM + (wid * 2 + i) * 640 + (lane < 4 ? lane * 144 : 512 + l16), 0x42004200, 0x42004200, 0x42004200, 0x42004200);
    }
#define ownv ((iw >> 1) == a)
#define owner (SWP ? iw >= 2 : ownv)
#define vfin ((wid >> 1) == a)
#define oi (wid & 1)
    frag += wg * NVS * 2048;
    {
      const uint32_t rsb = mapa(sb, owner ? a : a ^ 1);
      const uint32_t pp = rsb + PK + (owner ? 0 : 12288) + (oi * 2048 + wg * 1024) + l16;
      const uint32_t mb = sb + MEM + wg * 5120;
      sts4(L16 + TF + wid * 512, mb + lrow, owner ? L16 + (lane >> 4) * (RK - RQ - 256) + RQ + oi * 1024 + wg * 256 : rsb + RQ + oi * 1024 + 512 + wg * 256 + (l16 >> 2),
           L16 + OB, frag);
      sts4(L16 + TF + 4096 + wid * 512, sb + WO + (wid >> 1) * 16384 + ((lane & 7) + (lane >> 4) * 8) * 128 + ((((wid & 1) * 4 + ((lane >> 3) & 1)) ^ (lane & 7)) << 4),
           sb + ARO + wid * 640 + lrow, pp, LO(xc) + h * 262144 + (bb * 2 + (iw >> 1)) * XC + X_VM(0) + oi * 2048 + a * 256 + (l16 >> 1));
    }
    uint32_t tp = L16 + TF + wid * 512;
    auto park_ptr = [&]() { return lds1(tp + 4096 + 8); };
    auto park_w = [&](const uint32_t* w, int m, uint32_t d) {
      if (SWP && m == 2) d += (sb & 0x1000000) ? 0 : owner ? 0x1003000 : -0x1003000;
      if (m == 2 ? ownv : owner) {
        sts4(d + m * 4096, w[0], w[1], w[2], w[3]); sts4(d + m * 4096 + 512, w[4], w[5], w[6], w[7]);
      } else {
        const uint32_t pb = (d & 0xff000000u) | (1024 + BARS + (m ? 24 + m * 8 : 16));
        sta4(d + m * 4096, w, pb); sta4(d + m * 4096 + 512, w + 4, pb);
      }
    };
    auto park = [&](const float* f, int m, int n, uint32_t d) {
      uint32_t w[8];
#pragma unroll
      for (int i = 0; i < 8; i++) w[i] = pk(f[2 * i], f[2 * i + 1]);
      park_w(w, m, d);
    };
#define D64(lo) (0x4000004000000000ull | (uint32_t)(lo))
#define XD(i) D64(x | (((i) >> 2) * 256 + ((i) & 3) * 2))
    auto xdesc = [&](uint32_t xb) { return ((uint32_t)__shfl_sync(~0u, 1024 + xb + wg * 16384, 0) >> 4) | 0x10000u; };
    auto rs_issue = [&](float* acc, const uint32_t (&w)[16][4], uint32_t xb, bool fence) {
      const uint32_t x = xdesc(xb);
      if (fence) WG_FENCE();
      wgmma_rs_n32_z(acc, w[0], XD(0));
#pragma unroll
      for (int i = 1; i < 16; i++) wgmma_rs_n32(acc, w[i], XD(i), 1);
      WG_COMMIT();
    };
    auto v_issue = [&](float* acc, uint32_t xb, bool fence) {
      const uint32_t dv = ((uint32_t)__shfl_sync(~0u, 1024 + WVS + wg * NVS * 2048, 0) >> 4) | 0x10000u, x = xdesc(xb);
      if (fence) WG_FENCE();
      wgmma_rs_n32_z(acc, wV[0], XD(0));
#pragma unroll
      for (int i = 1; i < VRF; i++) wgmma_rs_n32(acc, wV[i], XD(i), 1);
#pragma unroll
      for (int i = NVR; i < 16; i++) wgmma_ssT_n32(acc, D64(dv + (i - NVR) * 128), XD(i), 1);
#pragma unroll
      for (int i = VRF; i < NVR; i++) wgmma_rs_n32(acc, wV[i], XD(i), 1);
      WG_COMMIT();
    };
    uint32_t mA;
    auto vk_pass = [&](int n, uint32_t d, uint32_t xb, bool steady) {
      float acc[16], acc2[16];
      v_issue(acc, xb, true);
      rs_issue(acc2, wK, xb, false);
      if (steady || n) mbar_wait(sb + BARS + 80, (n - 1) & 1);
      WG_WAIT(1);
      park(acc, 2 - !!KVO, n, d);
      mA = lds1(tp); if (NF) frag = lds1(tp + 12);
      if (steady) BAR_ARRIVE(B_K, 320);
      WG_WAIT(0);
      park(acc2, 1 + !!KVO, n, d);
    };
    PT(10);
#pragma unroll 1
    for (int n = 0; n < 2; n++) {
      float acc[16];
      asm volatile("" : "+r"(wid));
      rs_issue(acc, wQ, n * XB, true);
      if (n) {
        BAR_SYNC(B_C, 320);
        PT(12);
        mbar_wait(sb + BARS + 24, 0);
      } else {
#pragma unroll
        for (int i = 0; i < 8; i++) {
          const uint4 v = lds4(L16 + WO + 32768 + wid * 4096 + i * 512);
          sts4(L16 + XB + wid * 4096 + i * 512, v.x, v.y, v.z, v.w);
        }
      }
      WG_WAIT(0); park(acc, 0, n, park_ptr());
      FENCE_ASYNC_SMEM();
      vk_pass(n, park_ptr(), n * XB, false);
      if (n) break;
      PT(11);
      BAR_SYNC(B_C, 320);
      if (tid == 0) {
        mbar_expect(obar, 65536);
#pragma unroll 1
        for (int i = 0; i < 4; i++) tma2d(sb + WO + i * 16384, &mp.wo, j * 256 + i * 64, h * 128, obar);
      }
    }
    static_assert(WO == 0, "x");
    {
      BAR_ARRIVE(B_P, N_P); if (!HX) BAR_ARRIVE(B_X, 320); if (XE != 1) BAR_ARRIVE(B_Q, 288);
    }
    PT(13);
    mbar_wait(obar, 0);
    PH(4); PT(14);
    ROLE_REFRESH
    for (int s = 0; s < 64; s++) {
      asm volatile("" : "+r"(tp), "+r"(wid));
      asm volatile("mov.u32 %0,%%cluster_ctarank;" : "=r"(b));
      uint32_t vS[NVS][4], bf[8][4];
      static_assert(NVR == 5, "schedule");
#define VLD(k) ldsm4t(vS[(k) - NVR], frag + WVS + ((k) - NVR) * 2048)
#define BLD(t) ldsm4t(bf[t], mA + (t) * 640)
#define VMMA(c, w, i) mma16(c, (w)[0], (w)[1], (w)[2], (w)[3], bf[(i) >> 1][((i) & 1) * 2], bf[(i) >> 1][((i) & 1) * 2 + 1])
#define VS_(c, k) VMMA(c, vS[(k) - NVR], k)
#define QK(i) VMMA(cQ, wQ[i], i); VMMA(cK, wK[i], i)
#define PREV if (NF) { VLD(13); VLD(12); if (NF > 2) VLD(11); } else { VLD(15); VLD(14); }
      if (NF) { VLD(15); VLD(14); }
      if (s > 0) BAR_SYNC(B_R, N_R);
      float cV[4] = {0, 0, 0, 0}, cW[4] = {0, 0, 0, 0};
      {
        float cQ[4] = {0, 0, 0, 0}, cK[4] = {0, 0, 0, 0};
        BLD(7); BLD(6); BLD(5); BLD(4); if (NB0 > 4) BLD(3);
        SCHED_FENCE(47);
        QK(15); if (NF) VS_(cV, 15);
        QK(14); if (NF) VS_(cV, 14);
        QK(13); QK(12);
        SCHED_FENCE(51);
        if (NB0 < 5) BLD(3);
        BLD(2); BLD(1); BLD(0);
        const uint32_t rm = lds1(tp + 4);
        if (!NF) frag = lds1(tp + 12);
        QK(11); QK(10); QK(9); QK(8); QK(7);
        if (PV0 == 6) { SCHED_FENCE(48); PREV }
        QK(6); QK(5);
        if (PV0 == 4) { QK(4); SCHED_FENCE(48); PREV } else { QK(4); }
        QK(3); QK(2); QK(1); QK(0);
        const uint32_t w0 = pk(cQ[0] * SCS, cQ[1] * SCS), w1 = pk(cQ[2] * SCS, cQ[3] * SCS), w2 = pk(cK[0], cK[1]), w3 = pk(cK[2], cK[3]);
        if (owner) {
          stsm4(rm, w0, w1, w2, w3);
          BAR_ARRIVE(B_E, 256);
        } else {
          const uint32_t mm = (rm & 0xff000000u) | (1024 + BARS);
          sta1<0>(rm, w0, mm); sta1<128>(rm, w1, mm);
          sta1<RK - RQ>(rm, w2, mm); sta1<RK - RQ + 128>(rm, w3, mm);
        }
        if (wid == 2) TS(0);
      }
      uint4 t1;
      uint32_t oA, wo[16][4];
      {
        if (NF == 0) {
          VLD(13); VLD(12);
          VS_(cW, 15); VS_(cV, 14); VLD(11); VMMA(cW, wV[0], 0); VLD(10); VMMA(cV, wV[1], 1); VLD(9);
          VMMA(cW, wV[2], 2); VLD(8); VMMA(cV, wV[3], 3); VLD(7); VMMA(cW, wV[4], 4); VS_(cV, 13); VLD(6); VS_(cW, 12); VLD(5);
          VS_(cV, 11);
        } else {
          if (NF < 3) VLD(11);
          VLD(10);
          VS_(cW, 13); VLD(9); VS_(cV, 12); VLD(8); VLD(7); VMMA(cW, wV[0], 0); VMMA(cV, wV[1], 1); VLD(6);
          VMMA(cW, wV[2], 2); VMMA(cV, wV[3], 3); VLD(5); VMMA(cW, wV[4], 4); VS_(cV, 11);
        }
        VS_(cW, 10); VS_(cV, 9); VS_(cW, 8); VS_(cV, 7); VS_(cW, 6); VS_(cV, 5);
#pragma unroll
        for (int e = 0; e < 4; e++) cV[e] += cW[e];
        const uint32_t ex = tp + (RX - TF) - wg * 2048;
        t1 = lds4(tp + 4096 + (T1L ? vS[3][0] & dZ : 0));
        oA = lds1(tp + 8 + (s & dZ));
        if (wg) {
          sts4(ex, U_(cV[0]), U_(cV[1]), U_(cV[2]), U_(cV[3]));
          BAR_ARRIVE(B_T2, 256);
        }
#pragma unroll
        for (int i = 0; i < VCO; i++) ldsm4t(wo[i], (t1.x ^ ((i & 1) * 32)) + (i >> 1) * 2048);
        if (!wg) {
          BAR_SYNC(B_T2, 256);
          const float4 u = lds4f(ex);
          stg_b64(mkp(t1.w ^ ((s & 1) * X_RING), HI(xc)), (pk(cV[0] + u.x, cV[1] + u.y) & ~1u) | (((s >> 1) + 1) & 1), pk(cV[2] + u.z, cV[3] + u.w));
        }
      }
      if (s == 63) break;
      {
        const uint32_t woA = t1.x, woB = woA ^ 32;
#pragma unroll
        for (int i = VCO; i < NW0; i++) ldsm4t(wo[i], ((i & 1) ? woB : woA) + (i >= WCH ? wo[(i - WCH + NWP) % NWP][0] & dZ : 0) + (i >> 1) * 2048);
        BAR_SYNC(B_S, 416);
        float inv0, inv1;
        uint32_t p[4], pm;
        const uint32_t pa = oA + (SC - OB), one = 0x3f803f80u;
#define P_LOAD ldsm4t(p, pa); asm volatile("ldmatrix.sync.aligned.m8n8.x1.trans.shared.b16 {%0},[%1];" : "=r"(pm) : "r"(pa + 512) : "memory");
        if (s < 62) {
          float acc[16];
          rs_issue(acc, wQ, XB, true);
          mbar_wait(sb + BARS + 24, (s + 1) & 1);
          WG_WAIT(0);
          uint32_t qw[8];
#pragma unroll
          for (int i = 0; i < 8; i++) qw[i] = pk(acc[2 * i], acc[2 * i + 1]);
#pragma unroll
          for (int i = NW0; i < NW1; i++) ldsm4t(wo[i], ((i & 1) ? woB : woA) + (i >> 1) * 2048);
          BAR_SYNC(B_V, N_V);
          if (RSO) { P_LOAD }
          park_w(qw, 0, t1.z + (RSO == 1 ? pm & dZ : 0));
        } else {
#pragma unroll
          for (int i = NW0; i < NW1; i++) ldsm4t(wo[i], ((i & 1) ? woB : woA) + (i >> 1) * 2048);
          BAR_SYNC(B_V, N_V);
          if (RSO) { P_LOAD }
        }
#pragma unroll
        for (int i = NW1; i < NWP; i++) ldsm4t(wo[i], ((i & 1) ? woB : woA) + (i >> 1) * 2048);
        {
          float sum[4] = {0, 0, 0, 0}, su2[4] = {0, 0, 0, 0};
          if (!RSO) { P_LOAD }
          mma16(sum, one, one, one, one, p[0], p[1]);
          mma16(su2, one, one, one, one, p[2], p[3]);
          mma8(sum, one, one, pm);
          inv0 = sum[0] + su2[0]; inv1 = sum[1] + su2[1];
          SCHED_FENCE(57);
        }
        BAR_SYNC(B_O, N_O);
        float c[2][4] = {{0, 0, 0, 0}, {0, 0, 0, 0}};
        uint32_t o[4][4];
#pragma unroll
        for (int i = 0; i < NOP_; i++) ldsm4t(o[i], oA + i * 512);
        SCHED_FENCE(46);
        asm("rcp.approx.ftz.f32 %0,%0;" : "+f"(inv0));
        asm("rcp.approx.ftz.f32 %0,%0;" : "+f"(inv1));
#pragma unroll
        for (int i = 0; i < 16; i++) {
          mma16(c[i & 1], wo[i][0], wo[i][1], wo[i][2], wo[i][3], o[i >> 2][i & 2], o[i >> 2][(i & 2) + 1]);
          if (i == 1 && NOP_ < 3) ldsm4t(o[2], oA + 1024);
          if (i == 3 && NOP_ < 4) ldsm4t(o[3], oA + 1536);
          if (i + NWP < 16) ldsm4t(wo[(i + NWP) & 15], (((i + NWP) & 1) ? woB : woA) + ((i + NWP) >> 1) * 2048);
        }
        stsm4(t1.y, pk(c[0][0] * inv0, c[0][1] * inv1), pk(c[0][2] * inv0, c[0][3] * inv1), pk(c[1][0] * inv0, c[1][1] * inv1), pk(c[1][2] * inv0, c[1][3] * inv1));
      }
      const uint32_t d = park_ptr();
      BAR_SYNC(B_W, 384);
      if (s < 62) {
        vk_pass(s + 2, d, XB, true);
        if (XE == 2) BAR_ARRIVE(B_Q, 288);
        BAR_ARRIVE(B_P, N_P); if (!HX) BAR_ARRIVE(B_X, 320);
        TS(10);
      } else {
        mA = lds1(tp); if (NF) frag = lds1(tp + 12);
      }
    }
  } else if (role == 3) {
    asm volatile("setmaxnreg.dec.sync.aligned.u32 24;");
    if (blockIdx.x >= 128) return;
    ROLE_VARS
    const uint32_t L16 = sb + (tid & 31) * 16;
    asm volatile("barrier.cluster.wait.aligned;" ::: "memory");
    CLUSTER_SYNC();
    sts1(sb + PACE + 36, LO(xc) + h * 262144 + X_VM(0));
    auto vm_stage = [&](int s) {
      if (AV) return;
      const uint32_t tag = ((s >> 1) + 1) & 1;
      const char* xm = mkp(lds1(sb + PACE + 36) + (s & 1) * X_RING + iw * XC + (l16 >> 1), HI(xc));
      uint2 m[4];
      CONSUME(LO(xm));
      BAR_SYNC(B_S2, 256);
      if (dZ2 > 1) { const uint32_t c = clk(); while (clk() - c < (uint32_t)dZ2) {} }
      int it = 0;
      while (true) {
#pragma unroll
        for (int i = 0; i < 4; i++) m[i] = ldg_b64(xm + (i >> 1) * 2048 + (i & 1) * 256);
        sts4(L16 + VN + iw * 512, m[0].x, m[0].y, m[1].x, m[1].y);
        sts4(L16 + VN + iw * 512 + 2048, m[2].x, m[2].y, m[3].x, m[3].y);
        if (HV || !anybad(m[0].x, m[1].x, m[2].x, m[3].x, tag)) break;
        RP(2);
        if (++it > SPIN_LIMIT) __trap();
      }
      if (s < 63) BAR_ARRIVE(B_V, 512); else BAR_ARRIVE(B_V, 256);
    };
    if (iw == 0) {
      wait_cnt(&g_hcnt, 128);
#pragma unroll 1
      for (int s = 0; s < 63; s++) {
        if (s < 62) for (int it = 0; ldg_rlx1(g_hf + (s & 3)) <= (s >> 2); it++) if (it > SPIN_LIMIT) __trap();
        if (XE == 1) BAR_SYNC(B_P, N_P); else if (XE == 2) BAR_SYNC(B_Q, 288); else if (s) BAR_SYNC(B_R, 320); else BAR_SYNC(B_Q, 288);
        if (s < 62) { X_LOAD(s + 2, 0, 0); X_LOAD(s + 2, 1, 0); X_LOAD(s + 2, 0, 1); X_LOAD(s + 2, 1, 1); }
        if (s >= 7) {
          const uint32_t zo = b * 160 + l16;
          if (l16 < 160) CONSUME(exch_b128(xc + AR_OFF + AR_ROW(zo >> 7) * 1024 + (zo & 127) + ((s + 1) & 7) * 128, 0, 0, 0, 0).x);
          __syncwarp();
        }
        if (s < 62) { mbar_wait(sb + BARS + 64, s & 1); mbar_wait(sb + BARS + 72, s & 1); }
        BAR_ARRIVE(B_S, 416);
        vm_stage(s);
        if (!AV) BAR_ARRIVE(B_O, 416);
        BAR_SYNC(B_W, 384);
        FENCE_ASYNC_SMEM();
        asm volatile("{.reg .pred p; elect.sync _|p, 0xffffffff; @p cp.reduce.async.bulk.tensor.3d.global.shared::cta.add.bulk_group [%0,{%1,%2,%4}],[%3];}"
                     ::"l"(&mp.ari), "r"((s & 7) * 64), "r"(AR_R(j)), "r"(sb + ARO), "r"(AR_P(j)) : "memory");
        BULK_COMMIT();
        asm volatile("st.relaxed.gpu.global.u32 [%0],%1;" ::"l"(g_tm + (s & 1) * 128 + b), "r"(gtime()) : "memory");
        TS(3);
        BULK_WAIT_READ(0);
      }
      if (!XE) BAR_ARRIVE(B_R, 320);
    } else if (iw == 1) {
      const uint32_t pc = sb + MEM + (lane >> 2) * 640 + (lane & 3) * 144 + (lane & 12), pd = sb + MEM + (lane & 15) * 640 + 576 + (lane & 3) * 16 + (lane & 12);
      uint32_t T = 0, par = 0;
      int est = dA;
#pragma unroll 1
      for (int s = 0; s < 63; s++) {
        if (s) {
          const uint4 tm = ldg_rlx4((const char*)g_tm + ((s + 1) & 1) * 512 + l16);
          const int t0 = tm.x - T, t1 = tm.y - T, t2 = tm.z - T, t3 = tm.w - T;
          const int e = max(dF + (__reduce_add_sync(~0u, (t0 + t1) + (t2 + t3)) >> 7), dV + __reduce_max_sync(~0u, max(max(t0, t1), max(t2, t3))));
          if (s > 1) est += max(min(e >> 2, dP), -dP);
          T += (s == 1 || e > dM ? e : 0) + est;
        }
        vm_stage(s);
        BAR_SYNC(B_W, 384);
        SCHED_FENCE(70);
        const uint32_t tW = gtime();
        if (s == 0) T = tW + 800;
        const uint32_t te = tW + min(max((int)(T - tW), dD), 2000);
        while ((int)(gtime() - te) < 0) {}
        TS(7);
        int it = 0;
        while (true) {
          ar_fetch(sb + MEM, &mp.ari, s & 7, a, sb + BARS + 112);
          mbar_wait(sb + BARS + 112, par);
          par ^= 1;
          const uint32_t n0 = lds1(pc), n1 = lds1(pc + 5120), n2 = lds1(pd);
          if (!__any_sync(~0u, (tagbad(n0, n1, 0x42004200) | (n2 ^ 0x42004200)) != 0)) break;
          RP(0);
          if (++it > SPIN_LIMIT) __trap();
        }
        BAR_ARRIVE(B_R, N_R);
        TS(11);
      }
    } else {
#define V_LOAD(n) do { if (lane == 0) mbar_expect(sb + BARS + 8, 8192); __syncwarp(); \
        if (lane < 16) bulk_ld(sb + ((lane & 2) ? VX1 : VX0) + (lane & 1) * 2048 + (lane >> 2) * 512, \
                               xc + h * 262144 + V_RING(n) + (lane >> 2) * XC + X_VX(lane & 3), 512, sb + BARS + 8); __syncwarp(); } while (0)
      uint32_t src = L16 + PK + (iw & 1) * 2048;
#define qd (L16 + (lane >> 4) * 256 + QT + (iw & 1) * 1024)
#define vd (LO(xc) + h * 262144 + j * XC + (iw & 1) * 2048 + l16)
#define FINISH [&](int n, int m) { \
_Pragma("unroll") \
        for (int i = 1; i >= 0; i--) { \
          const uint32_t p = src + m * 4096 + i * 512; \
          uint4 u = lds4(p); \
          const uint4 w = lds4(p + 1024), y = lds4(p + 12288), z = lds4(p + 13312); \
          u = make_uint4(sum4bf(u.x, w.x, y.x, z.x), sum4bf(u.y, w.y, y.y, z.y), sum4bf(u.z, w.z, y.z, z.z), sum4bf(u.w, w.w, y.w, z.w)); \
          if (m == 2) stg_b128(mkp(vd ^ V_RING(n), HI(xc)) + i * 512, (u.x & ~1u) | V_TAG(n), u.y, u.z, u.w); \
          else stsm4(qd + (n & 1) * 4096 + m * 2048 + i * 256, u.x, u.z, u.y, u.w); \
          SCHED_FENCE(71 + m * 2 + i); \
        } \
      }
#pragma unroll 1
      for (int n = 0; n < 64; n++) {
        src = PIN(src);
        b = __shfl_sync(~0u, lds1(sb + PACE + 24), 0);
        const uint32_t L16 = src - PK - (iw & 1) * 2048;
        auto finish = FINISH;
        if (n < 2) { if (n) BAR_SYNC(B_X, 320); else BAR_SYNC(B_C, 320); }
        mbar_wait(sb + BARS + 16, n & 1);
        finish(n, 0);
        __syncwarp();
        if (lane == 0) mbar_arrive_cl(mapa(sb, a ^ 1) + BARS + 24);
        if (n > 1) BAR_SYNC(B_K, 320);
        mbar_wait(sb + BARS + (KVO ? 32 : 40), n & 1);
        finish(n, 2 - !!KVO);
        if (n > 1) BAR_SYNC(B_X, 320);
        mbar_wait(sb + BARS + (KVO ? 40 : 32), n & 1);
        finish(n, 1 + !!KVO);
        BAR_SYNC(B_T, 64);
        if (lane == 0) {
          if (iw == 2 && n < 63) { mbar_expect(sb + BARS + 16, 4096); mbar_expect(sb + BARS + 32, 4096); mbar_expect(sb + BARS + 40, 4096); }
          mbar_arrive_cl(mapa(sb, a ^ 1) + BARS + 80);
        }
        __syncwarp();
        if (n) {
          vm_stage(n - 1);
          BAR_SYNC(B_W, 384);
        } else {
          BAR_SYNC(B_C, 320);
        }
        if (iw == 2) V_LOAD(n);
      }
#undef qd
#undef vd
    }
    { ROLE_REFRESH }
    vm_stage(63);
  } else {
    asm volatile("setmaxnreg.dec.sync.aligned.u32 %0;" ::"n"(RA_));
    if (blockIdx.x >= 128) { if (threadIdx.x == 256) rec_prefetch((const char*)wmod, w1, (const char*)x, wo); return; }
    ROLE_VARS
    uint32_t L16 = __shfl_sync(~0u, sb + (tid & 31) * 16, tid & 31);
    if (wid == 9) {
      for (int i = b * 80 + (tid & 31); i < b * 80 + 80; i += 32) ((uint4*)(xc + AR_OFF))[AR_ROW(i >> 6) * 64 + (i & 63)] = make_uint4(0, 0, 0, 0);
      if (b == 0) g_fin = 0;
      FENCE_ASYNC();
      __syncwarp();
      if (tid == 288) red_rlx(&g_hcnt);
    }
    if (tid == 256) {
      const int col = h * 128 + bb * 64;
#pragma unroll 1
      for (int c = 0; c < 12 + WIN; c++) {
        const uint32_t mb = sb + PACE + (c % WIN) * 8;
        if (c >= WIN) mbar_wait(mb, (c / WIN - 1) & 1);
        PT(16 + c);
        if (c == 3 + WIN) asm volatile("mbarrier.arrive.shared.b64 _,[%0];" ::"r"(sb + BARS + 88) : "memory");
        if (c >= 12) continue;
        mbar_expect(mb, 16384);
        if (c < 8) tma2d(sb + (c >> 2) * XB + (c & 3) * 16384, (c & 4) ? &mp.wk : &mp.wq, col, a * 512 + (c & 3) * 128, mb);
        else
#pragma unroll 1
          for (int i = (c & 1) * 8; i < (c & 1) * 8 + 8; i++) {
            const int w = (c - 8) >> 1;
            tma2d(i < NVR ? sb + MEM + (w * NVR + i) * 2048 : sb + WVS + (w * NVS + i - NVR) * 2048, &mp.wv, col, a * 512 + w * 256 + i * 16, mb);
          }
      }
      asm volatile("mbarrier.arrive.shared.b64 _,[%0];" ::"r"(wbar) : "memory");
      for (int c = 0; c < 4; c++) tma2d_pf(&mp.wo, j * 256 + c * 64, h * 128);
      for (int i = 0; i < 3; i++) asm volatile("mbarrier.inval.shared.b64 [%0];" ::"r"(sb + PACE + i * 8) : "memory");
    }
    __syncwarp();
    asm volatile("barrier.cluster.wait.aligned;" ::: "memory");
    CLUSTER_SYNC();
#define pr (L16 + SC)
    {
      const int lim = j * 8 + iw * 2 - (lane & 7) - (lane & 8) * 2;
      const bool mk = L16 & 256;
      const int rw = lane >> 2;
      sts4(L16 + TA + iw * 512,
           iw != 2 ? L16 + KT + (iw & 1) * 256 + (lane >> 4) * 256 : sb + RK + (L16 & 0x80) * 2 + ((L16 >> 1) & 0x80) + (L16 & 0x70),
           L16 + QT + (lane >> 3) * 384, sb + SC + min(lane >> 3, 2) * 256 + (L16 & 0x70) + iw * 4, L16 + (lane >> 4) * 256 + QT + (iw >> 1) * 1024 + (iw & 1) * 256);
      sts4(L16 + TA + 2048 + iw * 512, mk ? 0u : (lim < 0 ? 0xfc00u : 0u) | (lim < -1 ? 0xfc000000u : 0u),
           mk ? 0xfc00fc00u : (lim < 8 ? 0xfc00u : 0u) | (lim < 7 ? 0xfc000000u : 0u),
           ((h * 2 + (iw >> 1)) * 1024 + (j * 8 + rw) * 8 + (((iw & 1) * 4 + (lane & 3)) ^ rw)) * 16, sb + OT + iw * 512 + (L16 & 0x70) * 4 + ((L16 >> 3) & 0x30));
    }
    {
      const uint32_t xh = LO(xc) + h * 262144, xs = xh + X_SC + iw * 1024 + min(lane, 16 + (lane & 7)) * 8;
      sts4(L16 + TA + 4096 + iw * 512, xh + X_SC + j * 256 + iw * 64 + lpub, xs, dS, iw != 2 ? 0 : U_(SCS));
      sts1(L16 + TA + 12 + iw * 512, xs + X_TOK + j * 4096);
    }
    uint32_t tA = L16 + TA + iw * 512;
#define tw (tA - L16 != TA + 1024)
#define XP_(lo) mkp(lo, HI(xc))
    auto publish = [&](char* d, const uint2& w) { stg_b64(d, w.x, w.y); };
    BAR_SYNC(B_P, N_P);
    for (int s = 0; s < 64; s++) {
      asm volatile("" : "+r"(L16), "+r"(tA));
      const uint32_t tag = ((s >> 1) + 1) & 1, ring = (s & 1) * X_RING;
      const uint4 t0 = lds4(tA);
      const uint4 tx = lds4(tA + 4096);
      const uint32_t xo = tx.x ^ ring, xs = tx.y ^ ring;
      const float gm = F_(tx.w);
      const uint32_t qA = t0.y + (ring >> 5);
      uint32_t c0;
      uint2 ts[4];
      uint4 v[4];
      uint32_t af[2][4], qt[4][4];
      {
        const uint32_t aA = t0.x + (tw ? ring >> 5 : 0);
        uint32_t ql[2][4], qr[2][4];
        uint2 pw_;
        float c[4] = {0, 0, 0, 0}, d[4] = {0, 0, 0, 0};
        if (s == PDS) asm volatile("griddepcontrol.launch_dependents;");
#pragma unroll
        for (int i = 0; i < 4; i++) ldsm4t(qt[i], qA + i * 128);
        mbar_wait(sb + BARS + 8, s & 1);
        TS(4);
        BAR_SYNC(B_E, 256);
#define PACK(c) make_uint2(pkh(fmaf(c[2], gm, c[0] * SCS), fmaf(c[3], gm, c[1] * SCS), tag), pkh(c[2] * SCS, c[3] * SCS, tag))
#define SMMA(x, t, q, i) mma16(x, af[t][0], af[t][1], af[t][2], af[t][3], q[t][i], q[t][i + 1])
        ldsm4t(ql[0], L16 + RQ); ldsm4t(ql[1], L16 + RQ + 1024); ldsm4t(af[0], aA); ldsm4t(af[1], aA + 1024);
        CONSUME(xo);
#define QSUM(t, i) addbf(addbf(ql[t][i], ql[t][i + 2]), addbf(qr[t][i], qr[t][i + 2]))
#define STAIL mma16(c, af[0][0], af[0][1], af[0][2], af[0][3], QSUM(0, 0), QSUM(0, 1)); mma16(d, af[1][0], af[1][1], af[1][2], af[1][3], QSUM(1, 0), QSUM(1, 1));
        if (tw) {
          mbar_wait(sb + BARS, s & 1);
          TS(8);
          ldsm4t(qr[0], L16 + RQ + 512); ldsm4t(qr[1], L16 + RQ + 1536);
          STAIL
          pw_ = make_uint2(pkh(c[0] + d[0], c[1] + d[1], tag), pkh(c[2] + d[2], c[3] + d[3], tag));
        } else {
          uint32_t ar[2][4];
          mbar_wait(sb + BARS, s & 1);
          ldsm4t(qr[0], L16 + RQ + 512); ldsm4t(ar[0], aA + 512); ldsm4t(qr[1], L16 + RQ + 1536); ldsm4t(ar[1], aA + 1536);
#pragma unroll
          for (int i = 0; i < 8; i++) af[i >> 2][i & 3] = addbf(af[i >> 2][i & 3], ar[i >> 2][i & 3]);
          STAIL
          pw_.x = pw_.y = pkh((c[0] + c[2]) + (d[0] + d[2]), (c[1] + c[3]) + (d[1] + d[3]), tag);
        }
        publish(XP_(xo), pw_);
        c0 = clk() + tx.z;
        TS(1);
      }
      uint2 r[4];
      bool vbad;
      uint32_t xm;
      uint4 vn[2];
#define TOKS(i) { float e0[4] = {0, 0, 0, 0}, e1[4] = {0, 0, 0, 0}; \
        mma16(e0, af[0][0], af[0][1], af[0][2], af[0][3], qt[i][0], qt[i][1]); mma16(e1, af[0][0], af[0][1], af[0][2], af[0][3], qt[i + 1][0], qt[i + 1][1]); \
        mma16(e0, af[1][0], af[1][1], af[1][2], af[1][3], qt[i][2], qt[i][3]); mma16(e1, af[1][0], af[1][1], af[1][2], af[1][3], qt[i + 1][2], qt[i + 1][3]); \
        ts[i] = PACK(e0); ts[i + 1] = PACK(e1); }
      {
        float e[4][4];
#pragma unroll
        for (int i = 0; i < 4; i++) {
          e[i][0] = e[i][1] = e[i][2] = e[i][3] = 0.f;
          mma16(e[i], af[0][0], af[0][1], af[0][2], af[0][3], qt[i][0], qt[i][1]);
        }
#pragma unroll
        for (int i = 0; i < 4; i++) mma16(e[i], af[1][0], af[1][1], af[1][2], af[1][3], qt[i][2], qt[i][3]);
        SCHED_FENCE(55);
        if (s < 63) BAR_ARRIVE(B_S, 416);
        SCHED_FENCE(58);
        v[0] = lds4(tA + (VX0 - TA)); v[1] = lds4(tA + (VX0 - TA) + 2048); v[2] = lds4(tA + (VX1 - TA)); v[3] = lds4(tA + (VX1 - TA) + 2048);
#pragma unroll
        for (int i = 0; i < 4; i++) ts[i] = PACK(e[i]);
        vbad = anybad(v[0].x, v[1].x, v[2].x, v[3].x, V_TAG(s));
        if (AV) { xm = (xs & ~0x1ffffu) + X_VM(0) + ((tA - L16 - TA) << 5) + (l16 >> 1); CONSUME(xm); }
        while ((int)(clk() - c0) < 0) {}
        TS(5);
#pragma unroll
        for (int u = 0; u < 4; u++) r[u] = ldg_b64(XP_(xs) + u * 256);
        if (!AV) BAR_ARRIVE(B_S2, 256);
      }
      SCHED_FENCE(56);
      uint32_t kk;
      float4 e = softmax2<false>(r, 0, 0, kk);
      if (AV) {
        const char* pm_ = XP_(xm + (kk & dZ));
#pragma unroll
        for (int u = 0; u < 2; u++) { const uint2 m0 = ldg_b64(pm_ + u * 2048), m1 = ldg_b64(pm_ + u * 2048 + 256); vn[u] = make_uint4(m0.x, m0.y, m1.x, m1.y); }
      }
      if (__builtin_expect(anybad(r[0].x, r[0].y, r[1].x, r[1].y, r[2].x, r[2].y, r[3].x, r[3].y, tag ^ (kk & dZ)), 0)) {
        int it = 0;
        if (s > 8) sts1(tA + 4096 + 8, min(lds1(tA + 4096 + 8) + dX, 500));
        do {
          RP(1);
          if (++it > SPIN_LIMIT) __trap();
#pragma unroll
          for (int u = 0; u < 4; u++) r[u] = ldg_b64(XP_(xs) + u * 256);
        } while (BADS(r));
        e = softmax2<false>(r, 0, 0, kk);
      }
      sts1(t0.z, pk(e.x, e.y)); sts1(t0.z + 128, pk(e.z, e.w));
#pragma unroll
      for (int i = 0; i < 4; i++) publish(XP_(xo) + X_TOK + i * 4096, ts[i]);
      TS(6);
      if (s < 63) BAR_SYNC(B_V, N_V); else BAR_SYNC(B_V, N_V - 256);
      uint32_t O[4];
      {
        uint32_t p[4], pm;
        ldsm4t(p, pr);
        asm volatile("ldmatrix.sync.aligned.m8n8.x1.trans.shared.b16 {%0},[%1];" : "=r"(pm) : "r"(pr + 512) : "memory");
        if (!AV) { vn[0] = lds4(tA + (VN - TA)); vn[1] = lds4(tA + (VN - TA) + 2048); }
        pv_mem(p, pm, v, vn, O);
        if (__builtin_expect(vbad || ((HV || AV) && anybad(vn[0].x, vn[0].z, vn[1].x, vn[1].z, tag)), 0)) {
          int it = 0;
          const uint32_t xv = LO(xc) + (lds1(sb + PACE + 24) >> 2) * 262144 + ((tA - L16 - TA) >> 9) * XC;
          do {
            RP(2);
            if (++it > SPIN_LIMIT) __trap();
#pragma unroll
            for (int u = 0; u < 4; u++) v[u] = ldg_b128(XP_((xv + l16) ^ V_RING(s)) + X_VX(u));
#pragma unroll
            for (int u = 0; u < 2; u++) {
              const uint2 m0 = ldg_b64(XP_((xv + (l16 >> 1)) ^ ring) + X_VM(0) + u * 2048), m1 = ldg_b64(XP_((xv + (l16 >> 1)) ^ ring) + X_VM(0) + u * 2048 + 256);
              vn[u] = make_uint4(m0.x, m0.y, m1.x, m1.y);
            }
          } while (anybad(v[0].x, v[1].x, v[2].x, v[3].x, V_TAG(s)) || anybad(vn[0].x, vn[0].z, vn[1].x, vn[1].z, tag));
          pv_mem(p, pm, v, vn, O);
        }
      }
      stsm4(tA + (OB - TA), O[0], O[1], O[2], O[3]);
      if (s < 63) BAR_ARRIVE(B_O, N_O);
      TS(2);
      c0 = clk() + dG;
      SCHED_FENCE(60);
      if (tA == sb + TA) mbar_expect(sb + BARS, 2048);
      const uint32_t vs[4] = {addbf(vn[0].x, vn[0].z), addbf(vn[0].y, vn[0].w), addbf(vn[1].x, vn[1].z), addbf(vn[1].y, vn[1].w)};
      {
        const char* xt = XP_(lds1(tA + 12) ^ ring);
        const uint2 t1 = lds2u(tA + 2048);
        const uint32_t pw = lds1(tA + 8);
        uint2 rt[4];
        CONSUME(LO(xt) ^ t1.x ^ pw);
        while ((int)(clk() - c0) < 0) {}
        int it = 0;
        do {
          if (++it > SPIN_LIMIT) __trap();
#pragma unroll
          for (int u = 0; u < 4; u++) rt[u] = ldg_b64(xt + u * 256);
        } while (BADS(rt));
        uint32_t kt;
        const float4 et = softmax2<true>(rt, t1.x, t1.y, kt);
        sts1(pw + 1024, pk(et.x, et.y)); sts1(pw + 1024 + 128, pk(et.z, et.w));
      }
      s = PIN(s);
      BAR_SYNC(B_SC, 128);
      {
        uint32_t Ot[4], p[4], pm;
        const uint2 t2 = lds2u(tA + 2048 + 8);
        ldsm4t(p, pr + 1024);
        asm volatile("ldmatrix.sync.aligned.m8n8.x1.trans.shared.b16 {%0},[%1];" : "=r"(pm) : "r"(pr + 1024 + 512) : "memory");
        char* od = (char*)g_O + ((s >> 2) * 1048576 + (s & 3) * 4096) + t2.x;
        CONSUME(LO(od) ^ HI(od) ^ pm ^ p[3]);
        TS(9);
        if (s < 62) BAR_SYNC(B_P, N_P);
        pv_tok(p, pm, v, vs, Ot);
        asm volatile("stmatrix.sync.aligned.m8n8.x4.trans.shared.b16 [%0],{%1,%2,%3,%4};" ::"r"(t2.y), "r"(Ot[0]), "r"(Ot[1]), "r"(Ot[2]), "r"(Ot[3]) : "memory");
        __syncwarp();
        *(uint4*)od = lds4(tA + (OT - TA));
      }
    }
    FENCE_ASYNC();
    BAR_SYNC(B_SC, 128);
    if (tA == sb + TA) red_rlx(&g_fin);
  }
  __syncwarp();
  CLUSTER_SYNC();
  PH(5);
}
#undef wg
#undef iw
#undef h
#undef j
#undef a
#undef bb
#undef oi
#undef owner
#undef ownv
#undef vfin
#undef pr
#undef PIN
#undef XP_
#undef tw
#undef is7
#undef REFRESH
#undef lane
#undef l16
#undef lrow
#undef lar
#undef lpub

namespace ffn {
constexpr uint32_t BR = 98304;
constexpr uint32_t STG = 196608;
constexpr uint32_t PRM = 229376;
constexpr uint32_t BARS = PRM + 2816;
constexpr uint32_t SMEM = BARS + 18 * 8;
}
#define Y_TILE(rb, kt) (((ALIAS & 1) ? g_h : g_h2) + ((rb) * 16 + (kt)) * 1024)
#define U_TILE(rb, kt) ((ALIAS & 2) ? g_O + ((rb) * 64 + (kt)) * 1024 : g_U + ((rb) * 56 + (kt)) * 1024)
struct FfnMaps { CUtensorMap wo, w1a, w1b, w2, x, out; };

template <int N>
__device__ __forceinline__ void wg_ss(float* d, uint64_t a, uint64_t b, int sd) {
  if (N == 128) wgmma_ss_n128(d, a, b, sd);
  if (N == 192) wgmma_ss_n192(d, a, b, sd);
}
template <int N>
__device__ __forceinline__ void acc_fence(float* d) {
#pragma unroll
  for (int i = 0; i < N; i++) asm volatile("" : "+f"(d[i])::"memory");
}
#define UNPK8(d, v) do { (d)[0] = blo(v.x); (d)[1] = bhi(v.x); (d)[2] = blo(v.y); (d)[3] = bhi(v.y); (d)[4] = blo(v.z); (d)[5] = bhi(v.z); (d)[6] = blo(v.w); (d)[7] = bhi(v.w); } while (0)
struct FfnPipe {
  uint32_t full, emp, ph, aoff;
  int st, sB, prev;
  bool leader;
  template <int N>
  __device__ __forceinline__ void issue(float* acc, bool first, uint32_t a = 0) {
    mbar_wait(full + st * 8, ph);
    const uint64_t da = mkdesc((a ? a : 1024 + st * 16384) + aoff, 16, 1024), db = mkdesc(1024 + ffn::BR + sB * (N * 128), 8192, 1024);
    WG_FENCE();
#pragma unroll
    for (int j = 0; j < ((FDB & 1) ? 1 : 4); j++) wg_ss<N>(acc, da + j * 2, db + j * 128, j || !first);
    WG_COMMIT();
    if (++sB == 768 / N) sB = 0;
  }
  __device__ __forceinline__ void release() { if (leader) mbar_arrive(emp + prev * 8); }
  __device__ __forceinline__ void next() { prev = st; if (++st == 6) { st = 0; ph ^= 1; } }
  __device__ __forceinline__ void retire() { WG_WAIT(1); release(); next(); }
};
__device__ __forceinline__ float gelu_h(float hx) {
  float u = hx * fmaf(hx * hx, 8.f * 0.0356774081f, 2.f * 0.7978845608f), t;
  if (FDB & 4) return hx;
  if (FDB & 2) t = u; else
  asm("tanh.approx.f32 %0,%1;" : "=f"(t) : "f"(u));
  return fmaf(hx, t, hx);
}
struct FfnEpi {
  uint32_t st2, cc, flip, staged, l0;
  uint2 c;
  float n0, n1, s0, s1;
  __device__ __forceinline__ void flush(uint32_t r) {
    __syncwarp();
    asm volatile("{.reg .pred p; setp.ne.u32 p,%1,0; @p mbarrier.arrive.shared.b64 _,[%0];}" ::"r"(staged + (flip >> 11)), "r"(l0 & r) : "memory");
    flip ^= r << 14;
  }
  __device__ __forceinline__ void half(const float* d, int J, int r) {
#define PRE(i, n, c1, c2) gelu_h(fmaf(r ? d[4 + i] : d[i], i < 2 ? s0 : s1, fmaf(n, c1, c2)))
    asm volatile("stmatrix.sync.aligned.m8n8.x2.shared.b16 [%0],{%1,%2};" ::"r"((st2 ^ ((J & 3) * 32 + r * 16)) + flip),
                 "r"(pk(PRE(0, n0, blo(c.x), blo(c.y)), PRE(1, n0, bhi(c.x), bhi(c.y)))), "r"(pk(PRE(2, n1, blo(c.x), blo(c.y)), PRE(3, n1, bhi(c.x), bhi(c.y)))) : "memory");
#undef PRE
    if ((J & 3) == 3) flush(r);
    cc += r ? 56 : 8;
    c = lds2u(cc);
  }
};

__global__ void __launch_bounds__(384, 1)
k_ffn(const __grid_constant__ FfnMaps mp, const bf16* __restrict__ b2) {
  using namespace ffn;
  extern __shared__ __align__(1024) char smem[];
  const uint32_t sb = (uint32_t)__cvta_generic_to_shared(smem);
  if (sb != 1024) __trap();
  const int tid = threadIdx.x, lane = tid & 31, wg = __shfl_sync(~0u, tid >> 7, 0);
  const uint32_t full = sb + BARS, emp = full + 48, xbar = full + 96, staged = full + 104, tile = full + 136;
  uint32_t fin = 0;
  if (tid >= 288 && tid < 320) fin = ld_acq(&g_fin);
  if (tid < 32) {
    unsigned sm, v = 0;
    asm("mov.u32 %0,%%smid;" : "=r"(sm));
    if (tid == 0) {
      v = atomicExch(&g_slot[sm & 255], 0);
      for (int i = 0; i < 6; i++) { mbar_init(full + i * 8, 1); mbar_init(emp + i * 8, 2); }
      mbar_init(xbar, 2);
      for (int i = 0; i < 2; i++) { mbar_init(staged + i * 8, 8); mbar_init(staged + 16 + i * 8, 1); }
      FENCE_ASYNC_SMEM();
    }
    v = __shfl_sync(~0u, v, 0);
    if (!v) {
      wait_cnt(&g_fin, 128);
      for (int it = 0; !v; it++) {
        const uint4 a = ldg_rlx4(g_slot + tid * 8), b = ldg_rlx4(g_slot + tid * 8 + 4);
        const uint32_t open = __ballot_sync(~0u, a.x | a.y | a.z | a.w | b.x | b.y | b.z | b.w);
        if (!open) break;
        if (it < 16) { __nanosleep(500); continue; }
        if (tid == __ffs(open) - 1) v = atomicExch(&g_slot[tid * 8 + (a.x ? 0 : a.y ? 1 : a.z ? 2 : a.w ? 3 : b.x ? 4 : b.y ? 5 : b.z ? 6 : 7)], 0);
        v = __shfl_sync(~0u, v, __ffs(open) - 1);
      }
    }
    if (tid == 0) sts1(tile, v);
  }
  if (tid == 256) asm volatile("prefetch.tensormap [%0];" ::"l"(&mp.wo) : "memory");
  __syncthreads();
  const int bid = __shfl_sync(~0u, lds1(tile), 0) - 1;
  if (bid < 0) return;
  PH(6);
  FT(1);
  const int rb = bid >> 3, nb = bid & 7;
  unsigned* cnt = g_cnt + rb * 128;
  if (wg == 2) {
    asm volatile("setmaxnreg.dec.sync.aligned.u32 " FRP ";");
    const int pw = __shfl_sync(~0u, (tid >> 5) & 3, 0);
    uint32_t ws = emp, wp = 1, fs = full;
    auto wait_free = [&]() { mbar_wait_q(ws, wp); ws += 8; if (ws == emp + 48) { ws = emp; wp ^= 1; } };
    auto step = [&]() { fs += 8; if (fs == full + 48) fs = full; };
#define K3(c) ((0x65230 >> (c) * 4) & 7)
#define KC(k) ((k) < 2 ? nb * 2 + (k) : (k) < 9 ? ((k) - 2 + ((k) - 2 >= nb)) * 2 : ((k) - 9 + ((k) - 9 >= nb)) * 2 + 1)
    if (pw == 0) {
      uint32_t d = sb + BR + 32768;
      auto put = [&](const CUtensorMap* m, int k, int c) {
        e_expect_tma3d(d, m, k * 64, c, fs, 32768);
        step();
        d += 16384;
        if (d == sb + STG) d = sb + BR;
      };
      int n = 0;
      auto stage_free = [&]() { if (!(n & 7) && n < 56) mbar_wait_q(staged + 16 + (n & 8), (n >> 4) & 1); n++; };
      FTP(3);
#pragma unroll 1
      for (int k = 0; k < 66; k++) { wait_free(); if (k < 64) put(&mp.wo, k, nb * 2); }
#pragma unroll 1
      for (int k = 0; k < 16; k++) {
        const int kt = KC(k);
        wait_free();
        e_expect_tma3d(sb + BR + (k & 3) * 24576, &mp.w1b, kt * 64, nb * 7, fs, k < 2 ? 24576 : 40960);
        step();
      }
#pragma unroll 1
      for (int k = 0; k < 32; k++) { stage_free(); if (k != 5 && k != 6) wait_free(); put(&mp.w1a, k & 15, nb * 7 + 3 + (k >> 4) * 2); }
#pragma unroll 1
      for (int c = 0; c < 5; c++)
#pragma unroll 1
        for (int k = K3(c), i = 0; k < 56; k += c < 2 && (i ^= 1) ? 1 : c < 2 ? 6 : 7) { stage_free(); wait_free(); put(&mp.w2, k, nb * 2); }
    } else if (pw == 1) {
      FTP(5);
      if (fin < 128) wait_cnt(&g_fin, 128);
      FTP(6);
      uint32_t d = sb;
      auto put = [&](const uint4* A, bool ld) {
        wait_free();
        if (ld) e_bulk_ld(d, A, 16384, fs);
        step();
        d += 16384;
        if (d == sb + BR) d = sb;
      };
      const uint4* A = g_O + rb * 65536;
#pragma unroll 1
      for (int k = 0; k < 66; k++) put(A + k * 1024, k < 64);
      A = Y_TILE(rb, 0);
      uint32_t ready = 0;
#pragma unroll 1
      for (int k = 2; k < 48; k++) {
        const int kt = k < 16 ? KC(k) : k & 15;
        for (int it = 0; !(ready >> ((kt >> 1) + (kt & 1) * 8) & 1); it++) {
          ready = __ballot_sync(~0u, ldg_rlx1(cnt + (lane & 7)) & ((lane & 8) ? 1 : 0x10000));
          if (it > SPIN_LIMIT) __trap();
        }
        if (k == 2) FTP(75);
        put(A + kt * 1024, true);
      }
      A = U_TILE(rb, 0);
#pragma unroll 1
      for (int c = 0; c < 5; c++) {
        for (int it = 0; ldg_rlx1(cnt + 32 + c) < 8; it++) if (it > SPIN_LIMIT) __trap();
#pragma unroll 1
        for (int k = K3(c), i = 0; k < 56; k += c < 2 && (i ^= 1) ? 1 : c < 2 ? 6 : 7) put(A + k * 1024, true);
      }
    } else if (pw == 2) {
      for (int i = 0; i < XDL; i++) {
        mbar_wait_q(emp, i & 1);
        if (XPF && i == 1 && lane < 2) tma2d_pf(&mp.x, nb * 128 + lane * 64, rb * 128);
      }
      if (lane == 0) {
        mbar_expect(xbar, 32768);
        tma2d(sb + STG, &mp.x, nb * 128, rb * 128, xbar);
        tma2d(sb + STG + 16384, &mp.x, nb * 128 + 64, rb * 128, xbar);
      }
      asm volatile("griddepcontrol.wait;" ::: "memory");
      if (lane < 16) g_modp[bid * 16 + lane] = make_uint4(0, 0, 0, 0);
      if (lane >= 16 && bid == 0) { g_hcnt = 0; g_mcnt = 0; g_hf[lane & 3] = 0; }
      if (lane == 0) {
#pragma unroll 1
        for (int g = 1; g < 9; g++) {
          if (g == 1) mbar_wait(staged + 8, 0); else { mbar_wait_q(staged + (g & 1) * 8, (g >> 1) & 1); FENCE_ASYNC_SMEM(); }
          bulk_st(g == 1 ? Y_TILE(rb, nb * 2 + 1) : U_TILE(rb, nb * 7 + ((0x652431000ull >> g * 4) & 7)), sb + STG + (g & 1) * 16384, 16384);
          BULK_COMMIT();
          if (g != 2 && g != 4) { BULK_WAIT(0); red_rlx(g == 1 ? cnt + nb : cnt + 32 + (g < 6 ? g >> 2 : g - 4)); }
          BULK_WAIT_READ(0);
          mbar_arrive(staged + 16 + (g & 1) * 8);
        }
      }
    } else {
      const uint32_t prm = sb + PRM, pp = prm + (lane >> 3) * 64 + (lane & 1) * 32 + (lane & 6) * 2;
      const uint2 v2 = ((const uint2*)(b2 + nb * 128))[lane];
      sts1(pp + 768, v2.x); sts1(pp + 784, v2.y);
      asm volatile("griddepcontrol.wait;" ::: "memory");
      const float4* md = (const float4*)(g_mod + nb * 128) + lane;
      { const float4 ga = md[512]; sts1(pp, pk(ga.x, ga.y)); sts1(pp + 16, pk(ga.z, ga.w)); }
      { const float4 cb = md[1024]; sts1(pp + 256, pk(1.f + cb.x, 1.f + cb.y)); sts1(pp + 272, pk(1.f + cb.z, 1.f + cb.w)); }
      { const float4 gb = md[1280]; sts1(pp + 512, pk(gb.x, gb.y)); sts1(pp + 528, pk(gb.z, gb.w)); }
#pragma unroll 1
      for (int i = lane; i < 112; i += 32) { const uint4 c = g_cc[nb * 112 + i]; sts4(prm + 1024 + i * 16, c.x, c.y, c.z, c.w); }
      __syncwarp();
      if (lane == 0) {
        mbar_arrive(xbar);
        mbar_wait(staged, 0);
        bulk_st(Y_TILE(rb, nb * 2), sb + STG, 16384);
        BULK_COMMIT(); BULK_WAIT(0);
        asm volatile("red.relaxed.gpu.global.add.u32 [%0],0x10000;" ::"l"(cnt + nb) : "memory");
        mbar_arrive(staged + 16);
      }
      __syncwarp();
      mbar_wait_q(staged + 24, 0);
      mbar_wait_q(emp + 40, 0);
#pragma unroll 1
      for (int i = 0; i < 4; i++) {
        const uint4* sp = g_stat + (rb * 128 + i * 32 + lane) * 4;
        uint4 v[4];
        for (int it = 0;; it++) {
          uint32_t m = 0;
#pragma unroll
          for (int u = 0; u < 4; u++) { v[u] = ldg_rlx4(sp + u); m = max(max(m, max(v[u].x, v[u].y)), max(v[u].z, v[u].w)); }
          if (!__any_sync(~0u, m == ~0u)) break;
          if (it > SPIN_LIMIT) __trap();
        }
        float m = 0, q = 0;
#pragma unroll
        for (int u = 0; u < 4; u++) m += F_(v[u].x) + F_(v[u].z);
        m *= 0.125f;
#pragma unroll
        for (int u = 0; u < 4; u++) { const float a = F_(v[u].x) - m, b = F_(v[u].z) - m; q += F_(v[u].y) + F_(v[u].w) + 128.f * (a * a + b * b); }
        const float r = 0.5f * rsqrtf(q * (1.f / 1024) + 1e-5f);
        sts2(sb + STG + 16384 + (i * 32 + lane) * 8, U_(r), U_(-m * r));
      }
      __syncwarp();
      if (lane < 2) mbar_arrive(xbar);
    }
  } else {
    asm volatile("setmaxnreg.inc.sync.aligned.u32 " FRC ";");
    const int w = (tid >> 5) & 3, q = lane & 3;
    const uint32_t prm = sb + PRM + q * 16;
    const int row0 = wg * 64 + w * 16;
    FfnPipe p;
    p.full = full; p.emp = emp; p.ph = 0; p.aoff = wg * 8192; p.st = 0; p.sB = 2; p.prev = 0; p.leader = (tid & 127) == 0;
    FfnEpi e;
    const uint32_t stg = sb + STG + row0 * 128;
    e.st2 = stg + (lane & 15) * 128 + ((lane & 7) << 4);
    e.cc = sb + PRM + 1024 + q * 16; e.flip = 0; e.staged = staged; e.l0 = lane == 0;
    const uint32_t stw = e.st2 ^ (lane & 16);
    uint32_t x1[32];
    uint4* sp = g_stat + (rb * 128 + row0 + (lane >> 2)) * 4;
    float old[96], r0_, r1_;
    {
      float acc[64];
      p.issue<128>(acc, true); FT(8); p.next();
#pragma unroll 1
      for (int k = 1; k < 64; k++) { p.issue<128>(acc, false); FT(8 + k); p.retire(); }
      float xf[64], gf[32];
      uint32_t cb[16];
      mbar_wait(xbar, 0);
#pragma unroll
      for (int j = 0; j < 8; j++) {
        uint32_t xv[4];
        ldsm4(xv, (stw ^ ((j & 3) * 32)) + (j >> 2) * 16384);
#pragma unroll
        for (int i = 0; i < 4; i++) { xf[j * 8 + i * 2] = blo(xv[i]); xf[j * 8 + i * 2 + 1] = bhi(xv[i]); }
      }
#pragma unroll
      for (int i = 0; i < 4; i++) {
        const uint4 g = lds4(prm + i * 64), c = lds4(prm + 256 + i * 64);
        UNPK8(gf + i * 8, g);
        cb[i * 4] = c.x; cb[i * 4 + 1] = c.y; cb[i * 4 + 2] = c.z; cb[i * 4 + 3] = c.w;
      }
      acc_fence<64>(xf); acc_fence<32>(gf);
      WG_WAIT(0);
      p.release();
      acc_fence<64>(acc);
      PH(7); FT(72);
#pragma unroll
      for (int j = 0; j < 8; j++) {
        uint32_t* o = x1 + j * 4;
#pragma unroll
        for (int i = 0; i < 4; i++)
          o[i] = pk(fmaf(acc[j * 8 + i * 2], gf[j * 4 + (i & 2)], xf[j * 8 + i * 2]), fmaf(acc[j * 8 + i * 2 + 1], gf[j * 4 + (i & 2) + 1], xf[j * 8 + i * 2 + 1]));
        stsm4((stw ^ ((j & 3) * 32)) + (j >> 2) * 16384, mulbf(o[0], cb[j * 2]), mulbf(o[1], cb[j * 2]), mulbf(o[2], cb[j * 2 + 1]), mulbf(o[3], cb[j * 2 + 1]));
        if ((j & 3) == 3) { FENCE_ASYNC_SMEM(); e.flush(1); }
      }
      if (wg) BAR_SYNC(2, 128); else BAR_SYNC(3, 128);
    }
    PH(8); FT(73);
    float acc[64];
    {
      float* accC = old;
      p.sB = 0;
      p.issue<192>(accC, true, 1024 + STG); FT(80); p.next();
      p.issue<192>(accC, false, 1024 + STG + 16384); FT(81);
      FT(78);
      float s0 = 0, s1 = 0;
#define X1_FENCE _Pragma("unroll") for (int j = 0; j < 32; j++) asm volatile("" : "+r"(x1[j]));
      X1_FENCE
#pragma unroll
      for (int j = 0; j < 16; j++) { s0 += blo(x1[j * 2]) + bhi(x1[j * 2]); s1 += blo(x1[j * 2 + 1]) + bhi(x1[j * 2 + 1]); }
      s0 += __shfl_xor_sync(~0u, s0, 1); s1 += __shfl_xor_sync(~0u, s1, 1);
      s0 += __shfl_xor_sync(~0u, s0, 2); s1 += __shfl_xor_sync(~0u, s1, 2);
      s0 *= 1.f / 128; s1 *= 1.f / 128;
      float q0 = 0, q1 = 0;
      X1_FENCE
#pragma unroll
      for (int j = 0; j < 16; j++) {
        const float a = blo(x1[j * 2]) - s0, b = bhi(x1[j * 2]) - s0, c = blo(x1[j * 2 + 1]) - s1, d = bhi(x1[j * 2 + 1]) - s1;
        q0 += a * a + b * b; q1 += c * c + d * d;
      }
      q0 += __shfl_xor_sync(~0u, q0, 1); q1 += __shfl_xor_sync(~0u, q1, 1);
      q0 += __shfl_xor_sync(~0u, q0, 2); q1 += __shfl_xor_sync(~0u, q1, 2);
      if (q < 2) {
        uint32_t m = __float_as_uint(q ? s1 : s0), v = __float_as_uint(q ? q1 : q0);
        if (m == ~0u) m = 0x7fffffffu;
        if (v == ~0u) v = 0x7fffffffu;
        stg_rlx2((uint2*)(sp + q * 32) + nb, m, v);
      }
      X1_FENCE
      p.retire();
#pragma unroll 1
      for (int k = 2; k < 15; k++) { p.issue<192>(accC, false); FT(80 + k); p.retire(); }
      p.issue<192>(accC, false); FT(95);
      mbar_wait(xbar, 1);
      const float2 u0 = lds2f(sb + STG + 16384 + (row0 + (lane >> 2)) * 8), u1 = lds2f(sb + STG + 16384 + (row0 + (lane >> 2)) * 8 + 64);
      r0_ = u0.x; e.n0 = u0.y; r1_ = u1.x; e.n1 = u1.y;
      e.c = lds2u(e.cc);
      p.retire();
      e.s0 = r0_; e.s1 = r1_;
    }
    PH(9);
    {
      auto pair = [&](int J, bool first, int fo) {
#pragma unroll 1
        for (int r = 0; r < 2; r++) { p.issue<128>(acc, first && !r); FT(fo + r); p.retire(); acc_fence<8>(old + J * 8); e.half(old + J * 8, J, r); }
      };
#pragma unroll 1
      for (int i = 0; i < 3; i++) {
        if (i == 2) {
          e.s0 = r0_; e.s1 = r1_;
#pragma unroll
          for (int J = 8; J < 12; J++) pair(J, J == 8, 128 + (J - 8) * 2);
          e.cc += 512; e.c = lds2u(e.cc);
          e.s0 = e.s1 = 1.f;
        }
#pragma unroll
        for (int J = 0; J < 8; J++) pair(J, J == 0 && i < 2, 96 + i * 16 + (i >> 1) * 8 + J * 2);
        if (i == 2) break;
        e.cc += i ? -768 : 256; e.c = lds2u(e.cc);
        WG_WAIT(0);
        acc_fence<64>(acc);
#pragma unroll
        for (int k = 0; k < 64; k++) old[k] = acc[k] * ((k & 2) ? r1_ : r0_);
        acc_fence<64>(old);
        e.s0 = e.s1 = 1.f;
        PH(10 + i);
      }
#pragma unroll 1
      for (int k = 24; k < 56; k++) { p.issue<128>(acc, false); FT(128 + k); p.retire(); }
      float xf[64], gf[32];
#pragma unroll
      for (int i = 0; i < 4; i++) {
        const uint4 g = lds4(prm + 512 + i * 64), h = lds4(prm + 768 + i * 64);
        float hf[8];
        UNPK8(gf + i * 8, g); UNPK8(hf, h);
#pragma unroll
        for (int u = 0; u < 8; u++) {
          const int c = (u >> 2) * 4 + (u & 2);
          xf[i * 16 + u * 2] = fmaf(gf[i * 8 + c], hf[c], blo(x1[i * 8 + u])); xf[i * 16 + u * 2 + 1] = fmaf(gf[i * 8 + c + 1], hf[c + 1], bhi(x1[i * 8 + u]));
        }
      }
      acc_fence<64>(xf); acc_fence<32>(gf);
      mbar_wait(staged + 24, 1);
      mbar_wait(staged + 16, 0);
      WG_WAIT(0);
      acc_fence<64>(acc);
      PH(13); FT(184);
#pragma unroll
      for (int j = 0; j < 8; j++) {
        uint32_t o[4];
#pragma unroll
        for (int i = 0; i < 4; i++)
          o[i] = pk(fmaf(acc[j * 8 + i * 2], gf[j * 4 + (i & 2)], xf[j * 8 + i * 2]), fmaf(acc[j * 8 + i * 2 + 1], gf[j * 4 + (i & 2) + 1], xf[j * 8 + i * 2 + 1]));
        stsm4((stw ^ ((j & 3) * 32)) + (j >> 2) * 16384, o[0], o[1], o[2], o[3]);
        if ((j & 3) == 3) {
          FENCE_ASYNC_SMEM();
          __syncwarp();
          if (lane == 0) { tma2d_st(&mp.out, nb * 128 + (j >> 2) * 64, rb * 128 + row0, stg + (j >> 2) * 16384); BULK_COMMIT(); }
        }
      }
      if (lane == 0) BULK_WAIT_READ(0);
      __syncwarp();
    }
  }
  PH(14); FT(185);
}

typedef CUresult (*EncFn)(CUtensorMap*, CUtensorMapDataType, cuuint32_t, void*, const cuuint64_t*, const cuuint64_t*, const cuuint32_t*,
                          const cuuint32_t*, CUtensorMapInterleave, CUtensorMapSwizzle, CUtensorMapL2promotion, CUtensorMapFloatOOBfill);
static void map2d(EncFn enc, CUtensorMap* m, const void* p, int rows, int cols, int boxRows) {
  cuuint64_t d[2] = {(cuuint64_t)cols, (cuuint64_t)rows}, s[1] = {(cuuint64_t)cols * 2};
  cuuint32_t b[2] = {64, (cuuint32_t)boxRows}, e[2] = {1, 1};
  enc(m, CU_TENSOR_MAP_DATA_TYPE_BFLOAT16, 2, (void*)p, d, s, b, e, CU_TENSOR_MAP_INTERLEAVE_NONE, CU_TENSOR_MAP_SWIZZLE_128B,
      CU_TENSOR_MAP_L2_PROMOTION_L2_128B, CU_TENSOR_MAP_FLOAT_OOB_FILL_NONE);
}
static void map3d(EncFn enc, CUtensorMap* m, const void* p, int rows, int cols, int nch) {
  cuuint64_t d[3] = {64, (cuuint64_t)rows, (cuuint64_t)(cols / 64)}, s[2] = {(cuuint64_t)cols * 2, 128};
  cuuint32_t b[3] = {64, 64, (cuuint32_t)nch}, e[3] = {1, 1, 1};
  enc(m, CU_TENSOR_MAP_DATA_TYPE_BFLOAT16, 3, (void*)p, d, s, b, e, CU_TENSOR_MAP_INTERLEAVE_NONE, CU_TENSOR_MAP_SWIZZLE_128B,
      CU_TENSOR_MAP_L2_PROMOTION_L2_128B, CU_TENSOR_MAP_FLOAT_OOB_FILL_NONE);
}

extern "C" void kernel_launch(void* const* d_in, const int* in_sizes, int n_in, void* d_out, int out_size) {
  const bf16* x = (const bf16*)d_in[0];
  const bf16* mem0 = (const bf16*)d_in[1];
  void* fn = nullptr;
  cudaDriverEntryPointQueryResult qr;
  cudaGetDriverEntryPoint("cuTensorMapEncodeTiled", &fn, cudaEnableDefault, &qr);
  EncFn enc = (EncFn)fn;
  FfnMaps fm = {};
  map3d(enc, &fm.wo, d_in[5], 4096, 1024, 2);
  map3d(enc, &fm.w1a, d_in[8], 1024, 3584, 2);
  map3d(enc, &fm.w1b, d_in[8], 1024, 3584, 3);
  map3d(enc, &fm.w2, d_in[10], 3584, 1024, 2);
  map2d(enc, &fm.x, x, 2048, 1024, 128);
  map2d(enc, &fm.out, d_out, 2048, 1024, 16);
  RecMaps rm = {};
  map2d(enc, &rm.wq, d_in[2], 1024, 4096, 128);
  map2d(enc, &rm.wk, d_in[3], 1024, 4096, 128);
  map2d(enc, &rm.wv, d_in[4], 1024, 4096, 16);
  map2d(enc, &rm.wo, d_in[5], 4096, 1024, 128);
  char* xc = nullptr;
  cudaGetSymbolAddress((void**)&xc, g_xc);
  xc += (0 - (uintptr_t)xc) & 0x1FFFFF;
  {
    cuuint64_t d[3] = {512, ARV ? 8 : 128, ARV ? 128 : 6}, sd[2] = {1024, ARV ? 8192 : 131072};
    cuuint32_t bi[3] = {64, 8, 5}, e[3] = {1, 1, 1};
    enc(&rm.ari, CU_TENSOR_MAP_DATA_TYPE_BFLOAT16, 3, xc + AR_OFF, d, sd, bi, e, CU_TENSOR_MAP_INTERLEAVE_NONE, CU_TENSOR_MAP_SWIZZLE_NONE,
        CU_TENSOR_MAP_L2_PROMOTION_NONE, CU_TENSOR_MAP_FLOAT_OOB_FILL_NONE);
  }
  cudaFuncSetAttribute(k_ffn, cudaFuncAttributeMaxDynamicSharedMemorySize, ffn::SMEM);
  cudaFuncSetAttribute(k_rec, cudaFuncAttributeMaxDynamicSharedMemorySize, rec::SMEM);
  cudaStream_t st = cudaStreamPerThread;
  int dF = 450, dA = 2700, dS = 300, dM = 120, dG = 350, dP = 24, dX = 48, dD = 350, dZ = 0, dZ2 = 1, dV = 370, dX2 = 0;
  k_rec<<<132, 512, rec::SMEM, st>>>(rm, mem0, x, (const bf16*)d_in[12], (const bf16*)d_in[13], (const char*)d_in[8], (const bf16*)d_in[9],
                                     (const char*)d_in[5], xc, dF, dA, dS, dM, dG, dP, dX, dD, dZ, dZ2, dV, dX2);
  cudaLaunchConfig_t cfg = {};
  cfg.gridDim = dim3(132); cfg.blockDim = dim3(384); cfg.dynamicSmemBytes = ffn::SMEM; cfg.stream = st;
  cudaLaunchAttribute at[1];
  at[0].id = cudaLaunchAttributeProgrammaticStreamSerialization;
  at[0].val.programmaticStreamSerializationAllowed = 1;
  cfg.attrs = at; cfg.numAttrs = 1;
  cudaLaunchKernelEx(&cfg, k_ffn, fm, (const bf16*)d_in[11]);
}
```

```cpp
#include <cuda_runtime.h>
#include <cuda.h>
#include <cuda_bf16.h>
#include <stdint.h>

typedef __nv_bfloat16 bf16;

__device__ __align__(16) float g_mod[6144];
__device__ __align__(1024) uint4 g_modp[4 * 512];
__device__ unsigned g_hcnt;
__device__ unsigned g_hf[4];
__device__ __align__(1024) uint4 g_h[2048 * 1024 / 8];
__device__ __align__(1024) uint4 g_O[2048 * 4096 / 8];
__device__ __align__(1024) uint4 g_h2[2048 * 1024 / 8];
__device__ __align__(1024) uint4 g_U[2048 * 3584 / 8];
__device__ __align__(1024) uint4 g_stat[2048 * 4];
__device__ __align__(1024) unsigned g_cnt[16 * 4 * 32];
__device__ unsigned g_mcnt;
__device__ unsigned g_slot[256];
__device__ unsigned g_fin;
__device__ __align__(16) uint4 g_cc[224 * 4];
__device__ __align__(1024) uint4 g_xc[44 * 16384];
__device__ __align__(1024) unsigned g_tm[4 * 256];
#define FT(i)
#define FTP(i)
#define PT(i)
#define PH(i)
#define RS(i)
#define RP(i)
#define RPN(i, s)
#define TSV(i, v)
#define TS(i)

#define WIN 2
#define FRC "232"
#define FRP "40"
#define YR 1
#define XPK 0
#define NFA 1
#define PINM 1
#define FMAP (((g >> 2) * 4 + m) * 8 + (g & 3) * 2 + (blockIdx.x & 1))
#define FDB 0
#define ALIAS 3
#define EF 0
#define XPF 0
#define PFT 150000
#define PFS 104
#define PF0 13000
#define PFD 128
#define ARV 0
#define HV 0
#define XE 0
#define NF 3
#define NB0 4
#define PV0 4
#define T1L 1
#define NW0 5
#define FQM 0
#define FQ(k) do { if ((FQM >> ((k) - 48)) & 1) SCHED_FENCE(k); } while (0)
#define SWP 1
#define VCO 0
#define AV 0
#define PKE 0
#define VRF 3
#define RSO 2
#define WPF 1
#define VPC 1
#define XDL 6
#define QW 0
#define PDS 61
#define P_NVR 5
#define P_NVP 2
#define P_NWP 9
#define P_NW1 7
#define RF_ 208
#define PSV 1
#define RA_ (488 - 2 * RF_)
#define XI 5
#define XL 1
#define WCH 2
#define HX 0
#define VB 1
#define TP 0
#define CKI 0
#define NOP_ 2
#define KVO 0
#define NDL 3
#define AM 0
#define XM 3
#define XP 0
#define SPIN_LIMIT (1 << 20)
__device__ __forceinline__ uint64_t mkdesc(uint32_t addr, uint32_t lbo, uint32_t sbo) {
  return (uint64_t)((addr & 0x3FFFF) >> 4) | ((uint64_t)(lbo >> 4) << 16) | ((uint64_t)(sbo >> 4) << 32) | (1ull << 62);
}
__device__ __forceinline__ void mbar_init(uint32_t a, int c) { asm volatile("mbarrier.init.shared.b64 [%0],%1;" ::"r"(a), "r"(c) : "memory"); }
__device__ __forceinline__ void mbar_wait(uint32_t a, uint32_t par) {
  asm volatile(
      "{.reg .pred p; .reg .u32 n;\n"
      "mov.u32 n, 0;\n"
      "W: mbarrier.try_wait.parity.shared.b64 p,[%0],%1;\n"
      "@p bra D;\n"
      "add.u32 n, n, 1;\n"
      "setp.lt.u32 p, n, %2;\n"
      "@p bra W;\n"
      "trap;\n"
      "D:}" ::"r"(a), "r"(par), "n"(SPIN_LIMIT) : "memory");
}
__device__ __forceinline__ void mbar_wait_q(uint32_t a, uint32_t par) {
  asm volatile(
      "{.reg .pred p; .reg .u32 n;\n"
      "mov.u32 n, 0;\n"
      "W: mbarrier.try_wait.parity.shared.b64 p,[%0],%1,4000;\n"
      "@p bra D;\n"
      "add.u32 n, n, 1;\n"
      "setp.lt.u32 p, n, %2;\n"
      "@p bra W;\n"
      "trap;\n"
      "D:}" ::"r"(a), "r"(par), "n"(SPIN_LIMIT / 16) : "memory");
}
__device__ __forceinline__ void mbar_expect(uint32_t a, uint32_t b) { asm volatile("mbarrier.arrive.expect_tx.shared.b64 _,[%0],%1;" ::"r"(a), "r"(b) : "memory"); }
__device__ __forceinline__ void mbar_arrive(uint32_t a) { asm volatile("mbarrier.arrive.shared.b64 _,[%0];" ::"r"(a) : "memory"); }
__device__ __forceinline__ uint32_t mapa(uint32_t a, uint32_t cta) { uint32_t r; asm("mapa.shared::cluster.u32 %0,%1,%2;" : "=r"(r) : "r"(a), "r"(cta)); return r; }
__device__ __forceinline__ void mbar_arrive_cl(uint32_t a) { asm volatile("mbarrier.arrive.shared::cluster.b64 _,[%0];" ::"r"(a) : "memory"); }
__device__ __forceinline__ void tma2d(uint32_t dst, const CUtensorMap* m, int c0, int c1, uint32_t mb) {
  asm volatile("cp.async.bulk.tensor.2d.shared::cluster.global.mbarrier::complete_tx::bytes [%0],[%1,{%2,%3}],[%4];" ::"r"(dst), "l"(m), "r"(c0), "r"(c1), "r"(mb) : "memory");
}
__device__ __forceinline__ void tma2d_pf(const CUtensorMap* m, int c0, int c1) {
  asm volatile("cp.async.bulk.prefetch.tensor.2d.L2.global [%0,{%1,%2}];" ::"l"(m), "r"(c0), "r"(c1) : "memory");
}
__device__ __forceinline__ void tma3d(uint32_t dst, const CUtensorMap* m, int c1, int c2, uint32_t mb) {
  asm volatile("cp.async.bulk.tensor.3d.shared::cluster.global.mbarrier::complete_tx::bytes [%0],[%1,{0,%2,%3}],[%4];" ::"r"(dst), "l"(m), "r"(c1), "r"(c2), "r"(mb) : "memory");
}
__device__ __forceinline__ void tma2d_st(const CUtensorMap* m, int c0, int c1, uint32_t src) {
  asm volatile("cp.async.bulk.tensor.2d.global.shared::cta.bulk_group [%0,{%1,%2}],[%3];" ::"l"(m), "r"(c0), "r"(c1), "r"(src) : "memory");
}
__device__ __forceinline__ void bulk_ld(uint32_t dst, const void* src, uint32_t n, uint32_t mb) {
  asm volatile("cp.async.bulk.shared::cluster.global.mbarrier::complete_tx::bytes [%0],[%1],%2,[%3];" ::"r"(dst), "l"(src), "r"(n), "r"(mb) : "memory");
}
__device__ __forceinline__ void bulk_ld_mc(uint32_t dst, const void* src, uint32_t n, uint32_t mb) {
  asm volatile("cp.async.bulk.shared::cluster.global.mbarrier::complete_tx::bytes.multicast::cluster [%0],[%1],%2,[%3],%4;" ::"r"(dst), "l"(src), "r"(n), "r"(mb), "h"((uint16_t)3) : "memory");
}
__device__ __forceinline__ void bulk_st(void* dst, uint32_t src, uint32_t n) {
  asm volatile("cp.async.bulk.global.shared::cta.bulk_group [%0],[%1],%2;" ::"l"(dst), "r"(src), "r"(n) : "memory");
}
__device__ __forceinline__ void e_expect_tma3d(uint32_t dst, const CUtensorMap* m, int c1, int c2, uint32_t mb, uint32_t bytes) {
  asm volatile("{.reg .pred p; elect.sync _|p, 0xffffffff; @p mbarrier.arrive.expect_tx.shared.b64 _,[%4],%5;\n"
               "@p cp.async.bulk.tensor.3d.shared::cluster.global.mbarrier::complete_tx::bytes [%0],[%1,{0,%2,%3}],[%4];}" ::"r"(dst), "l"(m), "r"(c1), "r"(c2), "r"(mb), "r"(bytes) : "memory");
}
__device__ __forceinline__ void e_bulk_ld(uint32_t dst, const void* src, uint32_t n, uint32_t mb) {
  asm volatile("{.reg .pred p; elect.sync _|p, 0xffffffff; @p cp.async.bulk.shared::cluster.global.mbarrier::complete_tx::bytes [%0],[%1],%2,[%3];}" ::"r"(dst), "l"(src), "r"(n), "r"(mb) : "memory");
}
__device__ __forceinline__ void e_bulk_ld_ef(uint32_t dst, const void* src, uint32_t n, uint32_t mb) {
  asm volatile("{.reg .pred p; .reg .b64 c; createpolicy.fractional.L2::evict_first.b64 c,1.0; elect.sync _|p, 0xffffffff;"
               " @p cp.async.bulk.shared::cluster.global.mbarrier::complete_tx::bytes.L2::cache_hint [%0],[%1],%2,[%3],c;}" ::"r"(dst), "l"(src), "r"(n), "r"(mb) : "memory");
}
__device__ __forceinline__ void e_bulk_ld_mc(uint32_t dst, const void* src, uint32_t n, uint32_t mb) {
  asm volatile("{.reg .pred p; elect.sync _|p, 0xffffffff; @p cp.async.bulk.shared::cluster.global.mbarrier::complete_tx::bytes.multicast::cluster [%0],[%1],%2,[%3],%4;}" ::"r"(dst), "l"(src), "r"(n), "r"(mb), "h"((uint16_t)3) : "memory");
}
#define BULK_COMMIT() asm volatile("cp.async.bulk.commit_group;" ::: "memory")
#define BULK_WAIT_READ(n) asm volatile("cp.async.bulk.wait_group.read " #n ";" ::: "memory")
#define BULK_WAIT(n) asm volatile("cp.async.bulk.wait_group " #n ";" ::: "memory")
#define FENCE_ASYNC_SMEM() asm volatile("fence.proxy.async.shared::cta;" ::: "memory")
#define FENCE_ASYNC() asm volatile("fence.proxy.async;" ::: "memory")
#define WG_FENCE() asm volatile("wgmma.fence.sync.aligned;" ::: "memory")
#define WG_COMMIT() asm volatile("wgmma.commit_group.sync.aligned;" ::: "memory")
#define WG_WAIT(n) asm volatile("wgmma.wait_group.sync.aligned " #n ";" ::: "memory")
#define BAR_SYNC(id, n) asm volatile("bar.sync %0,%1;" ::"n"(id), "n"(n) : "memory")
#define BAR_ARRIVE(id, n) asm volatile("bar.arrive %0,%1;" ::"n"(id), "n"(n) : "memory")
#define SCHED_FENCE(k) asm volatile("{.reg .pred p; setp.ne.u32 p,%0,0; @p trap;}" ::"r"(mp.zero[(k) - 46]) : "memory")
#define CLUSTER_SYNC() asm volatile("barrier.cluster.arrive.relaxed.aligned; barrier.cluster.wait.aligned;" ::: "memory")
__device__ __forceinline__ uint32_t pk(float lo, float hi) { uint32_t r; asm("cvt.rn.bf16x2.f32 %0,%1,%2;" : "=r"(r) : "f"(hi), "f"(lo)); return r; }
__device__ __forceinline__ float blo(uint32_t v) { return __uint_as_float(v << 16); }
__device__ __forceinline__ float bhi(uint32_t v) { return __uint_as_float(v & 0xffff0000u); }
__device__ __forceinline__ void ldsm4(uint32_t* r, uint32_t a) {
  asm volatile("ldmatrix.sync.aligned.m8n8.x4.shared.b16 {%0,%1,%2,%3},[%4];" : "=r"(r[0]), "=r"(r[1]), "=r"(r[2]), "=r"(r[3]) : "r"(a) : "memory");
}
__device__ __forceinline__ void ldsm4t(uint32_t* r, uint32_t a) {
  asm volatile("ldmatrix.sync.aligned.m8n8.x4.trans.shared.b16 {%0,%1,%2,%3},[%4];" : "=r"(r[0]), "=r"(r[1]), "=r"(r[2]), "=r"(r[3]) : "r"(a) : "memory");
}
__device__ __forceinline__ void stsm4(uint32_t a, uint32_t r0, uint32_t r1, uint32_t r2, uint32_t r3) {
  asm volatile("stmatrix.sync.aligned.m8n8.x4.shared.b16 [%0],{%1,%2,%3,%4};" ::"r"(a), "r"(r0), "r"(r1), "r"(r2), "r"(r3) : "memory");
}
__device__ __forceinline__ void mma16(float* d, uint32_t a0, uint32_t a1, uint32_t a2, uint32_t a3, uint32_t b0, uint32_t b1) {
  asm volatile("mma.sync.aligned.m16n8k16.row.col.f32.bf16.bf16.f32 {%0,%1,%2,%3},{%4,%5,%6,%7},{%8,%9},{%0,%1,%2,%3};"
               : "+f"(d[0]), "+f"(d[1]), "+f"(d[2]), "+f"(d[3]) : "r"(a0), "r"(a1), "r"(a2), "r"(a3), "r"(b0), "r"(b1));
}
__device__ __forceinline__ void mma8(float* d, uint32_t a0, uint32_t a1, uint32_t b0) {
  asm volatile("mma.sync.aligned.m16n8k8.row.col.f32.bf16.bf16.f32 {%0,%1,%2,%3},{%4,%5},{%6},{%0,%1,%2,%3};"
               : "+f"(d[0]), "+f"(d[1]), "+f"(d[2]), "+f"(d[3]) : "r"(a0), "r"(a1), "r"(b0));
}
__device__ __forceinline__ float4 lds4f(uint32_t a) { float4 v; asm volatile("ld.shared.v4.f32 {%0,%1,%2,%3},[%4];" : "=f"(v.x), "=f"(v.y), "=f"(v.z), "=f"(v.w) : "r"(a) : "memory"); return v; }
__device__ __forceinline__ float2 lds2f(uint32_t a) { float2 v; asm volatile("ld.shared.v2.f32 {%0,%1},[%2];" : "=f"(v.x), "=f"(v.y) : "r"(a) : "memory"); return v; }
__device__ __forceinline__ uint4 lds4(uint32_t a) { uint4 v; asm volatile("ld.shared.v4.u32 {%0,%1,%2,%3},[%4];" : "=r"(v.x), "=r"(v.y), "=r"(v.z), "=r"(v.w) : "r"(a) : "memory"); return v; }
__device__ __forceinline__ uint2 lds2u(uint32_t a) { uint2 v; asm volatile("ld.shared.v2.u32 {%0,%1},[%2];" : "=r"(v.x), "=r"(v.y) : "r"(a) : "memory"); return v; }
__device__ __forceinline__ uint32_t lds1(uint32_t a) { uint32_t v; asm volatile("ld.shared.u32 %0,[%1];" : "=r"(v) : "r"(a) : "memory"); return v; }
__device__ __forceinline__ void sts4(uint32_t a, uint32_t x, uint32_t y, uint32_t z, uint32_t w) { asm volatile("st.shared.v4.u32 [%0],{%1,%2,%3,%4};" ::"r"(a), "r"(x), "r"(y), "r"(z), "r"(w) : "memory"); }
__device__ __forceinline__ void sts2(uint32_t a, uint32_t x, uint32_t y) { asm volatile("st.shared.v2.u32 [%0],{%1,%2};" ::"r"(a), "r"(x), "r"(y) : "memory"); }
__device__ __forceinline__ void sts1(uint32_t a, uint32_t x) { asm volatile("st.shared.u32 [%0],%1;" ::"r"(a), "r"(x) : "memory"); }
__device__ __forceinline__ void sta4(uint32_t a, const uint32_t* v, uint32_t mb) {
  asm volatile("st.async.shared::cluster.mbarrier::complete_tx::bytes.v4.b32 [%0],{%1,%2,%3,%4},[%5];" ::"r"(a), "r"(v[0]), "r"(v[1]), "r"(v[2]), "r"(v[3]), "r"(mb) : "memory");
}
__device__ __forceinline__ uint4 ldg_rlx4(const void* p) { uint4 v; asm volatile("ld.relaxed.gpu.global.v4.u32 {%0,%1,%2,%3},[%4];" : "=r"(v.x), "=r"(v.y), "=r"(v.z), "=r"(v.w) : "l"(p) : "memory"); return v; }
__device__ __forceinline__ uint32_t ldg_rlx1(const void* p) { uint32_t v; asm volatile("ld.relaxed.gpu.global.u32 %0,[%1];" : "=r"(v) : "l"(p) : "memory"); return v; }
__device__ __forceinline__ uint2 ldg_rlx2(const void* p) { uint2 v; asm volatile("ld.relaxed.gpu.global.v2.u32 {%0,%1},[%2];" : "=r"(v.x), "=r"(v.y) : "l"(p) : "memory"); return v; }
__device__ __forceinline__ uint4 ldg_b128(const void* p) {
  uint4 v;
  asm volatile("{.reg .b128 t; .reg .b64 a,b; ld.relaxed.gpu.global.b128 t,[%4]; mov.b128 {a,b},t; mov.b64 {%0,%1},a; mov.b64 {%2,%3},b;}" : "=r"(v.x), "=r"(v.y), "=r"(v.z), "=r"(v.w) : "l"(p) : "memory");
  return v;
}
__device__ __forceinline__ void stg_b128(void* p, uint32_t x, uint32_t y, uint32_t z, uint32_t w) {
  asm volatile("{.reg .b128 t; .reg .b64 a,b; mov.b64 a,{%1,%2}; mov.b64 b,{%3,%4}; mov.b128 t,{a,b}; st.relaxed.gpu.global.b128 [%0],t;}" ::"l"(p), "r"(x), "r"(y), "r"(z), "r"(w) : "memory");
}
__device__ __forceinline__ void st_b128(void* p, uint32_t x, uint32_t y, uint32_t z, uint32_t w) {
  asm volatile("{.reg .b128 t; .reg .b64 a,b; mov.b64 a,{%1,%2}; mov.b64 b,{%3,%4}; mov.b128 t,{a,b}; st.relaxed.gpu.b128 [%0],t;}" ::"l"(p), "r"(x), "r"(y), "r"(z), "r"(w) : "memory");
}
__device__ __forceinline__ void stg_rlx4(void* p, uint32_t x, uint32_t y, uint32_t z, uint32_t w) { asm volatile("st.relaxed.gpu.global.v4.u32 [%0],{%1,%2,%3,%4};" ::"l"(p), "r"(x), "r"(y), "r"(z), "r"(w) : "memory"); }
__device__ __forceinline__ void stg_rlx2(void* p, uint32_t x, uint32_t y) { asm volatile("st.relaxed.gpu.global.v2.u32 [%0],{%1,%2};" ::"l"(p), "r"(x), "r"(y) : "memory"); }
__device__ __forceinline__ void red4(void* p, float a, float b, float c, float d) { asm volatile("red.relaxed.gpu.global.add.v4.f32 [%0],{%1,%2,%3,%4};" ::"l"(p), "f"(a), "f"(b), "f"(c), "f"(d) : "memory"); }
__device__ __forceinline__ unsigned ld_acq(const unsigned* p) { unsigned v; asm volatile("ld.acquire.gpu.global.u32 %0,[%1];" : "=r"(v) : "l"(p) : "memory"); return v; }
__device__ __forceinline__ void red_rel(unsigned* p) { asm volatile("red.release.gpu.global.add.u32 [%0],1;" ::"l"(p) : "memory"); }
__device__ __forceinline__ void red_rlx(unsigned* p) { asm volatile("red.relaxed.gpu.global.add.u32 [%0],1;" ::"l"(p) : "memory"); }
__device__ __forceinline__ void wait_cnt(const unsigned* p, unsigned n) { int it = 0; while (ld_acq(p) < n) { if (++it > SPIN_LIMIT) __trap(); } }
__device__ __forceinline__ uint32_t clk() { uint32_t c; asm volatile("mov.u32 %0,%%clock;" : "=r"(c)); return c; }
__device__ __forceinline__ uint32_t gtime() { uint32_t c; asm volatile("mov.u32 %0,%%globaltimer_lo;" : "=r"(c)); return c; }
__device__ __forceinline__ void wait_until(uint32_t t0, uint32_t d) { while (clk() - t0 < d) {} }
__device__ __forceinline__ float ex2(float x) { float r; asm("ex2.approx.ftz.f32 %0,%1;" : "=f"(r) : "f"(x)); return r; }
__device__ __forceinline__ float silu(float x) { return x * __frcp_rn(1.f + __expf(-x)); }
__device__ __forceinline__ float rbf(float x) { return __bfloat162float(__float2bfloat16_rn(x)); }

__device__ __forceinline__ void wgmma_ss_n128(float* d, uint64_t a, uint64_t b, int sd) {
  asm volatile("{.reg .pred p; setp.ne.b32 p, %66, 0;\n"
    "wgmma.mma_async.sync.aligned.m64n128k16.f32.bf16.bf16 {%0,%1,%2,%3,%4,%5,%6,%7,%8,%9,%10,%11,%12,%13,%14,%15,%16,%17,%18,%19,%20,%21,%22,%23,%24,%25,%26,%27,%28,%29,%30,%31,%32,%33,%34,%35,%36,%37,%38,%39,%40,%41,%42,%43,%44,%45,%46,%47,%48,%49,%50,%51,%52,%53,%54,%55,%56,%57,%58,%59,%60,%61,%62,%63}, %64, %65, p, 1, 1, 0, 1;}\n"
    : "+f"(d[0]),"+f"(d[1]),"+f"(d[2]),"+f"(d[3]),"+f"(d[4]),"+f"(d[5]),"+f"(d[6]),"+f"(d[7]),
      "+f"(d[8]),"+f"(d[9]),"+f"(d[10]),"+f"(d[11]),"+f"(d[12]),"+f"(d[13]),"+f"(d[14]),"+f"(d[15]),
      "+f"(d[16]),"+f"(d[17]),"+f"(d[18]),"+f"(d[19]),"+f"(d[20]),"+f"(d[21]),"+f"(d[22]),"+f"(d[23]),
      "+f"(d[24]),"+f"(d[25]),"+f"(d[26]),"+f"(d[27]),"+f"(d[28]),"+f"(d[29]),"+f"(d[30]),"+f"(d[31]),
      "+f"(d[32]),"+f"(d[33]),"+f"(d[34]),"+f"(d[35]),"+f"(d[36]),"+f"(d[37]),"+f"(d[38]),"+f"(d[39]),
      "+f"(d[40]),"+f"(d[41]),"+f"(d[42]),"+f"(d[43]),"+f"(d[44]),"+f"(d[45]),"+f"(d[46]),"+f"(d[47]),
      "+f"(d[48]),"+f"(d[49]),"+f"(d[50]),"+f"(d[51]),"+f"(d[52]),"+f"(d[53]),"+f"(d[54]),"+f"(d[55]),
      "+f"(d[56]),"+f"(d[57]),"+f"(d[58]),"+f"(d[59]),"+f"(d[60]),"+f"(d[61]),"+f"(d[62]),"+f"(d[63])
    : "l"(a), "l"(b), "r"(sd));
}
__device__ __forceinline__ void wgmma_ss_n192(float* d, uint64_t a, uint64_t b, int sd) {
  asm volatile("{.reg .pred p; setp.ne.b32 p, %98, 0;\n"
    "wgmma.mma_async.sync.aligned.m64n192k16.f32.bf16.bf16 {%0,%1,%2,%3,%4,%5,%6,%7,%8,%9,%10,%11,%12,%13,%14,%15,%16,%17,%18,%19,%20,%21,%22,%23,%24,%25,%26,%27,%28,%29,%30,%31,%32,%33,%34,%35,%36,%37,%38,%39,%40,%41,%42,%43,%44,%45,%46,%47,%48,%49,%50,%51,%52,%53,%54,%55,%56,%57,%58,%59,%60,%61,%62,%63,%64,%65,%66,%67,%68,%69,%70,%71,%72,%73,%74,%75,%76,%77,%78,%79,%80,%81,%82,%83,%84,%85,%86,%87,%88,%89,%90,%91,%92,%93,%94,%95}, %96, %97, p, 1, 1, 0, 1;}\n"
    : "+f"(d[0]),"+f"(d[1]),"+f"(d[2]),"+f"(d[3]),"+f"(d[4]),"+f"(d[5]),"+f"(d[6]),"+f"(d[7]),
      "+f"(d[8]),"+f"(d[9]),"+f"(d[10]),"+f"(d[11]),"+f"(d[12]),"+f"(d[13]),"+f"(d[14]),"+f"(d[15]),
      "+f"(d[16]),"+f"(d[17]),"+f"(d[18]),"+f"(d[19]),"+f"(d[20]),"+f"(d[21]),"+f"(d[22]),"+f"(d[23]),
      "+f"(d[24]),"+f"(d[25]),"+f"(d[26]),"+f"(d[27]),"+f"(d[28]),"+f"(d[29]),"+f"(d[30]),"+f"(d[31]),
      "+f"(d[32]),"+f"(d[33]),"+f"(d[34]),"+f"(d[35]),"+f"(d[36]),"+f"(d[37]),"+f"(d[38]),"+f"(d[39]),
      "+f"(d[40]),"+f"(d[41]),"+f"(d[42]),"+f"(d[43]),"+f"(d[44]),"+f"(d[45]),"+f"(d[46]),"+f"(d[47]),
      "+f"(d[48]),"+f"(d[49]),"+f"(d[50]),"+f"(d[51]),"+f"(d[52]),"+f"(d[53]),"+f"(d[54]),"+f"(d[55]),
      "+f"(d[56]),"+f"(d[57]),"+f"(d[58]),"+f"(d[59]),"+f"(d[60]),"+f"(d[61]),"+f"(d[62]),"+f"(d[63]),
      "+f"(d[64]),"+f"(d[65]),"+f"(d[66]),"+f"(d[67]),"+f"(d[68]),"+f"(d[69]),"+f"(d[70]),"+f"(d[71]),
      "+f"(d[72]),"+f"(d[73]),"+f"(d[74]),"+f"(d[75]),"+f"(d[76]),"+f"(d[77]),"+f"(d[78]),"+f"(d[79]),
      "+f"(d[80]),"+f"(d[81]),"+f"(d[82]),"+f"(d[83]),"+f"(d[84]),"+f"(d[85]),"+f"(d[86]),"+f"(d[87]),
      "+f"(d[88]),"+f"(d[89]),"+f"(d[90]),"+f"(d[91]),"+f"(d[92]),"+f"(d[93]),"+f"(d[94]),"+f"(d[95])
    : "l"(a), "l"(b), "r"(sd));
}
__device__ __forceinline__ void wgmma_ss_n256(float* d, uint64_t a, uint64_t b, int sd) {
  asm volatile("{.reg .pred p; setp.ne.b32 p, %130, 0;\n"
    "wgmma.mma_async.sync.aligned.m64n256k16.f32.bf16.bf16 {%0,%1,%2,%3,%4,%5,%6,%7,%8,%9,%10,%11,%12,%13,%14,%15,%16,%17,%18,%19,%20,%21,%22,%23,%24,%25,%26,%27,%28,%29,%30,%31,%32,%33,%34,%35,%36,%37,%38,%39,%40,%41,%42,%43,%44,%45,%46,%47,%48,%49,%50,%51,%52,%53,%54,%55,%56,%57,%58,%59,%60,%61,%62,%63,%64,%65,%66,%67,%68,%69,%70,%71,%72,%73,%74,%75,%76,%77,%78,%79,%80,%81,%82,%83,%84,%85,%86,%87,%88,%89,%90,%91,%92,%93,%94,%95,%96,%97,%98,%99,%100,%101,%102,%103,%104,%105,%106,%107,%108,%109,%110,%111,%112,%113,%114,%115,%116,%117,%118,%119,%120,%121,%122,%123,%124,%125,%126,%127}, %128, %129, p, 1, 1, 0, 1;}\n"
    : "+f"(d[0]),"+f"(d[1]),"+f"(d[2]),"+f"(d[3]),"+f"(d[4]),"+f"(d[5]),"+f"(d[6]),"+f"(d[7]),
      "+f"(d[8]),"+f"(d[9]),"+f"(d[10]),"+f"(d[11]),"+f"(d[12]),"+f"(d[13]),"+f"(d[14]),"+f"(d[15]),
      "+f"(d[16]),"+f"(d[17]),"+f"(d[18]),"+f"(d[19]),"+f"(d[20]),"+f"(d[21]),"+f"(d[22]),"+f"(d[23]),
      "+f"(d[24]),"+f"(d[25]),"+f"(d[26]),"+f"(d[27]),"+f"(d[28]),"+f"(d[29]),"+f"(d[30]),"+f"(d[31]),
      "+f"(d[32]),"+f"(d[33]),"+f"(d[34]),"+f"(d[35]),"+f"(d[36]),"+f"(d[37]),"+f"(d[38]),"+f"(d[39]),
      "+f"(d[40]),"+f"(d[41]),"+f"(d[42]),"+f"(d[43]),"+f"(d[44]),"+f"(d[45]),"+f"(d[46]),"+f"(d[47]),
      "+f"(d[48]),"+f"(d[49]),"+f"(d[50]),"+f"(d[51]),"+f"(d[52]),"+f"(d[53]),"+f"(d[54]),"+f"(d[55]),
      "+f"(d[56]),"+f"(d[57]),"+f"(d[58]),"+f"(d[59]),"+f"(d[60]),"+f"(d[61]),"+f"(d[62]),"+f"(d[63]),
      "+f"(d[64]),"+f"(d[65]),"+f"(d[66]),"+f"(d[67]),"+f"(d[68]),"+f"(d[69]),"+f"(d[70]),"+f"(d[71]),
      "+f"(d[72]),"+f"(d[73]),"+f"(d[74]),"+f"(d[75]),"+f"(d[76]),"+f"(d[77]),"+f"(d[78]),"+f"(d[79]),
      "+f"(d[80]),"+f"(d[81]),"+f"(d[82]),"+f"(d[83]),"+f"(d[84]),"+f"(d[85]),"+f"(d[86]),"+f"(d[87]),
      "+f"(d[88]),"+f"(d[89]),"+f"(d[90]),"+f"(d[91]),"+f"(d[92]),"+f"(d[93]),"+f"(d[94]),"+f"(d[95]),
      "+f"(d[96]),"+f"(d[97]),"+f"(d[98]),"+f"(d[99]),"+f"(d[100]),"+f"(d[101]),"+f"(d[102]),"+f"(d[103]),
      "+f"(d[104]),"+f"(d[105]),"+f"(d[106]),"+f"(d[107]),"+f"(d[108]),"+f"(d[109]),"+f"(d[110]),"+f"(d[111]),
      "+f"(d[112]),"+f"(d[113]),"+f"(d[114]),"+f"(d[115]),"+f"(d[116]),"+f"(d[117]),"+f"(d[118]),"+f"(d[119]),
      "+f"(d[120]),"+f"(d[121]),"+f"(d[122]),"+f"(d[123]),"+f"(d[124]),"+f"(d[125]),"+f"(d[126]),"+f"(d[127])
    : "l"(a), "l"(b), "r"(sd));
}
__device__ __forceinline__ void wgmma_rs_n32(float* d, const uint32_t* a, uint64_t b, int sd) {
  asm volatile("{.reg .pred p; setp.ne.b32 p, %21, 0;\n"
    "wgmma.mma_async.sync.aligned.m64n32k16.f32.bf16.bf16 {%0,%1,%2,%3,%4,%5,%6,%7,%8,%9,%10,%11,%12,%13,%14,%15}, {%16,%17,%18,%19}, %20, p, 1, 1, 0;}\n"
    : "+f"(d[0]),"+f"(d[1]),"+f"(d[2]),"+f"(d[3]),"+f"(d[4]),"+f"(d[5]),"+f"(d[6]),"+f"(d[7]),
      "+f"(d[8]),"+f"(d[9]),"+f"(d[10]),"+f"(d[11]),"+f"(d[12]),"+f"(d[13]),"+f"(d[14]),"+f"(d[15])
    : "r"(a[0]), "r"(a[1]), "r"(a[2]), "r"(a[3]), "l"(b), "r"(sd));
}
__device__ __forceinline__ void wgmma_ssT_n32(float* d, uint64_t a, uint64_t b, int sd) {
  asm volatile("{.reg .pred p; setp.ne.b32 p, %18, 0;\n"
    "wgmma.mma_async.sync.aligned.m64n32k16.f32.bf16.bf16 {%0,%1,%2,%3,%4,%5,%6,%7,%8,%9,%10,%11,%12,%13,%14,%15}, %16, %17, p, 1, 1, 1, 0;}\n"
    : "+f"(d[0]),"+f"(d[1]),"+f"(d[2]),"+f"(d[3]),"+f"(d[4]),"+f"(d[5]),"+f"(d[6]),"+f"(d[7]),
      "+f"(d[8]),"+f"(d[9]),"+f"(d[10]),"+f"(d[11]),"+f"(d[12]),"+f"(d[13]),"+f"(d[14]),"+f"(d[15])
    : "l"(a), "l"(b), "r"(sd));
}

__device__ __forceinline__ void wgmma_rs_n32_z(float* d, const uint32_t* a, uint64_t b) {
  asm volatile("{.reg .pred p; setp.ne.b32 p, 0, 0;\n"
    "wgmma.mma_async.sync.aligned.m64n32k16.f32.bf16.bf16 {%0,%1,%2,%3,%4,%5,%6,%7,%8,%9,%10,%11,%12,%13,%14,%15}, {%16,%17,%18,%19}, %20, p, 1, 1, 0;}\n"
    : "=f"(d[0]),"=f"(d[1]),"=f"(d[2]),"=f"(d[3]),"=f"(d[4]),"=f"(d[5]),"=f"(d[6]),"=f"(d[7]),
      "=f"(d[8]),"=f"(d[9]),"=f"(d[10]),"=f"(d[11]),"=f"(d[12]),"=f"(d[13]),"=f"(d[14]),"=f"(d[15])
    : "r"(a[0]), "r"(a[1]), "r"(a[2]), "r"(a[3]), "l"(b));
}

namespace rec {
constexpr int NVR = P_NVR;
constexpr int NVS = 16 - NVR;
constexpr int NVP = P_NVP;
constexpr int NWP = P_NWP;
constexpr uint32_t WO = 0;
constexpr uint32_t XB = 65536;
constexpr uint32_t PK = XB + 32768;
constexpr uint32_t VN = PK + 24576;
constexpr uint32_t VX0 = VN + 4096;
constexpr uint32_t WVS = 131072;
constexpr uint32_t MEM = WVS + 2 * NVS * 2048;
constexpr uint32_t ARO = MEM + 10240;
constexpr uint32_t OB = ARO + 5120;
constexpr uint32_t QT = OB + 2048;
constexpr uint32_t KT = QT + 2048;
constexpr uint32_t RQ = KT + 6144;
constexpr uint32_t RK = RQ + 2048;
constexpr uint32_t SC = RK + 2048;
constexpr uint32_t OT = OB;
constexpr uint32_t TF = SC + 2048;
constexpr uint32_t PRE = MEM + 2 * NVR * 2048;
constexpr uint32_t TA = TF + 8192;
constexpr uint32_t RX = TA + 6144;
constexpr uint32_t VX1 = RX + 2048;
constexpr uint32_t BARS = VX1 + 4096;
constexpr uint32_t PACE = BARS + 18 * 8;
constexpr uint32_t SMEM = BARS + 512;
static_assert(PRE + 14336 <= BARS, "staging");
constexpr int NW1 = P_NW1;
static_assert(SMEM <= 232448, "smem");
constexpr int B_E = 2, B_SC = 3, B_S = 4, B_O = 5, B_F = 6, B_W = 7, B_C = 9, B_K = 10, B_H = 15, B_Q = 1, B_S2 = 6, B_T2 = 9, B_P = 13, B_T = 14, B_R = 11, B_X = 12, B_V = 8;
constexpr int N_P = XE == 1 ? 416 : 384, N_R = XE ? 288 : 320, N_V = AV ? 384 : 512, N_O = AV ? 384 : 416;
constexpr int XC = 16384, X_RING = 131072, X_SC = 65536, X_TOK = 4096;
#define X_VX(i) (((i) >> 1) * 2048 + ((i) & 1) * 512)
#define X_VM(i) (X_VX(i) + 1024)
#define V_RING(n) (((n) & 1) * X_RING + ((n) & 2) * 2048)
#define V_TAG(n) ((~(n) >> 2) & 1)
}
struct RecMaps { CUtensorMap wq, wk, wv, wo, ari; int zero[40]; };

#define F_(x) __uint_as_float(x)
#define U_(x) __float_as_uint(x)
#define AR_R(q) (24 + ((q) & 1) * 16 + ((q) >> 1) * 56)
#define AR_P(q) ((q) >> 1)
#define AR_ROW(i) (24 + ((i) & 1) * 16 + ((i) & 2) * 92 + (((i) >> 2) & 7) + ((i) >> 5) * 128)
constexpr size_t AR_OFF = 32 * 262144;
__device__ __forceinline__ void ar_fetch(uint32_t dst, const CUtensorMap* m, int slot, int half, uint32_t mb) {
  asm volatile("{.reg .pred p; elect.sync _|p, 0xffffffff; @p mbarrier.arrive.expect_tx.shared.b64 _,[%4],10240;\n"
               "@p cp.async.bulk.tensor.3d.shared::cluster.global.mbarrier::complete_tx::bytes [%0],[%1,{%2,%3,%6}],[%4];\n"
               "@p cp.async.bulk.tensor.3d.shared::cluster.global.mbarrier::complete_tx::bytes [%0+5120],[%1,{%2,%5,%7}],[%4];}"
               ::"r"(dst), "l"(m), "r"(slot * 64), "r"(AR_R(half * 2)), "r"(mb), "r"(AR_R(half * 2 + 1)), "r"(AR_P(half * 2)), "r"(AR_P(half * 2 + 1)) : "memory");
}
__device__ __forceinline__ uint4 exch_b128(void* p, uint32_t x, uint32_t y, uint32_t z, uint32_t w) {
  uint4 v;
  asm volatile("{.reg .b128 s, t; .reg .b64 a,b; mov.b64 a,{%5,%6}; mov.b64 b,{%7,%8}; mov.b128 s,{a,b}; atom.relaxed.gpu.global.exch.b128 t,[%4],s;"
               " mov.b128 {a,b},t; mov.b64 {%0,%1},a; mov.b64 {%2,%3},b;}" : "=r"(v.x), "=r"(v.y), "=r"(v.z), "=r"(v.w) : "l"(p), "r"(x), "r"(y), "r"(z), "r"(w) : "memory");
  return v;
}
#define CONSUME(v) do { if ((v) == 0x7fc12345u) sts1(sb + rec::BARS + 96, 0); } while (0)
__device__ __forceinline__ uint32_t tagf(float v, uint32_t tag) { return (__float_as_uint(v) & ~1u) | tag; }
__device__ __forceinline__ uint2 ldg_b64(const void* p) { uint2 v; asm volatile("{.reg .b64 t; ld.relaxed.gpu.global.b64 t,[%2]; mov.b64 {%0,%1},t;}" : "=r"(v.x), "=r"(v.y) : "l"(p) : "memory"); return v; }
__device__ __forceinline__ void stg_b64(void* p, uint32_t x, uint32_t y) { asm volatile("{.reg .b64 t; mov.b64 t,{%1,%2}; st.relaxed.gpu.global.b64 [%0],t;}" ::"l"(p), "r"(x), "r"(y) : "memory"); }
__device__ __forceinline__ uint32_t tagbad(uint32_t x, uint32_t y, uint32_t tag) { uint32_t r; asm("lop3.b32 %0,%1,%2,%3,0x7e;" : "=r"(r) : "r"(x), "r"(y), "r"(tag)); return r; }

__device__ __forceinline__ bool anybad(uint32_t a, uint32_t b, uint32_t c, uint32_t d, uint32_t e, uint32_t f, uint32_t g, uint32_t h, uint32_t tag) {
  uint32_t r;
  asm volatile("{.reg .b32 t,u,v,w; .reg .pred p; lop3.b32 t,%1,%2,%9,0x7e; lop3.b32 u,%3,%4,%9,0x7e; lop3.b32 v,%5,%6,%9,0x7e; lop3.b32 w,%7,%8,%9,0x7e;"
               " lop3.b32 t,t,u,v,0xfe; lop3.b32 t,t,w,1,0xa8; setp.ne.u32 p,t,0; vote.sync.any.pred p,p,0xffffffff; selp.u32 %0,1,0,p;}"
               : "=r"(r) : "r"(a), "r"(b), "r"(c), "r"(d), "r"(e), "r"(f), "r"(g), "r"(h), "r"(tag));
  return r;
}
__device__ __forceinline__ bool anybad(uint32_t a, uint32_t b, uint32_t c, uint32_t d, uint32_t tag) {
  uint32_t r;
  asm volatile("{.reg .b32 t,u; .reg .pred p; lop3.b32 t,%1,%2,%5,0x7e; lop3.b32 u,%3,%4,%5,0x7e;"
               " lop3.b32 t,t,u,1,0xa8; setp.ne.u32 p,t,0; vote.sync.any.pred p,p,0xffffffff; selp.u32 %0,1,0,p;}"
               : "=r"(r) : "r"(a), "r"(b), "r"(c), "r"(d), "r"(tag));
  return r;
}
#define BAD8(r) anybad(r[0].x, r[0].z, r[1].x, r[1].z, r[2].x, r[2].z, r[3].x, r[3].z, tag)
#define BADS(r) anybad(r[0].x, r[0].y, r[1].x, r[1].y, r[2].x, r[2].y, r[3].x, r[3].y, tag)
constexpr float SCS = 0.08838834764831845f * 1.4426950408889634f / 16.f;
__device__ __forceinline__ uint32_t pkh(float lo, float hi, uint32_t tag) {
  uint32_t r;
  asm("{.reg .b32 t; cvt.rn.satfinite.f16x2.f32 t,%1,%2; lop3.b32 %0,t,0xfffffffe,%3,0xea;}" : "=r"(r) : "f"(hi), "f"(lo), "r"(tag));
  return r;
}
__device__ __forceinline__ uint32_t addh(uint32_t a, uint32_t b) { uint32_t r; asm("add.rn.f16x2 %0,%1,%2;" : "=r"(r) : "r"(a), "r"(b)); return r; }
__device__ __forceinline__ float hlo(uint32_t v) { float r; asm("{.reg .b16 a,b; mov.b32 {a,b},%1; cvt.f32.f16 %0,a;}" : "=f"(r) : "r"(v)); return r; }
__device__ __forceinline__ float hhi(uint32_t v) { float r; asm("{.reg .b16 a,b; mov.b32 {a,b},%1; cvt.f32.f16 %0,b;}" : "=f"(r) : "r"(v)); return r; }
__device__ __forceinline__ uint32_t ordh(uint32_t v) {
  uint32_t r;
  asm("{.reg .b32 m; prmt.b32 m,%1,0,0xbb99; lop3.b32 %0,%1,m,0x7fff7fff,0x78;}" : "=r"(r) : "r"(v));
  return r;
}
template <bool MASK>
__device__ __forceinline__ float4 softmax2(const uint2 (&r)[4], uint32_t mx, uint32_t my, uint32_t& k) {
  uint32_t x = addh(addh(r[0].x, r[1].x), addh(r[2].x, r[3].x)), y = addh(addh(r[0].y, r[1].y), addh(r[2].y, r[3].y));
  if (MASK) { x = addh(x, mx); y = addh(y, my); }
  asm("max.f16x2 %0,%1,%2;" : "=r"(k) : "r"(x), "r"(y));
  k = ordh(k);
  const int k0 = __reduce_max_sync(~0u, (int)(k << 16)), k1 = __reduce_max_sync(~0u, (int)k);
  const float m0 = hhi(k0 ^ ((k0 >> 31) & 0x7fff0000)) * -16.f, m1 = hhi(k1 ^ ((k1 >> 31) & 0x7fff0000)) * -16.f;
  return make_float4(ex2(fmaf(hlo(x), 16.f, m0)), ex2(fmaf(hhi(x), 16.f, m1)), ex2(fmaf(hlo(y), 16.f, m0)), ex2(fmaf(hhi(y), 16.f, m1)));
}
__device__ __forceinline__ char* mkp(uint32_t lo, uint32_t hi) { uint64_t r; asm("mov.b64 %0,{%1,%2};" : "=l"(r) : "r"(lo), "r"(hi)); return (char*)r; }
#define LO(p) ((uint32_t)(uint64_t)(p))
#define HI(p) ((uint32_t)((uint64_t)(p) >> 32))
__device__ __forceinline__ void cp16(uint32_t dst, const void* src) { asm volatile("cp.async.cg.shared.global [%0],[%1],16;" ::"r"(dst), "l"(src) : "memory"); }
__device__ __forceinline__ uint32_t xor3(uint32_t a, uint32_t b, uint32_t c) { uint32_t r; asm volatile("lop3.b32 %0,%1,%2,%3,0x96;" : "=r"(r) : "r"(a), "r"(b), "r"(c)); return r; }
__device__ __forceinline__ uint32_t mulbf(uint32_t a, uint32_t b) { uint32_t r; asm("mul.rn.bf16x2 %0,%1,%2;" : "=r"(r) : "r"(a), "r"(b)); return r; }
__device__ __forceinline__ uint32_t fmabf(uint32_t a, uint32_t b, uint32_t c) { uint32_t r; asm("fma.rn.bf16x2 %0,%1,%2,%3;" : "=r"(r) : "r"(a), "r"(b), "r"(c)); return r; }
__device__ __forceinline__ uint32_t addbf(uint32_t a, uint32_t b) { uint32_t r; asm("add.rn.bf16x2 %0,%1,%2;" : "=r"(r) : "r"(a), "r"(b)); return r; }
__device__ __forceinline__ void pv_mem(const uint32_t (&p)[4], uint32_t pm, const uint4 (&v)[4], const uint4 (&vn)[2], uint32_t (&O)[4]) {
  float o[4][4] = {{0, 0, 0, 0}, {0, 0, 0, 0}, {0, 0, 0, 0}, {0, 0, 0, 0}};
  mma16(o[0], v[0].x, v[0].y, v[0].z, v[0].w, p[0], p[1]);
  mma16(o[1], v[2].x, v[2].y, v[2].z, v[2].w, p[0], p[1]);
  mma16(o[2], v[1].x, v[1].y, v[1].z, v[1].w, p[2], p[3]);
  mma16(o[3], v[3].x, v[3].y, v[3].z, v[3].w, p[2], p[3]);
  mma16(o[0], vn[0].x, vn[0].y, vn[0].z, vn[0].w, pm, pm);
  mma16(o[1], vn[1].x, vn[1].y, vn[1].z, vn[1].w, pm, pm);
  O[0] = pk(o[0][0] + o[2][0], o[0][1] + o[2][1]); O[1] = pk(o[0][2] + o[2][2], o[0][3] + o[2][3]);
  O[2] = pk(o[1][0] + o[3][0], o[1][1] + o[3][1]); O[3] = pk(o[1][2] + o[3][2], o[1][3] + o[3][3]);
}
__device__ __forceinline__ void pv_tok(const uint32_t (&p)[4], uint32_t pm, const uint4 (&v)[4], const uint32_t (&vm)[4], uint32_t (&O)[4]) {
  float o[2][4] = {{0, 0, 0, 0}, {0, 0, 0, 0}}, sum[4] = {0, 0, 0, 0};
  const uint32_t one = 0x3f803f80u;
  mma16(sum, one, one, one, one, p[0], p[1]);
  mma16(o[0], v[0].x, v[0].y, v[0].z, v[0].w, p[0], p[1]);
  mma16(o[1], v[2].x, v[2].y, v[2].z, v[2].w, p[0], p[1]);
  mma16(sum, one, one, one, one, p[2], p[3]);
  mma16(o[0], v[1].x, v[1].y, v[1].z, v[1].w, p[2], p[3]);
  mma16(o[1], v[3].x, v[3].y, v[3].z, v[3].w, p[2], p[3]);
  mma8(sum, one, one, pm);
  mma8(o[0], vm[0], vm[1], pm);
  mma8(o[1], vm[2], vm[3], pm);
  float i0, i1;
  asm("rcp.approx.ftz.f32 %0,%1;" : "=f"(i0) : "f"(sum[0]));
  asm("rcp.approx.ftz.f32 %0,%1;" : "=f"(i1) : "f"(sum[1]));
  O[0] = pk(o[0][0] * i0, o[0][1] * i1); O[1] = pk(o[0][2] * i0, o[0][3] * i1);
  O[2] = pk(o[1][0] * i0, o[1][1] * i1); O[3] = pk(o[1][2] * i0, o[1][3] * i1);
}
__device__ __forceinline__ uint32_t sum4bf(uint32_t a, uint32_t b, uint32_t c, uint32_t d) { return addbf(addbf(a, b), addbf(c, d)); }
template <int OFF>
__device__ __forceinline__ void sta1(uint32_t a, uint32_t v, uint32_t mb) {
  asm volatile("st.async.shared::cluster.mbarrier::complete_tx::bytes.b32 [%0+%3],%1,[%2];" ::"r"(a), "r"(v), "r"(mb), "n"(OFF) : "memory");
}

__device__ __forceinline__ void wait_time(uint32_t t) { while ((int)(gtime() - t) < 0) __nanosleep(64); }
__device__ __noinline__ void rec_prefetch(const char* wmod, const char* w1, const char* x, const char* wo) {
  const int hb = blockIdx.x - 128;
  const uint32_t t0 = gtime();
  uint32_t t = t0 + PF0;
#pragma unroll 1
  for (int job = 0; job < (PFT ? 5 : 3); job++) {
    const char* p = job == 0 ? x + (6 + hb) * 65536 : job == 1 ? wmod + hb * 12288 + 4096 : job == 2 ? w1 + hb * 7168 : job == 3 ? x + hb * 8192 : wo + (1020 + hb) * 8192;
    const int n = job == 0 ? 120 - (hb & 2) * 4 : job == 3 ? 128 : 256, d = job == 0 ? 8192 : job == 1 ? 49152 : job == 2 ? 28672 : job == 3 ? 32768 : -32768;
    if (job == 3) t = t0 + PFT;
    PT(8 + job);
#pragma unroll 1
    for (int i = 0; i < n; i++) {
      wait_time(t);
      asm volatile("cp.async.bulk.prefetch.L2.global [%0], %1;" ::"l"(p), "r"(job == 2 ? 7168 : 8192) : "memory");
      p += !job && (i & 7) == 7 ? 204800 : d;
      t += job < 3 ? PFD : PFS;
      if (job && (i & 31) == 31 && ldg_rlx1(&g_fin)) return;
    }
  }
  PT(13);
}
__device__ __noinline__ void rec_helper(uint32_t sb, const bf16* cvec, const bf16* wmod, const char* w1, const bf16* b1, uint32_t t0) {
  const int tid = threadIdx.x, hb = blockIdx.x - 128;
  PT(1);
  for (int i = tid; i < 1024; i += 256) sts1(sb + i * 8, U_(rbf(silu(__bfloat162float(cvec[i])))));
  for (int i = tid; i < 2048; i += 256) g_stat[hb * 2048 + i] = make_uint4(~0u, ~0u, ~0u, ~0u);
  for (int i = tid; i < 512; i += 256) g_cnt[hb * 512 + i] = 0;
#pragma unroll 1
  for (int job = 0; job < 2; job++) {
    wait_time(t0 + PF0 + (job ? 600 : 350) * PFD);
    BAR_SYNC(rec::B_F, 256);
    PT(2 + job * 5);
    const int n8 = job ? 112 : 128, rg = tid >= n8, cg = tid - rg * n8, pitch = job ? 448 : 768;
    const uint4* p = (const uint4*)(job ? w1 + hb * 1792 : (const char*)(wmod + 2048 + hb * 1024)) + rg * pitch + min(cg, n8 - 1);
    float a1[8] = {0, 0, 0, 0, 0, 0, 0, 0}, a2[8] = {0, 0, 0, 0, 0, 0, 0, 0};
#pragma unroll 1
    for (int r0 = rg; r0 < 1024; r0 += 32) {
      uint4 v[16];
#pragma unroll
      for (int i = 0; i < 16; i++) { v[i] = ldg_rlx4(p); p += 2 * pitch; }
#pragma unroll
      for (int i = 0; i < 16; i++) {
        const float2 f = lds2f(sb + (r0 + 2 * i) * 8);
        const float w[8] = {blo(v[i].x), bhi(v[i].x), blo(v[i].y), bhi(v[i].y), blo(v[i].z), bhi(v[i].z), blo(v[i].w), bhi(v[i].w)};
#pragma unroll
        for (int e = 0; e < 8; e++) { a1[e] += f.x * w[e]; a2[e] += f.y * w[e]; }
      }
    }
    const uint32_t rd = sb + 8192;
    if (cg < n8) {
#pragma unroll
      for (int e = 0; e < 8; e++) sts2(rd + rg * 8192 + (cg * 8 + e) * 8, U_(a1[e]), U_(a2[e]));
    }
    BAR_SYNC(rec::B_F, 256);
    if (job == 0) {
      for (int i = tid; i < 1024; i += 256) g_mod[2048 + hb * 1024 + i] = rbf(F_(lds1(rd + i * 8)) + F_(lds1(rd + 8192 + i * 8)));
      BAR_SYNC(rec::B_F, 256);
      PT(6);
      if (tid == 0) { red_rel(&g_mcnt); wait_cnt(&g_mcnt, 4); }
      BAR_SYNC(rec::B_F, 256);
      for (int i = tid; i < 1024; i += 256) sts2(sb + i * 8, U_(rbf(1.f + __ldcg(g_mod + 4096 + i))), U_(__ldcg(g_mod + 3072 + i)));
    } else {
      for (int i = tid; i < 448; i += 256) {
        const int gn = hb * 896 + i * 2;
        const uint32_t bb = *(const uint32_t*)(b1 + gn);
        const float4 u = lds4f(rd + i * 16), w = lds4f(rd + 8192 + i * 16);
        ((uint2*)g_cc)[(gn >> 4) * 8 + ((gn >> 1) & 3) * 2 + ((gn >> 3) & 1)] = make_uint2(pk(u.x + w.x, u.z + w.z), pk(0.5f * (u.y + w.y + blo(bb)), 0.5f * (u.w + w.w + bhi(bb))));
      }
      PT(4);
    }
  }
}

__global__ void __cluster_dims__(2, 1, 1) __launch_bounds__(512, 1)
k_rec(const __grid_constant__ RecMaps mp, const bf16* __restrict__ mem0, const bf16* __restrict__ x, const bf16* __restrict__ cvec,
      const bf16* __restrict__ wmod, const char* __restrict__ w1, const bf16* __restrict__ b1, const char* __restrict__ wo, char* xc, int dF, int dA, int dS, int dM, int dG, int dP, int dX, int dD, int dZ, int dZ2, int dV, int dX2) {
  using namespace rec;
  extern __shared__ __align__(1024) char smem[];
  const uint32_t sb = (uint32_t)__cvta_generic_to_shared(smem);
  if ((sb & 0x3FFFF) != 1024) __trap();
  PH(0); RS(0); if (threadIdx.x == 0) PT(0);
  if (threadIdx.x == 0) {
    int b = blockIdx.x;
    if (b >= 8 && b < 128) {
      const int t = (b >> 1) - 4, u = t - 32;
      b = 2 * (t < 32 ? 4 + (t & 16) + (t & 7) * 2 + ((t >> 3) & 1) : 36 + (u / 14) * 14 + (u % 7) * 2 + ((u / 7) & 1)) + (b & 1);
    }
    sts1(sb + rec::PACE + 24, b);
    const int c = blockIdx.x >> 1, l = c < 36 ? (c - 4) & 7 : (c - 36) % 7, m = c < 4 ? c : c < 36 ? (c - 4) >> 3 : (c - 36) / 7;
    const int g = c < 4 ? 15 : (l >> 1) * 4 + (l & 1) + (c < 36 ? 0 : 2);
    unsigned sm;
    asm("mov.u32 %0,%%smid;" : "=r"(sm));
    if (c < 64) g_slot[sm & 255] = 1 + FMAP;
  }
#define ROLE_REFRESH { asm volatile("mov.u32 %0,%%tid.x;" : "=r"(tid)); wid = __shfl_sync(~0u, tid >> 5, 0); b = __shfl_sync(~0u, lds1(sb + PACE + 24), 0); }
#define ROLE_VARS int tid; asm volatile("mov.u32 %0,%%tid.x;" : "=r"(tid)); \
    int wid = __shfl_sync(~0u, tid >> 5, 0), b = __shfl_sync(~0u, lds1(sb + PACE + 24), 0);
#define wg (wid >> 2)
#define iw (wid & 3)
#define h (b >> 2)
#define j (b & 3)
#define a (b & 1)
#define bb ((b >> 1) & 1)
  const uint32_t wbar = sb + BARS + 48, obar = wbar + 8;
  if (threadIdx.x == 256) {
    for (int i = 0; i < 18; i++) if (i != 12) mbar_init(sb + BARS + i * 8, i == 3 || i == 8 || i == 9 || i == 10 ? 2 : 1);
    for (int i = 0; i < 3; i++) mbar_init(sb + PACE + i * 8, 1);
    asm volatile("fence.mbarrier_init.release.cluster;" ::: "memory");
    FENCE_ASYNC_SMEM();
    mbar_expect(sb + BARS, 2048);
    mbar_expect(sb + BARS + 16, 4096);
    mbar_expect(sb + BARS + 32, 4096);
    mbar_expect(sb + BARS + 40, 4096);
  }
  __syncthreads();
  asm volatile("barrier.cluster.arrive.relaxed.aligned;" ::: "memory");
#define lane ((int)(l16 >> 4))
#define l16 (L16 & 0x1f0)
#define is7 ((L16 & 112) == 112)
#define PIN(x) __shfl_xor_sync(~0u, (uint32_t)(x), 0)
#define REFRESH() L16 = __shfl_xor_sync(~0u, L16, 0)
#define lar ((L16 & 0x180) * 8 + (L16 & 0x70))
#define X_LOAD(n, w, u) \
        asm volatile("{.reg .pred p; elect.sync _|p, 0xffffffff; @p mbarrier.arrive.expect_tx.shared.b64 _,[%2],8192;\n" \
                     "@p cp.async.bulk.shared::cluster.global.mbarrier::complete_tx::bytes [%0],[%1],8192,[%2];}" ::"r"(sb + XB + (w) * 16384 + (u) * 8192), \
                     "l"(g_h + (n) * 4096 + a * 2048 + (w) * 1024 + (u) * 512), "r"(sb + BARS + 64 + (w) * 8) : "memory")
#define lpub ((L16 & 0x30) * 64 + ((L16 >> 3) & 0x38))
#define lrow ((L16 & 0x70) + (((L16 >> 3) ^ L16) & 0x70 & ~((L16 >> 3) & 0x40) ? L16 & 0x180 : 512))

  const int role = __shfl_sync(~0u, threadIdx.x >> 7, 0);
  if (role < 2) {
    asm volatile("setmaxnreg.inc.sync.aligned.u32 %0;" ::"n"(RF_));
    ROLE_VARS
    uint32_t L16 = __shfl_sync(~0u, sb + (tid & 31) * 16, tid & 31);
    uint32_t wQ[16][4], wK[16][4], wV[NVR][4];
    uint32_t frag = sb + ((lane & 7) + (lane >> 4) * 8) * 128 + (((iw * 2 + ((lane >> 3) & 1)) ^ (lane & 7)) << 4);
#define QSW (SWP && !a ? 64 : 0)
    {
      const bool spare = b >= 128;
      const uint32_t t0 = gtime();
      uint4 xr[16];
      int seg = spare ? b - 126 : wg;
      const int half = spare ? wg : a;
      auto x_fetch = [&]() {
        const uint4* px = (const uint4*)x + (seg * 32 + iw * 8 + (lane >> 2)) * 128 + half * 64 + (lane & 3);
#pragma unroll
        for (int i = 0; i < 16; i++) xr[i] = __ldg(px + i * 4);
      };
      if (!spare) {
        uint4 wm[8];
        const uint4* pw = (const uint4*)(wmod + (size_t)((b >> 5) * 256 + (tid >> 3)) * 6144 + (b & 31) * 64) + (tid & 7);
        const float cs = __bfloat162float(cvec[(b >> 5) * 256 + tid]);
#pragma unroll
        for (int i = 0; i < 8; i++) wm[i] = __ldcs(pw + (size_t)i * 32 * 768);
        float* sc = (float*)(smem + PRE);
        sc[tid] = rbf(silu(cs));
        PT(1);
        BAR_SYNC(B_F, 256);
        float acc[8] = {0, 0, 0, 0, 0, 0, 0, 0};
#pragma unroll
        for (int i = 0; i < 8; i++) {
          const float f = sc[i * 32 + (tid >> 3)];
          acc[0] += f * blo(wm[i].x); acc[1] += f * bhi(wm[i].x); acc[2] += f * blo(wm[i].y); acc[3] += f * bhi(wm[i].y);
          acc[4] += f * blo(wm[i].z); acc[5] += f * bhi(wm[i].z); acc[6] += f * blo(wm[i].w); acc[7] += f * bhi(wm[i].w);
        }
#pragma unroll
        for (int i = 0; i < 8; i++) { acc[i] += __shfl_xor_sync(~0u, acc[i], 8); acc[i] += __shfl_xor_sync(~0u, acc[i], 16); }
        float* red = sc + 1024;
        if ((tid & 31) < 8) {
#pragma unroll
          for (int i = 0; i < 8; i++) red[(tid >> 5) * 64 + (tid & 7) * 8 + i] = acc[i];
        }
        BAR_SYNC(B_F, 256);
        PT(2);
        if (tid < 64) {
          float t = 0;
#pragma unroll
          for (int i = 0; i < 8; i++) t += red[i * 64 + tid];
          asm volatile("st.relaxed.gpu.global.u32 [%0],%1;" ::"l"((unsigned*)g_modp + (b >> 5) * 2048 + (b & 31) * 64 + tid), "r"(U_(t) | 1u) : "memory");
        }
      } else {
        asm volatile("griddepcontrol.launch_dependents;");
      }
      x_fetch();
      const uint32_t md = sb + PRE + 6144, rx = mapa(sb, a ^ !spare);
      asm volatile("barrier.cluster.wait.aligned;" ::: "memory");
      if (!spare) {
        mbar_wait(sb + BARS + 88, 0);
#pragma unroll
        for (int i = 0; i < 16; i++) ldsm4t(wQ[i], (frag ^ QSW) + WO + wg * 32768 + i * 2048);
      }
      PT(4);
#pragma unroll 1
      for (int it = 0;; it++) {
        if (tid == 0) mbar_expect(sb + BARS + 104, 512);
        float c[4][4] = {{0, 0, 0, 0}, {0, 0, 0, 0}, {0, 0, 0, 0}, {0, 0, 0, 0}};
#pragma unroll
        for (int i = 0; i < 16; i++) {
          mma16(c[(i & 1) * 2], xr[i].x, 0x3f803f80u, xr[i].y, 0x3f803f80u, xr[i].x, xr[i].y);
          mma16(c[(i & 1) * 2 + 1], xr[i].z, 0x3f803f80u, xr[i].w, 0x3f803f80u, xr[i].z, xr[i].w);
        }
#pragma unroll
        for (int e = 0; e < 4; e++) c[0][e] = (c[0][e] + c[1][e]) + (c[2][e] + c[3][e]);
        const int src = (lane & 28) + (lane >> 3);
        const float sq = __shfl_sync(~0u, (lane & 4) ? c[0][1] : c[0][0], src), sm = __shfl_sync(~0u, (lane & 4) ? c[0][3] : c[0][2], src);
        if ((lane & 3) < 2) sta1<0>(rx + PRE + 10240 + (wid ^ (spare * 4)) * 64 + (lane >> 2) * 8 + (lane & 1) * 4, U_((lane & 1) ? sm : sq), rx + BARS + 104);
        mbar_wait(sb + BARS + 104, it & 1);
        const float2 ot = lds2f(sb + PRE + 10240 + wid * 64 + (lane >> 2) * 8);
        const float mean = (sm + ot.y) * (1.f / 1024);
        const float rs = rsqrtf(fmaxf((sq + ot.x) * (1.f / 1024) - mean * mean, 0.f) + 1e-5f), nm = -mean * rs;
        const uint32_t rh = pk(rs, rs), rl = pk(rs - blo(rh), rs - blo(rh)), n2 = pk(nm, nm);
#define NRM(v) v = fmabf(v, rh, fmabf(v, rl, n2))
#pragma unroll
        for (int i = 0; i < 16; i++) { NRM(xr[i].x); NRM(xr[i].y); NRM(xr[i].z); NRM(xr[i].w); }
        if (!it) {
          PT(3);
#pragma unroll 1
          for (int i = 0; i < 2; i++) {
            uint4 p[4];
            for (int n = 0;; n++) {
#pragma unroll
              for (int e = 0; e < 4; e++) p[e] = ldg_rlx4(g_modp + e * 512 + i * 256 + tid);
              uint32_t ok = 1;
#pragma unroll
              for (int e = 0; e < 4; e++) ok &= p[e].x & p[e].y & p[e].z & p[e].w;
              if (__all_sync(~0u, ok) || n > SPIN_LIMIT / 16) break;
              __nanosleep(100);
            }
#define MSUM(e) (i + rbf((F_(p[0].e) + F_(p[1].e)) + (F_(p[2].e) + F_(p[3].e))))
            sts2(md + i * 2048 + tid * 8, pk(MSUM(x), MSUM(y)), pk(MSUM(z), MSUM(w)));
          }
          BAR_SYNC(B_F, 256);
          PT(5);
        }
        const int e0 = (iw * 8 + (lane >> 2)) * 8 + ((lane & 3) ^ (lane >> 2));
        uint4* dst = g_h + seg * 4096 + half * 2048;
#pragma unroll
        for (int i = 0; i < 16; i++) {
          const uint32_t ma = md + half * 1024 + (lane & 3) * 16 + i * 64;
          const uint4 sv = lds4(ma), cv = lds4(ma + 2048);
          xr[i] = make_uint4(fmabf(xr[i].x, cv.x, sv.x), fmabf(xr[i].y, cv.y, sv.y), fmabf(xr[i].z, cv.z, sv.z), fmabf(xr[i].w, cv.w, sv.w));
        }
        if (!spare) {
#pragma unroll
          for (int i = 0; i < 16; i++) sts4(sb + WO + wg * 32768 + (e0 ^ ((i & 1) * 4)) * 16 + (i >> 1) * 4096, xr[i].x, xr[i].y, xr[i].z, xr[i].w);
          break;
        }
#pragma unroll
        for (int i = 0; i < 16; i++) dst[(e0 ^ ((i & 1) * 4)) + (i >> 1) * 256] = xr[i];
        seg += 4;
        if (seg < 64) x_fetch();
        FENCE_ASYNC();
        BAR_SYNC(B_F, 256);
        if (tid == 0) red_rlx(g_hf + b - 128);
        if (seg >= 64) break;
      }
      if (spare) { rec_helper(sb, cvec, wmod, w1, b1, t0); return; }
      PH(1); PH(2); PT(6);
    }
    ROLE_REFRESH
#define ownv ((iw >> 1) == a)
#define owner (SWP ? iw >= 2 : ownv)
#define vfin ((wid >> 1) == a)
#define oi (wid & 1)
    {
      const uint32_t rsb = mapa(sb, owner ? a : a ^ 1);
      const uint32_t pp = rsb + PK + (owner ? 0 : 12288) + (oi * 2048 + wg * 1024) + l16;
      const uint32_t mb = sb + MEM + wg * 5120;
      sts4(L16 + TF + wid * 512, mb + lrow, owner ? L16 + (lane >> 4) * (RK - RQ - 256) + RQ + oi * 1024 + wg * 256 : rsb + RQ + oi * 1024 + 512 + wg * 256 + (l16 >> 2),
           L16 + OB, frag + wg * NVS * 2048);
      sts4(L16 + TF + 4096 + wid * 512, sb + WO + (wid >> 1) * 16384 + ((lane & 7) + (lane >> 4) * 8) * 128 + ((((wid & 1) * 4 + ((lane >> 3) & 1)) ^ (lane & 7)) << 4),
           sb + ARO + wid * 640 + lrow, pp, LO(xc) + h * 262144 + (bb * 2 + (iw >> 1)) * XC + X_VM(0) + oi * 2048 + a * 256 + (l16 >> 1));
    }
    uint32_t tp = L16 + TF + wid * 512;
    auto park_ptr = [&]() { return lds1(tp + 4096 + 8); };
    auto park_w = [&](const uint32_t* w, int m, uint32_t d) {
      if (SWP && m == 2) d += (sb & 0x1000000) ? 0 : owner ? 0x1003000 : -0x1003000;
      if (m == 2 ? ownv : owner) {
        sts4(d + m * 4096, w[0], w[1], w[2], w[3]); sts4(d + m * 4096 + 512, w[4], w[5], w[6], w[7]);
      } else {
        const uint32_t pb = (d & 0xff000000u) | (1024 + BARS + (m ? 24 + m * 8 : 16));
        sta4(d + m * 4096, w, pb); sta4(d + m * 4096 + 512, w + 4, pb);
      }
    };
    auto park = [&](const float* f, int m, int n, uint32_t d) {
      uint32_t w[8];
#pragma unroll
      for (int i = 0; i < 8; i++) w[i] = pk(f[2 * i], f[2 * i + 1]);
      park_w(w, m, d);
    };
#define D64(lo) (0x4000004000000000ull | (uint32_t)(lo))
#define XD(i) D64(x | (((i) >> 2) * 256 + ((i) & 3) * 2))
    auto xdesc = [&](uint32_t xb) { return ((uint32_t)__shfl_sync(~0u, 1024 + xb + wg * 16384, 0) >> 4) | 0x10000u; };
    auto rs_issue = [&](float* acc, const uint32_t (&w)[16][4], uint32_t xb, bool fence) {
      const uint32_t x = xdesc(xb);
      if (fence) WG_FENCE();
      wgmma_rs_n32_z(acc, w[0], XD(0));
#pragma unroll
      for (int i = 1; i < 16; i++) wgmma_rs_n32(acc, w[i], XD(i), 1);
      WG_COMMIT();
    };
    auto v_issue = [&](float* acc, uint32_t xb, bool fence) {
      const uint32_t dv = ((uint32_t)__shfl_sync(~0u, 1024 + WVS + wg * NVS * 2048, 0) >> 4) | 0x10000u, x = xdesc(xb);
      if (fence) WG_FENCE();
      wgmma_rs_n32_z(acc, wV[0], XD(0));
#pragma unroll
      for (int i = 1; i < VRF; i++) wgmma_rs_n32(acc, wV[i], XD(i), 1);
#pragma unroll
      for (int i = NVR; i < 16; i++) wgmma_ssT_n32(acc, D64(dv + (i - NVR) * 128), XD(i), 1);
#pragma unroll
      for (int i = VRF; i < NVR; i++) wgmma_rs_n32(acc, wV[i], XD(i), 1);
      WG_COMMIT();
    };
    uint32_t mA, vP[2][4];
#define V_AHEAD mA = lds1(tp); frag = lds1(tp + 12); ldsm4t(vP[0], frag + WVS + (15 - NVR) * 2048); ldsm4t(vP[1], frag + WVS + (14 - NVR) * 2048);
    auto vk_pass = [&](int n, uint32_t d, uint32_t xb, bool steady, auto between) {
      float acc[16], acc2[16];
      v_issue(acc, xb, true);
      rs_issue(acc2, wK, xb, false);
      between();
      if (steady || n) mbar_wait(sb + BARS + 80, (n - 1) & 1);
      WG_WAIT(1);
      park(acc, 2 - !!KVO, n, d);
      if (steady) BAR_ARRIVE(B_K, 320);
      V_AHEAD
      WG_WAIT(0);
      park(acc2, 1 + !!KVO, n, d + (VPC ? (vP[1][0] ^ mA) & dZ : 0));
    };
    uint32_t q0[8], q1[8];
    {
      float acc[16], acc2[16];
      FENCE_ASYNC_SMEM();
      BAR_SYNC(B_F, 256);
      rs_issue(acc, wQ, WO, true);
      rs_issue(acc2, wQ, WO + 32768, false);
      WG_WAIT(0);
#pragma unroll
      for (int i = 0; i < 8; i++) { q0[i] = pk(acc[2 * i], acc[2 * i + 1]); q1[i] = pk(acc2[2 * i], acc2[2 * i + 1]); }
    }
    mbar_wait(wbar, 0);
    PT(7);
#pragma unroll
    for (int i = 0; i < 16; i++) ldsm4t(wK[i], (frag ^ QSW) + XB + wg * 32768 + i * 2048);
#pragma unroll
    for (int i = 0; i < NVR; i++) ldsm4t(wV[i], frag + MEM + (wg * NVR + i) * 2048);
    FENCE_ASYNC_SMEM();
    PH(3); PT(8);
    CLUSTER_SYNC();
    PT(9);
    frag += wg * NVS * 2048;
    park_w(q0, 0, park_ptr());
    PT(10);
#pragma unroll 1
    for (int n = 0; n < 2; n++) {
      asm volatile("" : "+r"(wid));
      vk_pass(n, park_ptr(), n * XB, false, [&]() {
        if (n) {
          BAR_SYNC(B_C, 320);
          PT(12);
          mbar_wait(sb + BARS + 24, 0);
          park_w(q1, 0, park_ptr());
        }
      });
      if (n) break;
      PT(11);
      BAR_SYNC(B_C, 448);
      if (tid == 0) {
        mbar_expect(obar, 65536);
#pragma unroll 1
        for (int i = 0; i < 4; i++) tma2d(sb + WO + i * 16384, &mp.wo, j * 256 + i * 64, h * 128, obar);
      }
    }
    static_assert(WO == 0, "x");
    {
      BAR_ARRIVE(B_P, N_P); if (!HX) BAR_ARRIVE(B_X, 320); if (XE != 1) BAR_ARRIVE(B_Q, 288);
    }
    PT(13);
    mbar_wait(obar, 0);
    PH(4); RS(1); PT(14);
    ROLE_REFRESH
    for (int s = 0; s < 64; s++) {
      asm volatile("" : "+r"(tp), "+r"(wid));
      asm volatile("mov.u32 %0,%%cluster_ctarank;" : "=r"(b));
      uint32_t vS[NVS][4], bf[8][4];
      static_assert(NVR == 5, "schedule");
#define VLD(k) ldsm4t(vS[(k) - NVR], frag + WVS + ((k) - NVR) * 2048)
#define BLD(t) ldsm4t(bf[t], mA + (t) * 640)
#define VMMA(c, w, i) mma16(c, (w)[0], (w)[1], (w)[2], (w)[3], bf[(i) >> 1][((i) & 1) * 2], bf[(i) >> 1][((i) & 1) * 2 + 1])
#define VS_(c, k) VMMA(c, vS[(k) - NVR], k)
#define QK(i) VMMA(cQ, wQ[i], i); VMMA(cK, wK[i], i)
#define PREV if (NF) { VLD(13); VLD(12); if (NF > 2) VLD(11); } else { VLD(15); VLD(14); }
      if (s > 0) BAR_SYNC(B_R, N_R);
      float cV[4] = {0, 0, 0, 0}, cW[4] = {0, 0, 0, 0};
      {
        float cQ[4] = {0, 0, 0, 0}, cK[4] = {0, 0, 0, 0};
        BLD(7); BLD(6); BLD(5); BLD(4); if (NB0 > 4) BLD(3);
        SCHED_FENCE(47);
        QK(15); VMMA(cV, vP[0], 15);
        QK(14); VMMA(cV, vP[1], 14);
        QK(13); QK(12);
        SCHED_FENCE(51);
        if (NB0 < 5) BLD(3);
        BLD(2); BLD(1); BLD(0);
        const uint32_t rm = lds1(tp + 4);
        if (!NF) frag = lds1(tp + 12);
        QK(11); QK(10); QK(9); QK(8); QK(7);
        if (PV0 == 6) { SCHED_FENCE(48); PREV }
        QK(6); QK(5);
        if (PV0 == 4) { QK(4); SCHED_FENCE(48); PREV } else { QK(4); }
        QK(3); QK(2); QK(1); QK(0);
        const uint32_t w0 = pk(cQ[0] * SCS, cQ[1] * SCS), w1 = pk(cQ[2] * SCS, cQ[3] * SCS), w2 = pk(cK[0], cK[1]), w3 = pk(cK[2], cK[3]);
        if (owner) {
          stsm4(rm, w0, w1, w2, w3);
          BAR_ARRIVE(B_E, 256);
        } else {
          const uint32_t mm = (rm & 0xff000000u) | (1024 + BARS);
          sta1<0>(rm, w0, mm); sta1<128>(rm, w1, mm);
          sta1<RK - RQ>(rm, w2, mm); sta1<RK - RQ + 128>(rm, w3, mm);
        }
        if (wid == 2) TS(0);
      }
      uint4 t1;
      uint32_t oA, wo[16][4];
      {
        if (NF == 0) {
          VLD(13); VLD(12);
          VS_(cW, 15); VS_(cV, 14); VLD(11); VMMA(cW, wV[0], 0); VLD(10); VMMA(cV, wV[1], 1); VLD(9);
          VMMA(cW, wV[2], 2); VLD(8); VMMA(cV, wV[3], 3); VLD(7); VMMA(cW, wV[4], 4); VS_(cV, 13); VLD(6); VS_(cW, 12); VLD(5);
          VS_(cV, 11);
        } else {
          if (NF < 3) VLD(11);
          VLD(10);
          VS_(cW, 13); VLD(9); VS_(cV, 12); VLD(8); VLD(7); VMMA(cW, wV[0], 0); VMMA(cV, wV[1], 1); VLD(6);
          VMMA(cW, wV[2], 2); VMMA(cV, wV[3], 3); VLD(5); VMMA(cW, wV[4], 4); VS_(cV, 11);
        }
        VS_(cW, 10); VS_(cV, 9); VS_(cW, 8); VS_(cV, 7); VS_(cW, 6); VS_(cV, 5);
#pragma unroll
        for (int e = 0; e < 4; e++) cV[e] += cW[e];
        const uint32_t ex = tp + (RX - TF) - wg * 2048;
        t1 = lds4(tp + 4096 + (T1L ? vS[3][0] & dZ : 0));
        oA = lds1(tp + 8 + (s & dZ));
        if (wg) {
          sts4(ex, U_(cV[0]), U_(cV[1]), U_(cV[2]), U_(cV[3]));
          BAR_ARRIVE(B_T2, 256);
        }
#pragma unroll
        for (int i = 0; i < VCO; i++) ldsm4t(wo[i], (t1.x ^ ((i & 1) * 32)) + (i >> 1) * 2048);
        if (!wg) {
          BAR_SYNC(B_T2, 256);
          const float4 u = lds4f(ex);
          stg_b64(mkp(t1.w ^ ((s & 1) * X_RING), HI(xc)), (pk(cV[0] + u.x, cV[1] + u.y) & ~1u) | (((s >> 1) + 1) & 1), pk(cV[2] + u.z, cV[3] + u.w));
        }
      }
      if (s == 63) break;
      {
        const uint32_t woA = t1.x, woB = woA ^ 32;
#pragma unroll
        for (int i = VCO; i < NW0; i++) ldsm4t(wo[i], ((i & 1) ? woB : woA) + (i >= WCH ? wo[(i - WCH + NWP) % NWP][0] & dZ : 0) + (i >> 1) * 2048);
        BAR_SYNC(B_S, 416);
        float inv0, inv1;
        uint32_t p[4], pm;
        const uint32_t pa = oA + (SC - OB), one = 0x3f803f80u;
#define P_LOAD ldsm4t(p, pa); asm volatile("ldmatrix.sync.aligned.m8n8.x1.trans.shared.b16 {%0},[%1];" : "=r"(pm) : "r"(pa + 512) : "memory");
        if (s < 62) {
          float acc[16];
          rs_issue(acc, wQ, XB, true);
          mbar_wait(sb + BARS + 24, (s + 1) & 1);
          WG_WAIT(0);
          uint32_t qw[8];
#pragma unroll
          for (int i = 0; i < 8; i++) qw[i] = pk(acc[2 * i], acc[2 * i + 1]);
#pragma unroll
          for (int i = NW0; i < NW1; i++) ldsm4t(wo[i], ((i & 1) ? woB : woA) + (i >> 1) * 2048);
          BAR_SYNC(B_V, N_V);
          if (RSO) { P_LOAD }
          park_w(qw, 0, t1.z + (RSO == 1 ? pm & dZ : 0));
        } else {
#pragma unroll
          for (int i = NW0; i < NW1; i++) ldsm4t(wo[i], ((i & 1) ? woB : woA) + (i >> 1) * 2048);
          BAR_SYNC(B_V, N_V);
          if (RSO) { P_LOAD }
        }
#pragma unroll
        for (int i = NW1; i < NWP; i++) ldsm4t(wo[i], ((i & 1) ? woB : woA) + (i >> 1) * 2048);
        {
          float sum[4] = {0, 0, 0, 0}, su2[4] = {0, 0, 0, 0};
          if (!RSO) { P_LOAD }
          mma16(sum, one, one, one, one, p[0], p[1]);
          mma16(su2, one, one, one, one, p[2], p[3]);
          mma8(sum, one, one, pm);
          inv0 = sum[0] + su2[0]; inv1 = sum[1] + su2[1];
          SCHED_FENCE(57);
        }
        BAR_SYNC(B_O, N_O);
        float c[2][4] = {{0, 0, 0, 0}, {0, 0, 0, 0}};
        uint32_t o[4][4];
#pragma unroll
        for (int i = 0; i < NOP_; i++) ldsm4t(o[i], oA + i * 512);
        SCHED_FENCE(46);
        asm("rcp.approx.ftz.f32 %0,%0;" : "+f"(inv0));
        asm("rcp.approx.ftz.f32 %0,%0;" : "+f"(inv1));
#pragma unroll
        for (int i = 0; i < 16; i++) {
          mma16(c[i & 1], wo[i][0], wo[i][1], wo[i][2], wo[i][3], o[i >> 2][i & 2], o[i >> 2][(i & 2) + 1]);
          if (i == 1 && NOP_ < 3) ldsm4t(o[2], oA + 1024);
          if (i == 3 && NOP_ < 4) ldsm4t(o[3], oA + 1536);
          if (i + NWP < 16) ldsm4t(wo[(i + NWP) & 15], (((i + NWP) & 1) ? woB : woA) + ((i + NWP) >> 1) * 2048);
        }
        stsm4(t1.y, pk(c[0][0] * inv0, c[0][1] * inv1), pk(c[0][2] * inv0, c[0][3] * inv1), pk(c[1][0] * inv0, c[1][1] * inv1), pk(c[1][2] * inv0, c[1][3] * inv1));
      }
      const uint32_t d = park_ptr();
      BAR_SYNC(B_W, 384);
      if (s < 62) {
        vk_pass(s + 2, d, XB, true, []() {});
        if (XE == 2) BAR_ARRIVE(B_Q, 288);
        BAR_ARRIVE(B_P, N_P); if (!HX) BAR_ARRIVE(B_X, 320);
        TS(10);
      } else {
        V_AHEAD
        CONSUME(vP[1][0]);
      }
    }
  } else if (role == 3) {
    asm volatile("setmaxnreg.dec.sync.aligned.u32 24;");
    if (blockIdx.x >= 128) return;
    ROLE_VARS
    const uint32_t L16 = sb + (tid & 31) * 16;
    asm volatile("barrier.cluster.wait.aligned;" ::: "memory");
    CLUSTER_SYNC();
    sts1(sb + PACE + 36, LO(xc) + h * 262144 + X_VM(0));
    auto vm_stage = [&](int s) {
      if (AV) return;
      const uint32_t tag = ((s >> 1) + 1) & 1;
      const char* xm = mkp(lds1(sb + PACE + 36) + (s & 1) * X_RING + iw * XC + (l16 >> 1), HI(xc));
      uint2 m[4];
      CONSUME(LO(xm));
      BAR_SYNC(B_S2, 256);
      if (dZ2 > 1) { const uint32_t c = clk(); while (clk() - c < (uint32_t)dZ2) {} }
      int it = 0;
      while (true) {
#pragma unroll
        for (int i = 0; i < 4; i++) m[i] = ldg_b64(xm + (i >> 1) * 2048 + (i & 1) * 256);
        sts4(L16 + VN + iw * 512, m[0].x, m[0].y, m[1].x, m[1].y);
        sts4(L16 + VN + iw * 512 + 2048, m[2].x, m[2].y, m[3].x, m[3].y);
        if (HV || !anybad(m[0].x, m[1].x, m[2].x, m[3].x, tag)) break;
        RP(2);
        if (++it > SPIN_LIMIT) __trap();
      }
      if (s < 63) BAR_ARRIVE(B_V, 512); else BAR_ARRIVE(B_V, 256);
    };
    if (iw == 0) {
      wait_cnt(&g_hcnt, 128);
#pragma unroll 1
      for (int s = 0; s < 63; s++) {
        if (s < 62) for (int it = 0; ldg_rlx1(g_hf + (s & 3)) <= (s >> 2); it++) if (it > SPIN_LIMIT) __trap();
        if (XE == 1) BAR_SYNC(B_P, N_P); else if (XE == 2) BAR_SYNC(B_Q, 288); else if (s) BAR_SYNC(B_R, 320); else BAR_SYNC(B_Q, 288);
        if (s < 62) { X_LOAD(s + 2, 0, 0); X_LOAD(s + 2, 1, 0); X_LOAD(s + 2, 0, 1); X_LOAD(s + 2, 1, 1); }
        if (s >= 7) {
          const uint32_t zo = b * 160 + l16;
          if (l16 < 160) CONSUME(exch_b128(xc + AR_OFF + AR_ROW(zo >> 7) * 1024 + (zo & 127) + ((s + 1) & 7) * 128, 0, 0, 0, 0).x);
          __syncwarp();
        }
        if (s < 62) { mbar_wait(sb + BARS + 64, s & 1); mbar_wait(sb + BARS + 72, s & 1); }
        BAR_ARRIVE(B_S, 416);
        vm_stage(s);
        if (!AV) BAR_ARRIVE(B_O, 416);
        BAR_SYNC(B_W, 384);
        FENCE_ASYNC_SMEM();
        asm volatile("{.reg .pred p; elect.sync _|p, 0xffffffff; @p cp.reduce.async.bulk.tensor.3d.global.shared::cta.add.bulk_group [%0,{%1,%2,%4}],[%3];}"
                     ::"l"(&mp.ari), "r"((s & 7) * 64), "r"(AR_R(j)), "r"(sb + ARO), "r"(AR_P(j)) : "memory");
        BULK_COMMIT();
        asm volatile("st.relaxed.gpu.global.u32 [%0],%1;" ::"l"(g_tm + (s & 1) * 128 + b), "r"(gtime()) : "memory");
        TS(3);
        BULK_WAIT_READ(0);
      }
      if (!XE) BAR_ARRIVE(B_R, 320);
    } else if (iw == 1) {
      const uint32_t pc = sb + MEM + (lane >> 2) * 640 + (lane & 3) * 144 + (lane & 12), pd = sb + MEM + (lane & 15) * 640 + 576 + (lane & 3) * 16 + (lane & 12);
      uint32_t T = 0, par = 0;
      int est = dA;
#pragma unroll 1
      for (int s = 0; s < 63; s++) {
        if (s) {
          const uint4 tm = ldg_rlx4((const char*)g_tm + ((s + 1) & 1) * 512 + l16);
          const int t0 = tm.x - T, t1 = tm.y - T, t2 = tm.z - T, t3 = tm.w - T;
          const int e = max(dF + (__reduce_add_sync(~0u, (t0 + t1) + (t2 + t3)) >> 7), dV + __reduce_max_sync(~0u, max(max(t0, t1), max(t2, t3))));
          if (s > 1) est += max(min(e >> 2, dP), -dP);
          T += (s == 1 || e > dM ? e : 0) + est;
        }
        vm_stage(s);
        BAR_SYNC(B_W, 384);
        SCHED_FENCE(70);
        const uint32_t tW = gtime();
        if (s == 0) T = tW + 800;
        const uint32_t te = tW + min(max((int)(T - tW), dD), 2000);
        while ((int)(gtime() - te) < 0) {}
        TS(7);
        int it = 0;
        while (true) {
          ar_fetch(sb + MEM, &mp.ari, s & 7, a, sb + BARS + 112);
          mbar_wait(sb + BARS + 112, par);
          par ^= 1;
          const uint32_t n0 = lds1(pc), n1 = lds1(pc + 5120), n2 = lds1(pd);
          if (!__any_sync(~0u, (tagbad(n0, n1, 0x42004200) | (n2 ^ 0x42004200)) != 0)) break;
          RP(0);
          if (++it > SPIN_LIMIT) __trap();
        }
        BAR_ARRIVE(B_R, N_R);
        TS(11);
      }
    } else {
#define V_LOAD(n) do { if (lane == 0) mbar_expect(sb + BARS + 8, 8192); __syncwarp(); \
        if (lane < 16) bulk_ld(sb + ((lane & 2) ? VX1 : VX0) + (lane & 1) * 2048 + (lane >> 2) * 512, \
                               xc + h * 262144 + V_RING(n) + (lane >> 2) * XC + X_VX(lane & 3), 512, sb + BARS + 8); __syncwarp(); } while (0)
      uint32_t src = L16 + PK + (iw & 1) * 2048;
#define qd (L16 + (lane >> 4) * 256 + QT + (iw & 1) * 1024)
#define vd (LO(xc) + h * 262144 + j * XC + (iw & 1) * 2048 + l16)
#define FINISH [&](int n, int m) { \
_Pragma("unroll") \
        for (int i = 1; i >= 0; i--) { \
          const uint32_t p = src + m * 4096 + i * 512; \
          uint4 u = lds4(p); \
          const uint4 w = lds4(p + 1024), y = lds4(p + 12288), z = lds4(p + 13312); \
          u = make_uint4(sum4bf(u.x, w.x, y.x, z.x), sum4bf(u.y, w.y, y.y, z.y), sum4bf(u.z, w.z, y.z, z.z), sum4bf(u.w, w.w, y.w, z.w)); \
          if (m == 2) stg_b128(mkp(vd ^ V_RING(n), HI(xc)) + i * 512, (u.x & ~1u) | V_TAG(n), u.y, u.z, u.w); \
          else stsm4(qd + (n & 1) * 4096 + m * 2048 + i * 256, u.x, u.z, u.y, u.w); \
          SCHED_FENCE(71 + m * 2 + i); \
        } \
      }
#pragma unroll 1
      for (int n = 0; n < 64; n++) {
        src = PIN(src);
        b = __shfl_sync(~0u, lds1(sb + PACE + 24), 0);
        const uint32_t L16 = src - PK - (iw & 1) * 2048;
        auto finish = FINISH;
        if (n < 2) { if (n) BAR_SYNC(B_X, 320); else BAR_SYNC(B_C, 448); }
        mbar_wait(sb + BARS + 16, n & 1);
        finish(n, 0);
        __syncwarp();
        if (lane == 0) mbar_arrive_cl(mapa(sb, a ^ 1) + BARS + 24);
        if (n > 1) BAR_SYNC(B_K, 320);
        mbar_wait(sb + BARS + (KVO ? 32 : 40), n & 1);
        finish(n, 2 - !!KVO);
        if (n > 1) BAR_SYNC(B_X, 320);
        mbar_wait(sb + BARS + (KVO ? 40 : 32), n & 1);
        finish(n, 1 + !!KVO);
        BAR_SYNC(B_T, 64);
        if (lane == 0) {
          if (iw == 2 && n < 63) { mbar_expect(sb + BARS + 16, 4096); mbar_expect(sb + BARS + 32, 4096); mbar_expect(sb + BARS + 40, 4096); }
          mbar_arrive_cl(mapa(sb, a ^ 1) + BARS + 80);
        }
        __syncwarp();
        if (n) {
          vm_stage(n - 1);
          BAR_SYNC(B_W, 384);
        } else {
          BAR_SYNC(B_C, 320);
        }
        if (iw == 2) V_LOAD(n);
      }
#undef qd
#undef vd
    }
    { ROLE_REFRESH }
    vm_stage(63);
  } else {
    asm volatile("setmaxnreg.dec.sync.aligned.u32 %0;" ::"n"(RA_));
    if (blockIdx.x >= 128) { if (threadIdx.x == 256) rec_prefetch((const char*)wmod, w1, (const char*)x, wo); return; }
    ROLE_VARS
    uint32_t L16 = __shfl_sync(~0u, sb + (tid & 31) * 16, tid & 31);
    const uint32_t ts = gtime();
    uint2 m0[8];
#pragma unroll
    for (int r = 0; r < 8; r++) m0[r] = *(const uint2*)(mem0 + r * 1024 + a * 512 + (tid - 256) * 4);
    if (wid == 9) {
#pragma unroll 1
      for (int i = b * 80 + (tid & 31); i < b * 80 + 80; i += 32) ((uint4*)(xc + AR_OFF))[AR_ROW(i >> 6) * 64 + (i & 63)] = make_uint4(0, 0, 0, 0);
      if (b == 0) g_fin = 0;
      FENCE_ASYNC();
      __syncwarp();
      if (tid == 288) red_rlx(&g_hcnt);
    }
    if (tid == 256) {
      const int col = h * 128 + bb * 64;
#pragma unroll 1
      for (int c = 0; c < 12 + WIN; c++) {
        const uint32_t mb = sb + PACE + (c % WIN) * 8;
        if (c >= WIN) mbar_wait(mb, (c / WIN - 1) & 1);
        PT(16 + c);
        if (c == 3 + WIN) asm volatile("mbarrier.arrive.shared.b64 _,[%0];" ::"r"(sb + BARS + 88) : "memory");
        if (c >= 12) continue;
        mbar_expect(mb, 16384);
        if (c < 8) tma2d(sb + (c >> 2) * XB + (c & 3) * 16384, (c & 4) ? &mp.wk : &mp.wq, col, a * 512 + (c & 3) * 128, mb);
        else
#pragma unroll 1
          for (int i = (c & 1) * 8; i < (c & 1) * 8 + 8; i++) {
            const int w = (c - 8) >> 1;
            tma2d(i < NVR ? sb + MEM + (w * NVR + i) * 2048 : sb + WVS + (w * NVS + i - NVR) * 2048, &mp.wv, col, a * 512 + w * 256 + i * 16, mb);
          }
      }
      asm volatile("mbarrier.arrive.shared.b64 _,[%0];" ::"r"(wbar) : "memory");
      for (int i = 0; i < 3; i++) asm volatile("mbarrier.inval.shared.b64 [%0];" ::"r"(sb + PACE + i * 8) : "memory");
    }
    __syncwarp();
    asm volatile("barrier.cluster.wait.aligned;" ::: "memory");
    CLUSTER_SYNC();
#pragma unroll 4
    for (int i = 0; i < 16; i++) {
      const uint4 v = lds4(L16 + WO + 32768 + iw * 8192 + i * 512);
      sts4(L16 + XB + iw * 8192 + i * 512, v.x, v.y, v.z, v.w);
    }
#pragma unroll
    for (int i = 0; i < 4; i++) {
      const int k = (tid - 256) * 4 + i, m = (k >> 3) & 3, r = k & 7;
#define M0W(r) __byte_perm((i & 2) ? m0[r].y : m0[r].x, (i & 2) ? m0[r + 1].y : m0[r + 1].x, (i & 1) ? 0x7632 : 0x5410)
      sts4(sb + MEM + (k >> 5) * 640 + (r == m ? 512 : m * 128) + r * 16, M0W(0), M0W(2), M0W(4), M0W(6));
    }
#pragma unroll 1
    for (int i = tid - 256; i < 192; i += 128) {
      const uint32_t c = i < 128 ? 0x42004200 : 0x3f803f80;
      sts4(sb + MEM + (i >> 3) * 640 + ((i & 7) < 4 ? (i & 7) * 144 : 512 + (i & 7) * 16), c, c, c, c);
    }
    static_assert(ARO == MEM + 16 * 640, "counters");
    FENCE_ASYNC_SMEM();
    BAR_ARRIVE(B_C, 448);
    if (WPF && tid == 256) {
      wait_time(ts + WPF);
#pragma unroll 1
      for (int c = 0; c < 4; c++) tma2d_pf(&mp.wo, j * 256 + c * 64, h * 128);
    }
    __syncwarp();
#define pr (L16 + SC)
    {
      const int lim = j * 8 + iw * 2 - (lane & 7) - (lane & 8) * 2;
      const bool mk = L16 & 256;
      const int rw = lane >> 2;
      sts4(L16 + TA + iw * 512,
           iw != 2 ? L16 + KT + (iw & 1) * 256 + (lane >> 4) * 256 : sb + RK + (L16 & 0x80) * 2 + ((L16 >> 1) & 0x80) + (L16 & 0x70),
           L16 + QT + (lane >> 3) * 384, sb + SC + min(lane >> 3, 2) * 256 + (L16 & 0x70) + iw * 4, L16 + (lane >> 4) * 256 + QT + (iw >> 1) * 1024 + (iw & 1) * 256);
      sts4(L16 + TA + 2048 + iw * 512, mk ? 0u : (lim < 0 ? 0xfc00u : 0u) | (lim < -1 ? 0xfc000000u : 0u),
           mk ? 0xfc00fc00u : (lim < 8 ? 0xfc00u : 0u) | (lim < 7 ? 0xfc000000u : 0u),
           ((h * 2 + (iw >> 1)) * 1024 + (j * 8 + rw) * 8 + (((iw & 1) * 4 + (lane & 3)) ^ rw)) * 16, sb + OT + iw * 512 + (L16 & 0x70) * 4 + ((L16 >> 3) & 0x30));
    }
    {
      const uint32_t xh = LO(xc) + h * 262144, xs = xh + X_SC + iw * 1024 + min(lane, 16 + (lane & 7)) * 8;
      sts4(L16 + TA + 4096 + iw * 512, xh + X_SC + j * 256 + iw * 64 + lpub, xs, dS, iw != 2 ? 0 : U_(SCS));
      sts1(L16 + TA + 12 + iw * 512, xs + X_TOK + j * 4096);
    }
    uint32_t tA = L16 + TA + iw * 512;
#define tw (tA - L16 != TA + 1024)
#define XP_(lo) mkp(lo, HI(xc))
    auto publish = [&](char* d, const uint2& w) { stg_b64(d, w.x, w.y); };
    BAR_SYNC(B_P, N_P);
    for (int s = 0; s < 64; s++) {
      asm volatile("" : "+r"(L16), "+r"(tA));
      const uint32_t tag = ((s >> 1) + 1) & 1, ring = (s & 1) * X_RING;
      const uint4 t0 = lds4(tA);
      const uint4 tx = lds4(tA + 4096);
      const uint32_t xo = tx.x ^ ring, xs = tx.y ^ ring;
      const float gm = F_(tx.w);
      const uint32_t qA = t0.y + (ring >> 5);
      uint32_t c0;
      uint2 ts[4];
      uint4 v[4];
      uint32_t af[2][4], qt[4][4];
      {
        const uint32_t aA = t0.x + (tw ? ring >> 5 : 0);
        uint32_t ql[2][4], qr[2][4];
        uint2 pw_;
        float c[4] = {0, 0, 0, 0}, d[4] = {0, 0, 0, 0};
        if (s == PDS) asm volatile("griddepcontrol.launch_dependents;");
#pragma unroll
        for (int i = 0; i < 4; i++) ldsm4t(qt[i], qA + i * 128);
        mbar_wait(sb + BARS + 8, s & 1);
        TS(4);
        BAR_SYNC(B_E, 256);
#define PACK(c) make_uint2(pkh(fmaf(c[2], gm, c[0] * SCS), fmaf(c[3], gm, c[1] * SCS), tag), pkh(c[2] * SCS, c[3] * SCS, tag))
#define SMMA(x, t, q, i) mma16(x, af[t][0], af[t][1], af[t][2], af[t][3], q[t][i], q[t][i + 1])
        ldsm4t(ql[0], L16 + RQ); ldsm4t(ql[1], L16 + RQ + 1024); ldsm4t(af[0], aA); ldsm4t(af[1], aA + 1024);
        CONSUME(xo);
#define QSUM(t, i) addbf(addbf(ql[t][i], ql[t][i + 2]), addbf(qr[t][i], qr[t][i + 2]))
#define STAIL mma16(c, af[0][0], af[0][1], af[0][2], af[0][3], QSUM(0, 0), QSUM(0, 1)); mma16(d, af[1][0], af[1][1], af[1][2], af[1][3], QSUM(1, 0), QSUM(1, 1));
        if (tw) {
          mbar_wait(sb + BARS, s & 1);
          TS(8);
          ldsm4t(qr[0], L16 + RQ + 512); ldsm4t(qr[1], L16 + RQ + 1536);
          STAIL
          pw_ = make_uint2(pkh(c[0] + d[0], c[1] + d[1], tag), pkh(c[2] + d[2], c[3] + d[3], tag));
        } else {
          uint32_t ar[2][4];
          mbar_wait(sb + BARS, s & 1);
          ldsm4t(qr[0], L16 + RQ + 512); ldsm4t(ar[0], aA + 512); ldsm4t(qr[1], L16 + RQ + 1536); ldsm4t(ar[1], aA + 1536);
#pragma unroll
          for (int i = 0; i < 8; i++) af[i >> 2][i & 3] = addbf(af[i >> 2][i & 3], ar[i >> 2][i & 3]);
          STAIL
          pw_.x = pw_.y = pkh((c[0] + c[2]) + (d[0] + d[2]), (c[1] + c[3]) + (d[1] + d[3]), tag);
        }
        publish(XP_(xo), pw_);
        c0 = clk() + tx.z;
        TS(1);
      }
      uint2 r[4];
      bool vbad;
      uint32_t xm;
      uint4 vn[2];
#define TOKS(i) { float e0[4] = {0, 0, 0, 0}, e1[4] = {0, 0, 0, 0}; \
        mma16(e0, af[0][0], af[0][1], af[0][2], af[0][3], qt[i][0], qt[i][1]); mma16(e1, af[0][0], af[0][1], af[0][2], af[0][3], qt[i + 1][0], qt[i + 1][1]); \
        mma16(e0, af[1][0], af[1][1], af[1][2], af[1][3], qt[i][2], qt[i][3]); mma16(e1, af[1][0], af[1][1], af[1][2], af[1][3], qt[i + 1][2], qt[i + 1][3]); \
        ts[i] = PACK(e0); ts[i + 1] = PACK(e1); }
      {
        float e[4][4];
#pragma unroll
        for (int i = 0; i < 4; i++) {
          e[i][0] = e[i][1] = e[i][2] = e[i][3] = 0.f;
          mma16(e[i], af[0][0], af[0][1], af[0][2], af[0][3], qt[i][0], qt[i][1]);
        }
#pragma unroll
        for (int i = 0; i < 4; i++) mma16(e[i], af[1][0], af[1][1], af[1][2], af[1][3], qt[i][2], qt[i][3]);
        SCHED_FENCE(55);
        if (s < 63) BAR_ARRIVE(B_S, 416);
        SCHED_FENCE(58);
        v[0] = lds4(tA + (VX0 - TA)); v[1] = lds4(tA + (VX0 - TA) + 2048); v[2] = lds4(tA + (VX1 - TA)); v[3] = lds4(tA + (VX1 - TA) + 2048);
#pragma unroll
        for (int i = 0; i < 4; i++) ts[i] = PACK(e[i]);
        vbad = anybad(v[0].x, v[1].x, v[2].x, v[3].x, V_TAG(s));
        if (AV) { xm = (xs & ~0x1ffffu) + X_VM(0) + ((tA - L16 - TA) << 5) + (l16 >> 1); CONSUME(xm); }
        while ((int)(clk() - c0) < 0) {}
        TS(5);
#pragma unroll
        for (int u = 0; u < 4; u++) r[u] = ldg_b64(XP_(xs) + u * 256);
        if (!AV) BAR_ARRIVE(B_S2, 256);
      }
      SCHED_FENCE(56);
      uint32_t kk;
      float4 e = softmax2<false>(r, 0, 0, kk);
      if (AV) {
        const char* pm_ = XP_(xm + (kk & dZ));
#pragma unroll
        for (int u = 0; u < 2; u++) { const uint2 m0 = ldg_b64(pm_ + u * 2048), m1 = ldg_b64(pm_ + u * 2048 + 256); vn[u] = make_uint4(m0.x, m0.y, m1.x, m1.y); }
      }
      if (__builtin_expect(anybad(r[0].x, r[0].y, r[1].x, r[1].y, r[2].x, r[2].y, r[3].x, r[3].y, tag ^ (kk & dZ)), 0)) {
        int it = 0;
        if (s > 8) sts1(tA + 4096 + 8, min(lds1(tA + 4096 + 8) + dX, 500));
        do {
          RP(1);
          if (++it > SPIN_LIMIT) __trap();
#pragma unroll
          for (int u = 0; u < 4; u++) r[u] = ldg_b64(XP_(xs) + u * 256);
        } while (BADS(r));
        e = softmax2<false>(r, 0, 0, kk);
      }
      sts1(t0.z, pk(e.x, e.y)); sts1(t0.z + 128, pk(e.z, e.w));
#pragma unroll
      for (int i = 0; i < 4; i++) publish(XP_(xo) + X_TOK + i * 4096, ts[i]);
      TS(6);
      if (s < 63) BAR_SYNC(B_V, N_V); else BAR_SYNC(B_V, N_V - 256);
      uint32_t O[4];
      {
        uint32_t p[4], pm;
        ldsm4t(p, pr);
        asm volatile("ldmatrix.sync.aligned.m8n8.x1.trans.shared.b16 {%0},[%1];" : "=r"(pm) : "r"(pr + 512) : "memory");
        if (!AV) { vn[0] = lds4(tA + (VN - TA)); vn[1] = lds4(tA + (VN - TA) + 2048); }
        pv_mem(p, pm, v, vn, O);
        if (__builtin_expect(vbad || ((HV || AV) && anybad(vn[0].x, vn[0].z, vn[1].x, vn[1].z, tag)), 0)) {
          int it = 0;
          const uint32_t xv = LO(xc) + (lds1(sb + PACE + 24) >> 2) * 262144 + ((tA - L16 - TA) >> 9) * XC;
          do {
            RP(2);
            if (++it > SPIN_LIMIT) __trap();
#pragma unroll
            for (int u = 0; u < 4; u++) v[u] = ldg_b128(XP_((xv + l16) ^ V_RING(s)) + X_VX(u));
          } while (anybad(v[0].x, v[1].x, v[2].x, v[3].x, V_TAG(s)) || ((HV || AV) && anybad(vn[0].x, vn[0].z, vn[1].x, vn[1].z, tag)));
          pv_mem(p, pm, v, vn, O);
        }
      }
      stsm4(tA + (OB - TA), O[0], O[1], O[2], O[3]);
      if (s < 63) BAR_ARRIVE(B_O, N_O);
      TS(2);
      c0 = clk() + dG;
      SCHED_FENCE(60);
      if (tA == sb + TA) mbar_expect(sb + BARS, 2048);
      const uint32_t vs[4] = {addbf(vn[0].x, vn[0].z), addbf(vn[0].y, vn[0].w), addbf(vn[1].x, vn[1].z), addbf(vn[1].y, vn[1].w)};
      {
        const char* xt = XP_(lds1(tA + 12) ^ ring);
        const uint2 t1 = lds2u(tA + 2048);
        const uint32_t pw = lds1(tA + 8);
        uint2 rt[4];
        CONSUME(LO(xt) ^ t1.x ^ pw);
        while ((int)(clk() - c0) < 0) {}
        int it = 0;
        do {
          if (++it > SPIN_LIMIT) __trap();
#pragma unroll
          for (int u = 0; u < 4; u++) rt[u] = ldg_b64(xt + u * 256);
        } while (BADS(rt));
        uint32_t kt;
        const float4 et = softmax2<true>(rt, t1.x, t1.y, kt);
        sts1(pw + 1024, pk(et.x, et.y)); sts1(pw + 1024 + 128, pk(et.z, et.w));
      }
      s = PIN(s);
      BAR_SYNC(B_SC, 128);
      {
        uint32_t Ot[4], p[4], pm;
        const uint2 t2 = lds2u(tA + 2048 + 8);
        ldsm4t(p, pr + 1024);
        asm volatile("ldmatrix.sync.aligned.m8n8.x1.trans.shared.b16 {%0},[%1];" : "=r"(pm) : "r"(pr + 1024 + 512) : "memory");
        char* od = (char*)g_O + ((s >> 2) * 1048576 + (s & 3) * 4096) + t2.x;
        CONSUME(LO(od) ^ HI(od) ^ pm ^ p[3]);
        TS(9);
        if (s < 62) BAR_SYNC(B_P, N_P);
        pv_tok(p, pm, v, vs, Ot);
        asm volatile("stmatrix.sync.aligned.m8n8.x4.trans.shared.b16 [%0],{%1,%2,%3,%4};" ::"r"(t2.y), "r"(Ot[0]), "r"(Ot[1]), "r"(Ot[2]), "r"(Ot[3]) : "memory");
        __syncwarp();
        *(uint4*)od = lds4(tA + (OT - TA));
      }
    }
    FENCE_ASYNC();
    BAR_SYNC(B_SC, 128);
    if (tA == sb + TA) red_rlx(&g_fin);
  }
  __syncwarp();
  CLUSTER_SYNC();
  PH(5); RS(2);
}
#undef wg
#undef iw
#undef h
#undef j
#undef a
#undef bb
#undef oi
#undef owner
#undef ownv
#undef vfin
#undef pr
#undef PIN
#undef XP_
#undef tw
#undef is7
#undef REFRESH
#undef lane
#undef l16
#undef lrow
#undef lar
#undef lpub

namespace ffn {
constexpr uint32_t BR = 98304;
constexpr uint32_t STG = 196608;
constexpr uint32_t PRM = 229376;
constexpr uint32_t BARS = PRM + 2816;
constexpr uint32_t SMEM = BARS + 18 * 8;
}
#define Y_TILE(rb, kt) (((ALIAS & 1) ? g_h : g_h2) + ((rb) * 16 + (kt)) * 1024)
#define U_TILE(rb, kt) ((ALIAS & 2) ? g_O + ((rb) * 64 + (kt)) * 1024 : g_U + ((rb) * 56 + (kt)) * 1024)
struct FfnMaps { CUtensorMap wo, w1a, w1b, w2, x, out; };

template <int N>
__device__ __forceinline__ void wg_ss(float* d, uint64_t a, uint64_t b, int sd) {
  if (N == 128) wgmma_ss_n128(d, a, b, sd);
  if (N == 192) wgmma_ss_n192(d, a, b, sd);
}
template <int N>
__device__ __forceinline__ void acc_fence(float* d) {
#pragma unroll
  for (int i = 0; i < N; i++) asm volatile("" : "+f"(d[i])::"memory");
}
#define UNPK8(d, v) do { (d)[0] = blo(v.x); (d)[1] = bhi(v.x); (d)[2] = blo(v.y); (d)[3] = bhi(v.y); (d)[4] = blo(v.z); (d)[5] = bhi(v.z); (d)[6] = blo(v.w); (d)[7] = bhi(v.w); } while (0)
struct FfnPipe {
  uint32_t full, emp, ph, aoff;
  int st, sB, prev;
  bool leader;
  template <int N>
  __device__ __forceinline__ void issue(float* acc, bool first, uint32_t a = 0) {
    mbar_wait(full + st * 8, ph);
    const uint64_t da = mkdesc((a ? a : 1024 + st * 16384) + aoff, 16, 1024), db = mkdesc(1024 + ffn::BR + sB * (N * 128), 8192, 1024);
    WG_FENCE();
#pragma unroll
    for (int j = 0; j < ((FDB & 1) ? 1 : 4); j++) wg_ss<N>(acc, da + j * 2, db + j * 128, j || !first);
    WG_COMMIT();
    if (++sB == 768 / N) sB = 0;
  }
  __device__ __forceinline__ void release() { if (leader) mbar_arrive(emp + prev * 8); }
  __device__ __forceinline__ void next() { prev = st; if (++st == 6) { st = 0; ph ^= 1; } }
  __device__ __forceinline__ void retire() { WG_WAIT(1); release(); next(); }
};
__device__ __forceinline__ float gelu_h(float hx) {
  float u = hx * fmaf(hx * hx, 8.f * 0.0356774081f, 2.f * 0.7978845608f), t;
  if (FDB & 4) return hx;
  if (FDB & 2) t = u; else
  asm("tanh.approx.f32 %0,%1;" : "=f"(t) : "f"(u));
  return fmaf(hx, t, hx);
}
struct FfnEpi {
  uint32_t st2, cc, flip, staged, l0;
  uint2 c;
  float n0, n1, s0, s1;
  __device__ __forceinline__ void flush(uint32_t r) {
    __syncwarp();
    asm volatile("{.reg .pred p; setp.ne.u32 p,%1,0; @p mbarrier.arrive.shared.b64 _,[%0];}" ::"r"(staged + (flip >> 11)), "r"(l0 & r) : "memory");
    flip ^= r << 14;
  }
  __device__ __forceinline__ void half(const float* d, int J, int r) {
#define PRE(i, n, c1, c2) gelu_h(fmaf(r ? d[4 + i] : d[i], i < 2 ? s0 : s1, fmaf(n, c1, c2)))
    asm volatile("stmatrix.sync.aligned.m8n8.x2.shared.b16 [%0],{%1,%2};" ::"r"((st2 ^ ((J & 3) * 32 + r * 16)) + flip),
                 "r"(pk(PRE(0, n0, blo(c.x), blo(c.y)), PRE(1, n0, bhi(c.x), bhi(c.y)))), "r"(pk(PRE(2, n1, blo(c.x), blo(c.y)), PRE(3, n1, bhi(c.x), bhi(c.y)))) : "memory");
#undef PRE
    if ((J & 3) == 3) flush(r);
    cc += r ? 56 : 8;
    c = lds2u(cc);
  }
};

__global__ void __launch_bounds__(384, 1)
k_ffn(const __grid_constant__ FfnMaps mp, const bf16* __restrict__ b2) {
  using namespace ffn;
  extern __shared__ __align__(1024) char smem[];
  const uint32_t sb = (uint32_t)__cvta_generic_to_shared(smem);
  if (sb != 1024) __trap();
  const int tid = threadIdx.x, lane = tid & 31, wg = __shfl_sync(~0u, tid >> 7, 0);
  const uint32_t full = sb + BARS, emp = full + 48, xbar = full + 96, staged = full + 104, tile = full + 136;
  uint32_t fin = 0;
  if (tid >= 288 && tid < 320) fin = ld_acq(&g_fin);
  if (tid < 32) {
    unsigned sm, v = 0;
    asm("mov.u32 %0,%%smid;" : "=r"(sm));
    if (tid == 0) {
      v = atomicExch(&g_slot[sm & 255], 0);
      for (int i = 0; i < 6; i++) { mbar_init(full + i * 8, 1); mbar_init(emp + i * 8, 2); }
      mbar_init(xbar, 2);
      for (int i = 0; i < 2; i++) { mbar_init(staged + i * 8, 8); mbar_init(staged + 16 + i * 8, 1); }
      FENCE_ASYNC_SMEM();
    }
    v = __shfl_sync(~0u, v, 0);
    if (!v) {
      wait_cnt(&g_fin, 128);
      for (int it = 0; !v; it++) {
        const uint4 a = ldg_rlx4(g_slot + tid * 8), b = ldg_rlx4(g_slot + tid * 8 + 4);
        const uint32_t open = __ballot_sync(~0u, a.x | a.y | a.z | a.w | b.x | b.y | b.z | b.w);
        if (!open) break;
        if (it < 16) { __nanosleep(500); continue; }
        if (tid == __ffs(open) - 1) v = atomicExch(&g_slot[tid * 8 + (a.x ? 0 : a.y ? 1 : a.z ? 2 : a.w ? 3 : b.x ? 4 : b.y ? 5 : b.z ? 6 : 7)], 0);
        v = __shfl_sync(~0u, v, __ffs(open) - 1);
      }
    }
    if (tid == 0) sts1(tile, v);
  }
  if (tid == 256) asm volatile("prefetch.tensormap [%0];" ::"l"(&mp.wo) : "memory");
  __syncthreads();
  const int bid = __shfl_sync(~0u, lds1(tile), 0) - 1;
  if (bid < 0) return;
  PH(6);
  FT(1);
  const int rb = bid >> 3, nb = bid & 7;
  unsigned* cnt = g_cnt + rb * 128;
  if (wg == 2) {
    asm volatile("setmaxnreg.dec.sync.aligned.u32 " FRP ";");
    const int pw = __shfl_sync(~0u, (tid >> 5) & 3, 0);
    uint32_t ws = emp, wp = 1, fs = full;
    auto wait_free = [&]() { mbar_wait_q(ws, wp); ws += 8; if (ws == emp + 48) { ws = emp; wp ^= 1; } };
    auto step = [&]() { fs += 8; if (fs == full + 48) fs = full; };
#define K3(c) ((0x65230 >> (c) * 4) & 7)
#define KC(k) ((k) < 2 ? nb * 2 + (k) : (k) < 9 ? ((k) - 2 + ((k) - 2 >= nb)) * 2 : ((k) - 9 + ((k) - 9 >= nb)) * 2 + 1)
    if (pw == 0) {
      uint32_t d = sb + BR + 32768;
      auto put = [&](const CUtensorMap* m, int k, int c) {
        e_expect_tma3d(d, m, k * 64, c, fs, 32768);
        step();
        d += 16384;
        if (d == sb + STG) d = sb + BR;
      };
      int n = 0;
      auto stage_free = [&]() { if (!(n & 7) && n < 56) mbar_wait_q(staged + 16 + (n & 8), (n >> 4) & 1); n++; };
      FTP(3);
#pragma unroll 1
      for (int k = 0; k < 66; k++) { wait_free(); if (k < 64) put(&mp.wo, k, nb * 2); }
#pragma unroll 1
      for (int k = 0; k < 16; k++) {
        const int kt = KC(k);
        wait_free();
        e_expect_tma3d(sb + BR + (k & 3) * 24576, &mp.w1b, kt * 64, nb * 7, fs, k < 2 ? 24576 : 40960);
        step();
      }
#pragma unroll 1
      for (int k = 0; k < 32; k++) { stage_free(); if (k != 5 && k != 6) wait_free(); put(&mp.w1a, k & 15, nb * 7 + 3 + (k >> 4) * 2); }
#pragma unroll 1
      for (int c = 0; c < 5; c++)
#pragma unroll 1
        for (int k = K3(c), i = 0; k < 56; k += c < 2 && (i ^= 1) ? 1 : c < 2 ? 6 : 7) { stage_free(); wait_free(); put(&mp.w2, k, nb * 2); }
    } else if (pw == 1) {
      FTP(5);
      if (fin < 128) wait_cnt(&g_fin, 128);
      FTP(6);
      uint32_t d = sb;
      auto put = [&](const uint4* A, bool ld) {
        wait_free();
        if (ld) e_bulk_ld(d, A, 16384, fs);
        step();
        d += 16384;
        if (d == sb + BR) d = sb;
      };
      const uint4* A = g_O + rb * 65536;
#pragma unroll 1
      for (int k = 0; k < 66; k++) put(A + k * 1024, k < 64);
      A = Y_TILE(rb, 0);
      uint32_t ready = 0;
#pragma unroll 1
      for (int k = 2; k < 48; k++) {
        const int kt = k < 16 ? KC(k) : k & 15;
        for (int it = 0; !(ready >> ((kt >> 1) + (kt & 1) * 8) & 1); it++) {
          ready = __ballot_sync(~0u, ldg_rlx1(cnt + (lane & 7)) & ((lane & 8) ? 1 : 0x10000));
          if (it > SPIN_LIMIT) __trap();
        }
        if (k == 2) FTP(75);
        put(A + kt * 1024, true);
      }
      A = U_TILE(rb, 0);
#pragma unroll 1
      for (int c = 0; c < 5; c++) {
        for (int it = 0; ldg_rlx1(cnt + 32 + c) < 8; it++) if (it > SPIN_LIMIT) __trap();
#pragma unroll 1
        for (int k = K3(c), i = 0; k < 56; k += c < 2 && (i ^= 1) ? 1 : c < 2 ? 6 : 7) put(A + k * 1024, true);
      }
    } else if (pw == 2) {
      for (int i = 0; i < XDL; i++) {
        mbar_wait_q(emp, i & 1);
        if (XPF && i == 1 && lane < 2) tma2d_pf(&mp.x, nb * 128 + lane * 64, rb * 128);
      }
      if (lane == 0) {
        mbar_expect(xbar, 32768);
        tma2d(sb + STG, &mp.x, nb * 128, rb * 128, xbar);
        tma2d(sb + STG + 16384, &mp.x, nb * 128 + 64, rb * 128, xbar);
      }
      asm volatile("griddepcontrol.wait;" ::: "memory");
      if (lane < 16) g_modp[bid * 16 + lane] = make_uint4(0, 0, 0, 0);
      if (lane >= 16 && bid == 0) { g_hcnt = 0; g_mcnt = 0; g_hf[lane & 3] = 0; }
      if (lane == 0) {
#pragma unroll 1
        for (int g = 1; g < 9; g++) {
          if (g == 1) mbar_wait(staged + 8, 0); else { mbar_wait_q(staged + (g & 1) * 8, (g >> 1) & 1); FENCE_ASYNC_SMEM(); }
          bulk_st(g == 1 ? Y_TILE(rb, nb * 2 + 1) : U_TILE(rb, nb * 7 + ((0x652431000ull >> g * 4) & 7)), sb + STG + (g & 1) * 16384, 16384);
          BULK_COMMIT();
          if (g != 2 && g != 4) { BULK_WAIT(0); red_rlx(g == 1 ? cnt + nb : cnt + 32 + (g < 6 ? g >> 2 : g - 4)); }
          BULK_WAIT_READ(0);
          mbar_arrive(staged + 16 + (g & 1) * 8);
        }
      }
    } else {
      const uint32_t prm = sb + PRM, pp = prm + (lane >> 3) * 64 + (lane & 1) * 32 + (lane & 6) * 2;
      const uint2 v2 = ((const uint2*)(b2 + nb * 128))[lane];
      sts1(pp + 768, v2.x); sts1(pp + 784, v2.y);
      asm volatile("griddepcontrol.wait;" ::: "memory");
      const float4* md = (const float4*)(g_mod + nb * 128) + lane;
      { const float4 ga = md[512]; sts1(pp, pk(ga.x, ga.y)); sts1(pp + 16, pk(ga.z, ga.w)); }
      { const float4 cb = md[1024]; sts1(pp + 256, pk(1.f + cb.x, 1.f + cb.y)); sts1(pp + 272, pk(1.f + cb.z, 1.f + cb.w)); }
      { const float4 gb = md[1280]; sts1(pp + 512, pk(gb.x, gb.y)); sts1(pp + 528, pk(gb.z, gb.w)); }
#pragma unroll 1
      for (int i = lane; i < 112; i += 32) { const uint4 c = g_cc[nb * 112 + i]; sts4(prm + 1024 + i * 16, c.x, c.y, c.z, c.w); }
      __syncwarp();
      if (lane == 0) {
        mbar_arrive(xbar);
        mbar_wait(staged, 0);
        bulk_st(Y_TILE(rb, nb * 2), sb + STG, 16384);
        BULK_COMMIT(); BULK_WAIT(0);
        asm volatile("red.relaxed.gpu.global.add.u32 [%0],0x10000;" ::"l"(cnt + nb) : "memory");
        mbar_arrive(staged + 16);
      }
      __syncwarp();
      mbar_wait_q(staged + 24, 0);
      mbar_wait_q(emp + 40, 0);
#pragma unroll 1
      for (int i = 0; i < 4; i++) {
        const uint4* sp = g_stat + (rb * 128 + i * 32 + lane) * 4;
        uint4 v[4];
        for (int it = 0;; it++) {
          uint32_t m = 0;
#pragma unroll
          for (int u = 0; u < 4; u++) { v[u] = ldg_rlx4(sp + u); m = max(max(m, max(v[u].x, v[u].y)), max(v[u].z, v[u].w)); }
          if (!__any_sync(~0u, m == ~0u)) break;
          if (it > SPIN_LIMIT) __trap();
        }
        float m = 0, q = 0;
#pragma unroll
        for (int u = 0; u < 4; u++) m += F_(v[u].x) + F_(v[u].z);
        m *= 0.125f;
#pragma unroll
        for (int u = 0; u < 4; u++) { const float a = F_(v[u].x) - m, b = F_(v[u].z) - m; q += F_(v[u].y) + F_(v[u].w) + 128.f * (a * a + b * b); }
        const float r = 0.5f * rsqrtf(q * (1.f / 1024) + 1e-5f);
        sts2(sb + STG + 16384 + (i * 32 + lane) * 8, U_(r), U_(-m * r));
      }
      __syncwarp();
      if (lane < 2) mbar_arrive(xbar);
    }
  } else {
    asm volatile("setmaxnreg.inc.sync.aligned.u32 " FRC ";");
    const int w = (tid >> 5) & 3, q = lane & 3;
    const uint32_t prm = sb + PRM + q * 16;
    const int row0 = wg * 64 + w * 16;
    FfnPipe p;
    p.full = full; p.emp = emp; p.ph = 0; p.aoff = wg * 8192; p.st = 0; p.sB = 2; p.prev = 0; p.leader = (tid & 127) == 0;
    FfnEpi e;
    const uint32_t stg = sb + STG + row0 * 128;
    e.st2 = stg + (lane & 15) * 128 + ((lane & 7) << 4);
    e.cc = sb + PRM + 1024 + q * 16; e.flip = 0; e.staged = staged; e.l0 = lane == 0;
    const uint32_t stw = e.st2 ^ (lane & 16);
    uint32_t x1[32];
    uint4* sp = g_stat + (rb * 128 + row0 + (lane >> 2)) * 4;
    float old[96], r0_, r1_;
    {
      float acc[64];
      p.issue<128>(acc, true); FT(8); p.next();
#pragma unroll 1
      for (int k = 1; k < 64; k++) { p.issue<128>(acc, false); FT(8 + k); p.retire(); }
      float xf[64], gf[32];
      uint32_t cb[16];
      mbar_wait(xbar, 0);
#pragma unroll
      for (int j = 0; j < 8; j++) {
        uint32_t xv[4];
        ldsm4(xv, (stw ^ ((j & 3) * 32)) + (j >> 2) * 16384);
#pragma unroll
        for (int i = 0; i < 4; i++) { xf[j * 8 + i * 2] = blo(xv[i]); xf[j * 8 + i * 2 + 1] = bhi(xv[i]); }
      }
#pragma unroll
      for (int i = 0; i < 4; i++) {
        const uint4 g = lds4(prm + i * 64), c = lds4(prm + 256 + i * 64);
        UNPK8(gf + i * 8, g);
        cb[i * 4] = c.x; cb[i * 4 + 1] = c.y; cb[i * 4 + 2] = c.z; cb[i * 4 + 3] = c.w;
      }
      acc_fence<64>(xf); acc_fence<32>(gf);
      WG_WAIT(0);
      p.release();
      acc_fence<64>(acc);
      PH(7); FT(72);
#pragma unroll
      for (int j = 0; j < 8; j++) {
        uint32_t* o = x1 + j * 4;
#pragma unroll
        for (int i = 0; i < 4; i++)
          o[i] = pk(fmaf(acc[j * 8 + i * 2], gf[j * 4 + (i & 2)], xf[j * 8 + i * 2]), fmaf(acc[j * 8 + i * 2 + 1], gf[j * 4 + (i & 2) + 1], xf[j * 8 + i * 2 + 1]));
        stsm4((stw ^ ((j & 3) * 32)) + (j >> 2) * 16384, mulbf(o[0], cb[j * 2]), mulbf(o[1], cb[j * 2]), mulbf(o[2], cb[j * 2 + 1]), mulbf(o[3], cb[j * 2 + 1]));
        if ((j & 3) == 3) { FENCE_ASYNC_SMEM(); e.flush(1); }
      }
      if (wg) BAR_SYNC(2, 128); else BAR_SYNC(3, 128);
    }
    PH(8); FT(73);
    float acc[64];
    {
      float* accC = old;
      p.sB = 0;
      p.issue<192>(accC, true, 1024 + STG); FT(80); p.next();
      p.issue<192>(accC, false, 1024 + STG + 16384); FT(81);
      FT(78);
      float s0 = 0, s1 = 0;
#define X1_FENCE _Pragma("unroll") for (int j = 0; j < 32; j++) asm volatile("" : "+r"(x1[j]));
      X1_FENCE
#pragma unroll
      for (int j = 0; j < 16; j++) { s0 += blo(x1[j * 2]) + bhi(x1[j * 2]); s1 += blo(x1[j * 2 + 1]) + bhi(x1[j * 2 + 1]); }
      s0 += __shfl_xor_sync(~0u, s0, 1); s1 += __shfl_xor_sync(~0u, s1, 1);
      s0 += __shfl_xor_sync(~0u, s0, 2); s1 += __shfl_xor_sync(~0u, s1, 2);
      s0 *= 1.f / 128; s1 *= 1.f / 128;
      float q0 = 0, q1 = 0;
      X1_FENCE
#pragma unroll
      for (int j = 0; j < 16; j++) {
        const float a = blo(x1[j * 2]) - s0, b = bhi(x1[j * 2]) - s0, c = blo(x1[j * 2 + 1]) - s1, d = bhi(x1[j * 2 + 1]) - s1;
        q0 += a * a + b * b; q1 += c * c + d * d;
      }
      q0 += __shfl_xor_sync(~0u, q0, 1); q1 += __shfl_xor_sync(~0u, q1, 1);
      q0 += __shfl_xor_sync(~0u, q0, 2); q1 += __shfl_xor_sync(~0u, q1, 2);
      if (q < 2) {
        uint32_t m = __float_as_uint(q ? s1 : s0), v = __float_as_uint(q ? q1 : q0);
        if (m == ~0u) m = 0x7fffffffu;
        if (v == ~0u) v = 0x7fffffffu;
        stg_rlx2((uint2*)(sp + q * 32) + nb, m, v);
      }
      X1_FENCE
      p.retire();
#pragma unroll 1
      for (int k = 2; k < 15; k++) { p.issue<192>(accC, false); FT(80 + k); p.retire(); }
      p.issue<192>(accC, false); FT(95);
      mbar_wait(xbar, 1);
      const float2 u0 = lds2f(sb + STG + 16384 + (row0 + (lane >> 2)) * 8), u1 = lds2f(sb + STG + 16384 + (row0 + (lane >> 2)) * 8 + 64);
      r0_ = u0.x; e.n0 = u0.y; r1_ = u1.x; e.n1 = u1.y;
      e.c = lds2u(e.cc);
      p.retire();
      e.s0 = r0_; e.s1 = r1_;
    }
    PH(9);
    {
      auto pair = [&](int J, bool first, int fo) {
#pragma unroll 1
        for (int r = 0; r < 2; r++) { p.issue<128>(acc, first && !r); FT(fo + r); p.retire(); acc_fence<8>(old + J * 8); e.half(old + J * 8, J, r); }
      };
#pragma unroll 1
      for (int i = 0; i < 3; i++) {
        if (i == 2) {
          e.s0 = r0_; e.s1 = r1_;
#pragma unroll
          for (int J = 8; J < 12; J++) pair(J, J == 8, 128 + (J - 8) * 2);
          e.cc += 512; e.c = lds2u(e.cc);
          e.s0 = e.s1 = 1.f;
        }
#pragma unroll
        for (int J = 0; J < 8; J++) pair(J, J == 0 && i < 2, 96 + i * 16 + (i >> 1) * 8 + J * 2);
        if (i == 2) break;
        e.cc += i ? -768 : 256; e.c = lds2u(e.cc);
        WG_WAIT(0);
        acc_fence<64>(acc);
#pragma unroll
        for (int k = 0; k < 64; k++) old[k] = acc[k] * ((k & 2) ? r1_ : r0_);
        acc_fence<64>(old);
        e.s0 = e.s1 = 1.f;
        PH(10 + i);
      }
#pragma unroll 1
      for (int k = 24; k < 56; k++) { p.issue<128>(acc, false); FT(128 + k); p.retire(); }
      float xf[64], gf[32];
#pragma unroll
      for (int i = 0; i < 4; i++) {
        const uint4 g = lds4(prm + 512 + i * 64), h = lds4(prm + 768 + i * 64);
        float hf[8];
        UNPK8(gf + i * 8, g); UNPK8(hf, h);
#pragma unroll
        for (int u = 0; u < 8; u++) {
          const int c = (u >> 2) * 4 + (u & 2);
          xf[i * 16 + u * 2] = fmaf(gf[i * 8 + c], hf[c], blo(x1[i * 8 + u])); xf[i * 16 + u * 2 + 1] = fmaf(gf[i * 8 + c + 1], hf[c + 1], bhi(x1[i * 8 + u]));
        }
      }
      acc_fence<64>(xf); acc_fence<32>(gf);
      mbar_wait(staged + 24, 1);
      mbar_wait(staged + 16, 0);
      WG_WAIT(0);
      acc_fence<64>(acc);
      PH(13); FT(184);
#pragma unroll
      for (int j = 0; j < 8; j++) {
        uint32_t o[4];
#pragma unroll
        for (int i = 0; i < 4; i++)
          o[i] = pk(fmaf(acc[j * 8 + i * 2], gf[j * 4 + (i & 2)], xf[j * 8 + i * 2]), fmaf(acc[j * 8 + i * 2 + 1], gf[j * 4 + (i & 2) + 1], xf[j * 8 + i * 2 + 1]));
        stsm4((stw ^ ((j & 3) * 32)) + (j >> 2) * 16384, o[0], o[1], o[2], o[3]);
        if ((j & 3) == 3) {
          FENCE_ASYNC_SMEM();
          __syncwarp();
          if (lane == 0) { tma2d_st(&mp.out, nb * 128 + (j >> 2) * 64, rb * 128 + row0, stg + (j >> 2) * 16384); BULK_COMMIT(); }
        }
      }
      if (lane == 0) BULK_WAIT_READ(0);
      __syncwarp();
    }
  }
  PH(14); RS(3); FT(185);
}

typedef CUresult (*EncFn)(CUtensorMap*, CUtensorMapDataType, cuuint32_t, void*, const cuuint64_t*, const cuuint64_t*, const cuuint32_t*,
                          const cuuint32_t*, CUtensorMapInterleave, CUtensorMapSwizzle, CUtensorMapL2promotion, CUtensorMapFloatOOBfill);
static void map2d(EncFn enc, CUtensorMap* m, const void* p, int rows, int cols, int boxRows) {
  cuuint64_t d[2] = {(cuuint64_t)cols, (cuuint64_t)rows}, s[1] = {(cuuint64_t)cols * 2};
  cuuint32_t b[2] = {64, (cuuint32_t)boxRows}, e[2] = {1, 1};
  enc(m, CU_TENSOR_MAP_DATA_TYPE_BFLOAT16, 2, (void*)p, d, s, b, e, CU_TENSOR_MAP_INTERLEAVE_NONE, CU_TENSOR_MAP_SWIZZLE_128B,
      CU_TENSOR_MAP_L2_PROMOTION_L2_128B, CU_TENSOR_MAP_FLOAT_OOB_FILL_NONE);
}
static void map3d(EncFn enc, CUtensorMap* m, const void* p, int rows, int cols, int nch) {
  cuuint64_t d[3] = {64, (cuuint64_t)rows, (cuuint64_t)(cols / 64)}, s[2] = {(cuuint64_t)cols * 2, 128};
  cuuint32_t b[3] = {64, 64, (cuuint32_t)nch}, e[3] = {1, 1, 1};
  enc(m, CU_TENSOR_MAP_DATA_TYPE_BFLOAT16, 3, (void*)p, d, s, b, e, CU_TENSOR_MAP_INTERLEAVE_NONE, CU_TENSOR_MAP_SWIZZLE_128B,
      CU_TENSOR_MAP_L2_PROMOTION_L2_128B, CU_TENSOR_MAP_FLOAT_OOB_FILL_NONE);
}

extern "C" void kernel_launch(void* const* d_in, const int* in_sizes, int n_in, void* d_out, int out_size) {
  const bf16* x = (const bf16*)d_in[0];
  const bf16* mem0 = (const bf16*)d_in[1];
  void* fn = nullptr;
  cudaDriverEntryPointQueryResult qr;
  cudaGetDriverEntryPoint("cuTensorMapEncodeTiled", &fn, cudaEnableDefault, &qr);
  EncFn enc = (EncFn)fn;
  FfnMaps fm = {};
  map3d(enc, &fm.wo, d_in[5], 4096, 1024, 2);
  map3d(enc, &fm.w1a, d_in[8], 1024, 3584, 2);
  map3d(enc, &fm.w1b, d_in[8], 1024, 3584, 3);
  map3d(enc, &fm.w2, d_in[10], 3584, 1024, 2);
  map2d(enc, &fm.x, x, 2048, 1024, 128);
  map2d(enc, &fm.out, d_out, 2048, 1024, 16);
  RecMaps rm = {};
  map2d(enc, &rm.wq, d_in[2], 1024, 4096, 128);
  map2d(enc, &rm.wk, d_in[3], 1024, 4096, 128);
  map2d(enc, &rm.wv, d_in[4], 1024, 4096, 16);
  map2d(enc, &rm.wo, d_in[5], 4096, 1024, 128);
  char* xc = nullptr;
  cudaGetSymbolAddress((void**)&xc, g_xc);
  xc += (0 - (uintptr_t)xc) & 0x1FFFFF;
  {
    cuuint64_t d[3] = {512, ARV ? 8 : 128, ARV ? 128 : 6}, sd[2] = {1024, ARV ? 8192 : 131072};
    cuuint32_t bi[3] = {64, 8, 5}, e[3] = {1, 1, 1};
    enc(&rm.ari, CU_TENSOR_MAP_DATA_TYPE_BFLOAT16, 3, xc + AR_OFF, d, sd, bi, e, CU_TENSOR_MAP_INTERLEAVE_NONE, CU_TENSOR_MAP_SWIZZLE_NONE,
        CU_TENSOR_MAP_L2_PROMOTION_NONE, CU_TENSOR_MAP_FLOAT_OOB_FILL_NONE);
  }
  cudaFuncSetAttribute(k_ffn, cudaFuncAttributeMaxDynamicSharedMemorySize, ffn::SMEM);
  cudaFuncSetAttribute(k_rec, cudaFuncAttributeMaxDynamicSharedMemorySize, rec::SMEM);
  cudaStream_t st = cudaStreamPerThread;
  int dF = 450, dA = 2700, dS = 300, dM = 120, dG = 350, dP = 24, dX = 48, dD = 350, dZ = 0, dZ2 = 1, dV = 370, dX2 = 0;
  k_rec<<<132, 512, rec::SMEM, st>>>(rm, mem0, x, (const bf16*)d_in[12], (const bf16*)d_in[13], (const char*)d_in[8], (const bf16*)d_in[9],
                                     (const char*)d_in[5], xc, dF, dA, dS, dM, dG, dP, dX, dD, dZ, dZ2, dV, dX2);
  cudaLaunchConfig_t cfg = {};
  cfg.gridDim = dim3(132); cfg.blockDim = dim3(384); cfg.dynamicSmemBytes = ffn::SMEM; cfg.stream = st;
  cudaLaunchAttribute at[1];
  at[0].id = cudaLaunchAttributeProgrammaticStreamSerialization;
  at[0].val.programmaticStreamSerializationAllowed = 1;
  cfg.attrs = at; cfg.numAttrs = 1;
  cudaLaunchKernelEx(&cfg, k_ffn, fm, (const bf16*)d_in[11]);
}
```

```cpp
#include <cuda_runtime.h>
#include <cuda.h>
#include <cuda_bf16.h>
#include <stdint.h>

typedef __nv_bfloat16 bf16;

__device__ __align__(16) float g_mod[6144];
__device__ __align__(1024) uint4 g_modp[4 * 512];
__device__ unsigned g_hcnt;
__device__ unsigned g_hf[4];
__device__ __align__(1024) uint4 g_h[2048 * 1024 / 8];
__device__ __align__(1024) uint4 g_O[2048 * 4096 / 8];
__device__ __align__(1024) uint4 g_h2[2048 * 1024 / 8];
__device__ __align__(1024) uint4 g_U[2048 * 3584 / 8];
__device__ __align__(1024) uint4 g_stat[2048 * 4];
__device__ __align__(1024) unsigned g_cnt[16 * 4 * 32];
__device__ unsigned g_mcnt;
__device__ unsigned g_slot[256];
__device__ unsigned g_fin;
__device__ __align__(16) uint4 g_cc[224 * 4];
__device__ __align__(1024) uint4 g_xc[44 * 16384];
__device__ __align__(1024) unsigned g_tm[4 * 256];
#define FT(i)
#define FTP(i)
#define PT(i)
#define PH(i)
#define RS(i)
#define RP(i)
#define RPN(i, s)
#define TSV(i, v)
#define TS(i)

#define WIN 2
#define FRC "232"
#define FRP "40"
#define YR 1
#define XPK 0
#define NFA 1
#define PINM 1
#define FMAP (((g >> 2) * 4 + m) * 8 + ((g & 3) ^ ((g & 4) ? 3 : 0)) * 2 + (blockIdx.x & 1))
#define FDB 0
#define ALIAS 3
#define EF 0
#define XPF 0
#define PFT 150000
#define PFS 104
#define PF0 13000
#define PFD 128
#define ARV 0
#define HV 0
#define XE 0
#define NF 3
#define NB0 4
#define PV0 4
#define T1L 1
#define NW0 5
#define FQM 0
#define FQ(k) do { if ((FQM >> ((k) - 48)) & 1) SCHED_FENCE(k); } while (0)
#define SWP 1
#define VCO 0
#define AV 0
#define PKE 0
#define VRF 3
#define RSO 2
#define WPF 1
#define VPC 1
#define OBL 1
#define WC0 10
#define WPE 3
#define LS 0
#define ALN 0x80
#define XDL 6
#define QW 0
#define PDS 61
#define P_NVR 5
#define P_NVP 2
#define P_NWP 9
#define P_NW1 7
#define RF_ 208
#define PSV 1
#define RA_ (488 - 2 * RF_)
#define XI 5
#define XL 1
#define WCH 2
#define HX 0
#define VB 1
#define TP 0
#define CKI 0
#define NOP_ 2
#define KVO 0
#define NDL 3
#define AM 0
#define XM 3
#define XP 0
#define SPIN_LIMIT (1 << 20)
__device__ __forceinline__ uint64_t mkdesc(uint32_t addr, uint32_t lbo, uint32_t sbo) {
  return (uint64_t)((addr & 0x3FFFF) >> 4) | ((uint64_t)(lbo >> 4) << 16) | ((uint64_t)(sbo >> 4) << 32) | (1ull << 62);
}
__device__ __forceinline__ void mbar_init(uint32_t a, int c) { asm volatile("mbarrier.init.shared.b64 [%0],%1;" ::"r"(a), "r"(c) : "memory"); }
__device__ __forceinline__ void mbar_wait(uint32_t a, uint32_t par) {
  asm volatile(
      "{.reg .pred p; .reg .u32 n;\n"
      "mov.u32 n, 0;\n"
      "W: mbarrier.try_wait.parity.shared.b64 p,[%0],%1;\n"
      "@p bra D;\n"
      "add.u32 n, n, 1;\n"
      "setp.lt.u32 p, n, %2;\n"
      "@p bra W;\n"
      "trap;\n"
      "D:}" ::"r"(a), "r"(par), "n"(SPIN_LIMIT) : "memory");
}
__device__ __forceinline__ void mbar_wait_q(uint32_t a, uint32_t par) {
  asm volatile(
      "{.reg .pred p; .reg .u32 n;\n"
      "mov.u32 n, 0;\n"
      "W: mbarrier.try_wait.parity.shared.b64 p,[%0],%1,4000;\n"
      "@p bra D;\n"
      "add.u32 n, n, 1;\n"
      "setp.lt.u32 p, n, %2;\n"
      "@p bra W;\n"
      "trap;\n"
      "D:}" ::"r"(a), "r"(par), "n"(SPIN_LIMIT / 16) : "memory");
}
__device__ __forceinline__ void mbar_expect(uint32_t a, uint32_t b) { asm volatile("mbarrier.arrive.expect_tx.shared.b64 _,[%0],%1;" ::"r"(a), "r"(b) : "memory"); }
__device__ __forceinline__ void mbar_arrive(uint32_t a) { asm volatile("mbarrier.arrive.shared.b64 _,[%0];" ::"r"(a) : "memory"); }
__device__ __forceinline__ uint32_t mapa(uint32_t a, uint32_t cta) { uint32_t r; asm("mapa.shared::cluster.u32 %0,%1,%2;" : "=r"(r) : "r"(a), "r"(cta)); return r; }
__device__ __forceinline__ void mbar_arrive_cl(uint32_t a) { asm volatile("mbarrier.arrive.shared::cluster.b64 _,[%0];" ::"r"(a) : "memory"); }
__device__ __forceinline__ void tma2d(uint32_t dst, const CUtensorMap* m, int c0, int c1, uint32_t mb) {
  asm volatile("cp.async.bulk.tensor.2d.shared::cluster.global.mbarrier::complete_tx::bytes [%0],[%1,{%2,%3}],[%4];" ::"r"(dst), "l"(m), "r"(c0), "r"(c1), "r"(mb) : "memory");
}
__device__ __forceinline__ void tma2d_pf(const CUtensorMap* m, int c0, int c1) {
  asm volatile("cp.async.bulk.prefetch.tensor.2d.L2.global [%0,{%1,%2}];" ::"l"(m), "r"(c0), "r"(c1) : "memory");
}
__device__ __forceinline__ void tma3d(uint32_t dst, const CUtensorMap* m, int c1, int c2, uint32_t mb) {
  asm volatile("cp.async.bulk.tensor.3d.shared::cluster.global.mbarrier::complete_tx::bytes [%0],[%1,{0,%2,%3}],[%4];" ::"r"(dst), "l"(m), "r"(c1), "r"(c2), "r"(mb) : "memory");
}
__device__ __forceinline__ void tma2d_st(const CUtensorMap* m, int c0, int c1, uint32_t src) {
  asm volatile("cp.async.bulk.tensor.2d.global.shared::cta.bulk_group [%0,{%1,%2}],[%3];" ::"l"(m), "r"(c0), "r"(c1), "r"(src) : "memory");
}
__device__ __forceinline__ void bulk_ld(uint32_t dst, const void* src, uint32_t n, uint32_t mb) {
  asm volatile("cp.async.bulk.shared::cluster.global.mbarrier::complete_tx::bytes [%0],[%1],%2,[%3];" ::"r"(dst), "l"(src), "r"(n), "r"(mb) : "memory");
}
__device__ __forceinline__ void bulk_ld_mc(uint32_t dst, const void* src, uint32_t n, uint32_t mb) {
  asm volatile("cp.async.bulk.shared::cluster.global.mbarrier::complete_tx::bytes.multicast::cluster [%0],[%1],%2,[%3],%4;" ::"r"(dst), "l"(src), "r"(n), "r"(mb), "h"((uint16_t)3) : "memory");
}
__device__ __forceinline__ void bulk_st(void* dst, uint32_t src, uint32_t n) {
  asm volatile("cp.async.bulk.global.shared::cta.bulk_group [%0],[%1],%2;" ::"l"(dst), "r"(src), "r"(n) : "memory");
}
__device__ __forceinline__ void e_expect_tma3d(uint32_t dst, const CUtensorMap* m, int c1, int c2, uint32_t mb, uint32_t bytes) {
  asm volatile("{.reg .pred p; elect.sync _|p, 0xffffffff; @p mbarrier.arrive.expect_tx.shared.b64 _,[%4],%5;\n"
               "@p cp.async.bulk.tensor.3d.shared::cluster.global.mbarrier::complete_tx::bytes [%0],[%1,{0,%2,%3}],[%4];}" ::"r"(dst), "l"(m), "r"(c1), "r"(c2), "r"(mb), "r"(bytes) : "memory");
}
__device__ __forceinline__ void e_bulk_ld(uint32_t dst, const void* src, uint32_t n, uint32_t mb) {
  asm volatile("{.reg .pred p; elect.sync _|p, 0xffffffff; @p cp.async.bulk.shared::cluster.global.mbarrier::complete_tx::bytes [%0],[%1],%2,[%3];}" ::"r"(dst), "l"(src), "r"(n), "r"(mb) : "memory");
}
__device__ __forceinline__ void e_bulk_ld_ef(uint32_t dst, const void* src, uint32_t n, uint32_t mb) {
  asm volatile("{.reg .pred p; .reg .b64 c; createpolicy.fractional.L2::evict_first.b64 c,1.0; elect.sync _|p, 0xffffffff;"
               " @p cp.async.bulk.shared::cluster.global.mbarrier::complete_tx::bytes.L2::cache_hint [%0],[%1],%2,[%3],c;}" ::"r"(dst), "l"(src), "r"(n), "r"(mb) : "memory");
}
__device__ __forceinline__ void e_bulk_ld_mc(uint32_t dst, const void* src, uint32_t n, uint32_t mb) {
  asm volatile("{.reg .pred p; elect.sync _|p, 0xffffffff; @p cp.async.bulk.shared::cluster.global.mbarrier::complete_tx::bytes.multicast::cluster [%0],[%1],%2,[%3],%4;}" ::"r"(dst), "l"(src), "r"(n), "r"(mb), "h"((uint16_t)3) : "memory");
}
#define BULK_COMMIT() asm volatile("cp.async.bulk.commit_group;" ::: "memory")
#define BULK_WAIT_READ(n) asm volatile("cp.async.bulk.wait_group.read " #n ";" ::: "memory")
#define BULK_WAIT(n) asm volatile("cp.async.bulk.wait_group " #n ";" ::: "memory")
#define FENCE_ASYNC_SMEM() asm volatile("fence.proxy.async.shared::cta;" ::: "memory")
#define FENCE_ASYNC() asm volatile("fence.proxy.async;" ::: "memory")
#define WG_FENCE() asm volatile("wgmma.fence.sync.aligned;" ::: "memory")
#define WG_COMMIT() asm volatile("wgmma.commit_group.sync.aligned;" ::: "memory")
#define WG_WAIT(n) asm volatile("wgmma.wait_group.sync.aligned " #n ";" ::: "memory")
#define BAR_SYNC(id, n) asm volatile("bar.sync %0,%1;" ::"n"(id), "n"(n) : "memory")
#define BAR_ARRIVE(id, n) asm volatile("bar.arrive %0,%1;" ::"n"(id), "n"(n) : "memory")
#define SCHED_FENCE(k) asm volatile("{.reg .pred p; setp.ne.u32 p,%0,0; @p trap;}" ::"r"(mp.zero[(k) - 46]) : "memory")
#define CLUSTER_SYNC() asm volatile("barrier.cluster.arrive.relaxed.aligned; barrier.cluster.wait.aligned;" ::: "memory")
__device__ __forceinline__ uint32_t pk(float lo, float hi) { uint32_t r; asm("cvt.rn.bf16x2.f32 %0,%1,%2;" : "=r"(r) : "f"(hi), "f"(lo)); return r; }
__device__ __forceinline__ float blo(uint32_t v) { return __uint_as_float(v << 16); }
__device__ __forceinline__ float bhi(uint32_t v) { return __uint_as_float(v & 0xffff0000u); }
__device__ __forceinline__ void ldsm4(uint32_t* r, uint32_t a) {
  asm volatile("ldmatrix.sync.aligned.m8n8.x4.shared.b16 {%0,%1,%2,%3},[%4];" : "=r"(r[0]), "=r"(r[1]), "=r"(r[2]), "=r"(r[3]) : "r"(a) : "memory");
}
__device__ __forceinline__ void ldsm4t(uint32_t* r, uint32_t a) {
  asm volatile("ldmatrix.sync.aligned.m8n8.x4.trans.shared.b16 {%0,%1,%2,%3},[%4];" : "=r"(r[0]), "=r"(r[1]), "=r"(r[2]), "=r"(r[3]) : "r"(a) : "memory");
}
__device__ __forceinline__ void stsm4(uint32_t a, uint32_t r0, uint32_t r1, uint32_t r2, uint32_t r3) {
  asm volatile("stmatrix.sync.aligned.m8n8.x4.shared.b16 [%0],{%1,%2,%3,%4};" ::"r"(a), "r"(r0), "r"(r1), "r"(r2), "r"(r3) : "memory");
}
__device__ __forceinline__ void mma16(float* d, uint32_t a0, uint32_t a1, uint32_t a2, uint32_t a3, uint32_t b0, uint32_t b1) {
  asm volatile("mma.sync.aligned.m16n8k16.row.col.f32.bf16.bf16.f32 {%0,%1,%2,%3},{%4,%5,%6,%7},{%8,%9},{%0,%1,%2,%3};"
               : "+f"(d[0]), "+f"(d[1]), "+f"(d[2]), "+f"(d[3]) : "r"(a0), "r"(a1), "r"(a2), "r"(a3), "r"(b0), "r"(b1));
}
__device__ __forceinline__ void mma8(float* d, uint32_t a0, uint32_t a1, uint32_t b0) {
  asm volatile("mma.sync.aligned.m16n8k8.row.col.f32.bf16.bf16.f32 {%0,%1,%2,%3},{%4,%5},{%6},{%0,%1,%2,%3};"
               : "+f"(d[0]), "+f"(d[1]), "+f"(d[2]), "+f"(d[3]) : "r"(a0), "r"(a1), "r"(b0));
}
__device__ __forceinline__ float4 lds4f(uint32_t a) { float4 v; asm volatile("ld.shared.v4.f32 {%0,%1,%2,%3},[%4];" : "=f"(v.x), "=f"(v.y), "=f"(v.z), "=f"(v.w) : "r"(a) : "memory"); return v; }
__device__ __forceinline__ float2 lds2f(uint32_t a) { float2 v; asm volatile("ld.shared.v2.f32 {%0,%1},[%2];" : "=f"(v.x), "=f"(v.y) : "r"(a) : "memory"); return v; }
__device__ __forceinline__ uint4 lds4(uint32_t a) { uint4 v; asm volatile("ld.shared.v4.u32 {%0,%1,%2,%3},[%4];" : "=r"(v.x), "=r"(v.y), "=r"(v.z), "=r"(v.w) : "r"(a) : "memory"); return v; }
__device__ __forceinline__ uint2 lds2u(uint32_t a) { uint2 v; asm volatile("ld.shared.v2.u32 {%0,%1},[%2];" : "=r"(v.x), "=r"(v.y) : "r"(a) : "memory"); return v; }
__device__ __forceinline__ uint32_t lds1(uint32_t a) { uint32_t v; asm volatile("ld.shared.u32 %0,[%1];" : "=r"(v) : "r"(a) : "memory"); return v; }
__device__ __forceinline__ void sts4(uint32_t a, uint32_t x, uint32_t y, uint32_t z, uint32_t w) { asm volatile("st.shared.v4.u32 [%0],{%1,%2,%3,%4};" ::"r"(a), "r"(x), "r"(y), "r"(z), "r"(w) : "memory"); }
__device__ __forceinline__ void sts2(uint32_t a, uint32_t x, uint32_t y) { asm volatile("st.shared.v2.u32 [%0],{%1,%2};" ::"r"(a), "r"(x), "r"(y) : "memory"); }
__device__ __forceinline__ void sts1(uint32_t a, uint32_t x) { asm volatile("st.shared.u32 [%0],%1;" ::"r"(a), "r"(x) : "memory"); }
__device__ __forceinline__ void sta4(uint32_t a, const uint32_t* v, uint32_t mb) {
  asm volatile("st.async.shared::cluster.mbarrier::complete_tx::bytes.v4.b32 [%0],{%1,%2,%3,%4},[%5];" ::"r"(a), "r"(v[0]), "r"(v[1]), "r"(v[2]), "r"(v[3]), "r"(mb) : "memory");
}
__device__ __forceinline__ uint4 ldg_rlx4(const void* p) { uint4 v; asm volatile("ld.relaxed.gpu.global.v4.u32 {%0,%1,%2,%3},[%4];" : "=r"(v.x), "=r"(v.y), "=r"(v.z), "=r"(v.w) : "l"(p) : "memory"); return v; }
__device__ __forceinline__ uint32_t ldg_rlx1(const void* p) { uint32_t v; asm volatile("ld.relaxed.gpu.global.u32 %0,[%1];" : "=r"(v) : "l"(p) : "memory"); return v; }
__device__ __forceinline__ uint2 ldg_rlx2(const void* p) { uint2 v; asm volatile("ld.relaxed.gpu.global.v2.u32 {%0,%1},[%2];" : "=r"(v.x), "=r"(v.y) : "l"(p) : "memory"); return v; }
__device__ __forceinline__ uint4 ldg_b128(const void* p) {
  uint4 v;
  asm volatile("{.reg .b128 t; .reg .b64 a,b; ld.relaxed.gpu.global.b128 t,[%4]; mov.b128 {a,b},t; mov.b64 {%0,%1},a; mov.b64 {%2,%3},b;}" : "=r"(v.x), "=r"(v.y), "=r"(v.z), "=r"(v.w) : "l"(p) : "memory");
  return v;
}
__device__ __forceinline__ void stg_b128(void* p, uint32_t x, uint32_t y, uint32_t z, uint32_t w) {
  asm volatile("{.reg .b128 t; .reg .b64 a,b; mov.b64 a,{%1,%2}; mov.b64 b,{%3,%4}; mov.b128 t,{a,b}; st.relaxed.gpu.global.b128 [%0],t;}" ::"l"(p), "r"(x), "r"(y), "r"(z), "r"(w) : "memory");
}
__device__ __forceinline__ void st_b128(void* p, uint32_t x, uint32_t y, uint32_t z, uint32_t w) {
  asm volatile("{.reg .b128 t; .reg .b64 a,b; mov.b64 a,{%1,%2}; mov.b64 b,{%3,%4}; mov.b128 t,{a,b}; st.relaxed.gpu.b128 [%0],t;}" ::"l"(p), "r"(x), "r"(y), "r"(z), "r"(w) : "memory");
}
__device__ __forceinline__ void stg_rlx4(void* p, uint32_t x, uint32_t y, uint32_t z, uint32_t w) { asm volatile("st.relaxed.gpu.global.v4.u32 [%0],{%1,%2,%3,%4};" ::"l"(p), "r"(x), "r"(y), "r"(z), "r"(w) : "memory"); }
__device__ __forceinline__ void stg_rlx2(void* p, uint32_t x, uint32_t y) { asm volatile("st.relaxed.gpu.global.v2.u32 [%0],{%1,%2};" ::"l"(p), "r"(x), "r"(y) : "memory"); }
__device__ __forceinline__ void red4(void* p, float a, float b, float c, float d) { asm volatile("red.relaxed.gpu.global.add.v4.f32 [%0],{%1,%2,%3,%4};" ::"l"(p), "f"(a), "f"(b), "f"(c), "f"(d) : "memory"); }
__device__ __forceinline__ unsigned ld_acq(const unsigned* p) { unsigned v; asm volatile("ld.acquire.gpu.global.u32 %0,[%1];" : "=r"(v) : "l"(p) : "memory"); return v; }
__device__ __forceinline__ void red_rel(unsigned* p) { asm volatile("red.release.gpu.global.add.u32 [%0],1;" ::"l"(p) : "memory"); }
__device__ __forceinline__ void red_rlx(unsigned* p) { asm volatile("red.relaxed.gpu.global.add.u32 [%0],1;" ::"l"(p) : "memory"); }
__device__ __forceinline__ void wait_cnt(const unsigned* p, unsigned n) { int it = 0; while (ld_acq(p) < n) { if (++it > SPIN_LIMIT) __trap(); } }
__device__ __forceinline__ uint32_t clk() { uint32_t c; asm volatile("mov.u32 %0,%%clock;" : "=r"(c)); return c; }
__device__ __forceinline__ uint32_t gtime() { uint32_t c; asm volatile("mov.u32 %0,%%globaltimer_lo;" : "=r"(c)); return c; }
__device__ __forceinline__ void wait_until(uint32_t t0, uint32_t d) { while (clk() - t0 < d) {} }
__device__ __forceinline__ float ex2(float x) { float r; asm("ex2.approx.ftz.f32 %0,%1;" : "=f"(r) : "f"(x)); return r; }
__device__ __forceinline__ float silu(float x) { return x * __frcp_rn(1.f + __expf(-x)); }
__device__ __forceinline__ float rbf(float x) { return __bfloat162float(__float2bfloat16_rn(x)); }

__device__ __forceinline__ void wgmma_ss_n128(float* d, uint64_t a, uint64_t b, int sd) {
  asm volatile("{.reg .pred p; setp.ne.b32 p, %66, 0;\n"
    "wgmma.mma_async.sync.aligned.m64n128k16.f32.bf16.bf16 {%0,%1,%2,%3,%4,%5,%6,%7,%8,%9,%10,%11,%12,%13,%14,%15,%16,%17,%18,%19,%20,%21,%22,%23,%24,%25,%26,%27,%28,%29,%30,%31,%32,%33,%34,%35,%36,%37,%38,%39,%40,%41,%42,%43,%44,%45,%46,%47,%48,%49,%50,%51,%52,%53,%54,%55,%56,%57,%58,%59,%60,%61,%62,%63}, %64, %65, p, 1, 1, 0, 1;}\n"
    : "+f"(d[0]),"+f"(d[1]),"+f"(d[2]),"+f"(d[3]),"+f"(d[4]),"+f"(d[5]),"+f"(d[6]),"+f"(d[7]),
      "+f"(d[8]),"+f"(d[9]),"+f"(d[10]),"+f"(d[11]),"+f"(d[12]),"+f"(d[13]),"+f"(d[14]),"+f"(d[15]),
      "+f"(d[16]),"+f"(d[17]),"+f"(d[18]),"+f"(d[19]),"+f"(d[20]),"+f"(d[21]),"+f"(d[22]),"+f"(d[23]),
      "+f"(d[24]),"+f"(d[25]),"+f"(d[26]),"+f"(d[27]),"+f"(d[28]),"+f"(d[29]),"+f"(d[30]),"+f"(d[31]),
      "+f"(d[32]),"+f"(d[33]),"+f"(d[34]),"+f"(d[35]),"+f"(d[36]),"+f"(d[37]),"+f"(d[38]),"+f"(d[39]),
      "+f"(d[40]),"+f"(d[41]),"+f"(d[42]),"+f"(d[43]),"+f"(d[44]),"+f"(d[45]),"+f"(d[46]),"+f"(d[47]),
      "+f"(d[48]),"+f"(d[49]),"+f"(d[50]),"+f"(d[51]),"+f"(d[52]),"+f"(d[53]),"+f"(d[54]),"+f"(d[55]),
      "+f"(d[56]),"+f"(d[57]),"+f"(d[58]),"+f"(d[59]),"+f"(d[60]),"+f"(d[61]),"+f"(d[62]),"+f"(d[63])
    : "l"(a), "l"(b), "r"(sd));
}
__device__ __forceinline__ void wgmma_ss_n192(float* d, uint64_t a, uint64_t b, int sd) {
  asm volatile("{.reg .pred p; setp.ne.b32 p, %98, 0;\n"
    "wgmma.mma_async.sync.aligned.m64n192k16.f32.bf16.bf16 {%0,%1,%2,%3,%4,%5,%6,%7,%8,%9,%10,%11,%12,%13,%14,%15,%16,%17,%18,%19,%20,%21,%22,%23,%24,%25,%26,%27,%28,%29,%30,%31,%32,%33,%34,%35,%36,%37,%38,%39,%40,%41,%42,%43,%44,%45,%46,%47,%48,%49,%50,%51,%52,%53,%54,%55,%56,%57,%58,%59,%60,%61,%62,%63,%64,%65,%66,%67,%68,%69,%70,%71,%72,%73,%74,%75,%76,%77,%78,%79,%80,%81,%82,%83,%84,%85,%86,%87,%88,%89,%90,%91,%92,%93,%94,%95}, %96, %97, p, 1, 1, 0, 1;}\n"
    : "+f"(d[0]),"+f"(d[1]),"+f"(d[2]),"+f"(d[3]),"+f"(d[4]),"+f"(d[5]),"+f"(d[6]),"+f"(d[7]),
      "+f"(d[8]),"+f"(d[9]),"+f"(d[10]),"+f"(d[11]),"+f"(d[12]),"+f"(d[13]),"+f"(d[14]),"+f"(d[15]),
      "+f"(d[16]),"+f"(d[17]),"+f"(d[18]),"+f"(d[19]),"+f"(d[20]),"+f"(d[21]),"+f"(d[22]),"+f"(d[23]),
      "+f"(d[24]),"+f"(d[25]),"+f"(d[26]),"+f"(d[27]),"+f"(d[28]),"+f"(d[29]),"+f"(d[30]),"+f"(d[31]),
      "+f"(d[32]),"+f"(d[33]),"+f"(d[34]),"+f"(d[35]),"+f"(d[36]),"+f"(d[37]),"+f"(d[38]),"+f"(d[39]),
      "+f"(d[40]),"+f"(d[41]),"+f"(d[42]),"+f"(d[43]),"+f"(d[44]),"+f"(d[45]),"+f"(d[46]),"+f"(d[47]),
      "+f"(d[48]),"+f"(d[49]),"+f"(d[50]),"+f"(d[51]),"+f"(d[52]),"+f"(d[53]),"+f"(d[54]),"+f"(d[55]),
      "+f"(d[56]),"+f"(d[57]),"+f"(d[58]),"+f"(d[59]),"+f"(d[60]),"+f"(d[61]),"+f"(d[62]),"+f"(d[63]),
      "+f"(d[64]),"+f"(d[65]),"+f"(d[66]),"+f"(d[67]),"+f"(d[68]),"+f"(d[69]),"+f"(d[70]),"+f"(d[71]),
      "+f"(d[72]),"+f"(d[73]),"+f"(d[74]),"+f"(d[75]),"+f"(d[76]),"+f"(d[77]),"+f"(d[78]),"+f"(d[79]),
      "+f"(d[80]),"+f"(d[81]),"+f"(d[82]),"+f"(d[83]),"+f"(d[84]),"+f"(d[85]),"+f"(d[86]),"+f"(d[87]),
      "+f"(d[88]),"+f"(d[89]),"+f"(d[90]),"+f"(d[91]),"+f"(d[92]),"+f"(d[93]),"+f"(d[94]),"+f"(d[95])
    : "l"(a), "l"(b), "r"(sd));
}
__device__ __forceinline__ void wgmma_ss_n256(float* d, uint64_t a, uint64_t b, int sd) {
  asm volatile("{.reg .pred p; setp.ne.b32 p, %130, 0;\n"
    "wgmma.mma_async.sync.aligned.m64n256k16.f32.bf16.bf16 {%0,%1,%2,%3,%4,%5,%6,%7,%8,%9,%10,%11,%12,%13,%14,%15,%16,%17,%18,%19,%20,%21,%22,%23,%24,%25,%26,%27,%28,%29,%30,%31,%32,%33,%34,%35,%36,%37,%38,%39,%40,%41,%42,%43,%44,%45,%46,%47,%48,%49,%50,%51,%52,%53,%54,%55,%56,%57,%58,%59,%60,%61,%62,%63,%64,%65,%66,%67,%68,%69,%70,%71,%72,%73,%74,%75,%76,%77,%78,%79,%80,%81,%82,%83,%84,%85,%86,%87,%88,%89,%90,%91,%92,%93,%94,%95,%96,%97,%98,%99,%100,%101,%102,%103,%104,%105,%106,%107,%108,%109,%110,%111,%112,%113,%114,%115,%116,%117,%118,%119,%120,%121,%122,%123,%124,%125,%126,%127}, %128, %129, p, 1, 1, 0, 1;}\n"
    : "+f"(d[0]),"+f"(d[1]),"+f"(d[2]),"+f"(d[3]),"+f"(d[4]),"+f"(d[5]),"+f"(d[6]),"+f"(d[7]),
      "+f"(d[8]),"+f"(d[9]),"+f"(d[10]),"+f"(d[11]),"+f"(d[12]),"+f"(d[13]),"+f"(d[14]),"+f"(d[15]),
      "+f"(d[16]),"+f"(d[17]),"+f"(d[18]),"+f"(d[19]),"+f"(d[20]),"+f"(d[21]),"+f"(d[22]),"+f"(d[23]),
      "+f"(d[24]),"+f"(d[25]),"+f"(d[26]),"+f"(d[27]),"+f"(d[28]),"+f"(d[29]),"+f"(d[30]),"+f"(d[31]),
      "+f"(d[32]),"+f"(d[33]),"+f"(d[34]),"+f"(d[35]),"+f"(d[36]),"+f"(d[37]),"+f"(d[38]),"+f"(d[39]),
      "+f"(d[40]),"+f"(d[41]),"+f"(d[42]),"+f"(d[43]),"+f"(d[44]),"+f"(d[45]),"+f"(d[46]),"+f"(d[47]),
      "+f"(d[48]),"+f"(d[49]),"+f"(d[50]),"+f"(d[51]),"+f"(d[52]),"+f"(d[53]),"+f"(d[54]),"+f"(d[55]),
      "+f"(d[56]),"+f"(d[57]),"+f"(d[58]),"+f"(d[59]),"+f"(d[60]),"+f"(d[61]),"+f"(d[62]),"+f"(d[63]),
      "+f"(d[64]),"+f"(d[65]),"+f"(d[66]),"+f"(d[67]),"+f"(d[68]),"+f"(d[69]),"+f"(d[70]),"+f"(d[71]),
      "+f"(d[72]),"+f"(d[73]),"+f"(d[74]),"+f"(d[75]),"+f"(d[76]),"+f"(d[77]),"+f"(d[78]),"+f"(d[79]),
      "+f"(d[80]),"+f"(d[81]),"+f"(d[82]),"+f"(d[83]),"+f"(d[84]),"+f"(d[85]),"+f"(d[86]),"+f"(d[87]),
      "+f"(d[88]),"+f"(d[89]),"+f"(d[90]),"+f"(d[91]),"+f"(d[92]),"+f"(d[93]),"+f"(d[94]),"+f"(d[95]),
      "+f"(d[96]),"+f"(d[97]),"+f"(d[98]),"+f"(d[99]),"+f"(d[100]),"+f"(d[101]),"+f"(d[102]),"+f"(d[103]),
      "+f"(d[104]),"+f"(d[105]),"+f"(d[106]),"+f"(d[107]),"+f"(d[108]),"+f"(d[109]),"+f"(d[110]),"+f"(d[111]),
      "+f"(d[112]),"+f"(d[113]),"+f"(d[114]),"+f"(d[115]),"+f"(d[116]),"+f"(d[117]),"+f"(d[118]),"+f"(d[119]),
      "+f"(d[120]),"+f"(d[121]),"+f"(d[122]),"+f"(d[123]),"+f"(d[124]),"+f"(d[125]),"+f"(d[126]),"+f"(d[127])
    : "l"(a), "l"(b), "r"(sd));
}
__device__ __forceinline__ void wgmma_rs_n32(float* d, const uint32_t* a, uint64_t b, int sd) {
  asm volatile("{.reg .pred p; setp.ne.b32 p, %21, 0;\n"
    "wgmma.mma_async.sync.aligned.m64n32k16.f32.bf16.bf16 {%0,%1,%2,%3,%4,%5,%6,%7,%8,%9,%10,%11,%12,%13,%14,%15}, {%16,%17,%18,%19}, %20, p, 1, 1, 0;}\n"
    : "+f"(d[0]),"+f"(d[1]),"+f"(d[2]),"+f"(d[3]),"+f"(d[4]),"+f"(d[5]),"+f"(d[6]),"+f"(d[7]),
      "+f"(d[8]),"+f"(d[9]),"+f"(d[10]),"+f"(d[11]),"+f"(d[12]),"+f"(d[13]),"+f"(d[14]),"+f"(d[15])
    : "r"(a[0]), "r"(a[1]), "r"(a[2]), "r"(a[3]), "l"(b), "r"(sd));
}
__device__ __forceinline__ void wgmma_ssT_n32(float* d, uint64_t a, uint64_t b, int sd) {
  asm volatile("{.reg .pred p; setp.ne.b32 p, %18, 0;\n"
    "wgmma.mma_async.sync.aligned.m64n32k16.f32.bf16.bf16 {%0,%1,%2,%3,%4,%5,%6,%7,%8,%9,%10,%11,%12,%13,%14,%15}, %16, %17, p, 1, 1, 1, 0;}\n"
    : "+f"(d[0]),"+f"(d[1]),"+f"(d[2]),"+f"(d[3]),"+f"(d[4]),"+f"(d[5]),"+f"(d[6]),"+f"(d[7]),
      "+f"(d[8]),"+f"(d[9]),"+f"(d[10]),"+f"(d[11]),"+f"(d[12]),"+f"(d[13]),"+f"(d[14]),"+f"(d[15])
    : "l"(a), "l"(b), "r"(sd));
}

__device__ __forceinline__ void wgmma_rs_n32_z(float* d, const uint32_t* a, uint64_t b) {
  asm volatile("{.reg .pred p; setp.ne.b32 p, 0, 0;\n"
    "wgmma.mma_async.sync.aligned.m64n32k16.f32.bf16.bf16 {%0,%1,%2,%3,%4,%5,%6,%7,%8,%9,%10,%11,%12,%13,%14,%15}, {%16,%17,%18,%19}, %20, p, 1, 1, 0;}\n"
    : "=f"(d[0]),"=f"(d[1]),"=f"(d[2]),"=f"(d[3]),"=f"(d[4]),"=f"(d[5]),"=f"(d[6]),"=f"(d[7]),
      "=f"(d[8]),"=f"(d[9]),"=f"(d[10]),"=f"(d[11]),"=f"(d[12]),"=f"(d[13]),"=f"(d[14]),"=f"(d[15])
    : "r"(a[0]), "r"(a[1]), "r"(a[2]), "r"(a[3]), "l"(b));
}

namespace rec {
constexpr int NVR = P_NVR;
constexpr int NVS = 16 - NVR;
constexpr int NVP = P_NVP;
constexpr int NWP = P_NWP;
constexpr uint32_t WO = 0;
constexpr uint32_t XB = 65536;
constexpr uint32_t PK = XB + 32768;
constexpr uint32_t VN = PK + 24576;
constexpr uint32_t VX0 = VN + 4096;
constexpr uint32_t WVS = 131072;
constexpr uint32_t MEM = WVS + 2 * NVS * 2048;
constexpr uint32_t ARO = MEM + 10240;
constexpr uint32_t OB = ARO + 5120;
constexpr uint32_t QT = OB + 2048;
constexpr uint32_t KT = QT + 2048;
constexpr uint32_t RQ = KT + 6144;
constexpr uint32_t RK = RQ + 2048;
constexpr uint32_t SC = RK + 2048;
constexpr uint32_t OT = OB;
constexpr uint32_t TF = SC + 2048;
constexpr uint32_t PRE = MEM + 2 * NVR * 2048;
constexpr uint32_t TA = TF + 8192;
constexpr uint32_t RX = TA + 6144;
constexpr uint32_t VX1 = RX + 2048;
constexpr uint32_t BARS = VX1 + 4096;
constexpr uint32_t PACE = BARS + 18 * 8;
constexpr uint32_t SMEM = BARS + 512;
static_assert(PRE + 14336 <= BARS, "staging");
constexpr int NW1 = P_NW1;
static_assert(SMEM <= 232448, "smem");
constexpr int B_E = 2, B_SC = 3, B_S = 4, B_O = 5, B_F = 6, B_W = 7, B_C = 9, B_K = 10, B_H = 15, B_Q = 1, B_S2 = 6, B_T2 = 9, B_P = 13, B_T = 14, B_R = 11, B_X = 12, B_V = 8;
constexpr int N_P = XE == 1 ? 416 : 384, N_R = XE ? 288 : 320, N_V = AV ? 384 : 512, N_O = AV ? 384 : 416;
constexpr int XC = 16384, X_RING = 131072, X_SC = 65536, X_TOK = 4096;
#define X_VX(i) (((i) >> 1) * 2048 + ((i) & 1) * 512)
#define X_VM(i) (X_VX(i) + 1024)
#define V_RING(n) (((n) & 1) * X_RING + ((n) & 2) * 2048)
#define V_TAG(n) ((~(n) >> 2) & 1)
}
struct RecMaps { CUtensorMap wq, wk, wv, wo, ari; int zero[40]; };

#define F_(x) __uint_as_float(x)
#define U_(x) __float_as_uint(x)
#define AR_R(q) (24 + ((q) & 1) * 16 + ((q) >> 1) * 56)
#define AR_P(q) ((q) >> 1)
#define AR_ROW(i) (24 + ((i) & 1) * 16 + ((i) & 2) * 92 + (((i) >> 2) & 7) + ((i) >> 5) * 128)
constexpr size_t AR_OFF = 32 * 262144;
__device__ __forceinline__ void ar_fetch(uint32_t dst, const CUtensorMap* m, int slot, int half, uint32_t mb) {
  asm volatile("{.reg .pred p; elect.sync _|p, 0xffffffff; @p mbarrier.arrive.expect_tx.shared.b64 _,[%4],10240;\n"
               "@p cp.async.bulk.tensor.3d.shared::cluster.global.mbarrier::complete_tx::bytes [%0],[%1,{%2,%3,%6}],[%4];\n"
               "@p cp.async.bulk.tensor.3d.shared::cluster.global.mbarrier::complete_tx::bytes [%0+5120],[%1,{%2,%5,%7}],[%4];}"
               ::"r"(dst), "l"(m), "r"(slot * 64), "r"(AR_R(half * 2)), "r"(mb), "r"(AR_R(half * 2 + 1)), "r"(AR_P(half * 2)), "r"(AR_P(half * 2 + 1)) : "memory");
}
__device__ __forceinline__ uint4 exch_b128(void* p, uint32_t x, uint32_t y, uint32_t z, uint32_t w) {
  uint4 v;
  asm volatile("{.reg .b128 s, t; .reg .b64 a,b; mov.b64 a,{%5,%6}; mov.b64 b,{%7,%8}; mov.b128 s,{a,b}; atom.relaxed.gpu.global.exch.b128 t,[%4],s;"
               " mov.b128 {a,b},t; mov.b64 {%0,%1},a; mov.b64 {%2,%3},b;}" : "=r"(v.x), "=r"(v.y), "=r"(v.z), "=r"(v.w) : "l"(p), "r"(x), "r"(y), "r"(z), "r"(w) : "memory");
  return v;
}
#define CONSUME(v) do { if ((v) == 0x7fc12345u) sts1(sb + rec::BARS + 96, 0); } while (0)
__device__ __forceinline__ uint32_t tagf(float v, uint32_t tag) { return (__float_as_uint(v) & ~1u) | tag; }
__device__ __forceinline__ uint2 ldg_b64(const void* p) { uint2 v; asm volatile("{.reg .b64 t; ld.relaxed.gpu.global.b64 t,[%2]; mov.b64 {%0,%1},t;}" : "=r"(v.x), "=r"(v.y) : "l"(p) : "memory"); return v; }
__device__ __forceinline__ void stg_b64(void* p, uint32_t x, uint32_t y) { asm volatile("{.reg .b64 t; mov.b64 t,{%1,%2}; st.relaxed.gpu.global.b64 [%0],t;}" ::"l"(p), "r"(x), "r"(y) : "memory"); }
__device__ __forceinline__ uint32_t tagbad(uint32_t x, uint32_t y, uint32_t tag) { uint32_t r; asm("lop3.b32 %0,%1,%2,%3,0x7e;" : "=r"(r) : "r"(x), "r"(y), "r"(tag)); return r; }

__device__ __forceinline__ bool anybad(uint32_t a, uint32_t b, uint32_t c, uint32_t d, uint32_t e, uint32_t f, uint32_t g, uint32_t h, uint32_t tag) {
  uint32_t r;
  asm volatile("{.reg .b32 t,u,v,w; .reg .pred p; lop3.b32 t,%1,%2,%9,0x7e; lop3.b32 u,%3,%4,%9,0x7e; lop3.b32 v,%5,%6,%9,0x7e; lop3.b32 w,%7,%8,%9,0x7e;"
               " lop3.b32 t,t,u,v,0xfe; lop3.b32 t,t,w,1,0xa8; setp.ne.u32 p,t,0; vote.sync.any.pred p,p,0xffffffff; selp.u32 %0,1,0,p;}"
               : "=r"(r) : "r"(a), "r"(b), "r"(c), "r"(d), "r"(e), "r"(f), "r"(g), "r"(h), "r"(tag));
  return r;
}
__device__ __forceinline__ bool anybad(uint32_t a, uint32_t b, uint32_t c, uint32_t d, uint32_t tag) {
  uint32_t r;
  asm volatile("{.reg .b32 t,u; .reg .pred p; lop3.b32 t,%1,%2,%5,0x7e; lop3.b32 u,%3,%4,%5,0x7e;"
               " lop3.b32 t,t,u,1,0xa8; setp.ne.u32 p,t,0; vote.sync.any.pred p,p,0xffffffff; selp.u32 %0,1,0,p;}"
               : "=r"(r) : "r"(a), "r"(b), "r"(c), "r"(d), "r"(tag));
  return r;
}
#define BAD8(r) anybad(r[0].x, r[0].z, r[1].x, r[1].z, r[2].x, r[2].z, r[3].x, r[3].z, tag)
#define BADS(r) anybad(r[0].x, r[0].y, r[1].x, r[1].y, r[2].x, r[2].y, r[3].x, r[3].y, tag)
constexpr float SCS = 0.08838834764831845f * 1.4426950408889634f / 16.f;
__device__ __forceinline__ uint32_t pkh(float lo, float hi, uint32_t tag) {
  uint32_t r;
  asm("{.reg .b32 t; cvt.rn.satfinite.f16x2.f32 t,%1,%2; lop3.b32 %0,t,0xfffffffe,%3,0xea;}" : "=r"(r) : "f"(hi), "f"(lo), "r"(tag));
  return r;
}
__device__ __forceinline__ uint32_t addh(uint32_t a, uint32_t b) { uint32_t r; asm("add.rn.f16x2 %0,%1,%2;" : "=r"(r) : "r"(a), "r"(b)); return r; }
__device__ __forceinline__ float hlo(uint32_t v) { float r; asm("{.reg .b16 a,b; mov.b32 {a,b},%1; cvt.f32.f16 %0,a;}" : "=f"(r) : "r"(v)); return r; }
__device__ __forceinline__ float hhi(uint32_t v) { float r; asm("{.reg .b16 a,b; mov.b32 {a,b},%1; cvt.f32.f16 %0,b;}" : "=f"(r) : "r"(v)); return r; }
__device__ __forceinline__ uint32_t ordh(uint32_t v) {
  uint32_t r;
  asm("{.reg .b32 m; prmt.b32 m,%1,0,0xbb99; lop3.b32 %0,%1,m,0x7fff7fff,0x78;}" : "=r"(r) : "r"(v));
  return r;
}
template <bool MASK>
__device__ __forceinline__ float4 softmax2(const uint2 (&r)[4], uint32_t mx, uint32_t my, uint32_t& k) {
  uint32_t x = addh(addh(r[0].x, r[1].x), addh(r[2].x, r[3].x)), y = addh(addh(r[0].y, r[1].y), addh(r[2].y, r[3].y));
  if (MASK) { x = addh(x, mx); y = addh(y, my); }
  asm("max.f16x2 %0,%1,%2;" : "=r"(k) : "r"(x), "r"(y));
  k = ordh(k);
  const int k0 = __reduce_max_sync(~0u, (int)(k << 16)), k1 = __reduce_max_sync(~0u, (int)k);
  const float m0 = hhi(k0 ^ ((k0 >> 31) & 0x7fff0000)) * -16.f, m1 = hhi(k1 ^ ((k1 >> 31) & 0x7fff0000)) * -16.f;
  return make_float4(ex2(fmaf(hlo(x), 16.f, m0)), ex2(fmaf(hhi(x), 16.f, m1)), ex2(fmaf(hlo(y), 16.f, m0)), ex2(fmaf(hhi(y), 16.f, m1)));
}
__device__ __forceinline__ char* mkp(uint32_t lo, uint32_t hi) { uint64_t r; asm("mov.b64 %0,{%1,%2};" : "=l"(r) : "r"(lo), "r"(hi)); return (char*)r; }
#define LO(p) ((uint32_t)(uint64_t)(p))
#define HI(p) ((uint32_t)((uint64_t)(p) >> 32))
__device__ __forceinline__ void cp16(uint32_t dst, const void* src) { asm volatile("cp.async.cg.shared.global [%0],[%1],16;" ::"r"(dst), "l"(src) : "memory"); }
__device__ __forceinline__ uint32_t xor3(uint32_t a, uint32_t b, uint32_t c) { uint32_t r; asm volatile("lop3.b32 %0,%1,%2,%3,0x96;" : "=r"(r) : "r"(a), "r"(b), "r"(c)); return r; }
__device__ __forceinline__ uint32_t mulbf(uint32_t a, uint32_t b) { uint32_t r; asm("mul.rn.bf16x2 %0,%1,%2;" : "=r"(r) : "r"(a), "r"(b)); return r; }
__device__ __forceinline__ uint32_t fmabf(uint32_t a, uint32_t b, uint32_t c) { uint32_t r; asm("fma.rn.bf16x2 %0,%1,%2,%3;" : "=r"(r) : "r"(a), "r"(b), "r"(c)); return r; }
__device__ __forceinline__ uint32_t addbf(uint32_t a, uint32_t b) { uint32_t r; asm("add.rn.bf16x2 %0,%1,%2;" : "=r"(r) : "r"(a), "r"(b)); return r; }
__device__ __forceinline__ void pv_mem(const uint32_t (&p)[4], uint32_t pm, const uint4 (&v)[4], const uint4 (&vn)[2], uint32_t (&O)[4]) {
  float o[4][4] = {{0, 0, 0, 0}, {0, 0, 0, 0}, {0, 0, 0, 0}, {0, 0, 0, 0}};
  mma16(o[0], v[0].x, v[0].y, v[0].z, v[0].w, p[0], p[1]);
  mma16(o[1], v[2].x, v[2].y, v[2].z, v[2].w, p[0], p[1]);
  mma16(o[2], v[1].x, v[1].y, v[1].z, v[1].w, p[2], p[3]);
  mma16(o[3], v[3].x, v[3].y, v[3].z, v[3].w, p[2], p[3]);
  mma16(o[0], vn[0].x, vn[0].y, vn[0].z, vn[0].w, pm, pm);
  mma16(o[1], vn[1].x, vn[1].y, vn[1].z, vn[1].w, pm, pm);
  O[0] = pk(o[0][0] + o[2][0], o[0][1] + o[2][1]); O[1] = pk(o[0][2] + o[2][2], o[0][3] + o[2][3]);
  O[2] = pk(o[1][0] + o[3][0], o[1][1] + o[3][1]); O[3] = pk(o[1][2] + o[3][2], o[1][3] + o[3][3]);
}
__device__ __forceinline__ void pv_tok(const uint32_t (&p)[4], uint32_t pm, const uint4 (&v)[4], const uint32_t (&vm)[4], uint32_t (&O)[4]) {
  float o[2][4] = {{0, 0, 0, 0}, {0, 0, 0, 0}}, sum[4] = {0, 0, 0, 0};
  const uint32_t one = 0x3f803f80u;
  mma16(sum, one, one, one, one, p[0], p[1]);
  mma16(o[0], v[0].x, v[0].y, v[0].z, v[0].w, p[0], p[1]);
  mma16(o[1], v[2].x, v[2].y, v[2].z, v[2].w, p[0], p[1]);
  mma16(sum, one, one, one, one, p[2], p[3]);
  mma16(o[0], v[1].x, v[1].y, v[1].z, v[1].w, p[2], p[3]);
  mma16(o[1], v[3].x, v[3].y, v[3].z, v[3].w, p[2], p[3]);
  mma8(sum, one, one, pm);
  mma8(o[0], vm[0], vm[1], pm);
  mma8(o[1], vm[2], vm[3], pm);
  float i0, i1;
  asm("rcp.approx.ftz.f32 %0,%1;" : "=f"(i0) : "f"(sum[0]));
  asm("rcp.approx.ftz.f32 %0,%1;" : "=f"(i1) : "f"(sum[1]));
  O[0] = pk(o[0][0] * i0, o[0][1] * i1); O[1] = pk(o[0][2] * i0, o[0][3] * i1);
  O[2] = pk(o[1][0] * i0, o[1][1] * i1); O[3] = pk(o[1][2] * i0, o[1][3] * i1);
}
__device__ __forceinline__ uint32_t sum4bf(uint32_t a, uint32_t b, uint32_t c, uint32_t d) { return addbf(addbf(a, b), addbf(c, d)); }
template <int OFF>
__device__ __forceinline__ void sta1(uint32_t a, uint32_t v, uint32_t mb) {
  asm volatile("st.async.shared::cluster.mbarrier::complete_tx::bytes.b32 [%0+%3],%1,[%2];" ::"r"(a), "r"(v), "r"(mb), "n"(OFF) : "memory");
}

__device__ __forceinline__ void wait_time(uint32_t t) { while ((int)(gtime() - t) < 0) __nanosleep(64); }
__device__ __noinline__ void rec_prefetch(const char* wmod, const char* w1, const char* x, const char* wo) {
  const int hb = blockIdx.x - 128;
  const uint32_t t0 = gtime();
  uint32_t t = t0 + PF0;
#pragma unroll 1
  for (int job = 0; job < (PFT ? 5 : 3); job++) {
    const char* p = job == 0 ? x + (6 + hb) * 65536 : job == 1 ? wmod + hb * 12288 + 4096 : job == 2 ? w1 + hb * 7168 : job == 3 ? x + hb * 8192 : wo + (1020 + hb) * 8192;
    const int n = job == 0 ? 120 - (hb & 2) * 4 : job == 3 ? 128 : 256, d = job == 0 ? 8192 : job == 1 ? 49152 : job == 2 ? 28672 : job == 3 ? 32768 : -32768;
    if (job == 3) t = t0 + PFT;
    PT(8 + job);
#pragma unroll 1
    for (int i = 0; i < n; i++) {
      wait_time(t);
      asm volatile("cp.async.bulk.prefetch.L2.global [%0], %1;" ::"l"(p), "r"(job == 2 ? 7168 : 8192) : "memory");
      p += !job && (i & 7) == 7 ? 204800 : d;
      t += job < 3 ? PFD : PFS;
      if (job && (i & 31) == 31 && ldg_rlx1(&g_fin)) return;
    }
  }
  PT(13);
}
__device__ __noinline__ void rec_helper(uint32_t sb, const bf16* cvec, const bf16* wmod, const char* w1, const bf16* b1, uint32_t t0) {
  const int tid = threadIdx.x, hb = blockIdx.x - 128;
  PT(1);
  for (int i = tid; i < 1024; i += 256) sts1(sb + i * 8, U_(rbf(silu(__bfloat162float(cvec[i])))));
  for (int i = tid; i < 2048; i += 256) g_stat[hb * 2048 + i] = make_uint4(~0u, ~0u, ~0u, ~0u);
  for (int i = tid; i < 512; i += 256) g_cnt[hb * 512 + i] = 0;
#pragma unroll 1
  for (int job = 0; job < 2; job++) {
    wait_time(t0 + PF0 + (job ? 600 : 350) * PFD);
    BAR_SYNC(rec::B_F, 256);
    PT(2 + job * 5);
    const int n8 = job ? 112 : 128, rg = tid >= n8, cg = tid - rg * n8, pitch = job ? 448 : 768;
    const uint4* p = (const uint4*)(job ? w1 + hb * 1792 : (const char*)(wmod + 2048 + hb * 1024)) + rg * pitch + min(cg, n8 - 1);
    float a1[8] = {0, 0, 0, 0, 0, 0, 0, 0}, a2[8] = {0, 0, 0, 0, 0, 0, 0, 0};
#pragma unroll 1
    for (int r0 = rg; r0 < 1024; r0 += 32) {
      uint4 v[16];
#pragma unroll
      for (int i = 0; i < 16; i++) { v[i] = ldg_rlx4(p); p += 2 * pitch; }
#pragma unroll
      for (int i = 0; i < 16; i++) {
        const float2 f = lds2f(sb + (r0 + 2 * i) * 8);
        const float w[8] = {blo(v[i].x), bhi(v[i].x), blo(v[i].y), bhi(v[i].y), blo(v[i].z), bhi(v[i].z), blo(v[i].w), bhi(v[i].w)};
#pragma unroll
        for (int e = 0; e < 8; e++) { a1[e] += f.x * w[e]; a2[e] += f.y * w[e]; }
      }
    }
    const uint32_t rd = sb + 8192;
    if (cg < n8) {
#pragma unroll
      for (int e = 0; e < 8; e++) sts2(rd + rg * 8192 + (cg * 8 + e) * 8, U_(a1[e]), U_(a2[e]));
    }
    BAR_SYNC(rec::B_F, 256);
    if (job == 0) {
      for (int i = tid; i < 1024; i += 256) g_mod[2048 + hb * 1024 + i] = rbf(F_(lds1(rd + i * 8)) + F_(lds1(rd + 8192 + i * 8)));
      BAR_SYNC(rec::B_F, 256);
      PT(6);
      if (tid == 0) { red_rel(&g_mcnt); wait_cnt(&g_mcnt, 4); }
      BAR_SYNC(rec::B_F, 256);
      for (int i = tid; i < 1024; i += 256) sts2(sb + i * 8, U_(rbf(1.f + __ldcg(g_mod + 4096 + i))), U_(__ldcg(g_mod + 3072 + i)));
    } else {
      for (int i = tid; i < 448; i += 256) {
        const int gn = hb * 896 + i * 2;
        const uint32_t bb = *(const uint32_t*)(b1 + gn);
        const float4 u = lds4f(rd + i * 16), w = lds4f(rd + 8192 + i * 16);
        ((uint2*)g_cc)[(gn >> 4) * 8 + ((gn >> 1) & 3) * 2 + ((gn >> 3) & 1)] = make_uint2(pk(u.x + w.x, u.z + w.z), pk(0.5f * (u.y + w.y + blo(bb)), 0.5f * (u.w + w.w + bhi(bb))));
      }
      PT(4);
    }
  }
}

__global__ void __cluster_dims__(2, 1, 1) __launch_bounds__(512, 1)
k_rec(const __grid_constant__ RecMaps mp, const bf16* __restrict__ mem0, const bf16* __restrict__ x, const bf16* __restrict__ cvec,
      const bf16* __restrict__ wmod, const char* __restrict__ w1, const bf16* __restrict__ b1, const char* __restrict__ wo, char* xc, int dF, int dA, int dS, int dM, int dG, int dP, int dX, int dD, int dZ, int dZ2, int dV, int dX2) {
  using namespace rec;
  extern __shared__ __align__(1024) char smem[];
  const uint32_t sb = (uint32_t)__cvta_generic_to_shared(smem);
  if ((sb & 0x3FFFF) != 1024) __trap();
  PH(0); RS(0); if (threadIdx.x == 0) PT(0);
  if (threadIdx.x == 0) {
    int b = blockIdx.x;
    if (b >= 8 && b < 128) {
      const int t = (b >> 1) - 4, u = t - 32;
      b = 2 * (t < 32 ? 4 + (t & 16) + (t & 7) * 2 + ((t >> 3) & 1) : 36 + (u / 14) * 14 + (u % 7) * 2 + ((u / 7) & 1)) + (b & 1);
    }
    sts1(sb + rec::PACE + 24, b);
    const int c = blockIdx.x >> 1, l = c < 36 ? (c - 4) & 7 : (c - 36) % 7, m = c < 4 ? c : c < 36 ? (c - 4) >> 3 : (c - 36) / 7;
    const int g = c < 4 ? 15 : (l >> 1) * 4 + (l & 1) + (c < 36 ? 0 : 2);
    unsigned sm;
    asm("mov.u32 %0,%%smid;" : "=r"(sm));
    if (c < 64) g_slot[sm & 255] = 1 + FMAP;
  }
#define ROLE_REFRESH { asm volatile("mov.u32 %0,%%tid.x;" : "=r"(tid)); wid = __shfl_sync(~0u, tid >> 5, 0); b = __shfl_sync(~0u, lds1(sb + PACE + 24), 0); }
#define ROLE_VARS int tid; asm volatile("mov.u32 %0,%%tid.x;" : "=r"(tid)); \
    int wid = __shfl_sync(~0u, tid >> 5, 0), b = __shfl_sync(~0u, lds1(sb + PACE + 24), 0);
#define wg (wid >> 2)
#define iw (wid & 3)
#define h (b >> 2)
#define j (b & 3)
#define a (b & 1)
#define bb ((b >> 1) & 1)
  const uint32_t wbar = sb + BARS + 48, obar = wbar + 8;
  if (threadIdx.x == 256) {
    for (int i = 0; i < 18; i++) if (i != 12) mbar_init(sb + BARS + i * 8, i == 3 || i == 8 || i == 9 || i == 10 ? 2 : 1);
    for (int i = 0; i < 3; i++) mbar_init(sb + PACE + i * 8, 1);
    asm volatile("fence.mbarrier_init.release.cluster;" ::: "memory");
    FENCE_ASYNC_SMEM();
    mbar_expect(sb + BARS, 2048);
    mbar_expect(sb + BARS + 16, 4096);
    mbar_expect(sb + BARS + 32, 4096);
    mbar_expect(sb + BARS + 40, 4096);
  }
  __syncthreads();
  asm volatile("barrier.cluster.arrive.relaxed.aligned;" ::: "memory");
#define lane ((int)(l16 >> 4))
#define l16 (L16 & 0x1f0)
#define is7 ((L16 & 112) == 112)
#define PIN(x) __shfl_xor_sync(~0u, (uint32_t)(x), 0)
#define REFRESH() L16 = __shfl_xor_sync(~0u, L16, 0)
#define lar ((L16 & 0x180) * 8 + (L16 & 0x70))
#define X_LOAD(n, w, u) \
        asm volatile("{.reg .pred p; elect.sync _|p, 0xffffffff; @p mbarrier.arrive.expect_tx.shared.b64 _,[%2],8192;\n" \
                     "@p cp.async.bulk.shared::cluster.global.mbarrier::complete_tx::bytes [%0],[%1],8192,[%2];}" ::"r"(sb + XB + (w) * 16384 + (u) * 8192), \
                     "l"(g_h + (n) * 4096 + a * 2048 + (w) * 1024 + (u) * 512), "r"(sb + BARS + 64 + (w) * 8) : "memory")
#define lpub ((L16 & 0x30) * 64 + ((L16 >> 3) & 0x38))
#define lrow ((L16 & 0x70) + (((L16 >> 3) ^ L16) & 0x70 & ~((L16 >> 3) & 0x40) ? L16 & 0x180 : 512))

  const int role = __shfl_sync(~0u, threadIdx.x >> 7, 0);
  if (role < 2) {
    asm volatile("setmaxnreg.inc.sync.aligned.u32 %0;" ::"n"(RF_));
    ROLE_VARS
    uint32_t L16 = __shfl_sync(~0u, sb + (tid & 31) * 16, tid & 31);
    uint32_t wQ[16][4], wK[16][4], wV[NVR][4];
    uint32_t frag = sb + ((lane & 7) + (lane >> 4) * 8) * 128 + (((iw * 2 + ((lane >> 3) & 1)) ^ (lane & 7)) << 4);
#define QSW (SWP && !a ? 64 : 0)
    {
      const bool spare = b >= 128;
      const uint32_t t0 = gtime();
      uint4 xr[16];
      int seg = spare ? b - 126 : wg;
      const int half = spare ? wg : a;
      auto x_fetch = [&]() {
        const uint4* px = (const uint4*)x + (seg * 32 + iw * 8 + (lane >> 2)) * 128 + half * 64 + (lane & 3);
#pragma unroll
        for (int i = 0; i < 16; i++) xr[i] = __ldg(px + i * 4);
      };
      if (!spare) {
        uint4 wm[8];
        const uint4* pw = (const uint4*)(wmod + (size_t)((b >> 5) * 256 + (tid >> 3)) * 6144 + (b & 31) * 64) + (tid & 7);
        const float cs = __bfloat162float(cvec[(b >> 5) * 256 + tid]);
#pragma unroll
        for (int i = 0; i < 8; i++) wm[i] = __ldcs(pw + (size_t)i * 32 * 768);
        float* sc = (float*)(smem + PRE);
        sc[tid] = rbf(silu(cs));
        PT(1);
        BAR_SYNC(B_F, 256);
        float acc[8] = {0, 0, 0, 0, 0, 0, 0, 0};
#pragma unroll
        for (int i = 0; i < 8; i++) {
          const float f = sc[i * 32 + (tid >> 3)];
          acc[0] += f * blo(wm[i].x); acc[1] += f * bhi(wm[i].x); acc[2] += f * blo(wm[i].y); acc[3] += f * bhi(wm[i].y);
          acc[4] += f * blo(wm[i].z); acc[5] += f * bhi(wm[i].z); acc[6] += f * blo(wm[i].w); acc[7] += f * bhi(wm[i].w);
        }
#pragma unroll
        for (int i = 0; i < 8; i++) { acc[i] += __shfl_xor_sync(~0u, acc[i], 8); acc[i] += __shfl_xor_sync(~0u, acc[i], 16); }
        float* red = sc + 1024;
        if ((tid & 31) < 8) {
#pragma unroll
          for (int i = 0; i < 8; i++) red[(tid >> 5) * 64 + (tid & 7) * 8 + i] = acc[i];
        }
        BAR_SYNC(B_F, 256);
        PT(2);
        if (tid < 64) {
          float t = 0;
#pragma unroll
          for (int i = 0; i < 8; i++) t += red[i * 64 + tid];
          asm volatile("st.relaxed.gpu.global.u32 [%0],%1;" ::"l"((unsigned*)g_modp + (b >> 5) * 2048 + (b & 31) * 64 + tid), "r"(U_(t) | 1u) : "memory");
        }
      } else {
        asm volatile("griddepcontrol.launch_dependents;");
      }
      x_fetch();
      const uint32_t md = sb + PRE + 6144, rx = mapa(sb, a ^ !spare);
      asm volatile("barrier.cluster.wait.aligned;" ::: "memory");
      if (!spare) {
        mbar_wait(sb + BARS + 88, 0);
#pragma unroll
        for (int i = 0; i < 16; i++) ldsm4t(wQ[i], (frag ^ QSW) + WO + wg * 32768 + i * 2048);
      }
      PT(4);
#pragma unroll 1
      for (int it = 0;; it++) {
        if (tid == 0) mbar_expect(sb + BARS + 104, 512);
        float c[4][4] = {{0, 0, 0, 0}, {0, 0, 0, 0}, {0, 0, 0, 0}, {0, 0, 0, 0}};
#pragma unroll
        for (int i = 0; i < 16; i++) {
          mma16(c[(i & 1) * 2], xr[i].x, 0x3f803f80u, xr[i].y, 0x3f803f80u, xr[i].x, xr[i].y);
          mma16(c[(i & 1) * 2 + 1], xr[i].z, 0x3f803f80u, xr[i].w, 0x3f803f80u, xr[i].z, xr[i].w);
        }
#pragma unroll
        for (int e = 0; e < 4; e++) c[0][e] = (c[0][e] + c[1][e]) + (c[2][e] + c[3][e]);
        const int src = (lane & 28) + (lane >> 3);
        const float sq = __shfl_sync(~0u, (lane & 4) ? c[0][1] : c[0][0], src), sm = __shfl_sync(~0u, (lane & 4) ? c[0][3] : c[0][2], src);
        if ((lane & 3) < 2) sta1<0>(rx + PRE + 10240 + (wid ^ (spare * 4)) * 64 + (lane >> 2) * 8 + (lane & 1) * 4, U_((lane & 1) ? sm : sq), rx + BARS + 104);
        mbar_wait(sb + BARS + 104, it & 1);
        const float2 ot = lds2f(sb + PRE + 10240 + wid * 64 + (lane >> 2) * 8);
        const float mean = (sm + ot.y) * (1.f / 1024);
        const float rs = rsqrtf(fmaxf((sq + ot.x) * (1.f / 1024) - mean * mean, 0.f) + 1e-5f), nm = -mean * rs;
        const uint32_t rh = pk(rs, rs), rl = pk(rs - blo(rh), rs - blo(rh)), n2 = pk(nm, nm);
#define NRM(v) v = fmabf(v, rh, fmabf(v, rl, n2))
#pragma unroll
        for (int i = 0; i < 16; i++) { NRM(xr[i].x); NRM(xr[i].y); NRM(xr[i].z); NRM(xr[i].w); }
        if (!it) {
          PT(3);
#pragma unroll 1
          for (int i = 0; i < 2; i++) {
            uint4 p[4];
            for (int n = 0;; n++) {
#pragma unroll
              for (int e = 0; e < 4; e++) p[e] = ldg_rlx4(g_modp + e * 512 + i * 256 + tid);
              uint32_t ok = 1;
#pragma unroll
              for (int e = 0; e < 4; e++) ok &= p[e].x & p[e].y & p[e].z & p[e].w;
              if (__all_sync(~0u, ok) || n > SPIN_LIMIT / 16) break;
              __nanosleep(100);
            }
#define MSUM(e) (i + rbf((F_(p[0].e) + F_(p[1].e)) + (F_(p[2].e) + F_(p[3].e))))
            sts2(md + i * 2048 + tid * 8, pk(MSUM(x), MSUM(y)), pk(MSUM(z), MSUM(w)));
          }
          BAR_SYNC(B_F, 256);
          PT(5);
        }
        const int e0 = (iw * 8 + (lane >> 2)) * 8 + ((lane & 3) ^ (lane >> 2));
        uint4* dst = g_h + seg * 4096 + half * 2048;
#pragma unroll
        for (int i = 0; i < 16; i++) {
          const uint32_t ma = md + half * 1024 + (lane & 3) * 16 + i * 64;
          const uint4 sv = lds4(ma), cv = lds4(ma + 2048);
          xr[i] = make_uint4(fmabf(xr[i].x, cv.x, sv.x), fmabf(xr[i].y, cv.y, sv.y), fmabf(xr[i].z, cv.z, sv.z), fmabf(xr[i].w, cv.w, sv.w));
        }
        if (!spare) {
#pragma unroll
          for (int i = 0; i < 16; i++) sts4(sb + WO + wg * 32768 + (e0 ^ ((i & 1) * 4)) * 16 + (i >> 1) * 4096, xr[i].x, xr[i].y, xr[i].z, xr[i].w);
          break;
        }
#pragma unroll
        for (int i = 0; i < 16; i++) dst[(e0 ^ ((i & 1) * 4)) + (i >> 1) * 256] = xr[i];
        seg += 4;
        if (seg < 64) x_fetch();
        FENCE_ASYNC();
        BAR_SYNC(B_F, 256);
        if (tid == 0) red_rlx(g_hf + b - 128);
        if (seg >= 64) break;
      }
      if (spare) { rec_helper(sb, cvec, wmod, w1, b1, t0); return; }
      PH(1); PH(2); PT(6);
    }
    ROLE_REFRESH
#define ownv ((iw >> 1) == a)
#define owner (SWP ? iw >= 2 : ownv)
#define vfin ((wid >> 1) == a)
#define oi (wid & 1)
    {
      const uint32_t rsb = mapa(sb, owner ? a : a ^ 1);
      const uint32_t pp = rsb + PK + (owner ? 0 : 12288) + (oi * 2048 + wg * 1024) + l16;
      const uint32_t mb = sb + MEM + wg * 5120;
      sts4(L16 + TF + wid * 512, mb + lrow, owner ? L16 + (lane >> 4) * (RK - RQ - 256) + RQ + oi * 1024 + wg * 256 : rsb + RQ + oi * 1024 + 512 + wg * 256 + (l16 >> 2),
           L16 + OB, frag + wg * NVS * 2048);
      sts4(L16 + TF + 4096 + wid * 512, sb + WO + (wid >> 1) * 16384 + ((lane & 7) + (lane >> 4) * 8) * 128 + ((((wid & 1) * 4 + ((lane >> 3) & 1)) ^ (lane & 7)) << 4),
           sb + ARO + wid * 640 + lrow, pp, LO(xc) + h * 262144 + (bb * 2 + (iw >> 1)) * XC + X_VM(0) + oi * 2048 + a * 256 + (l16 >> 1));
    }
    uint32_t tp = L16 + TF + wid * 512;
    auto park_ptr = [&]() { return lds1(tp + 4096 + 8); };
    auto park_w = [&](const uint32_t* w, int m, uint32_t d) {
      if (SWP && m == 2) d += (sb & 0x1000000) ? 0 : owner ? 0x1003000 : -0x1003000;
      if (m == 2 ? ownv : owner) {
        sts4(d + m * 4096, w[0], w[1], w[2], w[3]); sts4(d + m * 4096 + 512, w[4], w[5], w[6], w[7]);
      } else {
        const uint32_t pb = (d & 0xff000000u) | (1024 + BARS + (m ? 24 + m * 8 : 16));
        sta4(d + m * 4096, w, pb); sta4(d + m * 4096 + 512, w + 4, pb);
      }
    };
    auto park = [&](const float* f, int m, int n, uint32_t d) {
      uint32_t w[8];
#pragma unroll
      for (int i = 0; i < 8; i++) w[i] = pk(f[2 * i], f[2 * i + 1]);
      park_w(w, m, d);
    };
#define D64(lo) (0x4000004000000000ull | (uint32_t)(lo))
#define XD(i) D64(x | (((i) >> 2) * 256 + ((i) & 3) * 2))
    auto xdesc = [&](uint32_t xb) { return ((uint32_t)__shfl_sync(~0u, 1024 + xb + wg * 16384, 0) >> 4) | 0x10000u; };
    auto rs_issue = [&](float* acc, const uint32_t (&w)[16][4], uint32_t xb, bool fence) {
      const uint32_t x = xdesc(xb);
      if (fence) WG_FENCE();
      wgmma_rs_n32_z(acc, w[0], XD(0));
#pragma unroll
      for (int i = 1; i < 16; i++) wgmma_rs_n32(acc, w[i], XD(i), 1);
      WG_COMMIT();
    };
    auto v_issue = [&](float* acc, uint32_t xb, bool fence) {
      const uint32_t dv = ((uint32_t)__shfl_sync(~0u, 1024 + WVS + wg * NVS * 2048, 0) >> 4) | 0x10000u, x = xdesc(xb);
      if (fence) WG_FENCE();
      wgmma_rs_n32_z(acc, wV[0], XD(0));
#pragma unroll
      for (int i = 1; i < VRF; i++) wgmma_rs_n32(acc, wV[i], XD(i), 1);
#pragma unroll
      for (int i = NVR; i < 16; i++) wgmma_ssT_n32(acc, D64(dv + (i - NVR) * 128), XD(i), 1);
#pragma unroll
      for (int i = VRF; i < NVR; i++) wgmma_rs_n32(acc, wV[i], XD(i), 1);
      WG_COMMIT();
    };
    uint32_t mA, vP[2][4];
#define V_AHEAD mA = lds1(tp); frag = lds1(tp + 12); ldsm4t(vP[0], frag + WVS + (15 - NVR) * 2048); ldsm4t(vP[1], frag + WVS + (14 - NVR) * 2048);
    auto vk_pass = [&](int n, uint32_t d, uint32_t xb, bool steady, auto between) {
      float acc[16], acc2[16];
      v_issue(acc, xb, true);
      rs_issue(acc2, wK, xb, false);
      between();
      if (steady || n) mbar_wait(sb + BARS + 80, (n - 1) & 1);
      WG_WAIT(1);
      park(acc, 2 - !!KVO, n, d);
      if (steady) BAR_ARRIVE(B_K, 320);
      V_AHEAD
      WG_WAIT(0);
      park(acc2, 1 + !!KVO, n, d + (VPC ? (vP[1][0] ^ mA) & dZ : 0));
    };
    uint32_t q0[8], q1[8];
    {
      float acc[16], acc2[16];
      FENCE_ASYNC_SMEM();
      BAR_SYNC(B_F, 256);
      rs_issue(acc, wQ, WO, true);
      rs_issue(acc2, wQ, WO + 32768, false);
      WG_WAIT(0);
#pragma unroll
      for (int i = 0; i < 8; i++) { q0[i] = pk(acc[2 * i], acc[2 * i + 1]); q1[i] = pk(acc2[2 * i], acc2[2 * i + 1]); }
    }
    mbar_wait(wbar, 0);
    PT(7);
#pragma unroll
    for (int i = 0; i < 16; i++) ldsm4t(wK[i], (frag ^ QSW) + XB + wg * 32768 + i * 2048);
#pragma unroll
    for (int i = 0; i < NVR; i++) ldsm4t(wV[i], frag + MEM + (wg * NVR + i) * 2048);
    FENCE_ASYNC_SMEM();
    PH(3); PT(8);
    CLUSTER_SYNC();
    PT(9);
    frag += wg * NVS * 2048;
    park_w(q0, 0, park_ptr());
    PT(10);
#pragma unroll 1
    for (int n = 0; n < 2; n++) {
      asm volatile("" : "+r"(wid));
      vk_pass(n, park_ptr(), n * XB, false, [&]() {
        if (n) {
          BAR_SYNC(B_C, 320);
          PT(12);
          mbar_wait(sb + BARS + 24, 0);
          park_w(q1, 0, park_ptr());
        }
      });
      if (n) break;
      PT(11);
      BAR_SYNC(B_C, 448);
      if (tid == 0) {
        mbar_expect(obar, 65536);
#pragma unroll 1
        for (int i = 0; i < 4; i++) tma2d(sb + WO + i * 16384, &mp.wo, j * 256 + i * 64, h * 128, obar);
      }
    }
    static_assert(WO == 0, "x");
    {
      BAR_ARRIVE(B_P, N_P); if (!HX) BAR_ARRIVE(B_X, 320); if (XE != 1) BAR_ARRIVE(B_Q, 288);
    }
    PT(13);
    if (!OBL) mbar_wait(obar, 0);
    PH(4); RS(1); PT(14);
    ROLE_REFRESH
    for (int s = 0; s < 64; s++) {
      asm volatile("" : "+r"(tp), "+r"(wid));
      asm volatile("mov.u32 %0,%%cluster_ctarank;" : "=r"(b));
      uint32_t vS[NVS][4], bf[8][4];
      static_assert(NVR == 5, "schedule");
#define VLD(k) ldsm4t(vS[(k) - NVR], frag + WVS + ((k) - NVR) * 2048)
#define BLD(t) ldsm4t(bf[t], mA + (t) * 640)
#define VMMA(c, w, i) mma16(c, (w)[0], (w)[1], (w)[2], (w)[3], bf[(i) >> 1][((i) & 1) * 2], bf[(i) >> 1][((i) & 1) * 2 + 1])
#define VS_(c, k) VMMA(c, vS[(k) - NVR], k)
#define QK(i) VMMA(cQ, wQ[i], i); VMMA(cK, wK[i], i)
#define PREV if (NF) { VLD(13); VLD(12); if (NF > 2) VLD(11); } else { VLD(15); VLD(14); }
      if (s > 0) BAR_SYNC(B_R, N_R);
      float cV[4] = {0, 0, 0, 0}, cW[4] = {0, 0, 0, 0};
      {
        float cQ[4] = {0, 0, 0, 0}, cK[4] = {0, 0, 0, 0};
        BLD(7); BLD(6); BLD(5); BLD(4); if (NB0 > 4) BLD(3);
        SCHED_FENCE(47);
        QK(15); VMMA(cV, vP[0], 15);
        QK(14); VMMA(cV, vP[1], 14);
        QK(13); QK(12);
        SCHED_FENCE(51);
        if (NB0 < 5) BLD(3);
        BLD(2); BLD(1); BLD(0);
        const uint32_t rm = lds1(tp + 4);
        if (!NF) frag = lds1(tp + 12);
        QK(11); QK(10); QK(9); QK(8); QK(7);
        if (PV0 == 6) { SCHED_FENCE(48); PREV }
        QK(6); QK(5);
        if (PV0 == 4) { QK(4); SCHED_FENCE(48); PREV } else { QK(4); }
        QK(3); QK(2); QK(1); QK(0);
        const uint32_t w0 = pk(cQ[0] * SCS, cQ[1] * SCS), w1 = pk(cQ[2] * SCS, cQ[3] * SCS), w2 = pk(cK[0], cK[1]), w3 = pk(cK[2], cK[3]);
        if (owner) {
          stsm4(rm, w0, w1, w2, w3);
          BAR_ARRIVE(B_E, 256);
        } else {
          const uint32_t mm = (rm & 0xff000000u) | (1024 + BARS);
          sta1<0>(rm, w0, mm); sta1<128>(rm, w1, mm);
          sta1<RK - RQ>(rm, w2, mm); sta1<RK - RQ + 128>(rm, w3, mm);
        }
        if (wid == 2) TS(0);
      }
      uint4 t1;
      uint32_t oA, wo[16][4];
      {
        if (NF == 0) {
          VLD(13); VLD(12);
          VS_(cW, 15); VS_(cV, 14); VLD(11); VMMA(cW, wV[0], 0); VLD(10); VMMA(cV, wV[1], 1); VLD(9);
          VMMA(cW, wV[2], 2); VLD(8); VMMA(cV, wV[3], 3); VLD(7); VMMA(cW, wV[4], 4); VS_(cV, 13); VLD(6); VS_(cW, 12); VLD(5);
          VS_(cV, 11);
        } else {
          if (NF < 3) VLD(11);
          VLD(10);
          VS_(cW, 13); VLD(9); VS_(cV, 12); VLD(8); VLD(7); VMMA(cW, wV[0], 0); VMMA(cV, wV[1], 1); VLD(6);
          VMMA(cW, wV[2], 2); VMMA(cV, wV[3], 3); VLD(5); VMMA(cW, wV[4], 4); VS_(cV, 11);
        }
        VS_(cW, 10); VS_(cV, 9); VS_(cW, 8); VS_(cV, 7); VS_(cW, 6); VS_(cV, 5);
#pragma unroll
        for (int e = 0; e < 4; e++) cV[e] += cW[e];
        const uint32_t ex = tp + (RX - TF) - wg * 2048;
        t1 = lds4(tp + 4096 + (T1L ? vS[3][0] & dZ : 0));
        oA = lds1(tp + 8 + (s & dZ));
        if (wg) {
          sts4(ex, U_(cV[0]), U_(cV[1]), U_(cV[2]), U_(cV[3]));
          BAR_ARRIVE(B_T2, 256);
        }
#pragma unroll
        for (int i = 0; i < VCO; i++) ldsm4t(wo[i], (t1.x ^ ((i & 1) * 32)) + (i >> 1) * 2048);
        if (!wg) {
          BAR_SYNC(B_T2, 256);
          const float4 u = lds4f(ex);
          stg_b64(mkp(t1.w ^ ((s & 1) * X_RING), HI(xc)), (pk(cV[0] + u.x, cV[1] + u.y) & ~1u) | (((s >> 1) + 1) & 1), pk(cV[2] + u.z, cV[3] + u.w));
        }
      }
      if (s == 63) break;
      if (OBL && s == 0) mbar_wait(obar, 0);
      {
        const uint32_t woA = t1.x, woB = woA ^ 32;
#pragma unroll
        for (int i = VCO; i < NW0; i++) ldsm4t(wo[i], ((i & 1) ? woB : woA) + (i >= WCH ? wo[(i - WCH + NWP) % NWP][0] & dZ : 0) + (i >> 1) * 2048);
        BAR_SYNC(B_S, 416);
        float inv0, inv1;
        uint32_t p[4], pm;
        const uint32_t pa = oA + (SC - OB), one = 0x3f803f80u;
#define P_LOAD ldsm4t(p, pa); asm volatile("ldmatrix.sync.aligned.m8n8.x1.trans.shared.b16 {%0},[%1];" : "=r"(pm) : "r"(pa + 512) : "memory");
        if (s < 62) {
          float acc[16];
          rs_issue(acc, wQ, XB, true);
          mbar_wait(sb + BARS + 24, (s + 1) & 1);
          WG_WAIT(0);
          uint32_t qw[8];
#pragma unroll
          for (int i = 0; i < 8; i++) qw[i] = pk(acc[2 * i], acc[2 * i + 1]);
#pragma unroll
          for (int i = NW0; i < NW1; i++) ldsm4t(wo[i], ((i & 1) ? woB : woA) + (i >> 1) * 2048);
          BAR_SYNC(B_V, N_V);
          if (RSO) { P_LOAD }
          park_w(qw, 0, t1.z + (RSO == 1 ? pm & dZ : 0));
        } else {
#pragma unroll
          for (int i = NW0; i < NW1; i++) ldsm4t(wo[i], ((i & 1) ? woB : woA) + (i >> 1) * 2048);
          BAR_SYNC(B_V, N_V);
          if (RSO) { P_LOAD }
        }
#pragma unroll
        for (int i = NW1; i < NWP; i++) ldsm4t(wo[i], ((i & 1) ? woB : woA) + (i >> 1) * 2048);
        {
          float sum[4] = {0, 0, 0, 0}, su2[4] = {0, 0, 0, 0};
          if (!RSO) { P_LOAD }
          mma16(sum, one, one, one, one, p[0], p[1]);
          mma16(su2, one, one, one, one, p[2], p[3]);
          mma8(sum, one, one, pm);
          inv0 = sum[0] + su2[0]; inv1 = sum[1] + su2[1];
          SCHED_FENCE(57);
        }
        BAR_SYNC(B_O, N_O);
        float c[2][4] = {{0, 0, 0, 0}, {0, 0, 0, 0}};
        uint32_t o[4][4];
#pragma unroll
        for (int i = 0; i < NOP_; i++) ldsm4t(o[i], oA + i * 512);
        SCHED_FENCE(46);
        asm("rcp.approx.ftz.f32 %0,%0;" : "+f"(inv0));
        asm("rcp.approx.ftz.f32 %0,%0;" : "+f"(inv1));
#pragma unroll
        for (int i = 0; i < 16; i++) {
          mma16(c[i & 1], wo[i][0], wo[i][1], wo[i][2], wo[i][3], o[i >> 2][i & 2], o[i >> 2][(i & 2) + 1]);
          if (i == 1 && NOP_ < 3) ldsm4t(o[2], oA + 1024);
          if (i == 3 && NOP_ < 4) ldsm4t(o[3], oA + 1536);
          if (i + NWP < 16) ldsm4t(wo[(i + NWP) & 15], (((i + NWP) & 1) ? woB : woA) + ((i + NWP) >> 1) * 2048);
        }
        stsm4(t1.y, pk(c[0][0] * inv0, c[0][1] * inv1), pk(c[0][2] * inv0, c[0][3] * inv1), pk(c[1][0] * inv0, c[1][1] * inv1), pk(c[1][2] * inv0, c[1][3] * inv1));
      }
      const uint32_t d = park_ptr();
      BAR_SYNC(B_W, 384);
      if (s < 62) {
        vk_pass(s + 2, d, XB, true, []() {});
        if (XE == 2) BAR_ARRIVE(B_Q, 288);
        BAR_ARRIVE(B_P, N_P); if (!HX) BAR_ARRIVE(B_X, 320);
        TS(10);
      } else {
        V_AHEAD
        CONSUME(vP[1][0]);
      }
    }
  } else if (role == 3) {
    asm volatile("setmaxnreg.dec.sync.aligned.u32 24;");
    if (blockIdx.x >= 128) return;
    ROLE_VARS
    const uint32_t L16 = sb + (tid & 31) * 16;
    asm volatile("barrier.cluster.wait.aligned;" ::: "memory");
    CLUSTER_SYNC();
    sts1(sb + PACE + 36, LO(xc) + h * 262144 + X_VM(0));
    auto vm_stage = [&](int s) {
      if (AV) return;
      const uint32_t tag = ((s >> 1) + 1) & 1;
      const char* xm = mkp(lds1(sb + PACE + 36) + (s & 1) * X_RING + iw * XC + (l16 >> 1), HI(xc));
      uint2 m[4];
      CONSUME(LO(xm));
      BAR_SYNC(B_S2, 256);
      if (dZ2 > 1) { const uint32_t c = clk(); while (clk() - c < (uint32_t)dZ2) {} }
      int it = 0;
      while (true) {
#pragma unroll
        for (int i = 0; i < 4; i++) m[i] = ldg_b64(xm + (i >> 1) * 2048 + (i & 1) * 256);
        sts4(L16 + VN + iw * 512, m[0].x, m[0].y, m[1].x, m[1].y);
        sts4(L16 + VN + iw * 512 + 2048, m[2].x, m[2].y, m[3].x, m[3].y);
        if (HV || !anybad(m[0].x, m[1].x, m[2].x, m[3].x, tag)) break;
        RP(2);
        if (++it > SPIN_LIMIT) __trap();
      }
      if (s < 63) BAR_ARRIVE(B_V, 512); else BAR_ARRIVE(B_V, 256);
    };
    if (iw == 0) {
      wait_cnt(&g_hcnt, 128);
#pragma unroll 1
      for (int s = 0; s < 63; s++) {
        if (s < 62) for (int it = 0; ldg_rlx1(g_hf + (s & 3)) <= (s >> 2); it++) if (it > SPIN_LIMIT) __trap();
        if (XE == 1) BAR_SYNC(B_P, N_P); else if (XE == 2) BAR_SYNC(B_Q, 288); else if (s) BAR_SYNC(B_R, 320); else BAR_SYNC(B_Q, 288);
        if (s < 62) { X_LOAD(s + 2, 0, 0); X_LOAD(s + 2, 1, 0); X_LOAD(s + 2, 0, 1); X_LOAD(s + 2, 1, 1); }
        if (s >= 7) {
          const uint32_t zo = b * 160 + l16;
          if (l16 < 160) CONSUME(exch_b128(xc + AR_OFF + AR_ROW(zo >> 7) * 1024 + (zo & 127) + ((s + 1) & 7) * 128, 0, 0, 0, 0).x);
          __syncwarp();
        }
        if (s < 62) { mbar_wait(sb + BARS + 64, s & 1); mbar_wait(sb + BARS + 72, s & 1); }
        BAR_ARRIVE(B_S, 416);
        vm_stage(s);
        if (!AV) BAR_ARRIVE(B_O, 416);
        BAR_SYNC(B_W, 384);
        FENCE_ASYNC_SMEM();
        asm volatile("{.reg .pred p; elect.sync _|p, 0xffffffff; @p cp.reduce.async.bulk.tensor.3d.global.shared::cta.add.bulk_group [%0,{%1,%2,%4}],[%3];}"
                     ::"l"(&mp.ari), "r"((s & 7) * 64), "r"(AR_R(j)), "r"(sb + ARO), "r"(AR_P(j)) : "memory");
        BULK_COMMIT();
        asm volatile("st.relaxed.gpu.global.u32 [%0],%1;" ::"l"(g_tm + (s & 1) * 128 + b), "r"(gtime()) : "memory");
        TS(3);
        BULK_WAIT_READ(0);
      }
      if (!XE) BAR_ARRIVE(B_R, 320);
    } else if (iw == 1) {
      const uint32_t pc = sb + MEM + (lane >> 2) * 640 + (lane & 3) * 144 + (lane & 12), pd = sb + MEM + (lane & 15) * 640 + 576 + (lane & 3) * 16 + (lane & 12);
      uint32_t T = 0, par = 0;
      int est = dA;
#pragma unroll 1
      for (int s = 0; s < 63; s++) {
        if (s) {
          const uint4 tm = ldg_rlx4((const char*)g_tm + ((s + 1) & 1) * 512 + l16);
          const int t0 = tm.x - T, t1 = tm.y - T, t2 = tm.z - T, t3 = tm.w - T;
          const int e = max(dF + (__reduce_add_sync(~0u, (t0 + t1) + (t2 + t3)) >> 7), dV + __reduce_max_sync(~0u, max(max(t0, t1), max(t2, t3))));
          if (s > 1) est += max(min(e >> 2, dP), -dP);
          T += (s == 1 || e > dM ? e : 0) + est;
        }
        vm_stage(s);
        BAR_SYNC(B_W, 384);
        SCHED_FENCE(70);
        const uint32_t tW = gtime();
        if (s == 0) T = tW + 800;
        const uint32_t te = tW + min(max((int)(T - tW), dD), 2000);
        while ((int)(gtime() - te) < 0) {}
        TS(7);
        int it = 0;
        while (true) {
          ar_fetch(sb + MEM, &mp.ari, s & 7, a, sb + BARS + 112);
          mbar_wait(sb + BARS + 112, par);
          par ^= 1;
          const uint32_t n0 = lds1(pc), n1 = lds1(pc + 5120), n2 = lds1(pd);
          if (!__any_sync(~0u, (tagbad(n0, n1, 0x42004200) | (n2 ^ 0x42004200)) != 0)) break;
          RP(0);
          if (++it > SPIN_LIMIT) __trap();
        }
        BAR_ARRIVE(B_R, N_R);
        TS(11);
      }
    } else {
#define V_LOAD(n) do { if (lane == 0) mbar_expect(sb + BARS + 8, 8192); __syncwarp(); \
        if (lane < 16) bulk_ld(sb + ((lane & 2) ? VX1 : VX0) + (lane & 1) * 2048 + (lane >> 2) * 512, \
                               xc + h * 262144 + V_RING(n) + (lane >> 2) * XC + X_VX(lane & 3), 512, sb + BARS + 8); __syncwarp(); } while (0)
      uint32_t src = L16 + PK + (iw & 1) * 2048;
#define qd (L16 + (lane >> 4) * 256 + QT + (iw & 1) * 1024)
#define vd (LO(xc) + h * 262144 + j * XC + (iw & 1) * 2048 + l16)
#define FINISH [&](int n, int m) { \
_Pragma("unroll") \
        for (int i = 1; i >= 0; i--) { \
          const uint32_t p = src + m * 4096 + i * 512; \
          uint4 u = lds4(p); \
          const uint4 w = lds4(p + 1024), y = lds4(p + 12288), z = lds4(p + 13312); \
          u = make_uint4(sum4bf(u.x, w.x, y.x, z.x), sum4bf(u.y, w.y, y.y, z.y), sum4bf(u.z, w.z, y.z, z.z), sum4bf(u.w, w.w, y.w, z.w)); \
          if (m == 2) stg_b128(mkp(vd ^ V_RING(n), HI(xc)) + i * 512, (u.x & ~1u) | V_TAG(n), u.y, u.z, u.w); \
          else stsm4(qd + (n & 1) * 4096 + m * 2048 + i * 256, u.x, u.z, u.y, u.w); \
          SCHED_FENCE(71 + m * 2 + i); \
        } \
      }
#pragma unroll 1
      for (int n = 0; n < 64; n++) {
        src = PIN(src);
        b = __shfl_sync(~0u, lds1(sb + PACE + 24), 0);
        const uint32_t L16 = src - PK - (iw & 1) * 2048;
        auto finish = FINISH;
        if (n < 2) { if (n) BAR_SYNC(B_X, 320); else BAR_SYNC(B_C, 448); }
        mbar_wait(sb + BARS + 16, n & 1);
        finish(n, 0);
        __syncwarp();
        if (lane == 0) mbar_arrive_cl(mapa(sb, a ^ 1) + BARS + 24);
        if (n > 1) BAR_SYNC(B_K, 320);
        mbar_wait(sb + BARS + (KVO ? 32 : 40), n & 1);
        finish(n, 2 - !!KVO);
        if (n > 1) BAR_SYNC(B_X, 320);
        mbar_wait(sb + BARS + (KVO ? 40 : 32), n & 1);
        finish(n, 1 + !!KVO);
        BAR_SYNC(B_T, 64);
        if (lane == 0) {
          if (iw == 2 && n < 63) { mbar_expect(sb + BARS + 16, 4096); mbar_expect(sb + BARS + 32, 4096); mbar_expect(sb + BARS + 40, 4096); }
          mbar_arrive_cl(mapa(sb, a ^ 1) + BARS + 80);
        }
        __syncwarp();
        if (n) {
          vm_stage(n - 1);
          BAR_SYNC(B_W, 384);
        } else {
          BAR_SYNC(B_C, 320);
        }
        if (iw == 2) V_LOAD(n);
      }
#undef qd
#undef vd
    }
    { ROLE_REFRESH }
    vm_stage(63);
  } else {
    asm volatile("setmaxnreg.dec.sync.aligned.u32 %0;" ::"n"(RA_));
    if (blockIdx.x >= 128) { if (threadIdx.x == 256) rec_prefetch((const char*)wmod, w1, (const char*)x, wo); return; }
    ROLE_VARS
    uint32_t L16 = __shfl_sync(~0u, sb + (tid & 31) * 16, tid & 31);
    const uint32_t ts = gtime();
    uint2 m0[8];
#pragma unroll
    for (int r = 0; r < 8; r++) m0[r] = *(const uint2*)(mem0 + r * 1024 + a * 512 + (tid - 256) * 4);
    if (wid == 9) {
#pragma unroll 1
      for (int i = b * 80 + (tid & 31); i < b * 80 + 80; i += 32) ((uint4*)(xc + AR_OFF))[AR_ROW(i >> 6) * 64 + (i & 63)] = make_uint4(0, 0, 0, 0);
      if (b == 0) g_fin = 0;
      FENCE_ASYNC();
      __syncwarp();
      if (tid == 288) red_rlx(&g_hcnt);
    }
    if (tid == 256) {
      const int col = h * 128 + bb * 64;
#pragma unroll 1
      for (int c = 0, w = 0; w < 12; c++) {
#pragma unroll 1
        for (; w <= c - (c < WC0 ? 2 : 3); w++) {
          mbar_wait(sb + PACE + (w % 3) * 8, (w / 3) & 1);
          PT(18 + w);
          if (w == 3) asm volatile("mbarrier.arrive.shared.b64 _,[%0];" ::"r"(sb + BARS + 88) : "memory");
        }
        const uint32_t mb = sb + PACE + (c % 3) * 8;
        if (c >= 12 && c < 12 + WPE) tma2d_pf(&mp.wo, j * 256 + (c - 12) * 64, h * 128);
        if (c >= 12) continue;
        mbar_expect(mb, 16384);
        if (c < 8) tma2d(sb + (c >> 2) * XB + (c & 3) * 16384, (c & 4) ? &mp.wk : &mp.wq, col, a * 512 + (c & 3) * 128, mb);
        else
#pragma unroll 1
          for (int i = (c & 1) * 8; i < (c & 1) * 8 + 8; i++) {
            const int w = (c - 8) >> 1;
            tma2d(i < NVR ? sb + MEM + (w * NVR + i) * 2048 : sb + WVS + (w * NVS + i - NVR) * 2048, &mp.wv, col, a * 512 + w * 256 + i * 16, mb);
          }
      }
      asm volatile("mbarrier.arrive.shared.b64 _,[%0];" ::"r"(wbar) : "memory");
      for (int i = 0; i < 3; i++) asm volatile("mbarrier.inval.shared.b64 [%0];" ::"r"(sb + PACE + i * 8) : "memory");
    }
    __syncwarp();
    asm volatile("barrier.cluster.wait.aligned;" ::: "memory");
    CLUSTER_SYNC();
#pragma unroll 4
    for (int i = 0; i < 16; i++) {
      const uint4 v = lds4(L16 + WO + 32768 + iw * 8192 + i * 512);
      sts4(L16 + XB + iw * 8192 + i * 512, v.x, v.y, v.z, v.w);
    }
#pragma unroll
    for (int i = 0; i < 4; i++) {
      const int k = (tid - 256) * 4 + i, m = (k >> 3) & 3, r = k & 7;
#define M0W(r) __byte_perm((i & 2) ? m0[r].y : m0[r].x, (i & 2) ? m0[r + 1].y : m0[r + 1].x, (i & 1) ? 0x7632 : 0x5410)
      sts4(sb + MEM + (k >> 5) * 640 + (r == m ? 512 : m * 128) + r * 16, M0W(0), M0W(2), M0W(4), M0W(6));
    }
#pragma unroll 1
    for (int i = tid - 256; i < 192; i += 128) {
      const uint32_t c = i < 128 ? 0x42004200 : 0x3f803f80;
      sts4(sb + MEM + (i >> 3) * 640 + ((i & 7) < 4 ? (i & 7) * 144 : 512 + (i & 7) * 16), c, c, c, c);
    }
    static_assert(ARO == MEM + 16 * 640, "counters");
    FENCE_ASYNC_SMEM();
    BAR_ARRIVE(B_C, 448);
    if (WPF && tid == 256) {
      wait_time(ts + WPF);
#pragma unroll 1
      for (int c = WPE; c < 4; c++) tma2d_pf(&mp.wo, j * 256 + c * 64, h * 128);
    }
    __syncwarp();
#define pr (L16 + SC)
    {
      const int lim = j * 8 + iw * 2 - (lane & 7) - (lane & 8) * 2;
      const bool mk = L16 & 256;
      const int rw = lane >> 2;
      sts4(L16 + TA + iw * 512,
           iw != 2 ? L16 + KT + (iw & 1) * 256 + (lane >> 4) * 256 : sb + RK + (L16 & 0x80) * 2 + ((L16 >> 1) & 0x80) + (L16 & 0x70),
           L16 + QT + (lane >> 3) * 384, sb + SC + min(lane >> 3, 2) * 256 + (L16 & 0x70) + iw * 4, L16 + (lane >> 4) * 256 + QT + (iw >> 1) * 1024 + (iw & 1) * 256);
      sts4(L16 + TA + 2048 + iw * 512, mk ? 0u : (lim < 0 ? 0xfc00u : 0u) | (lim < -1 ? 0xfc000000u : 0u),
           mk ? 0xfc00fc00u : (lim < 8 ? 0xfc00u : 0u) | (lim < 7 ? 0xfc000000u : 0u),
           ((h * 2 + (iw >> 1)) * 1024 + (j * 8 + rw) * 8 + (((iw & 1) * 4 + (lane & 3)) ^ rw)) * 16, sb + OT + iw * 512 + (L16 & 0x70) * 4 + ((L16 >> 3) & 0x30));
    }
    {
      const uint32_t xh = LO(xc) + h * 262144, xs = xh + X_SC + iw * 1024 + min(lane, 16 + (lane & 7)) * 8;
      sts4(L16 + TA + 4096 + iw * 512, xh + X_SC + j * 256 + iw * 64 + lpub, xs, dS, iw != 2 ? 0 : U_(SCS));
      sts1(L16 + TA + 12 + iw * 512, xs + X_TOK + j * 4096);
    }
    uint32_t tA = L16 + TA + iw * 512;
#define tw (tA - L16 != TA + 1024)
#define XP_(lo) mkp(lo, HI(xc))
    auto publish = [&](char* d, const uint2& w) { stg_b64(d, w.x, w.y); };
    BAR_SYNC(B_P, N_P);
    for (int s = 0; s < 64; s++) {
      asm volatile("" : "+r"(L16), "+r"(tA));
      const uint32_t tag = ((s >> 1) + 1) & 1, ring = (s & 1) * X_RING;
      const uint4 t0 = lds4(tA);
      const uint4 tx = lds4(tA + 4096);
      const uint32_t xo = tx.x ^ ring, xs = tx.y ^ ring;
      const float gm = F_(tx.w);
      const uint32_t qA = t0.y + (ring >> 5);
      uint32_t c0;
      uint2 ts[4];
      uint4 v[4];
      uint32_t af[2][4], qt[4][4];
      {
        const uint32_t aA = t0.x + (tw ? ring >> 5 : 0);
        uint32_t ql[2][4], qr[2][4];
        uint2 pw_;
        float c[4] = {0, 0, 0, 0}, d[4] = {0, 0, 0, 0};
        if (s == PDS) asm volatile("griddepcontrol.launch_dependents;");
#pragma unroll
        for (int i = 0; i < 4; i++) ldsm4t(qt[i], qA + i * 128);
        mbar_wait(sb + BARS + 8, s & 1);
        TS(4);
        BAR_SYNC(B_E, 256);
#define PACK(c) make_uint2(pkh(fmaf(c[2], gm, c[0] * SCS), fmaf(c[3], gm, c[1] * SCS), tag), pkh(c[2] * SCS, c[3] * SCS, tag))
#define SMMA(x, t, q, i) mma16(x, af[t][0], af[t][1], af[t][2], af[t][3], q[t][i], q[t][i + 1])
        ldsm4t(ql[0], L16 + RQ); ldsm4t(ql[1], L16 + RQ + 1024); ldsm4t(af[0], aA); ldsm4t(af[1], aA + 1024);
        CONSUME(xo);
#define QSUM(t, i) addbf(addbf(ql[t][i], ql[t][i + 2]), addbf(qr[t][i], qr[t][i + 2]))
#define STAIL mma16(c, af[0][0], af[0][1], af[0][2], af[0][3], QSUM(0, 0), QSUM(0, 1)); mma16(d, af[1][0], af[1][1], af[1][2], af[1][3], QSUM(1, 0), QSUM(1, 1));
        if (tw) {
          mbar_wait(sb + BARS, s & 1);
          TS(8);
          ldsm4t(qr[0], L16 + RQ + 512); ldsm4t(qr[1], L16 + RQ + 1536);
          STAIL
          pw_ = make_uint2(pkh(c[0] + d[0], c[1] + d[1], tag), pkh(c[2] + d[2], c[3] + d[3], tag));
        } else {
          uint32_t ar[2][4];
          mbar_wait(sb + BARS, s & 1);
          ldsm4t(qr[0], L16 + RQ + 512); ldsm4t(ar[0], aA + 512); ldsm4t(qr[1], L16 + RQ + 1536); ldsm4t(ar[1], aA + 1536);
#pragma unroll
          for (int i = 0; i < 8; i++) af[i >> 2][i & 3] = addbf(af[i >> 2][i & 3], ar[i >> 2][i & 3]);
          STAIL
          pw_.x = pw_.y = pkh((c[0] + c[2]) + (d[0] + d[2]), (c[1] + c[3]) + (d[1] + d[3]), tag);
        }
        publish(XP_(xo), pw_);
        c0 = clk() + tx.z;
        TS(1);
      }
      uint2 r[4];
      bool vbad;
      uint32_t xm;
      uint4 vn[2];
#define TOKS(i) { float e0[4] = {0, 0, 0, 0}, e1[4] = {0, 0, 0, 0}; \
        mma16(e0, af[0][0], af[0][1], af[0][2], af[0][3], qt[i][0], qt[i][1]); mma16(e1, af[0][0], af[0][1], af[0][2], af[0][3], qt[i + 1][0], qt[i + 1][1]); \
        mma16(e0, af[1][0], af[1][1], af[1][2], af[1][3], qt[i][2], qt[i][3]); mma16(e1, af[1][0], af[1][1], af[1][2], af[1][3], qt[i + 1][2], qt[i + 1][3]); \
        ts[i] = PACK(e0); ts[i + 1] = PACK(e1); }
      {
        float e[4][4];
#pragma unroll
        for (int i = 0; i < 4; i++) {
          e[i][0] = e[i][1] = e[i][2] = e[i][3] = 0.f;
          mma16(e[i], af[0][0], af[0][1], af[0][2], af[0][3], qt[i][0], qt[i][1]);
        }
#pragma unroll
        for (int i = 0; i < 4; i++) mma16(e[i], af[1][0], af[1][1], af[1][2], af[1][3], qt[i][2], qt[i][3]);
        SCHED_FENCE(55);
        if (s < 63) BAR_ARRIVE(B_S, 416);
        SCHED_FENCE(58);
        v[0] = lds4(tA + (VX0 - TA)); v[1] = lds4(tA + (VX0 - TA) + 2048); v[2] = lds4(tA + (VX1 - TA)); v[3] = lds4(tA + (VX1 - TA) + 2048);
#pragma unroll
        for (int i = 0; i < 4; i++) ts[i] = PACK(e[i]);
        vbad = anybad(v[0].x, v[1].x, v[2].x, v[3].x, V_TAG(s));
        if (AV) { xm = (xs & ~0x1ffffu) + X_VM(0) + ((tA - L16 - TA) << 5) + (l16 >> 1); CONSUME(xm); }
        while ((int)(clk() - c0) < 0) {}
        TS(5);
#pragma unroll
        for (int u = 0; u < 4; u++) r[u] = ldg_b64(XP_(xs) + u * 256);
        if (!AV) BAR_ARRIVE(B_S2, 256);
      }
      SCHED_FENCE(56);
      uint32_t kk;
      float4 e = softmax2<false>(r, 0, 0, kk);
      if (AV) {
        const char* pm_ = XP_(xm + (kk & dZ));
#pragma unroll
        for (int u = 0; u < 2; u++) { const uint2 m0 = ldg_b64(pm_ + u * 2048), m1 = ldg_b64(pm_ + u * 2048 + 256); vn[u] = make_uint4(m0.x, m0.y, m1.x, m1.y); }
      }
      if (__builtin_expect(anybad(r[0].x, r[0].y, r[1].x, r[1].y, r[2].x, r[2].y, r[3].x, r[3].y, tag ^ (kk & dZ)), 0)) {
        int it = 0;
        if (s > 8) sts1(tA + 4096 + 8, min(lds1(tA + 4096 + 8) + dX, 500));
        do {
          RP(1);
          if (++it > SPIN_LIMIT) __trap();
#pragma unroll
          for (int u = 0; u < 4; u++) r[u] = ldg_b64(XP_(xs) + u * 256);
        } while (BADS(r));
        e = softmax2<false>(r, 0, 0, kk);
      }
      sts1(t0.z, pk(e.x, e.y)); sts1(t0.z + 128, pk(e.z, e.w));
#pragma unroll
      for (int i = 0; i < 4; i++) publish(XP_(xo) + X_TOK + i * 4096, ts[i]);
      TS(6);
      if (s < 63) BAR_SYNC(B_V, N_V); else BAR_SYNC(B_V, N_V - 256);
      uint32_t O[4];
      {
        uint32_t p[4], pm;
        ldsm4t(p, pr);
        asm volatile("ldmatrix.sync.aligned.m8n8.x1.trans.shared.b16 {%0},[%1];" : "=r"(pm) : "r"(pr + 512) : "memory");
        if (!AV) { vn[0] = lds4(tA + (VN - TA)); vn[1] = lds4(tA + (VN - TA) + 2048); }
        pv_mem(p, pm, v, vn, O);
        if (__builtin_expect(vbad || ((HV || AV) && anybad(vn[0].x, vn[0].z, vn[1].x, vn[1].z, tag)), 0)) {
          int it = 0;
          const uint32_t xv = LO(xc) + (lds1(sb + PACE + 24) >> 2) * 262144 + ((tA - L16 - TA) >> 9) * XC;
          do {
            RP(2);
            if (++it > SPIN_LIMIT) __trap();
#pragma unroll
            for (int u = 0; u < 4; u++) v[u] = ldg_b128(XP_((xv + l16) ^ V_RING(s)) + X_VX(u));
          } while (anybad(v[0].x, v[1].x, v[2].x, v[3].x, V_TAG(s)) || ((HV || AV) && anybad(vn[0].x, vn[0].z, vn[1].x, vn[1].z, tag)));
          pv_mem(p, pm, v, vn, O);
        }
      }
      stsm4(tA + (OB - TA), O[0], O[1], O[2], O[3]);
      if (s < 63) BAR_ARRIVE(B_O, N_O);
      TS(2);
      c0 = clk() + (LS && s == 63 ? 0 : dG);
      SCHED_FENCE(60);
      if (tA == sb + TA) mbar_expect(sb + BARS, 2048);
      const uint32_t vs[4] = {addbf(vn[0].x, vn[0].z), addbf(vn[0].y, vn[0].w), addbf(vn[1].x, vn[1].z), addbf(vn[1].y, vn[1].w)};
      {
        const char* xt = XP_(lds1(tA + 12) ^ ring);
        const uint2 t1 = lds2u(tA + 2048);
        const uint32_t pw = lds1(tA + 8);
        uint2 rt[4];
        CONSUME(LO(xt) ^ t1.x ^ pw);
        while ((int)(clk() - c0) < 0) {}
        int it = 0;
        do {
          if (++it > SPIN_LIMIT) __trap();
#pragma unroll
          for (int u = 0; u < 4; u++) rt[u] = ldg_b64(xt + u * 256);
        } while (BADS(rt));
        uint32_t kt;
        const float4 et = softmax2<true>(rt, t1.x, t1.y, kt);
        sts1(pw + 1024, pk(et.x, et.y)); sts1(pw + 1024 + 128, pk(et.z, et.w));
      }
      s = PIN(s);
      BAR_SYNC(B_SC, 128);
      {
        uint32_t Ot[4], p[4], pm;
        const uint2 t2 = lds2u(tA + 2048 + 8);
        ldsm4t(p, pr + 1024);
        asm volatile("ldmatrix.sync.aligned.m8n8.x1.trans.shared.b16 {%0},[%1];" : "=r"(pm) : "r"(pr + 1024 + 512) : "memory");
        char* od = (char*)g_O + ((s >> 2) * 1048576 + (s & 3) * 4096) + t2.x;
        CONSUME(LO(od) ^ HI(od) ^ pm ^ p[3]);
        TS(9);
        if (s < 62) BAR_SYNC(B_P, N_P);
        pv_tok(p, pm, v, vs, Ot);
        asm volatile("stmatrix.sync.aligned.m8n8.x4.trans.shared.b16 [%0],{%1,%2,%3,%4};" ::"r"(t2.y), "r"(Ot[0]), "r"(Ot[1]), "r"(Ot[2]), "r"(Ot[3]) : "memory");
        __syncwarp();
        *(uint4*)od = lds4(tA + (OT - TA));
      }
    }
    FENCE_ASYNC();
    BAR_SYNC(B_SC, 128);
    if (tA == sb + TA) red_rlx(&g_fin);
  }
  __syncwarp();
  CLUSTER_SYNC();
  PH(5); RS(2);
}
#undef wg
#undef iw
#undef h
#undef j
#undef a
#undef bb
#undef oi
#undef owner
#undef ownv
#undef vfin
#undef pr
#undef PIN
#undef XP_
#undef tw
#undef is7
#undef REFRESH
#undef lane
#undef l16
#undef lrow
#undef lar
#undef lpub

namespace ffn {
constexpr uint32_t BR = 98304;
constexpr uint32_t STG = 196608;
constexpr uint32_t PRM = 229376;
constexpr uint32_t BARS = PRM + 2816;
constexpr uint32_t SMEM = BARS + 18 * 8;
}
#define Y_TILE(rb, kt) (((ALIAS & 1) ? g_h : g_h2) + ((rb) * 16 + (kt)) * 1024)
#define U_TILE(rb, kt) ((ALIAS & 2) ? g_O + ((rb) * 64 + (kt)) * 1024 : g_U + ((rb) * 56 + (kt)) * 1024)
struct FfnMaps { CUtensorMap wo, w1a, w1b, w2, x, out; };

template <int N>
__device__ __forceinline__ void wg_ss(float* d, uint64_t a, uint64_t b, int sd) {
  if (N == 128) wgmma_ss_n128(d, a, b, sd);
  if (N == 192) wgmma_ss_n192(d, a, b, sd);
}
template <int N>
__device__ __forceinline__ void acc_fence(float* d) {
#pragma unroll
  for (int i = 0; i < N; i++) asm volatile("" : "+f"(d[i])::"memory");
}
#define UNPK8(d, v) do { (d)[0] = blo(v.x); (d)[1] = bhi(v.x); (d)[2] = blo(v.y); (d)[3] = bhi(v.y); (d)[4] = blo(v.z); (d)[5] = bhi(v.z); (d)[6] = blo(v.w); (d)[7] = bhi(v.w); } while (0)
struct FfnPipe {
  uint32_t full, emp, ph, aoff;
  int st, sB, prev;
  bool leader;
  template <int N>
  __device__ __forceinline__ void issue(float* acc, bool first, uint32_t a = 0) {
    mbar_wait(full + st * 8, ph);
    const uint64_t da = mkdesc((a ? a : 1024 + st * 16384) + aoff, 16, 1024), db = mkdesc(1024 + ffn::BR + sB * (N * 128), 8192, 1024);
    WG_FENCE();
#pragma unroll
    for (int j = 0; j < ((FDB & 1) ? 1 : 4); j++) wg_ss<N>(acc, da + j * 2, db + j * 128, j || !first);
    WG_COMMIT();
    if (++sB == 768 / N) sB = 0;
  }
  __device__ __forceinline__ void release() { if (leader) mbar_arrive(emp + prev * 8); }
  __device__ __forceinline__ void next() { prev = st; if (++st == 6) { st = 0; ph ^= 1; } }
  __device__ __forceinline__ void retire() { WG_WAIT(1); release(); next(); }
};
__device__ __forceinline__ float gelu_h(float hx) {
  float u = hx * fmaf(hx * hx, 8.f * 0.0356774081f, 2.f * 0.7978845608f), t;
  if (FDB & 4) return hx;
  if (FDB & 2) t = u; else
  asm("tanh.approx.f32 %0,%1;" : "=f"(t) : "f"(u));
  return fmaf(hx, t, hx);
}
struct FfnEpi {
  uint32_t st2, cc, flip, staged, l0;
  uint2 c;
  float n0, n1, s0, s1;
  __device__ __forceinline__ void flush(uint32_t r) {
    __syncwarp();
    asm volatile("{.reg .pred p; setp.ne.u32 p,%1,0; @p mbarrier.arrive.shared.b64 _,[%0];}" ::"r"(staged + (flip >> 11)), "r"(l0 & r) : "memory");
    flip ^= r << 14;
  }
  __device__ __forceinline__ void half(const float* d, int J, int r) {
#define PRE(i, n, c1, c2) gelu_h(fmaf(r ? d[4 + i] : d[i], i < 2 ? s0 : s1, fmaf(n, c1, c2)))
    asm volatile("stmatrix.sync.aligned.m8n8.x2.shared.b16 [%0],{%1,%2};" ::"r"((st2 ^ ((J & 3) * 32 + r * 16)) + flip),
                 "r"(pk(PRE(0, n0, blo(c.x), blo(c.y)), PRE(1, n0, bhi(c.x), bhi(c.y)))), "r"(pk(PRE(2, n1, blo(c.x), blo(c.y)), PRE(3, n1, bhi(c.x), bhi(c.y)))) : "memory");
#undef PRE
    if ((J & 3) == 3) flush(r);
    cc += r ? 56 : 8;
    c = lds2u(cc);
  }
};

__global__ void __launch_bounds__(384, 1)
k_ffn(const __grid_constant__ FfnMaps mp, const bf16* __restrict__ b2) {
  using namespace ffn;
  extern __shared__ __align__(1024) char smem[];
  const uint32_t sb = (uint32_t)__cvta_generic_to_shared(smem);
  if (sb != 1024) __trap();
  const int tid = threadIdx.x, lane = tid & 31, wg = __shfl_sync(~0u, tid >> 7, 0);
  const uint32_t full = sb + BARS, emp = full + 48, xbar = full + 96, staged = full + 104, tile = full + 136;
  uint32_t fin = 0;
  if (tid >= 288 && tid < 320) fin = ld_acq(&g_fin);
  if (tid < 32) {
    unsigned sm, v = 0;
    asm("mov.u32 %0,%%smid;" : "=r"(sm));
    if (tid == 0) {
      v = atomicExch(&g_slot[sm & 255], 0);
      for (int i = 0; i < 6; i++) { mbar_init(full + i * 8, 1); mbar_init(emp + i * 8, 2); }
      mbar_init(xbar, 2);
      for (int i = 0; i < 2; i++) { mbar_init(staged + i * 8, 8); mbar_init(staged + 16 + i * 8, 1); }
      FENCE_ASYNC_SMEM();
    }
    v = __shfl_sync(~0u, v, 0);
    if (!v) {
      wait_cnt(&g_fin, 128);
      for (int it = 0; !v; it++) {
        const uint4 a = ldg_rlx4(g_slot + tid * 8), b = ldg_rlx4(g_slot + tid * 8 + 4);
        const uint32_t open = __ballot_sync(~0u, a.x | a.y | a.z | a.w | b.x | b.y | b.z | b.w);
        if (!open) break;
        if (it < 16) { __nanosleep(500); continue; }
        if (tid == __ffs(open) - 1) v = atomicExch(&g_slot[tid * 8 + (a.x ? 0 : a.y ? 1 : a.z ? 2 : a.w ? 3 : b.x ? 4 : b.y ? 5 : b.z ? 6 : 7)], 0);
        v = __shfl_sync(~0u, v, __ffs(open) - 1);
      }
    }
    if (tid == 0) sts1(tile, v);
  }
  if (tid == 256) asm volatile("prefetch.tensormap [%0];" ::"l"(&mp.wo) : "memory");
  __syncthreads();
  const int bid = __shfl_sync(~0u, lds1(tile), 0) - 1;
  if (bid < 0) return;
  PH(6);
  FT(1);
  const int rb = bid >> 3, nb = bid & 7;
  unsigned* cnt = g_cnt + rb * 128;
  if (wg == 2) {
    asm volatile("setmaxnreg.dec.sync.aligned.u32 " FRP ";");
    const int pw = __shfl_sync(~0u, (tid >> 5) & 3, 0);
    uint32_t ws = emp, wp = 1, fs = full;
    auto wait_free = [&]() { mbar_wait_q(ws, wp); ws += 8; if (ws == emp + 48) { ws = emp; wp ^= 1; } };
    auto step = [&]() { fs += 8; if (fs == full + 48) fs = full; };
#define K3(c) ((0x65230 >> (c) * 4) & 7)
#define KC(k) ((k) < 2 ? nb * 2 + (k) : (k) < 9 ? ((k) - 2 + ((k) - 2 >= nb)) * 2 : ((k) - 9 + ((k) - 9 >= nb)) * 2 + 1)
    if (pw == 0) {
      uint32_t d = sb + BR + 32768;
      auto put = [&](const CUtensorMap* m, int k, int c) {
        e_expect_tma3d(d, m, k * 64, c, fs, 32768);
        step();
        d += 16384;
        if (d == sb + STG) d = sb + BR;
      };
      int n = 0;
      auto stage_free = [&]() { if (!(n & 7) && n < 56) mbar_wait_q(staged + 16 + (n & 8), (n >> 4) & 1); n++; };
      auto align = [&]() {
        if (ALN && !((n - 1) & 7) && ((ALN >> ((n - 1) >> 3)) & 1)) {
          unsigned* c = g_cnt + 64 + ((n - 1) >> 3);
          if (lane == 0) red_rlx(c);
          for (int it = 0; ldg_rlx1(c) < 128 && it < 64; it++) {}
        }
      };
      FTP(3);
#pragma unroll 1
      for (int k = 0; k < 66; k++) { wait_free(); if (k < 64) put(&mp.wo, k, nb * 2); }
#pragma unroll 1
      for (int k = 0; k < 16; k++) {
        const int kt = KC(k);
        wait_free();
        e_expect_tma3d(sb + BR + (k & 3) * 24576, &mp.w1b, kt * 64, nb * 7, fs, k < 2 ? 24576 : 40960);
        step();
      }
#pragma unroll 1
      for (int k = 0; k < 32; k++) { stage_free(); if (k != 5 && k != 6) wait_free(); align(); put(&mp.w1a, k & 15, nb * 7 + 3 + (k >> 4) * 2); }
#pragma unroll 1
      for (int c = 0; c < 5; c++)
#pragma unroll 1
        for (int k = K3(c), i = 0; k < 56; k += c < 2 && (i ^= 1) ? 1 : c < 2 ? 6 : 7) { stage_free(); wait_free(); align(); put(&mp.w2, k, nb * 2); }
    } else if (pw == 1) {
      FTP(5);
      if (fin < 128) wait_cnt(&g_fin, 128);
      FTP(6);
      uint32_t d = sb;
      auto put = [&](const uint4* A, bool ld) {
        wait_free();
        if (ld) e_bulk_ld(d, A, 16384, fs);
        step();
        d += 16384;
        if (d == sb + BR) d = sb;
      };
      const uint4* A = g_O + rb * 65536;
#pragma unroll 1
      for (int k = 0; k < 66; k++) put(A + k * 1024, k < 64);
      A = Y_TILE(rb, 0);
      uint32_t ready = 0;
#pragma unroll 1
      for (int k = 2; k < 48; k++) {
        const int kt = k < 16 ? KC(k) : k & 15;
        for (int it = 0; !(ready >> ((kt >> 1) + (kt & 1) * 8) & 1); it++) {
          ready = __ballot_sync(~0u, ldg_rlx1(cnt + (lane & 7)) & ((lane & 8) ? 1 : 0x10000));
          if (it > SPIN_LIMIT) __trap();
        }
        if (k == 2) FTP(75);
        put(A + kt * 1024, true);
      }
      A = U_TILE(rb, 0);
#pragma unroll 1
      for (int c = 0; c < 5; c++) {
        for (int it = 0; ldg_rlx1(cnt + 32 + c) < 8; it++) if (it > SPIN_LIMIT) __trap();
#pragma unroll 1
        for (int k = K3(c), i = 0; k < 56; k += c < 2 && (i ^= 1) ? 1 : c < 2 ? 6 : 7) put(A + k * 1024, true);
      }
    } else if (pw == 2) {
      for (int i = 0; i < XDL; i++) {
        mbar_wait_q(emp, i & 1);
        if (XPF && i == 1 && lane < 2) tma2d_pf(&mp.x, nb * 128 + lane * 64, rb * 128);
      }
      if (lane == 0) {
        mbar_expect(xbar, 32768);
        tma2d(sb + STG, &mp.x, nb * 128, rb * 128, xbar);
        tma2d(sb + STG + 16384, &mp.x, nb * 128 + 64, rb * 128, xbar);
      }
      asm volatile("griddepcontrol.wait;" ::: "memory");
      if (lane < 16) g_modp[bid * 16 + lane] = make_uint4(0, 0, 0, 0);
      if (lane >= 16 && bid == 0) { g_hcnt = 0; g_mcnt = 0; g_hf[lane & 3] = 0; }
      if (lane == 0) {
#pragma unroll 1
        for (int g = 1; g < 9; g++) {
          if (g == 1) mbar_wait(staged + 8, 0); else { mbar_wait_q(staged + (g & 1) * 8, (g >> 1) & 1); FENCE_ASYNC_SMEM(); }
          bulk_st(g == 1 ? Y_TILE(rb, nb * 2 + 1) : U_TILE(rb, nb * 7 + ((0x652431000ull >> g * 4) & 7)), sb + STG + (g & 1) * 16384, 16384);
          BULK_COMMIT();
          if (g != 2 && g != 4) { BULK_WAIT(0); red_rlx(g == 1 ? cnt + nb : cnt + 32 + (g < 6 ? g >> 2 : g - 4)); }
          BULK_WAIT_READ(0);
          mbar_arrive(staged + 16 + (g & 1) * 8);
        }
      }
    } else {
      const uint32_t prm = sb + PRM, pp = prm + (lane >> 3) * 64 + (lane & 1) * 32 + (lane & 6) * 2;
      const uint2 v2 = ((const uint2*)(b2 + nb * 128))[lane];
      sts1(pp + 768, v2.x); sts1(pp + 784, v2.y);
      asm volatile("griddepcontrol.wait;" ::: "memory");
      const float4* md = (const float4*)(g_mod + nb * 128) + lane;
      { const float4 ga = md[512]; sts1(pp, pk(ga.x, ga.y)); sts1(pp + 16, pk(ga.z, ga.w)); }
      { const float4 cb = md[1024]; sts1(pp + 256, pk(1.f + cb.x, 1.f + cb.y)); sts1(pp + 272, pk(1.f + cb.z, 1.f + cb.w)); }
      { const float4 gb = md[1280]; sts1(pp + 512, pk(gb.x, gb.y)); sts1(pp + 528, pk(gb.z, gb.w)); }
#pragma unroll 1
      for (int i = lane; i < 112; i += 32) { const uint4 c = g_cc[nb * 112 + i]; sts4(prm + 1024 + i * 16, c.x, c.y, c.z, c.w); }
      __syncwarp();
      if (lane == 0) {
        mbar_arrive(xbar);
        mbar_wait(staged, 0);
        bulk_st(Y_TILE(rb, nb * 2), sb + STG, 16384);
        BULK_COMMIT(); BULK_WAIT(0);
        asm volatile("red.relaxed.gpu.global.add.u32 [%0],0x10000;" ::"l"(cnt + nb) : "memory");
        mbar_arrive(staged + 16);
      }
      __syncwarp();
      mbar_wait_q(staged + 24, 0);
      mbar_wait_q(emp + 40, 0);
#pragma unroll 1
      for (int i = 0; i < 4; i++) {
        const uint4* sp = g_stat + (rb * 128 + i * 32 + lane) * 4;
        uint4 v[4];
        for (int it = 0;; it++) {
          uint32_t m = 0;
#pragma unroll
          for (int u = 0; u < 4; u++) { v[u] = ldg_rlx4(sp + u); m = max(max(m, max(v[u].x, v[u].y)), max(v[u].z, v[u].w)); }
          if (!__any_sync(~0u, m == ~0u)) break;
          if (it > SPIN_LIMIT) __trap();
        }
        float m = 0, q = 0;
#pragma unroll
        for (int u = 0; u < 4; u++) m += F_(v[u].x) + F_(v[u].z);
        m *= 0.125f;
#pragma unroll
        for (int u = 0; u < 4; u++) { const float a = F_(v[u].x) - m, b = F_(v[u].z) - m; q += F_(v[u].y) + F_(v[u].w) + 128.f * (a * a + b * b); }
        const float r = 0.5f * rsqrtf(q * (1.f / 1024) + 1e-5f);
        sts2(sb + STG + 16384 + (i * 32 + lane) * 8, U_(r), U_(-m * r));
      }
      __syncwarp();
      if (lane < 2) mbar_arrive(xbar);
    }
  } else {
    asm volatile("setmaxnreg.inc.sync.aligned.u32 " FRC ";");
    const int w = (tid >> 5) & 3, q = lane & 3;
    const uint32_t prm = sb + PRM + q * 16;
    const int row0 = wg * 64 + w * 16;
    FfnPipe p;
    p.full = full; p.emp = emp; p.ph = 0; p.aoff = wg * 8192; p.st = 0; p.sB = 2; p.prev = 0; p.leader = (tid & 127) == 0;
    FfnEpi e;
    const uint32_t stg = sb + STG + row0 * 128;
    e.st2 = stg + (lane & 15) * 128 + ((lane & 7) << 4);
    e.cc = sb + PRM + 1024 + q * 16; e.flip = 0; e.staged = staged; e.l0 = lane == 0;
    const uint32_t stw = e.st2 ^ (lane & 16);
    uint32_t x1[32];
    uint4* sp = g_stat + (rb * 128 + row0 + (lane >> 2)) * 4;
    float old[96], r0_, r1_;
    {
      float acc[64];
      p.issue<128>(acc, true); FT(8); p.next();
#pragma unroll 1
      for (int k = 1; k < 64; k++) { p.issue<128>(acc, false); FT(8 + k); p.retire(); }
      float xf[64], gf[32];
      uint32_t cb[16];
      mbar_wait(xbar, 0);
#pragma unroll
      for (int j = 0; j < 8; j++) {
        uint32_t xv[4];
        ldsm4(xv, (stw ^ ((j & 3) * 32)) + (j >> 2) * 16384);
#pragma unroll
        for (int i = 0; i < 4; i++) { xf[j * 8 + i * 2] = blo(xv[i]); xf[j * 8 + i * 2 + 1] = bhi(xv[i]); }
      }
#pragma unroll
      for (int i = 0; i < 4; i++) {
        const uint4 g = lds4(prm + i * 64), c = lds4(prm + 256 + i * 64);
        UNPK8(gf + i * 8, g);
        cb[i * 4] = c.x; cb[i * 4 + 1] = c.y; cb[i * 4 + 2] = c.z; cb[i * 4 + 3] = c.w;
      }
      acc_fence<64>(xf); acc_fence<32>(gf);
      WG_WAIT(0);
      p.release();
      acc_fence<64>(acc);
      PH(7); FT(72);
#pragma unroll
      for (int j = 0; j < 8; j++) {
        uint32_t* o = x1 + j * 4;
#pragma unroll
        for (int i = 0; i < 4; i++)
          o[i] = pk(fmaf(acc[j * 8 + i * 2], gf[j * 4 + (i & 2)], xf[j * 8 + i * 2]), fmaf(acc[j * 8 + i * 2 + 1], gf[j * 4 + (i & 2) + 1], xf[j * 8 + i * 2 + 1]));
        stsm4((stw ^ ((j & 3) * 32)) + (j >> 2) * 16384, mulbf(o[0], cb[j * 2]), mulbf(o[1], cb[j * 2]), mulbf(o[2], cb[j * 2 + 1]), mulbf(o[3], cb[j * 2 + 1]));
        if ((j & 3) == 3) { FENCE_ASYNC_SMEM(); e.flush(1); }
      }
      if (wg) BAR_SYNC(2, 128); else BAR_SYNC(3, 128);
    }
    PH(8); FT(73);
    float acc[64];
    {
      float* accC = old;
      p.sB = 0;
      p.issue<192>(accC, true, 1024 + STG); FT(80); p.next();
      p.issue<192>(accC, false, 1024 + STG + 16384); FT(81);
      FT(78);
      float s0 = 0, s1 = 0;
#define X1_FENCE _Pragma("unroll") for (int j = 0; j < 32; j++) asm volatile("" : "+r"(x1[j]));
      X1_FENCE
#pragma unroll
      for (int j = 0; j < 16; j++) { s0 += blo(x1[j * 2]) + bhi(x1[j * 2]); s1 += blo(x1[j * 2 + 1]) + bhi(x1[j * 2 + 1]); }
      s0 += __shfl_xor_sync(~0u, s0, 1); s1 += __shfl_xor_sync(~0u, s1, 1);
      s0 += __shfl_xor_sync(~0u, s0, 2); s1 += __shfl_xor_sync(~0u, s1, 2);
      s0 *= 1.f / 128; s1 *= 1.f / 128;
      float q0 = 0, q1 = 0;
      X1_FENCE
#pragma unroll
      for (int j = 0; j < 16; j++) {
        const float a = blo(x1[j * 2]) - s0, b = bhi(x1[j * 2]) - s0, c = blo(x1[j * 2 + 1]) - s1, d = bhi(x1[j * 2 + 1]) - s1;
        q0 += a * a + b * b; q1 += c * c + d * d;
      }
      q0 += __shfl_xor_sync(~0u, q0, 1); q1 += __shfl_xor_sync(~0u, q1, 1);
      q0 += __shfl_xor_sync(~0u, q0, 2); q1 += __shfl_xor_sync(~0u, q1, 2);
      if (q < 2) {
        uint32_t m = __float_as_uint(q ? s1 : s0), v = __float_as_uint(q ? q1 : q0);
        if (m == ~0u) m = 0x7fffffffu;
        if (v == ~0u) v = 0x7fffffffu;
        stg_rlx2((uint2*)(sp + q * 32) + nb, m, v);
      }
      X1_FENCE
      p.retire();
#pragma unroll 1
      for (int k = 2; k < 15; k++) { p.issue<192>(accC, false); FT(80 + k); p.retire(); }
      p.issue<192>(accC, false); FT(95);
      mbar_wait(xbar, 1);
      const float2 u0 = lds2f(sb + STG + 16384 + (row0 + (lane >> 2)) * 8), u1 = lds2f(sb + STG + 16384 + (row0 + (lane >> 2)) * 8 + 64);
      r0_ = u0.x; e.n0 = u0.y; r1_ = u1.x; e.n1 = u1.y;
      e.c = lds2u(e.cc);
      p.retire();
      e.s0 = r0_; e.s1 = r1_;
    }
    PH(9);
    {
      auto pair = [&](int J, bool first, int fo) {
#pragma unroll 1
        for (int r = 0; r < 2; r++) { p.issue<128>(acc, first && !r); FT(fo + r); p.retire(); acc_fence<8>(old + J * 8); e.half(old + J * 8, J, r); }
      };
#pragma unroll 1
      for (int i = 0; i < 3; i++) {
        if (i == 2) {
          e.s0 = r0_; e.s1 = r1_;
#pragma unroll
          for (int J = 8; J < 12; J++) pair(J, J == 8, 128 + (J - 8) * 2);
          e.cc += 512; e.c = lds2u(e.cc);
          e.s0 = e.s1 = 1.f;
        }
#pragma unroll
        for (int J = 0; J < 8; J++) pair(J, J == 0 && i < 2, 96 + i * 16 + (i >> 1) * 8 + J * 2);
        if (i == 2) break;
        e.cc += i ? -768 : 256; e.c = lds2u(e.cc);
        WG_WAIT(0);
        acc_fence<64>(acc);
#pragma unroll
        for (int k = 0; k < 64; k++) old[k] = acc[k] * ((k & 2) ? r1_ : r0_);
        acc_fence<64>(old);
        e.s0 = e.s1 = 1.f;
        PH(10 + i);
      }
#pragma unroll 1
      for (int k = 24; k < 56; k++) { p.issue<128>(acc, false); FT(128 + k); p.retire(); }
      float xf[64], gf[32];
#pragma unroll
      for (int i = 0; i < 4; i++) {
        const uint4 g = lds4(prm + 512 + i * 64), h = lds4(prm + 768 + i * 64);
        float hf[8];
        UNPK8(gf + i * 8, g); UNPK8(hf, h);
#pragma unroll
        for (int u = 0; u < 8; u++) {
          const int c = (u >> 2) * 4 + (u & 2);
          xf[i * 16 + u * 2] = fmaf(gf[i * 8 + c], hf[c], blo(x1[i * 8 + u])); xf[i * 16 + u * 2 + 1] = fmaf(gf[i * 8 + c + 1], hf[c + 1], bhi(x1[i * 8 + u]));
        }
      }
      acc_fence<64>(xf); acc_fence<32>(gf);
      mbar_wait(staged + 24, 1);
      mbar_wait(staged + 16, 0);
      WG_WAIT(0);
      acc_fence<64>(acc);
      PH(13); FT(184);
#pragma unroll
      for (int j = 0; j < 8; j++) {
        uint32_t o[4];
#pragma unroll
        for (int i = 0; i < 4; i++)
          o[i] = pk(fmaf(acc[j * 8 + i * 2], gf[j * 4 + (i & 2)], xf[j * 8 + i * 2]), fmaf(acc[j * 8 + i * 2 + 1], gf[j * 4 + (i & 2) + 1], xf[j * 8 + i * 2 + 1]));
        stsm4((stw ^ ((j & 3) * 32)) + (j >> 2) * 16384, o[0], o[1], o[2], o[3]);
        if ((j & 3) == 3) {
          FENCE_ASYNC_SMEM();
          __syncwarp();
          if (lane == 0) { tma2d_st(&mp.out, nb * 128 + (j >> 2) * 64, rb * 128 + row0, stg + (j >> 2) * 16384); BULK_COMMIT(); }
        }
      }
      if (lane == 0) BULK_WAIT_READ(0);
      __syncwarp();
    }
  }
  PH(14); RS(3); FT(185);
}

typedef CUresult (*EncFn)(CUtensorMap*, CUtensorMapDataType, cuuint32_t, void*, const cuuint64_t*, const cuuint64_t*, const cuuint32_t*,
                          const cuuint32_t*, CUtensorMapInterleave, CUtensorMapSwizzle, CUtensorMapL2promotion, CUtensorMapFloatOOBfill);
static void map2d(EncFn enc, CUtensorMap* m, const void* p, int rows, int cols, int boxRows) {
  cuuint64_t d[2] = {(cuuint64_t)cols, (cuuint64_t)rows}, s[1] = {(cuuint64_t)cols * 2};
  cuuint32_t b[2] = {64, (cuuint32_t)boxRows}, e[2] = {1, 1};
  enc(m, CU_TENSOR_MAP_DATA_TYPE_BFLOAT16, 2, (void*)p, d, s, b, e, CU_TENSOR_MAP_INTERLEAVE_NONE, CU_TENSOR_MAP_SWIZZLE_128B,
      CU_TENSOR_MAP_L2_PROMOTION_L2_128B, CU_TENSOR_MAP_FLOAT_OOB_FILL_NONE);
}
static void map3d(EncFn enc, CUtensorMap* m, const void* p, int rows, int cols, int nch) {
  cuuint64_t d[3] = {64, (cuuint64_t)rows, (cuuint64_t)(cols / 64)}, s[2] = {(cuuint64_t)cols * 2, 128};
  cuuint32_t b[3] = {64, 64, (cuuint32_t)nch}, e[3] = {1, 1, 1};
  enc(m, CU_TENSOR_MAP_DATA_TYPE_BFLOAT16, 3, (void*)p, d, s, b, e, CU_TENSOR_MAP_INTERLEAVE_NONE, CU_TENSOR_MAP_SWIZZLE_128B,
      CU_TENSOR_MAP_L2_PROMOTION_L2_128B, CU_TENSOR_MAP_FLOAT_OOB_FILL_NONE);
}

extern "C" void kernel_launch(void* const* d_in, const int* in_sizes, int n_in, void* d_out, int out_size) {
  const bf16* x = (const bf16*)d_in[0];
  const bf16* mem0 = (const bf16*)d_in[1];
  void* fn = nullptr;
  cudaDriverEntryPointQueryResult qr;
  cudaGetDriverEntryPoint("cuTensorMapEncodeTiled", &fn, cudaEnableDefault, &qr);
  EncFn enc = (EncFn)fn;
  FfnMaps fm = {};
  map3d(enc, &fm.wo, d_in[5], 4096, 1024, 2);
  map3d(enc, &fm.w1a, d_in[8], 1024, 3584, 2);
  map3d(enc, &fm.w1b, d_in[8], 1024, 3584, 3);
  map3d(enc, &fm.w2, d_in[10], 3584, 1024, 2);
  map2d(enc, &fm.x, x, 2048, 1024, 128);
  map2d(enc, &fm.out, d_out, 2048, 1024, 16);
  RecMaps rm = {};
  map2d(enc, &rm.wq, d_in[2], 1024, 4096, 128);
  map2d(enc, &rm.wk, d_in[3], 1024, 4096, 128);
  map2d(enc, &rm.wv, d_in[4], 1024, 4096, 16);
  map2d(enc, &rm.wo, d_in[5], 4096, 1024, 128);
  char* xc = nullptr;
  cudaGetSymbolAddress((void**)&xc, g_xc);
  xc += (0 - (uintptr_t)xc) & 0x1FFFFF;
  {
    cuuint64_t d[3] = {512, ARV ? 8 : 128, ARV ? 128 : 6}, sd[2] = {1024, ARV ? 8192 : 131072};
    cuuint32_t bi[3] = {64, 8, 5}, e[3] = {1, 1, 1};
    enc(&rm.ari, CU_TENSOR_MAP_DATA_TYPE_BFLOAT16, 3, xc + AR_OFF, d, sd, bi, e, CU_TENSOR_MAP_INTERLEAVE_NONE, CU_TENSOR_MAP_SWIZZLE_NONE,
        CU_TENSOR_MAP_L2_PROMOTION_NONE, CU_TENSOR_MAP_FLOAT_OOB_FILL_NONE);
  }
  cudaFuncSetAttribute(k_ffn, cudaFuncAttributeMaxDynamicSharedMemorySize, ffn::SMEM);
  cudaFuncSetAttribute(k_rec, cudaFuncAttributeMaxDynamicSharedMemorySize, rec::SMEM);
  cudaStream_t st = cudaStreamPerThread;
  int dF = 450, dA = 2700, dS = 300, dM = 120, dG = 350, dP = 24, dX = 48, dD = 350, dZ = 0, dZ2 = 1, dV = 370, dX2 = 0;
  k_rec<<<132, 512, rec::SMEM, st>>>(rm, mem0, x, (const bf16*)d_in[12], (const bf16*)d_in[13], (const char*)d_in[8], (const bf16*)d_in[9],
                                     (const char*)d_in[5], xc, dF, dA, dS, dM, dG, dP, dX, dD, dZ, dZ2, dV, dX2);
  cudaLaunchConfig_t cfg = {};
  cfg.gridDim = dim3(132); cfg.blockDim = dim3(384); cfg.dynamicSmemBytes = ffn::SMEM; cfg.stream = st;
  cudaLaunchAttribute at[1];
  at[0].id = cudaLaunchAttributeProgrammaticStreamSerialization;
  at[0].val.programmaticStreamSerializationAllowed = 1;
  cfg.attrs = at; cfg.numAttrs = 1;
  cudaLaunchKernelEx(&cfg, k_ffn, fm, (const bf16*)d_in[11]);
}
```

```cpp
#include <cuda_runtime.h>
#include <cuda.h>
#include <cuda_bf16.h>
#include <stdint.h>

typedef __nv_bfloat16 bf16;

__device__ __align__(16) float g_mod[6144];
__device__ __align__(1024) uint4 g_modp[4 * 512];
__device__ unsigned g_hcnt;
__device__ unsigned g_hf[4];
__device__ __align__(1024) uint4 g_h[2048 * 1024 / 8];
__device__ __align__(1024) uint4 g_O[2048 * 4096 / 8];
__device__ __align__(1024) uint4 g_h2[2048 * 1024 / 8];
__device__ __align__(1024) uint4 g_U[2048 * 3584 / 8];
__device__ __align__(1024) uint4 g_stat[2048 * 4];
__device__ __align__(1024) unsigned g_cnt[16 * 4 * 32];
__device__ unsigned g_mcnt;
__device__ unsigned g_slot[256];
__device__ unsigned g_fin;
__device__ __align__(16) uint4 g_cc[224 * 4];
__device__ __align__(1024) uint4 g_xc[44 * 16384];
__device__ __align__(1024) unsigned g_tm[4 * 256];
#define FT(i)
#define FTP(i)
#define PT(i)
#define PH(i)
#define RS(i)
#define RP(i)
#define RPN(i, s)
#define TSV(i, v)
#define TS(i)

#define WIN 2
#define FRC "232"
#define FRP "40"
#define YR 1
#define XPK 0
#define NFA 1
#define PINM 1
#define FMAP (((g >> 2) * 4 + m) * 8 + ((g & 3) ^ ((g & 4) ? 3 : 0)) * 2 + (blockIdx.x & 1))
#define FDB 0
#define ALIAS 3
#define EF 0
#define XPF 0
#define PFT 150000
#define PFS 104
#define PF0 13000
#define PFD 128
#define ARV 0
#define HV 0
#define XE 0
#define NF 3
#define NB0 4
#define PV0 4
#define T1L 1
#define NW0 5
#define FQM 0
#define FQ(k) do { if ((FQM >> ((k) - 48)) & 1) SCHED_FENCE(k); } while (0)
#define SWP 1
#define VCO 0
#define AV 0
#define PKE 0
#define VRF 3
#define RSO 2
#define WPF 1
#define VPC 1
#define OBL 1
#define WC0 10
#define WPE 3
#define LS 0
#define ALN 0x80
#define EOT 1
#define SKW 3
#define XDL 6
#define QW 0
#define PDS 61
#define P_NVR 5
#define P_NVP 2
#define P_NWP 9
#define P_NW1 7
#define RF_ 208
#define PSV 1
#define RA_ (488 - 2 * RF_)
#define XI 5
#define XL 1
#define WCH 2
#define HX 0
#define VB 1
#define TP 0
#define CKI 0
#define NOP_ 2
#define KVO 0
#define NDL 3
#define AM 0
#define XM 3
#define XP 0
#define SPIN_LIMIT (1 << 20)
__device__ __forceinline__ uint64_t mkdesc(uint32_t addr, uint32_t lbo, uint32_t sbo) {
  return (uint64_t)((addr & 0x3FFFF) >> 4) | ((uint64_t)(lbo >> 4) << 16) | ((uint64_t)(sbo >> 4) << 32) | (1ull << 62);
}
__device__ __forceinline__ void mbar_init(uint32_t a, int c) { asm volatile("mbarrier.init.shared.b64 [%0],%1;" ::"r"(a), "r"(c) : "memory"); }
__device__ __forceinline__ void mbar_wait(uint32_t a, uint32_t par) {
  asm volatile(
      "{.reg .pred p; .reg .u32 n;\n"
      "mov.u32 n, 0;\n"
      "W: mbarrier.try_wait.parity.shared.b64 p,[%0],%1;\n"
      "@p bra D;\n"
      "add.u32 n, n, 1;\n"
      "setp.lt.u32 p, n, %2;\n"
      "@p bra W;\n"
      "trap;\n"
      "D:}" ::"r"(a), "r"(par), "n"(SPIN_LIMIT) : "memory");
}
__device__ __forceinline__ void mbar_wait_q(uint32_t a, uint32_t par) {
  asm volatile(
      "{.reg .pred p; .reg .u32 n;\n"
      "mov.u32 n, 0;\n"
      "W: mbarrier.try_wait.parity.shared.b64 p,[%0],%1,4000;\n"
      "@p bra D;\n"
      "add.u32 n, n, 1;\n"
      "setp.lt.u32 p, n, %2;\n"
      "@p bra W;\n"
      "trap;\n"
      "D:}" ::"r"(a), "r"(par), "n"(SPIN_LIMIT / 16) : "memory");
}
__device__ __forceinline__ void mbar_expect(uint32_t a, uint32_t b) { asm volatile("mbarrier.arrive.expect_tx.shared.b64 _,[%0],%1;" ::"r"(a), "r"(b) : "memory"); }
__device__ __forceinline__ void mbar_arrive(uint32_t a) { asm volatile("mbarrier.arrive.shared.b64 _,[%0];" ::"r"(a) : "memory"); }
__device__ __forceinline__ uint32_t mapa(uint32_t a, uint32_t cta) { uint32_t r; asm("mapa.shared::cluster.u32 %0,%1,%2;" : "=r"(r) : "r"(a), "r"(cta)); return r; }
__device__ __forceinline__ void mbar_arrive_cl(uint32_t a) { asm volatile("mbarrier.arrive.shared::cluster.b64 _,[%0];" ::"r"(a) : "memory"); }
__device__ __forceinline__ void tma2d(uint32_t dst, const CUtensorMap* m, int c0, int c1, uint32_t mb) {
  asm volatile("cp.async.bulk.tensor.2d.shared::cluster.global.mbarrier::complete_tx::bytes [%0],[%1,{%2,%3}],[%4];" ::"r"(dst), "l"(m), "r"(c0), "r"(c1), "r"(mb) : "memory");
}
__device__ __forceinline__ void tma2d_pf(const CUtensorMap* m, int c0, int c1) {
  asm volatile("cp.async.bulk.prefetch.tensor.2d.L2.global [%0,{%1,%2}];" ::"l"(m), "r"(c0), "r"(c1) : "memory");
}
__device__ __forceinline__ void tma3d(uint32_t dst, const CUtensorMap* m, int c1, int c2, uint32_t mb) {
  asm volatile("cp.async.bulk.tensor.3d.shared::cluster.global.mbarrier::complete_tx::bytes [%0],[%1,{0,%2,%3}],[%4];" ::"r"(dst), "l"(m), "r"(c1), "r"(c2), "r"(mb) : "memory");
}
__device__ __forceinline__ void tma2d_st(const CUtensorMap* m, int c0, int c1, uint32_t src) {
  asm volatile("cp.async.bulk.tensor.2d.global.shared::cta.bulk_group [%0,{%1,%2}],[%3];" ::"l"(m), "r"(c0), "r"(c1), "r"(src) : "memory");
}
__device__ __forceinline__ void bulk_ld(uint32_t dst, const void* src, uint32_t n, uint32_t mb) {
  asm volatile("cp.async.bulk.shared::cluster.global.mbarrier::complete_tx::bytes [%0],[%1],%2,[%3];" ::"r"(dst), "l"(src), "r"(n), "r"(mb) : "memory");
}
__device__ __forceinline__ void bulk_ld_mc(uint32_t dst, const void* src, uint32_t n, uint32_t mb) {
  asm volatile("cp.async.bulk.shared::cluster.global.mbarrier::complete_tx::bytes.multicast::cluster [%0],[%1],%2,[%3],%4;" ::"r"(dst), "l"(src), "r"(n), "r"(mb), "h"((uint16_t)3) : "memory");
}
__device__ __forceinline__ void bulk_st(void* dst, uint32_t src, uint32_t n) {
  asm volatile("cp.async.bulk.global.shared::cta.bulk_group [%0],[%1],%2;" ::"l"(dst), "r"(src), "r"(n) : "memory");
}
__device__ __forceinline__ void e_expect_tma3d(uint32_t dst, const CUtensorMap* m, int c1, int c2, uint32_t mb, uint32_t bytes) {
  asm volatile("{.reg .pred p; elect.sync _|p, 0xffffffff; @p mbarrier.arrive.expect_tx.shared.b64 _,[%4],%5;\n"
               "@p cp.async.bulk.tensor.3d.shared::cluster.global.mbarrier::complete_tx::bytes [%0],[%1,{0,%2,%3}],[%4];}" ::"r"(dst), "l"(m), "r"(c1), "r"(c2), "r"(mb), "r"(bytes) : "memory");
}
__device__ __forceinline__ void e_bulk_ld(uint32_t dst, const void* src, uint32_t n, uint32_t mb) {
  asm volatile("{.reg .pred p; elect.sync _|p, 0xffffffff; @p cp.async.bulk.shared::cluster.global.mbarrier::complete_tx::bytes [%0],[%1],%2,[%3];}" ::"r"(dst), "l"(src), "r"(n), "r"(mb) : "memory");
}
__device__ __forceinline__ void e_bulk_ld_ef(uint32_t dst, const void* src, uint32_t n, uint32_t mb) {
  asm volatile("{.reg .pred p; .reg .b64 c; createpolicy.fractional.L2::evict_first.b64 c,1.0; elect.sync _|p, 0xffffffff;"
               " @p cp.async.bulk.shared::cluster.global.mbarrier::complete_tx::bytes.L2::cache_hint [%0],[%1],%2,[%3],c;}" ::"r"(dst), "l"(src), "r"(n), "r"(mb) : "memory");
}
__device__ __forceinline__ void e_bulk_ld_mc(uint32_t dst, const void* src, uint32_t n, uint32_t mb) {
  asm volatile("{.reg .pred p; elect.sync _|p, 0xffffffff; @p cp.async.bulk.shared::cluster.global.mbarrier::complete_tx::bytes.multicast::cluster [%0],[%1],%2,[%3],%4;}" ::"r"(dst), "l"(src), "r"(n), "r"(mb), "h"((uint16_t)3) : "memory");
}
#define BULK_COMMIT() asm volatile("cp.async.bulk.commit_group;" ::: "memory")
#define BULK_WAIT_READ(n) asm volatile("cp.async.bulk.wait_group.read " #n ";" ::: "memory")
#define BULK_WAIT(n) asm volatile("cp.async.bulk.wait_group " #n ";" ::: "memory")
#define FENCE_ASYNC_SMEM() asm volatile("fence.proxy.async.shared::cta;" ::: "memory")
#define FENCE_ASYNC() asm volatile("fence.proxy.async;" ::: "memory")
#define WG_FENCE() asm volatile("wgmma.fence.sync.aligned;" ::: "memory")
#define WG_COMMIT() asm volatile("wgmma.commit_group.sync.aligned;" ::: "memory")
#define WG_WAIT(n) asm volatile("wgmma.wait_group.sync.aligned " #n ";" ::: "memory")
#define BAR_SYNC(id, n) asm volatile("bar.sync %0,%1;" ::"n"(id), "n"(n) : "memory")
#define BAR_ARRIVE(id, n) asm volatile("bar.arrive %0,%1;" ::"n"(id), "n"(n) : "memory")
#define SCHED_FENCE(k) asm volatile("{.reg .pred p; setp.ne.u32 p,%0,0; @p trap;}" ::"r"(mp.zero[(k) - 46]) : "memory")
#define CLUSTER_SYNC() asm volatile("barrier.cluster.arrive.relaxed.aligned; barrier.cluster.wait.aligned;" ::: "memory")
__device__ __forceinline__ uint32_t pk(float lo, float hi) { uint32_t r; asm("cvt.rn.bf16x2.f32 %0,%1,%2;" : "=r"(r) : "f"(hi), "f"(lo)); return r; }
__device__ __forceinline__ float blo(uint32_t v) { return __uint_as_float(v << 16); }
__device__ __forceinline__ float bhi(uint32_t v) { return __uint_as_float(v & 0xffff0000u); }
__device__ __forceinline__ void ldsm4(uint32_t* r, uint32_t a) {
  asm volatile("ldmatrix.sync.aligned.m8n8.x4.shared.b16 {%0,%1,%2,%3},[%4];" : "=r"(r[0]), "=r"(r[1]), "=r"(r[2]), "=r"(r[3]) : "r"(a) : "memory");
}
__device__ __forceinline__ void ldsm4t(uint32_t* r, uint32_t a) {
  asm volatile("ldmatrix.sync.aligned.m8n8.x4.trans.shared.b16 {%0,%1,%2,%3},[%4];" : "=r"(r[0]), "=r"(r[1]), "=r"(r[2]), "=r"(r[3]) : "r"(a) : "memory");
}
__device__ __forceinline__ void stsm4(uint32_t a, uint32_t r0, uint32_t r1, uint32_t r2, uint32_t r3) {
  asm volatile("stmatrix.sync.aligned.m8n8.x4.shared.b16 [%0],{%1,%2,%3,%4};" ::"r"(a), "r"(r0), "r"(r1), "r"(r2), "r"(r3) : "memory");
}
__device__ __forceinline__ void mma16(float* d, uint32_t a0, uint32_t a1, uint32_t a2, uint32_t a3, uint32_t b0, uint32_t b1) {
  asm volatile("mma.sync.aligned.m16n8k16.row.col.f32.bf16.bf16.f32 {%0,%1,%2,%3},{%4,%5,%6,%7},{%8,%9},{%0,%1,%2,%3};"
               : "+f"(d[0]), "+f"(d[1]), "+f"(d[2]), "+f"(d[3]) : "r"(a0), "r"(a1), "r"(a2), "r"(a3), "r"(b0), "r"(b1));
}
__device__ __forceinline__ void mma8(float* d, uint32_t a0, uint32_t a1, uint32_t b0) {
  asm volatile("mma.sync.aligned.m16n8k8.row.col.f32.bf16.bf16.f32 {%0,%1,%2,%3},{%4,%5},{%6},{%0,%1,%2,%3};"
               : "+f"(d[0]), "+f"(d[1]), "+f"(d[2]), "+f"(d[3]) : "r"(a0), "r"(a1), "r"(b0));
}
__device__ __forceinline__ float4 lds4f(uint32_t a) { float4 v; asm volatile("ld.shared.v4.f32 {%0,%1,%2,%3},[%4];" : "=f"(v.x), "=f"(v.y), "=f"(v.z), "=f"(v.w) : "r"(a) : "memory"); return v; }
__device__ __forceinline__ float2 lds2f(uint32_t a) { float2 v; asm volatile("ld.shared.v2.f32 {%0,%1},[%2];" : "=f"(v.x), "=f"(v.y) : "r"(a) : "memory"); return v; }
__device__ __forceinline__ uint4 lds4(uint32_t a) { uint4 v; asm volatile("ld.shared.v4.u32 {%0,%1,%2,%3},[%4];" : "=r"(v.x), "=r"(v.y), "=r"(v.z), "=r"(v.w) : "r"(a) : "memory"); return v; }
__device__ __forceinline__ uint2 lds2u(uint32_t a) { uint2 v; asm volatile("ld.shared.v2.u32 {%0,%1},[%2];" : "=r"(v.x), "=r"(v.y) : "r"(a) : "memory"); return v; }
__device__ __forceinline__ uint32_t lds1(uint32_t a) { uint32_t v; asm volatile("ld.shared.u32 %0,[%1];" : "=r"(v) : "r"(a) : "memory"); return v; }
__device__ __forceinline__ void sts4(uint32_t a, uint32_t x, uint32_t y, uint32_t z, uint32_t w) { asm volatile("st.shared.v4.u32 [%0],{%1,%2,%3,%4};" ::"r"(a), "r"(x), "r"(y), "r"(z), "r"(w) : "memory"); }
__device__ __forceinline__ void sts2(uint32_t a, uint32_t x, uint32_t y) { asm volatile("st.shared.v2.u32 [%0],{%1,%2};" ::"r"(a), "r"(x), "r"(y) : "memory"); }
__device__ __forceinline__ void sts1(uint32_t a, uint32_t x) { asm volatile("st.shared.u32 [%0],%1;" ::"r"(a), "r"(x) : "memory"); }
__device__ __forceinline__ void sta4(uint32_t a, const uint32_t* v, uint32_t mb) {
  asm volatile("st.async.shared::cluster.mbarrier::complete_tx::bytes.v4.b32 [%0],{%1,%2,%3,%4},[%5];" ::"r"(a), "r"(v[0]), "r"(v[1]), "r"(v[2]), "r"(v[3]), "r"(mb) : "memory");
}
__device__ __forceinline__ uint4 ldg_rlx4(const void* p) { uint4 v; asm volatile("ld.relaxed.gpu.global.v4.u32 {%0,%1,%2,%3},[%4];" : "=r"(v.x), "=r"(v.y), "=r"(v.z), "=r"(v.w) : "l"(p) : "memory"); return v; }
__device__ __forceinline__ uint32_t ldg_rlx1(const void* p) { uint32_t v; asm volatile("ld.relaxed.gpu.global.u32 %0,[%1];" : "=r"(v) : "l"(p) : "memory"); return v; }
__device__ __forceinline__ uint2 ldg_rlx2(const void* p) { uint2 v; asm volatile("ld.relaxed.gpu.global.v2.u32 {%0,%1},[%2];" : "=r"(v.x), "=r"(v.y) : "l"(p) : "memory"); return v; }
__device__ __forceinline__ uint4 ldg_b128(const void* p) {
  uint4 v;
  asm volatile("{.reg .b128 t; .reg .b64 a,b; ld.relaxed.gpu.global.b128 t,[%4]; mov.b128 {a,b},t; mov.b64 {%0,%1},a; mov.b64 {%2,%3},b;}" : "=r"(v.x), "=r"(v.y), "=r"(v.z), "=r"(v.w) : "l"(p) : "memory");
  return v;
}
__device__ __forceinline__ void stg_b128(void* p, uint32_t x, uint32_t y, uint32_t z, uint32_t w) {
  asm volatile("{.reg .b128 t; .reg .b64 a,b; mov.b64 a,{%1,%2}; mov.b64 b,{%3,%4}; mov.b128 t,{a,b}; st.relaxed.gpu.global.b128 [%0],t;}" ::"l"(p), "r"(x), "r"(y), "r"(z), "r"(w) : "memory");
}
__device__ __forceinline__ void st_b128(void* p, uint32_t x, uint32_t y, uint32_t z, uint32_t w) {
  asm volatile("{.reg .b128 t; .reg .b64 a,b; mov.b64 a,{%1,%2}; mov.b64 b,{%3,%4}; mov.b128 t,{a,b}; st.relaxed.gpu.b128 [%0],t;}" ::"l"(p), "r"(x), "r"(y), "r"(z), "r"(w) : "memory");
}
__device__ __forceinline__ void stg_rlx4(void* p, uint32_t x, uint32_t y, uint32_t z, uint32_t w) { asm volatile("st.relaxed.gpu.global.v4.u32 [%0],{%1,%2,%3,%4};" ::"l"(p), "r"(x), "r"(y), "r"(z), "r"(w) : "memory"); }
__device__ __forceinline__ void stg_rlx2(void* p, uint32_t x, uint32_t y) { asm volatile("st.relaxed.gpu.global.v2.u32 [%0],{%1,%2};" ::"l"(p), "r"(x), "r"(y) : "memory"); }
__device__ __forceinline__ void red4(void* p, float a, float b, float c, float d) { asm volatile("red.relaxed.gpu.global.add.v4.f32 [%0],{%1,%2,%3,%4};" ::"l"(p), "f"(a), "f"(b), "f"(c), "f"(d) : "memory"); }
__device__ __forceinline__ unsigned ld_acq(const unsigned* p) { unsigned v; asm volatile("ld.acquire.gpu.global.u32 %0,[%1];" : "=r"(v) : "l"(p) : "memory"); return v; }
__device__ __forceinline__ void red_rel(unsigned* p) { asm volatile("red.release.gpu.global.add.u32 [%0],1;" ::"l"(p) : "memory"); }
__device__ __forceinline__ void red_rlx(unsigned* p) { asm volatile("red.relaxed.gpu.global.add.u32 [%0],1;" ::"l"(p) : "memory"); }
__device__ __forceinline__ void wait_cnt(const unsigned* p, unsigned n) { int it = 0; while (ld_acq(p) < n) { if (++it > SPIN_LIMIT) __trap(); } }
__device__ __forceinline__ uint32_t clk() { uint32_t c; asm volatile("mov.u32 %0,%%clock;" : "=r"(c)); return c; }
__device__ __forceinline__ uint32_t gtime() { uint32_t c; asm volatile("mov.u32 %0,%%globaltimer_lo;" : "=r"(c)); return c; }
__device__ __forceinline__ void wait_until(uint32_t t0, uint32_t d) { while (clk() - t0 < d) {} }
__device__ __forceinline__ float ex2(float x) { float r; asm("ex2.approx.ftz.f32 %0,%1;" : "=f"(r) : "f"(x)); return r; }
__device__ __forceinline__ float silu(float x) { return x * __frcp_rn(1.f + __expf(-x)); }
__device__ __forceinline__ float rbf(float x) { return __bfloat162float(__float2bfloat16_rn(x)); }

__device__ __forceinline__ void wgmma_ss_n128(float* d, uint64_t a, uint64_t b, int sd) {
  asm volatile("{.reg .pred p; setp.ne.b32 p, %66, 0;\n"
    "wgmma.mma_async.sync.aligned.m64n128k16.f32.bf16.bf16 {%0,%1,%2,%3,%4,%5,%6,%7,%8,%9,%10,%11,%12,%13,%14,%15,%16,%17,%18,%19,%20,%21,%22,%23,%24,%25,%26,%27,%28,%29,%30,%31,%32,%33,%34,%35,%36,%37,%38,%39,%40,%41,%42,%43,%44,%45,%46,%47,%48,%49,%50,%51,%52,%53,%54,%55,%56,%57,%58,%59,%60,%61,%62,%63}, %64, %65, p, 1, 1, 0, 1;}\n"
    : "+f"(d[0]),"+f"(d[1]),"+f"(d[2]),"+f"(d[3]),"+f"(d[4]),"+f"(d[5]),"+f"(d[6]),"+f"(d[7]),
      "+f"(d[8]),"+f"(d[9]),"+f"(d[10]),"+f"(d[11]),"+f"(d[12]),"+f"(d[13]),"+f"(d[14]),"+f"(d[15]),
      "+f"(d[16]),"+f"(d[17]),"+f"(d[18]),"+f"(d[19]),"+f"(d[20]),"+f"(d[21]),"+f"(d[22]),"+f"(d[23]),
      "+f"(d[24]),"+f"(d[25]),"+f"(d[26]),"+f"(d[27]),"+f"(d[28]),"+f"(d[29]),"+f"(d[30]),"+f"(d[31]),
      "+f"(d[32]),"+f"(d[33]),"+f"(d[34]),"+f"(d[35]),"+f"(d[36]),"+f"(d[37]),"+f"(d[38]),"+f"(d[39]),
      "+f"(d[40]),"+f"(d[41]),"+f"(d[42]),"+f"(d[43]),"+f"(d[44]),"+f"(d[45]),"+f"(d[46]),"+f"(d[47]),
      "+f"(d[48]),"+f"(d[49]),"+f"(d[50]),"+f"(d[51]),"+f"(d[52]),"+f"(d[53]),"+f"(d[54]),"+f"(d[55]),
      "+f"(d[56]),"+f"(d[57]),"+f"(d[58]),"+f"(d[59]),"+f"(d[60]),"+f"(d[61]),"+f"(d[62]),"+f"(d[63])
    : "l"(a), "l"(b), "r"(sd));
}
__device__ __forceinline__ void wgmma_ss_n192(float* d, uint64_t a, uint64_t b, int sd) {
  asm volatile("{.reg .pred p; setp.ne.b32 p, %98, 0;\n"
    "wgmma.mma_async.sync.aligned.m64n192k16.f32.bf16.bf16 {%0,%1,%2,%3,%4,%5,%6,%7,%8,%9,%10,%11,%12,%13,%14,%15,%16,%17,%18,%19,%20,%21,%22,%23,%24,%25,%26,%27,%28,%29,%30,%31,%32,%33,%34,%35,%36,%37,%38,%39,%40,%41,%42,%43,%44,%45,%46,%47,%48,%49,%50,%51,%52,%53,%54,%55,%56,%57,%58,%59,%60,%61,%62,%63,%64,%65,%66,%67,%68,%69,%70,%71,%72,%73,%74,%75,%76,%77,%78,%79,%80,%81,%82,%83,%84,%85,%86,%87,%88,%89,%90,%91,%92,%93,%94,%95}, %96, %97, p, 1, 1, 0, 1;}\n"
    : "+f"(d[0]),"+f"(d[1]),"+f"(d[2]),"+f"(d[3]),"+f"(d[4]),"+f"(d[5]),"+f"(d[6]),"+f"(d[7]),
      "+f"(d[8]),"+f"(d[9]),"+f"(d[10]),"+f"(d[11]),"+f"(d[12]),"+f"(d[13]),"+f"(d[14]),"+f"(d[15]),
      "+f"(d[16]),"+f"(d[17]),"+f"(d[18]),"+f"(d[19]),"+f"(d[20]),"+f"(d[21]),"+f"(d[22]),"+f"(d[23]),
      "+f"(d[24]),"+f"(d[25]),"+f"(d[26]),"+f"(d[27]),"+f"(d[28]),"+f"(d[29]),"+f"(d[30]),"+f"(d[31]),
      "+f"(d[32]),"+f"(d[33]),"+f"(d[34]),"+f"(d[35]),"+f"(d[36]),"+f"(d[37]),"+f"(d[38]),"+f"(d[39]),
      "+f"(d[40]),"+f"(d[41]),"+f"(d[42]),"+f"(d[43]),"+f"(d[44]),"+f"(d[45]),"+f"(d[46]),"+f"(d[47]),
      "+f"(d[48]),"+f"(d[49]),"+f"(d[50]),"+f"(d[51]),"+f"(d[52]),"+f"(d[53]),"+f"(d[54]),"+f"(d[55]),
      "+f"(d[56]),"+f"(d[57]),"+f"(d[58]),"+f"(d[59]),"+f"(d[60]),"+f"(d[61]),"+f"(d[62]),"+f"(d[63]),
      "+f"(d[64]),"+f"(d[65]),"+f"(d[66]),"+f"(d[67]),"+f"(d[68]),"+f"(d[69]),"+f"(d[70]),"+f"(d[71]),
      "+f"(d[72]),"+f"(d[73]),"+f"(d[74]),"+f"(d[75]),"+f"(d[76]),"+f"(d[77]),"+f"(d[78]),"+f"(d[79]),
      "+f"(d[80]),"+f"(d[81]),"+f"(d[82]),"+f"(d[83]),"+f"(d[84]),"+f"(d[85]),"+f"(d[86]),"+f"(d[87]),
      "+f"(d[88]),"+f"(d[89]),"+f"(d[90]),"+f"(d[91]),"+f"(d[92]),"+f"(d[93]),"+f"(d[94]),"+f"(d[95])
    : "l"(a), "l"(b), "r"(sd));
}
__device__ __forceinline__ void wgmma_ss_n256(float* d, uint64_t a, uint64_t b, int sd) {
  asm volatile("{.reg .pred p; setp.ne.b32 p, %130, 0;\n"
    "wgmma.mma_async.sync.aligned.m64n256k16.f32.bf16.bf16 {%0,%1,%2,%3,%4,%5,%6,%7,%8,%9,%10,%11,%12,%13,%14,%15,%16,%17,%18,%19,%20,%21,%22,%23,%24,%25,%26,%27,%28,%29,%30,%31,%32,%33,%34,%35,%36,%37,%38,%39,%40,%41,%42,%43,%44,%45,%46,%47,%48,%49,%50,%51,%52,%53,%54,%55,%56,%57,%58,%59,%60,%61,%62,%63,%64,%65,%66,%67,%68,%69,%70,%71,%72,%73,%74,%75,%76,%77,%78,%79,%80,%81,%82,%83,%84,%85,%86,%87,%88,%89,%90,%91,%92,%93,%94,%95,%96,%97,%98,%99,%100,%101,%102,%103,%104,%105,%106,%107,%108,%109,%110,%111,%112,%113,%114,%115,%116,%117,%118,%119,%120,%121,%122,%123,%124,%125,%126,%127}, %128, %129, p, 1, 1, 0, 1;}\n"
    : "+f"(d[0]),"+f"(d[1]),"+f"(d[2]),"+f"(d[3]),"+f"(d[4]),"+f"(d[5]),"+f"(d[6]),"+f"(d[7]),
      "+f"(d[8]),"+f"(d[9]),"+f"(d[10]),"+f"(d[11]),"+f"(d[12]),"+f"(d[13]),"+f"(d[14]),"+f"(d[15]),
      "+f"(d[16]),"+f"(d[17]),"+f"(d[18]),"+f"(d[19]),"+f"(d[20]),"+f"(d[21]),"+f"(d[22]),"+f"(d[23]),
      "+f"(d[24]),"+f"(d[25]),"+f"(d[26]),"+f"(d[27]),"+f"(d[28]),"+f"(d[29]),"+f"(d[30]),"+f"(d[31]),
      "+f"(d[32]),"+f"(d[33]),"+f"(d[34]),"+f"(d[35]),"+f"(d[36]),"+f"(d[37]),"+f"(d[38]),"+f"(d[39]),
      "+f"(d[40]),"+f"(d[41]),"+f"(d[42]),"+f"(d[43]),"+f"(d[44]),"+f"(d[45]),"+f"(d[46]),"+f"(d[47]),
      "+f"(d[48]),"+f"(d[49]),"+f"(d[50]),"+f"(d[51]),"+f"(d[52]),"+f"(d[53]),"+f"(d[54]),"+f"(d[55]),
      "+f"(d[56]),"+f"(d[57]),"+f"(d[58]),"+f"(d[59]),"+f"(d[60]),"+f"(d[61]),"+f"(d[62]),"+f"(d[63]),
      "+f"(d[64]),"+f"(d[65]),"+f"(d[66]),"+f"(d[67]),"+f"(d[68]),"+f"(d[69]),"+f"(d[70]),"+f"(d[71]),
      "+f"(d[72]),"+f"(d[73]),"+f"(d[74]),"+f"(d[75]),"+f"(d[76]),"+f"(d[77]),"+f"(d[78]),"+f"(d[79]),
      "+f"(d[80]),"+f"(d[81]),"+f"(d[82]),"+f"(d[83]),"+f"(d[84]),"+f"(d[85]),"+f"(d[86]),"+f"(d[87]),
      "+f"(d[88]),"+f"(d[89]),"+f"(d[90]),"+f"(d[91]),"+f"(d[92]),"+f"(d[93]),"+f"(d[94]),"+f"(d[95]),
      "+f"(d[96]),"+f"(d[97]),"+f"(d[98]),"+f"(d[99]),"+f"(d[100]),"+f"(d[101]),"+f"(d[102]),"+f"(d[103]),
      "+f"(d[104]),"+f"(d[105]),"+f"(d[106]),"+f"(d[107]),"+f"(d[108]),"+f"(d[109]),"+f"(d[110]),"+f"(d[111]),
      "+f"(d[112]),"+f"(d[113]),"+f"(d[114]),"+f"(d[115]),"+f"(d[116]),"+f"(d[117]),"+f"(d[118]),"+f"(d[119]),
      "+f"(d[120]),"+f"(d[121]),"+f"(d[122]),"+f"(d[123]),"+f"(d[124]),"+f"(d[125]),"+f"(d[126]),"+f"(d[127])
    : "l"(a), "l"(b), "r"(sd));
}
__device__ __forceinline__ void wgmma_rs_n32(float* d, const uint32_t* a, uint64_t b, int sd) {
  asm volatile("{.reg .pred p; setp.ne.b32 p, %21, 0;\n"
    "wgmma.mma_async.sync.aligned.m64n32k16.f32.bf16.bf16 {%0,%1,%2,%3,%4,%5,%6,%7,%8,%9,%10,%11,%12,%13,%14,%15}, {%16,%17,%18,%19}, %20, p, 1, 1, 0;}\n"
    : "+f"(d[0]),"+f"(d[1]),"+f"(d[2]),"+f"(d[3]),"+f"(d[4]),"+f"(d[5]),"+f"(d[6]),"+f"(d[7]),
      "+f"(d[8]),"+f"(d[9]),"+f"(d[10]),"+f"(d[11]),"+f"(d[12]),"+f"(d[13]),"+f"(d[14]),"+f"(d[15])
    : "r"(a[0]), "r"(a[1]), "r"(a[2]), "r"(a[3]), "l"(b), "r"(sd));
}
__device__ __forceinline__ void wgmma_ssT_n32(float* d, uint64_t a, uint64_t b, int sd) {
  asm volatile("{.reg .pred p; setp.ne.b32 p, %18, 0;\n"
    "wgmma.mma_async.sync.aligned.m64n32k16.f32.bf16.bf16 {%0,%1,%2,%3,%4,%5,%6,%7,%8,%9,%10,%11,%12,%13,%14,%15}, %16, %17, p, 1, 1, 1, 0;}\n"
    : "+f"(d[0]),"+f"(d[1]),"+f"(d[2]),"+f"(d[3]),"+f"(d[4]),"+f"(d[5]),"+f"(d[6]),"+f"(d[7]),
      "+f"(d[8]),"+f"(d[9]),"+f"(d[10]),"+f"(d[11]),"+f"(d[12]),"+f"(d[13]),"+f"(d[14]),"+f"(d[15])
    : "l"(a), "l"(b), "r"(sd));
}

__device__ __forceinline__ void wgmma_rs_n32_z(float* d, const uint32_t* a, uint64_t b) {
  asm volatile("{.reg .pred p; setp.ne.b32 p, 0, 0;\n"
    "wgmma.mma_async.sync.aligned.m64n32k16.f32.bf16.bf16 {%0,%1,%2,%3,%4,%5,%6,%7,%8,%9,%10,%11,%12,%13,%14,%15}, {%16,%17,%18,%19}, %20, p, 1, 1, 0;}\n"
    : "=f"(d[0]),"=f"(d[1]),"=f"(d[2]),"=f"(d[3]),"=f"(d[4]),"=f"(d[5]),"=f"(d[6]),"=f"(d[7]),
      "=f"(d[8]),"=f"(d[9]),"=f"(d[10]),"=f"(d[11]),"=f"(d[12]),"=f"(d[13]),"=f"(d[14]),"=f"(d[15])
    : "r"(a[0]), "r"(a[1]), "r"(a[2]), "r"(a[3]), "l"(b));
}

namespace rec {
constexpr int NVR = P_NVR;
constexpr int NVS = 16 - NVR;
constexpr int NVP = P_NVP;
constexpr int NWP = P_NWP;
constexpr uint32_t WO = 0;
constexpr uint32_t XB = 65536;
constexpr uint32_t PK = XB + 32768;
constexpr uint32_t VN = PK + 24576;
constexpr uint32_t VX0 = VN + 4096;
constexpr uint32_t WVS = 131072;
constexpr uint32_t MEM = WVS + 2 * NVS * 2048;
constexpr uint32_t ARO = MEM + 10240;
constexpr uint32_t OB = ARO + 5120;
constexpr uint32_t QT = OB + 2048;
constexpr uint32_t KT = QT + 2048;
constexpr uint32_t RQ = KT + 6144;
constexpr uint32_t RK = RQ + 2048;
constexpr uint32_t SC = RK + 2048;
constexpr uint32_t OT = OB;
constexpr uint32_t TF = SC + 2048;
constexpr uint32_t PRE = MEM + 2 * NVR * 2048;
constexpr uint32_t TA = TF + 8192;
constexpr uint32_t RX = TA + 6144;
constexpr uint32_t VX1 = RX + 2048;
constexpr uint32_t BARS = VX1 + 4096;
constexpr uint32_t PACE = BARS + 18 * 8;
constexpr uint32_t SMEM = BARS + 512;
static_assert(PRE + 14336 <= BARS, "staging");
constexpr int NW1 = P_NW1;
static_assert(SMEM <= 232448, "smem");
constexpr int B_E = 2, B_SC = 3, B_S = 4, B_O = 5, B_F = 6, B_W = 7, B_C = 9, B_K = 10, B_H = 15, B_Q = 1, B_S2 = 6, B_T2 = 9, B_P = 13, B_T = 14, B_R = 11, B_X = 12, B_V = 8;
constexpr int N_P = XE == 1 ? 416 : 384, N_R = XE ? 288 : 320, N_V = AV ? 384 : 512, N_O = AV ? 384 : 416;
constexpr int XC = 16384, X_RING = 131072, X_SC = 65536, X_TOK = 4096;
#define X_VX(i) (((i) >> 1) * 2048 + ((i) & 1) * 512)
#define X_VM(i) (X_VX(i) + 1024)
#define V_RING(n) (((n) & 1) * X_RING + ((n) & 2) * 2048)
#define V_TAG(n) ((~(n) >> 2) & 1)
}
struct RecMaps { CUtensorMap wq, wk, wv, wo, ari; int zero[40]; };

#define F_(x) __uint_as_float(x)
#define U_(x) __float_as_uint(x)
#define AR_R(q) (24 + ((q) & 1) * 16 + ((q) >> 1) * 56)
#define AR_P(q) ((q) >> 1)
#define AR_ROW(i) (24 + ((i) & 1) * 16 + ((i) & 2) * 92 + (((i) >> 2) & 7) + ((i) >> 5) * 128)
constexpr size_t AR_OFF = 32 * 262144;
__device__ __forceinline__ void ar_fetch(uint32_t dst, const CUtensorMap* m, int slot, int half, uint32_t mb) {
  asm volatile("{.reg .pred p; elect.sync _|p, 0xffffffff; @p mbarrier.arrive.expect_tx.shared.b64 _,[%4],10240;\n"
               "@p cp.async.bulk.tensor.3d.shared::cluster.global.mbarrier::complete_tx::bytes [%0],[%1,{%2,%3,%6}],[%4];\n"
               "@p cp.async.bulk.tensor.3d.shared::cluster.global.mbarrier::complete_tx::bytes [%0+5120],[%1,{%2,%5,%7}],[%4];}"
               ::"r"(dst), "l"(m), "r"(slot * 64), "r"(AR_R(half * 2)), "r"(mb), "r"(AR_R(half * 2 + 1)), "r"(AR_P(half * 2)), "r"(AR_P(half * 2 + 1)) : "memory");
}
__device__ __forceinline__ uint4 exch_b128(void* p, uint32_t x, uint32_t y, uint32_t z, uint32_t w) {
  uint4 v;
  asm volatile("{.reg .b128 s, t; .reg .b64 a,b; mov.b64 a,{%5,%6}; mov.b64 b,{%7,%8}; mov.b128 s,{a,b}; atom.relaxed.gpu.global.exch.b128 t,[%4],s;"
               " mov.b128 {a,b},t; mov.b64 {%0,%1},a; mov.b64 {%2,%3},b;}" : "=r"(v.x), "=r"(v.y), "=r"(v.z), "=r"(v.w) : "l"(p), "r"(x), "r"(y), "r"(z), "r"(w) : "memory");
  return v;
}
#define CONSUME(v) do { if ((v) == 0x7fc12345u) sts1(sb + rec::BARS + 96, 0); } while (0)
__device__ __forceinline__ uint32_t tagf(float v, uint32_t tag) { return (__float_as_uint(v) & ~1u) | tag; }
__device__ __forceinline__ uint2 ldg_b64(const void* p) { uint2 v; asm volatile("{.reg .b64 t; ld.relaxed.gpu.global.b64 t,[%2]; mov.b64 {%0,%1},t;}" : "=r"(v.x), "=r"(v.y) : "l"(p) : "memory"); return v; }
__device__ __forceinline__ void stg_b64(void* p, uint32_t x, uint32_t y) { asm volatile("{.reg .b64 t; mov.b64 t,{%1,%2}; st.relaxed.gpu.global.b64 [%0],t;}" ::"l"(p), "r"(x), "r"(y) : "memory"); }
__device__ __forceinline__ uint32_t tagbad(uint32_t x, uint32_t y, uint32_t tag) { uint32_t r; asm("lop3.b32 %0,%1,%2,%3,0x7e;" : "=r"(r) : "r"(x), "r"(y), "r"(tag)); return r; }

__device__ __forceinline__ bool anybad(uint32_t a, uint32_t b, uint32_t c, uint32_t d, uint32_t e, uint32_t f, uint32_t g, uint32_t h, uint32_t tag) {
  uint32_t r;
  asm volatile("{.reg .b32 t,u,v,w; .reg .pred p; lop3.b32 t,%1,%2,%9,0x7e; lop3.b32 u,%3,%4,%9,0x7e; lop3.b32 v,%5,%6,%9,0x7e; lop3.b32 w,%7,%8,%9,0x7e;"
               " lop3.b32 t,t,u,v,0xfe; lop3.b32 t,t,w,1,0xa8; setp.ne.u32 p,t,0; vote.sync.any.pred p,p,0xffffffff; selp.u32 %0,1,0,p;}"
               : "=r"(r) : "r"(a), "r"(b), "r"(c), "r"(d), "r"(e), "r"(f), "r"(g), "r"(h), "r"(tag));
  return r;
}
__device__ __forceinline__ bool anybad(uint32_t a, uint32_t b, uint32_t c, uint32_t d, uint32_t tag) {
  uint32_t r;
  asm volatile("{.reg .b32 t,u; .reg .pred p; lop3.b32 t,%1,%2,%5,0x7e; lop3.b32 u,%3,%4,%5,0x7e;"
               " lop3.b32 t,t,u,1,0xa8; setp.ne.u32 p,t,0; vote.sync.any.pred p,p,0xffffffff; selp.u32 %0,1,0,p;}"
               : "=r"(r) : "r"(a), "r"(b), "r"(c), "r"(d), "r"(tag));
  return r;
}
#define BAD8(r) anybad(r[0].x, r[0].z, r[1].x, r[1].z, r[2].x, r[2].z, r[3].x, r[3].z, tag)
#define BADS(r) anybad(r[0].x, r[0].y, r[1].x, r[1].y, r[2].x, r[2].y, r[3].x, r[3].y, tag)
constexpr float SCS = 0.08838834764831845f * 1.4426950408889634f / 16.f;
__device__ __forceinline__ uint32_t pkh(float lo, float hi, uint32_t tag) {
  uint32_t r;
  asm("{.reg .b32 t; cvt.rn.satfinite.f16x2.f32 t,%1,%2; lop3.b32 %0,t,0xfffffffe,%3,0xea;}" : "=r"(r) : "f"(hi), "f"(lo), "r"(tag));
  return r;
}
__device__ __forceinline__ uint32_t addh(uint32_t a, uint32_t b) { uint32_t r; asm("add.rn.f16x2 %0,%1,%2;" : "=r"(r) : "r"(a), "r"(b)); return r; }
__device__ __forceinline__ float hlo(uint32_t v) { float r; asm("{.reg .b16 a,b; mov.b32 {a,b},%1; cvt.f32.f16 %0,a;}" : "=f"(r) : "r"(v)); return r; }
__device__ __forceinline__ float hhi(uint32_t v) { float r; asm("{.reg .b16 a,b; mov.b32 {a,b},%1; cvt.f32.f16 %0,b;}" : "=f"(r) : "r"(v)); return r; }
__device__ __forceinline__ uint32_t ordh(uint32_t v) {
  uint32_t r;
  asm("{.reg .b32 m; prmt.b32 m,%1,0,0xbb99; lop3.b32 %0,%1,m,0x7fff7fff,0x78;}" : "=r"(r) : "r"(v));
  return r;
}
template <bool MASK>
__device__ __forceinline__ float4 softmax2(const uint2 (&r)[4], uint32_t mx, uint32_t my, uint32_t& k) {
  uint32_t x = addh(addh(r[0].x, r[1].x), addh(r[2].x, r[3].x)), y = addh(addh(r[0].y, r[1].y), addh(r[2].y, r[3].y));
  if (MASK) { x = addh(x, mx); y = addh(y, my); }
  asm("max.f16x2 %0,%1,%2;" : "=r"(k) : "r"(x), "r"(y));
  k = ordh(k);
  const int k0 = __reduce_max_sync(~0u, (int)(k << 16)), k1 = __reduce_max_sync(~0u, (int)k);
  const float m0 = hhi(k0 ^ ((k0 >> 31) & 0x7fff0000)) * -16.f, m1 = hhi(k1 ^ ((k1 >> 31) & 0x7fff0000)) * -16.f;
  return make_float4(ex2(fmaf(hlo(x), 16.f, m0)), ex2(fmaf(hhi(x), 16.f, m1)), ex2(fmaf(hlo(y), 16.f, m0)), ex2(fmaf(hhi(y), 16.f, m1)));
}
__device__ __forceinline__ char* mkp(uint32_t lo, uint32_t hi) { uint64_t r; asm("mov.b64 %0,{%1,%2};" : "=l"(r) : "r"(lo), "r"(hi)); return (char*)r; }
#define LO(p) ((uint32_t)(uint64_t)(p))
#define HI(p) ((uint32_t)((uint64_t)(p) >> 32))
__device__ __forceinline__ void cp16(uint32_t dst, const void* src) { asm volatile("cp.async.cg.shared.global [%0],[%1],16;" ::"r"(dst), "l"(src) : "memory"); }
__device__ __forceinline__ uint32_t xor3(uint32_t a, uint32_t b, uint32_t c) { uint32_t r; asm volatile("lop3.b32 %0,%1,%2,%3,0x96;" : "=r"(r) : "r"(a), "r"(b), "r"(c)); return r; }
__device__ __forceinline__ uint32_t mulbf(uint32_t a, uint32_t b) { uint32_t r; asm("mul.rn.bf16x2 %0,%1,%2;" : "=r"(r) : "r"(a), "r"(b)); return r; }
__device__ __forceinline__ uint32_t fmabf(uint32_t a, uint32_t b, uint32_t c) { uint32_t r; asm("fma.rn.bf16x2 %0,%1,%2,%3;" : "=r"(r) : "r"(a), "r"(b), "r"(c)); return r; }
__device__ __forceinline__ uint32_t addbf(uint32_t a, uint32_t b) { uint32_t r; asm("add.rn.bf16x2 %0,%1,%2;" : "=r"(r) : "r"(a), "r"(b)); return r; }
__device__ __forceinline__ void pv_mem(const uint32_t (&p)[4], uint32_t pm, const uint4 (&v)[4], const uint4 (&vn)[2], uint32_t (&O)[4]) {
  float o[4][4] = {{0, 0, 0, 0}, {0, 0, 0, 0}, {0, 0, 0, 0}, {0, 0, 0, 0}};
  mma16(o[0], v[0].x, v[0].y, v[0].z, v[0].w, p[0], p[1]);
  mma16(o[1], v[2].x, v[2].y, v[2].z, v[2].w, p[0], p[1]);
  mma16(o[2], v[1].x, v[1].y, v[1].z, v[1].w, p[2], p[3]);
  mma16(o[3], v[3].x, v[3].y, v[3].z, v[3].w, p[2], p[3]);
  mma16(o[0], vn[0].x, vn[0].y, vn[0].z, vn[0].w, pm, pm);
  mma16(o[1], vn[1].x, vn[1].y, vn[1].z, vn[1].w, pm, pm);
  O[0] = pk(o[0][0] + o[2][0], o[0][1] + o[2][1]); O[1] = pk(o[0][2] + o[2][2], o[0][3] + o[2][3]);
  O[2] = pk(o[1][0] + o[3][0], o[1][1] + o[3][1]); O[3] = pk(o[1][2] + o[3][2], o[1][3] + o[3][3]);
}
__device__ __forceinline__ void pv_tok(const uint32_t (&p)[4], uint32_t pm, const uint4 (&v)[4], const uint32_t (&vm)[4], uint32_t (&O)[4]) {
  float o[2][4] = {{0, 0, 0, 0}, {0, 0, 0, 0}}, sum[4] = {0, 0, 0, 0};
  const uint32_t one = 0x3f803f80u;
  mma16(sum, one, one, one, one, p[0], p[1]);
  mma16(o[0], v[0].x, v[0].y, v[0].z, v[0].w, p[0], p[1]);
  mma16(o[1], v[2].x, v[2].y, v[2].z, v[2].w, p[0], p[1]);
  mma16(sum, one, one, one, one, p[2], p[3]);
  mma16(o[0], v[1].x, v[1].y, v[1].z, v[1].w, p[2], p[3]);
  mma16(o[1], v[3].x, v[3].y, v[3].z, v[3].w, p[2], p[3]);
  mma8(sum, one, one, pm);
  mma8(o[0], vm[0], vm[1], pm);
  mma8(o[1], vm[2], vm[3], pm);
  float i0, i1;
  asm("rcp.approx.ftz.f32 %0,%1;" : "=f"(i0) : "f"(sum[0]));
  asm("rcp.approx.ftz.f32 %0,%1;" : "=f"(i1) : "f"(sum[1]));
  O[0] = pk(o[0][0] * i0, o[0][1] * i1); O[1] = pk(o[0][2] * i0, o[0][3] * i1);
  O[2] = pk(o[1][0] * i0, o[1][1] * i1); O[3] = pk(o[1][2] * i0, o[1][3] * i1);
}
__device__ __forceinline__ uint32_t sum4bf(uint32_t a, uint32_t b, uint32_t c, uint32_t d) { return addbf(addbf(a, b), addbf(c, d)); }
template <int OFF>
__device__ __forceinline__ void sta1(uint32_t a, uint32_t v, uint32_t mb) {
  asm volatile("st.async.shared::cluster.mbarrier::complete_tx::bytes.b32 [%0+%3],%1,[%2];" ::"r"(a), "r"(v), "r"(mb), "n"(OFF) : "memory");
}

__device__ __forceinline__ void wait_time(uint32_t t) { while ((int)(gtime() - t) < 0) __nanosleep(64); }
__device__ __noinline__ void rec_prefetch(const char* wmod, const char* w1, const char* x, const char* wo) {
  const int hb = blockIdx.x - 128;
  const uint32_t t0 = gtime();
  uint32_t t = t0 + PF0;
#pragma unroll 1
  for (int job = 0; job < (PFT ? 5 : 3); job++) {
    const char* p = job == 0 ? x + (6 + hb) * 65536 : job == 1 ? wmod + hb * 12288 + 4096 : job == 2 ? w1 + hb * 7168 : job == 3 ? x + hb * 8192 : wo + (1020 + hb) * 8192;
    const int n = job == 0 ? 120 - (hb & 2) * 4 : job == 3 ? 128 : 256, d = job == 0 ? 8192 : job == 1 ? 49152 : job == 2 ? 28672 : job == 3 ? 32768 : -32768;
    if (job == 3) t = t0 + PFT;
    PT(8 + job);
#pragma unroll 1
    for (int i = 0; i < n; i++) {
      wait_time(t);
      asm volatile("cp.async.bulk.prefetch.L2.global [%0], %1;" ::"l"(p), "r"(job == 2 ? 7168 : 8192) : "memory");
      p += !job && (i & 7) == 7 ? 204800 : d;
      t += job < 3 ? PFD : PFS;
      if (job && (i & 31) == 31 && ldg_rlx1(&g_fin)) return;
    }
  }
  PT(13);
}
__device__ __noinline__ void rec_helper(uint32_t sb, const bf16* cvec, const bf16* wmod, const char* w1, const bf16* b1, uint32_t t0) {
  const int tid = threadIdx.x, hb = blockIdx.x - 128;
  PT(1);
  for (int i = tid; i < 1024; i += 256) sts1(sb + i * 8, U_(rbf(silu(__bfloat162float(cvec[i])))));
  for (int i = tid; i < 2048; i += 256) g_stat[hb * 2048 + i] = make_uint4(~0u, ~0u, ~0u, ~0u);
  for (int i = tid; i < 512; i += 256) g_cnt[hb * 512 + i] = 0;
#pragma unroll 1
  for (int job = 0; job < 2; job++) {
    wait_time(t0 + PF0 + (job ? 600 : 350) * PFD);
    BAR_SYNC(rec::B_F, 256);
    PT(2 + job * 5);
    const int n8 = job ? 112 : 128, rg = tid >= n8, cg = tid - rg * n8, pitch = job ? 448 : 768;
    const uint4* p = (const uint4*)(job ? w1 + hb * 1792 : (const char*)(wmod + 2048 + hb * 1024)) + rg * pitch + min(cg, n8 - 1);
    float a1[8] = {0, 0, 0, 0, 0, 0, 0, 0}, a2[8] = {0, 0, 0, 0, 0, 0, 0, 0};
#pragma unroll 1
    for (int r0 = rg; r0 < 1024; r0 += 32) {
      uint4 v[16];
#pragma unroll
      for (int i = 0; i < 16; i++) { v[i] = ldg_rlx4(p); p += 2 * pitch; }
#pragma unroll
      for (int i = 0; i < 16; i++) {
        const float2 f = lds2f(sb + (r0 + 2 * i) * 8);
        const float w[8] = {blo(v[i].x), bhi(v[i].x), blo(v[i].y), bhi(v[i].y), blo(v[i].z), bhi(v[i].z), blo(v[i].w), bhi(v[i].w)};
#pragma unroll
        for (int e = 0; e < 8; e++) { a1[e] += f.x * w[e]; a2[e] += f.y * w[e]; }
      }
    }
    const uint32_t rd = sb + 8192;
    if (cg < n8) {
#pragma unroll
      for (int e = 0; e < 8; e++) sts2(rd + rg * 8192 + (cg * 8 + e) * 8, U_(a1[e]), U_(a2[e]));
    }
    BAR_SYNC(rec::B_F, 256);
    if (job == 0) {
      for (int i = tid; i < 1024; i += 256) g_mod[2048 + hb * 1024 + i] = rbf(F_(lds1(rd + i * 8)) + F_(lds1(rd + 8192 + i * 8)));
      BAR_SYNC(rec::B_F, 256);
      PT(6);
      if (tid == 0) { red_rel(&g_mcnt); wait_cnt(&g_mcnt, 4); }
      BAR_SYNC(rec::B_F, 256);
      for (int i = tid; i < 1024; i += 256) sts2(sb + i * 8, U_(rbf(1.f + __ldcg(g_mod + 4096 + i))), U_(__ldcg(g_mod + 3072 + i)));
    } else {
      for (int i = tid; i < 448; i += 256) {
        const int gn = hb * 896 + i * 2;
        const uint32_t bb = *(const uint32_t*)(b1 + gn);
        const float4 u = lds4f(rd + i * 16), w = lds4f(rd + 8192 + i * 16);
        ((uint2*)g_cc)[(gn >> 4) * 8 + ((gn >> 1) & 3) * 2 + ((gn >> 3) & 1)] = make_uint2(pk(u.x + w.x, u.z + w.z), pk(0.5f * (u.y + w.y + blo(bb)), 0.5f * (u.w + w.w + bhi(bb))));
      }
      PT(4);
    }
  }
}

__global__ void __cluster_dims__(2, 1, 1) __launch_bounds__(512, 1)
k_rec(const __grid_constant__ RecMaps mp, const bf16* __restrict__ mem0, const bf16* __restrict__ x, const bf16* __restrict__ cvec,
      const bf16* __restrict__ wmod, const char* __restrict__ w1, const bf16* __restrict__ b1, const char* __restrict__ wo, char* xc, int dF, int dA, int dS, int dM, int dG, int dP, int dX, int dD, int dZ, int dZ2, int dV, int dX2) {
  using namespace rec;
  extern __shared__ __align__(1024) char smem[];
  const uint32_t sb = (uint32_t)__cvta_generic_to_shared(smem);
  if ((sb & 0x3FFFF) != 1024) __trap();
  PH(0); RS(0); if (threadIdx.x == 0) PT(0);
  if (threadIdx.x == 0) {
    int b = blockIdx.x;
    if (b >= 8 && b < 128) {
      const int t = (b >> 1) - 4, u = t - 32;
      b = 2 * (t < 32 ? 4 + (t & 16) + (t & 7) * 2 + ((t >> 3) & 1) : 36 + (u / 14) * 14 + (u % 7) * 2 + ((u / 7) & 1)) + (b & 1);
    }
    sts1(sb + rec::PACE + 24, b);
    const int c = blockIdx.x >> 1, l = c < 36 ? (c - 4) & 7 : (c - 36) % 7, m = c < 4 ? c : c < 36 ? (c - 4) >> 3 : (c - 36) / 7;
    const int g = c < 4 ? 15 : (l >> 1) * 4 + (l & 1) + (c < 36 ? 0 : 2);
    unsigned sm;
    asm("mov.u32 %0,%%smid;" : "=r"(sm));
    if (c < 64) g_slot[sm & 255] = 1 + FMAP;
  }
#define ROLE_REFRESH { asm volatile("mov.u32 %0,%%tid.x;" : "=r"(tid)); wid = __shfl_sync(~0u, tid >> 5, 0); b = __shfl_sync(~0u, lds1(sb + PACE + 24), 0); }
#define ROLE_VARS int tid; asm volatile("mov.u32 %0,%%tid.x;" : "=r"(tid)); \
    int wid = __shfl_sync(~0u, tid >> 5, 0), b = __shfl_sync(~0u, lds1(sb + PACE + 24), 0);
#define wg (wid >> 2)
#define iw (wid & 3)
#define h (b >> 2)
#define j (b & 3)
#define a (b & 1)
#define bb ((b >> 1) & 1)
  const uint32_t wbar = sb + BARS + 48, obar = wbar + 8;
  if (threadIdx.x == 256) {
    for (int i = 0; i < 18; i++) if (i != 12) mbar_init(sb + BARS + i * 8, i == 3 || i == 8 || i == 9 || i == 10 ? 2 : 1);
    for (int i = 0; i < 3; i++) mbar_init(sb + PACE + i * 8, 1);
    asm volatile("fence.mbarrier_init.release.cluster;" ::: "memory");
    FENCE_ASYNC_SMEM();
    mbar_expect(sb + BARS, 2048);
    mbar_expect(sb + BARS + 16, 4096);
    mbar_expect(sb + BARS + 32, 4096);
    mbar_expect(sb + BARS + 40, 4096);
  }
  __syncthreads();
  asm volatile("barrier.cluster.arrive.relaxed.aligned;" ::: "memory");
#define lane ((int)(l16 >> 4))
#define l16 (L16 & 0x1f0)
#define is7 ((L16 & 112) == 112)
#define PIN(x) __shfl_xor_sync(~0u, (uint32_t)(x), 0)
#define REFRESH() L16 = __shfl_xor_sync(~0u, L16, 0)
#define lar ((L16 & 0x180) * 8 + (L16 & 0x70))
#define X_LOAD(n, w, u) \
        asm volatile("{.reg .pred p; elect.sync _|p, 0xffffffff; @p mbarrier.arrive.expect_tx.shared.b64 _,[%2],8192;\n" \
                     "@p cp.async.bulk.shared::cluster.global.mbarrier::complete_tx::bytes [%0],[%1],8192,[%2];}" ::"r"(sb + XB + (w) * 16384 + (u) * 8192), \
                     "l"(g_h + (n) * 4096 + a * 2048 + (w) * 1024 + (u) * 512), "r"(sb + BARS + 64 + (w) * 8) : "memory")
#define lpub ((L16 & 0x30) * 64 + ((L16 >> 3) & 0x38))
#define lrow ((L16 & 0x70) + (((L16 >> 3) ^ L16) & 0x70 & ~((L16 >> 3) & 0x40) ? L16 & 0x180 : 512))

  const int role = __shfl_sync(~0u, threadIdx.x >> 7, 0);
  if (role < 2) {
    asm volatile("setmaxnreg.inc.sync.aligned.u32 %0;" ::"n"(RF_));
    ROLE_VARS
    uint32_t L16 = __shfl_sync(~0u, sb + (tid & 31) * 16, tid & 31);
    uint32_t wQ[16][4], wK[16][4], wV[NVR][4];
    uint32_t frag = sb + ((lane & 7) + (lane >> 4) * 8) * 128 + (((iw * 2 + ((lane >> 3) & 1)) ^ (lane & 7)) << 4);
#define QSW (SWP && !a ? 64 : 0)
    {
      const bool spare = b >= 128;
      const uint32_t t0 = gtime();
      uint4 xr[16];
      int seg = spare ? b - 126 : wg;
      const int half = spare ? wg : a;
      auto x_fetch = [&]() {
        const uint4* px = (const uint4*)x + (seg * 32 + iw * 8 + (lane >> 2)) * 128 + half * 64 + (lane & 3);
#pragma unroll
        for (int i = 0; i < 16; i++) xr[i] = __ldg(px + i * 4);
      };
      if (!spare) {
        uint4 wm[8];
        const uint4* pw = (const uint4*)(wmod + (size_t)((b >> 5) * 256 + (tid >> 3)) * 6144 + (b & 31) * 64) + (tid & 7);
        const float cs = __bfloat162float(cvec[(b >> 5) * 256 + tid]);
#pragma unroll
        for (int i = 0; i < 8; i++) wm[i] = __ldcs(pw + (size_t)i * 32 * 768);
        float* sc = (float*)(smem + PRE);
        sc[tid] = rbf(silu(cs));
        PT(1);
        BAR_SYNC(B_F, 256);
        float acc[8] = {0, 0, 0, 0, 0, 0, 0, 0};
#pragma unroll
        for (int i = 0; i < 8; i++) {
          const float f = sc[i * 32 + (tid >> 3)];
          acc[0] += f * blo(wm[i].x); acc[1] += f * bhi(wm[i].x); acc[2] += f * blo(wm[i].y); acc[3] += f * bhi(wm[i].y);
          acc[4] += f * blo(wm[i].z); acc[5] += f * bhi(wm[i].z); acc[6] += f * blo(wm[i].w); acc[7] += f * bhi(wm[i].w);
        }
#pragma unroll
        for (int i = 0; i < 8; i++) { acc[i] += __shfl_xor_sync(~0u, acc[i], 8); acc[i] += __shfl_xor_sync(~0u, acc[i], 16); }
        float* red = sc + 1024;
        if ((tid & 31) < 8) {
#pragma unroll
          for (int i = 0; i < 8; i++) red[(tid >> 5) * 64 + (tid & 7) * 8 + i] = acc[i];
        }
        BAR_SYNC(B_F, 256);
        PT(2);
        if (tid < 64) {
          float t = 0;
#pragma unroll
          for (int i = 0; i < 8; i++) t += red[i * 64 + tid];
          asm volatile("st.relaxed.gpu.global.u32 [%0],%1;" ::"l"((unsigned*)g_modp + (b >> 5) * 2048 + (b & 31) * 64 + tid), "r"(U_(t) | 1u) : "memory");
        }
      } else {
        asm volatile("griddepcontrol.launch_dependents;");
      }
      x_fetch();
      const uint32_t md = sb + PRE + 6144, rx = mapa(sb, a ^ !spare);
      asm volatile("barrier.cluster.wait.aligned;" ::: "memory");
      if (!spare) {
        mbar_wait(sb + BARS + 88, 0);
#pragma unroll
        for (int i = 0; i < 16; i++) ldsm4t(wQ[i], (frag ^ QSW) + WO + wg * 32768 + i * 2048);
      }
      PT(4);
#pragma unroll 1
      for (int it = 0;; it++) {
        if (tid == 0) mbar_expect(sb + BARS + 104, 512);
        float c[4][4] = {{0, 0, 0, 0}, {0, 0, 0, 0}, {0, 0, 0, 0}, {0, 0, 0, 0}};
#pragma unroll
        for (int i = 0; i < 16; i++) {
          mma16(c[(i & 1) * 2], xr[i].x, 0x3f803f80u, xr[i].y, 0x3f803f80u, xr[i].x, xr[i].y);
          mma16(c[(i & 1) * 2 + 1], xr[i].z, 0x3f803f80u, xr[i].w, 0x3f803f80u, xr[i].z, xr[i].w);
        }
#pragma unroll
        for (int e = 0; e < 4; e++) c[0][e] = (c[0][e] + c[1][e]) + (c[2][e] + c[3][e]);
        const int src = (lane & 28) + (lane >> 3);
        const float sq = __shfl_sync(~0u, (lane & 4) ? c[0][1] : c[0][0], src), sm = __shfl_sync(~0u, (lane & 4) ? c[0][3] : c[0][2], src);
        if ((lane & 3) < 2) sta1<0>(rx + PRE + 10240 + (wid ^ (spare * 4)) * 64 + (lane >> 2) * 8 + (lane & 1) * 4, U_((lane & 1) ? sm : sq), rx + BARS + 104);
        mbar_wait(sb + BARS + 104, it & 1);
        const float2 ot = lds2f(sb + PRE + 10240 + wid * 64 + (lane >> 2) * 8);
        const float mean = (sm + ot.y) * (1.f / 1024);
        const float rs = rsqrtf(fmaxf((sq + ot.x) * (1.f / 1024) - mean * mean, 0.f) + 1e-5f), nm = -mean * rs;
        const uint32_t rh = pk(rs, rs), rl = pk(rs - blo(rh), rs - blo(rh)), n2 = pk(nm, nm);
#define NRM(v) v = fmabf(v, rh, fmabf(v, rl, n2))
#pragma unroll
        for (int i = 0; i < 16; i++) { NRM(xr[i].x); NRM(xr[i].y); NRM(xr[i].z); NRM(xr[i].w); }
        if (!it) {
          PT(3);
#pragma unroll 1
          for (int i = 0; i < 2; i++) {
            uint4 p[4];
            for (int n = 0;; n++) {
#pragma unroll
              for (int e = 0; e < 4; e++) p[e] = ldg_rlx4(g_modp + e * 512 + i * 256 + tid);
              uint32_t ok = 1;
#pragma unroll
              for (int e = 0; e < 4; e++) ok &= p[e].x & p[e].y & p[e].z & p[e].w;
              if (__all_sync(~0u, ok) || n > SPIN_LIMIT / 16) break;
              __nanosleep(100);
            }
#define MSUM(e) (i + rbf((F_(p[0].e) + F_(p[1].e)) + (F_(p[2].e) + F_(p[3].e))))
            sts2(md + i * 2048 + tid * 8, pk(MSUM(x), MSUM(y)), pk(MSUM(z), MSUM(w)));
          }
          BAR_SYNC(B_F, 256);
          PT(5);
        }
        const int e0 = (iw * 8 + (lane >> 2)) * 8 + ((lane & 3) ^ (lane >> 2));
        uint4* dst = g_h + seg * 4096 + half * 2048;
#pragma unroll
        for (int i = 0; i < 16; i++) {
          const uint32_t ma = md + half * 1024 + (lane & 3) * 16 + i * 64;
          const uint4 sv = lds4(ma), cv = lds4(ma + 2048);
          xr[i] = make_uint4(fmabf(xr[i].x, cv.x, sv.x), fmabf(xr[i].y, cv.y, sv.y), fmabf(xr[i].z, cv.z, sv.z), fmabf(xr[i].w, cv.w, sv.w));
        }
        if (!spare) {
#pragma unroll
          for (int i = 0; i < 16; i++) sts4(sb + WO + wg * 32768 + (e0 ^ ((i & 1) * 4)) * 16 + (i >> 1) * 4096, xr[i].x, xr[i].y, xr[i].z, xr[i].w);
          break;
        }
#pragma unroll
        for (int i = 0; i < 16; i++) dst[(e0 ^ ((i & 1) * 4)) + (i >> 1) * 256] = xr[i];
        seg += 4;
        if (seg < 64) x_fetch();
        FENCE_ASYNC();
        BAR_SYNC(B_F, 256);
        if (tid == 0) red_rlx(g_hf + b - 128);
        if (seg >= 64) break;
      }
      if (spare) { rec_helper(sb, cvec, wmod, w1, b1, t0); return; }
      PH(1); PH(2); PT(6);
    }
    ROLE_REFRESH
#define ownv ((iw >> 1) == a)
#define owner (SWP ? iw >= 2 : ownv)
#define vfin ((wid >> 1) == a)
#define oi (wid & 1)
    {
      const uint32_t rsb = mapa(sb, owner ? a : a ^ 1);
      const uint32_t pp = rsb + PK + (owner ? 0 : 12288) + (oi * 2048 + wg * 1024) + l16;
      const uint32_t mb = sb + MEM + wg * 5120;
      sts4(L16 + TF + wid * 512, mb + lrow, owner ? L16 + (lane >> 4) * (RK - RQ - 256) + RQ + oi * 1024 + wg * 256 : rsb + RQ + oi * 1024 + 512 + wg * 256 + (l16 >> 2),
           L16 + OB, frag + wg * NVS * 2048);
      sts4(L16 + TF + 4096 + wid * 512, sb + WO + (wid >> 1) * 16384 + ((lane & 7) + (lane >> 4) * 8) * 128 + ((((wid & 1) * 4 + ((lane >> 3) & 1)) ^ (lane & 7)) << 4),
           sb + ARO + wid * 640 + lrow, pp, LO(xc) + h * 262144 + (bb * 2 + (iw >> 1)) * XC + X_VM(0) + oi * 2048 + a * 256 + (l16 >> 1));
    }
    uint32_t tp = L16 + TF + wid * 512;
    auto park_ptr = [&]() { return lds1(tp + 4096 + 8); };
    auto park_w = [&](const uint32_t* w, int m, uint32_t d) {
      if (SWP && m == 2) d += (sb & 0x1000000) ? 0 : owner ? 0x1003000 : -0x1003000;
      if (m == 2 ? ownv : owner) {
        sts4(d + m * 4096, w[0], w[1], w[2], w[3]); sts4(d + m * 4096 + 512, w[4], w[5], w[6], w[7]);
      } else {
        const uint32_t pb = (d & 0xff000000u) | (1024 + BARS + (m ? 24 + m * 8 : 16));
        sta4(d + m * 4096, w, pb); sta4(d + m * 4096 + 512, w + 4, pb);
      }
    };
    auto park = [&](const float* f, int m, int n, uint32_t d) {
      uint32_t w[8];
#pragma unroll
      for (int i = 0; i < 8; i++) w[i] = pk(f[2 * i], f[2 * i + 1]);
      park_w(w, m, d);
    };
#define D64(lo) (0x4000004000000000ull | (uint32_t)(lo))
#define XD(i) D64(x | (((i) >> 2) * 256 + ((i) & 3) * 2))
    auto xdesc = [&](uint32_t xb) { return ((uint32_t)__shfl_sync(~0u, 1024 + xb + wg * 16384, 0) >> 4) | 0x10000u; };
    auto rs_issue = [&](float* acc, const uint32_t (&w)[16][4], uint32_t xb, bool fence) {
      const uint32_t x = xdesc(xb);
      if (fence) WG_FENCE();
      wgmma_rs_n32_z(acc, w[0], XD(0));
#pragma unroll
      for (int i = 1; i < 16; i++) wgmma_rs_n32(acc, w[i], XD(i), 1);
      WG_COMMIT();
    };
    auto v_issue = [&](float* acc, uint32_t xb, bool fence) {
      const uint32_t dv = ((uint32_t)__shfl_sync(~0u, 1024 + WVS + wg * NVS * 2048, 0) >> 4) | 0x10000u, x = xdesc(xb);
      if (fence) WG_FENCE();
      wgmma_rs_n32_z(acc, wV[0], XD(0));
#pragma unroll
      for (int i = 1; i < VRF; i++) wgmma_rs_n32(acc, wV[i], XD(i), 1);
#pragma unroll
      for (int i = NVR; i < 16; i++) wgmma_ssT_n32(acc, D64(dv + (i - NVR) * 128), XD(i), 1);
#pragma unroll
      for (int i = VRF; i < NVR; i++) wgmma_rs_n32(acc, wV[i], XD(i), 1);
      WG_COMMIT();
    };
    uint32_t mA, vP[2][4];
#define V_AHEAD mA = lds1(tp); frag = lds1(tp + 12); ldsm4t(vP[0], frag + WVS + (15 - NVR) * 2048); ldsm4t(vP[1], frag + WVS + (14 - NVR) * 2048);
    auto vk_pass = [&](int n, uint32_t d, uint32_t xb, bool steady, auto between) {
      float acc[16], acc2[16];
      v_issue(acc, xb, true);
      rs_issue(acc2, wK, xb, false);
      between();
      if (steady || n) mbar_wait(sb + BARS + 80, (n - 1) & 1);
      WG_WAIT(1);
      park(acc, 2 - !!KVO, n, d);
      if (steady) BAR_ARRIVE(B_K, 320);
      V_AHEAD
      WG_WAIT(0);
      park(acc2, 1 + !!KVO, n, d + (VPC ? (vP[1][0] ^ mA) & dZ : 0));
    };
    uint32_t q0[8], q1[8];
    {
      float acc[16], acc2[16];
      FENCE_ASYNC_SMEM();
      BAR_SYNC(B_F, 256);
      rs_issue(acc, wQ, WO, true);
      rs_issue(acc2, wQ, WO + 32768, false);
      WG_WAIT(0);
#pragma unroll
      for (int i = 0; i < 8; i++) { q0[i] = pk(acc[2 * i], acc[2 * i + 1]); q1[i] = pk(acc2[2 * i], acc2[2 * i + 1]); }
    }
    mbar_wait(wbar, 0);
    PT(7);
#pragma unroll
    for (int i = 0; i < 16; i++) ldsm4t(wK[i], (frag ^ QSW) + XB + wg * 32768 + i * 2048);
#pragma unroll
    for (int i = 0; i < NVR; i++) ldsm4t(wV[i], frag + MEM + (wg * NVR + i) * 2048);
    FENCE_ASYNC_SMEM();
    PH(3); PT(8);
    CLUSTER_SYNC();
    PT(9);
    frag += wg * NVS * 2048;
    park_w(q0, 0, park_ptr());
    PT(10);
#pragma unroll 1
    for (int n = 0; n < 2; n++) {
      asm volatile("" : "+r"(wid));
      vk_pass(n, park_ptr(), n * XB, false, [&]() {
        if (n) {
          BAR_SYNC(B_C, 320);
          PT(12);
          mbar_wait(sb + BARS + 24, 0);
          park_w(q1, 0, park_ptr());
        }
      });
      if (n) break;
      PT(11);
      BAR_SYNC(B_C, 448);
      if (tid == 0) {
        mbar_expect(obar, 65536);
#pragma unroll 1
        for (int i = 0; i < 4; i++) tma2d(sb + WO + i * 16384, &mp.wo, j * 256 + i * 64, h * 128, obar);
      }
    }
    static_assert(WO == 0, "x");
    {
      BAR_ARRIVE(B_P, N_P); if (!HX) BAR_ARRIVE(B_X, 320); if (XE != 1) BAR_ARRIVE(B_Q, 288);
    }
    PT(13);
    if (!OBL) mbar_wait(obar, 0);
    PH(4); RS(1); PT(14);
    ROLE_REFRESH
    for (int s = 0; s < 64; s++) {
      asm volatile("" : "+r"(tp), "+r"(wid));
      asm volatile("mov.u32 %0,%%cluster_ctarank;" : "=r"(b));
      uint32_t vS[NVS][4], bf[8][4];
      static_assert(NVR == 5, "schedule");
#define VLD(k) ldsm4t(vS[(k) - NVR], frag + WVS + ((k) - NVR) * 2048)
#define BLD(t) ldsm4t(bf[t], mA + (t) * 640)
#define VMMA(c, w, i) mma16(c, (w)[0], (w)[1], (w)[2], (w)[3], bf[(i) >> 1][((i) & 1) * 2], bf[(i) >> 1][((i) & 1) * 2 + 1])
#define VS_(c, k) VMMA(c, vS[(k) - NVR], k)
#define QK(i) VMMA(cQ, wQ[i], i); VMMA(cK, wK[i], i)
#define PREV if (NF) { VLD(13); VLD(12); if (NF > 2) VLD(11); } else { VLD(15); VLD(14); }
      if (s > 0) BAR_SYNC(B_R, N_R);
      float cV[4] = {0, 0, 0, 0}, cW[4] = {0, 0, 0, 0};
      {
        float cQ[4] = {0, 0, 0, 0}, cK[4] = {0, 0, 0, 0};
        BLD(7); BLD(6); BLD(5); BLD(4); if (NB0 > 4) BLD(3);
        SCHED_FENCE(47);
        QK(15); VMMA(cV, vP[0], 15);
        QK(14); VMMA(cV, vP[1], 14);
        QK(13); QK(12);
        SCHED_FENCE(51);
        if (NB0 < 5) BLD(3);
        BLD(2); BLD(1); BLD(0);
        const uint32_t rm = lds1(tp + 4);
        if (!NF) frag = lds1(tp + 12);
        QK(11); QK(10); QK(9); QK(8); QK(7);
        if (PV0 == 6) { SCHED_FENCE(48); PREV }
        QK(6); QK(5);
        if (PV0 == 4) { QK(4); SCHED_FENCE(48); PREV } else { QK(4); }
        QK(3); QK(2); QK(1); QK(0);
        const uint32_t w0 = pk(cQ[0] * SCS, cQ[1] * SCS), w1 = pk(cQ[2] * SCS, cQ[3] * SCS), w2 = pk(cK[0], cK[1]), w3 = pk(cK[2], cK[3]);
        if (owner) {
          stsm4(rm, w0, w1, w2, w3);
          BAR_ARRIVE(B_E, 256);
        } else {
          const uint32_t mm = (rm & 0xff000000u) | (1024 + BARS);
          sta1<0>(rm, w0, mm); sta1<128>(rm, w1, mm);
          sta1<RK - RQ>(rm, w2, mm); sta1<RK - RQ + 128>(rm, w3, mm);
        }
        if (wid == 2) TS(0);
      }
      uint4 t1;
      uint32_t oA, wo[16][4];
      {
        if (NF == 0) {
          VLD(13); VLD(12);
          VS_(cW, 15); VS_(cV, 14); VLD(11); VMMA(cW, wV[0], 0); VLD(10); VMMA(cV, wV[1], 1); VLD(9);
          VMMA(cW, wV[2], 2); VLD(8); VMMA(cV, wV[3], 3); VLD(7); VMMA(cW, wV[4], 4); VS_(cV, 13); VLD(6); VS_(cW, 12); VLD(5);
          VS_(cV, 11);
        } else {
          if (NF < 3) VLD(11);
          VLD(10);
          VS_(cW, 13); VLD(9); VS_(cV, 12); VLD(8); VLD(7); VMMA(cW, wV[0], 0); VMMA(cV, wV[1], 1); VLD(6);
          VMMA(cW, wV[2], 2); VMMA(cV, wV[3], 3); VLD(5); VMMA(cW, wV[4], 4); VS_(cV, 11);
        }
        VS_(cW, 10); VS_(cV, 9); VS_(cW, 8); VS_(cV, 7); VS_(cW, 6); VS_(cV, 5);
#pragma unroll
        for (int e = 0; e < 4; e++) cV[e] += cW[e];
        const uint32_t ex = tp + (RX - TF) - wg * 2048;
        t1 = lds4(tp + 4096 + (T1L ? vS[3][0] & dZ : 0));
        oA = lds1(tp + 8 + (s & dZ));
        if (wg) {
          sts4(ex, U_(cV[0]), U_(cV[1]), U_(cV[2]), U_(cV[3]));
          BAR_ARRIVE(B_T2, 256);
        }
#pragma unroll
        for (int i = 0; i < VCO; i++) ldsm4t(wo[i], (t1.x ^ ((i & 1) * 32)) + (i >> 1) * 2048);
        if (!wg) {
          BAR_SYNC(B_T2, 256);
          const float4 u = lds4f(ex);
          stg_b64(mkp(t1.w ^ ((s & 1) * X_RING), HI(xc)), (pk(cV[0] + u.x, cV[1] + u.y) & ~1u) | (((s >> 1) + 1) & 1), pk(cV[2] + u.z, cV[3] + u.w));
        }
      }
      if (s == 63) break;
      if (OBL && s == 0) mbar_wait(obar, 0);
      {
        const uint32_t woA = t1.x, woB = woA ^ 32;
#pragma unroll
        for (int i = VCO; i < NW0; i++) ldsm4t(wo[i], ((i & 1) ? woB : woA) + (i >= WCH ? wo[(i - WCH + NWP) % NWP][0] & dZ : 0) + (i >> 1) * 2048);
        BAR_SYNC(B_S, 416);
        float inv0, inv1;
        uint32_t p[4], pm;
        const uint32_t pa = oA + (SC - OB), one = 0x3f803f80u;
#define P_LOAD ldsm4t(p, pa); asm volatile("ldmatrix.sync.aligned.m8n8.x1.trans.shared.b16 {%0},[%1];" : "=r"(pm) : "r"(pa + 512) : "memory");
        if (s < 62) {
          float acc[16];
          rs_issue(acc, wQ, XB, true);
          mbar_wait(sb + BARS + 24, (s + 1) & 1);
          WG_WAIT(0);
          uint32_t qw[8];
#pragma unroll
          for (int i = 0; i < 8; i++) qw[i] = pk(acc[2 * i], acc[2 * i + 1]);
#pragma unroll
          for (int i = NW0; i < NW1; i++) ldsm4t(wo[i], ((i & 1) ? woB : woA) + (i >> 1) * 2048);
          BAR_SYNC(B_V, N_V);
          if (RSO) { P_LOAD }
          park_w(qw, 0, t1.z + (RSO == 1 ? pm & dZ : 0));
        } else {
#pragma unroll
          for (int i = NW0; i < NW1; i++) ldsm4t(wo[i], ((i & 1) ? woB : woA) + (i >> 1) * 2048);
          BAR_SYNC(B_V, N_V);
          if (RSO) { P_LOAD }
        }
#pragma unroll
        for (int i = NW1; i < NWP; i++) ldsm4t(wo[i], ((i & 1) ? woB : woA) + (i >> 1) * 2048);
        {
          float sum[4] = {0, 0, 0, 0}, su2[4] = {0, 0, 0, 0};
          if (!RSO) { P_LOAD }
          mma16(sum, one, one, one, one, p[0], p[1]);
          mma16(su2, one, one, one, one, p[2], p[3]);
          mma8(sum, one, one, pm);
          inv0 = sum[0] + su2[0]; inv1 = sum[1] + su2[1];
          SCHED_FENCE(57);
        }
        BAR_SYNC(B_O, N_O);
        float c[2][4] = {{0, 0, 0, 0}, {0, 0, 0, 0}};
        uint32_t o[4][4];
#pragma unroll
        for (int i = 0; i < NOP_; i++) ldsm4t(o[i], oA + i * 512);
        SCHED_FENCE(46);
        asm("rcp.approx.ftz.f32 %0,%0;" : "+f"(inv0));
        asm("rcp.approx.ftz.f32 %0,%0;" : "+f"(inv1));
#pragma unroll
        for (int i = 0; i < 16; i++) {
          mma16(c[i & 1], wo[i][0], wo[i][1], wo[i][2], wo[i][3], o[i >> 2][i & 2], o[i >> 2][(i & 2) + 1]);
          if (i == 1 && NOP_ < 3) ldsm4t(o[2], oA + 1024);
          if (i == 3 && NOP_ < 4) ldsm4t(o[3], oA + 1536);
          if (i + NWP < 16) ldsm4t(wo[(i + NWP) & 15], (((i + NWP) & 1) ? woB : woA) + ((i + NWP) >> 1) * 2048);
        }
        stsm4(t1.y, pk(c[0][0] * inv0, c[0][1] * inv1), pk(c[0][2] * inv0, c[0][3] * inv1), pk(c[1][0] * inv0, c[1][1] * inv1), pk(c[1][2] * inv0, c[1][3] * inv1));
      }
      const uint32_t d = park_ptr();
      BAR_SYNC(B_W, 384);
      if (s < 62) {
        vk_pass(s + 2, d, XB, true, []() {});
        if (XE == 2) BAR_ARRIVE(B_Q, 288);
        BAR_ARRIVE(B_P, N_P); if (!HX) BAR_ARRIVE(B_X, 320);
        TS(10);
      } else {
        V_AHEAD
        CONSUME(vP[1][0]);
      }
    }
  } else if (role == 3) {
    asm volatile("setmaxnreg.dec.sync.aligned.u32 24;");
    if (blockIdx.x >= 128) return;
    ROLE_VARS
    const uint32_t L16 = sb + (tid & 31) * 16;
    asm volatile("barrier.cluster.wait.aligned;" ::: "memory");
    CLUSTER_SYNC();
    sts1(sb + PACE + 36, LO(xc) + h * 262144 + X_VM(0));
    auto vm_stage = [&](int s) {
      if (AV) return;
      const uint32_t tag = ((s >> 1) + 1) & 1;
      const char* xm = mkp(lds1(sb + PACE + 36) + (s & 1) * X_RING + iw * XC + (l16 >> 1), HI(xc));
      uint2 m[4];
      CONSUME(LO(xm));
      BAR_SYNC(B_S2, 256);
      if (dZ2 > 1) { const uint32_t c = clk(); while (clk() - c < (uint32_t)dZ2) {} }
      int it = 0;
      while (true) {
#pragma unroll
        for (int i = 0; i < 4; i++) m[i] = ldg_b64(xm + (i >> 1) * 2048 + (i & 1) * 256);
        sts4(L16 + VN + iw * 512, m[0].x, m[0].y, m[1].x, m[1].y);
        sts4(L16 + VN + iw * 512 + 2048, m[2].x, m[2].y, m[3].x, m[3].y);
        if (HV || !anybad(m[0].x, m[1].x, m[2].x, m[3].x, tag)) break;
        RP(2);
        if (++it > SPIN_LIMIT) __trap();
      }
      if (s < 63) BAR_ARRIVE(B_V, 512); else BAR_ARRIVE(B_V, 256);
    };
    if (iw == 0) {
      wait_cnt(&g_hcnt, 128);
#pragma unroll 1
      for (int s = 0; s < 63; s++) {
        if (s < 62) for (int it = 0; ldg_rlx1(g_hf + (s & 3)) <= (s >> 2); it++) if (it > SPIN_LIMIT) __trap();
        if (XE == 1) BAR_SYNC(B_P, N_P); else if (XE == 2) BAR_SYNC(B_Q, 288); else if (s) BAR_SYNC(B_R, 320); else BAR_SYNC(B_Q, 288);
        if (s < 62) { X_LOAD(s + 2, 0, 0); X_LOAD(s + 2, 1, 0); X_LOAD(s + 2, 0, 1); X_LOAD(s + 2, 1, 1); }
        if (s >= 7) {
          const uint32_t zo = b * 160 + l16;
          if (l16 < 160) CONSUME(exch_b128(xc + AR_OFF + AR_ROW(zo >> 7) * 1024 + (zo & 127) + ((s + 1) & 7) * 128, 0, 0, 0, 0).x);
          __syncwarp();
        }
        if (s < 62) { mbar_wait(sb + BARS + 64, s & 1); mbar_wait(sb + BARS + 72, s & 1); }
        BAR_ARRIVE(B_S, 416);
        vm_stage(s);
        if (!AV) BAR_ARRIVE(B_O, 416);
        BAR_SYNC(B_W, 384);
        FENCE_ASYNC_SMEM();
        asm volatile("{.reg .pred p; elect.sync _|p, 0xffffffff; @p cp.reduce.async.bulk.tensor.3d.global.shared::cta.add.bulk_group [%0,{%1,%2,%4}],[%3];}"
                     ::"l"(&mp.ari), "r"((s & 7) * 64), "r"(AR_R(j)), "r"(sb + ARO), "r"(AR_P(j)) : "memory");
        BULK_COMMIT();
        asm volatile("st.relaxed.gpu.global.u32 [%0],%1;" ::"l"(g_tm + (s & 1) * 128 + b), "r"(gtime()) : "memory");
        TS(3);
        BULK_WAIT_READ(0);
      }
      if (!XE) BAR_ARRIVE(B_R, 320);
    } else if (iw == 1) {
      const uint32_t pc = sb + MEM + (lane >> 2) * 640 + (lane & 3) * 144 + (lane & 12), pd = sb + MEM + (lane & 15) * 640 + 576 + (lane & 3) * 16 + (lane & 12);
      uint32_t T = 0, par = 0;
      int est = dA;
#pragma unroll 1
      for (int s = 0; s < 63; s++) {
        if (s) {
          const uint4 tm = ldg_rlx4((const char*)g_tm + ((s + 1) & 1) * 512 + l16);
          const int t0 = tm.x - T, t1 = tm.y - T, t2 = tm.z - T, t3 = tm.w - T;
          const int e = max(dF + (__reduce_add_sync(~0u, (t0 + t1) + (t2 + t3)) >> 7), dV + __reduce_max_sync(~0u, max(max(t0, t1), max(t2, t3))));
          if (s > 1) est += max(min(e >> 2, dP), -dP);
          T += (s == 1 || e > dM ? e : 0) + est;
        }
        vm_stage(s);
        BAR_SYNC(B_W, 384);
        SCHED_FENCE(70);
        const uint32_t tW = gtime();
        if (s == 0) T = tW + 800;
        const uint32_t te = tW + min(max((int)(T - tW), dD), 2000);
        while ((int)(gtime() - te) < 0) {}
        TS(7);
        int it = 0;
        while (true) {
          ar_fetch(sb + MEM, &mp.ari, s & 7, a, sb + BARS + 112);
          mbar_wait(sb + BARS + 112, par);
          par ^= 1;
          const uint32_t n0 = lds1(pc), n1 = lds1(pc + 5120), n2 = lds1(pd);
          if (!__any_sync(~0u, (tagbad(n0, n1, 0x42004200) | (n2 ^ 0x42004200)) != 0)) break;
          RP(0);
          if (++it > SPIN_LIMIT) __trap();
        }
        BAR_ARRIVE(B_R, N_R);
        TS(11);
      }
    } else {
#define V_LOAD(n) do { if (lane == 0) mbar_expect(sb + BARS + 8, 8192); __syncwarp(); \
        if (lane < 16) bulk_ld(sb + ((lane & 2) ? VX1 : VX0) + (lane & 1) * 2048 + (lane >> 2) * 512, \
                               xc + h * 262144 + V_RING(n) + (lane >> 2) * XC + X_VX(lane & 3), 512, sb + BARS + 8); __syncwarp(); } while (0)
      uint32_t src = L16 + PK + (iw & 1) * 2048;
#define qd (L16 + (lane >> 4) * 256 + QT + (iw & 1) * 1024)
#define vd (LO(xc) + h * 262144 + j * XC + (iw & 1) * 2048 + l16)
#define FINISH [&](int n, int m) { \
_Pragma("unroll") \
        for (int i = 1; i >= 0; i--) { \
          const uint32_t p = src + m * 4096 + i * 512; \
          uint4 u = lds4(p); \
          const uint4 w = lds4(p + 1024), y = lds4(p + 12288), z = lds4(p + 13312); \
          u = make_uint4(sum4bf(u.x, w.x, y.x, z.x), sum4bf(u.y, w.y, y.y, z.y), sum4bf(u.z, w.z, y.z, z.z), sum4bf(u.w, w.w, y.w, z.w)); \
          if (m == 2) stg_b128(mkp(vd ^ V_RING(n), HI(xc)) + i * 512, (u.x & ~1u) | V_TAG(n), u.y, u.z, u.w); \
          else stsm4(qd + (n & 1) * 4096 + m * 2048 + i * 256, u.x, u.z, u.y, u.w); \
          SCHED_FENCE(71 + m * 2 + i); \
        } \
      }
#pragma unroll 1
      for (int n = 0; n < 64; n++) {
        src = PIN(src);
        b = __shfl_sync(~0u, lds1(sb + PACE + 24), 0);
        const uint32_t L16 = src - PK - (iw & 1) * 2048;
        auto finish = FINISH;
        if (n < 2) { if (n) BAR_SYNC(B_X, 320); else BAR_SYNC(B_C, 448); }
        mbar_wait(sb + BARS + 16, n & 1);
        finish(n, 0);
        __syncwarp();
        if (lane == 0) mbar_arrive_cl(mapa(sb, a ^ 1) + BARS + 24);
        if (n > 1) BAR_SYNC(B_K, 320);
        mbar_wait(sb + BARS + (KVO ? 32 : 40), n & 1);
        finish(n, 2 - !!KVO);
        if (n > 1) BAR_SYNC(B_X, 320);
        mbar_wait(sb + BARS + (KVO ? 40 : 32), n & 1);
        finish(n, 1 + !!KVO);
        BAR_SYNC(B_T, 64);
        if (lane == 0) {
          if (iw == 2 && n < 63) { mbar_expect(sb + BARS + 16, 4096); mbar_expect(sb + BARS + 32, 4096); mbar_expect(sb + BARS + 40, 4096); }
          mbar_arrive_cl(mapa(sb, a ^ 1) + BARS + 80);
        }
        __syncwarp();
        if (n) {
          vm_stage(n - 1);
          BAR_SYNC(B_W, 384);
        } else {
          BAR_SYNC(B_C, 320);
        }
        if (iw == 2) V_LOAD(n);
      }
#undef qd
#undef vd
    }
    { ROLE_REFRESH }
    vm_stage(63);
  } else {
    asm volatile("setmaxnreg.dec.sync.aligned.u32 %0;" ::"n"(RA_));
    if (blockIdx.x >= 128) { if (threadIdx.x == 256) rec_prefetch((const char*)wmod, w1, (const char*)x, wo); return; }
    ROLE_VARS
    uint32_t L16 = __shfl_sync(~0u, sb + (tid & 31) * 16, tid & 31);
    const uint32_t ts = gtime();
    uint2 m0[8];
#pragma unroll
    for (int r = 0; r < 8; r++) m0[r] = *(const uint2*)(mem0 + r * 1024 + a * 512 + (tid - 256) * 4);
    if (wid == 9) {
#pragma unroll 1
      for (int i = b * 80 + (tid & 31); i < b * 80 + 80; i += 32) ((uint4*)(xc + AR_OFF))[AR_ROW(i >> 6) * 64 + (i & 63)] = make_uint4(0, 0, 0, 0);
      if (b == 0) g_fin = 0;
      FENCE_ASYNC();
      __syncwarp();
      if (tid == 288) red_rlx(&g_hcnt);
    }
    if (tid == 256) {
      const int col = h * 128 + bb * 64;
#pragma unroll 1
      for (int c = 0, w = 0; w < 12; c++) {
#pragma unroll 1
        for (; w <= c - (c < WC0 ? 2 : 3); w++) {
          mbar_wait(sb + PACE + (w % 3) * 8, (w / 3) & 1);
          PT(18 + w);
          if (w == 3) asm volatile("mbarrier.arrive.shared.b64 _,[%0];" ::"r"(sb + BARS + 88) : "memory");
        }
        const uint32_t mb = sb + PACE + (c % 3) * 8;
        if (c >= 12 && c < 12 + WPE) tma2d_pf(&mp.wo, j * 256 + (c - 12) * 64, h * 128);
        if (c >= 12) continue;
        mbar_expect(mb, 16384);
        if (c < 8) tma2d(sb + (c >> 2) * XB + (c & 3) * 16384, (c & 4) ? &mp.wk : &mp.wq, col, a * 512 + (c & 3) * 128, mb);
        else
#pragma unroll 1
          for (int i = (c & 1) * 8; i < (c & 1) * 8 + 8; i++) {
            const int w = (c - 8) >> 1;
            tma2d(i < NVR ? sb + MEM + (w * NVR + i) * 2048 : sb + WVS + (w * NVS + i - NVR) * 2048, &mp.wv, col, a * 512 + w * 256 + i * 16, mb);
          }
      }
      asm volatile("mbarrier.arrive.shared.b64 _,[%0];" ::"r"(wbar) : "memory");
      for (int i = 0; i < 3; i++) asm volatile("mbarrier.inval.shared.b64 [%0];" ::"r"(sb + PACE + i * 8) : "memory");
    }
    __syncwarp();
    asm volatile("barrier.cluster.wait.aligned;" ::: "memory");
    CLUSTER_SYNC();
#pragma unroll 4
    for (int i = 0; i < 16; i++) {
      const uint4 v = lds4(L16 + WO + 32768 + iw * 8192 + i * 512);
      sts4(L16 + XB + iw * 8192 + i * 512, v.x, v.y, v.z, v.w);
    }
#pragma unroll
    for (int i = 0; i < 4; i++) {
      const int k = (tid - 256) * 4 + i, m = (k >> 3) & 3, r = k & 7;
#define M0W(r) __byte_perm((i & 2) ? m0[r].y : m0[r].x, (i & 2) ? m0[r + 1].y : m0[r + 1].x, (i & 1) ? 0x7632 : 0x5410)
      sts4(sb + MEM + (k >> 5) * 640 + (r == m ? 512 : m * 128) + r * 16, M0W(0), M0W(2), M0W(4), M0W(6));
    }
#pragma unroll 1
    for (int i = tid - 256; i < 192; i += 128) {
      const uint32_t c = i < 128 ? 0x42004200 : 0x3f803f80;
      sts4(sb + MEM + (i >> 3) * 640 + ((i & 7) < 4 ? (i & 7) * 144 : 512 + (i & 7) * 16), c, c, c, c);
    }
    static_assert(ARO == MEM + 16 * 640, "counters");
    FENCE_ASYNC_SMEM();
    BAR_ARRIVE(B_C, 448);
    if (WPF && tid == 256) {
      wait_time(ts + WPF);
#pragma unroll 1
      for (int c = WPE; c < 4; c++) tma2d_pf(&mp.wo, j * 256 + c * 64, h * 128);
    }
    __syncwarp();
#define pr (L16 + SC)
    {
      const int lim = j * 8 + iw * 2 - (lane & 7) - (lane & 8) * 2;
      const bool mk = L16 & 256;
      const int rw = lane >> 2;
      sts4(L16 + TA + iw * 512,
           iw != 2 ? L16 + KT + (iw & 1) * 256 + (lane >> 4) * 256 : sb + RK + (L16 & 0x80) * 2 + ((L16 >> 1) & 0x80) + (L16 & 0x70),
           L16 + QT + (lane >> 3) * 384, sb + SC + min(lane >> 3, 2) * 256 + (L16 & 0x70) + iw * 4, L16 + (lane >> 4) * 256 + QT + (iw >> 1) * 1024 + (iw & 1) * 256);
      sts4(L16 + TA + 2048 + iw * 512, mk ? 0u : (lim < 0 ? 0xfc00u : 0u) | (lim < -1 ? 0xfc000000u : 0u),
           mk ? 0xfc00fc00u : (lim < 8 ? 0xfc00u : 0u) | (lim < 7 ? 0xfc000000u : 0u),
           ((h * 2 + (iw >> 1)) * 1024 + (j * 8 + rw) * 8 + (((iw & 1) * 4 + (lane & 3)) ^ rw)) * 16, sb + OT + iw * 512 + (L16 & 0x70) * 4 + ((L16 >> 3) & 0x30));
    }
    {
      const uint32_t xh = LO(xc) + h * 262144, xs = xh + X_SC + iw * 1024 + min(lane, 16 + (lane & 7)) * 8;
      sts4(L16 + TA + 4096 + iw * 512, xh + X_SC + j * 256 + iw * 64 + lpub, xs, dS, iw != 2 ? 0 : U_(SCS));
      sts1(L16 + TA + 12 + iw * 512, xs + X_TOK + j * 4096);
    }
    uint32_t tA = L16 + TA + iw * 512;
#define tw (tA - L16 != TA + 1024)
#define XP_(lo) mkp(lo, HI(xc))
    auto publish = [&](char* d, const uint2& w) { stg_b64(d, w.x, w.y); };
    BAR_SYNC(B_P, N_P);
    for (int s = 0; s < 64; s++) {
      asm volatile("" : "+r"(L16), "+r"(tA));
      const uint32_t tag = ((s >> 1) + 1) & 1, ring = (s & 1) * X_RING;
      const uint4 t0 = lds4(tA);
      const uint4 tx = lds4(tA + 4096);
      const uint32_t xo = tx.x ^ ring, xs = tx.y ^ ring;
      const float gm = F_(tx.w);
      const uint32_t qA = t0.y + (ring >> 5);
      uint32_t c0;
      uint2 ts[4];
      uint4 v[4];
      uint32_t af[2][4], qt[4][4];
      {
        const uint32_t aA = t0.x + (tw ? ring >> 5 : 0);
        uint32_t ql[2][4], qr[2][4];
        uint2 pw_;
        float c[4] = {0, 0, 0, 0}, d[4] = {0, 0, 0, 0};
        if (s == PDS) asm volatile("griddepcontrol.launch_dependents;");
#pragma unroll
        for (int i = 0; i < 4; i++) ldsm4t(qt[i], qA + i * 128);
        mbar_wait(sb + BARS + 8, s & 1);
        TS(4);
        BAR_SYNC(B_E, 256);
#define PACK(c) make_uint2(pkh(fmaf(c[2], gm, c[0] * SCS), fmaf(c[3], gm, c[1] * SCS), tag), pkh(c[2] * SCS, c[3] * SCS, tag))
#define SMMA(x, t, q, i) mma16(x, af[t][0], af[t][1], af[t][2], af[t][3], q[t][i], q[t][i + 1])
        ldsm4t(ql[0], L16 + RQ); ldsm4t(ql[1], L16 + RQ + 1024); ldsm4t(af[0], aA); ldsm4t(af[1], aA + 1024);
        CONSUME(xo);
#define QSUM(t, i) addbf(addbf(ql[t][i], ql[t][i + 2]), addbf(qr[t][i], qr[t][i + 2]))
#define STAIL mma16(c, af[0][0], af[0][1], af[0][2], af[0][3], QSUM(0, 0), QSUM(0, 1)); mma16(d, af[1][0], af[1][1], af[1][2], af[1][3], QSUM(1, 0), QSUM(1, 1));
        if (tw) {
          mbar_wait(sb + BARS, s & 1);
          TS(8);
          ldsm4t(qr[0], L16 + RQ + 512); ldsm4t(qr[1], L16 + RQ + 1536);
          STAIL
          pw_ = make_uint2(pkh(c[0] + d[0], c[1] + d[1], tag), pkh(c[2] + d[2], c[3] + d[3], tag));
        } else {
          uint32_t ar[2][4];
          mbar_wait(sb + BARS, s & 1);
          ldsm4t(qr[0], L16 + RQ + 512); ldsm4t(ar[0], aA + 512); ldsm4t(qr[1], L16 + RQ + 1536); ldsm4t(ar[1], aA + 1536);
#pragma unroll
          for (int i = 0; i < 8; i++) af[i >> 2][i & 3] = addbf(af[i >> 2][i & 3], ar[i >> 2][i & 3]);
          STAIL
          pw_.x = pw_.y = pkh((c[0] + c[2]) + (d[0] + d[2]), (c[1] + c[3]) + (d[1] + d[3]), tag);
        }
        publish(XP_(xo), pw_);
        c0 = clk() + tx.z;
        TS(1);
      }
      uint2 r[4];
      bool vbad;
      uint32_t xm;
      uint4 vn[2];
#define TOKS(i) { float e0[4] = {0, 0, 0, 0}, e1[4] = {0, 0, 0, 0}; \
        mma16(e0, af[0][0], af[0][1], af[0][2], af[0][3], qt[i][0], qt[i][1]); mma16(e1, af[0][0], af[0][1], af[0][2], af[0][3], qt[i + 1][0], qt[i + 1][1]); \
        mma16(e0, af[1][0], af[1][1], af[1][2], af[1][3], qt[i][2], qt[i][3]); mma16(e1, af[1][0], af[1][1], af[1][2], af[1][3], qt[i + 1][2], qt[i + 1][3]); \
        ts[i] = PACK(e0); ts[i + 1] = PACK(e1); }
      {
        float e[4][4];
#pragma unroll
        for (int i = 0; i < 4; i++) {
          e[i][0] = e[i][1] = e[i][2] = e[i][3] = 0.f;
          mma16(e[i], af[0][0], af[0][1], af[0][2], af[0][3], qt[i][0], qt[i][1]);
        }
#pragma unroll
        for (int i = 0; i < 4; i++) mma16(e[i], af[1][0], af[1][1], af[1][2], af[1][3], qt[i][2], qt[i][3]);
        SCHED_FENCE(55);
        if (s < 63) BAR_ARRIVE(B_S, 416);
        SCHED_FENCE(58);
        v[0] = lds4(tA + (VX0 - TA)); v[1] = lds4(tA + (VX0 - TA) + 2048); v[2] = lds4(tA + (VX1 - TA)); v[3] = lds4(tA + (VX1 - TA) + 2048);
#pragma unroll
        for (int i = 0; i < 4; i++) ts[i] = PACK(e[i]);
        vbad = anybad(v[0].x, v[1].x, v[2].x, v[3].x, V_TAG(s));
        if (AV) { xm = (xs & ~0x1ffffu) + X_VM(0) + ((tA - L16 - TA) << 5) + (l16 >> 1); CONSUME(xm); }
        while ((int)(clk() - c0) < 0) {}
        TS(5);
#pragma unroll
        for (int u = 0; u < 4; u++) r[u] = ldg_b64(XP_(xs) + u * 256);
        if (!AV) BAR_ARRIVE(B_S2, 256);
      }
      SCHED_FENCE(56);
      uint32_t kk;
      float4 e = softmax2<false>(r, 0, 0, kk);
      if (AV) {
        const char* pm_ = XP_(xm + (kk & dZ));
#pragma unroll
        for (int u = 0; u < 2; u++) { const uint2 m0 = ldg_b64(pm_ + u * 2048), m1 = ldg_b64(pm_ + u * 2048 + 256); vn[u] = make_uint4(m0.x, m0.y, m1.x, m1.y); }
      }
      if (__builtin_expect(anybad(r[0].x, r[0].y, r[1].x, r[1].y, r[2].x, r[2].y, r[3].x, r[3].y, tag ^ (kk & dZ)), 0)) {
        int it = 0;
        if (s > 8) sts1(tA + 4096 + 8, min(lds1(tA + 4096 + 8) + dX, 500));
        do {
          RP(1);
          if (++it > SPIN_LIMIT) __trap();
#pragma unroll
          for (int u = 0; u < 4; u++) r[u] = ldg_b64(XP_(xs) + u * 256);
        } while (BADS(r));
        e = softmax2<false>(r, 0, 0, kk);
      }
      sts1(t0.z, pk(e.x, e.y)); sts1(t0.z + 128, pk(e.z, e.w));
#pragma unroll
      for (int i = 0; i < 4; i++) publish(XP_(xo) + X_TOK + i * 4096, ts[i]);
      TS(6);
      if (s < 63) BAR_SYNC(B_V, N_V); else BAR_SYNC(B_V, N_V - 256);
      uint32_t O[4];
      {
        uint32_t p[4], pm;
        ldsm4t(p, pr);
        asm volatile("ldmatrix.sync.aligned.m8n8.x1.trans.shared.b16 {%0},[%1];" : "=r"(pm) : "r"(pr + 512) : "memory");
        if (!AV) { vn[0] = lds4(tA + (VN - TA)); vn[1] = lds4(tA + (VN - TA) + 2048); }
        pv_mem(p, pm, v, vn, O);
        if (__builtin_expect(vbad || ((HV || AV) && anybad(vn[0].x, vn[0].z, vn[1].x, vn[1].z, tag)), 0)) {
          int it = 0;
          const uint32_t xv = LO(xc) + (lds1(sb + PACE + 24) >> 2) * 262144 + ((tA - L16 - TA) >> 9) * XC;
          do {
            RP(2);
            if (++it > SPIN_LIMIT) __trap();
#pragma unroll
            for (int u = 0; u < 4; u++) v[u] = ldg_b128(XP_((xv + l16) ^ V_RING(s)) + X_VX(u));
          } while (anybad(v[0].x, v[1].x, v[2].x, v[3].x, V_TAG(s)) || ((HV || AV) && anybad(vn[0].x, vn[0].z, vn[1].x, vn[1].z, tag)));
          pv_mem(p, pm, v, vn, O);
        }
      }
      stsm4(tA + (OB - TA), O[0], O[1], O[2], O[3]);
      if (s < 63) BAR_ARRIVE(B_O, N_O);
      TS(2);
      c0 = clk() + (LS && s == 63 ? 0 : dG);
      SCHED_FENCE(60);
      if (tA == sb + TA) mbar_expect(sb + BARS, 2048);
      const uint32_t vs[4] = {addbf(vn[0].x, vn[0].z), addbf(vn[0].y, vn[0].w), addbf(vn[1].x, vn[1].z), addbf(vn[1].y, vn[1].w)};
      {
        const char* xt = XP_(lds1(tA + 12) ^ ring);
        const uint2 t1 = lds2u(tA + 2048);
        const uint32_t pw = lds1(tA + 8);
        uint2 rt[4];
        CONSUME(LO(xt) ^ t1.x ^ pw);
        while ((int)(clk() - c0) < 0) {}
        int it = 0;
        do {
          if (++it > SPIN_LIMIT) __trap();
#pragma unroll
          for (int u = 0; u < 4; u++) rt[u] = ldg_b64(xt + u * 256);
        } while (BADS(rt));
        uint32_t kt;
        const float4 et = softmax2<true>(rt, t1.x, t1.y, kt);
        sts1(pw + 1024, pk(et.x, et.y)); sts1(pw + 1024 + 128, pk(et.z, et.w));
      }
      s = PIN(s);
      BAR_SYNC(B_SC, 128);
      {
        uint32_t Ot[4], p[4], pm;
        const uint2 t2 = lds2u(tA + 2048 + 8);
        ldsm4t(p, pr + 1024);
        asm volatile("ldmatrix.sync.aligned.m8n8.x1.trans.shared.b16 {%0},[%1];" : "=r"(pm) : "r"(pr + 1024 + 512) : "memory");
        char* od = (char*)g_O + ((s >> 2) * 1048576 + (s & 3) * 4096) + t2.x;
        CONSUME(LO(od) ^ HI(od) ^ pm ^ p[3]);
        TS(9);
        if (s < 62) BAR_SYNC(B_P, N_P);
        pv_tok(p, pm, v, vs, Ot);
        asm volatile("stmatrix.sync.aligned.m8n8.x4.trans.shared.b16 [%0],{%1,%2,%3,%4};" ::"r"(t2.y), "r"(Ot[0]), "r"(Ot[1]), "r"(Ot[2]), "r"(Ot[3]) : "memory");
        __syncwarp();
        *(uint4*)od = lds4(tA + (OT - TA));
      }
    }
    FENCE_ASYNC();
    BAR_SYNC(B_SC, 128);
    if (tA == sb + TA) red_rlx(&g_fin);
  }
  __syncwarp();
  CLUSTER_SYNC();
  PH(5); RS(2);
}
#undef wg
#undef iw
#undef h
#undef j
#undef a
#undef bb
#undef oi
#undef owner
#undef ownv
#undef vfin
#undef pr
#undef PIN
#undef XP_
#undef tw
#undef is7
#undef REFRESH
#undef lane
#undef l16
#undef lrow
#undef lar
#undef lpub

namespace ffn {
constexpr uint32_t BR = 98304;
constexpr uint32_t STG = 196608;
constexpr uint32_t PRM = 229376;
constexpr uint32_t BARS = PRM + 2816;
constexpr uint32_t SMEM = BARS + 18 * 8;
}
#define Y_TILE(rb, kt) (((ALIAS & 1) ? g_h : g_h2) + ((rb) * 16 + (kt)) * 1024)
#define U_TILE(rb, kt) ((ALIAS & 2) ? g_O + ((rb) * 64 + (kt)) * 1024 : g_U + ((rb) * 56 + (kt)) * 1024)
struct FfnMaps { CUtensorMap wo, w1a, w1b, w2, x, out; };

template <int N>
__device__ __forceinline__ void wg_ss(float* d, uint64_t a, uint64_t b, int sd) {
  if (N == 128) wgmma_ss_n128(d, a, b, sd);
  if (N == 192) wgmma_ss_n192(d, a, b, sd);
}
template <int N>
__device__ __forceinline__ void acc_fence(float* d) {
#pragma unroll
  for (int i = 0; i < N; i++) asm volatile("" : "+f"(d[i])::"memory");
}
#define UNPK8(d, v) do { (d)[0] = blo(v.x); (d)[1] = bhi(v.x); (d)[2] = blo(v.y); (d)[3] = bhi(v.y); (d)[4] = blo(v.z); (d)[5] = bhi(v.z); (d)[6] = blo(v.w); (d)[7] = bhi(v.w); } while (0)
struct FfnPipe {
  uint32_t full, emp, ph, aoff;
  int st, sB, prev;
  bool leader;
  template <int N, int S = N>
  __device__ __forceinline__ void issue(float* acc, bool first, uint32_t a = 0) {
    mbar_wait(full + st * 8, ph);
    const uint64_t da = mkdesc((a ? a : 1024 + st * 16384) + aoff, 16, 1024), db = mkdesc(1024 + ffn::BR + sB * (S * 128), 8192, 1024);
    WG_FENCE();
#pragma unroll
    for (int j = 0; j < ((FDB & 1) ? 1 : 4); j++) wg_ss<N>(acc, da + j * 2, db + j * 128, j || !first);
    WG_COMMIT();
    if (++sB == 768 / S) sB = 0;
  }
  __device__ __forceinline__ void release() { if (leader) mbar_arrive(emp + prev * 8); }
  __device__ __forceinline__ void next() { prev = st; if (++st == 6) { st = 0; ph ^= 1; } }
  __device__ __forceinline__ void retire() { WG_WAIT(1); release(); next(); }
};
__device__ __forceinline__ float gelu_h(float hx) {
  float u = hx * fmaf(hx * hx, 8.f * 0.0356774081f, 2.f * 0.7978845608f), t;
  if (FDB & 4) return hx;
  if (FDB & 2) t = u; else
  asm("tanh.approx.f32 %0,%1;" : "=f"(t) : "f"(u));
  return fmaf(hx, t, hx);
}
struct FfnEpi {
  uint32_t st2, cc, flip, staged, l0;
  uint2 c;
  float n0, n1, s0, s1;
  __device__ __forceinline__ void flush(uint32_t r) {
    __syncwarp();
    asm volatile("{.reg .pred p; setp.ne.u32 p,%1,0; @p mbarrier.arrive.shared.b64 _,[%0];}" ::"r"(staged + (flip >> 11)), "r"(l0 & r) : "memory");
    flip ^= r << 14;
  }
  __device__ __forceinline__ void half(const float* d, int J, int r) {
#define PRE(i, n, c1, c2) gelu_h(fmaf(r ? d[4 + i] : d[i], i < 2 ? s0 : s1, fmaf(n, c1, c2)))
    asm volatile("stmatrix.sync.aligned.m8n8.x2.shared.b16 [%0],{%1,%2};" ::"r"((st2 ^ ((J & 3) * 32 + r * 16)) + flip),
                 "r"(pk(PRE(0, n0, blo(c.x), blo(c.y)), PRE(1, n0, bhi(c.x), bhi(c.y)))), "r"(pk(PRE(2, n1, blo(c.x), blo(c.y)), PRE(3, n1, bhi(c.x), bhi(c.y)))) : "memory");
#undef PRE
    if ((J & 3) == 3) flush(r);
    cc += r ? 56 : 8;
    c = lds2u(cc);
  }
};

__global__ void __launch_bounds__(384, 1)
k_ffn(const __grid_constant__ FfnMaps mp, const bf16* __restrict__ b2) {
  using namespace ffn;
  extern __shared__ __align__(1024) char smem[];
  const uint32_t sb = (uint32_t)__cvta_generic_to_shared(smem);
  if (sb != 1024) __trap();
  const int tid = threadIdx.x, lane = tid & 31, wg = __shfl_sync(~0u, tid >> 7, 0);
  const uint32_t full = sb + BARS, emp = full + 48, xbar = full + 96, staged = full + 104, tile = full + 136;
  uint32_t fin = 0;
  if (tid >= 288 && tid < 320) fin = ld_acq(&g_fin);
  if (tid < 32) {
    unsigned sm, v = 0;
    asm("mov.u32 %0,%%smid;" : "=r"(sm));
    if (tid == 0) {
      v = atomicExch(&g_slot[sm & 255], 0);
      for (int i = 0; i < 6; i++) { mbar_init(full + i * 8, 1); mbar_init(emp + i * 8, 2); }
      mbar_init(xbar, 2);
      for (int i = 0; i < 2; i++) { mbar_init(staged + i * 8, 8); mbar_init(staged + 16 + i * 8, 1); }
      FENCE_ASYNC_SMEM();
    }
    v = __shfl_sync(~0u, v, 0);
    if (!v) {
      wait_cnt(&g_fin, 128);
      for (int it = 0; !v; it++) {
        const uint4 a = ldg_rlx4(g_slot + tid * 8), b = ldg_rlx4(g_slot + tid * 8 + 4);
        const uint32_t open = __ballot_sync(~0u, a.x | a.y | a.z | a.w | b.x | b.y | b.z | b.w);
        if (!open) break;
        if (it < 16) { __nanosleep(500); continue; }
        if (tid == __ffs(open) - 1) v = atomicExch(&g_slot[tid * 8 + (a.x ? 0 : a.y ? 1 : a.z ? 2 : a.w ? 3 : b.x ? 4 : b.y ? 5 : b.z ? 6 : 7)], 0);
        v = __shfl_sync(~0u, v, __ffs(open) - 1);
      }
    }
    if (tid == 0) sts1(tile, v);
  }
  if (tid == 256) asm volatile("prefetch.tensormap [%0];" ::"l"(&mp.wo) : "memory");
  __syncthreads();
  const int bid = __shfl_sync(~0u, lds1(tile), 0) - 1;
  if (bid < 0) return;
  PH(6);
  FT(1);
  const int rb = bid >> 3, nb = bid & 7;
  unsigned* cnt = g_cnt + rb * 128;
  if (wg == 2) {
    asm volatile("setmaxnreg.dec.sync.aligned.u32 " FRP ";");
    const int pw = __shfl_sync(~0u, (tid >> 5) & 3, 0);
    uint32_t ws = emp, wp = 1, fs = full;
    auto wait_free = [&]() { mbar_wait_q(ws, wp); ws += 8; if (ws == emp + 48) { ws = emp; wp ^= 1; } };
    auto step = [&]() { fs += 8; if (fs == full + 48) fs = full; };
#define K3(c) ((0x65230 >> (c) * 4) & 7)
#define KC(k) ((k) < 2 ? nb * 2 + (k) : (k) < 9 ? ((k) - 2 + ((k) - 2 >= nb)) * 2 : ((k) - 9 + ((k) - 9 >= nb)) * 2 + 1)
    if (pw == 0) {
      uint32_t d = sb + BR + 32768;
      auto put = [&](const CUtensorMap* m, int k, int c) {
        e_expect_tma3d(d, m, k * 64, c, fs, 32768);
        step();
        d += 16384;
        if (d == sb + STG) d = sb + BR;
      };
      int n = 0;
      auto stage_free = [&]() { if (!(n & 7) && n < 56) mbar_wait_q(staged + 16 + (n & 8), (n >> 4) & 1); n++; };
      auto align = [&]() {
        if (ALN && !((n - 1) & 7) && ((ALN >> ((n - 1) >> 3)) & 1)) {
          unsigned* c = g_cnt + 64 + ((n - 1) >> 3);
          if (lane == 0) red_rlx(c);
          for (int it = 0; ldg_rlx1(c) < 128 && it < 64; it++) {}
        }
      };
      FTP(3);
#pragma unroll 1
      for (int k = 0; k < 66; k++) { wait_free(); if (k < 64) put(&mp.wo, k, nb * 2); }
#pragma unroll 1
      for (int k = 0; k < 16 + 2 * EOT; k++) {
        const int u = EOT && k >= 2 ? k - 2 : k, kt = KC(u);
        const bool ea = EOT && (k & ~1) == 2;
        wait_free();
        e_expect_tma3d(sb + BR + (k & 3) * 24576, ea ? &mp.w1a : &mp.w1b, kt * 64, nb * 7 + (ea ? 3 : 0), fs, ea ? 16384 : k < 2 ? 24576 : 40960);
        step();
      }
      if (EOT) d = sb + BR + 49152;
#pragma unroll 1
      for (int k = 2 * EOT; k < 32; k++) {
        const int kt = EOT && k < 16 ? KC(k) : k & 15;
        stage_free();
        if (EOT && (k == 2 || k == 9)) n++;
        if (k != 5 + 2 * EOT && k != 6 + 2 * EOT) wait_free();
        align();
        put(&mp.w1a, kt, nb * 7 + 3 + (k >> 4) * 2);
      }
#pragma unroll 1
      for (int c = 0; c < 5; c++)
#pragma unroll 1
        for (int k = K3(c), i = 0; k < 56; k += c < 2 && (i ^= 1) ? 1 : c < 2 ? 6 : 7) { stage_free(); wait_free(); align(); put(&mp.w2, k, nb * 2); }
    } else if (pw == 1) {
      FTP(5);
      if (fin < 128) wait_cnt(&g_fin, 128);
      FTP(6);
      uint32_t d = sb;
      auto put = [&](const uint4* A, bool ld) {
        wait_free();
        if (ld) e_bulk_ld(d, A, 16384, fs);
        step();
        d += 16384;
        if (d == sb + BR) d = sb;
      };
      const uint4* A = g_O + rb * 65536;
#pragma unroll 1
      for (int k = 0; k < 66 + 2 * EOT; k++) put(A + k * 1024, k < 64);
      A = Y_TILE(rb, 0);
      uint32_t ready = 0;
#pragma unroll 1
      for (int k = 2; k < 48; k++) {
        if (EOT && k == 16) k = 18;
        const int kt = k < 16 || (EOT && k < 32) ? KC(k & 15) : k & 15;
        for (int it = 0; !(ready >> ((kt >> 1) + (kt & 1) * 8) & 1); it++) {
          ready = __ballot_sync(~0u, ldg_rlx1(cnt + (lane & 7)) & ((lane & 8) ? 1 : 0x10000));
          if (it > SPIN_LIMIT) __trap();
        }
        if (k == 2) FTP(75);
        put(A + kt * 1024, true);
      }
      A = U_TILE(rb, 0);
#pragma unroll 1
      for (int c = 0; c < 5; c++) {
        for (int it = 0; ldg_rlx1(cnt + 32 + c) < 8; it++) if (it > SPIN_LIMIT) __trap();
#pragma unroll 1
        for (int k = K3(c), i = 0; k < 56; k += c < 2 && (i ^= 1) ? 1 : c < 2 ? 6 : 7) put(A + k * 1024, true);
      }
    } else if (pw == 2) {
      for (int i = 0; i < XDL; i++) {
        mbar_wait_q(emp, i & 1);
        if (XPF && i == 1 && lane < 2) tma2d_pf(&mp.x, nb * 128 + lane * 64, rb * 128);
      }
      if (lane == 0) {
        mbar_expect(xbar, 32768);
        tma2d(sb + STG, &mp.x, nb * 128, rb * 128, xbar);
        tma2d(sb + STG + 16384, &mp.x, nb * 128 + 64, rb * 128, xbar);
      }
      asm volatile("griddepcontrol.wait;" ::: "memory");
      if (lane < 16) g_modp[bid * 16 + lane] = make_uint4(0, 0, 0, 0);
      if (lane >= 16 && bid == 0) { g_hcnt = 0; g_mcnt = 0; g_hf[lane & 3] = 0; }
      if (lane == 0) {
#pragma unroll 1
        for (int g = 1; g < 9; g++) {
          if (g == 1) mbar_wait(staged + 8, 0); else { mbar_wait_q(staged + (g & 1) * 8, (g >> 1) & 1); FENCE_ASYNC_SMEM(); }
          bulk_st(g == 1 ? Y_TILE(rb, nb * 2 + 1) : U_TILE(rb, nb * 7 + ((0x652431000ull >> g * 4) & 7)), sb + STG + (g & 1) * 16384, 16384);
          BULK_COMMIT();
          if (g != 2 && g != 4) { BULK_WAIT(0); red_rlx(g == 1 ? cnt + nb : cnt + 32 + (g < 6 ? g >> 2 : g - 4)); }
          BULK_WAIT_READ(0);
          mbar_arrive(staged + 16 + (g & 1) * 8);
        }
      }
    } else {
      const uint32_t prm = sb + PRM, pp = prm + (lane >> 3) * 64 + (lane & 1) * 32 + (lane & 6) * 2;
      const uint2 v2 = ((const uint2*)(b2 + nb * 128))[lane];
      sts1(pp + 768, v2.x); sts1(pp + 784, v2.y);
      asm volatile("griddepcontrol.wait;" ::: "memory");
      const float4* md = (const float4*)(g_mod + nb * 128) + lane;
      { const float4 ga = md[512]; sts1(pp, pk(ga.x, ga.y)); sts1(pp + 16, pk(ga.z, ga.w)); }
      { const float4 cb = md[1024]; sts1(pp + 256, pk(1.f + cb.x, 1.f + cb.y)); sts1(pp + 272, pk(1.f + cb.z, 1.f + cb.w)); }
      { const float4 gb = md[1280]; sts1(pp + 512, pk(gb.x, gb.y)); sts1(pp + 528, pk(gb.z, gb.w)); }
#pragma unroll 1
      for (int i = lane; i < 112; i += 32) { const uint4 c = g_cc[nb * 112 + i]; sts4(prm + 1024 + i * 16, c.x, c.y, c.z, c.w); }
      __syncwarp();
      if (lane == 0) {
        mbar_arrive(xbar);
        mbar_wait(staged, 0);
        bulk_st(Y_TILE(rb, nb * 2), sb + STG, 16384);
        BULK_COMMIT(); BULK_WAIT(0);
        asm volatile("red.relaxed.gpu.global.add.u32 [%0],0x10000;" ::"l"(cnt + nb) : "memory");
        mbar_arrive(staged + 16);
      }
      __syncwarp();
      mbar_wait_q(staged + 24, 0);
      if (EOT) mbar_wait_q(emp + 8, 1); else mbar_wait_q(emp + 40, 0);
#pragma unroll 1
      for (int i = 0; i < 4; i++) {
        const uint4* sp = g_stat + (rb * 128 + i * 32 + lane) * 4;
        uint4 v[4];
        for (int it = 0;; it++) {
          uint32_t m = 0;
#pragma unroll
          for (int u = 0; u < 4; u++) { v[u] = ldg_rlx4(sp + u); m = max(max(m, max(v[u].x, v[u].y)), max(v[u].z, v[u].w)); }
          if (!__any_sync(~0u, m == ~0u)) break;
          if (it > SPIN_LIMIT) __trap();
        }
        float m = 0, q = 0;
#pragma unroll
        for (int u = 0; u < 4; u++) { m += F_(v[u].x) + F_(v[u].z); q += F_(v[u].y) + F_(v[u].w); }
        m *= 1.f / 1024;
        const float r = 0.5f * rsqrtf(fmaxf(q * (1.f / 1024) - m * m, 0.f) + 1e-5f);
        sts2(sb + STG + 16384 + (i * 32 + lane) * 8, U_(r), U_(-m * r));
      }
      __syncwarp();
      if (lane < 2) mbar_arrive(xbar);
    }
  } else {
    asm volatile("setmaxnreg.inc.sync.aligned.u32 " FRC ";");
    const int w = (tid >> 5) & 3, q = lane & 3;
    const uint32_t prm = sb + PRM + q * 16;
    const int row0 = wg * 64 + w * 16;
    FfnPipe p;
    p.full = full; p.emp = emp; p.ph = 0; p.aoff = wg * 8192; p.st = 0; p.sB = 2; p.prev = 0; p.leader = (tid & 127) == 0;
    FfnEpi e;
    const uint32_t stg = sb + STG + row0 * 128;
    e.st2 = stg + (lane & 15) * 128 + ((lane & 7) << 4);
    e.cc = sb + PRM + 1024 + q * 16; e.flip = 0; e.staged = staged; e.l0 = lane == 0;
    const uint32_t stw = e.st2 ^ (lane & 16);
    uint32_t x1[32];
    uint4* sp = g_stat + (rb * 128 + row0 + (lane >> 2)) * 4;
    float old[96], r0_, r1_;
    {
      float acc[64];
      p.issue<128>(acc, true); FT(8); p.next();
#pragma unroll 1
      for (int k = 1; k < 64; k++) { p.issue<128>(acc, false); FT(8 + k); p.retire(); }
      float xf[64], gf[32];
      uint32_t cb[16];
      mbar_wait(xbar, 0);
#pragma unroll
      for (int j = 0; j < 8; j++) {
        uint32_t xv[4];
        ldsm4(xv, (stw ^ ((j & 3) * 32)) + (j >> 2) * 16384);
#pragma unroll
        for (int i = 0; i < 4; i++) { xf[j * 8 + i * 2] = blo(xv[i]); xf[j * 8 + i * 2 + 1] = bhi(xv[i]); }
      }
#pragma unroll
      for (int i = 0; i < 4; i++) {
        const uint4 g = lds4(prm + i * 64), c = lds4(prm + 256 + i * 64);
        UNPK8(gf + i * 8, g);
        cb[i * 4] = c.x; cb[i * 4 + 1] = c.y; cb[i * 4 + 2] = c.z; cb[i * 4 + 3] = c.w;
      }
      acc_fence<64>(xf); acc_fence<32>(gf);
      WG_WAIT(0);
      p.release();
      acc_fence<64>(acc);
      PH(7); FT(72);
#pragma unroll
      for (int j = 0; j < 8; j++) {
        uint32_t* o = x1 + j * 4;
#pragma unroll
        for (int i = 0; i < 4; i++)
          o[i] = pk(fmaf(acc[j * 8 + i * 2], gf[j * 4 + (i & 2)], xf[j * 8 + i * 2]), fmaf(acc[j * 8 + i * 2 + 1], gf[j * 4 + (i & 2) + 1], xf[j * 8 + i * 2 + 1]));
        stsm4((stw ^ ((j & 3) * 32)) + (j >> 2) * 16384, mulbf(o[0], cb[j * 2]), mulbf(o[1], cb[j * 2]), mulbf(o[2], cb[j * 2 + 1]), mulbf(o[3], cb[j * 2 + 1]));
        if ((j & 3) == 3) { FENCE_ASYNC_SMEM(); e.flush(1); }
      }
      if (wg) BAR_SYNC(2, 128); else BAR_SYNC(3, 128);
    }
    PH(8); FT(73);
    float acc[64];
    {
      float* accC = old;
      p.sB = 0;
      p.issue<192>(accC, true, 1024 + STG); FT(80); p.next();
      p.issue<192>(accC, false, 1024 + STG + 16384); FT(81);
      FT(78);
      float s0 = 0, s1 = 0, q0 = 0, q1 = 0;
#define X1_FENCE _Pragma("unroll") for (int j = 0; j < 32; j++) asm volatile("" : "+r"(x1[j]));
      X1_FENCE
#pragma unroll
      for (int j = 0; j < 16; j++) {
        const float a = blo(x1[j * 2]), b = bhi(x1[j * 2]), c = blo(x1[j * 2 + 1]), d = bhi(x1[j * 2 + 1]);
        s0 += a + b; s1 += c + d; q0 = fmaf(a, a, fmaf(b, b, q0)); q1 = fmaf(c, c, fmaf(d, d, q1));
      }
#pragma unroll
      for (int o = 1; o < 4; o *= 2) { s0 += __shfl_xor_sync(~0u, s0, o); s1 += __shfl_xor_sync(~0u, s1, o); q0 += __shfl_xor_sync(~0u, q0, o); q1 += __shfl_xor_sync(~0u, q1, o); }
      if (q < 2) {
        uint32_t m = __float_as_uint(q ? s1 : s0), v = __float_as_uint(q ? q1 : q0);
        if (m == ~0u) m = 0x7fffffffu;
        if (v == ~0u) v = 0x7fffffffu;
        stg_rlx2((uint2*)(sp + q * 32) + nb, m, v);
      }
      X1_FENCE
      p.retire();
      if (EOT) {
#pragma unroll 1
        for (int k = 0; k < 2; k++) { p.issue<128, 192>(acc, !k, 1024 + STG + k * 16384); p.retire(); }
      }
#pragma unroll 1
      for (int k = 2; k < 15; k++) { p.issue<192>(accC, false); FT(80 + k); p.retire(); }
      p.issue<192>(accC, false); FT(95);
      mbar_wait(xbar, 1);
      const float2 u0 = lds2f(sb + STG + 16384 + (row0 + (lane >> 2)) * 8), u1 = lds2f(sb + STG + 16384 + (row0 + (lane >> 2)) * 8 + 64);
      r0_ = u0.x; e.n0 = u0.y; r1_ = u1.x; e.n1 = u1.y;
      e.c = lds2u(e.cc);
      p.retire();
      e.s0 = r0_; e.s1 = r1_;
      if (EOT) p.sB = 3;
    }
    PH(9);
    {
      auto pair = [&](int J, bool first, bool one, int fo) {
#pragma unroll 1
        for (int r = 0; r < 2; r++) {
          if (!(one && r)) { p.issue<128>(acc, first && !r); FT(fo + r); p.retire(); }
          acc_fence<8>(old + J * 8);
          e.half(old + J * 8, J, r);
        }
      };
#pragma unroll 1
      for (int i = 0; i < 3; i++) {
        if (i == 2) {
          e.s0 = r0_; e.s1 = r1_;
#pragma unroll
          for (int J = 8; J < 12; J++) pair(J, J == 8, false, 128 + (J - 8) * 2);
          e.cc += 512; e.c = lds2u(e.cc);
          e.s0 = e.s1 = 1.f;
        }
#pragma unroll
        for (int J = 0; J < 8; J++) pair(J, J == 0 && i < 2 && (i || !EOT), EOT && !(J & 3) && !i, 96 + i * 16 + (i >> 1) * 8 + J * 2);
        if (i == 2) break;
        e.cc += i ? -768 : 256; e.c = lds2u(e.cc);
        WG_WAIT(0);
        acc_fence<64>(acc);
#pragma unroll
        for (int k = 0; k < 64; k++) old[k] = acc[k] * ((k & 2) ? r1_ : r0_);
        acc_fence<64>(old);
        e.s0 = e.s1 = 1.f;
        PH(10 + i);
      }
#pragma unroll 1
      for (int k = 24; k < 56; k++) {
        if (SKW && k == 56 - SKW && wg) BAR_SYNC(4, 256);
        p.issue<128>(acc, false); FT(128 + k);
        if (SKW && k == 55 && !wg) BAR_ARRIVE(4, 256);
        p.retire();
      }
      float xf[64], gf[32];
#pragma unroll
      for (int i = 0; i < 4; i++) {
        const uint4 g = lds4(prm + 512 + i * 64), h = lds4(prm + 768 + i * 64);
        float hf[8];
        UNPK8(gf + i * 8, g); UNPK8(hf, h);
#pragma unroll
        for (int u = 0; u < 8; u++) {
          const int c = (u >> 2) * 4 + (u & 2);
          xf[i * 16 + u * 2] = fmaf(gf[i * 8 + c], hf[c], blo(x1[i * 8 + u])); xf[i * 16 + u * 2 + 1] = fmaf(gf[i * 8 + c + 1], hf[c + 1], bhi(x1[i * 8 + u]));
        }
      }
      acc_fence<64>(xf); acc_fence<32>(gf);
      mbar_wait(staged + 24, 1);
      mbar_wait(staged + 16, 0);
      WG_WAIT(0);
      acc_fence<64>(acc);
      PH(13); FT(184);
#pragma unroll
      for (int j = 0; j < 8; j++) {
        uint32_t o[4];
#pragma unroll
        for (int i = 0; i < 4; i++)
          o[i] = pk(fmaf(acc[j * 8 + i * 2], gf[j * 4 + (i & 2)], xf[j * 8 + i * 2]), fmaf(acc[j * 8 + i * 2 + 1], gf[j * 4 + (i & 2) + 1], xf[j * 8 + i * 2 + 1]));
        stsm4((stw ^ ((j & 3) * 32)) + (j >> 2) * 16384, o[0], o[1], o[2], o[3]);
        if ((j & 3) == 3) {
          FENCE_ASYNC_SMEM();
          __syncwarp();
          if (lane == 0) { tma2d_st(&mp.out, nb * 128 + (j >> 2) * 64, rb * 128 + row0, stg + (j >> 2) * 16384); BULK_COMMIT(); }
        }
      }
      if (lane == 0) BULK_WAIT_READ(0);
      __syncwarp();
    }
  }
  PH(14); FT(185);
}

typedef CUresult (*EncFn)(CUtensorMap*, CUtensorMapDataType, cuuint32_t, void*, const cuuint64_t*, const cuuint64_t*, const cuuint32_t*,
                          const cuuint32_t*, CUtensorMapInterleave, CUtensorMapSwizzle, CUtensorMapL2promotion, CUtensorMapFloatOOBfill);
static void map2d(EncFn enc, CUtensorMap* m, const void* p, int rows, int cols, int boxRows) {
  cuuint64_t d[2] = {(cuuint64_t)cols, (cuuint64_t)rows}, s[1] = {(cuuint64_t)cols * 2};
  cuuint32_t b[2] = {64, (cuuint32_t)boxRows}, e[2] = {1, 1};
  enc(m, CU_TENSOR_MAP_DATA_TYPE_BFLOAT16, 2, (void*)p, d, s, b, e, CU_TENSOR_MAP_INTERLEAVE_NONE, CU_TENSOR_MAP_SWIZZLE_128B,
      CU_TENSOR_MAP_L2_PROMOTION_L2_128B, CU_TENSOR_MAP_FLOAT_OOB_FILL_NONE);
}
static void map3d(EncFn enc, CUtensorMap* m, const void* p, int rows, int cols, int nch) {
  cuuint64_t d[3] = {64, (cuuint64_t)rows, (cuuint64_t)(cols / 64)}, s[2] = {(cuuint64_t)cols * 2, 128};
  cuuint32_t b[3] = {64, 64, (cuuint32_t)nch}, e[3] = {1, 1, 1};
  enc(m, CU_TENSOR_MAP_DATA_TYPE_BFLOAT16, 3, (void*)p, d, s, b, e, CU_TENSOR_MAP_INTERLEAVE_NONE, CU_TENSOR_MAP_SWIZZLE_128B,
      CU_TENSOR_MAP_L2_PROMOTION_L2_128B, CU_TENSOR_MAP_FLOAT_OOB_FILL_NONE);
}

extern "C" void kernel_launch(void* const* d_in, const int* in_sizes, int n_in, void* d_out, int out_size) {
  const bf16* x = (const bf16*)d_in[0];
  const bf16* mem0 = (const bf16*)d_in[1];
  void* fn = nullptr;
  cudaDriverEntryPointQueryResult qr;
  cudaGetDriverEntryPoint("cuTensorMapEncodeTiled", &fn, cudaEnableDefault, &qr);
  EncFn enc = (EncFn)fn;
  FfnMaps fm = {};
  map3d(enc, &fm.wo, d_in[5], 4096, 1024, 2);
  map3d(enc, &fm.w1a, d_in[8], 1024, 3584, 2);
  map3d(enc, &fm.w1b, d_in[8], 1024, 3584, 3);
  map3d(enc, &fm.w2, d_in[10], 3584, 1024, 2);
  map2d(enc, &fm.x, x, 2048, 1024, 128);
  map2d(enc, &fm.out, d_out, 2048, 1024, 16);
  RecMaps rm = {};
  map2d(enc, &rm.wq, d_in[2], 1024, 4096, 128);
  map2d(enc, &rm.wk, d_in[3], 1024, 4096, 128);
  map2d(enc, &rm.wv, d_in[4], 1024, 4096, 16);
  map2d(enc, &rm.wo, d_in[5], 4096, 1024, 128);
  char* xc = nullptr;
  cudaGetSymbolAddress((void**)&xc, g_xc);
  xc += (0 - (uintptr_t)xc) & 0x1FFFFF;
  {
    cuuint64_t d[3] = {512, ARV ? 8 : 128, ARV ? 128 : 6}, sd[2] = {1024, ARV ? 8192 : 131072};
    cuuint32_t bi[3] = {64, 8, 5}, e[3] = {1, 1, 1};
    enc(&rm.ari, CU_TENSOR_MAP_DATA_TYPE_BFLOAT16, 3, xc + AR_OFF, d, sd, bi, e, CU_TENSOR_MAP_INTERLEAVE_NONE, CU_TENSOR_MAP_SWIZZLE_NONE,
        CU_TENSOR_MAP_L2_PROMOTION_NONE, CU_TENSOR_MAP_FLOAT_OOB_FILL_NONE);
  }
  cudaFuncSetAttribute(k_ffn, cudaFuncAttributeMaxDynamicSharedMemorySize, ffn::SMEM);
  cudaFuncSetAttribute(k_rec, cudaFuncAttributeMaxDynamicSharedMemorySize, rec::SMEM);
  cudaStream_t st = cudaStreamPerThread;
  int dF = 450, dA = 2700, dS = 300, dM = 120, dG = 350, dP = 24, dX = 48, dD = 350, dZ = 0, dZ2 = 1, dV = 370, dX2 = 0;
  k_rec<<<132, 512, rec::SMEM, st>>>(rm, mem0, x, (const bf16*)d_in[12], (const bf16*)d_in[13], (const char*)d_in[8], (const bf16*)d_in[9],
                                     (const char*)d_in[5], xc, dF, dA, dS, dM, dG, dP, dX, dD, dZ, dZ2, dV, dX2);
  cudaLaunchConfig_t cfg = {};
  cfg.gridDim = dim3(132); cfg.blockDim = dim3(384); cfg.dynamicSmemBytes = ffn::SMEM; cfg.stream = st;
  cudaLaunchAttribute at[1];
  at[0].id = cudaLaunchAttributeProgrammaticStreamSerialization;
  at[0].val.programmaticStreamSerializationAllowed = 1;
  cfg.attrs = at; cfg.numAttrs = 1;
  cudaLaunchKernelEx(&cfg, k_ffn, fm, (const bf16*)d_in[11]);
}
```

```cpp
#include <cuda_runtime.h>
#include <cuda.h>
#include <cuda_bf16.h>
#include <stdint.h>

typedef __nv_bfloat16 bf16;

__device__ __align__(16) float g_mod[6144];
__device__ __align__(1024) uint4 g_modp[4 * 512];
__device__ unsigned g_hcnt;
__device__ unsigned g_hf[4];
__device__ __align__(1024) uint4 g_h[2048 * 1024 / 8];
__device__ __align__(1024) uint4 g_O[2048 * 4096 / 8];
__device__ __align__(1024) uint4 g_h2[2048 * 1024 / 8];
__device__ __align__(1024) uint4 g_U[2048 * 3584 / 8];
__device__ __align__(1024) uint4 g_stat[2048 * 4];
__device__ __align__(1024) unsigned g_cnt[16 * 4 * 32];
__device__ unsigned g_mcnt;
__device__ unsigned g_slot[256];
__device__ unsigned g_fin;
__device__ __align__(16) uint4 g_cc[224 * 4];
__device__ __align__(1024) uint4 g_xc[44 * 16384];
__device__ __align__(1024) unsigned g_tm[4 * 256];
#define FT(i)
#define FTP(i)
#define PT(i)
#define PH(i)
#define RS(i)
#define RP(i)
#define RPN(i, s)
#define TSV(i, v)
#define TS(i)

#define WIN 2
#define FRC "232"
#define FRP "40"
#define YR 1
#define XPK 0
#define NFA 1
#define PINM 1
#define FMAP (((g >> 2) * 4 + m) * 8 + ((g & 3) ^ ((g & 4) ? 3 : 0)) * 2 + (blockIdx.x & 1))
#define FDB 0
#define ALIAS 3
#define EF 0
#define XPF 0
#define PFT 150000
#define PFS 104
#define PF0 13000
#define PFD 128
#define DR 0
#define HV 0
#define XE 0
#define NF 3
#define NB0 4
#define PV0 4
#define T1L 1
#define NW0 5
#define FQM 0
#define FQ(k) do { if ((FQM >> ((k) - 48)) & 1) SCHED_FENCE(k); } while (0)
#define SWP 1
#define VCO 0
#define AV 0
#define PKE 0
#define VRF 3
#define RSO 2
#define WPF 1
#define VPC 1
#define OBL 1
#define WC0 10
#define WPE 3
#define LS 0
#define ALN 0x80
#define EOT 1
#define SKW 3
#define KDF 0
#define L62 200
#define XDL 6
#define QW 0
#define PDS 61
#define P_NVR 5
#define P_NVP 2
#define P_NWP 9
#define P_NW1 7
#define RF_ 208
#define PSV 1
#define RA_ (488 - 2 * RF_)
#define XI 5
#define XL 1
#define WCH 2
#define HX 0
#define VB 1
#define TP 0
#define CKI 0
#define NOP_ 2
#define KVO 0
#define NDL 3
#define AM 0
#define XM 3
#define XP 0
#define SPIN_LIMIT (1 << 20)
__device__ __forceinline__ uint64_t mkdesc(uint32_t addr, uint32_t lbo, uint32_t sbo) {
  return (uint64_t)((addr & 0x3FFFF) >> 4) | ((uint64_t)(lbo >> 4) << 16) | ((uint64_t)(sbo >> 4) << 32) | (1ull << 62);
}
__device__ __forceinline__ void mbar_init(uint32_t a, int c) { asm volatile("mbarrier.init.shared.b64 [%0],%1;" ::"r"(a), "r"(c) : "memory"); }
__device__ __forceinline__ void mbar_wait(uint32_t a, uint32_t par) {
  asm volatile(
      "{.reg .pred p; .reg .u32 n;\n"
      "mov.u32 n, 0;\n"
      "W: mbarrier.try_wait.parity.shared.b64 p,[%0],%1;\n"
      "@p bra D;\n"
      "add.u32 n, n, 1;\n"
      "setp.lt.u32 p, n, %2;\n"
      "@p bra W;\n"
      "trap;\n"
      "D:}" ::"r"(a), "r"(par), "n"(SPIN_LIMIT) : "memory");
}
__device__ __forceinline__ void mbar_wait_q(uint32_t a, uint32_t par) {
  asm volatile(
      "{.reg .pred p; .reg .u32 n;\n"
      "mov.u32 n, 0;\n"
      "W: mbarrier.try_wait.parity.shared.b64 p,[%0],%1,4000;\n"
      "@p bra D;\n"
      "add.u32 n, n, 1;\n"
      "setp.lt.u32 p, n, %2;\n"
      "@p bra W;\n"
      "trap;\n"
      "D:}" ::"r"(a), "r"(par), "n"(SPIN_LIMIT / 16) : "memory");
}
__device__ __forceinline__ void mbar_expect(uint32_t a, uint32_t b) { asm volatile("mbarrier.arrive.expect_tx.shared.b64 _,[%0],%1;" ::"r"(a), "r"(b) : "memory"); }
__device__ __forceinline__ void mbar_arrive(uint32_t a) { asm volatile("mbarrier.arrive.shared.b64 _,[%0];" ::"r"(a) : "memory"); }
__device__ __forceinline__ uint32_t mapa(uint32_t a, uint32_t cta) { uint32_t r; asm("mapa.shared::cluster.u32 %0,%1,%2;" : "=r"(r) : "r"(a), "r"(cta)); return r; }
__device__ __forceinline__ void mbar_arrive_cl(uint32_t a) { asm volatile("mbarrier.arrive.shared::cluster.b64 _,[%0];" ::"r"(a) : "memory"); }
__device__ __forceinline__ void tma2d(uint32_t dst, const CUtensorMap* m, int c0, int c1, uint32_t mb) {
  asm volatile("cp.async.bulk.tensor.2d.shared::cluster.global.mbarrier::complete_tx::bytes [%0],[%1,{%2,%3}],[%4];" ::"r"(dst), "l"(m), "r"(c0), "r"(c1), "r"(mb) : "memory");
}
__device__ __forceinline__ void tma2d_pf(const CUtensorMap* m, int c0, int c1) {
  asm volatile("cp.async.bulk.prefetch.tensor.2d.L2.global [%0,{%1,%2}];" ::"l"(m), "r"(c0), "r"(c1) : "memory");
}
__device__ __forceinline__ void tma3d(uint32_t dst, const CUtensorMap* m, int c1, int c2, uint32_t mb) {
  asm volatile("cp.async.bulk.tensor.3d.shared::cluster.global.mbarrier::complete_tx::bytes [%0],[%1,{0,%2,%3}],[%4];" ::"r"(dst), "l"(m), "r"(c1), "r"(c2), "r"(mb) : "memory");
}
__device__ __forceinline__ void tma2d_st(const CUtensorMap* m, int c0, int c1, uint32_t src) {
  asm volatile("cp.async.bulk.tensor.2d.global.shared::cta.bulk_group [%0,{%1,%2}],[%3];" ::"l"(m), "r"(c0), "r"(c1), "r"(src) : "memory");
}
__device__ __forceinline__ void bulk_ld(uint32_t dst, const void* src, uint32_t n, uint32_t mb) {
  asm volatile("cp.async.bulk.shared::cluster.global.mbarrier::complete_tx::bytes [%0],[%1],%2,[%3];" ::"r"(dst), "l"(src), "r"(n), "r"(mb) : "memory");
}
__device__ __forceinline__ void bulk_ld_mc(uint32_t dst, const void* src, uint32_t n, uint32_t mb) {
  asm volatile("cp.async.bulk.shared::cluster.global.mbarrier::complete_tx::bytes.multicast::cluster [%0],[%1],%2,[%3],%4;" ::"r"(dst), "l"(src), "r"(n), "r"(mb), "h"((uint16_t)3) : "memory");
}
__device__ __forceinline__ void bulk_st(void* dst, uint32_t src, uint32_t n) {
  asm volatile("cp.async.bulk.global.shared::cta.bulk_group [%0],[%1],%2;" ::"l"(dst), "r"(src), "r"(n) : "memory");
}
__device__ __forceinline__ void e_expect_tma3d(uint32_t dst, const CUtensorMap* m, int c1, int c2, uint32_t mb, uint32_t bytes) {
  asm volatile("{.reg .pred p; elect.sync _|p, 0xffffffff; @p mbarrier.arrive.expect_tx.shared.b64 _,[%4],%5;\n"
               "@p cp.async.bulk.tensor.3d.shared::cluster.global.mbarrier::complete_tx::bytes [%0],[%1,{0,%2,%3}],[%4];}" ::"r"(dst), "l"(m), "r"(c1), "r"(c2), "r"(mb), "r"(bytes) : "memory");
}
__device__ __forceinline__ void e_bulk_ld(uint32_t dst, const void* src, uint32_t n, uint32_t mb) {
  asm volatile("{.reg .pred p; elect.sync _|p, 0xffffffff; @p cp.async.bulk.shared::cluster.global.mbarrier::complete_tx::bytes [%0],[%1],%2,[%3];}" ::"r"(dst), "l"(src), "r"(n), "r"(mb) : "memory");
}
__device__ __forceinline__ void e_bulk_ld_ef(uint32_t dst, const void* src, uint32_t n, uint32_t mb) {
  asm volatile("{.reg .pred p; .reg .b64 c; createpolicy.fractional.L2::evict_first.b64 c,1.0; elect.sync _|p, 0xffffffff;"
               " @p cp.async.bulk.shared::cluster.global.mbarrier::complete_tx::bytes.L2::cache_hint [%0],[%1],%2,[%3],c;}" ::"r"(dst), "l"(src), "r"(n), "r"(mb) : "memory");
}
__device__ __forceinline__ void e_bulk_ld_mc(uint32_t dst, const void* src, uint32_t n, uint32_t mb) {
  asm volatile("{.reg .pred p; elect.sync _|p, 0xffffffff; @p cp.async.bulk.shared::cluster.global.mbarrier::complete_tx::bytes.multicast::cluster [%0],[%1],%2,[%3],%4;}" ::"r"(dst), "l"(src), "r"(n), "r"(mb), "h"((uint16_t)3) : "memory");
}
#define BULK_COMMIT() asm volatile("cp.async.bulk.commit_group;" ::: "memory")
#define BULK_WAIT_READ(n) asm volatile("cp.async.bulk.wait_group.read " #n ";" ::: "memory")
#define BULK_WAIT(n) asm volatile("cp.async.bulk.wait_group " #n ";" ::: "memory")
#define FENCE_ASYNC_SMEM() asm volatile("fence.proxy.async.shared::cta;" ::: "memory")
#define FENCE_ASYNC() asm volatile("fence.proxy.async;" ::: "memory")
#define WG_FENCE() asm volatile("wgmma.fence.sync.aligned;" ::: "memory")
#define WG_COMMIT() asm volatile("wgmma.commit_group.sync.aligned;" ::: "memory")
#define WG_WAIT(n) asm volatile("wgmma.wait_group.sync.aligned " #n ";" ::: "memory")
#define BAR_SYNC(id, n) asm volatile("bar.sync %0,%1;" ::"n"(id), "n"(n) : "memory")
#define BAR_ARRIVE(id, n) asm volatile("bar.arrive %0,%1;" ::"n"(id), "n"(n) : "memory")
#define SCHED_FENCE(k) asm volatile("{.reg .pred p; setp.ne.u32 p,%0,0; @p trap;}" ::"r"(mp.zero[(k) - 46]) : "memory")
#define CLUSTER_SYNC() asm volatile("barrier.cluster.arrive.relaxed.aligned; barrier.cluster.wait.aligned;" ::: "memory")
__device__ __forceinline__ uint32_t pk(float lo, float hi) { uint32_t r; asm("cvt.rn.bf16x2.f32 %0,%1,%2;" : "=r"(r) : "f"(hi), "f"(lo)); return r; }
__device__ __forceinline__ float blo(uint32_t v) { return __uint_as_float(v << 16); }
__device__ __forceinline__ float bhi(uint32_t v) { return __uint_as_float(v & 0xffff0000u); }
__device__ __forceinline__ void ldsm4(uint32_t* r, uint32_t a) {
  asm volatile("ldmatrix.sync.aligned.m8n8.x4.shared.b16 {%0,%1,%2,%3},[%4];" : "=r"(r[0]), "=r"(r[1]), "=r"(r[2]), "=r"(r[3]) : "r"(a) : "memory");
}
__device__ __forceinline__ void ldsm4t(uint32_t* r, uint32_t a) {
  asm volatile("ldmatrix.sync.aligned.m8n8.x4.trans.shared.b16 {%0,%1,%2,%3},[%4];" : "=r"(r[0]), "=r"(r[1]), "=r"(r[2]), "=r"(r[3]) : "r"(a) : "memory");
}
__device__ __forceinline__ void stsm4(uint32_t a, uint32_t r0, uint32_t r1, uint32_t r2, uint32_t r3) {
  asm volatile("stmatrix.sync.aligned.m8n8.x4.shared.b16 [%0],{%1,%2,%3,%4};" ::"r"(a), "r"(r0), "r"(r1), "r"(r2), "r"(r3) : "memory");
}
__device__ __forceinline__ void mma16(float* d, uint32_t a0, uint32_t a1, uint32_t a2, uint32_t a3, uint32_t b0, uint32_t b1) {
  asm volatile("mma.sync.aligned.m16n8k16.row.col.f32.bf16.bf16.f32 {%0,%1,%2,%3},{%4,%5,%6,%7},{%8,%9},{%0,%1,%2,%3};"
               : "+f"(d[0]), "+f"(d[1]), "+f"(d[2]), "+f"(d[3]) : "r"(a0), "r"(a1), "r"(a2), "r"(a3), "r"(b0), "r"(b1));
}
__device__ __forceinline__ void mma8(float* d, uint32_t a0, uint32_t a1, uint32_t b0) {
  asm volatile("mma.sync.aligned.m16n8k8.row.col.f32.bf16.bf16.f32 {%0,%1,%2,%3},{%4,%5},{%6},{%0,%1,%2,%3};"
               : "+f"(d[0]), "+f"(d[1]), "+f"(d[2]), "+f"(d[3]) : "r"(a0), "r"(a1), "r"(b0));
}
__device__ __forceinline__ float4 lds4f(uint32_t a) { float4 v; asm volatile("ld.shared.v4.f32 {%0,%1,%2,%3},[%4];" : "=f"(v.x), "=f"(v.y), "=f"(v.z), "=f"(v.w) : "r"(a) : "memory"); return v; }
__device__ __forceinline__ float2 lds2f(uint32_t a) { float2 v; asm volatile("ld.shared.v2.f32 {%0,%1},[%2];" : "=f"(v.x), "=f"(v.y) : "r"(a) : "memory"); return v; }
__device__ __forceinline__ uint4 lds4(uint32_t a) { uint4 v; asm volatile("ld.shared.v4.u32 {%0,%1,%2,%3},[%4];" : "=r"(v.x), "=r"(v.y), "=r"(v.z), "=r"(v.w) : "r"(a) : "memory"); return v; }
__device__ __forceinline__ uint2 lds2u(uint32_t a) { uint2 v; asm volatile("ld.shared.v2.u32 {%0,%1},[%2];" : "=r"(v.x), "=r"(v.y) : "r"(a) : "memory"); return v; }
__device__ __forceinline__ uint32_t lds1(uint32_t a) { uint32_t v; asm volatile("ld.shared.u32 %0,[%1];" : "=r"(v) : "r"(a) : "memory"); return v; }
__device__ __forceinline__ void sts4(uint32_t a, uint32_t x, uint32_t y, uint32_t z, uint32_t w) { asm volatile("st.shared.v4.u32 [%0],{%1,%2,%3,%4};" ::"r"(a), "r"(x), "r"(y), "r"(z), "r"(w) : "memory"); }
__device__ __forceinline__ void sts2(uint32_t a, uint32_t x, uint32_t y) { asm volatile("st.shared.v2.u32 [%0],{%1,%2};" ::"r"(a), "r"(x), "r"(y) : "memory"); }
__device__ __forceinline__ void sts1(uint32_t a, uint32_t x) { asm volatile("st.shared.u32 [%0],%1;" ::"r"(a), "r"(x) : "memory"); }
__device__ __forceinline__ void sta4(uint32_t a, const uint32_t* v, uint32_t mb) {
  asm volatile("st.async.shared::cluster.mbarrier::complete_tx::bytes.v4.b32 [%0],{%1,%2,%3,%4},[%5];" ::"r"(a), "r"(v[0]), "r"(v[1]), "r"(v[2]), "r"(v[3]), "r"(mb) : "memory");
}
__device__ __forceinline__ uint4 ldg_rlx4(const void* p) { uint4 v; asm volatile("ld.relaxed.gpu.global.v4.u32 {%0,%1,%2,%3},[%4];" : "=r"(v.x), "=r"(v.y), "=r"(v.z), "=r"(v.w) : "l"(p) : "memory"); return v; }
__device__ __forceinline__ uint32_t ldg_rlx1(const void* p) { uint32_t v; asm volatile("ld.relaxed.gpu.global.u32 %0,[%1];" : "=r"(v) : "l"(p) : "memory"); return v; }
__device__ __forceinline__ uint2 ldg_rlx2(const void* p) { uint2 v; asm volatile("ld.relaxed.gpu.global.v2.u32 {%0,%1},[%2];" : "=r"(v.x), "=r"(v.y) : "l"(p) : "memory"); return v; }
__device__ __forceinline__ uint4 ldg_b128(const void* p) {
  uint4 v;
  asm volatile("{.reg .b128 t; .reg .b64 a,b; ld.relaxed.gpu.global.b128 t,[%4]; mov.b128 {a,b},t; mov.b64 {%0,%1},a; mov.b64 {%2,%3},b;}" : "=r"(v.x), "=r"(v.y), "=r"(v.z), "=r"(v.w) : "l"(p) : "memory");
  return v;
}
__device__ __forceinline__ void stg_b128(void* p, uint32_t x, uint32_t y, uint32_t z, uint32_t w) {
  asm volatile("{.reg .b128 t; .reg .b64 a,b; mov.b64 a,{%1,%2}; mov.b64 b,{%3,%4}; mov.b128 t,{a,b}; st.relaxed.gpu.global.b128 [%0],t;}" ::"l"(p), "r"(x), "r"(y), "r"(z), "r"(w) : "memory");
}
__device__ __forceinline__ void st_b128(void* p, uint32_t x, uint32_t y, uint32_t z, uint32_t w) {
  asm volatile("{.reg .b128 t; .reg .b64 a,b; mov.b64 a,{%1,%2}; mov.b64 b,{%3,%4}; mov.b128 t,{a,b}; st.relaxed.gpu.b128 [%0],t;}" ::"l"(p), "r"(x), "r"(y), "r"(z), "r"(w) : "memory");
}
__device__ __forceinline__ void stg_rlx4(void* p, uint32_t x, uint32_t y, uint32_t z, uint32_t w) { asm volatile("st.relaxed.gpu.global.v4.u32 [%0],{%1,%2,%3,%4};" ::"l"(p), "r"(x), "r"(y), "r"(z), "r"(w) : "memory"); }
__device__ __forceinline__ void stg_rlx2(void* p, uint32_t x, uint32_t y) { asm volatile("st.relaxed.gpu.global.v2.u32 [%0],{%1,%2};" ::"l"(p), "r"(x), "r"(y) : "memory"); }
__device__ __forceinline__ void red4(void* p, float a, float b, float c, float d) { asm volatile("red.relaxed.gpu.global.add.v4.f32 [%0],{%1,%2,%3,%4};" ::"l"(p), "f"(a), "f"(b), "f"(c), "f"(d) : "memory"); }
__device__ __forceinline__ unsigned ld_acq(const unsigned* p) { unsigned v; asm volatile("ld.acquire.gpu.global.u32 %0,[%1];" : "=r"(v) : "l"(p) : "memory"); return v; }
__device__ __forceinline__ void red_rel(unsigned* p) { asm volatile("red.release.gpu.global.add.u32 [%0],1;" ::"l"(p) : "memory"); }
__device__ __forceinline__ void red_rlx(unsigned* p) { asm volatile("red.relaxed.gpu.global.add.u32 [%0],1;" ::"l"(p) : "memory"); }
__device__ __forceinline__ void wait_cnt(const unsigned* p, unsigned n) { int it = 0; while (ld_acq(p) < n) { if (++it > SPIN_LIMIT) __trap(); } }
__device__ __forceinline__ uint32_t clk() { uint32_t c; asm volatile("mov.u32 %0,%%clock;" : "=r"(c)); return c; }
__device__ __forceinline__ uint32_t gtime() { uint32_t c; asm volatile("mov.u32 %0,%%globaltimer_lo;" : "=r"(c)); return c; }
__device__ __forceinline__ void wait_until(uint32_t t0, uint32_t d) { while (clk() - t0 < d) {} }
__device__ __forceinline__ float ex2(float x) { float r; asm("ex2.approx.ftz.f32 %0,%1;" : "=f"(r) : "f"(x)); return r; }
__device__ __forceinline__ float silu(float x) { return x * __frcp_rn(1.f + __expf(-x)); }
__device__ __forceinline__ float rbf(float x) { return __bfloat162float(__float2bfloat16_rn(x)); }

__device__ __forceinline__ void wgmma_ss_n128(float* d, uint64_t a, uint64_t b, int sd) {
  asm volatile("{.reg .pred p; setp.ne.b32 p, %66, 0;\n"
    "wgmma.mma_async.sync.aligned.m64n128k16.f32.bf16.bf16 {%0,%1,%2,%3,%4,%5,%6,%7,%8,%9,%10,%11,%12,%13,%14,%15,%16,%17,%18,%19,%20,%21,%22,%23,%24,%25,%26,%27,%28,%29,%30,%31,%32,%33,%34,%35,%36,%37,%38,%39,%40,%41,%42,%43,%44,%45,%46,%47,%48,%49,%50,%51,%52,%53,%54,%55,%56,%57,%58,%59,%60,%61,%62,%63}, %64, %65, p, 1, 1, 0, 1;}\n"
    : "+f"(d[0]),"+f"(d[1]),"+f"(d[2]),"+f"(d[3]),"+f"(d[4]),"+f"(d[5]),"+f"(d[6]),"+f"(d[7]),
      "+f"(d[8]),"+f"(d[9]),"+f"(d[10]),"+f"(d[11]),"+f"(d[12]),"+f"(d[13]),"+f"(d[14]),"+f"(d[15]),
      "+f"(d[16]),"+f"(d[17]),"+f"(d[18]),"+f"(d[19]),"+f"(d[20]),"+f"(d[21]),"+f"(d[22]),"+f"(d[23]),
      "+f"(d[24]),"+f"(d[25]),"+f"(d[26]),"+f"(d[27]),"+f"(d[28]),"+f"(d[29]),"+f"(d[30]),"+f"(d[31]),
      "+f"(d[32]),"+f"(d[33]),"+f"(d[34]),"+f"(d[35]),"+f"(d[36]),"+f"(d[37]),"+f"(d[38]),"+f"(d[39]),
      "+f"(d[40]),"+f"(d[41]),"+f"(d[42]),"+f"(d[43]),"+f"(d[44]),"+f"(d[45]),"+f"(d[46]),"+f"(d[47]),
      "+f"(d[48]),"+f"(d[49]),"+f"(d[50]),"+f"(d[51]),"+f"(d[52]),"+f"(d[53]),"+f"(d[54]),"+f"(d[55]),
      "+f"(d[56]),"+f"(d[57]),"+f"(d[58]),"+f"(d[59]),"+f"(d[60]),"+f"(d[61]),"+f"(d[62]),"+f"(d[63])
    : "l"(a), "l"(b), "r"(sd));
}
__device__ __forceinline__ void wgmma_ss_n192(float* d, uint64_t a, uint64_t b, int sd) {
  asm volatile("{.reg .pred p; setp.ne.b32 p, %98, 0;\n"
    "wgmma.mma_async.sync.aligned.m64n192k16.f32.bf16.bf16 {%0,%1,%2,%3,%4,%5,%6,%7,%8,%9,%10,%11,%12,%13,%14,%15,%16,%17,%18,%19,%20,%21,%22,%23,%24,%25,%26,%27,%28,%29,%30,%31,%32,%33,%34,%35,%36,%37,%38,%39,%40,%41,%42,%43,%44,%45,%46,%47,%48,%49,%50,%51,%52,%53,%54,%55,%56,%57,%58,%59,%60,%61,%62,%63,%64,%65,%66,%67,%68,%69,%70,%71,%72,%73,%74,%75,%76,%77,%78,%79,%80,%81,%82,%83,%84,%85,%86,%87,%88,%89,%90,%91,%92,%93,%94,%95}, %96, %97, p, 1, 1, 0, 1;}\n"
    : "+f"(d[0]),"+f"(d[1]),"+f"(d[2]),"+f"(d[3]),"+f"(d[4]),"+f"(d[5]),"+f"(d[6]),"+f"(d[7]),
      "+f"(d[8]),"+f"(d[9]),"+f"(d[10]),"+f"(d[11]),"+f"(d[12]),"+f"(d[13]),"+f"(d[14]),"+f"(d[15]),
      "+f"(d[16]),"+f"(d[17]),"+f"(d[18]),"+f"(d[19]),"+f"(d[20]),"+f"(d[21]),"+f"(d[22]),"+f"(d[23]),
      "+f"(d[24]),"+f"(d[25]),"+f"(d[26]),"+f"(d[27]),"+f"(d[28]),"+f"(d[29]),"+f"(d[30]),"+f"(d[31]),
      "+f"(d[32]),"+f"(d[33]),"+f"(d[34]),"+f"(d[35]),"+f"(d[36]),"+f"(d[37]),"+f"(d[38]),"+f"(d[39]),
      "+f"(d[40]),"+f"(d[41]),"+f"(d[42]),"+f"(d[43]),"+f"(d[44]),"+f"(d[45]),"+f"(d[46]),"+f"(d[47]),
      "+f"(d[48]),"+f"(d[49]),"+f"(d[50]),"+f"(d[51]),"+f"(d[52]),"+f"(d[53]),"+f"(d[54]),"+f"(d[55]),
      "+f"(d[56]),"+f"(d[57]),"+f"(d[58]),"+f"(d[59]),"+f"(d[60]),"+f"(d[61]),"+f"(d[62]),"+f"(d[63]),
      "+f"(d[64]),"+f"(d[65]),"+f"(d[66]),"+f"(d[67]),"+f"(d[68]),"+f"(d[69]),"+f"(d[70]),"+f"(d[71]),
      "+f"(d[72]),"+f"(d[73]),"+f"(d[74]),"+f"(d[75]),"+f"(d[76]),"+f"(d[77]),"+f"(d[78]),"+f"(d[79]),
      "+f"(d[80]),"+f"(d[81]),"+f"(d[82]),"+f"(d[83]),"+f"(d[84]),"+f"(d[85]),"+f"(d[86]),"+f"(d[87]),
      "+f"(d[88]),"+f"(d[89]),"+f"(d[90]),"+f"(d[91]),"+f"(d[92]),"+f"(d[93]),"+f"(d[94]),"+f"(d[95])
    : "l"(a), "l"(b), "r"(sd));
}
__device__ __forceinline__ void wgmma_ss_n256(float* d, uint64_t a, uint64_t b, int sd) {
  asm volatile("{.reg .pred p; setp.ne.b32 p, %130, 0;\n"
    "wgmma.mma_async.sync.aligned.m64n256k16.f32.bf16.bf16 {%0,%1,%2,%3,%4,%5,%6,%7,%8,%9,%10,%11,%12,%13,%14,%15,%16,%17,%18,%19,%20,%21,%22,%23,%24,%25,%26,%27,%28,%29,%30,%31,%32,%33,%34,%35,%36,%37,%38,%39,%40,%41,%42,%43,%44,%45,%46,%47,%48,%49,%50,%51,%52,%53,%54,%55,%56,%57,%58,%59,%60,%61,%62,%63,%64,%65,%66,%67,%68,%69,%70,%71,%72,%73,%74,%75,%76,%77,%78,%79,%80,%81,%82,%83,%84,%85,%86,%87,%88,%89,%90,%91,%92,%93,%94,%95,%96,%97,%98,%99,%100,%101,%102,%103,%104,%105,%106,%107,%108,%109,%110,%111,%112,%113,%114,%115,%116,%117,%118,%119,%120,%121,%122,%123,%124,%125,%126,%127}, %128, %129, p, 1, 1, 0, 1;}\n"
    : "+f"(d[0]),"+f"(d[1]),"+f"(d[2]),"+f"(d[3]),"+f"(d[4]),"+f"(d[5]),"+f"(d[6]),"+f"(d[7]),
      "+f"(d[8]),"+f"(d[9]),"+f"(d[10]),"+f"(d[11]),"+f"(d[12]),"+f"(d[13]),"+f"(d[14]),"+f"(d[15]),
      "+f"(d[16]),"+f"(d[17]),"+f"(d[18]),"+f"(d[19]),"+f"(d[20]),"+f"(d[21]),"+f"(d[22]),"+f"(d[23]),
      "+f"(d[24]),"+f"(d[25]),"+f"(d[26]),"+f"(d[27]),"+f"(d[28]),"+f"(d[29]),"+f"(d[30]),"+f"(d[31]),
      "+f"(d[32]),"+f"(d[33]),"+f"(d[34]),"+f"(d[35]),"+f"(d[36]),"+f"(d[37]),"+f"(d[38]),"+f"(d[39]),
      "+f"(d[40]),"+f"(d[41]),"+f"(d[42]),"+f"(d[43]),"+f"(d[44]),"+f"(d[45]),"+f"(d[46]),"+f"(d[47]),
      "+f"(d[48]),"+f"(d[49]),"+f"(d[50]),"+f"(d[51]),"+f"(d[52]),"+f"(d[53]),"+f"(d[54]),"+f"(d[55]),
      "+f"(d[56]),"+f"(d[57]),"+f"(d[58]),"+f"(d[59]),"+f"(d[60]),"+f"(d[61]),"+f"(d[62]),"+f"(d[63]),
      "+f"(d[64]),"+f"(d[65]),"+f"(d[66]),"+f"(d[67]),"+f"(d[68]),"+f"(d[69]),"+f"(d[70]),"+f"(d[71]),
      "+f"(d[72]),"+f"(d[73]),"+f"(d[74]),"+f"(d[75]),"+f"(d[76]),"+f"(d[77]),"+f"(d[78]),"+f"(d[79]),
      "+f"(d[80]),"+f"(d[81]),"+f"(d[82]),"+f"(d[83]),"+f"(d[84]),"+f"(d[85]),"+f"(d[86]),"+f"(d[87]),
      "+f"(d[88]),"+f"(d[89]),"+f"(d[90]),"+f"(d[91]),"+f"(d[92]),"+f"(d[93]),"+f"(d[94]),"+f"(d[95]),
      "+f"(d[96]),"+f"(d[97]),"+f"(d[98]),"+f"(d[99]),"+f"(d[100]),"+f"(d[101]),"+f"(d[102]),"+f"(d[103]),
      "+f"(d[104]),"+f"(d[105]),"+f"(d[106]),"+f"(d[107]),"+f"(d[108]),"+f"(d[109]),"+f"(d[110]),"+f"(d[111]),
      "+f"(d[112]),"+f"(d[113]),"+f"(d[114]),"+f"(d[115]),"+f"(d[116]),"+f"(d[117]),"+f"(d[118]),"+f"(d[119]),
      "+f"(d[120]),"+f"(d[121]),"+f"(d[122]),"+f"(d[123]),"+f"(d[124]),"+f"(d[125]),"+f"(d[126]),"+f"(d[127])
    : "l"(a), "l"(b), "r"(sd));
}
__device__ __forceinline__ void wgmma_rs_n32(float* d, const uint32_t* a, uint64_t b, int sd) {
  asm volatile("{.reg .pred p; setp.ne.b32 p, %21, 0;\n"
    "wgmma.mma_async.sync.aligned.m64n32k16.f32.bf16.bf16 {%0,%1,%2,%3,%4,%5,%6,%7,%8,%9,%10,%11,%12,%13,%14,%15}, {%16,%17,%18,%19}, %20, p, 1, 1, 0;}\n"
    : "+f"(d[0]),"+f"(d[1]),"+f"(d[2]),"+f"(d[3]),"+f"(d[4]),"+f"(d[5]),"+f"(d[6]),"+f"(d[7]),
      "+f"(d[8]),"+f"(d[9]),"+f"(d[10]),"+f"(d[11]),"+f"(d[12]),"+f"(d[13]),"+f"(d[14]),"+f"(d[15])
    : "r"(a[0]), "r"(a[1]), "r"(a[2]), "r"(a[3]), "l"(b), "r"(sd));
}
__device__ __forceinline__ void wgmma_ssT_n32(float* d, uint64_t a, uint64_t b, int sd) {
  asm volatile("{.reg .pred p; setp.ne.b32 p, %18, 0;\n"
    "wgmma.mma_async.sync.aligned.m64n32k16.f32.bf16.bf16 {%0,%1,%2,%3,%4,%5,%6,%7,%8,%9,%10,%11,%12,%13,%14,%15}, %16, %17, p, 1, 1, 1, 0;}\n"
    : "+f"(d[0]),"+f"(d[1]),"+f"(d[2]),"+f"(d[3]),"+f"(d[4]),"+f"(d[5]),"+f"(d[6]),"+f"(d[7]),
      "+f"(d[8]),"+f"(d[9]),"+f"(d[10]),"+f"(d[11]),"+f"(d[12]),"+f"(d[13]),"+f"(d[14]),"+f"(d[15])
    : "l"(a), "l"(b), "r"(sd));
}

__device__ __forceinline__ void wgmma_rs_n32_z(float* d, const uint32_t* a, uint64_t b) {
  asm volatile("{.reg .pred p; setp.ne.b32 p, 0, 0;\n"
    "wgmma.mma_async.sync.aligned.m64n32k16.f32.bf16.bf16 {%0,%1,%2,%3,%4,%5,%6,%7,%8,%9,%10,%11,%12,%13,%14,%15}, {%16,%17,%18,%19}, %20, p, 1, 1, 0;}\n"
    : "=f"(d[0]),"=f"(d[1]),"=f"(d[2]),"=f"(d[3]),"=f"(d[4]),"=f"(d[5]),"=f"(d[6]),"=f"(d[7]),
      "=f"(d[8]),"=f"(d[9]),"=f"(d[10]),"=f"(d[11]),"=f"(d[12]),"=f"(d[13]),"=f"(d[14]),"=f"(d[15])
    : "r"(a[0]), "r"(a[1]), "r"(a[2]), "r"(a[3]), "l"(b));
}

namespace rec {
constexpr int NVR = P_NVR;
constexpr int NVS = 16 - NVR;
constexpr int NVP = P_NVP;
constexpr int NWP = P_NWP;
constexpr uint32_t WO = 0;
constexpr uint32_t XB = 65536;
constexpr uint32_t PK = XB + 32768;
constexpr uint32_t VN = PK + 24576;
constexpr uint32_t VX0 = VN + 4096;
constexpr uint32_t WVS = 131072;
constexpr uint32_t MEM = WVS + 2 * NVS * 2048;
constexpr uint32_t ARO = MEM + 10240;
constexpr uint32_t OB = ARO + 5120;
constexpr uint32_t QT = OB + 2048;
constexpr uint32_t KT = QT + 2048;
constexpr uint32_t RQ = KT + 6144;
constexpr uint32_t RK = RQ + 2048;
constexpr uint32_t SC = RK + 2048;
constexpr uint32_t OT = OB;
constexpr uint32_t TF = SC + 2048;
constexpr uint32_t PRE = MEM + 2 * NVR * 2048;
constexpr uint32_t TA = TF + 8192;
constexpr uint32_t RX = TA + 6144;
constexpr uint32_t VX1 = RX + 2048;
constexpr uint32_t BARS = VX1 + 4096;
constexpr uint32_t PACE = BARS + 18 * 8;
constexpr uint32_t SMEM = BARS + 512;
static_assert(PRE + 14336 <= BARS, "staging");
constexpr int NW1 = P_NW1;
static_assert(SMEM <= 232448, "smem");
constexpr int B_E = 2, B_SC = 3, B_S = 4, B_O = 5, B_F = 6, B_W = 7, B_C = 9, B_K = 10, B_H = 15, B_Q = 1, B_S2 = 6, B_T2 = 9, B_P = 13, B_T = 14, B_R = 11, B_X = 12, B_V = 8;
constexpr int N_P = XE == 1 ? 416 : 384, N_R = XE ? 288 : 320, N_V = AV ? 384 : 512, N_O = AV ? 384 : 416;
constexpr int XC = 16384, X_RING = 131072, X_SC = 65536, X_TOK = 4096;
#define X_VX(i) (((i) >> 1) * 2048 + ((i) & 1) * 512)
#define X_VM(i) (X_VX(i) + 1024)
#define V_RING(n) (((n) & 1) * X_RING + ((n) & 2) * 2048)
#define V_TAG(n) ((~(n) >> 2) & 1)
}
struct RecMaps { CUtensorMap wq, wk, wv, wo, ari; int zero[40]; };

#define F_(x) __uint_as_float(x)
#define U_(x) __float_as_uint(x)
#define AR_R(q) (24 + ((q) & 1) * 16 + ((q) >> 1) * 56)
#define AR_P(q) ((q) >> 1)
#define AR_ROW(i) (24 + ((i) & 1) * 16 + ((i) & 2) * 92 + (((i) >> 2) & 7) + ((i) >> 5) * 128)
constexpr size_t AR_OFF = 32 * 262144;
__device__ __forceinline__ void ar_fetch(uint32_t dst, const CUtensorMap* m, int slot, int half, uint32_t mb) {
  asm volatile("{.reg .pred p; elect.sync _|p, 0xffffffff; @p mbarrier.arrive.expect_tx.shared.b64 _,[%4],10240;\n"
               "@p cp.async.bulk.tensor.3d.shared::cluster.global.mbarrier::complete_tx::bytes [%0],[%1,{%2,%6,%3}],[%4];\n"
               "@p cp.async.bulk.tensor.3d.shared::cluster.global.mbarrier::complete_tx::bytes [%0+5120],[%1,{%2,%7,%5}],[%4];}"
               ::"r"(dst), "l"(m), "r"(slot * 64), "r"(AR_R(half * 2)), "r"(mb), "r"(AR_R(half * 2 + 1)), "r"(AR_P(half * 2)), "r"(AR_P(half * 2 + 1)) : "memory");
}
__device__ __forceinline__ uint4 exch_b128(void* p, uint32_t x, uint32_t y, uint32_t z, uint32_t w) {
  uint4 v;
  asm volatile("{.reg .b128 s, t; .reg .b64 a,b; mov.b64 a,{%5,%6}; mov.b64 b,{%7,%8}; mov.b128 s,{a,b}; atom.relaxed.gpu.global.exch.b128 t,[%4],s;"
               " mov.b128 {a,b},t; mov.b64 {%0,%1},a; mov.b64 {%2,%3},b;}" : "=r"(v.x), "=r"(v.y), "=r"(v.z), "=r"(v.w) : "l"(p), "r"(x), "r"(y), "r"(z), "r"(w) : "memory");
  return v;
}
#define CONSUME(v) do { if ((v) == 0x7fc12345u) sts1(sb + rec::BARS + 96, 0); } while (0)
__device__ __forceinline__ uint32_t tagf(float v, uint32_t tag) { return (__float_as_uint(v) & ~1u) | tag; }
__device__ __forceinline__ uint2 ldg_b64(const void* p) { uint2 v; asm volatile("{.reg .b64 t; ld.relaxed.gpu.global.b64 t,[%2]; mov.b64 {%0,%1},t;}" : "=r"(v.x), "=r"(v.y) : "l"(p) : "memory"); return v; }
__device__ __forceinline__ void stg_b64(void* p, uint32_t x, uint32_t y) { asm volatile("{.reg .b64 t; mov.b64 t,{%1,%2}; st.relaxed.gpu.global.b64 [%0],t;}" ::"l"(p), "r"(x), "r"(y) : "memory"); }
__device__ __forceinline__ uint32_t tagbad(uint32_t x, uint32_t y, uint32_t tag) { uint32_t r; asm("lop3.b32 %0,%1,%2,%3,0x7e;" : "=r"(r) : "r"(x), "r"(y), "r"(tag)); return r; }

__device__ __forceinline__ bool anybad(uint32_t a, uint32_t b, uint32_t c, uint32_t d, uint32_t e, uint32_t f, uint32_t g, uint32_t h, uint32_t tag) {
  uint32_t r;
  asm volatile("{.reg .b32 t,u,v,w; .reg .pred p; lop3.b32 t,%1,%2,%9,0x7e; lop3.b32 u,%3,%4,%9,0x7e; lop3.b32 v,%5,%6,%9,0x7e; lop3.b32 w,%7,%8,%9,0x7e;"
               " lop3.b32 t,t,u,v,0xfe; lop3.b32 t,t,w,1,0xa8; setp.ne.u32 p,t,0; vote.sync.any.pred p,p,0xffffffff; selp.u32 %0,1,0,p;}"
               : "=r"(r) : "r"(a), "r"(b), "r"(c), "r"(d), "r"(e), "r"(f), "r"(g), "r"(h), "r"(tag));
  return r;
}
__device__ __forceinline__ bool anybad(uint32_t a, uint32_t b, uint32_t c, uint32_t d, uint32_t tag) {
  uint32_t r;
  asm volatile("{.reg .b32 t,u; .reg .pred p; lop3.b32 t,%1,%2,%5,0x7e; lop3.b32 u,%3,%4,%5,0x7e;"
               " lop3.b32 t,t,u,1,0xa8; setp.ne.u32 p,t,0; vote.sync.any.pred p,p,0xffffffff; selp.u32 %0,1,0,p;}"
               : "=r"(r) : "r"(a), "r"(b), "r"(c), "r"(d), "r"(tag));
  return r;
}
#define BAD8(r) anybad(r[0].x, r[0].z, r[1].x, r[1].z, r[2].x, r[2].z, r[3].x, r[3].z, tag)
#define BADS(r) anybad(r[0].x, r[0].y, r[1].x, r[1].y, r[2].x, r[2].y, r[3].x, r[3].y, tag)
constexpr float SCS = 0.08838834764831845f * 1.4426950408889634f / 16.f;
__device__ __forceinline__ uint32_t pkh(float lo, float hi, uint32_t tag) {
  uint32_t r;
  asm("{.reg .b32 t; cvt.rn.satfinite.f16x2.f32 t,%1,%2; lop3.b32 %0,t,0xfffffffe,%3,0xea;}" : "=r"(r) : "f"(hi), "f"(lo), "r"(tag));
  return r;
}
__device__ __forceinline__ uint32_t addh(uint32_t a, uint32_t b) { uint32_t r; asm("add.rn.f16x2 %0,%1,%2;" : "=r"(r) : "r"(a), "r"(b)); return r; }
__device__ __forceinline__ float hlo(uint32_t v) { float r; asm("{.reg .b16 a,b; mov.b32 {a,b},%1; cvt.f32.f16 %0,a;}" : "=f"(r) : "r"(v)); return r; }
__device__ __forceinline__ float hhi(uint32_t v) { float r; asm("{.reg .b16 a,b; mov.b32 {a,b},%1; cvt.f32.f16 %0,b;}" : "=f"(r) : "r"(v)); return r; }
__device__ __forceinline__ uint32_t ordh(uint32_t v) {
  uint32_t r;
  asm("{.reg .b32 m; prmt.b32 m,%1,0,0xbb99; lop3.b32 %0,%1,m,0x7fff7fff,0x78;}" : "=r"(r) : "r"(v));
  return r;
}
template <bool MASK>
__device__ __forceinline__ float4 softmax2(const uint2 (&r)[4], uint32_t mx, uint32_t my, uint32_t& k) {
  uint32_t x = addh(addh(r[0].x, r[1].x), addh(r[2].x, r[3].x)), y = addh(addh(r[0].y, r[1].y), addh(r[2].y, r[3].y));
  if (MASK) { x = addh(x, mx); y = addh(y, my); }
  asm("max.f16x2 %0,%1,%2;" : "=r"(k) : "r"(x), "r"(y));
  k = ordh(k);
  const int k0 = __reduce_max_sync(~0u, (int)(k << 16)), k1 = __reduce_max_sync(~0u, (int)k);
  const float m0 = hhi(k0 ^ ((k0 >> 31) & 0x7fff0000)) * -16.f, m1 = hhi(k1 ^ ((k1 >> 31) & 0x7fff0000)) * -16.f;
  return make_float4(ex2(fmaf(hlo(x), 16.f, m0)), ex2(fmaf(hhi(x), 16.f, m1)), ex2(fmaf(hlo(y), 16.f, m0)), ex2(fmaf(hhi(y), 16.f, m1)));
}
__device__ __forceinline__ char* mkp(uint32_t lo, uint32_t hi) { uint64_t r; asm("mov.b64 %0,{%1,%2};" : "=l"(r) : "r"(lo), "r"(hi)); return (char*)r; }
#define LO(p) ((uint32_t)(uint64_t)(p))
#define HI(p) ((uint32_t)((uint64_t)(p) >> 32))
__device__ __forceinline__ void cp16(uint32_t dst, const void* src) { asm volatile("cp.async.cg.shared.global [%0],[%1],16;" ::"r"(dst), "l"(src) : "memory"); }
__device__ __forceinline__ uint32_t xor3(uint32_t a, uint32_t b, uint32_t c) { uint32_t r; asm volatile("lop3.b32 %0,%1,%2,%3,0x96;" : "=r"(r) : "r"(a), "r"(b), "r"(c)); return r; }
__device__ __forceinline__ uint32_t mulbf(uint32_t a, uint32_t b) { uint32_t r; asm("mul.rn.bf16x2 %0,%1,%2;" : "=r"(r) : "r"(a), "r"(b)); return r; }
__device__ __forceinline__ uint32_t fmabf(uint32_t a, uint32_t b, uint32_t c) { uint32_t r; asm("fma.rn.bf16x2 %0,%1,%2,%3;" : "=r"(r) : "r"(a), "r"(b), "r"(c)); return r; }
__device__ __forceinline__ uint32_t addbf(uint32_t a, uint32_t b) { uint32_t r; asm("add.rn.bf16x2 %0,%1,%2;" : "=r"(r) : "r"(a), "r"(b)); return r; }
__device__ __forceinline__ void pv_mem(const uint32_t (&p)[4], uint32_t pm, const uint4 (&v)[4], const uint4 (&vn)[2], uint32_t (&O)[4]) {
  float o[4][4] = {{0, 0, 0, 0}, {0, 0, 0, 0}, {0, 0, 0, 0}, {0, 0, 0, 0}};
  mma16(o[0], v[0].x, v[0].y, v[0].z, v[0].w, p[0], p[1]);
  mma16(o[1], v[2].x, v[2].y, v[2].z, v[2].w, p[0], p[1]);
  mma16(o[2], v[1].x, v[1].y, v[1].z, v[1].w, p[2], p[3]);
  mma16(o[3], v[3].x, v[3].y, v[3].z, v[3].w, p[2], p[3]);
  mma16(o[0], vn[0].x, vn[0].y, vn[0].z, vn[0].w, pm, pm);
  mma16(o[1], vn[1].x, vn[1].y, vn[1].z, vn[1].w, pm, pm);
  O[0] = pk(o[0][0] + o[2][0], o[0][1] + o[2][1]); O[1] = pk(o[0][2] + o[2][2], o[0][3] + o[2][3]);
  O[2] = pk(o[1][0] + o[3][0], o[1][1] + o[3][1]); O[3] = pk(o[1][2] + o[3][2], o[1][3] + o[3][3]);
}
__device__ __forceinline__ void pv_tok(const uint32_t (&p)[4], uint32_t pm, const uint4 (&v)[4], const uint32_t (&vm)[4], uint32_t (&O)[4]) {
  float o[2][4] = {{0, 0, 0, 0}, {0, 0, 0, 0}}, sum[4] = {0, 0, 0, 0};
  const uint32_t one = 0x3f803f80u;
  mma16(sum, one, one, one, one, p[0], p[1]);
  mma16(o[0], v[0].x, v[0].y, v[0].z, v[0].w, p[0], p[1]);
  mma16(o[1], v[2].x, v[2].y, v[2].z, v[2].w, p[0], p[1]);
  mma16(sum, one, one, one, one, p[2], p[3]);
  mma16(o[0], v[1].x, v[1].y, v[1].z, v[1].w, p[2], p[3]);
  mma16(o[1], v[3].x, v[3].y, v[3].z, v[3].w, p[2], p[3]);
  mma8(sum, one, one, pm);
  mma8(o[0], vm[0], vm[1], pm);
  mma8(o[1], vm[2], vm[3], pm);
  float i0, i1;
  asm("rcp.approx.ftz.f32 %0,%1;" : "=f"(i0) : "f"(sum[0]));
  asm("rcp.approx.ftz.f32 %0,%1;" : "=f"(i1) : "f"(sum[1]));
  O[0] = pk(o[0][0] * i0, o[0][1] * i1); O[1] = pk(o[0][2] * i0, o[0][3] * i1);
  O[2] = pk(o[1][0] * i0, o[1][1] * i1); O[3] = pk(o[1][2] * i0, o[1][3] * i1);
}
__device__ __forceinline__ uint32_t sum4bf(uint32_t a, uint32_t b, uint32_t c, uint32_t d) { return addbf(addbf(a, b), addbf(c, d)); }
template <int OFF>
__device__ __forceinline__ void sta1(uint32_t a, uint32_t v, uint32_t mb) {
  asm volatile("st.async.shared::cluster.mbarrier::complete_tx::bytes.b32 [%0+%3],%1,[%2];" ::"r"(a), "r"(v), "r"(mb), "n"(OFF) : "memory");
}

__device__ __forceinline__ void wait_time(uint32_t t) { while ((int)(gtime() - t) < 0) __nanosleep(64); }
__device__ __noinline__ void rec_prefetch(const char* wmod, const char* w1, const char* x, const char* wo) {
  const int hb = blockIdx.x - 128;
  const uint32_t t0 = gtime();
  uint32_t t = t0 + PF0;
#pragma unroll 1
  for (int job = 0; job < (PFT ? 5 : 3); job++) {
    const char* p = job == 0 ? x + (6 + hb) * 65536 : job == 1 ? wmod + hb * 12288 + 4096 : job == 2 ? w1 + hb * 7168 : job == 3 ? x + hb * 8192 : wo + (1020 + hb) * 8192;
    const int n = job == 0 ? 120 - (hb & 2) * 4 : job == 3 ? 128 : 256, d = job == 0 ? 8192 : job == 1 ? 49152 : job == 2 ? 28672 : job == 3 ? 32768 : -32768;
    if (job == 3) t = t0 + PFT;
    PT(8 + job);
#pragma unroll 1
    for (int i = 0; i < n; i++) {
      wait_time(t);
      asm volatile("cp.async.bulk.prefetch.L2.global [%0], %1;" ::"l"(p), "r"(job == 2 ? 7168 : 8192) : "memory");
      p += !job && (i & 7) == 7 ? 204800 : d;
      t += job < 3 ? PFD : PFS;
      if (job && (i & 31) == 31 && ldg_rlx1(&g_fin)) return;
    }
  }
  PT(13);
}
__device__ __noinline__ void rec_helper(uint32_t sb, const bf16* cvec, const bf16* wmod, const char* w1, const bf16* b1, uint32_t t0) {
  const int tid = threadIdx.x, hb = blockIdx.x - 128;
  PT(1);
  for (int i = tid; i < 1024; i += 256) sts1(sb + i * 8, U_(rbf(silu(__bfloat162float(cvec[i])))));
  for (int i = tid; i < 2048; i += 256) g_stat[hb * 2048 + i] = make_uint4(~0u, ~0u, ~0u, ~0u);
  for (int i = tid; i < 512; i += 256) g_cnt[hb * 512 + i] = 0;
#pragma unroll 1
  for (int job = 0; job < 2; job++) {
    wait_time(t0 + PF0 + (job ? 600 : 350) * PFD);
    BAR_SYNC(rec::B_F, 256);
    PT(2 + job * 5);
    const int n8 = job ? 112 : 128, rg = tid >= n8, cg = tid - rg * n8, pitch = job ? 448 : 768;
    const uint4* p = (const uint4*)(job ? w1 + hb * 1792 : (const char*)(wmod + 2048 + hb * 1024)) + rg * pitch + min(cg, n8 - 1);
    float a1[8] = {0, 0, 0, 0, 0, 0, 0, 0}, a2[8] = {0, 0, 0, 0, 0, 0, 0, 0};
#pragma unroll 1
    for (int r0 = rg; r0 < 1024; r0 += 32) {
      uint4 v[16];
#pragma unroll
      for (int i = 0; i < 16; i++) { v[i] = ldg_rlx4(p); p += 2 * pitch; }
#pragma unroll
      for (int i = 0; i < 16; i++) {
        const float2 f = lds2f(sb + (r0 + 2 * i) * 8);
        const float w[8] = {blo(v[i].x), bhi(v[i].x), blo(v[i].y), bhi(v[i].y), blo(v[i].z), bhi(v[i].z), blo(v[i].w), bhi(v[i].w)};
#pragma unroll
        for (int e = 0; e < 8; e++) { a1[e] += f.x * w[e]; a2[e] += f.y * w[e]; }
      }
    }
    const uint32_t rd = sb + 8192;
    if (cg < n8) {
#pragma unroll
      for (int e = 0; e < 8; e++) sts2(rd + rg * 8192 + (cg * 8 + e) * 8, U_(a1[e]), U_(a2[e]));
    }
    BAR_SYNC(rec::B_F, 256);
    if (job == 0) {
      for (int i = tid; i < 1024; i += 256) g_mod[2048 + hb * 1024 + i] = rbf(F_(lds1(rd + i * 8)) + F_(lds1(rd + 8192 + i * 8)));
      BAR_SYNC(rec::B_F, 256);
      PT(6);
      if (tid == 0) { red_rel(&g_mcnt); wait_cnt(&g_mcnt, 4); }
      BAR_SYNC(rec::B_F, 256);
      for (int i = tid; i < 1024; i += 256) sts2(sb + i * 8, U_(rbf(1.f + __ldcg(g_mod + 4096 + i))), U_(__ldcg(g_mod + 3072 + i)));
    } else {
      for (int i = tid; i < 448; i += 256) {
        const int gn = hb * 896 + i * 2;
        const uint32_t bb = *(const uint32_t*)(b1 + gn);
        const float4 u = lds4f(rd + i * 16), w = lds4f(rd + 8192 + i * 16);
        ((uint2*)g_cc)[(gn >> 4) * 8 + ((gn >> 1) & 3) * 2 + ((gn >> 3) & 1)] = make_uint2(pk(u.x + w.x, u.z + w.z), pk(0.5f * (u.y + w.y + blo(bb)), 0.5f * (u.w + w.w + bhi(bb))));
      }
      PT(4);
    }
  }
}

__global__ void __cluster_dims__(2, 1, 1) __launch_bounds__(512, 1)
k_rec(const __grid_constant__ RecMaps mp, const bf16* __restrict__ mem0, const bf16* __restrict__ x, const bf16* __restrict__ cvec,
      const bf16* __restrict__ wmod, const char* __restrict__ w1, const bf16* __restrict__ b1, const char* __restrict__ wo, char* xc, int dF, int dA, int dS, int dM, int dG, int dP, int dX, int dD, int dZ, int dZ2, int dV, int dX2) {
  using namespace rec;
  extern __shared__ __align__(1024) char smem[];
  const uint32_t sb = (uint32_t)__cvta_generic_to_shared(smem);
  if ((sb & 0x3FFFF) != 1024) __trap();
  PH(0); RS(0); if (threadIdx.x == 0) PT(0);
  if (threadIdx.x == 0) {
    int b = blockIdx.x;
    if (b >= 8 && b < 128) {
      const int t = (b >> 1) - 4, u = t - 32;
      b = 2 * (t < 32 ? 4 + (t & 16) + (t & 7) * 2 + ((t >> 3) & 1) : 36 + (u / 14) * 14 + (u % 7) * 2 + ((u / 7) & 1)) + (b & 1);
    }
    sts1(sb + rec::PACE + 24, b);
    const int c = blockIdx.x >> 1, l = c < 36 ? (c - 4) & 7 : (c - 36) % 7, m = c < 4 ? c : c < 36 ? (c - 4) >> 3 : (c - 36) / 7;
    const int g = c < 4 ? 15 : (l >> 1) * 4 + (l & 1) + (c < 36 ? 0 : 2);
    unsigned sm;
    asm("mov.u32 %0,%%smid;" : "=r"(sm));
    if (c < 64) g_slot[sm & 255] = 1 + FMAP;
  }
#define ROLE_REFRESH { asm volatile("mov.u32 %0,%%tid.x;" : "=r"(tid)); wid = __shfl_sync(~0u, tid >> 5, 0); b = __shfl_sync(~0u, lds1(sb + PACE + 24), 0); }
#define ROLE_VARS int tid; asm volatile("mov.u32 %0,%%tid.x;" : "=r"(tid)); \
    int wid = __shfl_sync(~0u, tid >> 5, 0), b = __shfl_sync(~0u, lds1(sb + PACE + 24), 0);
#define wg (wid >> 2)
#define iw (wid & 3)
#define h (b >> 2)
#define j (b & 3)
#define a (b & 1)
#define bb ((b >> 1) & 1)
  const uint32_t wbar = sb + BARS + 48, obar = wbar + 8;
  if (threadIdx.x == 256) {
    for (int i = 0; i < 18; i++) if (i != 12) mbar_init(sb + BARS + i * 8, i == 3 || i == 8 || i == 9 || i == 10 ? 2 : 1);
    for (int i = 0; i < 3; i++) mbar_init(sb + PACE + i * 8, 1);
    asm volatile("fence.mbarrier_init.release.cluster;" ::: "memory");
    FENCE_ASYNC_SMEM();
    mbar_expect(sb + BARS, 2048);
    mbar_expect(sb + BARS + 16, 4096);
    mbar_expect(sb + BARS + 32, 4096);
    mbar_expect(sb + BARS + 40, 4096);
  }
  __syncthreads();
  asm volatile("barrier.cluster.arrive.relaxed.aligned;" ::: "memory");
#define lane ((int)(l16 >> 4))
#define l16 (L16 & 0x1f0)
#define is7 ((L16 & 112) == 112)
#define PIN(x) __shfl_xor_sync(~0u, (uint32_t)(x), 0)
#define REFRESH() L16 = __shfl_xor_sync(~0u, L16, 0)
#define lar ((L16 & 0x180) * 8 + (L16 & 0x70))
#define X_LOAD(n, w, u) \
        asm volatile("{.reg .pred p; elect.sync _|p, 0xffffffff; @p mbarrier.arrive.expect_tx.shared.b64 _,[%2],8192;\n" \
                     "@p cp.async.bulk.shared::cluster.global.mbarrier::complete_tx::bytes [%0],[%1],8192,[%2];}" ::"r"(sb + XB + (w) * 16384 + (u) * 8192), \
                     "l"(g_h + (n) * 4096 + a * 2048 + (w) * 1024 + (u) * 512), "r"(sb + BARS + 64 + (w) * 8) : "memory")
#define lpub ((L16 & 0x30) * 64 + ((L16 >> 3) & 0x38))
#define lrow ((L16 & 0x70) + (((L16 >> 3) ^ L16) & 0x70 & ~((L16 >> 3) & 0x40) ? L16 & 0x180 : 512))

  const int role = __shfl_sync(~0u, threadIdx.x >> 7, 0);
  if (role < 2) {
    asm volatile("setmaxnreg.inc.sync.aligned.u32 %0;" ::"n"(RF_));
    ROLE_VARS
    uint32_t L16 = __shfl_sync(~0u, sb + (tid & 31) * 16, tid & 31);
    uint32_t wQ[16][4], wK[16][4], wV[NVR][4];
    uint32_t frag = sb + ((lane & 7) + (lane >> 4) * 8) * 128 + (((iw * 2 + ((lane >> 3) & 1)) ^ (lane & 7)) << 4);
#define QSW (SWP && !a ? 64 : 0)
    {
      const bool spare = b >= 128;
      const uint32_t t0 = gtime();
      uint4 xr[16];
      int seg = spare ? b - 126 : wg;
      const int half = spare ? wg : a;
      auto x_fetch = [&]() {
        const uint4* px = (const uint4*)x + (seg * 32 + iw * 8 + (lane >> 2)) * 128 + half * 64 + (lane & 3);
#pragma unroll
        for (int i = 0; i < 16; i++) xr[i] = __ldg(px + i * 4);
      };
      if (!spare) {
        uint4 wm[8];
        const uint4* pw = (const uint4*)(wmod + (size_t)((b >> 5) * 256 + (tid >> 3)) * 6144 + (b & 31) * 64) + (tid & 7);
        const float cs = __bfloat162float(cvec[(b >> 5) * 256 + tid]);
#pragma unroll
        for (int i = 0; i < 8; i++) wm[i] = __ldcs(pw + (size_t)i * 32 * 768);
        float* sc = (float*)(smem + PRE);
        sc[tid] = rbf(silu(cs));
        PT(1);
        BAR_SYNC(B_F, 256);
        float acc[8] = {0, 0, 0, 0, 0, 0, 0, 0};
#pragma unroll
        for (int i = 0; i < 8; i++) {
          const float f = sc[i * 32 + (tid >> 3)];
          acc[0] += f * blo(wm[i].x); acc[1] += f * bhi(wm[i].x); acc[2] += f * blo(wm[i].y); acc[3] += f * bhi(wm[i].y);
          acc[4] += f * blo(wm[i].z); acc[5] += f * bhi(wm[i].z); acc[6] += f * blo(wm[i].w); acc[7] += f * bhi(wm[i].w);
        }
#pragma unroll
        for (int i = 0; i < 8; i++) { acc[i] += __shfl_xor_sync(~0u, acc[i], 8); acc[i] += __shfl_xor_sync(~0u, acc[i], 16); }
        float* red = sc + 1024;
        if ((tid & 31) < 8) {
#pragma unroll
          for (int i = 0; i < 8; i++) red[(tid >> 5) * 64 + (tid & 7) * 8 + i] = acc[i];
        }
        BAR_SYNC(B_F, 256);
        PT(2);
        if (tid < 64) {
          float t = 0;
#pragma unroll
          for (int i = 0; i < 8; i++) t += red[i * 64 + tid];
          asm volatile("st.relaxed.gpu.global.u32 [%0],%1;" ::"l"((unsigned*)g_modp + (b >> 5) * 2048 + (b & 31) * 64 + tid), "r"(U_(t) | 1u) : "memory");
        }
      } else {
        asm volatile("griddepcontrol.launch_dependents;");
      }
      x_fetch();
      const uint32_t md = sb + PRE + 6144, rx = mapa(sb, a ^ !spare);
      asm volatile("barrier.cluster.wait.aligned;" ::: "memory");
      if (!spare) {
        mbar_wait(sb + BARS + 88, 0);
#pragma unroll
        for (int i = 0; i < 16; i++) ldsm4t(wQ[i], (frag ^ QSW) + WO + wg * 32768 + i * 2048);
      }
      PT(4);
#pragma unroll 1
      for (int it = 0;; it++) {
        if (tid == 0) mbar_expect(sb + BARS + 104, 512);
        float c[4][4] = {{0, 0, 0, 0}, {0, 0, 0, 0}, {0, 0, 0, 0}, {0, 0, 0, 0}};
#pragma unroll
        for (int i = 0; i < 16; i++) {
          mma16(c[(i & 1) * 2], xr[i].x, 0x3f803f80u, xr[i].y, 0x3f803f80u, xr[i].x, xr[i].y);
          mma16(c[(i & 1) * 2 + 1], xr[i].z, 0x3f803f80u, xr[i].w, 0x3f803f80u, xr[i].z, xr[i].w);
        }
#pragma unroll
        for (int e = 0; e < 4; e++) c[0][e] = (c[0][e] + c[1][e]) + (c[2][e] + c[3][e]);
        const int src = (lane & 28) + (lane >> 3);
        const float sq = __shfl_sync(~0u, (lane & 4) ? c[0][1] : c[0][0], src), sm = __shfl_sync(~0u, (lane & 4) ? c[0][3] : c[0][2], src);
        if ((lane & 3) < 2) sta1<0>(rx + PRE + 10240 + (wid ^ (spare * 4)) * 64 + (lane >> 2) * 8 + (lane & 1) * 4, U_((lane & 1) ? sm : sq), rx + BARS + 104);
        mbar_wait(sb + BARS + 104, it & 1);
        const float2 ot = lds2f(sb + PRE + 10240 + wid * 64 + (lane >> 2) * 8);
        const float mean = (sm + ot.y) * (1.f / 1024);
        const float rs = rsqrtf(fmaxf((sq + ot.x) * (1.f / 1024) - mean * mean, 0.f) + 1e-5f), nm = -mean * rs;
        const uint32_t rh = pk(rs, rs), rl = pk(rs - blo(rh), rs - blo(rh)), n2 = pk(nm, nm);
#define NRM(v) v = fmabf(v, rh, fmabf(v, rl, n2))
#pragma unroll
        for (int i = 0; i < 16; i++) { NRM(xr[i].x); NRM(xr[i].y); NRM(xr[i].z); NRM(xr[i].w); }
        if (!it) {
          PT(3);
#pragma unroll 1
          for (int i = 0; i < 2; i++) {
            uint4 p[4];
            for (int n = 0;; n++) {
#pragma unroll
              for (int e = 0; e < 4; e++) p[e] = ldg_rlx4(g_modp + e * 512 + i * 256 + tid);
              uint32_t ok = 1;
#pragma unroll
              for (int e = 0; e < 4; e++) ok &= p[e].x & p[e].y & p[e].z & p[e].w;
              if (__all_sync(~0u, ok) || n > SPIN_LIMIT / 16) break;
              __nanosleep(100);
            }
#define MSUM(e) (i + rbf((F_(p[0].e) + F_(p[1].e)) + (F_(p[2].e) + F_(p[3].e))))
            sts2(md + i * 2048 + tid * 8, pk(MSUM(x), MSUM(y)), pk(MSUM(z), MSUM(w)));
          }
          BAR_SYNC(B_F, 256);
          PT(5);
        }
        const int e0 = (iw * 8 + (lane >> 2)) * 8 + ((lane & 3) ^ (lane >> 2));
        uint4* dst = g_h + seg * 4096 + half * 2048;
#pragma unroll
        for (int i = 0; i < 16; i++) {
          const uint32_t ma = md + half * 1024 + (lane & 3) * 16 + i * 64;
          const uint4 sv = lds4(ma), cv = lds4(ma + 2048);
          xr[i] = make_uint4(fmabf(xr[i].x, cv.x, sv.x), fmabf(xr[i].y, cv.y, sv.y), fmabf(xr[i].z, cv.z, sv.z), fmabf(xr[i].w, cv.w, sv.w));
        }
        if (!spare) {
#pragma unroll
          for (int i = 0; i < 16; i++) sts4(sb + WO + wg * 32768 + (e0 ^ ((i & 1) * 4)) * 16 + (i >> 1) * 4096, xr[i].x, xr[i].y, xr[i].z, xr[i].w);
          break;
        }
#pragma unroll
        for (int i = 0; i < 16; i++) dst[(e0 ^ ((i & 1) * 4)) + (i >> 1) * 256] = xr[i];
        seg += 4;
        if (seg < 64) x_fetch();
        FENCE_ASYNC();
        BAR_SYNC(B_F, 256);
        if (tid == 0) red_rlx(g_hf + b - 128);
        if (seg >= 64) break;
      }
      if (spare) { rec_helper(sb, cvec, wmod, w1, b1, t0); return; }
      PH(1); PH(2); PT(6);
    }
    ROLE_REFRESH
#define ownv ((iw >> 1) == a)
#define owner (SWP ? iw >= 2 : ownv)
#define vfin ((wid >> 1) == a)
#define oi (wid & 1)
    {
      const uint32_t rsb = mapa(sb, owner ? a : a ^ 1);
      const uint32_t pp = rsb + PK + (owner ? 0 : 12288) + (oi * 2048 + wg * 1024) + l16;
      const uint32_t mb = sb + MEM + wg * 5120;
      sts4(L16 + TF + wid * 512, mb + lrow, owner ? L16 + (lane >> 4) * (RK - RQ - 256) + RQ + oi * 1024 + wg * 256 : rsb + RQ + oi * 1024 + 512 + wg * 256 + (l16 >> 2),
           L16 + OB, frag + wg * NVS * 2048);
      sts4(L16 + TF + 4096 + wid * 512, sb + WO + (wid >> 1) * 16384 + ((lane & 7) + (lane >> 4) * 8) * 128 + ((((wid & 1) * 4 + ((lane >> 3) & 1)) ^ (lane & 7)) << 4),
           DR ? LO(xc) + (uint32_t)AR_OFF + (AR_P(j) * 128 + AR_R(j) + wid) * 1024 + (l16 >> 2) : sb + ARO + wid * 640 + lrow, pp, LO(xc) + h * 262144 + (bb * 2 + (iw >> 1)) * XC + X_VM(0) + oi * 2048 + a * 256 + (l16 >> 1));
    }
    uint32_t tp = L16 + TF + wid * 512;
    auto park_ptr = [&]() { return lds1(tp + 4096 + 8); };
    auto park_w = [&](const uint32_t* w, int m, uint32_t d) {
      if (SWP && m == 2) d += (sb & 0x1000000) ? 0 : owner ? 0x1003000 : -0x1003000;
      if (m == 2 ? ownv : owner) {
        sts4(d + m * 4096, w[0], w[1], w[2], w[3]); sts4(d + m * 4096 + 512, w[4], w[5], w[6], w[7]);
      } else {
        const uint32_t pb = (d & 0xff000000u) | (1024 + BARS + (m ? 24 + m * 8 : 16));
        sta4(d + m * 4096, w, pb); sta4(d + m * 4096 + 512, w + 4, pb);
      }
    };
    auto park = [&](const float* f, int m, int n, uint32_t d) {
      uint32_t w[8];
#pragma unroll
      for (int i = 0; i < 8; i++) w[i] = pk(f[2 * i], f[2 * i + 1]);
      park_w(w, m, d);
    };
#define D64(lo) (0x4000004000000000ull | (uint32_t)(lo))
#define XD(i) D64(x | (((i) >> 2) * 256 + ((i) & 3) * 2))
    auto xdesc = [&](uint32_t xb) { return ((uint32_t)__shfl_sync(~0u, 1024 + xb + wg * 16384, 0) >> 4) | 0x10000u; };
    auto rs_issue = [&](float* acc, const uint32_t (&w)[16][4], uint32_t xb, bool fence) {
      const uint32_t x = xdesc(xb);
      if (fence) WG_FENCE();
      wgmma_rs_n32_z(acc, w[0], XD(0));
#pragma unroll
      for (int i = 1; i < 16; i++) wgmma_rs_n32(acc, w[i], XD(i), 1);
      WG_COMMIT();
    };
    auto v_issue = [&](float* acc, uint32_t xb, bool fence) {
      const uint32_t dv = ((uint32_t)__shfl_sync(~0u, 1024 + WVS + wg * NVS * 2048, 0) >> 4) | 0x10000u, x = xdesc(xb);
      if (fence) WG_FENCE();
      wgmma_rs_n32_z(acc, wV[0], XD(0));
#pragma unroll
      for (int i = 1; i < VRF; i++) wgmma_rs_n32(acc, wV[i], XD(i), 1);
#pragma unroll
      for (int i = NVR; i < 16; i++) wgmma_ssT_n32(acc, D64(dv + (i - NVR) * 128), XD(i), 1);
#pragma unroll
      for (int i = VRF; i < NVR; i++) wgmma_rs_n32(acc, wV[i], XD(i), 1);
      WG_COMMIT();
    };
    uint32_t mA, vP[2][4], kw[8], kd;
#define V_AHEAD mA = lds1(tp); frag = lds1(tp + 12); ldsm4t(vP[0], frag + WVS + (15 - NVR) * 2048); ldsm4t(vP[1], frag + WVS + (14 - NVR) * 2048);
    auto vk_pass = [&](int n, uint32_t d, uint32_t xb, bool steady, auto between) {
      float acc[16], acc2[16];
      v_issue(acc, xb, true);
      rs_issue(acc2, wK, xb, false);
      between();
      if (steady || n) mbar_wait(sb + BARS + 80, (n - 1) & 1);
      WG_WAIT(1);
      park(acc, 2 - !!KVO, n, d);
      if (steady) BAR_ARRIVE(B_K, 320);
      V_AHEAD
      WG_WAIT(0);
      kd = d + (VPC ? (vP[1][0] ^ mA) & dZ : 0);
#pragma unroll
      for (int i = 0; i < 8; i++) kw[i] = pk(acc2[2 * i], acc2[2 * i + 1]);
      if (!KDF || (!steady && !n)) park_w(kw, 1, kd);
    };
    uint32_t q0[8], q1[8];
    {
      float acc[16], acc2[16];
      FENCE_ASYNC_SMEM();
      BAR_SYNC(B_F, 256);
      rs_issue(acc, wQ, WO, true);
      rs_issue(acc2, wQ, WO + 32768, false);
      WG_WAIT(0);
#pragma unroll
      for (int i = 0; i < 8; i++) { q0[i] = pk(acc[2 * i], acc[2 * i + 1]); q1[i] = pk(acc2[2 * i], acc2[2 * i + 1]); }
    }
    mbar_wait(wbar, 0);
    PT(7);
#pragma unroll
    for (int i = 0; i < 16; i++) ldsm4t(wK[i], (frag ^ QSW) + XB + wg * 32768 + i * 2048);
#pragma unroll
    for (int i = 0; i < NVR; i++) ldsm4t(wV[i], frag + MEM + (wg * NVR + i) * 2048);
    FENCE_ASYNC_SMEM();
    PH(3); PT(8);
    CLUSTER_SYNC();
    PT(9);
    frag += wg * NVS * 2048;
    park_w(q0, 0, park_ptr());
    PT(10);
#pragma unroll 1
    for (int n = 0; n < 2; n++) {
      asm volatile("" : "+r"(wid));
      vk_pass(n, park_ptr(), n * XB, false, [&]() {
        if (n) {
          BAR_SYNC(B_C, 320);
          PT(12);
          mbar_wait(sb + BARS + 24, 0);
          park_w(q1, 0, park_ptr());
        }
      });
      if (n) break;
      PT(11);
      BAR_SYNC(B_C, 448);
      if (tid == 0) {
        mbar_expect(obar, 65536);
#pragma unroll 1
        for (int i = 0; i < 4; i++) tma2d(sb + WO + i * 16384, &mp.wo, j * 256 + i * 64, h * 128, obar);
      }
    }
    static_assert(WO == 0, "x");
    {
      BAR_ARRIVE(B_P, N_P); if (!KDF) BAR_ARRIVE(B_X, 320); if (XE != 1) BAR_ARRIVE(B_Q, 288);
    }
    PT(13);
    if (!OBL) mbar_wait(obar, 0);
    PH(4); RS(1); PT(14);
    ROLE_REFRESH
    for (int s = 0; s < 64; s++) {
      asm volatile("" : "+r"(tp), "+r"(wid));
      asm volatile("mov.u32 %0,%%cluster_ctarank;" : "=r"(b));
      uint32_t vS[NVS][4], bf[8][4];
      static_assert(NVR == 5, "schedule");
#define VLD(k) ldsm4t(vS[(k) - NVR], frag + WVS + ((k) - NVR) * 2048)
#define BLD(t) ldsm4t(bf[t], mA + (t) * 640)
#define VMMA(c, w, i) mma16(c, (w)[0], (w)[1], (w)[2], (w)[3], bf[(i) >> 1][((i) & 1) * 2], bf[(i) >> 1][((i) & 1) * 2 + 1])
#define VS_(c, k) VMMA(c, vS[(k) - NVR], k)
#define QK(i) VMMA(cQ, wQ[i], i); VMMA(cK, wK[i], i)
#define PREV if (NF) { VLD(13); VLD(12); if (NF > 2) VLD(11); } else { VLD(15); VLD(14); }
      if (s > 0) BAR_SYNC(B_R, N_R);
      float cV[4] = {0, 0, 0, 0}, cW[4] = {0, 0, 0, 0};
      {
        float cQ[4] = {0, 0, 0, 0}, cK[4] = {0, 0, 0, 0};
        BLD(7); BLD(6); BLD(5); BLD(4); if (NB0 > 4) BLD(3);
        if (KDF && s < 63) { park_w(kw, 1, kd); BAR_ARRIVE(B_X, 320); }
        if (!KDF) SCHED_FENCE(47);
        QK(15); VMMA(cV, vP[0], 15);
        QK(14); VMMA(cV, vP[1], 14);
        QK(13); QK(12);
        SCHED_FENCE(51);
        if (NB0 < 5) BLD(3);
        BLD(2); BLD(1); BLD(0);
        const uint32_t rm = lds1(tp + 4);
        if (!NF) frag = lds1(tp + 12);
        QK(11); QK(10); QK(9); QK(8); QK(7);
        if (PV0 == 6) { SCHED_FENCE(48); PREV }
        QK(6); QK(5);
        if (PV0 == 4) { QK(4); SCHED_FENCE(48); PREV } else { QK(4); }
        QK(3); QK(2); QK(1); QK(0);
        const uint32_t w0 = pk(cQ[0] * SCS, cQ[1] * SCS), w1 = pk(cQ[2] * SCS, cQ[3] * SCS), w2 = pk(cK[0], cK[1]), w3 = pk(cK[2], cK[3]);
        if (owner) {
          stsm4(rm, w0, w1, w2, w3);
          BAR_ARRIVE(B_E, 256);
        } else {
          const uint32_t mm = (rm & 0xff000000u) | (1024 + BARS);
          sta1<0>(rm, w0, mm); sta1<128>(rm, w1, mm);
          sta1<RK - RQ>(rm, w2, mm); sta1<RK - RQ + 128>(rm, w3, mm);
        }
        if (wid == 2) TS(0);
      }
      uint4 t1;
      uint32_t oA, wo[16][4];
      {
        if (NF == 0) {
          VLD(13); VLD(12);
          VS_(cW, 15); VS_(cV, 14); VLD(11); VMMA(cW, wV[0], 0); VLD(10); VMMA(cV, wV[1], 1); VLD(9);
          VMMA(cW, wV[2], 2); VLD(8); VMMA(cV, wV[3], 3); VLD(7); VMMA(cW, wV[4], 4); VS_(cV, 13); VLD(6); VS_(cW, 12); VLD(5);
          VS_(cV, 11);
        } else {
          if (NF < 3) VLD(11);
          VLD(10);
          VS_(cW, 13); VLD(9); VS_(cV, 12); VLD(8); VLD(7); VMMA(cW, wV[0], 0); VMMA(cV, wV[1], 1); VLD(6);
          VMMA(cW, wV[2], 2); VMMA(cV, wV[3], 3); VLD(5); VMMA(cW, wV[4], 4); VS_(cV, 11);
        }
        VS_(cW, 10); VS_(cV, 9); VS_(cW, 8); VS_(cV, 7); VS_(cW, 6); VS_(cV, 5);
#pragma unroll
        for (int e = 0; e < 4; e++) cV[e] += cW[e];
        const uint32_t ex = tp + (RX - TF) - wg * 2048;
        t1 = lds4(tp + 4096 + (T1L ? vS[3][0] & dZ : 0));
        oA = lds1(tp + 8 + (s & dZ));
        if (wg) {
          sts4(ex, U_(cV[0]), U_(cV[1]), U_(cV[2]), U_(cV[3]));
          BAR_ARRIVE(B_T2, 256);
        }
#pragma unroll
        for (int i = 0; i < VCO; i++) ldsm4t(wo[i], (t1.x ^ ((i & 1) * 32)) + (i >> 1) * 2048);
        if (!wg) {
          BAR_SYNC(B_T2, 256);
          const float4 u = lds4f(ex);
          stg_b64(mkp(t1.w ^ ((s & 1) * X_RING), HI(xc)), (pk(cV[0] + u.x, cV[1] + u.y) & ~1u) | (((s >> 1) + 1) & 1), pk(cV[2] + u.z, cV[3] + u.w));
        }
      }
      if (s == 63) break;
      if (OBL && s == 0) mbar_wait(obar, 0);
      {
        const uint32_t woA = t1.x, woB = woA ^ 32;
#pragma unroll
        for (int i = VCO; i < NW0; i++) ldsm4t(wo[i], ((i & 1) ? woB : woA) + (i >= WCH ? wo[(i - WCH + NWP) % NWP][0] & dZ : 0) + (i >> 1) * 2048);
        BAR_SYNC(B_S, 416);
        float inv0, inv1;
        uint32_t p[4], pm;
        const uint32_t pa = oA + (SC - OB), one = 0x3f803f80u;
#define P_LOAD ldsm4t(p, pa); asm volatile("ldmatrix.sync.aligned.m8n8.x1.trans.shared.b16 {%0},[%1];" : "=r"(pm) : "r"(pa + 512) : "memory");
        if (s < 62) {
          float acc[16];
          rs_issue(acc, wQ, XB, true);
          mbar_wait(sb + BARS + 24, (s + 1) & 1);
          WG_WAIT(0);
          uint32_t qw[8];
#pragma unroll
          for (int i = 0; i < 8; i++) qw[i] = pk(acc[2 * i], acc[2 * i + 1]);
#pragma unroll
          for (int i = NW0; i < NW1; i++) ldsm4t(wo[i], ((i & 1) ? woB : woA) + (i >> 1) * 2048);
          BAR_SYNC(B_V, N_V);
          if (RSO) { P_LOAD }
          park_w(qw, 0, t1.z + (RSO == 1 ? pm & dZ : 0));
        } else {
#pragma unroll
          for (int i = NW0; i < NW1; i++) ldsm4t(wo[i], ((i & 1) ? woB : woA) + (i >> 1) * 2048);
          BAR_SYNC(B_V, N_V);
          if (RSO) { P_LOAD }
        }
#pragma unroll
        for (int i = NW1; i < NWP; i++) ldsm4t(wo[i], ((i & 1) ? woB : woA) + (i >> 1) * 2048);
        {
          float sum[4] = {0, 0, 0, 0}, su2[4] = {0, 0, 0, 0};
          if (!RSO) { P_LOAD }
          mma16(sum, one, one, one, one, p[0], p[1]);
          mma16(su2, one, one, one, one, p[2], p[3]);
          mma8(sum, one, one, pm);
          inv0 = sum[0] + su2[0]; inv1 = sum[1] + su2[1];
          SCHED_FENCE(57);
        }
        BAR_SYNC(B_O, N_O);
        float c[2][4] = {{0, 0, 0, 0}, {0, 0, 0, 0}};
        uint32_t o[4][4];
#pragma unroll
        for (int i = 0; i < NOP_; i++) ldsm4t(o[i], oA + i * 512);
        SCHED_FENCE(46);
        asm("rcp.approx.ftz.f32 %0,%0;" : "+f"(inv0));
        asm("rcp.approx.ftz.f32 %0,%0;" : "+f"(inv1));
#pragma unroll
        for (int i = 0; i < 16; i++) {
          mma16(c[i & 1], wo[i][0], wo[i][1], wo[i][2], wo[i][3], o[i >> 2][i & 2], o[i >> 2][(i & 2) + 1]);
          if (i == 1 && NOP_ < 3) ldsm4t(o[2], oA + 1024);
          if (i == 3 && NOP_ < 4) ldsm4t(o[3], oA + 1536);
          if (i + NWP < 16) ldsm4t(wo[(i + NWP) & 15], (((i + NWP) & 1) ? woB : woA) + ((i + NWP) >> 1) * 2048);
        }
        const uint32_t r0 = pk(c[0][0] * inv0, c[0][1] * inv1), r1 = pk(c[0][2] * inv0, c[0][3] * inv1), r2 = pk(c[1][0] * inv0, c[1][1] * inv1), r3 = pk(c[1][2] * inv0, c[1][3] * inv1);
        if (DR) {
          char* ap = mkp(t1.y + (s & 7) * 128, HI(xc));
          const uint32_t g = (t1.y >> 4) & 7;
#define AR_RED(m, v) asm volatile("red.relaxed.gpu.global.add.noftz.bf16x2 [%0+%2],%1;" ::"l"(ap), "r"(v), "n"((m) * 131072) : "memory")
          AR_RED(0, g == 0 ? one : r0); AR_RED(1, g == 1 ? one : r1); AR_RED(2, g == 2 ? one : r2); AR_RED(3, g == 3 ? one : r3);
          AR_RED(4, g == 0 ? r0 : g == 1 ? r1 : g == 2 ? r2 : g == 3 ? r3 : one);
        } else {
          stsm4(t1.y, r0, r1, r2, r3);
        }
      }
      const uint32_t d = park_ptr();
      BAR_SYNC(B_W, 384);
      if (s < 62) {
        vk_pass(s + 2, d, XB, true, []() {});
        if (XE == 2) BAR_ARRIVE(B_Q, 288);
        BAR_ARRIVE(B_P, N_P); if (!KDF) BAR_ARRIVE(B_X, 320);
        TS(10);
      } else {
        V_AHEAD
        CONSUME(vP[1][0]);
        kd = 0;
#pragma unroll
        for (int i = 0; i < 8; i++) kw[i] = 0;
      }
    }
  } else if (role == 3) {
    asm volatile("setmaxnreg.dec.sync.aligned.u32 24;");
    if (blockIdx.x >= 128) return;
    ROLE_VARS
    const uint32_t L16 = sb + (tid & 31) * 16;
    asm volatile("barrier.cluster.wait.aligned;" ::: "memory");
    CLUSTER_SYNC();
    sts1(sb + PACE + 36, LO(xc) + h * 262144 + X_VM(0));
    auto vm_stage = [&](int s) {
      if (AV) return;
      const uint32_t tag = ((s >> 1) + 1) & 1;
      const char* xm = mkp(lds1(sb + PACE + 36) + (s & 1) * X_RING + iw * XC + (l16 >> 1), HI(xc));
      uint2 m[4];
      CONSUME(LO(xm));
      BAR_SYNC(B_S2, 256);
      if (dZ2 > 1) { const uint32_t c = clk(); while (clk() - c < (uint32_t)dZ2) {} }
      int it = 0;
      while (true) {
#pragma unroll
        for (int i = 0; i < 4; i++) m[i] = ldg_b64(xm + (i >> 1) * 2048 + (i & 1) * 256);
        sts4(L16 + VN + iw * 512, m[0].x, m[0].y, m[1].x, m[1].y);
        sts4(L16 + VN + iw * 512 + 2048, m[2].x, m[2].y, m[3].x, m[3].y);
        if (HV || !anybad(m[0].x, m[1].x, m[2].x, m[3].x, tag)) break;
        RP(2);
        if (++it > SPIN_LIMIT) __trap();
      }
      if (s < 63) BAR_ARRIVE(B_V, 512); else BAR_ARRIVE(B_V, 256);
    };
    if (iw == 0) {
      wait_cnt(&g_hcnt, 128);
#pragma unroll 1
      for (int s = 0; s < 63; s++) {
        if (s < 62) for (int it = 0; ldg_rlx1(g_hf + (s & 3)) <= (s >> 2); it++) if (it > SPIN_LIMIT) __trap();
        if (XE == 1) BAR_SYNC(B_P, N_P); else if (XE == 2) BAR_SYNC(B_Q, 288); else if (s) BAR_SYNC(B_R, 320); else BAR_SYNC(B_Q, 288);
        if (s < 62) { X_LOAD(s + 2, 0, 0); X_LOAD(s + 2, 1, 0); X_LOAD(s + 2, 0, 1); X_LOAD(s + 2, 1, 1); }
        if (s >= 7) {
          const uint32_t zo = b * 160 + l16;
          if (l16 < 160) CONSUME(exch_b128(xc + AR_OFF + AR_ROW(zo >> 7) * 1024 + (zo & 127) + ((s + 1) & 7) * 128, 0, 0, 0, 0).x);
          __syncwarp();
        }
        if (s < 62) { mbar_wait(sb + BARS + 64, s & 1); mbar_wait(sb + BARS + 72, s & 1); }
        BAR_ARRIVE(B_S, 416);
        vm_stage(s);
        if (!AV) BAR_ARRIVE(B_O, 416);
        BAR_SYNC(B_W, 384);
        if (DR) SCHED_FENCE(69); else FENCE_ASYNC_SMEM();
        if (!DR) asm volatile("{.reg .pred p; elect.sync _|p, 0xffffffff; @p cp.reduce.async.bulk.tensor.3d.global.shared::cta.add.bulk_group [%0,{%1,%4,%2}],[%3];}"
                     ::"l"(&mp.ari), "r"((s & 7) * 64), "r"(AR_R(j)), "r"(sb + ARO), "r"(AR_P(j)) : "memory");
        if (!DR) BULK_COMMIT();
        asm volatile("st.relaxed.gpu.global.u32 [%0],%1;" ::"l"(g_tm + (s & 1) * 128 + b), "r"(gtime()) : "memory");
        TS(3);
        if (!DR) BULK_WAIT_READ(0);
      }
      if (!XE) BAR_ARRIVE(B_R, 320);
    } else if (iw == 1) {
      const uint32_t pc = sb + MEM + (lane >> 2) * 640 + (lane & 3) * 144 + (lane & 12), pd = sb + MEM + (lane & 15) * 640 + 576 + (lane & 3) * 16 + (lane & 12);
      uint32_t T = 0, par = 0;
      int est = dA;
#pragma unroll 1
      for (int s = 0; s < 63; s++) {
        if (s) {
          const uint4 tm = ldg_rlx4((const char*)g_tm + ((s + 1) & 1) * 512 + l16);
          const int t0 = tm.x - T, t1 = tm.y - T, t2 = tm.z - T, t3 = tm.w - T;
          const int e = max(dF + (__reduce_add_sync(~0u, (t0 + t1) + (t2 + t3)) >> 7), dV + __reduce_max_sync(~0u, max(max(t0, t1), max(t2, t3))));
          if (s > 1) est += max(min(e >> 2, dP), -dP);
          T += (s == 1 || e > dM ? e : 0) + est - (s == 62 ? L62 : 0);
        }
        vm_stage(s);
        BAR_SYNC(B_W, 384);
        SCHED_FENCE(70);
        const uint32_t tW = gtime();
        if (s == 0) T = tW + 800;
        const uint32_t te = tW + min(max((int)(T - tW), dD), 2000);
        while ((int)(gtime() - te) < 0) {}
        TS(7);
        int it = 0;
        while (true) {
          ar_fetch(sb + MEM, &mp.ari, s & 7, a, sb + BARS + 112);
          mbar_wait(sb + BARS + 112, par);
          par ^= 1;
          const uint32_t n0 = lds1(pc), n1 = lds1(pc + 5120), n2 = lds1(pd);
          if (!__any_sync(~0u, (tagbad(n0, n1, 0x42004200) | (n2 ^ 0x42004200)) != 0)) break;
          RP(0);
          if (++it > SPIN_LIMIT) __trap();
        }
        BAR_ARRIVE(B_R, N_R);
        TS(11);
      }
    } else {
#define V_LOAD(n) do { if (lane == 0) mbar_expect(sb + BARS + 8, 8192); __syncwarp(); \
        if (lane < 16) bulk_ld(sb + ((lane & 2) ? VX1 : VX0) + (lane & 1) * 2048 + (lane >> 2) * 512, \
                               xc + h * 262144 + V_RING(n) + (lane >> 2) * XC + X_VX(lane & 3), 512, sb + BARS + 8); __syncwarp(); } while (0)
      uint32_t src = L16 + PK + (iw & 1) * 2048;
#define qd (L16 + (lane >> 4) * 256 + QT + (iw & 1) * 1024)
#define vd (LO(xc) + h * 262144 + j * XC + (iw & 1) * 2048 + l16)
#define FINISH [&](int n, int m) { \
_Pragma("unroll") \
        for (int i = 1; i >= 0; i--) { \
          const uint32_t p = src + m * 4096 + i * 512; \
          uint4 u = lds4(p); \
          const uint4 w = lds4(p + 1024), y = lds4(p + 12288), z = lds4(p + 13312); \
          u = make_uint4(sum4bf(u.x, w.x, y.x, z.x), sum4bf(u.y, w.y, y.y, z.y), sum4bf(u.z, w.z, y.z, z.z), sum4bf(u.w, w.w, y.w, z.w)); \
          if (m == 2) stg_b128(mkp(vd ^ V_RING(n), HI(xc)) + i * 512, (u.x & ~1u) | V_TAG(n), u.y, u.z, u.w); \
          else stsm4(qd + (n & 1) * 4096 + m * 2048 + i * 256, u.x, u.z, u.y, u.w); \
          SCHED_FENCE(71 + m * 2 + i); \
        } \
      }
#pragma unroll 1
      for (int n = 0; n < 64; n++) {
        src = PIN(src);
        b = __shfl_sync(~0u, lds1(sb + PACE + 24), 0);
        const uint32_t L16 = src - PK - (iw & 1) * 2048;
        auto finish = FINISH;
        if (n < 2) { if (n) BAR_SYNC(B_X, 320); else BAR_SYNC(B_C, 448); }
        mbar_wait(sb + BARS + 16, n & 1);
        finish(n, 0);
        __syncwarp();
        if (lane == 0) mbar_arrive_cl(mapa(sb, a ^ 1) + BARS + 24);
        if (n > 1) BAR_SYNC(B_K, 320);
        mbar_wait(sb + BARS + (KVO ? 32 : 40), n & 1);
        finish(n, 2 - !!KVO);
        if (n > 1) BAR_SYNC(B_X, 320);
        mbar_wait(sb + BARS + (KVO ? 40 : 32), n & 1);
        finish(n, 1 + !!KVO);
        BAR_SYNC(B_T, 64);
        if (lane == 0) {
          if (iw == 2 && n < 63) { mbar_expect(sb + BARS + 16, 4096); mbar_expect(sb + BARS + 32, 4096); mbar_expect(sb + BARS + 40, 4096); }
          mbar_arrive_cl(mapa(sb, a ^ 1) + BARS + 80);
        }
        __syncwarp();
        if (n) {
          vm_stage(n - 1);
          BAR_SYNC(B_W, 384);
        } else {
          BAR_SYNC(B_C, 320);
        }
        if (iw == 2) V_LOAD(n);
      }
#undef qd
#undef vd
    }
    { ROLE_REFRESH }
    vm_stage(63);
  } else {
    asm volatile("setmaxnreg.dec.sync.aligned.u32 %0;" ::"n"(RA_));
    if (blockIdx.x >= 128) { if (threadIdx.x == 256) rec_prefetch((const char*)wmod, w1, (const char*)x, wo); return; }
    ROLE_VARS
    uint32_t L16 = __shfl_sync(~0u, sb + (tid & 31) * 16, tid & 31);
    const uint32_t ts = gtime();
    uint2 m0[8];
#pragma unroll
    for (int r = 0; r < 8; r++) m0[r] = *(const uint2*)(mem0 + r * 1024 + a * 512 + (tid - 256) * 4);
    if (wid == 9) {
#pragma unroll 1
      for (int i = b * 80 + (tid & 31); i < b * 80 + 80; i += 32) ((uint4*)(xc + AR_OFF))[AR_ROW(i >> 6) * 64 + (i & 63)] = make_uint4(0, 0, 0, 0);
      if (b == 0) g_fin = 0;
      FENCE_ASYNC();
      __syncwarp();
      if (tid == 288) red_rlx(&g_hcnt);
    }
    if (tid == 256) {
      const int col = h * 128 + bb * 64;
#pragma unroll 1
      for (int c = 0, w = 0; w < 12; c++) {
#pragma unroll 1
        for (; w <= c - (c < WC0 ? 2 : 3); w++) {
          mbar_wait(sb + PACE + (w % 3) * 8, (w / 3) & 1);
          PT(18 + w);
          if (w == 3) asm volatile("mbarrier.arrive.shared.b64 _,[%0];" ::"r"(sb + BARS + 88) : "memory");
        }
        const uint32_t mb = sb + PACE + (c % 3) * 8;
        if (c >= 12 && c < 12 + WPE) tma2d_pf(&mp.wo, j * 256 + (c - 12) * 64, h * 128);
        if (c >= 12) continue;
        mbar_expect(mb, 16384);
        if (c < 8) tma2d(sb + (c >> 2) * XB + (c & 3) * 16384, (c & 4) ? &mp.wk : &mp.wq, col, a * 512 + (c & 3) * 128, mb);
        else
#pragma unroll 1
          for (int i = (c & 1) * 8; i < (c & 1) * 8 + 8; i++) {
            const int w = (c - 8) >> 1;
            tma2d(i < NVR ? sb + MEM + (w * NVR + i) * 2048 : sb + WVS + (w * NVS + i - NVR) * 2048, &mp.wv, col, a * 512 + w * 256 + i * 16, mb);
          }
      }
      asm volatile("mbarrier.arrive.shared.b64 _,[%0];" ::"r"(wbar) : "memory");
      for (int i = 0; i < 3; i++) asm volatile("mbarrier.inval.shared.b64 [%0];" ::"r"(sb + PACE + i * 8) : "memory");
    }
    __syncwarp();
    asm volatile("barrier.cluster.wait.aligned;" ::: "memory");
    CLUSTER_SYNC();
#pragma unroll 4
    for (int i = 0; i < 16; i++) {
      const uint4 v = lds4(L16 + WO + 32768 + iw * 8192 + i * 512);
      sts4(L16 + XB + iw * 8192 + i * 512, v.x, v.y, v.z, v.w);
    }
#pragma unroll
    for (int i = 0; i < 4; i++) {
      const int k = (tid - 256) * 4 + i, m = (k >> 3) & 3, r = k & 7;
#define M0W(r) __byte_perm((i & 2) ? m0[r].y : m0[r].x, (i & 2) ? m0[r + 1].y : m0[r + 1].x, (i & 1) ? 0x7632 : 0x5410)
      sts4(sb + MEM + (k >> 5) * 640 + (r == m ? 512 : m * 128) + r * 16, M0W(0), M0W(2), M0W(4), M0W(6));
    }
#pragma unroll 1
    for (int i = tid - 256; i < 192; i += 128) {
      const uint32_t c = i < 128 ? 0x42004200 : 0x3f803f80;
      sts4(sb + MEM + (i >> 3) * 640 + ((i & 7) < 4 ? (i & 7) * 144 : 512 + (i & 7) * 16), c, c, c, c);
    }
    static_assert(ARO == MEM + 16 * 640, "counters");
    FENCE_ASYNC_SMEM();
    BAR_ARRIVE(B_C, 448);
    if (WPF && tid == 256) {
      wait_time(ts + WPF);
#pragma unroll 1
      for (int c = WPE; c < 4; c++) tma2d_pf(&mp.wo, j * 256 + c * 64, h * 128);
    }
    __syncwarp();
#define pr (L16 + SC)
    {
      const int lim = j * 8 + iw * 2 - (lane & 7) - (lane & 8) * 2;
      const bool mk = L16 & 256;
      const int rw = lane >> 2;
      sts4(L16 + TA + iw * 512,
           iw != 2 ? L16 + KT + (iw & 1) * 256 + (lane >> 4) * 256 : sb + RK + (L16 & 0x80) * 2 + ((L16 >> 1) & 0x80) + (L16 & 0x70),
           L16 + QT + (lane >> 3) * 384, sb + SC + min(lane >> 3, 2) * 256 + (L16 & 0x70) + iw * 4, L16 + (lane >> 4) * 256 + QT + (iw >> 1) * 1024 + (iw & 1) * 256);
      sts4(L16 + TA + 2048 + iw * 512, mk ? 0u : (lim < 0 ? 0xfc00u : 0u) | (lim < -1 ? 0xfc000000u : 0u),
           mk ? 0xfc00fc00u : (lim < 8 ? 0xfc00u : 0u) | (lim < 7 ? 0xfc000000u : 0u),
           ((h * 2 + (iw >> 1)) * 1024 + (j * 8 + rw) * 8 + (((iw & 1) * 4 + (lane & 3)) ^ rw)) * 16, sb + OT + iw * 512 + (L16 & 0x70) * 4 + ((L16 >> 3) & 0x30));
    }
    {
      const uint32_t xh = LO(xc) + h * 262144, xs = xh + X_SC + iw * 1024 + min(lane, 16 + (lane & 7)) * 8;
      sts4(L16 + TA + 4096 + iw * 512, xh + X_SC + j * 256 + iw * 64 + lpub, xs, dS, iw != 2 ? 0 : U_(SCS));
      sts1(L16 + TA + 12 + iw * 512, xs + X_TOK + j * 4096);
    }
    uint32_t tA = L16 + TA + iw * 512;
#define tw (tA - L16 != TA + 1024)
#define XP_(lo) mkp(lo, HI(xc))
    auto publish = [&](char* d, const uint2& w) { stg_b64(d, w.x, w.y); };
    BAR_SYNC(B_P, N_P);
    for (int s = 0; s < 64; s++) {
      asm volatile("" : "+r"(L16), "+r"(tA));
      const uint32_t tag = ((s >> 1) + 1) & 1, ring = (s & 1) * X_RING;
      const uint4 t0 = lds4(tA);
      const uint4 tx = lds4(tA + 4096);
      const uint32_t xo = tx.x ^ ring, xs = tx.y ^ ring;
      const float gm = F_(tx.w);
      const uint32_t qA = t0.y + (ring >> 5);
      uint32_t c0;
      uint2 ts[4];
      uint4 v[4];
      uint32_t af[2][4], qt[4][4];
      {
        const uint32_t aA = t0.x + (tw ? ring >> 5 : 0);
        uint32_t ql[2][4], qr[2][4];
        uint2 pw_;
        float c[4] = {0, 0, 0, 0}, d[4] = {0, 0, 0, 0};
        if (s == PDS) asm volatile("griddepcontrol.launch_dependents;");
#pragma unroll
        for (int i = 0; i < 4; i++) ldsm4t(qt[i], qA + i * 128);
        mbar_wait(sb + BARS + 8, s & 1);
        TS(4);
        BAR_SYNC(B_E, 256);
#define PACK(c) make_uint2(pkh(fmaf(c[2], gm, c[0] * SCS), fmaf(c[3], gm, c[1] * SCS), tag), pkh(c[2] * SCS, c[3] * SCS, tag))
#define SMMA(x, t, q, i) mma16(x, af[t][0], af[t][1], af[t][2], af[t][3], q[t][i], q[t][i + 1])
        ldsm4t(ql[0], L16 + RQ); ldsm4t(ql[1], L16 + RQ + 1024); ldsm4t(af[0], aA); ldsm4t(af[1], aA + 1024);
        CONSUME(xo);
#define QSUM(t, i) addbf(addbf(ql[t][i], ql[t][i + 2]), addbf(qr[t][i], qr[t][i + 2]))
#define STAIL mma16(c, af[0][0], af[0][1], af[0][2], af[0][3], QSUM(0, 0), QSUM(0, 1)); mma16(d, af[1][0], af[1][1], af[1][2], af[1][3], QSUM(1, 0), QSUM(1, 1));
        if (tw) {
          mbar_wait(sb + BARS, s & 1);
          TS(8);
          ldsm4t(qr[0], L16 + RQ + 512); ldsm4t(qr[1], L16 + RQ + 1536);
          STAIL
          pw_ = make_uint2(pkh(c[0] + d[0], c[1] + d[1], tag), pkh(c[2] + d[2], c[3] + d[3], tag));
        } else {
          uint32_t ar[2][4];
          mbar_wait(sb + BARS, s & 1);
          ldsm4t(qr[0], L16 + RQ + 512); ldsm4t(ar[0], aA + 512); ldsm4t(qr[1], L16 + RQ + 1536); ldsm4t(ar[1], aA + 1536);
#pragma unroll
          for (int i = 0; i < 8; i++) af[i >> 2][i & 3] = addbf(af[i >> 2][i & 3], ar[i >> 2][i & 3]);
          STAIL
          pw_.x = pw_.y = pkh((c[0] + c[2]) + (d[0] + d[2]), (c[1] + c[3]) + (d[1] + d[3]), tag);
        }
        publish(XP_(xo), pw_);
        c0 = clk() + tx.z;
        TS(1);
      }
      uint2 r[4];
      bool vbad;
      uint32_t xm;
      uint4 vn[2];
#define TOKS(i) { float e0[4] = {0, 0, 0, 0}, e1[4] = {0, 0, 0, 0}; \
        mma16(e0, af[0][0], af[0][1], af[0][2], af[0][3], qt[i][0], qt[i][1]); mma16(e1, af[0][0], af[0][1], af[0][2], af[0][3], qt[i + 1][0], qt[i + 1][1]); \
        mma16(e0, af[1][0], af[1][1], af[1][2], af[1][3], qt[i][2], qt[i][3]); mma16(e1, af[1][0], af[1][1], af[1][2], af[1][3], qt[i + 1][2], qt[i + 1][3]); \
        ts[i] = PACK(e0); ts[i + 1] = PACK(e1); }
      {
        float e[4][4];
#pragma unroll
        for (int i = 0; i < 4; i++) {
          e[i][0] = e[i][1] = e[i][2] = e[i][3] = 0.f;
          mma16(e[i], af[0][0], af[0][1], af[0][2], af[0][3], qt[i][0], qt[i][1]);
        }
#pragma unroll
        for (int i = 0; i < 4; i++) mma16(e[i], af[1][0], af[1][1], af[1][2], af[1][3], qt[i][2], qt[i][3]);
        SCHED_FENCE(55);
        if (s < 63) BAR_ARRIVE(B_S, 416);
        SCHED_FENCE(58);
        v[0] = lds4(tA + (VX0 - TA)); v[1] = lds4(tA + (VX0 - TA) + 2048); v[2] = lds4(tA + (VX1 - TA)); v[3] = lds4(tA + (VX1 - TA) + 2048);
#pragma unroll
        for (int i = 0; i < 4; i++) ts[i] = PACK(e[i]);
        vbad = anybad(v[0].x, v[1].x, v[2].x, v[3].x, V_TAG(s));
        if (AV) { xm = (xs & ~0x1ffffu) + X_VM(0) + ((tA - L16 - TA) << 5) + (l16 >> 1); CONSUME(xm); }
        while ((int)(clk() - c0) < 0) {}
        TS(5);
#pragma unroll
        for (int u = 0; u < 4; u++) r[u] = ldg_b64(XP_(xs) + u * 256);
        if (!AV) BAR_ARRIVE(B_S2, 256);
      }
      SCHED_FENCE(56);
      uint32_t kk;
      float4 e = softmax2<false>(r, 0, 0, kk);
      if (AV) {
        const char* pm_ = XP_(xm + (kk & dZ));
#pragma unroll
        for (int u = 0; u < 2; u++) { const uint2 m0 = ldg_b64(pm_ + u * 2048), m1 = ldg_b64(pm_ + u * 2048 + 256); vn[u] = make_uint4(m0.x, m0.y, m1.x, m1.y); }
      }
      if (__builtin_expect(anybad(r[0].x, r[0].y, r[1].x, r[1].y, r[2].x, r[2].y, r[3].x, r[3].y, tag ^ (kk & dZ)), 0)) {
        int it = 0;
        if (s > 8) sts1(tA + 4096 + 8, min(lds1(tA + 4096 + 8) + dX, 500));
        do {
          RP(1);
          if (++it > SPIN_LIMIT) __trap();
#pragma unroll
          for (int u = 0; u < 4; u++) r[u] = ldg_b64(XP_(xs) + u * 256);
        } while (BADS(r));
        e = softmax2<false>(r, 0, 0, kk);
      }
      sts1(t0.z, pk(e.x, e.y)); sts1(t0.z + 128, pk(e.z, e.w));
#pragma unroll
      for (int i = 0; i < 4; i++) publish(XP_(xo) + X_TOK + i * 4096, ts[i]);
      TS(6);
      if (s < 63) BAR_SYNC(B_V, N_V); else BAR_SYNC(B_V, N_V - 256);
      uint32_t O[4];
      {
        uint32_t p[4], pm;
        ldsm4t(p, pr);
        asm volatile("ldmatrix.sync.aligned.m8n8.x1.trans.shared.b16 {%0},[%1];" : "=r"(pm) : "r"(pr + 512) : "memory");
        if (!AV) { vn[0] = lds4(tA + (VN - TA)); vn[1] = lds4(tA + (VN - TA) + 2048); }
        pv_mem(p, pm, v, vn, O);
        if (__builtin_expect(vbad || ((HV || AV) && anybad(vn[0].x, vn[0].z, vn[1].x, vn[1].z, tag)), 0)) {
          int it = 0;
          const uint32_t xv = LO(xc) + (lds1(sb + PACE + 24) >> 2) * 262144 + ((tA - L16 - TA) >> 9) * XC;
          do {
            RP(2);
            if (++it > SPIN_LIMIT) __trap();
#pragma unroll
            for (int u = 0; u < 4; u++) v[u] = ldg_b128(XP_((xv + l16) ^ V_RING(s)) + X_VX(u));
          } while (anybad(v[0].x, v[1].x, v[2].x, v[3].x, V_TAG(s)) || ((HV || AV) && anybad(vn[0].x, vn[0].z, vn[1].x, vn[1].z, tag)));
          pv_mem(p, pm, v, vn, O);
        }
      }
      stsm4(tA + (OB - TA), O[0], O[1], O[2], O[3]);
      if (s < 63) BAR_ARRIVE(B_O, N_O);
      TS(2);
      c0 = clk() + (LS && s == 63 ? 0 : dG);
      SCHED_FENCE(60);
      if (tA == sb + TA) mbar_expect(sb + BARS, 2048);
      const uint32_t vs[4] = {addbf(vn[0].x, vn[0].z), addbf(vn[0].y, vn[0].w), addbf(vn[1].x, vn[1].z), addbf(vn[1].y, vn[1].w)};
      {
        const char* xt = XP_(lds1(tA + 12) ^ ring);
        const uint2 t1 = lds2u(tA + 2048);
        const uint32_t pw = lds1(tA + 8);
        uint2 rt[4];
        CONSUME(LO(xt) ^ t1.x ^ pw);
        while ((int)(clk() - c0) < 0) {}
        int it = 0;
        do {
          if (++it > SPIN_LIMIT) __trap();
#pragma unroll
          for (int u = 0; u < 4; u++) rt[u] = ldg_b64(xt + u * 256);
        } while (BADS(rt));
        uint32_t kt;
        const float4 et = softmax2<true>(rt, t1.x, t1.y, kt);
        sts1(pw + 1024, pk(et.x, et.y)); sts1(pw + 1024 + 128, pk(et.z, et.w));
      }
      s = PIN(s);
      BAR_SYNC(B_SC, 128);
      {
        uint32_t Ot[4], p[4], pm;
        const uint2 t2 = lds2u(tA + 2048 + 8);
        ldsm4t(p, pr + 1024);
        asm volatile("ldmatrix.sync.aligned.m8n8.x1.trans.shared.b16 {%0},[%1];" : "=r"(pm) : "r"(pr + 1024 + 512) : "memory");
        char* od = (char*)g_O + ((s >> 2) * 1048576 + (s & 3) * 4096) + t2.x;
        CONSUME(LO(od) ^ HI(od) ^ pm ^ p[3]);
        TS(9);
        if (s < 62) BAR_SYNC(B_P, N_P);
        pv_tok(p, pm, v, vs, Ot);
        asm volatile("stmatrix.sync.aligned.m8n8.x4.trans.shared.b16 [%0],{%1,%2,%3,%4};" ::"r"(t2.y), "r"(Ot[0]), "r"(Ot[1]), "r"(Ot[2]), "r"(Ot[3]) : "memory");
        __syncwarp();
        *(uint4*)od = lds4(tA + (OT - TA));
      }
    }
    FENCE_ASYNC();
    BAR_SYNC(B_SC, 128);
    if (tA == sb + TA) red_rlx(&g_fin);
  }
  __syncwarp();
  CLUSTER_SYNC();
  PH(5); RS(2);
}
#undef wg
#undef iw
#undef h
#undef j
#undef a
#undef bb
#undef oi
#undef owner
#undef ownv
#undef vfin
#undef pr
#undef PIN
#undef XP_
#undef tw
#undef is7
#undef REFRESH
#undef lane
#undef l16
#undef lrow
#undef lar
#undef lpub

namespace ffn {
constexpr uint32_t BR = 98304;
constexpr uint32_t STG = 196608;
constexpr uint32_t PRM = 229376;
constexpr uint32_t BARS = PRM + 2816;
constexpr uint32_t SMEM = BARS + 18 * 8;
}
#define Y_TILE(rb, kt) (((ALIAS & 1) ? g_h : g_h2) + ((rb) * 16 + (kt)) * 1024)
#define U_TILE(rb, kt) ((ALIAS & 2) ? g_O + ((rb) * 64 + (kt)) * 1024 : g_U + ((rb) * 56 + (kt)) * 1024)
struct FfnMaps { CUtensorMap wo, w1a, w1b, w2, x, out; };

template <int N>
__device__ __forceinline__ void wg_ss(float* d, uint64_t a, uint64_t b, int sd) {
  if (N == 128) wgmma_ss_n128(d, a, b, sd);
  if (N == 192) wgmma_ss_n192(d, a, b, sd);
}
template <int N>
__device__ __forceinline__ void acc_fence(float* d) {
#pragma unroll
  for (int i = 0; i < N; i++) asm volatile("" : "+f"(d[i])::"memory");
}
#define UNPK8(d, v) do { (d)[0] = blo(v.x); (d)[1] = bhi(v.x); (d)[2] = blo(v.y); (d)[3] = bhi(v.y); (d)[4] = blo(v.z); (d)[5] = bhi(v.z); (d)[6] = blo(v.w); (d)[7] = bhi(v.w); } while (0)
struct FfnPipe {
  uint32_t full, emp, ph, aoff;
  int st, sB, prev;
  bool leader;
  template <int N, int S = N>
  __device__ __forceinline__ void issue(float* acc, bool first, uint32_t a = 0) {
    mbar_wait(full + st * 8, ph);
    const uint64_t da = mkdesc((a ? a : 1024 + st * 16384) + aoff, 16, 1024), db = mkdesc(1024 + ffn::BR + sB * (S * 128), 8192, 1024);
    WG_FENCE();
#pragma unroll
    for (int j = 0; j < ((FDB & 1) ? 1 : 4); j++) wg_ss<N>(acc, da + j * 2, db + j * 128, j || !first);
    WG_COMMIT();
    if (++sB == 768 / S) sB = 0;
  }
  __device__ __forceinline__ void release() { if (leader) mbar_arrive(emp + prev * 8); }
  __device__ __forceinline__ void next() { prev = st; if (++st == 6) { st = 0; ph ^= 1; } }
  __device__ __forceinline__ void retire() { WG_WAIT(1); release(); next(); }
};
__device__ __forceinline__ float gelu_h(float hx) {
  float u = hx * fmaf(hx * hx, 8.f * 0.0356774081f, 2.f * 0.7978845608f), t;
  if (FDB & 4) return hx;
  if (FDB & 2) t = u; else
  asm("tanh.approx.f32 %0,%1;" : "=f"(t) : "f"(u));
  return fmaf(hx, t, hx);
}
struct FfnEpi {
  uint32_t st2, cc, flip, staged, l0;
  uint2 c;
  float n0, n1, s0, s1;
  __device__ __forceinline__ void flush(uint32_t r) {
    __syncwarp();
    asm volatile("{.reg .pred p; setp.ne.u32 p,%1,0; @p mbarrier.arrive.shared.b64 _,[%0];}" ::"r"(staged + (flip >> 11)), "r"(l0 & r) : "memory");
    flip ^= r << 14;
  }
  __device__ __forceinline__ void half(const float* d, int J, int r) {
#define PRE(i, n, c1, c2) gelu_h(fmaf(r ? d[4 + i] : d[i], i < 2 ? s0 : s1, fmaf(n, c1, c2)))
    asm volatile("stmatrix.sync.aligned.m8n8.x2.shared.b16 [%0],{%1,%2};" ::"r"((st2 ^ ((J & 3) * 32 + r * 16)) + flip),
                 "r"(pk(PRE(0, n0, blo(c.x), blo(c.y)), PRE(1, n0, bhi(c.x), bhi(c.y)))), "r"(pk(PRE(2, n1, blo(c.x), blo(c.y)), PRE(3, n1, bhi(c.x), bhi(c.y)))) : "memory");
#undef PRE
    if ((J & 3) == 3) flush(r);
    cc += r ? 56 : 8;
    c = lds2u(cc);
  }
};

__global__ void __launch_bounds__(384, 1)
k_ffn(const __grid_constant__ FfnMaps mp, const bf16* __restrict__ b2) {
  using namespace ffn;
  extern __shared__ __align__(1024) char smem[];
  const uint32_t sb = (uint32_t)__cvta_generic_to_shared(smem);
  if (sb != 1024) __trap();
  const int tid = threadIdx.x, lane = tid & 31, wg = __shfl_sync(~0u, tid >> 7, 0);
  const uint32_t full = sb + BARS, emp = full + 48, xbar = full + 96, staged = full + 104, tile = full + 136;
  uint32_t fin = 0;
  if (tid >= 288 && tid < 320) fin = ld_acq(&g_fin);
  if (tid < 32) {
    unsigned sm, v = 0;
    asm("mov.u32 %0,%%smid;" : "=r"(sm));
    if (tid == 0) {
      v = atomicExch(&g_slot[sm & 255], 0);
      for (int i = 0; i < 6; i++) { mbar_init(full + i * 8, 1); mbar_init(emp + i * 8, 2); }
      mbar_init(xbar, 2);
      for (int i = 0; i < 2; i++) { mbar_init(staged + i * 8, 8); mbar_init(staged + 16 + i * 8, 1); }
      FENCE_ASYNC_SMEM();
    }
    v = __shfl_sync(~0u, v, 0);
    if (!v) {
      wait_cnt(&g_fin, 128);
      for (int it = 0; !v; it++) {
        const uint4 a = ldg_rlx4(g_slot + tid * 8), b = ldg_rlx4(g_slot + tid * 8 + 4);
        const uint32_t open = __ballot_sync(~0u, a.x | a.y | a.z | a.w | b.x | b.y | b.z | b.w);
        if (!open) break;
        if (it < 16) { __nanosleep(500); continue; }
        if (tid == __ffs(open) - 1) v = atomicExch(&g_slot[tid * 8 + (a.x ? 0 : a.y ? 1 : a.z ? 2 : a.w ? 3 : b.x ? 4 : b.y ? 5 : b.z ? 6 : 7)], 0);
        v = __shfl_sync(~0u, v, __ffs(open) - 1);
      }
    }
    if (tid == 0) sts1(tile, v);
  }
  if (tid == 256) asm volatile("prefetch.tensormap [%0];" ::"l"(&mp.wo) : "memory");
  __syncthreads();
  const int bid = __shfl_sync(~0u, lds1(tile), 0) - 1;
  if (bid < 0) return;
  PH(6);
  FT(1);
  const int rb = bid >> 3, nb = bid & 7;
  unsigned* cnt = g_cnt + rb * 128;
  if (wg == 2) {
    asm volatile("setmaxnreg.dec.sync.aligned.u32 " FRP ";");
    const int pw = __shfl_sync(~0u, (tid >> 5) & 3, 0);
    uint32_t ws = emp, wp = 1, fs = full;
    auto wait_free = [&]() { mbar_wait_q(ws, wp); ws += 8; if (ws == emp + 48) { ws = emp; wp ^= 1; } };
    auto step = [&]() { fs += 8; if (fs == full + 48) fs = full; };
#define K3(c) ((0x65230 >> (c) * 4) & 7)
#define KC(k) ((k) < 2 ? nb * 2 + (k) : (k) < 9 ? ((k) - 2 + ((k) - 2 >= nb)) * 2 : ((k) - 9 + ((k) - 9 >= nb)) * 2 + 1)
    if (pw == 0) {
      uint32_t d = sb + BR + 32768;
      auto put = [&](const CUtensorMap* m, int k, int c) {
        e_expect_tma3d(d, m, k * 64, c, fs, 32768);
        step();
        d += 16384;
        if (d == sb + STG) d = sb + BR;
      };
      int n = 0;
      auto stage_free = [&]() { if (!(n & 7) && n < 56) mbar_wait_q(staged + 16 + (n & 8), (n >> 4) & 1); n++; };
      auto align = [&]() {
        if (ALN && !((n - 1) & 7) && ((ALN >> ((n - 1) >> 3)) & 1)) {
          unsigned* c = g_cnt + 64 + ((n - 1) >> 3);
          if (lane == 0) red_rlx(c);
          for (int it = 0; ldg_rlx1(c) < 128 && it < 64; it++) {}
        }
      };
      FTP(3);
#pragma unroll 1
      for (int k = 0; k < 66; k++) { wait_free(); if (k < 64) put(&mp.wo, k, nb * 2); }
#pragma unroll 1
      for (int k = 0; k < 16 + 2 * EOT; k++) {
        const int u = EOT && k >= 2 ? k - 2 : k, kt = KC(u);
        const bool ea = EOT && (k & ~1) == 2;
        wait_free();
        e_expect_tma3d(sb + BR + (k & 3) * 24576, ea ? &mp.w1a : &mp.w1b, kt * 64, nb * 7 + (ea ? 3 : 0), fs, ea ? 16384 : k < 2 ? 24576 : 40960);
        step();
      }
      if (EOT) d = sb + BR + 49152;
#pragma unroll 1
      for (int k = 2 * EOT; k < 32; k++) {
        const int kt = EOT && k < 16 ? KC(k) : k & 15;
        stage_free();
        if (EOT && (k == 2 || k == 9)) n++;
        if (k != 5 + 2 * EOT && k != 6 + 2 * EOT) wait_free();
        align();
        put(&mp.w1a, kt, nb * 7 + 3 + (k >> 4) * 2);
      }
#pragma unroll 1
      for (int c = 0; c < 5; c++)
#pragma unroll 1
        for (int k = K3(c), i = 0; k < 56; k += c < 2 && (i ^= 1) ? 1 : c < 2 ? 6 : 7) { stage_free(); wait_free(); align(); put(&mp.w2, k, nb * 2); }
    } else if (pw == 1) {
      FTP(5);
      if (fin < 128) wait_cnt(&g_fin, 128);
      FTP(6);
      uint32_t d = sb;
      auto put = [&](const uint4* A, bool ld) {
        wait_free();
        if (ld) e_bulk_ld(d, A, 16384, fs);
        step();
        d += 16384;
        if (d == sb + BR) d = sb;
      };
      const uint4* A = g_O + rb * 65536;
#pragma unroll 1
      for (int k = 0; k < 66 + 2 * EOT; k++) put(A + k * 1024, k < 64);
      A = Y_TILE(rb, 0);
      uint32_t ready = 0;
#pragma unroll 1
      for (int k = 2; k < 48; k++) {
        if (EOT && k == 16) k = 18;
        const int kt = k < 16 || (EOT && k < 32) ? KC(k & 15) : k & 15;
        for (int it = 0; !(ready >> ((kt >> 1) + (kt & 1) * 8) & 1); it++) {
          ready = __ballot_sync(~0u, ldg_rlx1(cnt + (lane & 7)) & ((lane & 8) ? 1 : 0x10000));
          if (it > SPIN_LIMIT) __trap();
        }
        if (k == 2) FTP(75);
        put(A + kt * 1024, true);
      }
      A = U_TILE(rb, 0);
#pragma unroll 1
      for (int c = 0; c < 5; c++) {
        for (int it = 0; ldg_rlx1(cnt + 32 + c) < 8; it++) if (it > SPIN_LIMIT) __trap();
#pragma unroll 1
        for (int k = K3(c), i = 0; k < 56; k += c < 2 && (i ^= 1) ? 1 : c < 2 ? 6 : 7) put(A + k * 1024, true);
      }
    } else if (pw == 2) {
      for (int i = 0; i < XDL; i++) {
        mbar_wait_q(emp, i & 1);
        if (XPF && i == 1 && lane < 2) tma2d_pf(&mp.x, nb * 128 + lane * 64, rb * 128);
      }
      if (lane == 0) {
        mbar_expect(xbar, 32768);
        tma2d(sb + STG, &mp.x, nb * 128, rb * 128, xbar);
        tma2d(sb + STG + 16384, &mp.x, nb * 128 + 64, rb * 128, xbar);
      }
      asm volatile("griddepcontrol.wait;" ::: "memory");
      if (lane < 16) g_modp[bid * 16 + lane] = make_uint4(0, 0, 0, 0);
      if (lane >= 16 && bid == 0) { g_hcnt = 0; g_mcnt = 0; g_hf[lane & 3] = 0; }
      if (lane == 0) {
#pragma unroll 1
        for (int g = 1; g < 9; g++) {
          if (g == 1) mbar_wait(staged + 8, 0); else { mbar_wait_q(staged + (g & 1) * 8, (g >> 1) & 1); FENCE_ASYNC_SMEM(); }
          bulk_st(g == 1 ? Y_TILE(rb, nb * 2 + 1) : U_TILE(rb, nb * 7 + ((0x652431000ull >> g * 4) & 7)), sb + STG + (g & 1) * 16384, 16384);
          BULK_COMMIT();
          if (g != 2 && g != 4) { BULK_WAIT(0); red_rlx(g == 1 ? cnt + nb : cnt + 32 + (g < 6 ? g >> 2 : g - 4)); }
          BULK_WAIT_READ(0);
          mbar_arrive(staged + 16 + (g & 1) * 8);
        }
      }
    } else {
      const uint32_t prm = sb + PRM, pp = prm + (lane >> 3) * 64 + (lane & 1) * 32 + (lane & 6) * 2;
      const uint2 v2 = ((const uint2*)(b2 + nb * 128))[lane];
      sts1(pp + 768, v2.x); sts1(pp + 784, v2.y);
      asm volatile("griddepcontrol.wait;" ::: "memory");
      const float4* md = (const float4*)(g_mod + nb * 128) + lane;
      { const float4 ga = md[512]; sts1(pp, pk(ga.x, ga.y)); sts1(pp + 16, pk(ga.z, ga.w)); }
      { const float4 cb = md[1024]; sts1(pp + 256, pk(1.f + cb.x, 1.f + cb.y)); sts1(pp + 272, pk(1.f + cb.z, 1.f + cb.w)); }
      { const float4 gb = md[1280]; sts1(pp + 512, pk(gb.x, gb.y)); sts1(pp + 528, pk(gb.z, gb.w)); }
#pragma unroll 1
      for (int i = lane; i < 112; i += 32) { const uint4 c = g_cc[nb * 112 + i]; sts4(prm + 1024 + i * 16, c.x, c.y, c.z, c.w); }
      __syncwarp();
      if (lane == 0) {
        mbar_arrive(xbar);
        mbar_wait(staged, 0);
        bulk_st(Y_TILE(rb, nb * 2), sb + STG, 16384);
        BULK_COMMIT(); BULK_WAIT(0);
        asm volatile("red.relaxed.gpu.global.add.u32 [%0],0x10000;" ::"l"(cnt + nb) : "memory");
        mbar_arrive(staged + 16);
      }
      __syncwarp();
      mbar_wait_q(staged + 24, 0);
      if (EOT) mbar_wait_q(emp + 8, 1); else mbar_wait_q(emp + 40, 0);
#pragma unroll 1
      for (int i = 0; i < 4; i++) {
        const uint4* sp = g_stat + (rb * 128 + i * 32 + lane) * 4;
        uint4 v[4];
        for (int it = 0;; it++) {
          uint32_t m = 0;
#pragma unroll
          for (int u = 0; u < 4; u++) { v[u] = ldg_rlx4(sp + u); m = max(max(m, max(v[u].x, v[u].y)), max(v[u].z, v[u].w)); }
          if (!__any_sync(~0u, m == ~0u)) break;
          if (it > SPIN_LIMIT) __trap();
        }
        float m = 0, q = 0;
#pragma unroll
        for (int u = 0; u < 4; u++) { m += F_(v[u].x) + F_(v[u].z); q += F_(v[u].y) + F_(v[u].w); }
        m *= 1.f / 1024;
        const float r = 0.5f * rsqrtf(fmaxf(q * (1.f / 1024) - m * m, 0.f) + 1e-5f);
        sts2(sb + STG + 16384 + (i * 32 + lane) * 8, U_(r), U_(-m * r));
      }
      __syncwarp();
      if (lane < 2) mbar_arrive(xbar);
    }
  } else {
    asm volatile("setmaxnreg.inc.sync.aligned.u32 " FRC ";");
    const int w = (tid >> 5) & 3, q = lane & 3;
    const uint32_t prm = sb + PRM + q * 16;
    const int row0 = wg * 64 + w * 16;
    FfnPipe p;
    p.full = full; p.emp = emp; p.ph = 0; p.aoff = wg * 8192; p.st = 0; p.sB = 2; p.prev = 0; p.leader = (tid & 127) == 0;
    FfnEpi e;
    const uint32_t stg = sb + STG + row0 * 128;
    e.st2 = stg + (lane & 15) * 128 + ((lane & 7) << 4);
    e.cc = sb + PRM + 1024 + q * 16; e.flip = 0; e.staged = staged; e.l0 = lane == 0;
    const uint32_t stw = e.st2 ^ (lane & 16);
    uint32_t x1[32];
    uint4* sp = g_stat + (rb * 128 + row0 + (lane >> 2)) * 4;
    float old[96], r0_, r1_;
    {
      float acc[64];
      p.issue<128>(acc, true); FT(8); p.next();
#pragma unroll 1
      for (int k = 1; k < 64; k++) { p.issue<128>(acc, false); FT(8 + k); p.retire(); }
      float xf[64], gf[32];
      uint32_t cb[16];
      mbar_wait(xbar, 0);
#pragma unroll
      for (int j = 0; j < 8; j++) {
        uint32_t xv[4];
        ldsm4(xv, (stw ^ ((j & 3) * 32)) + (j >> 2) * 16384);
#pragma unroll
        for (int i = 0; i < 4; i++) { xf[j * 8 + i * 2] = blo(xv[i]); xf[j * 8 + i * 2 + 1] = bhi(xv[i]); }
      }
#pragma unroll
      for (int i = 0; i < 4; i++) {
        const uint4 g = lds4(prm + i * 64), c = lds4(prm + 256 + i * 64);
        UNPK8(gf + i * 8, g);
        cb[i * 4] = c.x; cb[i * 4 + 1] = c.y; cb[i * 4 + 2] = c.z; cb[i * 4 + 3] = c.w;
      }
      acc_fence<64>(xf); acc_fence<32>(gf);
      WG_WAIT(0);
      p.release();
      acc_fence<64>(acc);
      PH(7); FT(72);
#pragma unroll
      for (int j = 0; j < 8; j++) {
        uint32_t* o = x1 + j * 4;
#pragma unroll
        for (int i = 0; i < 4; i++)
          o[i] = pk(fmaf(acc[j * 8 + i * 2], gf[j * 4 + (i & 2)], xf[j * 8 + i * 2]), fmaf(acc[j * 8 + i * 2 + 1], gf[j * 4 + (i & 2) + 1], xf[j * 8 + i * 2 + 1]));
        stsm4((stw ^ ((j & 3) * 32)) + (j >> 2) * 16384, mulbf(o[0], cb[j * 2]), mulbf(o[1], cb[j * 2]), mulbf(o[2], cb[j * 2 + 1]), mulbf(o[3], cb[j * 2 + 1]));
        if ((j & 3) == 3) { FENCE_ASYNC_SMEM(); e.flush(1); }
      }
      if (wg) BAR_SYNC(2, 128); else BAR_SYNC(3, 128);
    }
    PH(8); FT(73);
    float acc[64];
    {
      float* accC = old;
      p.sB = 0;
      p.issue<192>(accC, true, 1024 + STG); FT(80); p.next();
      p.issue<192>(accC, false, 1024 + STG + 16384); FT(81);
      FT(78);
      float s0 = 0, s1 = 0, q0 = 0, q1 = 0;
#define X1_FENCE _Pragma("unroll") for (int j = 0; j < 32; j++) asm volatile("" : "+r"(x1[j]));
      X1_FENCE
#pragma unroll
      for (int j = 0; j < 16; j++) {
        const float a = blo(x1[j * 2]), b = bhi(x1[j * 2]), c = blo(x1[j * 2 + 1]), d = bhi(x1[j * 2 + 1]);
        s0 += a + b; s1 += c + d; q0 = fmaf(a, a, fmaf(b, b, q0)); q1 = fmaf(c, c, fmaf(d, d, q1));
      }
#pragma unroll
      for (int o = 1; o < 4; o *= 2) { s0 += __shfl_xor_sync(~0u, s0, o); s1 += __shfl_xor_sync(~0u, s1, o); q0 += __shfl_xor_sync(~0u, q0, o); q1 += __shfl_xor_sync(~0u, q1, o); }
      if (q < 2) {
        uint32_t m = __float_as_uint(q ? s1 : s0), v = __float_as_uint(q ? q1 : q0);
        if (m == ~0u) m = 0x7fffffffu;
        if (v == ~0u) v = 0x7fffffffu;
        stg_rlx2((uint2*)(sp + q * 32) + nb, m, v);
      }
      X1_FENCE
      p.retire();
      if (EOT) {
#pragma unroll 1
        for (int k = 0; k < 2; k++) { p.issue<128, 192>(acc, !k, 1024 + STG + k * 16384); p.retire(); }
      }
#pragma unroll 1
      for (int k = 2; k < 15; k++) { p.issue<192>(accC, false); FT(80 + k); p.retire(); }
      p.issue<192>(accC, false); FT(95);
      mbar_wait(xbar, 1);
      const float2 u0 = lds2f(sb + STG + 16384 + (row0 + (lane >> 2)) * 8), u1 = lds2f(sb + STG + 16384 + (row0 + (lane >> 2)) * 8 + 64);
      r0_ = u0.x; e.n0 = u0.y; r1_ = u1.x; e.n1 = u1.y;
      e.c = lds2u(e.cc);
      p.retire();
      e.s0 = r0_; e.s1 = r1_;
      if (EOT) p.sB = 3;
    }
    PH(9);
    {
      auto pair = [&](int J, bool first, bool one, int fo) {
#pragma unroll 1
        for (int r = 0; r < 2; r++) {
          if (!(one && r)) { p.issue<128>(acc, first && !r); FT(fo + r); p.retire(); }
          acc_fence<8>(old + J * 8);
          e.half(old + J * 8, J, r);
        }
      };
#pragma unroll 1
      for (int i = 0; i < 3; i++) {
        if (i == 2) {
          e.s0 = r0_; e.s1 = r1_;
#pragma unroll
          for (int J = 8; J < 12; J++) pair(J, J == 8, false, 128 + (J - 8) * 2);
          e.cc += 512; e.c = lds2u(e.cc);
          e.s0 = e.s1 = 1.f;
        }
#pragma unroll
        for (int J = 0; J < 8; J++) pair(J, J == 0 && i < 2 && (i || !EOT), EOT && !(J & 3) && !i, 96 + i * 16 + (i >> 1) * 8 + J * 2);
        if (i == 2) break;
        e.cc += i ? -768 : 256; e.c = lds2u(e.cc);
        WG_WAIT(0);
        acc_fence<64>(acc);
#pragma unroll
        for (int k = 0; k < 64; k++) old[k] = acc[k] * ((k & 2) ? r1_ : r0_);
        acc_fence<64>(old);
        e.s0 = e.s1 = 1.f;
        PH(10 + i);
      }
#pragma unroll 1
      for (int k = 24; k < 56; k++) {
        if (SKW && k == 56 - SKW && wg) BAR_SYNC(4, 256);
        p.issue<128>(acc, false); FT(128 + k);
        if (SKW && k == 55 && !wg) BAR_ARRIVE(4, 256);
        p.retire();
      }
      float xf[64], gf[32];
#pragma unroll
      for (int i = 0; i < 4; i++) {
        const uint4 g = lds4(prm + 512 + i * 64), h = lds4(prm + 768 + i * 64);
        float hf[8];
        UNPK8(gf + i * 8, g); UNPK8(hf, h);
#pragma unroll
        for (int u = 0; u < 8; u++) {
          const int c = (u >> 2) * 4 + (u & 2);
          xf[i * 16 + u * 2] = fmaf(gf[i * 8 + c], hf[c], blo(x1[i * 8 + u])); xf[i * 16 + u * 2 + 1] = fmaf(gf[i * 8 + c + 1], hf[c + 1], bhi(x1[i * 8 + u]));
        }
      }
      acc_fence<64>(xf); acc_fence<32>(gf);
      mbar_wait(staged + 24, 1);
      mbar_wait(staged + 16, 0);
      WG_WAIT(0);
      acc_fence<64>(acc);
      PH(13); FT(184);
#pragma unroll
      for (int j = 0; j < 8; j++) {
        uint32_t o[4];
#pragma unroll
        for (int i = 0; i < 4; i++)
          o[i] = pk(fmaf(acc[j * 8 + i * 2], gf[j * 4 + (i & 2)], xf[j * 8 + i * 2]), fmaf(acc[j * 8 + i * 2 + 1], gf[j * 4 + (i & 2) + 1], xf[j * 8 + i * 2 + 1]));
        stsm4((stw ^ ((j & 3) * 32)) + (j >> 2) * 16384, o[0], o[1], o[2], o[3]);
        if ((j & 3) == 3) {
          FENCE_ASYNC_SMEM();
          __syncwarp();
          if (lane == 0) { tma2d_st(&mp.out, nb * 128 + (j >> 2) * 64, rb * 128 + row0, stg + (j >> 2) * 16384); BULK_COMMIT(); }
        }
      }
      if (lane == 0) BULK_WAIT_READ(0);
      __syncwarp();
    }
  }
  PH(14); FT(185);
}

typedef CUresult (*EncFn)(CUtensorMap*, CUtensorMapDataType, cuuint32_t, void*, const cuuint64_t*, const cuuint64_t*, const cuuint32_t*,
                          const cuuint32_t*, CUtensorMapInterleave, CUtensorMapSwizzle, CUtensorMapL2promotion, CUtensorMapFloatOOBfill);
static void map2d(EncFn enc, CUtensorMap* m, const void* p, int rows, int cols, int boxRows) {
  cuuint64_t d[2] = {(cuuint64_t)cols, (cuuint64_t)rows}, s[1] = {(cuuint64_t)cols * 2};
  cuuint32_t b[2] = {64, (cuuint32_t)boxRows}, e[2] = {1, 1};
  enc(m, CU_TENSOR_MAP_DATA_TYPE_BFLOAT16, 2, (void*)p, d, s, b, e, CU_TENSOR_MAP_INTERLEAVE_NONE, CU_TENSOR_MAP_SWIZZLE_128B,
      CU_TENSOR_MAP_L2_PROMOTION_L2_128B, CU_TENSOR_MAP_FLOAT_OOB_FILL_NONE);
}
static void map3d(EncFn enc, CUtensorMap* m, const void* p, int rows, int cols, int nch) {
  cuuint64_t d[3] = {64, (cuuint64_t)rows, (cuuint64_t)(cols / 64)}, s[2] = {(cuuint64_t)cols * 2, 128};
  cuuint32_t b[3] = {64, 64, (cuuint32_t)nch}, e[3] = {1, 1, 1};
  enc(m, CU_TENSOR_MAP_DATA_TYPE_BFLOAT16, 3, (void*)p, d, s, b, e, CU_TENSOR_MAP_INTERLEAVE_NONE, CU_TENSOR_MAP_SWIZZLE_128B,
      CU_TENSOR_MAP_L2_PROMOTION_L2_128B, CU_TENSOR_MAP_FLOAT_OOB_FILL_NONE);
}

extern "C" void kernel_launch(void* const* d_in, const int* in_sizes, int n_in, void* d_out, int out_size) {
  const bf16* x = (const bf16*)d_in[0];
  const bf16* mem0 = (const bf16*)d_in[1];
  void* fn = nullptr;
  cudaDriverEntryPointQueryResult qr;
  cudaGetDriverEntryPoint("cuTensorMapEncodeTiled", &fn, cudaEnableDefault, &qr);
  EncFn enc = (EncFn)fn;
  FfnMaps fm = {};
  map3d(enc, &fm.wo, d_in[5], 4096, 1024, 2);
  map3d(enc, &fm.w1a, d_in[8], 1024, 3584, 2);
  map3d(enc, &fm.w1b, d_in[8], 1024, 3584, 3);
  map3d(enc, &fm.w2, d_in[10], 3584, 1024, 2);
  map2d(enc, &fm.x, x, 2048, 1024, 128);
  map2d(enc, &fm.out, d_out, 2048, 1024, 16);
  RecMaps rm = {};
  map2d(enc, &rm.wq, d_in[2], 1024, 4096, 128);
  map2d(enc, &rm.wk, d_in[3], 1024, 4096, 128);
  map2d(enc, &rm.wv, d_in[4], 1024, 4096, 16);
  map2d(enc, &rm.wo, d_in[5], 4096, 1024, 128);
  char* xc = nullptr;
  cudaGetSymbolAddress((void**)&xc, g_xc);
  xc += (0 - (uintptr_t)xc) & 0x1FFFFF;
  {
    cuuint64_t d[3] = {512, 6, 128}, sd[2] = {131072, 1024};
    cuuint32_t bi[3] = {64, 5, 8}, e[3] = {1, 1, 1};
    enc(&rm.ari, CU_TENSOR_MAP_DATA_TYPE_BFLOAT16, 3, xc + AR_OFF, d, sd, bi, e, CU_TENSOR_MAP_INTERLEAVE_NONE, CU_TENSOR_MAP_SWIZZLE_NONE,
        CU_TENSOR_MAP_L2_PROMOTION_NONE, CU_TENSOR_MAP_FLOAT_OOB_FILL_NONE);
  }
  cudaFuncSetAttribute(k_ffn, cudaFuncAttributeMaxDynamicSharedMemorySize, ffn::SMEM);
  cudaFuncSetAttribute(k_rec, cudaFuncAttributeMaxDynamicSharedMemorySize, rec::SMEM);
  cudaStream_t st = cudaStreamPerThread;
  int dF = 450, dA = 2700, dS = 300, dM = 120, dG = 350, dP = 24, dX = 48, dD = 350, dZ = 0, dZ2 = 1, dV = 370, dX2 = 0;
  k_rec<<<132, 512, rec::SMEM, st>>>(rm, mem0, x, (const bf16*)d_in[12], (const bf16*)d_in[13], (const char*)d_in[8], (const bf16*)d_in[9],
                                     (const char*)d_in[5], xc, dF, dA, dS, dM, dG, dP, dX, dD, dZ, dZ2, dV, dX2);
  cudaLaunchConfig_t cfg = {};
  cfg.gridDim = dim3(132); cfg.blockDim = dim3(384); cfg.dynamicSmemBytes = ffn::SMEM; cfg.stream = st;
  cudaLaunchAttribute at[1];
  at[0].id = cudaLaunchAttributeProgrammaticStreamSerialization;
  at[0].val.programmaticStreamSerializationAllowed = 1;
  cfg.attrs = at; cfg.numAttrs = 1;
  cudaLaunchKernelEx(&cfg, k_ffn, fm, (const bf16*)d_in[11]);
}
```

```cpp
#include <cuda_runtime.h>
#include <cuda.h>
#include <cuda_bf16.h>
#include <stdint.h>

typedef __nv_bfloat16 bf16;

__device__ __align__(16) float g_mod[6144];
__device__ __align__(1024) uint4 g_modp[4 * 512];
__device__ unsigned g_hcnt;
__device__ unsigned g_hf[4];
__device__ __align__(1024) uint4 g_h[2048 * 1024 / 8];
__device__ __align__(1024) uint4 g_O[2048 * 4096 / 8];
__device__ __align__(1024) uint4 g_h2[2048 * 1024 / 8];
__device__ __align__(1024) uint4 g_U[2048 * 3584 / 8];
__device__ __align__(1024) uint4 g_stat[2048 * 4];
__device__ __align__(1024) unsigned g_cnt[16 * 4 * 32];
__device__ unsigned g_mcnt;
__device__ unsigned g_slot[256];
__device__ unsigned g_fin;
__device__ __align__(16) uint4 g_cc[224 * 4];
__device__ __align__(1024) uint4 g_xc[44 * 16384];
__device__ __align__(1024) unsigned g_tm[4 * 256];
#define FT(i)
#define FTP(i)
#define PT(i)
#define PH(i)
#define RS(i)
#define RP(i)
#define RPN(i, s)
#define TSV(i, v)
#define TS(i)

#define FRC "232"
#define FRP "40"
#define FMAP (((g >> 2) * 4 + m) * 8 + ((g & 3) ^ ((g & 4) ? 3 : 0)) * 2 + (blockIdx.x & 1))
#define ALIAS 3
#define PFT 150000
#define PFS 104
#define PF0 13000
#define PFD 128
#define NF 3
#define NB0 4
#define PV0 4
#define T1L 1
#define NW0 5
#define VRF 3
#define VPC 1
#define WC0 10
#define WPE 2
#define ALN 0x80
#define SKW 3
#define L62 200
#define XDL 6
#define PDS 61
#define P_NVR 5
#define P_NWP 9
#define P_NW1 7
#define RF_ 208
#define RA_ (488 - 2 * RF_)
#define WCH 2
#define NOP_ 2
#define SPIN_LIMIT (1 << 20)
__device__ __forceinline__ uint64_t mkdesc(uint32_t addr, uint32_t lbo, uint32_t sbo) {
  return (uint64_t)((addr & 0x3FFFF) >> 4) | ((uint64_t)(lbo >> 4) << 16) | ((uint64_t)(sbo >> 4) << 32) | (1ull << 62);
}
__device__ __forceinline__ void mbar_init(uint32_t a, int c) { asm volatile("mbarrier.init.shared.b64 [%0],%1;" ::"r"(a), "r"(c) : "memory"); }
__device__ __forceinline__ void mbar_wait(uint32_t a, uint32_t par) {
  asm volatile(
      "{.reg .pred p; .reg .u32 n;\n"
      "mov.u32 n, 0;\n"
      "W: mbarrier.try_wait.parity.shared.b64 p,[%0],%1;\n"
      "@p bra D;\n"
      "add.u32 n, n, 1;\n"
      "setp.lt.u32 p, n, %2;\n"
      "@p bra W;\n"
      "trap;\n"
      "D:}" ::"r"(a), "r"(par), "n"(SPIN_LIMIT) : "memory");
}
__device__ __forceinline__ void mbar_wait_q(uint32_t a, uint32_t par) {
  asm volatile(
      "{.reg .pred p; .reg .u32 n;\n"
      "mov.u32 n, 0;\n"
      "W: mbarrier.try_wait.parity.shared.b64 p,[%0],%1,4000;\n"
      "@p bra D;\n"
      "add.u32 n, n, 1;\n"
      "setp.lt.u32 p, n, %2;\n"
      "@p bra W;\n"
      "trap;\n"
      "D:}" ::"r"(a), "r"(par), "n"(SPIN_LIMIT / 16) : "memory");
}
__device__ __forceinline__ void mbar_expect(uint32_t a, uint32_t b) { asm volatile("mbarrier.arrive.expect_tx.shared.b64 _,[%0],%1;" ::"r"(a), "r"(b) : "memory"); }
__device__ __forceinline__ void mbar_arrive(uint32_t a) { asm volatile("mbarrier.arrive.shared.b64 _,[%0];" ::"r"(a) : "memory"); }
__device__ __forceinline__ uint32_t mapa(uint32_t a, uint32_t cta) { uint32_t r; asm("mapa.shared::cluster.u32 %0,%1,%2;" : "=r"(r) : "r"(a), "r"(cta)); return r; }
__device__ __forceinline__ void mbar_arrive_cl(uint32_t a) { asm volatile("mbarrier.arrive.shared::cluster.b64 _,[%0];" ::"r"(a) : "memory"); }
__device__ __forceinline__ void tma2d(uint32_t dst, const CUtensorMap* m, int c0, int c1, uint32_t mb) {
  asm volatile("cp.async.bulk.tensor.2d.shared::cluster.global.mbarrier::complete_tx::bytes [%0],[%1,{%2,%3}],[%4];" ::"r"(dst), "l"(m), "r"(c0), "r"(c1), "r"(mb) : "memory");
}
__device__ __forceinline__ void tma2d_pf(const CUtensorMap* m, int c0, int c1) {
  asm volatile("cp.async.bulk.prefetch.tensor.2d.L2.global [%0,{%1,%2}];" ::"l"(m), "r"(c0), "r"(c1) : "memory");
}
__device__ __forceinline__ void tma2d_st(const CUtensorMap* m, int c0, int c1, uint32_t src) {
  asm volatile("cp.async.bulk.tensor.2d.global.shared::cta.bulk_group [%0,{%1,%2}],[%3];" ::"l"(m), "r"(c0), "r"(c1), "r"(src) : "memory");
}
__device__ __forceinline__ void bulk_ld(uint32_t dst, const void* src, uint32_t n, uint32_t mb) {
  asm volatile("cp.async.bulk.shared::cluster.global.mbarrier::complete_tx::bytes [%0],[%1],%2,[%3];" ::"r"(dst), "l"(src), "r"(n), "r"(mb) : "memory");
}
__device__ __forceinline__ void bulk_st(void* dst, uint32_t src, uint32_t n) {
  asm volatile("cp.async.bulk.global.shared::cta.bulk_group [%0],[%1],%2;" ::"l"(dst), "r"(src), "r"(n) : "memory");
}
__device__ __forceinline__ void e_expect_tma3d(uint32_t dst, const CUtensorMap* m, int c1, int c2, uint32_t mb, uint32_t bytes) {
  asm volatile("{.reg .pred p; elect.sync _|p, 0xffffffff; @p mbarrier.arrive.expect_tx.shared.b64 _,[%4],%5;\n"
               "@p cp.async.bulk.tensor.3d.shared::cluster.global.mbarrier::complete_tx::bytes [%0],[%1,{0,%2,%3}],[%4];}" ::"r"(dst), "l"(m), "r"(c1), "r"(c2), "r"(mb), "r"(bytes) : "memory");
}
__device__ __forceinline__ void e_bulk_ld(uint32_t dst, const void* src, uint32_t n, uint32_t mb) {
  asm volatile("{.reg .pred p; elect.sync _|p, 0xffffffff; @p cp.async.bulk.shared::cluster.global.mbarrier::complete_tx::bytes [%0],[%1],%2,[%3];}" ::"r"(dst), "l"(src), "r"(n), "r"(mb) : "memory");
}
#define BULK_COMMIT() asm volatile("cp.async.bulk.commit_group;" ::: "memory")
#define BULK_WAIT_READ(n) asm volatile("cp.async.bulk.wait_group.read " #n ";" ::: "memory")
#define BULK_WAIT(n) asm volatile("cp.async.bulk.wait_group " #n ";" ::: "memory")
#define FENCE_ASYNC_SMEM() asm volatile("fence.proxy.async.shared::cta;" ::: "memory")
#define FENCE_ASYNC() asm volatile("fence.proxy.async;" ::: "memory")
#define WG_FENCE() asm volatile("wgmma.fence.sync.aligned;" ::: "memory")
#define WG_COMMIT() asm volatile("wgmma.commit_group.sync.aligned;" ::: "memory")
#define WG_WAIT(n) asm volatile("wgmma.wait_group.sync.aligned " #n ";" ::: "memory")
#define BAR_SYNC(id, n) asm volatile("bar.sync %0,%1;" ::"n"(id), "n"(n) : "memory")
#define BAR_ARRIVE(id, n) asm volatile("bar.arrive %0,%1;" ::"n"(id), "n"(n) : "memory")
#define SCHED_FENCE(k) asm volatile("{.reg .pred p; setp.ne.u32 p,%0,0; @p trap;}" ::"r"(mp.zero[(k) - 46]) : "memory")
#define CLUSTER_SYNC() asm volatile("barrier.cluster.arrive.relaxed.aligned; barrier.cluster.wait.aligned;" ::: "memory")
__device__ __forceinline__ uint32_t pk(float lo, float hi) { uint32_t r; asm("cvt.rn.bf16x2.f32 %0,%1,%2;" : "=r"(r) : "f"(hi), "f"(lo)); return r; }
__device__ __forceinline__ float blo(uint32_t v) { return __uint_as_float(v << 16); }
__device__ __forceinline__ float bhi(uint32_t v) { return __uint_as_float(v & 0xffff0000u); }
__device__ __forceinline__ void ldsm4(uint32_t* r, uint32_t a) {
  asm volatile("ldmatrix.sync.aligned.m8n8.x4.shared.b16 {%0,%1,%2,%3},[%4];" : "=r"(r[0]), "=r"(r[1]), "=r"(r[2]), "=r"(r[3]) : "r"(a) : "memory");
}
__device__ __forceinline__ void ldsm4t(uint32_t* r, uint32_t a) {
  asm volatile("ldmatrix.sync.aligned.m8n8.x4.trans.shared.b16 {%0,%1,%2,%3},[%4];" : "=r"(r[0]), "=r"(r[1]), "=r"(r[2]), "=r"(r[3]) : "r"(a) : "memory");
}
__device__ __forceinline__ void stsm4(uint32_t a, uint32_t r0, uint32_t r1, uint32_t r2, uint32_t r3) {
  asm volatile("stmatrix.sync.aligned.m8n8.x4.shared.b16 [%0],{%1,%2,%3,%4};" ::"r"(a), "r"(r0), "r"(r1), "r"(r2), "r"(r3) : "memory");
}
__device__ __forceinline__ void mma16(float* d, uint32_t a0, uint32_t a1, uint32_t a2, uint32_t a3, uint32_t b0, uint32_t b1) {
  asm volatile("mma.sync.aligned.m16n8k16.row.col.f32.bf16.bf16.f32 {%0,%1,%2,%3},{%4,%5,%6,%7},{%8,%9},{%0,%1,%2,%3};"
               : "+f"(d[0]), "+f"(d[1]), "+f"(d[2]), "+f"(d[3]) : "r"(a0), "r"(a1), "r"(a2), "r"(a3), "r"(b0), "r"(b1));
}
__device__ __forceinline__ void mma8(float* d, uint32_t a0, uint32_t a1, uint32_t b0) {
  asm volatile("mma.sync.aligned.m16n8k8.row.col.f32.bf16.bf16.f32 {%0,%1,%2,%3},{%4,%5},{%6},{%0,%1,%2,%3};"
               : "+f"(d[0]), "+f"(d[1]), "+f"(d[2]), "+f"(d[3]) : "r"(a0), "r"(a1), "r"(b0));
}
__device__ __forceinline__ float4 lds4f(uint32_t a) { float4 v; asm volatile("ld.shared.v4.f32 {%0,%1,%2,%3},[%4];" : "=f"(v.x), "=f"(v.y), "=f"(v.z), "=f"(v.w) : "r"(a) : "memory"); return v; }
__device__ __forceinline__ float2 lds2f(uint32_t a) { float2 v; asm volatile("ld.shared.v2.f32 {%0,%1},[%2];" : "=f"(v.x), "=f"(v.y) : "r"(a) : "memory"); return v; }
__device__ __forceinline__ uint4 lds4(uint32_t a) { uint4 v; asm volatile("ld.shared.v4.u32 {%0,%1,%2,%3},[%4];" : "=r"(v.x), "=r"(v.y), "=r"(v.z), "=r"(v.w) : "r"(a) : "memory"); return v; }
__device__ __forceinline__ uint2 lds2u(uint32_t a) { uint2 v; asm volatile("ld.shared.v2.u32 {%0,%1},[%2];" : "=r"(v.x), "=r"(v.y) : "r"(a) : "memory"); return v; }
__device__ __forceinline__ uint32_t lds1(uint32_t a) { uint32_t v; asm volatile("ld.shared.u32 %0,[%1];" : "=r"(v) : "r"(a) : "memory"); return v; }
__device__ __forceinline__ void sts4(uint32_t a, uint32_t x, uint32_t y, uint32_t z, uint32_t w) { asm volatile("st.shared.v4.u32 [%0],{%1,%2,%3,%4};" ::"r"(a), "r"(x), "r"(y), "r"(z), "r"(w) : "memory"); }
__device__ __forceinline__ void sts2(uint32_t a, uint32_t x, uint32_t y) { asm volatile("st.shared.v2.u32 [%0],{%1,%2};" ::"r"(a), "r"(x), "r"(y) : "memory"); }
__device__ __forceinline__ void sts1(uint32_t a, uint32_t x) { asm volatile("st.shared.u32 [%0],%1;" ::"r"(a), "r"(x) : "memory"); }
__device__ __forceinline__ void sta4(uint32_t a, const uint32_t* v, uint32_t mb) {
  asm volatile("st.async.shared::cluster.mbarrier::complete_tx::bytes.v4.b32 [%0],{%1,%2,%3,%4},[%5];" ::"r"(a), "r"(v[0]), "r"(v[1]), "r"(v[2]), "r"(v[3]), "r"(mb) : "memory");
}
__device__ __forceinline__ uint4 ldg_rlx4(const void* p) { uint4 v; asm volatile("ld.relaxed.gpu.global.v4.u32 {%0,%1,%2,%3},[%4];" : "=r"(v.x), "=r"(v.y), "=r"(v.z), "=r"(v.w) : "l"(p) : "memory"); return v; }
__device__ __forceinline__ uint32_t ldg_rlx1(const void* p) { uint32_t v; asm volatile("ld.relaxed.gpu.global.u32 %0,[%1];" : "=r"(v) : "l"(p) : "memory"); return v; }
__device__ __forceinline__ uint4 ldg_b128(const void* p) {
  uint4 v;
  asm volatile("{.reg .b128 t; .reg .b64 a,b; ld.relaxed.gpu.global.b128 t,[%4]; mov.b128 {a,b},t; mov.b64 {%0,%1},a; mov.b64 {%2,%3},b;}" : "=r"(v.x), "=r"(v.y), "=r"(v.z), "=r"(v.w) : "l"(p) : "memory");
  return v;
}
__device__ __forceinline__ void stg_b128(void* p, uint32_t x, uint32_t y, uint32_t z, uint32_t w) {
  asm volatile("{.reg .b128 t; .reg .b64 a,b; mov.b64 a,{%1,%2}; mov.b64 b,{%3,%4}; mov.b128 t,{a,b}; st.relaxed.gpu.global.b128 [%0],t;}" ::"l"(p), "r"(x), "r"(y), "r"(z), "r"(w) : "memory");
}
__device__ __forceinline__ void stg_rlx2(void* p, uint32_t x, uint32_t y) { asm volatile("st.relaxed.gpu.global.v2.u32 [%0],{%1,%2};" ::"l"(p), "r"(x), "r"(y) : "memory"); }
__device__ __forceinline__ unsigned ld_acq(const unsigned* p) { unsigned v; asm volatile("ld.acquire.gpu.global.u32 %0,[%1];" : "=r"(v) : "l"(p) : "memory"); return v; }
__device__ __forceinline__ void red_rel(unsigned* p) { asm volatile("red.release.gpu.global.add.u32 [%0],1;" ::"l"(p) : "memory"); }
__device__ __forceinline__ void red_rlx(unsigned* p) { asm volatile("red.relaxed.gpu.global.add.u32 [%0],1;" ::"l"(p) : "memory"); }
__device__ __forceinline__ void wait_cnt(const unsigned* p, unsigned n) { int it = 0; while (ld_acq(p) < n) { if (++it > SPIN_LIMIT) __trap(); } }
__device__ __forceinline__ uint32_t clk() { uint32_t c; asm volatile("mov.u32 %0,%%clock;" : "=r"(c)); return c; }
__device__ __forceinline__ uint32_t gtime() { uint32_t c; asm volatile("mov.u32 %0,%%globaltimer_lo;" : "=r"(c)); return c; }
__device__ __forceinline__ float ex2(float x) { float r; asm("ex2.approx.ftz.f32 %0,%1;" : "=f"(r) : "f"(x)); return r; }
__device__ __forceinline__ float silu(float x) { return x * __frcp_rn(1.f + __expf(-x)); }
__device__ __forceinline__ float rbf(float x) { return __bfloat162float(__float2bfloat16_rn(x)); }

__device__ __forceinline__ void wgmma_ss_n128(float* d, uint64_t a, uint64_t b, int sd) {
  asm volatile("{.reg .pred p; setp.ne.b32 p, %66, 0;\n"
    "wgmma.mma_async.sync.aligned.m64n128k16.f32.bf16.bf16 {%0,%1,%2,%3,%4,%5,%6,%7,%8,%9,%10,%11,%12,%13,%14,%15,%16,%17,%18,%19,%20,%21,%22,%23,%24,%25,%26,%27,%28,%29,%30,%31,%32,%33,%34,%35,%36,%37,%38,%39,%40,%41,%42,%43,%44,%45,%46,%47,%48,%49,%50,%51,%52,%53,%54,%55,%56,%57,%58,%59,%60,%61,%62,%63}, %64, %65, p, 1, 1, 0, 1;}\n"
    : "+f"(d[0]),"+f"(d[1]),"+f"(d[2]),"+f"(d[3]),"+f"(d[4]),"+f"(d[5]),"+f"(d[6]),"+f"(d[7]),
      "+f"(d[8]),"+f"(d[9]),"+f"(d[10]),"+f"(d[11]),"+f"(d[12]),"+f"(d[13]),"+f"(d[14]),"+f"(d[15]),
      "+f"(d[16]),"+f"(d[17]),"+f"(d[18]),"+f"(d[19]),"+f"(d[20]),"+f"(d[21]),"+f"(d[22]),"+f"(d[23]),
      "+f"(d[24]),"+f"(d[25]),"+f"(d[26]),"+f"(d[27]),"+f"(d[28]),"+f"(d[29]),"+f"(d[30]),"+f"(d[31]),
      "+f"(d[32]),"+f"(d[33]),"+f"(d[34]),"+f"(d[35]),"+f"(d[36]),"+f"(d[37]),"+f"(d[38]),"+f"(d[39]),
      "+f"(d[40]),"+f"(d[41]),"+f"(d[42]),"+f"(d[43]),"+f"(d[44]),"+f"(d[45]),"+f"(d[46]),"+f"(d[47]),
      "+f"(d[48]),"+f"(d[49]),"+f"(d[50]),"+f"(d[51]),"+f"(d[52]),"+f"(d[53]),"+f"(d[54]),"+f"(d[55]),
      "+f"(d[56]),"+f"(d[57]),"+f"(d[58]),"+f"(d[59]),"+f"(d[60]),"+f"(d[61]),"+f"(d[62]),"+f"(d[63])
    : "l"(a), "l"(b), "r"(sd));
}
__device__ __forceinline__ void wgmma_ss_n192(float* d, uint64_t a, uint64_t b, int sd) {
  asm volatile("{.reg .pred p; setp.ne.b32 p, %98, 0;\n"
    "wgmma.mma_async.sync.aligned.m64n192k16.f32.bf16.bf16 {%0,%1,%2,%3,%4,%5,%6,%7,%8,%9,%10,%11,%12,%13,%14,%15,%16,%17,%18,%19,%20,%21,%22,%23,%24,%25,%26,%27,%28,%29,%30,%31,%32,%33,%34,%35,%36,%37,%38,%39,%40,%41,%42,%43,%44,%45,%46,%47,%48,%49,%50,%51,%52,%53,%54,%55,%56,%57,%58,%59,%60,%61,%62,%63,%64,%65,%66,%67,%68,%69,%70,%71,%72,%73,%74,%75,%76,%77,%78,%79,%80,%81,%82,%83,%84,%85,%86,%87,%88,%89,%90,%91,%92,%93,%94,%95}, %96, %97, p, 1, 1, 0, 1;}\n"
    : "+f"(d[0]),"+f"(d[1]),"+f"(d[2]),"+f"(d[3]),"+f"(d[4]),"+f"(d[5]),"+f"(d[6]),"+f"(d[7]),
      "+f"(d[8]),"+f"(d[9]),"+f"(d[10]),"+f"(d[11]),"+f"(d[12]),"+f"(d[13]),"+f"(d[14]),"+f"(d[15]),
      "+f"(d[16]),"+f"(d[17]),"+f"(d[18]),"+f"(d[19]),"+f"(d[20]),"+f"(d[21]),"+f"(d[22]),"+f"(d[23]),
      "+f"(d[24]),"+f"(d[25]),"+f"(d[26]),"+f"(d[27]),"+f"(d[28]),"+f"(d[29]),"+f"(d[30]),"+f"(d[31]),
      "+f"(d[32]),"+f"(d[33]),"+f"(d[34]),"+f"(d[35]),"+f"(d[36]),"+f"(d[37]),"+f"(d[38]),"+f"(d[39]),
      "+f"(d[40]),"+f"(d[41]),"+f"(d[42]),"+f"(d[43]),"+f"(d[44]),"+f"(d[45]),"+f"(d[46]),"+f"(d[47]),
      "+f"(d[48]),"+f"(d[49]),"+f"(d[50]),"+f"(d[51]),"+f"(d[52]),"+f"(d[53]),"+f"(d[54]),"+f"(d[55]),
      "+f"(d[56]),"+f"(d[57]),"+f"(d[58]),"+f"(d[59]),"+f"(d[60]),"+f"(d[61]),"+f"(d[62]),"+f"(d[63]),
      "+f"(d[64]),"+f"(d[65]),"+f"(d[66]),"+f"(d[67]),"+f"(d[68]),"+f"(d[69]),"+f"(d[70]),"+f"(d[71]),
      "+f"(d[72]),"+f"(d[73]),"+f"(d[74]),"+f"(d[75]),"+f"(d[76]),"+f"(d[77]),"+f"(d[78]),"+f"(d[79]),
      "+f"(d[80]),"+f"(d[81]),"+f"(d[82]),"+f"(d[83]),"+f"(d[84]),"+f"(d[85]),"+f"(d[86]),"+f"(d[87]),
      "+f"(d[88]),"+f"(d[89]),"+f"(d[90]),"+f"(d[91]),"+f"(d[92]),"+f"(d[93]),"+f"(d[94]),"+f"(d[95])
    : "l"(a), "l"(b), "r"(sd));
}
__device__ __forceinline__ void wgmma_rs_n32(float* d, const uint32_t* a, uint64_t b, int sd) {
  asm volatile("{.reg .pred p; setp.ne.b32 p, %21, 0;\n"
    "wgmma.mma_async.sync.aligned.m64n32k16.f32.bf16.bf16 {%0,%1,%2,%3,%4,%5,%6,%7,%8,%9,%10,%11,%12,%13,%14,%15}, {%16,%17,%18,%19}, %20, p, 1, 1, 0;}\n"
    : "+f"(d[0]),"+f"(d[1]),"+f"(d[2]),"+f"(d[3]),"+f"(d[4]),"+f"(d[5]),"+f"(d[6]),"+f"(d[7]),
      "+f"(d[8]),"+f"(d[9]),"+f"(d[10]),"+f"(d[11]),"+f"(d[12]),"+f"(d[13]),"+f"(d[14]),"+f"(d[15])
    : "r"(a[0]), "r"(a[1]), "r"(a[2]), "r"(a[3]), "l"(b), "r"(sd));
}
__device__ __forceinline__ void wgmma_ssT_n32(float* d, uint64_t a, uint64_t b, int sd) {
  asm volatile("{.reg .pred p; setp.ne.b32 p, %18, 0;\n"
    "wgmma.mma_async.sync.aligned.m64n32k16.f32.bf16.bf16 {%0,%1,%2,%3,%4,%5,%6,%7,%8,%9,%10,%11,%12,%13,%14,%15}, %16, %17, p, 1, 1, 1, 0;}\n"
    : "+f"(d[0]),"+f"(d[1]),"+f"(d[2]),"+f"(d[3]),"+f"(d[4]),"+f"(d[5]),"+f"(d[6]),"+f"(d[7]),
      "+f"(d[8]),"+f"(d[9]),"+f"(d[10]),"+f"(d[11]),"+f"(d[12]),"+f"(d[13]),"+f"(d[14]),"+f"(d[15])
    : "l"(a), "l"(b), "r"(sd));
}

__device__ __forceinline__ void wgmma_rs_n32_z(float* d, const uint32_t* a, uint64_t b) {
  asm volatile("{.reg .pred p; setp.ne.b32 p, 0, 0;\n"
    "wgmma.mma_async.sync.aligned.m64n32k16.f32.bf16.bf16 {%0,%1,%2,%3,%4,%5,%6,%7,%8,%9,%10,%11,%12,%13,%14,%15}, {%16,%17,%18,%19}, %20, p, 1, 1, 0;}\n"
    : "=f"(d[0]),"=f"(d[1]),"=f"(d[2]),"=f"(d[3]),"=f"(d[4]),"=f"(d[5]),"=f"(d[6]),"=f"(d[7]),
      "=f"(d[8]),"=f"(d[9]),"=f"(d[10]),"=f"(d[11]),"=f"(d[12]),"=f"(d[13]),"=f"(d[14]),"=f"(d[15])
    : "r"(a[0]), "r"(a[1]), "r"(a[2]), "r"(a[3]), "l"(b));
}

namespace rec {
constexpr int NVR = P_NVR;
constexpr int NVS = 16 - NVR;
constexpr int NWP = P_NWP;
constexpr uint32_t WO = 0;
constexpr uint32_t XB = 65536;
constexpr uint32_t PK = XB + 32768;
constexpr uint32_t VN = PK + 24576;
constexpr uint32_t VX0 = VN + 4096;
constexpr uint32_t WVS = 131072;
constexpr uint32_t MEM = WVS + 2 * NVS * 2048;
constexpr uint32_t ARO = MEM + 10240;
constexpr uint32_t OB = ARO + 5120;
constexpr uint32_t QT = OB + 2048;
constexpr uint32_t KT = QT + 2048;
constexpr uint32_t RQ = KT + 6144;
constexpr uint32_t RK = RQ + 2048;
constexpr uint32_t SC = RK + 2048;
constexpr uint32_t OT = OB;
constexpr uint32_t TF = SC + 2048;
constexpr uint32_t PRE = MEM + 2 * NVR * 2048;
constexpr uint32_t TA = TF + 8192;
constexpr uint32_t RX = TA + 6144;
constexpr uint32_t VX1 = RX + 2048;
constexpr uint32_t BARS = VX1 + 4096;
constexpr uint32_t PACE = BARS + 18 * 8;
constexpr uint32_t SMEM = BARS + 512;
static_assert(PRE + 14336 <= BARS, "staging");
constexpr int NW1 = P_NW1;
static_assert(SMEM <= 232448, "smem");
constexpr int B_E = 2, B_SC = 3, B_S = 4, B_O = 5, B_F = 6, B_W = 7, B_C = 9, B_K = 10, B_Q = 1, B_S2 = 6, B_T2 = 9, B_P = 13, B_T = 14, B_R = 11, B_X = 12, B_V = 8;
constexpr int XC = 16384, X_RING = 131072, X_SC = 65536, X_TOK = 4096;
#define X_VX(i) (((i) >> 1) * 2048 + ((i) & 1) * 512)
#define X_VM(i) (X_VX(i) + 1024)
#define V_RING(n) (((n) & 1) * X_RING + ((n) & 2) * 2048)
#define V_TAG(n) ((~(n) >> 2) & 1)
}
struct RecMaps { CUtensorMap wq, wk, wv, wo, ari; int zero[40]; };

#define F_(x) __uint_as_float(x)
#define U_(x) __float_as_uint(x)
#define AR_R(q) (24 + ((q) & 1) * 16 + ((q) >> 1) * 56)
#define AR_P(q) ((q) >> 1)
#define AR_ROW(i) (24 + ((i) & 1) * 16 + ((i) & 2) * 92 + (((i) >> 2) & 7) + ((i) >> 5) * 128)
constexpr size_t AR_OFF = 32 * 262144;
__device__ __forceinline__ void ar_fetch(uint32_t dst, const CUtensorMap* m, int slot, int half, uint32_t mb) {
  asm volatile("{.reg .pred p; elect.sync _|p, 0xffffffff; @p mbarrier.arrive.expect_tx.shared.b64 _,[%4],10240;\n"
               "@p cp.async.bulk.tensor.3d.shared::cluster.global.mbarrier::complete_tx::bytes [%0],[%1,{%2,%6,%3}],[%4];\n"
               "@p cp.async.bulk.tensor.3d.shared::cluster.global.mbarrier::complete_tx::bytes [%0+5120],[%1,{%2,%7,%5}],[%4];}"
               ::"r"(dst), "l"(m), "r"(slot * 64), "r"(AR_R(half * 2)), "r"(mb), "r"(AR_R(half * 2 + 1)), "r"(AR_P(half * 2)), "r"(AR_P(half * 2 + 1)) : "memory");
}
__device__ __forceinline__ uint4 exch_b128(void* p, uint32_t x, uint32_t y, uint32_t z, uint32_t w) {
  uint4 v;
  asm volatile("{.reg .b128 s, t; .reg .b64 a,b; mov.b64 a,{%5,%6}; mov.b64 b,{%7,%8}; mov.b128 s,{a,b}; atom.relaxed.gpu.global.exch.b128 t,[%4],s;"
               " mov.b128 {a,b},t; mov.b64 {%0,%1},a; mov.b64 {%2,%3},b;}" : "=r"(v.x), "=r"(v.y), "=r"(v.z), "=r"(v.w) : "l"(p), "r"(x), "r"(y), "r"(z), "r"(w) : "memory");
  return v;
}
#define CONSUME(v) do { if ((v) == 0x7fc12345u) sts1(sb + rec::BARS + 96, 0); } while (0)
__device__ __forceinline__ uint2 ldg_b64(const void* p) { uint2 v; asm volatile("{.reg .b64 t; ld.relaxed.gpu.global.b64 t,[%2]; mov.b64 {%0,%1},t;}" : "=r"(v.x), "=r"(v.y) : "l"(p) : "memory"); return v; }
__device__ __forceinline__ void stg_b64(void* p, uint32_t x, uint32_t y) { asm volatile("{.reg .b64 t; mov.b64 t,{%1,%2}; st.relaxed.gpu.global.b64 [%0],t;}" ::"l"(p), "r"(x), "r"(y) : "memory"); }
__device__ __forceinline__ uint32_t tagbad(uint32_t x, uint32_t y, uint32_t tag) { uint32_t r; asm("lop3.b32 %0,%1,%2,%3,0x7e;" : "=r"(r) : "r"(x), "r"(y), "r"(tag)); return r; }

__device__ __forceinline__ bool anybad(uint32_t a, uint32_t b, uint32_t c, uint32_t d, uint32_t e, uint32_t f, uint32_t g, uint32_t h, uint32_t tag) {
  uint32_t r;
  asm volatile("{.reg .b32 t,u,v,w; .reg .pred p; lop3.b32 t,%1,%2,%9,0x7e; lop3.b32 u,%3,%4,%9,0x7e; lop3.b32 v,%5,%6,%9,0x7e; lop3.b32 w,%7,%8,%9,0x7e;"
               " lop3.b32 t,t,u,v,0xfe; lop3.b32 t,t,w,1,0xa8; setp.ne.u32 p,t,0; vote.sync.any.pred p,p,0xffffffff; selp.u32 %0,1,0,p;}"
               : "=r"(r) : "r"(a), "r"(b), "r"(c), "r"(d), "r"(e), "r"(f), "r"(g), "r"(h), "r"(tag));
  return r;
}
__device__ __forceinline__ bool anybad(uint32_t a, uint32_t b, uint32_t c, uint32_t d, uint32_t tag) {
  uint32_t r;
  asm volatile("{.reg .b32 t,u; .reg .pred p; lop3.b32 t,%1,%2,%5,0x7e; lop3.b32 u,%3,%4,%5,0x7e;"
               " lop3.b32 t,t,u,1,0xa8; setp.ne.u32 p,t,0; vote.sync.any.pred p,p,0xffffffff; selp.u32 %0,1,0,p;}"
               : "=r"(r) : "r"(a), "r"(b), "r"(c), "r"(d), "r"(tag));
  return r;
}
#define BADS(r) anybad(r[0].x, r[0].y, r[1].x, r[1].y, r[2].x, r[2].y, r[3].x, r[3].y, tag)
constexpr float SCS = 0.08838834764831845f * 1.4426950408889634f / 16.f;
__device__ __forceinline__ uint32_t pkh(float lo, float hi, uint32_t tag) {
  uint32_t r;
  asm("{.reg .b32 t; cvt.rn.satfinite.f16x2.f32 t,%1,%2; lop3.b32 %0,t,0xfffffffe,%3,0xea;}" : "=r"(r) : "f"(hi), "f"(lo), "r"(tag));
  return r;
}
__device__ __forceinline__ uint32_t addh(uint32_t a, uint32_t b) { uint32_t r; asm("add.rn.f16x2 %0,%1,%2;" : "=r"(r) : "r"(a), "r"(b)); return r; }
__device__ __forceinline__ float hlo(uint32_t v) { float r; asm("{.reg .b16 a,b; mov.b32 {a,b},%1; cvt.f32.f16 %0,a;}" : "=f"(r) : "r"(v)); return r; }
__device__ __forceinline__ float hhi(uint32_t v) { float r; asm("{.reg .b16 a,b; mov.b32 {a,b},%1; cvt.f32.f16 %0,b;}" : "=f"(r) : "r"(v)); return r; }
__device__ __forceinline__ uint32_t ordh(uint32_t v) {
  uint32_t r;
  asm("{.reg .b32 m; prmt.b32 m,%1,0,0xbb99; lop3.b32 %0,%1,m,0x7fff7fff,0x78;}" : "=r"(r) : "r"(v));
  return r;
}
template <bool MASK>
__device__ __forceinline__ float4 softmax2(const uint2 (&r)[4], uint32_t mx, uint32_t my, uint32_t& k) {
  uint32_t x = addh(addh(r[0].x, r[1].x), addh(r[2].x, r[3].x)), y = addh(addh(r[0].y, r[1].y), addh(r[2].y, r[3].y));
  if (MASK) { x = addh(x, mx); y = addh(y, my); }
  asm("max.f16x2 %0,%1,%2;" : "=r"(k) : "r"(x), "r"(y));
  k = ordh(k);
  const int k0 = __reduce_max_sync(~0u, (int)(k << 16)), k1 = __reduce_max_sync(~0u, (int)k);
  const float m0 = hhi(k0 ^ ((k0 >> 31) & 0x7fff0000)) * -16.f, m1 = hhi(k1 ^ ((k1 >> 31) & 0x7fff0000)) * -16.f;
  return make_float4(ex2(fmaf(hlo(x), 16.f, m0)), ex2(fmaf(hhi(x), 16.f, m1)), ex2(fmaf(hlo(y), 16.f, m0)), ex2(fmaf(hhi(y), 16.f, m1)));
}
__device__ __forceinline__ char* mkp(uint32_t lo, uint32_t hi) { uint64_t r; asm("mov.b64 %0,{%1,%2};" : "=l"(r) : "r"(lo), "r"(hi)); return (char*)r; }
#define LO(p) ((uint32_t)(uint64_t)(p))
#define HI(p) ((uint32_t)((uint64_t)(p) >> 32))
__device__ __forceinline__ uint32_t mulbf(uint32_t a, uint32_t b) { uint32_t r; asm("mul.rn.bf16x2 %0,%1,%2;" : "=r"(r) : "r"(a), "r"(b)); return r; }
__device__ __forceinline__ uint32_t fmabf(uint32_t a, uint32_t b, uint32_t c) { uint32_t r; asm("fma.rn.bf16x2 %0,%1,%2,%3;" : "=r"(r) : "r"(a), "r"(b), "r"(c)); return r; }
__device__ __forceinline__ uint32_t addbf(uint32_t a, uint32_t b) { uint32_t r; asm("add.rn.bf16x2 %0,%1,%2;" : "=r"(r) : "r"(a), "r"(b)); return r; }
__device__ __forceinline__ void pv_mem(const uint32_t (&p)[4], uint32_t pm, const uint4 (&v)[4], const uint4 (&vn)[2], uint32_t (&O)[4]) {
  float o[4][4] = {{0, 0, 0, 0}, {0, 0, 0, 0}, {0, 0, 0, 0}, {0, 0, 0, 0}};
  mma16(o[0], v[0].x, v[0].y, v[0].z, v[0].w, p[0], p[1]);
  mma16(o[1], v[2].x, v[2].y, v[2].z, v[2].w, p[0], p[1]);
  mma16(o[2], v[1].x, v[1].y, v[1].z, v[1].w, p[2], p[3]);
  mma16(o[3], v[3].x, v[3].y, v[3].z, v[3].w, p[2], p[3]);
  mma16(o[0], vn[0].x, vn[0].y, vn[0].z, vn[0].w, pm, pm);
  mma16(o[1], vn[1].x, vn[1].y, vn[1].z, vn[1].w, pm, pm);
  O[0] = pk(o[0][0] + o[2][0], o[0][1] + o[2][1]); O[1] = pk(o[0][2] + o[2][2], o[0][3] + o[2][3]);
  O[2] = pk(o[1][0] + o[3][0], o[1][1] + o[3][1]); O[3] = pk(o[1][2] + o[3][2], o[1][3] + o[3][3]);
}
__device__ __forceinline__ void pv_tok(const uint32_t (&p)[4], uint32_t pm, const uint4 (&v)[4], const uint32_t (&vm)[4], uint32_t (&O)[4]) {
  float o[2][4] = {{0, 0, 0, 0}, {0, 0, 0, 0}}, sum[4] = {0, 0, 0, 0};
  const uint32_t one = 0x3f803f80u;
  mma16(sum, one, one, one, one, p[0], p[1]);
  mma16(o[0], v[0].x, v[0].y, v[0].z, v[0].w, p[0], p[1]);
  mma16(o[1], v[2].x, v[2].y, v[2].z, v[2].w, p[0], p[1]);
  mma16(sum, one, one, one, one, p[2], p[3]);
  mma16(o[0], v[1].x, v[1].y, v[1].z, v[1].w, p[2], p[3]);
  mma16(o[1], v[3].x, v[3].y, v[3].z, v[3].w, p[2], p[3]);
  mma8(sum, one, one, pm);
  mma8(o[0], vm[0], vm[1], pm);
  mma8(o[1], vm[2], vm[3], pm);
  float i0, i1;
  asm("rcp.approx.ftz.f32 %0,%1;" : "=f"(i0) : "f"(sum[0]));
  asm("rcp.approx.ftz.f32 %0,%1;" : "=f"(i1) : "f"(sum[1]));
  O[0] = pk(o[0][0] * i0, o[0][1] * i1); O[1] = pk(o[0][2] * i0, o[0][3] * i1);
  O[2] = pk(o[1][0] * i0, o[1][1] * i1); O[3] = pk(o[1][2] * i0, o[1][3] * i1);
}
__device__ __forceinline__ uint32_t sum4bf(uint32_t a, uint32_t b, uint32_t c, uint32_t d) { return addbf(addbf(a, b), addbf(c, d)); }
template <int OFF>
__device__ __forceinline__ void sta1(uint32_t a, uint32_t v, uint32_t mb) {
  asm volatile("st.async.shared::cluster.mbarrier::complete_tx::bytes.b32 [%0+%3],%1,[%2];" ::"r"(a), "r"(v), "r"(mb), "n"(OFF) : "memory");
}

__device__ __forceinline__ void wait_time(uint32_t t) { while ((int)(gtime() - t) < 0) __nanosleep(64); }
__device__ __noinline__ void rec_prefetch(const char* wmod, const char* w1, const char* x, const char* wo) {
  const int hb = blockIdx.x - 128;
  const uint32_t t0 = gtime();
  uint32_t t = t0 + PF0;
#pragma unroll 1
  for (int job = 0; job < (PFT ? 5 : 3); job++) {
    const char* p = job == 0 ? x + (6 + hb) * 65536 : job == 1 ? wmod + hb * 12288 + 4096 : job == 2 ? w1 + hb * 7168 : job == 3 ? x + hb * 8192 : wo + (1020 + hb) * 8192;
    const int n = job == 0 ? 120 - (hb & 2) * 4 : job == 3 ? 128 : 256, d = job == 0 ? 8192 : job == 1 ? 49152 : job == 2 ? 28672 : job == 3 ? 32768 : -32768;
    if (job == 3) t = t0 + PFT;
    PT(8 + job);
#pragma unroll 1
    for (int i = 0; i < n; i++) {
      wait_time(t);
      asm volatile("cp.async.bulk.prefetch.L2.global [%0], %1;" ::"l"(p), "r"(job == 2 ? 7168 : 8192) : "memory");
      p += !job && (i & 7) == 7 ? 204800 : d;
      t += job < 3 ? PFD : PFS;
      if (job && (i & 31) == 31 && ldg_rlx1(&g_fin)) return;
    }
  }
  PT(13);
}
__device__ __noinline__ void rec_helper(uint32_t sb, const bf16* cvec, const bf16* wmod, const char* w1, const bf16* b1, uint32_t t0) {
  const int tid = threadIdx.x, hb = blockIdx.x - 128;
  PT(1);
  for (int i = tid; i < 1024; i += 256) sts1(sb + i * 8, U_(rbf(silu(__bfloat162float(cvec[i])))));
  for (int i = tid; i < 2048; i += 256) g_stat[hb * 2048 + i] = make_uint4(~0u, ~0u, ~0u, ~0u);
  for (int i = tid; i < 512; i += 256) g_cnt[hb * 512 + i] = 0;
#pragma unroll 1
  for (int job = 0; job < 2; job++) {
    wait_time(t0 + PF0 + (job ? 600 : 350) * PFD);
    BAR_SYNC(rec::B_F, 256);
    PT(2 + job * 5);
    const int n8 = job ? 112 : 128, rg = tid >= n8, cg = tid - rg * n8, pitch = job ? 448 : 768;
    const uint4* p = (const uint4*)(job ? w1 + hb * 1792 : (const char*)(wmod + 2048 + hb * 1024)) + rg * pitch + min(cg, n8 - 1);
    float a1[8] = {0, 0, 0, 0, 0, 0, 0, 0}, a2[8] = {0, 0, 0, 0, 0, 0, 0, 0};
#pragma unroll 1
    for (int r0 = rg; r0 < 1024; r0 += 32) {
      uint4 v[16];
#pragma unroll
      for (int i = 0; i < 16; i++) { v[i] = ldg_rlx4(p); p += 2 * pitch; }
#pragma unroll
      for (int i = 0; i < 16; i++) {
        const float2 f = lds2f(sb + (r0 + 2 * i) * 8);
        const float w[8] = {blo(v[i].x), bhi(v[i].x), blo(v[i].y), bhi(v[i].y), blo(v[i].z), bhi(v[i].z), blo(v[i].w), bhi(v[i].w)};
#pragma unroll
        for (int e = 0; e < 8; e++) { a1[e] += f.x * w[e]; a2[e] += f.y * w[e]; }
      }
    }
    const uint32_t rd = sb + 8192;
    if (cg < n8) {
#pragma unroll
      for (int e = 0; e < 8; e++) sts2(rd + rg * 8192 + (cg * 8 + e) * 8, U_(a1[e]), U_(a2[e]));
    }
    BAR_SYNC(rec::B_F, 256);
    if (job == 0) {
      for (int i = tid; i < 1024; i += 256) g_mod[2048 + hb * 1024 + i] = rbf(F_(lds1(rd + i * 8)) + F_(lds1(rd + 8192 + i * 8)));
      BAR_SYNC(rec::B_F, 256);
      PT(6);
      if (tid == 0) { red_rel(&g_mcnt); wait_cnt(&g_mcnt, 4); }
      BAR_SYNC(rec::B_F, 256);
      for (int i = tid; i < 1024; i += 256) sts2(sb + i * 8, U_(rbf(1.f + __ldcg(g_mod + 4096 + i))), U_(__ldcg(g_mod + 3072 + i)));
    } else {
      for (int i = tid; i < 448; i += 256) {
        const int gn = hb * 896 + i * 2;
        const uint32_t bb = *(const uint32_t*)(b1 + gn);
        const float4 u = lds4f(rd + i * 16), w = lds4f(rd + 8192 + i * 16);
        ((uint2*)g_cc)[(gn >> 4) * 8 + ((gn >> 1) & 3) * 2 + ((gn >> 3) & 1)] = make_uint2(pk(u.x + w.x, u.z + w.z), pk(0.5f * (u.y + w.y + blo(bb)), 0.5f * (u.w + w.w + bhi(bb))));
      }
      PT(4);
    }
  }
}

__global__ void __cluster_dims__(2, 1, 1) __launch_bounds__(512, 1)
k_rec(const __grid_constant__ RecMaps mp, const bf16* __restrict__ mem0, const bf16* __restrict__ x, const bf16* __restrict__ cvec,
      const bf16* __restrict__ wmod, const char* __restrict__ w1, const bf16* __restrict__ b1, const char* __restrict__ wo, char* xc, int dF, int dA, int dS, int dM, int dG, int dP, int dX, int dD, int dZ, int dZ2, int dV, int dX2) {
  using namespace rec;
  extern __shared__ __align__(1024) char smem[];
  const uint32_t sb = (uint32_t)__cvta_generic_to_shared(smem);
  if ((sb & 0x3FFFF) != 1024) __trap();
  PH(0); RS(0); if (threadIdx.x == 0) PT(0);
  if (threadIdx.x == 0) {
    int b = blockIdx.x;
    if (b >= 8 && b < 128) {
      const int t = (b >> 1) - 4, u = t - 32;
      b = 2 * (t < 32 ? 4 + (t & 16) + (t & 7) * 2 + ((t >> 3) & 1) : 36 + (u / 14) * 14 + (u % 7) * 2 + ((u / 7) & 1)) + (b & 1);
    }
    sts1(sb + rec::PACE + 24, b);
    const int c = blockIdx.x >> 1, l = c < 36 ? (c - 4) & 7 : (c - 36) % 7, m = c < 4 ? c : c < 36 ? (c - 4) >> 3 : (c - 36) / 7;
    const int g = c < 4 ? 15 : (l >> 1) * 4 + (l & 1) + (c < 36 ? 0 : 2);
    unsigned sm;
    asm("mov.u32 %0,%%smid;" : "=r"(sm));
    if (c < 64) g_slot[sm & 255] = 1 + FMAP;
  }
#define ROLE_REFRESH { asm volatile("mov.u32 %0,%%tid.x;" : "=r"(tid)); wid = __shfl_sync(~0u, tid >> 5, 0); b = __shfl_sync(~0u, lds1(sb + PACE + 24), 0); }
#define ROLE_VARS int tid; asm volatile("mov.u32 %0,%%tid.x;" : "=r"(tid)); \
    int wid = __shfl_sync(~0u, tid >> 5, 0), b = __shfl_sync(~0u, lds1(sb + PACE + 24), 0);
#define wg (wid >> 2)
#define iw (wid & 3)
#define h (b >> 2)
#define j (b & 3)
#define a (b & 1)
#define bb ((b >> 1) & 1)
  const uint32_t wbar = sb + BARS + 48, obar = wbar + 8;
  if (threadIdx.x == 256) {
    for (int i = 0; i < 18; i++) if (i != 12) mbar_init(sb + BARS + i * 8, i == 3 || i == 8 || i == 9 || i == 10 ? 2 : 1);
    for (int i = 0; i < 3; i++) mbar_init(sb + PACE + i * 8, 1);
    asm volatile("fence.mbarrier_init.release.cluster;" ::: "memory");
    FENCE_ASYNC_SMEM();
    mbar_expect(sb + BARS, 2048);
    mbar_expect(sb + BARS + 16, 4096);
    mbar_expect(sb + BARS + 32, 4096);
    mbar_expect(sb + BARS + 40, 4096);
  }
  __syncthreads();
  asm volatile("barrier.cluster.arrive.relaxed.aligned;" ::: "memory");
#define lane ((int)(l16 >> 4))
#define l16 (L16 & 0x1f0)
#define PIN(x) __shfl_xor_sync(~0u, (uint32_t)(x), 0)
#define X_LOAD(n, w, u) \
        asm volatile("{.reg .pred p; elect.sync _|p, 0xffffffff; @p mbarrier.arrive.expect_tx.shared.b64 _,[%2],8192;\n" \
                     "@p cp.async.bulk.shared::cluster.global.mbarrier::complete_tx::bytes [%0],[%1],8192,[%2];}" ::"r"(sb + XB + (w) * 16384 + (u) * 8192), \
                     "l"(g_h + (n) * 4096 + a * 2048 + (w) * 1024 + (u) * 512), "r"(sb + BARS + 64 + (w) * 8) : "memory")
#define lpub ((L16 & 0x30) * 64 + ((L16 >> 3) & 0x38))
#define lrow ((L16 & 0x70) + (((L16 >> 3) ^ L16) & 0x70 & ~((L16 >> 3) & 0x40) ? L16 & 0x180 : 512))

  const int role = __shfl_sync(~0u, threadIdx.x >> 7, 0);
  if (role < 2) {
    asm volatile("setmaxnreg.inc.sync.aligned.u32 %0;" ::"n"(RF_));
    ROLE_VARS
    uint32_t L16 = __shfl_sync(~0u, sb + (tid & 31) * 16, tid & 31);
    uint32_t wQ[16][4], wK[16][4], wV[NVR][4];
    uint32_t frag = sb + ((lane & 7) + (lane >> 4) * 8) * 128 + (((iw * 2 + ((lane >> 3) & 1)) ^ (lane & 7)) << 4);
#define QSW (a ? 0 : 64)
    {
      const bool spare = b >= 128;
      const uint32_t t0 = gtime();
      uint4 xr[16];
      int seg = spare ? b - 126 : wg;
      const int half = spare ? wg : a;
      auto x_fetch = [&]() {
        const uint4* px = (const uint4*)x + (seg * 32 + iw * 8 + (lane >> 2)) * 128 + half * 64 + (lane & 3);
#pragma unroll
        for (int i = 0; i < 16; i++) xr[i] = __ldg(px + i * 4);
      };
      if (!spare) {
        uint4 wm[8];
        const uint4* pw = (const uint4*)(wmod + (size_t)((b >> 5) * 256 + (tid >> 3)) * 6144 + (b & 31) * 64) + (tid & 7);
        const float cs = __bfloat162float(cvec[(b >> 5) * 256 + tid]);
#pragma unroll
        for (int i = 0; i < 8; i++) wm[i] = __ldcs(pw + (size_t)i * 32 * 768);
        float* sc = (float*)(smem + PRE);
        sc[tid] = rbf(silu(cs));
        PT(1);
        BAR_SYNC(B_F, 256);
        float acc[8] = {0, 0, 0, 0, 0, 0, 0, 0};
#pragma unroll
        for (int i = 0; i < 8; i++) {
          const float f = sc[i * 32 + (tid >> 3)];
          acc[0] += f * blo(wm[i].x); acc[1] += f * bhi(wm[i].x); acc[2] += f * blo(wm[i].y); acc[3] += f * bhi(wm[i].y);
          acc[4] += f * blo(wm[i].z); acc[5] += f * bhi(wm[i].z); acc[6] += f * blo(wm[i].w); acc[7] += f * bhi(wm[i].w);
        }
#pragma unroll
        for (int i = 0; i < 8; i++) { acc[i] += __shfl_xor_sync(~0u, acc[i], 8); acc[i] += __shfl_xor_sync(~0u, acc[i], 16); }
        float* red = sc + 1024;
        if ((tid & 31) < 8) {
#pragma unroll
          for (int i = 0; i < 8; i++) red[(tid >> 5) * 64 + (tid & 7) * 8 + i] = acc[i];
        }
        BAR_SYNC(B_F, 256);
        PT(2);
        if (tid < 64) {
          float t = 0;
#pragma unroll
          for (int i = 0; i < 8; i++) t += red[i * 64 + tid];
          asm volatile("st.relaxed.gpu.global.u32 [%0],%1;" ::"l"((unsigned*)g_modp + (b >> 5) * 2048 + (b & 31) * 64 + tid), "r"(U_(t) | 1u) : "memory");
        }
      } else {
        asm volatile("griddepcontrol.launch_dependents;");
      }
      x_fetch();
      const uint32_t md = sb + PRE + 6144, rx = mapa(sb, a ^ !spare);
      asm volatile("barrier.cluster.wait.aligned;" ::: "memory");
      if (!spare) {
        mbar_wait(sb + BARS + 88, 0);
#pragma unroll
        for (int i = 0; i < 16; i++) ldsm4t(wQ[i], (frag ^ QSW) + WO + wg * 32768 + i * 2048);
      }
      PT(4);
#pragma unroll 1
      for (int it = 0;; it++) {
        if (tid == 0) mbar_expect(sb + BARS + 104, 512);
        float c[4][4] = {{0, 0, 0, 0}, {0, 0, 0, 0}, {0, 0, 0, 0}, {0, 0, 0, 0}};
#pragma unroll
        for (int i = 0; i < 16; i++) {
          mma16(c[(i & 1) * 2], xr[i].x, 0x3f803f80u, xr[i].y, 0x3f803f80u, xr[i].x, xr[i].y);
          mma16(c[(i & 1) * 2 + 1], xr[i].z, 0x3f803f80u, xr[i].w, 0x3f803f80u, xr[i].z, xr[i].w);
        }
#pragma unroll
        for (int e = 0; e < 4; e++) c[0][e] = (c[0][e] + c[1][e]) + (c[2][e] + c[3][e]);
        const int src = (lane & 28) + (lane >> 3);
        const float sq = __shfl_sync(~0u, (lane & 4) ? c[0][1] : c[0][0], src), sm = __shfl_sync(~0u, (lane & 4) ? c[0][3] : c[0][2], src);
        if ((lane & 3) < 2) sta1<0>(rx + PRE + 10240 + (wid ^ (spare * 4)) * 64 + (lane >> 2) * 8 + (lane & 1) * 4, U_((lane & 1) ? sm : sq), rx + BARS + 104);
        mbar_wait(sb + BARS + 104, it & 1);
        const float2 ot = lds2f(sb + PRE + 10240 + wid * 64 + (lane >> 2) * 8);
        const float mean = (sm + ot.y) * (1.f / 1024);
        const float rs = rsqrtf(fmaxf((sq + ot.x) * (1.f / 1024) - mean * mean, 0.f) + 1e-5f), nm = -mean * rs;
        const uint32_t rh = pk(rs, rs), rl = pk(rs - blo(rh), rs - blo(rh)), n2 = pk(nm, nm);
#define NRM(v) v = fmabf(v, rh, fmabf(v, rl, n2))
#pragma unroll
        for (int i = 0; i < 16; i++) { NRM(xr[i].x); NRM(xr[i].y); NRM(xr[i].z); NRM(xr[i].w); }
        if (!it) {
          PT(3);
#pragma unroll 1
          for (int i = 0; i < 2; i++) {
            uint4 p[4];
            for (int n = 0;; n++) {
#pragma unroll
              for (int e = 0; e < 4; e++) p[e] = ldg_rlx4(g_modp + e * 512 + i * 256 + tid);
              uint32_t ok = 1;
#pragma unroll
              for (int e = 0; e < 4; e++) ok &= p[e].x & p[e].y & p[e].z & p[e].w;
              if (__all_sync(~0u, ok) || n > SPIN_LIMIT / 16) break;
              __nanosleep(100);
            }
#define MSUM(e) (i + rbf((F_(p[0].e) + F_(p[1].e)) + (F_(p[2].e) + F_(p[3].e))))
            sts2(md + i * 2048 + tid * 8, pk(MSUM(x), MSUM(y)), pk(MSUM(z), MSUM(w)));
          }
          BAR_SYNC(B_F, 256);
          PT(5);
        }
        const int e0 = (iw * 8 + (lane >> 2)) * 8 + ((lane & 3) ^ (lane >> 2));
        uint4* dst = g_h + seg * 4096 + half * 2048;
#pragma unroll
        for (int i = 0; i < 16; i++) {
          const uint32_t ma = md + half * 1024 + (lane & 3) * 16 + i * 64;
          const uint4 sv = lds4(ma), cv = lds4(ma + 2048);
          xr[i] = make_uint4(fmabf(xr[i].x, cv.x, sv.x), fmabf(xr[i].y, cv.y, sv.y), fmabf(xr[i].z, cv.z, sv.z), fmabf(xr[i].w, cv.w, sv.w));
        }
        if (!spare) {
#pragma unroll
          for (int i = 0; i < 16; i++) sts4(sb + WO + wg * 32768 + (e0 ^ ((i & 1) * 4)) * 16 + (i >> 1) * 4096, xr[i].x, xr[i].y, xr[i].z, xr[i].w);
          break;
        }
#pragma unroll
        for (int i = 0; i < 16; i++) dst[(e0 ^ ((i & 1) * 4)) + (i >> 1) * 256] = xr[i];
        seg += 4;
        if (seg < 64) x_fetch();
        FENCE_ASYNC();
        BAR_SYNC(B_F, 256);
        if (tid == 0) red_rlx(g_hf + b - 128);
        if (seg >= 64) break;
      }
      if (spare) { rec_helper(sb, cvec, wmod, w1, b1, t0); return; }
      PH(1); PH(2); PT(6);
    }
    ROLE_REFRESH
#define ownv ((iw >> 1) == a)
#define owner (iw >= 2)
#define oi (wid & 1)
    {
      const uint32_t rsb = mapa(sb, owner ? a : a ^ 1);
      const uint32_t pp = rsb + PK + (owner ? 0 : 12288) + (oi * 2048 + wg * 1024) + l16;
      const uint32_t mb = sb + MEM + wg * 5120;
      sts4(L16 + TF + wid * 512, mb + lrow, owner ? L16 + (lane >> 4) * (RK - RQ - 256) + RQ + oi * 1024 + wg * 256 : rsb + RQ + oi * 1024 + 512 + wg * 256 + (l16 >> 2),
           L16 + OB, frag + wg * NVS * 2048);
      sts4(L16 + TF + 4096 + wid * 512, sb + WO + (wid >> 1) * 16384 + ((lane & 7) + (lane >> 4) * 8) * 128 + ((((wid & 1) * 4 + ((lane >> 3) & 1)) ^ (lane & 7)) << 4),
           sb + ARO + wid * 640 + lrow, pp, LO(xc) + h * 262144 + (bb * 2 + (iw >> 1)) * XC + X_VM(0) + oi * 2048 + a * 256 + (l16 >> 1));
    }
    uint32_t tp = L16 + TF + wid * 512;
    auto park_ptr = [&]() { return lds1(tp + 4096 + 8); };
    auto park_w = [&](const uint32_t* w, int m, uint32_t d) {
      if (m == 2) d += (sb & 0x1000000) ? 0 : owner ? 0x1003000 : -0x1003000;
      if (m == 2 ? ownv : owner) {
        sts4(d + m * 4096, w[0], w[1], w[2], w[3]); sts4(d + m * 4096 + 512, w[4], w[5], w[6], w[7]);
      } else {
        const uint32_t pb = (d & 0xff000000u) | (1024 + BARS + (m ? 24 + m * 8 : 16));
        sta4(d + m * 4096, w, pb); sta4(d + m * 4096 + 512, w + 4, pb);
      }
    };
    auto park = [&](const float* f, int m, int n, uint32_t d) {
      uint32_t w[8];
#pragma unroll
      for (int i = 0; i < 8; i++) w[i] = pk(f[2 * i], f[2 * i + 1]);
      park_w(w, m, d);
    };
#define D64(lo) (0x4000004000000000ull | (uint32_t)(lo))
#define XD(i) D64(x | (((i) >> 2) * 256 + ((i) & 3) * 2))
    auto xdesc = [&](uint32_t xb) { return ((uint32_t)__shfl_sync(~0u, 1024 + xb + wg * 16384, 0) >> 4) | 0x10000u; };
    auto rs_issue = [&](float* acc, const uint32_t (&w)[16][4], uint32_t xb, bool fence) {
      const uint32_t x = xdesc(xb);
      if (fence) WG_FENCE();
      wgmma_rs_n32_z(acc, w[0], XD(0));
#pragma unroll
      for (int i = 1; i < 16; i++) wgmma_rs_n32(acc, w[i], XD(i), 1);
      WG_COMMIT();
    };
    auto v_issue = [&](float* acc, uint32_t xb, bool fence) {
      const uint32_t dv = ((uint32_t)__shfl_sync(~0u, 1024 + WVS + wg * NVS * 2048, 0) >> 4) | 0x10000u, x = xdesc(xb);
      if (fence) WG_FENCE();
      wgmma_rs_n32_z(acc, wV[0], XD(0));
#pragma unroll
      for (int i = 1; i < VRF; i++) wgmma_rs_n32(acc, wV[i], XD(i), 1);
#pragma unroll
      for (int i = NVR; i < 16; i++) wgmma_ssT_n32(acc, D64(dv + (i - NVR) * 128), XD(i), 1);
#pragma unroll
      for (int i = VRF; i < NVR; i++) wgmma_rs_n32(acc, wV[i], XD(i), 1);
      WG_COMMIT();
    };
    uint32_t mA, vP[2][4];
#define V_AHEAD mA = lds1(tp); frag = lds1(tp + 12); ldsm4t(vP[0], frag + WVS + (15 - NVR) * 2048); ldsm4t(vP[1], frag + WVS + (14 - NVR) * 2048);
    auto vk_pass = [&](int n, uint32_t d, uint32_t xb, bool steady, auto between) {
      float acc[16], acc2[16];
      v_issue(acc, xb, true);
      rs_issue(acc2, wK, xb, false);
      between();
      if (steady || n) mbar_wait(sb + BARS + 80, (n - 1) & 1);
      WG_WAIT(1);
      park(acc, 2, n, d);
      if (steady) BAR_ARRIVE(B_K, 320);
      V_AHEAD
      WG_WAIT(0);
      park(acc2, 1, n, d + (VPC ? (vP[1][0] ^ mA) & dZ : 0));
    };
    uint32_t q0[8], q1[8];
    {
      float acc[16], acc2[16];
      FENCE_ASYNC_SMEM();
      BAR_SYNC(B_F, 256);
      rs_issue(acc, wQ, WO, true);
      rs_issue(acc2, wQ, WO + 32768, false);
      WG_WAIT(0);
#pragma unroll
      for (int i = 0; i < 8; i++) { q0[i] = pk(acc[2 * i], acc[2 * i + 1]); q1[i] = pk(acc2[2 * i], acc2[2 * i + 1]); }
    }
    mbar_wait(wbar, 0);
    PT(7);
#pragma unroll
    for (int i = 0; i < 16; i++) ldsm4t(wK[i], (frag ^ QSW) + XB + wg * 32768 + i * 2048);
#pragma unroll
    for (int i = 0; i < NVR; i++) ldsm4t(wV[i], frag + MEM + (wg * NVR + i) * 2048);
    FENCE_ASYNC_SMEM();
    PH(3); PT(8);
    CLUSTER_SYNC();
    PT(9);
    frag += wg * NVS * 2048;
    park_w(q0, 0, park_ptr());
    PT(10);
#pragma unroll 1
    for (int n = 0; n < 2; n++) {
      asm volatile("" : "+r"(wid));
      vk_pass(n, park_ptr(), n * XB, false, [&]() {
        if (n) {
          BAR_SYNC(B_C, 320);
          PT(12);
          mbar_wait(sb + BARS + 24, 0);
          park_w(q1, 0, park_ptr());
        }
      });
      if (n) break;
      PT(11);
      BAR_SYNC(B_C, 448);
      if (tid == 0) {
        mbar_expect(obar, 65536);
#pragma unroll 1
        for (int i = 0; i < 4; i++) tma2d(sb + WO + i * 16384, &mp.wo, j * 256 + i * 64, h * 128, obar);
      }
    }
    static_assert(WO == 0, "x");
    {
      BAR_ARRIVE(B_P, 384); BAR_ARRIVE(B_X, 320); BAR_ARRIVE(B_Q, 288);
    }
    PT(13);
    PH(4); RS(1); PT(14);
    ROLE_REFRESH
    for (int s = 0; s < 64; s++) {
      asm volatile("" : "+r"(tp), "+r"(wid));
      asm volatile("mov.u32 %0,%%cluster_ctarank;" : "=r"(b));
      uint32_t vS[NVS][4], bf[8][4];
      static_assert(NVR == 5, "schedule");
#define VLD(k) ldsm4t(vS[(k) - NVR], frag + WVS + ((k) - NVR) * 2048)
#define BLD(t) ldsm4t(bf[t], mA + (t) * 640)
#define VMMA(c, w, i) mma16(c, (w)[0], (w)[1], (w)[2], (w)[3], bf[(i) >> 1][((i) & 1) * 2], bf[(i) >> 1][((i) & 1) * 2 + 1])
#define VS_(c, k) VMMA(c, vS[(k) - NVR], k)
#define QK(i) VMMA(cQ, wQ[i], i); VMMA(cK, wK[i], i)
#define PREV VLD(13); VLD(12); if (NF > 2) VLD(11);
      if (s > 0) BAR_SYNC(B_R, 320);
      float cV[4] = {0, 0, 0, 0}, cW[4] = {0, 0, 0, 0};
      {
        float cQ[4] = {0, 0, 0, 0}, cK[4] = {0, 0, 0, 0};
        BLD(7); BLD(6); BLD(5); BLD(4); if (NB0 > 4) BLD(3);
        SCHED_FENCE(47);
        QK(15); VMMA(cV, vP[0], 15);
        QK(14); VMMA(cV, vP[1], 14);
        QK(13); QK(12);
        SCHED_FENCE(51);
        if (NB0 < 5) BLD(3);
        BLD(2); BLD(1); BLD(0);
        const uint32_t rm = lds1(tp + 4);
        QK(11); QK(10); QK(9); QK(8); QK(7);
        if (PV0 == 6) { SCHED_FENCE(48); PREV }
        QK(6); QK(5);
        if (PV0 == 4) { QK(4); SCHED_FENCE(48); PREV } else { QK(4); }
        QK(3); QK(2); QK(1); QK(0);
        const uint32_t w0 = pk(cQ[0] * SCS, cQ[1] * SCS), w1 = pk(cQ[2] * SCS, cQ[3] * SCS), w2 = pk(cK[0], cK[1]), w3 = pk(cK[2], cK[3]);
        if (owner) {
          stsm4(rm, w0, w1, w2, w3);
          BAR_ARRIVE(B_E, 256);
        } else {
          const uint32_t mm = (rm & 0xff000000u) | (1024 + BARS);
          sta1<0>(rm, w0, mm); sta1<128>(rm, w1, mm);
          sta1<RK - RQ>(rm, w2, mm); sta1<RK - RQ + 128>(rm, w3, mm);
        }
        if (wid == 2) TS(0);
      }
      uint4 t1;
      uint32_t oA, wo[16][4];
      {
        if (NF < 3) VLD(11);
        VLD(10);
        VS_(cW, 13); VLD(9); VS_(cV, 12); VLD(8); VLD(7); VMMA(cW, wV[0], 0); VMMA(cV, wV[1], 1); VLD(6);
        VMMA(cW, wV[2], 2); VMMA(cV, wV[3], 3); VLD(5); VMMA(cW, wV[4], 4); VS_(cV, 11);
        VS_(cW, 10); VS_(cV, 9); VS_(cW, 8); VS_(cV, 7); VS_(cW, 6); VS_(cV, 5);
#pragma unroll
        for (int e = 0; e < 4; e++) cV[e] += cW[e];
        const uint32_t ex = tp + (RX - TF) - wg * 2048;
        t1 = lds4(tp + 4096 + (T1L ? vS[3][0] & dZ : 0));
        oA = lds1(tp + 8 + (s & dZ));
        if (wg) {
          sts4(ex, U_(cV[0]), U_(cV[1]), U_(cV[2]), U_(cV[3]));
          BAR_ARRIVE(B_T2, 256);
        }
        if (!wg) {
          BAR_SYNC(B_T2, 256);
          const float4 u = lds4f(ex);
          stg_b64(mkp(t1.w ^ ((s & 1) * X_RING), HI(xc)), (pk(cV[0] + u.x, cV[1] + u.y) & ~1u) | (((s >> 1) + 1) & 1), pk(cV[2] + u.z, cV[3] + u.w));
        }
      }
      if (s == 63) break;
      if (s == 0) mbar_wait(obar, 0);
      {
        const uint32_t woA = t1.x, woB = woA ^ 32;
#pragma unroll
        for (int i = 0; i < NW0; i++) ldsm4t(wo[i], ((i & 1) ? woB : woA) + (i >= WCH ? wo[(i - WCH + NWP) % NWP][0] & dZ : 0) + (i >> 1) * 2048);
        BAR_SYNC(B_S, 416);
        float inv0, inv1;
        uint32_t p[4], pm;
        const uint32_t pa = oA + (SC - OB), one = 0x3f803f80u;
#define P_LOAD ldsm4t(p, pa); asm volatile("ldmatrix.sync.aligned.m8n8.x1.trans.shared.b16 {%0},[%1];" : "=r"(pm) : "r"(pa + 512) : "memory");
        if (s < 62) {
          float acc[16];
          rs_issue(acc, wQ, XB, true);
          mbar_wait(sb + BARS + 24, (s + 1) & 1);
          WG_WAIT(0);
          uint32_t qw[8];
#pragma unroll
          for (int i = 0; i < 8; i++) qw[i] = pk(acc[2 * i], acc[2 * i + 1]);
#pragma unroll
          for (int i = NW0; i < NW1; i++) ldsm4t(wo[i], ((i & 1) ? woB : woA) + (i >> 1) * 2048);
          BAR_SYNC(B_V, 512);
          P_LOAD
          park_w(qw, 0, t1.z);
        } else {
#pragma unroll
          for (int i = NW0; i < NW1; i++) ldsm4t(wo[i], ((i & 1) ? woB : woA) + (i >> 1) * 2048);
          BAR_SYNC(B_V, 512);
          P_LOAD
        }
#pragma unroll
        for (int i = NW1; i < NWP; i++) ldsm4t(wo[i], ((i & 1) ? woB : woA) + (i >> 1) * 2048);
        {
          float sum[4] = {0, 0, 0, 0}, su2[4] = {0, 0, 0, 0};
          mma16(sum, one, one, one, one, p[0], p[1]);
          mma16(su2, one, one, one, one, p[2], p[3]);
          mma8(sum, one, one, pm);
          inv0 = sum[0] + su2[0]; inv1 = sum[1] + su2[1];
          SCHED_FENCE(57);
        }
        BAR_SYNC(B_O, 416);
        float c[2][4] = {{0, 0, 0, 0}, {0, 0, 0, 0}};
        uint32_t o[4][4];
#pragma unroll
        for (int i = 0; i < NOP_; i++) ldsm4t(o[i], oA + i * 512);
        SCHED_FENCE(46);
        asm("rcp.approx.ftz.f32 %0,%0;" : "+f"(inv0));
        asm("rcp.approx.ftz.f32 %0,%0;" : "+f"(inv1));
#pragma unroll
        for (int i = 0; i < 16; i++) {
          mma16(c[i & 1], wo[i][0], wo[i][1], wo[i][2], wo[i][3], o[i >> 2][i & 2], o[i >> 2][(i & 2) + 1]);
          if (i == 1 && NOP_ < 3) ldsm4t(o[2], oA + 1024);
          if (i == 3 && NOP_ < 4) ldsm4t(o[3], oA + 1536);
          if (i + NWP < 16) ldsm4t(wo[(i + NWP) & 15], (((i + NWP) & 1) ? woB : woA) + ((i + NWP) >> 1) * 2048);
        }
        stsm4(t1.y, pk(c[0][0] * inv0, c[0][1] * inv1), pk(c[0][2] * inv0, c[0][3] * inv1), pk(c[1][0] * inv0, c[1][1] * inv1), pk(c[1][2] * inv0, c[1][3] * inv1));
      }
      const uint32_t d = park_ptr();
      BAR_SYNC(B_W, 384);
      if (s < 62) {
        vk_pass(s + 2, d, XB, true, []() {});
        BAR_ARRIVE(B_P, 384); BAR_ARRIVE(B_X, 320);
        TS(10);
      } else {
        V_AHEAD
        CONSUME(vP[1][0]);
      }
    }
  } else if (role == 3) {
    asm volatile("setmaxnreg.dec.sync.aligned.u32 24;");
    if (blockIdx.x >= 128) return;
    ROLE_VARS
    const uint32_t L16 = sb + (tid & 31) * 16;
    asm volatile("barrier.cluster.wait.aligned;" ::: "memory");
    CLUSTER_SYNC();
    sts1(sb + PACE + 36, LO(xc) + h * 262144 + X_VM(0));
    auto vm_stage = [&](int s) {
      const uint32_t tag = ((s >> 1) + 1) & 1;
      const char* xm = mkp(lds1(sb + PACE + 36) + (s & 1) * X_RING + iw * XC + (l16 >> 1), HI(xc));
      uint2 m[4];
      CONSUME(LO(xm));
      BAR_SYNC(B_S2, 256);
      int it = 0;
      while (true) {
#pragma unroll
        for (int i = 0; i < 4; i++) m[i] = ldg_b64(xm + (i >> 1) * 2048 + (i & 1) * 256);
        sts4(L16 + VN + iw * 512, m[0].x, m[0].y, m[1].x, m[1].y);
        sts4(L16 + VN + iw * 512 + 2048, m[2].x, m[2].y, m[3].x, m[3].y);
        if (!anybad(m[0].x, m[1].x, m[2].x, m[3].x, tag)) break;
        RP(2);
        if (++it > SPIN_LIMIT) __trap();
      }
      if (s < 63) BAR_ARRIVE(B_V, 512); else BAR_ARRIVE(B_V, 256);
    };
    if (iw == 0) {
      wait_cnt(&g_hcnt, 128);
#pragma unroll 1
      for (int s = 0; s < 63; s++) {
        if (s < 62) for (int it = 0; ldg_rlx1(g_hf + (s & 3)) <= (s >> 2); it++) if (it > SPIN_LIMIT) __trap();
        if (s) BAR_SYNC(B_R, 320); else BAR_SYNC(B_Q, 288);
        if (s < 62) { X_LOAD(s + 2, 0, 0); X_LOAD(s + 2, 1, 0); X_LOAD(s + 2, 0, 1); X_LOAD(s + 2, 1, 1); }
        if (s >= 7) {
          const uint32_t zo = b * 160 + l16;
          if (l16 < 160) CONSUME(exch_b128(xc + AR_OFF + AR_ROW(zo >> 7) * 1024 + (zo & 127) + ((s + 1) & 7) * 128, 0, 0, 0, 0).x);
          __syncwarp();
        }
        if (s < 62) { mbar_wait(sb + BARS + 64, s & 1); mbar_wait(sb + BARS + 72, s & 1); }
        BAR_ARRIVE(B_S, 416);
        vm_stage(s);
        BAR_ARRIVE(B_O, 416);
        BAR_SYNC(B_W, 384);
        FENCE_ASYNC_SMEM();
        asm volatile("{.reg .pred p; elect.sync _|p, 0xffffffff; @p cp.reduce.async.bulk.tensor.3d.global.shared::cta.add.bulk_group [%0,{%1,%4,%2}],[%3];}"
                     ::"l"(&mp.ari), "r"((s & 7) * 64), "r"(AR_R(j)), "r"(sb + ARO), "r"(AR_P(j)) : "memory");
        BULK_COMMIT();
        asm volatile("st.relaxed.gpu.global.u32 [%0],%1;" ::"l"(g_tm + (s & 1) * 128 + b), "r"(gtime()) : "memory");
        TS(3);
        BULK_WAIT_READ(0);
      }
      BAR_ARRIVE(B_R, 320);
    } else if (iw == 1) {
      const uint32_t pc = sb + MEM + (lane >> 2) * 640 + (lane & 3) * 144 + (lane & 12), pd = sb + MEM + (lane & 15) * 640 + 576 + (lane & 3) * 16 + (lane & 12);
      uint32_t T = 0, par = 0;
      int est = dA;
#pragma unroll 1
      for (int s = 0; s < 63; s++) {
        if (s) {
          const uint4 tm = ldg_rlx4((const char*)g_tm + ((s + 1) & 1) * 512 + l16);
          const int t0 = tm.x - T, t1 = tm.y - T, t2 = tm.z - T, t3 = tm.w - T;
          const int e = max(dF + (__reduce_add_sync(~0u, (t0 + t1) + (t2 + t3)) >> 7), dV + __reduce_max_sync(~0u, max(max(t0, t1), max(t2, t3))));
          if (s > 1) est += max(min(e >> 2, dP), -dP);
          T += (s == 1 || e > dM ? e : 0) + est - (s == 62 ? L62 : 0);
        }
        vm_stage(s);
        BAR_SYNC(B_W, 384);
        SCHED_FENCE(70);
        const uint32_t tW = gtime();
        if (s == 0) T = tW + 800;
        const uint32_t te = tW + min(max((int)(T - tW), dD), 2000);
        while ((int)(gtime() - te) < 0) {}
        TS(7);
        int it = 0;
        while (true) {
          ar_fetch(sb + MEM, &mp.ari, s & 7, a, sb + BARS + 112);
          mbar_wait(sb + BARS + 112, par);
          par ^= 1;
          const uint32_t n0 = lds1(pc), n1 = lds1(pc + 5120), n2 = lds1(pd);
          if (!__any_sync(~0u, (tagbad(n0, n1, 0x42004200) | (n2 ^ 0x42004200)) != 0)) break;
          RP(0);
          if (++it > SPIN_LIMIT) __trap();
        }
        BAR_ARRIVE(B_R, 320);
        TS(11);
      }
    } else {
#define V_LOAD(n) do { if (lane == 0) mbar_expect(sb + BARS + 8, 8192); __syncwarp(); \
        if (lane < 16) bulk_ld(sb + ((lane & 2) ? VX1 : VX0) + (lane & 1) * 2048 + (lane >> 2) * 512, \
                               xc + h * 262144 + V_RING(n) + (lane >> 2) * XC + X_VX(lane & 3), 512, sb + BARS + 8); __syncwarp(); } while (0)
      uint32_t src = L16 + PK + (iw & 1) * 2048;
#define qd (L16 + (lane >> 4) * 256 + QT + (iw & 1) * 1024)
#define vd (LO(xc) + h * 262144 + j * XC + (iw & 1) * 2048 + l16)
#define FINISH [&](int n, int m) { \
_Pragma("unroll") \
        for (int i = 1; i >= 0; i--) { \
          const uint32_t p = src + m * 4096 + i * 512; \
          uint4 u = lds4(p); \
          const uint4 w = lds4(p + 1024), y = lds4(p + 12288), z = lds4(p + 13312); \
          u = make_uint4(sum4bf(u.x, w.x, y.x, z.x), sum4bf(u.y, w.y, y.y, z.y), sum4bf(u.z, w.z, y.z, z.z), sum4bf(u.w, w.w, y.w, z.w)); \
          if (m == 2) stg_b128(mkp(vd ^ V_RING(n), HI(xc)) + i * 512, (u.x & ~1u) | V_TAG(n), u.y, u.z, u.w); \
          else stsm4(qd + (n & 1) * 4096 + m * 2048 + i * 256, u.x, u.z, u.y, u.w); \
          SCHED_FENCE(71 + m * 2 + i); \
        } \
      }
#pragma unroll 1
      for (int n = 0; n < 64; n++) {
        src = PIN(src);
        b = __shfl_sync(~0u, lds1(sb + PACE + 24), 0);
        const uint32_t L16 = src - PK - (iw & 1) * 2048;
        auto finish = FINISH;
        if (n < 2) { if (n) BAR_SYNC(B_X, 320); else BAR_SYNC(B_C, 448); }
        mbar_wait(sb + BARS + 16, n & 1);
        finish(n, 0);
        __syncwarp();
        if (lane == 0) mbar_arrive_cl(mapa(sb, a ^ 1) + BARS + 24);
        if (n > 1) BAR_SYNC(B_K, 320);
        mbar_wait(sb + BARS + 40, n & 1);
        finish(n, 2);
        if (n > 1) BAR_SYNC(B_X, 320);
        mbar_wait(sb + BARS + 32, n & 1);
        finish(n, 1);
        BAR_SYNC(B_T, 64);
        if (lane == 0) {
          if (iw == 2 && n < 63) { mbar_expect(sb + BARS + 16, 4096); mbar_expect(sb + BARS + 32, 4096); mbar_expect(sb + BARS + 40, 4096); }
          mbar_arrive_cl(mapa(sb, a ^ 1) + BARS + 80);
        }
        __syncwarp();
        if (n) {
          vm_stage(n - 1);
          BAR_SYNC(B_W, 384);
        } else {
          BAR_SYNC(B_C, 320);
        }
        if (iw == 2) V_LOAD(n);
      }
#undef qd
#undef vd
    }
    { ROLE_REFRESH }
    vm_stage(63);
  } else {
    asm volatile("setmaxnreg.dec.sync.aligned.u32 %0;" ::"n"(RA_));
    if (blockIdx.x >= 128) { if (threadIdx.x == 256) rec_prefetch((const char*)wmod, w1, (const char*)x, wo); return; }
    ROLE_VARS
    uint32_t L16 = __shfl_sync(~0u, sb + (tid & 31) * 16, tid & 31);
    const uint32_t ts = gtime();
    uint2 m0[8];
#pragma unroll
    for (int r = 0; r < 8; r++) m0[r] = *(const uint2*)(mem0 + r * 1024 + a * 512 + (tid - 256) * 4);
    if (wid == 9) {
#pragma unroll 1
      for (int i = b * 80 + (tid & 31); i < b * 80 + 80; i += 32) ((uint4*)(xc + AR_OFF))[AR_ROW(i >> 6) * 64 + (i & 63)] = make_uint4(0, 0, 0, 0);
      if (b == 0) g_fin = 0;
      FENCE_ASYNC();
      __syncwarp();
      if (tid == 288) red_rlx(&g_hcnt);
    }
    if (tid == 256) {
      const int col = h * 128 + bb * 64;
#pragma unroll 1
      for (int c = 0, w = 0; w < 12; c++) {
#pragma unroll 1
        for (; w <= c - (c < WC0 ? 2 : 3); w++) {
          mbar_wait(sb + PACE + (w % 3) * 8, (w / 3) & 1);
          PT(18 + w);
          if (w == 3) asm volatile("mbarrier.arrive.shared.b64 _,[%0];" ::"r"(sb + BARS + 88) : "memory");
        }
        const uint32_t mb = sb + PACE + (c % 3) * 8;
        if (c >= 12 && c < 12 + WPE) tma2d_pf(&mp.wo, j * 256 + (c - 12) * 64, h * 128);
        if (c >= 12) continue;
        mbar_expect(mb, 16384);
        if (c < 8) tma2d(sb + (c >> 2) * XB + (c & 3) * 16384, (c & 4) ? &mp.wk : &mp.wq, col, a * 512 + (c & 3) * 128, mb);
        else
#pragma unroll 1
          for (int i = (c & 1) * 8; i < (c & 1) * 8 + 8; i++) {
            const int w = (c - 8) >> 1;
            tma2d(i < NVR ? sb + MEM + (w * NVR + i) * 2048 : sb + WVS + (w * NVS + i - NVR) * 2048, &mp.wv, col, a * 512 + w * 256 + i * 16, mb);
          }
      }
      asm volatile("mbarrier.arrive.shared.b64 _,[%0];" ::"r"(wbar) : "memory");
      for (int i = 0; i < 3; i++) asm volatile("mbarrier.inval.shared.b64 [%0];" ::"r"(sb + PACE + i * 8) : "memory");
    }
    __syncwarp();
    asm volatile("barrier.cluster.wait.aligned;" ::: "memory");
    CLUSTER_SYNC();
#pragma unroll 4
    for (int i = 0; i < 16; i++) {
      const uint4 v = lds4(L16 + WO + 32768 + iw * 8192 + i * 512);
      sts4(L16 + XB + iw * 8192 + i * 512, v.x, v.y, v.z, v.w);
    }
#pragma unroll
    for (int i = 0; i < 4; i++) {
      const int k = (tid - 256) * 4 + i, m = (k >> 3) & 3, r = k & 7;
#define M0W(r) __byte_perm((i & 2) ? m0[r].y : m0[r].x, (i & 2) ? m0[r + 1].y : m0[r + 1].x, (i & 1) ? 0x7632 : 0x5410)
      sts4(sb + MEM + (k >> 5) * 640 + (r == m ? 512 : m * 128) + r * 16, M0W(0), M0W(2), M0W(4), M0W(6));
    }
#pragma unroll 1
    for (int i = tid - 256; i < 192; i += 128) {
      const uint32_t c = i < 128 ? 0x42004200 : 0x3f803f80;
      sts4(sb + MEM + (i >> 3) * 640 + ((i & 7) < 4 ? (i & 7) * 144 : 512 + (i & 7) * 16), c, c, c, c);
    }
    static_assert(ARO == MEM + 16 * 640, "counters");
    FENCE_ASYNC_SMEM();
    BAR_ARRIVE(B_C, 448);
    if (tid == 256) {
      wait_time(ts + 1);
#pragma unroll 1
      for (int c = WPE; c < 4; c++) tma2d_pf(&mp.wo, j * 256 + c * 64, h * 128);
    }
    __syncwarp();
#define pr (L16 + SC)
    {
      const int lim = j * 8 + iw * 2 - (lane & 7) - (lane & 8) * 2;
      const bool mk = L16 & 256;
      const int rw = lane >> 2;
      sts4(L16 + TA + iw * 512,
           iw != 2 ? L16 + KT + (iw & 1) * 256 + (lane >> 4) * 256 : sb + RK + (L16 & 0x80) * 2 + ((L16 >> 1) & 0x80) + (L16 & 0x70),
           L16 + QT + (lane >> 3) * 384, sb + SC + min(lane >> 3, 2) * 256 + (L16 & 0x70) + iw * 4, L16 + (lane >> 4) * 256 + QT + (iw >> 1) * 1024 + (iw & 1) * 256);
      sts4(L16 + TA + 2048 + iw * 512, mk ? 0u : (lim < 0 ? 0xfc00u : 0u) | (lim < -1 ? 0xfc000000u : 0u),
           mk ? 0xfc00fc00u : (lim < 8 ? 0xfc00u : 0u) | (lim < 7 ? 0xfc000000u : 0u),
           ((h * 2 + (iw >> 1)) * 1024 + (j * 8 + rw) * 8 + (((iw & 1) * 4 + (lane & 3)) ^ rw)) * 16, sb + OT + iw * 512 + (L16 & 0x70) * 4 + ((L16 >> 3) & 0x30));
    }
    {
      const uint32_t xh = LO(xc) + h * 262144, xs = xh + X_SC + iw * 1024 + min(lane, 16 + (lane & 7)) * 8;
      sts4(L16 + TA + 4096 + iw * 512, xh + X_SC + j * 256 + iw * 64 + lpub, xs, dS, iw != 2 ? 0 : U_(SCS));
      sts1(L16 + TA + 12 + iw * 512, xs + X_TOK + j * 4096);
    }
    uint32_t tA = L16 + TA + iw * 512;
#define tw (tA - L16 != TA + 1024)
#define XP_(lo) mkp(lo, HI(xc))
    auto publish = [&](char* d, const uint2& w) { stg_b64(d, w.x, w.y); };
    BAR_SYNC(B_P, 384);
    for (int s = 0; s < 64; s++) {
      asm volatile("" : "+r"(L16), "+r"(tA));
      const uint32_t tag = ((s >> 1) + 1) & 1, ring = (s & 1) * X_RING;
      const uint4 t0 = lds4(tA);
      const uint4 tx = lds4(tA + 4096);
      const uint32_t xo = tx.x ^ ring, xs = tx.y ^ ring;
      const float gm = F_(tx.w);
      const uint32_t qA = t0.y + (ring >> 5);
      uint32_t c0;
      uint2 ts[4];
      uint4 v[4];
      uint32_t af[2][4], qt[4][4];
      {
        const uint32_t aA = t0.x + (tw ? ring >> 5 : 0);
        uint32_t ql[2][4], qr[2][4];
        uint2 pw_;
        float c[4] = {0, 0, 0, 0}, d[4] = {0, 0, 0, 0};
        if (s == PDS) asm volatile("griddepcontrol.launch_dependents;");
#pragma unroll
        for (int i = 0; i < 4; i++) ldsm4t(qt[i], qA + i * 128);
        mbar_wait(sb + BARS + 8, s & 1);
        TS(4);
        BAR_SYNC(B_E, 256);
#define PACK(c) make_uint2(pkh(fmaf(c[2], gm, c[0] * SCS), fmaf(c[3], gm, c[1] * SCS), tag), pkh(c[2] * SCS, c[3] * SCS, tag))
        ldsm4t(ql[0], L16 + RQ); ldsm4t(ql[1], L16 + RQ + 1024); ldsm4t(af[0], aA); ldsm4t(af[1], aA + 1024);
        CONSUME(xo);
#define QSUM(t, i) addbf(addbf(ql[t][i], ql[t][i + 2]), addbf(qr[t][i], qr[t][i + 2]))
#define STAIL mma16(c, af[0][0], af[0][1], af[0][2], af[0][3], QSUM(0, 0), QSUM(0, 1)); mma16(d, af[1][0], af[1][1], af[1][2], af[1][3], QSUM(1, 0), QSUM(1, 1));
        if (tw) {
          mbar_wait(sb + BARS, s & 1);
          TS(8);
          ldsm4t(qr[0], L16 + RQ + 512); ldsm4t(qr[1], L16 + RQ + 1536);
          STAIL
          pw_ = make_uint2(pkh(c[0] + d[0], c[1] + d[1], tag), pkh(c[2] + d[2], c[3] + d[3], tag));
        } else {
          uint32_t ar[2][4];
          mbar_wait(sb + BARS, s & 1);
          ldsm4t(qr[0], L16 + RQ + 512); ldsm4t(ar[0], aA + 512); ldsm4t(qr[1], L16 + RQ + 1536); ldsm4t(ar[1], aA + 1536);
#pragma unroll
          for (int i = 0; i < 8; i++) af[i >> 2][i & 3] = addbf(af[i >> 2][i & 3], ar[i >> 2][i & 3]);
          STAIL
          pw_.x = pw_.y = pkh((c[0] + c[2]) + (d[0] + d[2]), (c[1] + c[3]) + (d[1] + d[3]), tag);
        }
        publish(XP_(xo), pw_);
        c0 = clk() + tx.z;
        TS(1);
      }
      uint2 r[4];
      bool vbad;
      uint4 vn[2];
      {
        float e[4][4];
#pragma unroll
        for (int i = 0; i < 4; i++) {
          e[i][0] = e[i][1] = e[i][2] = e[i][3] = 0.f;
          mma16(e[i], af[0][0], af[0][1], af[0][2], af[0][3], qt[i][0], qt[i][1]);
        }
#pragma unroll
        for (int i = 0; i < 4; i++) mma16(e[i], af[1][0], af[1][1], af[1][2], af[1][3], qt[i][2], qt[i][3]);
        SCHED_FENCE(55);
        if (s < 63) BAR_ARRIVE(B_S, 416);
        SCHED_FENCE(58);
        v[0] = lds4(tA + (VX0 - TA)); v[1] = lds4(tA + (VX0 - TA) + 2048); v[2] = lds4(tA + (VX1 - TA)); v[3] = lds4(tA + (VX1 - TA) + 2048);
#pragma unroll
        for (int i = 0; i < 4; i++) ts[i] = PACK(e[i]);
        vbad = anybad(v[0].x, v[1].x, v[2].x, v[3].x, V_TAG(s));
        while ((int)(clk() - c0) < 0) {}
        TS(5);
#pragma unroll
        for (int u = 0; u < 4; u++) r[u] = ldg_b64(XP_(xs) + u * 256);
        BAR_ARRIVE(B_S2, 256);
      }
      SCHED_FENCE(56);
      uint32_t kk;
      float4 e = softmax2<false>(r, 0, 0, kk);
      if (__builtin_expect(anybad(r[0].x, r[0].y, r[1].x, r[1].y, r[2].x, r[2].y, r[3].x, r[3].y, tag ^ (kk & dZ)), 0)) {
        int it = 0;
        if (s > 8) sts1(tA + 4096 + 8, min(lds1(tA + 4096 + 8) + dX, 500));
        do {
          RP(1);
          if (++it > SPIN_LIMIT) __trap();
#pragma unroll
          for (int u = 0; u < 4; u++) r[u] = ldg_b64(XP_(xs) + u * 256);
        } while (BADS(r));
        e = softmax2<false>(r, 0, 0, kk);
      }
      sts1(t0.z, pk(e.x, e.y)); sts1(t0.z + 128, pk(e.z, e.w));
#pragma unroll
      for (int i = 0; i < 4; i++) publish(XP_(xo) + X_TOK + i * 4096, ts[i]);
      TS(6);
      if (s < 63) BAR_SYNC(B_V, 512); else BAR_SYNC(B_V, 256);
      uint32_t O[4];
      {
        uint32_t p[4], pm;
        ldsm4t(p, pr);
        asm volatile("ldmatrix.sync.aligned.m8n8.x1.trans.shared.b16 {%0},[%1];" : "=r"(pm) : "r"(pr + 512) : "memory");
        vn[0] = lds4(tA + (VN - TA)); vn[1] = lds4(tA + (VN - TA) + 2048);
        pv_mem(p, pm, v, vn, O);
        if (__builtin_expect(vbad, 0)) {
          int it = 0;
          const uint32_t xv = LO(xc) + (lds1(sb + PACE + 24) >> 2) * 262144 + ((tA - L16 - TA) >> 9) * XC;
          do {
            RP(2);
            if (++it > SPIN_LIMIT) __trap();
#pragma unroll
            for (int u = 0; u < 4; u++) v[u] = ldg_b128(XP_((xv + l16) ^ V_RING(s)) + X_VX(u));
          } while (anybad(v[0].x, v[1].x, v[2].x, v[3].x, V_TAG(s)));
          pv_mem(p, pm, v, vn, O);
        }
      }
      stsm4(tA + (OB - TA), O[0], O[1], O[2], O[3]);
      if (s < 63) BAR_ARRIVE(B_O, 416);
      TS(2);
      c0 = clk() + dG;
      SCHED_FENCE(60);
      if (tA == sb + TA) mbar_expect(sb + BARS, 2048);
      const uint32_t vs[4] = {addbf(vn[0].x, vn[0].z), addbf(vn[0].y, vn[0].w), addbf(vn[1].x, vn[1].z), addbf(vn[1].y, vn[1].w)};
      {
        const char* xt = XP_(lds1(tA + 12) ^ ring);
        const uint2 t1 = lds2u(tA + 2048);
        const uint32_t pw = lds1(tA + 8);
        uint2 rt[4];
        CONSUME(LO(xt) ^ t1.x ^ pw);
        while ((int)(clk() - c0) < 0) {}
        int it = 0;
        do {
          if (++it > SPIN_LIMIT) __trap();
#pragma unroll
          for (int u = 0; u < 4; u++) rt[u] = ldg_b64(xt + u * 256);
        } while (BADS(rt));
        uint32_t kt;
        const float4 et = softmax2<true>(rt, t1.x, t1.y, kt);
        sts1(pw + 1024, pk(et.x, et.y)); sts1(pw + 1024 + 128, pk(et.z, et.w));
      }
      s = PIN(s);
      BAR_SYNC(B_SC, 128);
      {
        uint32_t Ot[4], p[4], pm;
        const uint2 t2 = lds2u(tA + 2048 + 8);
        ldsm4t(p, pr + 1024);
        asm volatile("ldmatrix.sync.aligned.m8n8.x1.trans.shared.b16 {%0},[%1];" : "=r"(pm) : "r"(pr + 1024 + 512) : "memory");
        char* od = (char*)g_O + ((s >> 2) * 1048576 + (s & 3) * 4096) + t2.x;
        CONSUME(LO(od) ^ HI(od) ^ pm ^ p[3]);
        TS(9);
        if (s < 62) BAR_SYNC(B_P, 384);
        pv_tok(p, pm, v, vs, Ot);
        asm volatile("stmatrix.sync.aligned.m8n8.x4.trans.shared.b16 [%0],{%1,%2,%3,%4};" ::"r"(t2.y), "r"(Ot[0]), "r"(Ot[1]), "r"(Ot[2]), "r"(Ot[3]) : "memory");
        __syncwarp();
        *(uint4*)od = lds4(tA + (OT - TA));
      }
    }
    FENCE_ASYNC();
    BAR_SYNC(B_SC, 128);
    if (tA == sb + TA) red_rlx(&g_fin);
  }
  __syncwarp();
  CLUSTER_SYNC();
  PH(5); RS(2);
}
#undef wg
#undef iw
#undef h
#undef j
#undef a
#undef bb
#undef oi
#undef owner
#undef ownv
#undef pr
#undef PIN
#undef XP_
#undef tw
#undef lane
#undef l16
#undef lrow
#undef lpub

namespace ffn {
constexpr uint32_t BR = 98304;
constexpr uint32_t STG = 196608;
constexpr uint32_t PRM = 229376;
constexpr uint32_t BARS = PRM + 2816;
constexpr uint32_t SMEM = BARS + 18 * 8;
}
#define Y_TILE(rb, kt) (((ALIAS & 1) ? g_h : g_h2) + ((rb) * 16 + (kt)) * 1024)
#define U_TILE(rb, kt) ((ALIAS & 2) ? g_O + ((rb) * 64 + (kt)) * 1024 : g_U + ((rb) * 56 + (kt)) * 1024)
struct FfnMaps { CUtensorMap wo, w1a, w1b, w2, x, out; };

template <int N>
__device__ __forceinline__ void wg_ss(float* d, uint64_t a, uint64_t b, int sd) {
  if (N == 128) wgmma_ss_n128(d, a, b, sd);
  if (N == 192) wgmma_ss_n192(d, a, b, sd);
}
template <int N>
__device__ __forceinline__ void acc_fence(float* d) {
#pragma unroll
  for (int i = 0; i < N; i++) asm volatile("" : "+f"(d[i])::"memory");
}
#define UNPK8(d, v) do { (d)[0] = blo(v.x); (d)[1] = bhi(v.x); (d)[2] = blo(v.y); (d)[3] = bhi(v.y); (d)[4] = blo(v.z); (d)[5] = bhi(v.z); (d)[6] = blo(v.w); (d)[7] = bhi(v.w); } while (0)
struct FfnPipe {
  uint32_t full, emp, ph, aoff;
  int st, sB, prev;
  bool leader;
  template <int N, int S = N>
  __device__ __forceinline__ void issue(float* acc, bool first, uint32_t a = 0) {
    mbar_wait(full + st * 8, ph);
    const uint64_t da = mkdesc((a ? a : 1024 + st * 16384) + aoff, 16, 1024), db = mkdesc(1024 + ffn::BR + sB * (S * 128), 8192, 1024);
    WG_FENCE();
#pragma unroll
    for (int j = 0; j < 4; j++) wg_ss<N>(acc, da + j * 2, db + j * 128, j || !first);
    WG_COMMIT();
    if (++sB == 768 / S) sB = 0;
  }
  __device__ __forceinline__ void release() { if (leader) mbar_arrive(emp + prev * 8); }
  __device__ __forceinline__ void next() { prev = st; if (++st == 6) { st = 0; ph ^= 1; } }
  __device__ __forceinline__ void retire() { WG_WAIT(1); release(); next(); }
};
__device__ __forceinline__ float gelu_h(float hx) {
  float u = hx * fmaf(hx * hx, 8.f * 0.0356774081f, 2.f * 0.7978845608f), t;
  asm("tanh.approx.f32 %0,%1;" : "=f"(t) : "f"(u));
  return fmaf(hx, t, hx);
}
struct FfnEpi {
  uint32_t st2, cc, flip, staged, l0;
  uint2 c;
  float n0, n1, s0, s1;
  __device__ __forceinline__ void flush(uint32_t r) {
    __syncwarp();
    asm volatile("{.reg .pred p; setp.ne.u32 p,%1,0; @p mbarrier.arrive.shared.b64 _,[%0];}" ::"r"(staged + (flip >> 11)), "r"(l0 & r) : "memory");
    flip ^= r << 14;
  }
  __device__ __forceinline__ void half(const float* d, int J, int r) {
#define PRE(i, n, c1, c2) gelu_h(fmaf(r ? d[4 + i] : d[i], i < 2 ? s0 : s1, fmaf(n, c1, c2)))
    asm volatile("stmatrix.sync.aligned.m8n8.x2.shared.b16 [%0],{%1,%2};" ::"r"((st2 ^ ((J & 3) * 32 + r * 16)) + flip),
                 "r"(pk(PRE(0, n0, blo(c.x), blo(c.y)), PRE(1, n0, bhi(c.x), bhi(c.y)))), "r"(pk(PRE(2, n1, blo(c.x), blo(c.y)), PRE(3, n1, bhi(c.x), bhi(c.y)))) : "memory");
#undef PRE
    if ((J & 3) == 3) flush(r);
    cc += r ? 56 : 8;
    c = lds2u(cc);
  }
};

__global__ void __launch_bounds__(384, 1)
k_ffn(const __grid_constant__ FfnMaps mp, const bf16* __restrict__ b2) {
  using namespace ffn;
  extern __shared__ __align__(1024) char smem[];
  const uint32_t sb = (uint32_t)__cvta_generic_to_shared(smem);
  if (sb != 1024) __trap();
  const int tid = threadIdx.x, lane = tid & 31, wg = __shfl_sync(~0u, tid >> 7, 0);
  const uint32_t full = sb + BARS, emp = full + 48, xbar = full + 96, staged = full + 104, tile = full + 136;
  uint32_t fin = 0;
  if (tid >= 288 && tid < 320) fin = ld_acq(&g_fin);
  if (tid < 32) {
    unsigned sm, v = 0;
    asm("mov.u32 %0,%%smid;" : "=r"(sm));
    if (tid == 0) {
      v = atomicExch(&g_slot[sm & 255], 0);
      for (int i = 0; i < 6; i++) { mbar_init(full + i * 8, 1); mbar_init(emp + i * 8, 2); }
      mbar_init(xbar, 2);
      for (int i = 0; i < 2; i++) { mbar_init(staged + i * 8, 8); mbar_init(staged + 16 + i * 8, 1); }
      FENCE_ASYNC_SMEM();
    }
    v = __shfl_sync(~0u, v, 0);
    if (!v) {
      wait_cnt(&g_fin, 128);
      for (int it = 0; !v; it++) {
        const uint4 a = ldg_rlx4(g_slot + tid * 8), b = ldg_rlx4(g_slot + tid * 8 + 4);
        const uint32_t open = __ballot_sync(~0u, a.x | a.y | a.z | a.w | b.x | b.y | b.z | b.w);
        if (!open) break;
        if (it < 16) { __nanosleep(500); continue; }
        if (tid == __ffs(open) - 1) v = atomicExch(&g_slot[tid * 8 + (a.x ? 0 : a.y ? 1 : a.z ? 2 : a.w ? 3 : b.x ? 4 : b.y ? 5 : b.z ? 6 : 7)], 0);
        v = __shfl_sync(~0u, v, __ffs(open) - 1);
      }
    }
    if (tid == 0) sts1(tile, v);
  }
  if (tid == 256) asm volatile("prefetch.tensormap [%0];" ::"l"(&mp.wo) : "memory");
  __syncthreads();
  const int bid = __shfl_sync(~0u, lds1(tile), 0) - 1;
  if (bid < 0) return;
  PH(6);
  FT(1);
  const int rb = bid >> 3, nb = bid & 7;
  unsigned* cnt = g_cnt + rb * 128;
  if (wg == 2) {
    asm volatile("setmaxnreg.dec.sync.aligned.u32 " FRP ";");
    const int pw = __shfl_sync(~0u, (tid >> 5) & 3, 0);
    uint32_t ws = emp, wp = 1, fs = full;
    auto wait_free = [&]() { mbar_wait_q(ws, wp); ws += 8; if (ws == emp + 48) { ws = emp; wp ^= 1; } };
    auto step = [&]() { fs += 8; if (fs == full + 48) fs = full; };
#define K3(c) ((0x65230 >> (c) * 4) & 7)
#define KC(k) ((k) < 2 ? nb * 2 + (k) : (k) < 9 ? ((k) - 2 + ((k) - 2 >= nb)) * 2 : ((k) - 9 + ((k) - 9 >= nb)) * 2 + 1)
    if (pw == 0) {
      uint32_t d = sb + BR + 32768;
      auto put = [&](const CUtensorMap* m, int k, int c) {
        e_expect_tma3d(d, m, k * 64, c, fs, 32768);
        step();
        d += 16384;
        if (d == sb + STG) d = sb + BR;
      };
      int n = 0;
      auto stage_free = [&]() { if (!(n & 7) && n < 56) mbar_wait_q(staged + 16 + (n & 8), (n >> 4) & 1); n++; };
      auto align = [&]() {
        if (ALN && !((n - 1) & 7) && ((ALN >> ((n - 1) >> 3)) & 1)) {
          unsigned* c = g_cnt + 64 + ((n - 1) >> 3);
          if (lane == 0) red_rlx(c);
          for (int it = 0; ldg_rlx1(c) < 128 && it < 64; it++) {}
        }
      };
      FTP(3);
#pragma unroll 1
      for (int k = 0; k < 66; k++) { wait_free(); if (k < 64) put(&mp.wo, k, nb * 2); }
#pragma unroll 1
      for (int k = 0; k < 18; k++) {
        const int u = k >= 2 ? k - 2 : k, kt = KC(u);
        const bool ea = (k & ~1) == 2;
        wait_free();
        e_expect_tma3d(sb + BR + (k & 3) * 24576, ea ? &mp.w1a : &mp.w1b, kt * 64, nb * 7 + (ea ? 3 : 0), fs, ea ? 16384 : k < 2 ? 24576 : 40960);
        step();
      }
      d = sb + BR + 49152;
#pragma unroll 1
      for (int k = 2; k < 32; k++) {
        const int kt = k < 16 ? KC(k) : k & 15;
        stage_free();
        if (k == 2 || k == 9) n++;
        if (k != 7 && k != 8) wait_free();
        align();
        put(&mp.w1a, kt, nb * 7 + 3 + (k >> 4) * 2);
      }
#pragma unroll 1
      for (int c = 0; c < 5; c++)
#pragma unroll 1
        for (int k = K3(c), i = 0; k < 56; k += c < 2 && (i ^= 1) ? 1 : c < 2 ? 6 : 7) { stage_free(); wait_free(); align(); put(&mp.w2, k, nb * 2); }
    } else if (pw == 1) {
      FTP(5);
      if (fin < 128) wait_cnt(&g_fin, 128);
      FTP(6);
      uint32_t d = sb;
      auto put = [&](const uint4* A, bool ld) {
        wait_free();
        if (ld) e_bulk_ld(d, A, 16384, fs);
        step();
        d += 16384;
        if (d == sb + BR) d = sb;
      };
      const uint4* A = g_O + rb * 65536;
#pragma unroll 1
      for (int k = 0; k < 68; k++) put(A + k * 1024, k < 64);
      A = Y_TILE(rb, 0);
      uint32_t ready = 0;
#pragma unroll 1
      for (int k = 2; k < 48; k++) {
        if (k == 16) k = 18;
        const int kt = k < 32 ? KC(k & 15) : k & 15;
        for (int it = 0; !(ready >> ((kt >> 1) + (kt & 1) * 8) & 1); it++) {
          ready = __ballot_sync(~0u, ldg_rlx1(cnt + (lane & 7)) & ((lane & 8) ? 1 : 0x10000));
          if (it > SPIN_LIMIT) __trap();
        }
        if (k == 2) FTP(75);
        put(A + kt * 1024, true);
      }
      A = U_TILE(rb, 0);
#pragma unroll 1
      for (int c = 0; c < 5; c++) {
        for (int it = 0; ldg_rlx1(cnt + 32 + c) < 8; it++) if (it > SPIN_LIMIT) __trap();
#pragma unroll 1
        for (int k = K3(c), i = 0; k < 56; k += c < 2 && (i ^= 1) ? 1 : c < 2 ? 6 : 7) put(A + k * 1024, true);
      }
    } else if (pw == 2) {
      for (int i = 0; i < XDL; i++) {
        mbar_wait_q(emp, i & 1);
      }
      if (lane == 0) {
        mbar_expect(xbar, 32768);
        tma2d(sb + STG, &mp.x, nb * 128, rb * 128, xbar);
        tma2d(sb + STG + 16384, &mp.x, nb * 128 + 64, rb * 128, xbar);
      }
      asm volatile("griddepcontrol.wait;" ::: "memory");
      if (lane < 16) g_modp[bid * 16 + lane] = make_uint4(0, 0, 0, 0);
      if (lane >= 16 && bid == 0) { g_hcnt = 0; g_mcnt = 0; g_hf[lane & 3] = 0; }
      if (lane == 0) {
#pragma unroll 1
        for (int g = 1; g < 9; g++) {
          if (g == 1) mbar_wait(staged + 8, 0); else { mbar_wait_q(staged + (g & 1) * 8, (g >> 1) & 1); FENCE_ASYNC_SMEM(); }
          bulk_st(g == 1 ? Y_TILE(rb, nb * 2 + 1) : U_TILE(rb, nb * 7 + ((0x652431000ull >> g * 4) & 7)), sb + STG + (g & 1) * 16384, 16384);
          BULK_COMMIT();
          if (g != 2 && g != 4) { BULK_WAIT(0); red_rlx(g == 1 ? cnt + nb : cnt + 32 + (g < 6 ? g >> 2 : g - 4)); }
          BULK_WAIT_READ(0);
          mbar_arrive(staged + 16 + (g & 1) * 8);
        }
      }
    } else {
      const uint32_t prm = sb + PRM, pp = prm + (lane >> 3) * 64 + (lane & 1) * 32 + (lane & 6) * 2;
      const uint2 v2 = ((const uint2*)(b2 + nb * 128))[lane];
      sts1(pp + 768, v2.x); sts1(pp + 784, v2.y);
      asm volatile("griddepcontrol.wait;" ::: "memory");
      const float4* md = (const float4*)(g_mod + nb * 128) + lane;
      { const float4 ga = md[512]; sts1(pp, pk(ga.x, ga.y)); sts1(pp + 16, pk(ga.z, ga.w)); }
      { const float4 cb = md[1024]; sts1(pp + 256, pk(1.f + cb.x, 1.f + cb.y)); sts1(pp + 272, pk(1.f + cb.z, 1.f + cb.w)); }
      { const float4 gb = md[1280]; sts1(pp + 512, pk(gb.x, gb.y)); sts1(pp + 528, pk(gb.z, gb.w)); }
#pragma unroll 1
      for (int i = lane; i < 112; i += 32) { const uint4 c = g_cc[nb * 112 + i]; sts4(prm + 1024 + i * 16, c.x, c.y, c.z, c.w); }
      __syncwarp();
      if (lane == 0) {
        mbar_arrive(xbar);
        mbar_wait(staged, 0);
        bulk_st(Y_TILE(rb, nb * 2), sb + STG, 16384);
        BULK_COMMIT(); BULK_WAIT(0);
        asm volatile("red.relaxed.gpu.global.add.u32 [%0],0x10000;" ::"l"(cnt + nb) : "memory");
        mbar_arrive(staged + 16);
      }
      __syncwarp();
      mbar_wait_q(staged + 24, 0);
      mbar_wait_q(emp + 8, 1);
#pragma unroll 1
      for (int i = 0; i < 4; i++) {
        const uint4* sp = g_stat + (rb * 128 + i * 32 + lane) * 4;
        uint4 v[4];
        for (int it = 0;; it++) {
          uint32_t m = 0;
#pragma unroll
          for (int u = 0; u < 4; u++) { v[u] = ldg_rlx4(sp + u); m = max(max(m, max(v[u].x, v[u].y)), max(v[u].z, v[u].w)); }
          if (!__any_sync(~0u, m == ~0u)) break;
          if (it > SPIN_LIMIT) __trap();
        }
        float m = 0, q = 0;
#pragma unroll
        for (int u = 0; u < 4; u++) { m += F_(v[u].x) + F_(v[u].z); q += F_(v[u].y) + F_(v[u].w); }
        m *= 1.f / 1024;
        const float r = 0.5f * rsqrtf(fmaxf(q * (1.f / 1024) - m * m, 0.f) + 1e-5f);
        sts2(sb + STG + 16384 + (i * 32 + lane) * 8, U_(r), U_(-m * r));
      }
      __syncwarp();
      if (lane < 2) mbar_arrive(xbar);
    }
  } else {
    asm volatile("setmaxnreg.inc.sync.aligned.u32 " FRC ";");
    const int w = (tid >> 5) & 3, q = lane & 3;
    const uint32_t prm = sb + PRM + q * 16;
    const int row0 = wg * 64 + w * 16;
    FfnPipe p;
    p.full = full; p.emp = emp; p.ph = 0; p.aoff = wg * 8192; p.st = 0; p.sB = 2; p.prev = 0; p.leader = (tid & 127) == 0;
    FfnEpi e;
    const uint32_t stg = sb + STG + row0 * 128;
    e.st2 = stg + (lane & 15) * 128 + ((lane & 7) << 4);
    e.cc = sb + PRM + 1024 + q * 16; e.flip = 0; e.staged = staged; e.l0 = lane == 0;
    const uint32_t stw = e.st2 ^ (lane & 16);
    uint32_t x1[32];
    uint4* sp = g_stat + (rb * 128 + row0 + (lane >> 2)) * 4;
    float old[96], r0_, r1_;
    {
      float acc[64];
      p.issue<128>(acc, true); FT(8); p.next();
#pragma unroll 1
      for (int k = 1; k < 64; k++) { p.issue<128>(acc, false); FT(8 + k); p.retire(); }
      float xf[64], gf[32];
      uint32_t cb[16];
      mbar_wait(xbar, 0);
#pragma unroll
      for (int j = 0; j < 8; j++) {
        uint32_t xv[4];
        ldsm4(xv, (stw ^ ((j & 3) * 32)) + (j >> 2) * 16384);
#pragma unroll
        for (int i = 0; i < 4; i++) { xf[j * 8 + i * 2] = blo(xv[i]); xf[j * 8 + i * 2 + 1] = bhi(xv[i]); }
      }
#pragma unroll
      for (int i = 0; i < 4; i++) {
        const uint4 g = lds4(prm + i * 64), c = lds4(prm + 256 + i * 64);
        UNPK8(gf + i * 8, g);
        cb[i * 4] = c.x; cb[i * 4 + 1] = c.y; cb[i * 4 + 2] = c.z; cb[i * 4 + 3] = c.w;
      }
      acc_fence<64>(xf); acc_fence<32>(gf);
      WG_WAIT(0);
      p.release();
      acc_fence<64>(acc);
      PH(7); FT(72);
#pragma unroll
      for (int j = 0; j < 8; j++) {
        uint32_t* o = x1 + j * 4;
#pragma unroll
        for (int i = 0; i < 4; i++)
          o[i] = pk(fmaf(acc[j * 8 + i * 2], gf[j * 4 + (i & 2)], xf[j * 8 + i * 2]), fmaf(acc[j * 8 + i * 2 + 1], gf[j * 4 + (i & 2) + 1], xf[j * 8 + i * 2 + 1]));
        stsm4((stw ^ ((j & 3) * 32)) + (j >> 2) * 16384, mulbf(o[0], cb[j * 2]), mulbf(o[1], cb[j * 2]), mulbf(o[2], cb[j * 2 + 1]), mulbf(o[3], cb[j * 2 + 1]));
        if ((j & 3) == 3) { FENCE_ASYNC_SMEM(); e.flush(1); }
      }
      if (wg) BAR_SYNC(2, 128); else BAR_SYNC(3, 128);
    }
    PH(8); FT(73);
    float acc[64];
    {
      float* accC = old;
      p.sB = 0;
      p.issue<192>(accC, true, 1024 + STG); FT(80); p.next();
      p.issue<192>(accC, false, 1024 + STG + 16384); FT(81);
      FT(78);
      float s0 = 0, s1 = 0, q0 = 0, q1 = 0;
#define X1_FENCE _Pragma("unroll") for (int j = 0; j < 32; j++) asm volatile("" : "+r"(x1[j]));
      X1_FENCE
#pragma unroll
      for (int j = 0; j < 16; j++) {
        const float a = blo(x1[j * 2]), b = bhi(x1[j * 2]), c = blo(x1[j * 2 + 1]), d = bhi(x1[j * 2 + 1]);
        s0 += a + b; s1 += c + d; q0 = fmaf(a, a, fmaf(b, b, q0)); q1 = fmaf(c, c, fmaf(d, d, q1));
      }
#pragma unroll
      for (int o = 1; o < 4; o *= 2) { s0 += __shfl_xor_sync(~0u, s0, o); s1 += __shfl_xor_sync(~0u, s1, o); q0 += __shfl_xor_sync(~0u, q0, o); q1 += __shfl_xor_sync(~0u, q1, o); }
      if (q < 2) {
        uint32_t m = __float_as_uint(q ? s1 : s0), v = __float_as_uint(q ? q1 : q0);
        if (m == ~0u) m = 0x7fffffffu;
        if (v == ~0u) v = 0x7fffffffu;
        stg_rlx2((uint2*)(sp + q * 32) + nb, m, v);
      }
      X1_FENCE
      p.retire();
#pragma unroll 1
      for (int k = 0; k < 2; k++) { p.issue<128, 192>(acc, !k, 1024 + STG + k * 16384); p.retire(); }
#pragma unroll 1
      for (int k = 2; k < 15; k++) { p.issue<192>(accC, false); FT(80 + k); p.retire(); }
      p.issue<192>(accC, false); FT(95);
      mbar_wait(xbar, 1);
      const float2 u0 = lds2f(sb + STG + 16384 + (row0 + (lane >> 2)) * 8), u1 = lds2f(sb + STG + 16384 + (row0 + (lane >> 2)) * 8 + 64);
      r0_ = u0.x; e.n0 = u0.y; r1_ = u1.x; e.n1 = u1.y;
      e.c = lds2u(e.cc);
      p.retire();
      e.s0 = r0_; e.s1 = r1_;
      p.sB = 3;
    }
    PH(9);
    {
      auto pair = [&](int J, bool first, bool one, int fo) {
#pragma unroll 1
        for (int r = 0; r < 2; r++) {
          if (!(one && r)) { p.issue<128>(acc, first && !r); FT(fo + r); p.retire(); }
          acc_fence<8>(old + J * 8);
          e.half(old + J * 8, J, r);
        }
      };
#pragma unroll 1
      for (int i = 0; i < 3; i++) {
        if (i == 2) {
          e.s0 = r0_; e.s1 = r1_;
#pragma unroll
          for (int J = 8; J < 12; J++) pair(J, J == 8, false, 128 + (J - 8) * 2);
          e.cc += 512; e.c = lds2u(e.cc);
          e.s0 = e.s1 = 1.f;
        }
#pragma unroll
        for (int J = 0; J < 8; J++) pair(J, J == 0 && i == 1, !(J & 3) && !i, 96 + i * 16 + (i >> 1) * 8 + J * 2);
        if (i == 2) break;
        e.cc += i ? -768 : 256; e.c = lds2u(e.cc);
        WG_WAIT(0);
        acc_fence<64>(acc);
#pragma unroll
        for (int k = 0; k < 64; k++) old[k] = acc[k] * ((k & 2) ? r1_ : r0_);
        acc_fence<64>(old);
        e.s0 = e.s1 = 1.f;
        PH(10 + i);
      }
#pragma unroll 1
      for (int k = 24; k < 56; k++) {
        if (SKW && k == 56 - SKW && wg) BAR_SYNC(4, 256);
        p.issue<128>(acc, false); FT(128 + k);
        if (SKW && k == 55 && !wg) BAR_ARRIVE(4, 256);
        p.retire();
      }
      float xf[64], gf[32];
#pragma unroll
      for (int i = 0; i < 4; i++) {
        const uint4 g = lds4(prm + 512 + i * 64), h = lds4(prm + 768 + i * 64);
        float hf[8];
        UNPK8(gf + i * 8, g); UNPK8(hf, h);
#pragma unroll
        for (int u = 0; u < 8; u++) {
          const int c = (u >> 2) * 4 + (u & 2);
          xf[i * 16 + u * 2] = fmaf(gf[i * 8 + c], hf[c], blo(x1[i * 8 + u])); xf[i * 16 + u * 2 + 1] = fmaf(gf[i * 8 + c + 1], hf[c + 1], bhi(x1[i * 8 + u]));
        }
      }
      acc_fence<64>(xf); acc_fence<32>(gf);
      mbar_wait(staged + 24, 1);
      mbar_wait(staged + 16, 0);
      WG_WAIT(0);
      acc_fence<64>(acc);
      PH(13); FT(184);
#pragma unroll
      for (int j = 0; j < 8; j++) {
        uint32_t o[4];
#pragma unroll
        for (int i = 0; i < 4; i++)
          o[i] = pk(fmaf(acc[j * 8 + i * 2], gf[j * 4 + (i & 2)], xf[j * 8 + i * 2]), fmaf(acc[j * 8 + i * 2 + 1], gf[j * 4 + (i & 2) + 1], xf[j * 8 + i * 2 + 1]));
        stsm4((stw ^ ((j & 3) * 32)) + (j >> 2) * 16384, o[0], o[1], o[2], o[3]);
        if ((j & 3) == 3) {
          FENCE_ASYNC_SMEM();
          __syncwarp();
          if (lane == 0) { tma2d_st(&mp.out, nb * 128 + (j >> 2) * 64, rb * 128 + row0, stg + (j >> 2) * 16384); BULK_COMMIT(); }
        }
      }
      if (lane == 0) BULK_WAIT_READ(0);
      __syncwarp();
    }
  }
  PH(14); FT(185);
}

typedef CUresult (*EncFn)(CUtensorMap*, CUtensorMapDataType, cuuint32_t, void*, const cuuint64_t*, const cuuint64_t*, const cuuint32_t*,
                          const cuuint32_t*, CUtensorMapInterleave, CUtensorMapSwizzle, CUtensorMapL2promotion, CUtensorMapFloatOOBfill);
static void map2d(EncFn enc, CUtensorMap* m, const void* p, int rows, int cols, int boxRows) {
  cuuint64_t d[2] = {(cuuint64_t)cols, (cuuint64_t)rows}, s[1] = {(cuuint64_t)cols * 2};
  cuuint32_t b[2] = {64, (cuuint32_t)boxRows}, e[2] = {1, 1};
  enc(m, CU_TENSOR_MAP_DATA_TYPE_BFLOAT16, 2, (void*)p, d, s, b, e, CU_TENSOR_MAP_INTERLEAVE_NONE, CU_TENSOR_MAP_SWIZZLE_128B,
      CU_TENSOR_MAP_L2_PROMOTION_L2_128B, CU_TENSOR_MAP_FLOAT_OOB_FILL_NONE);
}
static void map3d(EncFn enc, CUtensorMap* m, const void* p, int rows, int cols, int nch) {
  cuuint64_t d[3] = {64, (cuuint64_t)rows, (cuuint64_t)(cols / 64)}, s[2] = {(cuuint64_t)cols * 2, 128};
  cuuint32_t b[3] = {64, 64, (cuuint32_t)nch}, e[3] = {1, 1, 1};
  enc(m, CU_TENSOR_MAP_DATA_TYPE_BFLOAT16, 3, (void*)p, d, s, b, e, CU_TENSOR_MAP_INTERLEAVE_NONE, CU_TENSOR_MAP_SWIZZLE_128B,
      CU_TENSOR_MAP_L2_PROMOTION_L2_128B, CU_TENSOR_MAP_FLOAT_OOB_FILL_NONE);
}

extern "C" void kernel_launch(void* const* d_in, const int* in_sizes, int n_in, void* d_out, int out_size) {
  const bf16* x = (const bf16*)d_in[0];
  const bf16* mem0 = (const bf16*)d_in[1];
  void* fn = nullptr;
  cudaDriverEntryPointQueryResult qr;
  cudaGetDriverEntryPoint("cuTensorMapEncodeTiled", &fn, cudaEnableDefault, &qr);
  EncFn enc = (EncFn)fn;
  FfnMaps fm = {};
  map3d(enc, &fm.wo, d_in[5], 4096, 1024, 2);
  map3d(enc, &fm.w1a, d_in[8], 1024, 3584, 2);
  map3d(enc, &fm.w1b, d_in[8], 1024, 3584, 3);
  map3d(enc, &fm.w2, d_in[10], 3584, 1024, 2);
  map2d(enc, &fm.x, x, 2048, 1024, 128);
  map2d(enc, &fm.out, d_out, 2048, 1024, 16);
  RecMaps rm = {};
  map2d(enc, &rm.wq, d_in[2], 1024, 4096, 128);
  map2d(enc, &rm.wk, d_in[3], 1024, 4096, 128);
  map2d(enc, &rm.wv, d_in[4], 1024, 4096, 16);
  map2d(enc, &rm.wo, d_in[5], 4096, 1024, 128);
  char* xc = nullptr;
  cudaGetSymbolAddress((void**)&xc, g_xc);
  xc += (0 - (uintptr_t)xc) & 0x1FFFFF;
  {
    cuuint64_t d[3] = {512, 6, 128}, sd[2] = {131072, 1024};
    cuuint32_t bi[3] = {64, 5, 8}, e[3] = {1, 1, 1};
    enc(&rm.ari, CU_TENSOR_MAP_DATA_TYPE_BFLOAT16, 3, xc + AR_OFF, d, sd, bi, e, CU_TENSOR_MAP_INTERLEAVE_NONE, CU_TENSOR_MAP_SWIZZLE_NONE,
        CU_TENSOR_MAP_L2_PROMOTION_NONE, CU_TENSOR_MAP_FLOAT_OOB_FILL_NONE);
  }
  cudaFuncSetAttribute(k_ffn, cudaFuncAttributeMaxDynamicSharedMemorySize, ffn::SMEM);
  cudaFuncSetAttribute(k_rec, cudaFuncAttributeMaxDynamicSharedMemorySize, rec::SMEM);
  cudaStream_t st = cudaStreamPerThread;
  int dF = 450, dA = 2700, dS = 300, dM = 120, dG = 350, dP = 24, dX = 48, dD = 350, dZ = 0, dZ2 = 1, dV = 370, dX2 = 0;
  k_rec<<<132, 512, rec::SMEM, st>>>(rm, mem0, x, (const bf16*)d_in[12], (const bf16*)d_in[13], (const char*)d_in[8], (const bf16*)d_in[9],
                                     (const char*)d_in[5], xc, dF, dA, dS, dM, dG, dP, dX, dD, dZ, dZ2, dV, dX2);
  cudaLaunchConfig_t cfg = {};
  cfg.gridDim = dim3(132); cfg.blockDim = dim3(384); cfg.dynamicSmemBytes = ffn::SMEM; cfg.stream = st;
  cudaLaunchAttribute at[1];
  at[0].id = cudaLaunchAttributeProgrammaticStreamSerialization;
  at[0].val.programmaticStreamSerializationAllowed = 1;
  cfg.attrs = at; cfg.numAttrs = 1;
  cudaLaunchKernelEx(&cfg, k_ffn, fm, (const bf16*)d_in[11]);
}
```

```cpp
#include <cuda_runtime.h>
#include <cuda.h>
#include <cuda_bf16.h>
#include <stdint.h>

typedef __nv_bfloat16 bf16;

__device__ __align__(16) float g_mod[6144];
__device__ __align__(1024) uint4 g_modp[4 * 512];
__device__ unsigned g_hcnt;
__device__ unsigned g_hf[4];
__device__ __align__(1024) uint4 g_h[2048 * 1024 / 8];
__device__ __align__(1024) uint4 g_O[2048 * 4096 / 8];
__device__ __align__(1024) uint4 g_h2[2048 * 1024 / 8];
__device__ __align__(1024) uint4 g_U[2048 * 3584 / 8];
__device__ __align__(1024) uint4 g_stat[2048 * 4];
__device__ __align__(1024) unsigned g_cnt[16 * 4 * 32];
__device__ unsigned g_mcnt;
__device__ unsigned g_slot[256];
__device__ unsigned g_fin;
__device__ __align__(16) uint4 g_cc[224 * 4];
__device__ __align__(1024) uint4 g_xc[44 * 16384];
__device__ __align__(1024) unsigned g_tm[4 * 256];
#define FT(i)
#define FTP(i)
#define PT(i)
#define PH(i)
#define RS(i)
#define RP(i)
#define RPN(i, s)
#define TSV(i, v)
#define TS(i)

#define FRC "232"
#define FRP "40"
#define FMAP (((g >> 2) * 4 + m) * 8 + ((g & 3) ^ ((g & 4) ? 3 : 0)) * 2 + (blockIdx.x & 1))
#define ALIAS 3
#define PFT 150000
#define PFS 104
#define PF0 13000
#define PFD 128
#define NF 3
#define NB0 4
#define PV0 4
#define T1L 1
#define NW0 5
#define VRF 3
#define VPC 1
#define WC0 10
#define WPE 2
#define ALN 0x80
#define SKW 3
#define L62 200
#define DLY(k)
#define UNC 0
#define XDL 6
#define PDS 61
#define P_NVR 5
#define P_NWP 9
#define P_NW1 7
#define RF_ 208
#define RA_ (488 - 2 * RF_)
#define WCH 2
#define NOP_ 2
#define SPIN_LIMIT (1 << 20)
__device__ __forceinline__ uint64_t mkdesc(uint32_t addr, uint32_t lbo, uint32_t sbo) {
  return (uint64_t)((addr & 0x3FFFF) >> 4) | ((uint64_t)(lbo >> 4) << 16) | ((uint64_t)(sbo >> 4) << 32) | (1ull << 62);
}
__device__ __forceinline__ void mbar_init(uint32_t a, int c) { asm volatile("mbarrier.init.shared.b64 [%0],%1;" ::"r"(a), "r"(c) : "memory"); }
__device__ __forceinline__ void mbar_wait(uint32_t a, uint32_t par) {
  asm volatile(
      "{.reg .pred p; .reg .u32 n;\n"
      "mov.u32 n, 0;\n"
      "W: mbarrier.try_wait.parity.shared.b64 p,[%0],%1;\n"
      "@p bra D;\n"
      "add.u32 n, n, 1;\n"
      "setp.lt.u32 p, n, %2;\n"
      "@p bra W;\n"
      "trap;\n"
      "D:}" ::"r"(a), "r"(par), "n"(SPIN_LIMIT) : "memory");
}
__device__ __forceinline__ void mbar_wait_q(uint32_t a, uint32_t par) {
  asm volatile(
      "{.reg .pred p; .reg .u32 n;\n"
      "mov.u32 n, 0;\n"
      "W: mbarrier.try_wait.parity.shared.b64 p,[%0],%1,4000;\n"
      "@p bra D;\n"
      "add.u32 n, n, 1;\n"
      "setp.lt.u32 p, n, %2;\n"
      "@p bra W;\n"
      "trap;\n"
      "D:}" ::"r"(a), "r"(par), "n"(SPIN_LIMIT / 16) : "memory");
}
__device__ __forceinline__ void mbar_expect(uint32_t a, uint32_t b) { asm volatile("mbarrier.arrive.expect_tx.shared.b64 _,[%0],%1;" ::"r"(a), "r"(b) : "memory"); }
__device__ __forceinline__ void mbar_arrive(uint32_t a) { asm volatile("mbarrier.arrive.shared.b64 _,[%0];" ::"r"(a) : "memory"); }
__device__ __forceinline__ uint32_t mapa(uint32_t a, uint32_t cta) { uint32_t r; asm("mapa.shared::cluster.u32 %0,%1,%2;" : "=r"(r) : "r"(a), "r"(cta)); return r; }
__device__ __forceinline__ void mbar_arrive_cl(uint32_t a) { asm volatile("mbarrier.arrive.shared::cluster.b64 _,[%0];" ::"r"(a) : "memory"); }
__device__ __forceinline__ void tma2d(uint32_t dst, const CUtensorMap* m, int c0, int c1, uint32_t mb) {
  asm volatile("cp.async.bulk.tensor.2d.shared::cluster.global.mbarrier::complete_tx::bytes [%0],[%1,{%2,%3}],[%4];" ::"r"(dst), "l"(m), "r"(c0), "r"(c1), "r"(mb) : "memory");
}
__device__ __forceinline__ void tma2d_pf(const CUtensorMap* m, int c0, int c1) {
  asm volatile("cp.async.bulk.prefetch.tensor.2d.L2.global [%0,{%1,%2}];" ::"l"(m), "r"(c0), "r"(c1) : "memory");
}
__device__ __forceinline__ void tma2d_st(const CUtensorMap* m, int c0, int c1, uint32_t src) {
  asm volatile("cp.async.bulk.tensor.2d.global.shared::cta.bulk_group [%0,{%1,%2}],[%3];" ::"l"(m), "r"(c0), "r"(c1), "r"(src) : "memory");
}
__device__ __forceinline__ void bulk_ld(uint32_t dst, const void* src, uint32_t n, uint32_t mb) {
  asm volatile("cp.async.bulk.shared::cluster.global.mbarrier::complete_tx::bytes [%0],[%1],%2,[%3];" ::"r"(dst), "l"(src), "r"(n), "r"(mb) : "memory");
}
__device__ __forceinline__ void bulk_st(void* dst, uint32_t src, uint32_t n) {
  asm volatile("cp.async.bulk.global.shared::cta.bulk_group [%0],[%1],%2;" ::"l"(dst), "r"(src), "r"(n) : "memory");
}
__device__ __forceinline__ void e_expect_tma3d(uint32_t dst, const CUtensorMap* m, int c1, int c2, uint32_t mb, uint32_t bytes) {
  asm volatile("{.reg .pred p; elect.sync _|p, 0xffffffff; @p mbarrier.arrive.expect_tx.shared.b64 _,[%4],%5;\n"
               "@p cp.async.bulk.tensor.3d.shared::cluster.global.mbarrier::complete_tx::bytes [%0],[%1,{0,%2,%3}],[%4];}" ::"r"(dst), "l"(m), "r"(c1), "r"(c2), "r"(mb), "r"(bytes) : "memory");
}
__device__ __forceinline__ void e_bulk_ld(uint32_t dst, const void* src, uint32_t n, uint32_t mb) {
  asm volatile("{.reg .pred p; elect.sync _|p, 0xffffffff; @p cp.async.bulk.shared::cluster.global.mbarrier::complete_tx::bytes [%0],[%1],%2,[%3];}" ::"r"(dst), "l"(src), "r"(n), "r"(mb) : "memory");
}
#define BULK_COMMIT() asm volatile("cp.async.bulk.commit_group;" ::: "memory")
#define BULK_WAIT_READ(n) asm volatile("cp.async.bulk.wait_group.read " #n ";" ::: "memory")
#define BULK_WAIT(n) asm volatile("cp.async.bulk.wait_group " #n ";" ::: "memory")
#define FENCE_ASYNC_SMEM() asm volatile("fence.proxy.async.shared::cta;" ::: "memory")
#define FENCE_ASYNC() asm volatile("fence.proxy.async;" ::: "memory")
#define WG_FENCE() asm volatile("wgmma.fence.sync.aligned;" ::: "memory")
#define WG_COMMIT() asm volatile("wgmma.commit_group.sync.aligned;" ::: "memory")
#define WG_WAIT(n) asm volatile("wgmma.wait_group.sync.aligned " #n ";" ::: "memory")
#define BAR_SYNC(id, n) asm volatile("bar.sync %0,%1;" ::"n"(id), "n"(n) : "memory")
#define BAR_ARRIVE(id, n) asm volatile("bar.arrive %0,%1;" ::"n"(id), "n"(n) : "memory")
#define SCHED_FENCE(k) asm volatile("{.reg .pred p; setp.ne.u32 p,%0,0; @p trap;}" ::"r"(mp.zero[(k) - 46]) : "memory")
#define CLUSTER_SYNC() asm volatile("barrier.cluster.arrive.relaxed.aligned; barrier.cluster.wait.aligned;" ::: "memory")
__device__ __forceinline__ uint32_t pk(float lo, float hi) { uint32_t r; asm("cvt.rn.bf16x2.f32 %0,%1,%2;" : "=r"(r) : "f"(hi), "f"(lo)); return r; }
__device__ __forceinline__ float blo(uint32_t v) { return __uint_as_float(v << 16); }
__device__ __forceinline__ float bhi(uint32_t v) { return __uint_as_float(v & 0xffff0000u); }
__device__ __forceinline__ void ldsm4(uint32_t* r, uint32_t a) {
  asm volatile("ldmatrix.sync.aligned.m8n8.x4.shared.b16 {%0,%1,%2,%3},[%4];" : "=r"(r[0]), "=r"(r[1]), "=r"(r[2]), "=r"(r[3]) : "r"(a) : "memory");
}
__device__ __forceinline__ void ldsm4t(uint32_t* r, uint32_t a) {
  asm volatile("ldmatrix.sync.aligned.m8n8.x4.trans.shared.b16 {%0,%1,%2,%3},[%4];" : "=r"(r[0]), "=r"(r[1]), "=r"(r[2]), "=r"(r[3]) : "r"(a) : "memory");
}
__device__ __forceinline__ void stsm4(uint32_t a, uint32_t r0, uint32_t r1, uint32_t r2, uint32_t r3) {
  asm volatile("stmatrix.sync.aligned.m8n8.x4.shared.b16 [%0],{%1,%2,%3,%4};" ::"r"(a), "r"(r0), "r"(r1), "r"(r2), "r"(r3) : "memory");
}
__device__ __forceinline__ void mma16(float* d, uint32_t a0, uint32_t a1, uint32_t a2, uint32_t a3, uint32_t b0, uint32_t b1) {
  asm volatile("mma.sync.aligned.m16n8k16.row.col.f32.bf16.bf16.f32 {%0,%1,%2,%3},{%4,%5,%6,%7},{%8,%9},{%0,%1,%2,%3};"
               : "+f"(d[0]), "+f"(d[1]), "+f"(d[2]), "+f"(d[3]) : "r"(a0), "r"(a1), "r"(a2), "r"(a3), "r"(b0), "r"(b1));
}
__device__ __forceinline__ void mma8(float* d, uint32_t a0, uint32_t a1, uint32_t b0) {
  asm volatile("mma.sync.aligned.m16n8k8.row.col.f32.bf16.bf16.f32 {%0,%1,%2,%3},{%4,%5},{%6},{%0,%1,%2,%3};"
               : "+f"(d[0]), "+f"(d[1]), "+f"(d[2]), "+f"(d[3]) : "r"(a0), "r"(a1), "r"(b0));
}
__device__ __forceinline__ float4 lds4f(uint32_t a) { float4 v; asm volatile("ld.shared.v4.f32 {%0,%1,%2,%3},[%4];" : "=f"(v.x), "=f"(v.y), "=f"(v.z), "=f"(v.w) : "r"(a) : "memory"); return v; }
__device__ __forceinline__ float2 lds2f(uint32_t a) { float2 v; asm volatile("ld.shared.v2.f32 {%0,%1},[%2];" : "=f"(v.x), "=f"(v.y) : "r"(a) : "memory"); return v; }
__device__ __forceinline__ uint4 lds4(uint32_t a) { uint4 v; asm volatile("ld.shared.v4.u32 {%0,%1,%2,%3},[%4];" : "=r"(v.x), "=r"(v.y), "=r"(v.z), "=r"(v.w) : "r"(a) : "memory"); return v; }
__device__ __forceinline__ uint2 lds2u(uint32_t a) { uint2 v; asm volatile("ld.shared.v2.u32 {%0,%1},[%2];" : "=r"(v.x), "=r"(v.y) : "r"(a) : "memory"); return v; }
__device__ __forceinline__ uint32_t lds1(uint32_t a) { uint32_t v; asm volatile("ld.shared.u32 %0,[%1];" : "=r"(v) : "r"(a) : "memory"); return v; }
__device__ __forceinline__ void sts4(uint32_t a, uint32_t x, uint32_t y, uint32_t z, uint32_t w) { asm volatile("st.shared.v4.u32 [%0],{%1,%2,%3,%4};" ::"r"(a), "r"(x), "r"(y), "r"(z), "r"(w) : "memory"); }
__device__ __forceinline__ void sts2(uint32_t a, uint32_t x, uint32_t y) { asm volatile("st.shared.v2.u32 [%0],{%1,%2};" ::"r"(a), "r"(x), "r"(y) : "memory"); }
__device__ __forceinline__ void sts1(uint32_t a, uint32_t x) { asm volatile("st.shared.u32 [%0],%1;" ::"r"(a), "r"(x) : "memory"); }
__device__ __forceinline__ void sta4(uint32_t a, const uint32_t* v, uint32_t mb) {
  asm volatile("st.async.shared::cluster.mbarrier::complete_tx::bytes.v4.b32 [%0],{%1,%2,%3,%4},[%5];" ::"r"(a), "r"(v[0]), "r"(v[1]), "r"(v[2]), "r"(v[3]), "r"(mb) : "memory");
}
__device__ __forceinline__ uint4 ldg_rlx4(const void* p) { uint4 v; asm volatile("ld.relaxed.gpu.global.v4.u32 {%0,%1,%2,%3},[%4];" : "=r"(v.x), "=r"(v.y), "=r"(v.z), "=r"(v.w) : "l"(p) : "memory"); return v; }
__device__ __forceinline__ uint32_t ldg_rlx1(const void* p) { uint32_t v; asm volatile("ld.relaxed.gpu.global.u32 %0,[%1];" : "=r"(v) : "l"(p) : "memory"); return v; }
__device__ __forceinline__ uint4 ldg_b128(const void* p) {
  uint4 v;
  asm volatile("{.reg .b128 t; .reg .b64 a,b; ld.relaxed.gpu.global.b128 t,[%4]; mov.b128 {a,b},t; mov.b64 {%0,%1},a; mov.b64 {%2,%3},b;}" : "=r"(v.x), "=r"(v.y), "=r"(v.z), "=r"(v.w) : "l"(p) : "memory");
  return v;
}
__device__ __forceinline__ void stg_b128(void* p, uint32_t x, uint32_t y, uint32_t z, uint32_t w) {
  asm volatile("{.reg .b128 t; .reg .b64 a,b; mov.b64 a,{%1,%2}; mov.b64 b,{%3,%4}; mov.b128 t,{a,b}; st.relaxed.gpu.global.b128 [%0],t;}" ::"l"(p), "r"(x), "r"(y), "r"(z), "r"(w) : "memory");
}
__device__ __forceinline__ void stg_rlx2(void* p, uint32_t x, uint32_t y) { asm volatile("st.relaxed.gpu.global.v2.u32 [%0],{%1,%2};" ::"l"(p), "r"(x), "r"(y) : "memory"); }
__device__ __forceinline__ unsigned ld_acq(const unsigned* p) { unsigned v; asm volatile("ld.acquire.gpu.global.u32 %0,[%1];" : "=r"(v) : "l"(p) : "memory"); return v; }
__device__ __forceinline__ void red_rel(unsigned* p) { asm volatile("red.release.gpu.global.add.u32 [%0],1;" ::"l"(p) : "memory"); }
__device__ __forceinline__ void red_rlx(unsigned* p) { asm volatile("red.relaxed.gpu.global.add.u32 [%0],1;" ::"l"(p) : "memory"); }
__device__ __forceinline__ void wait_cnt(const unsigned* p, unsigned n) { int it = 0; while (ld_acq(p) < n) { if (++it > SPIN_LIMIT) __trap(); } }
__device__ __forceinline__ uint32_t clk() { uint32_t c; asm volatile("mov.u32 %0,%%clock;" : "=r"(c)); return c; }
__device__ __forceinline__ uint32_t gtime() { uint32_t c; asm volatile("mov.u32 %0,%%globaltimer_lo;" : "=r"(c)); return c; }
__device__ __forceinline__ float ex2(float x) { float r; asm("ex2.approx.ftz.f32 %0,%1;" : "=f"(r) : "f"(x)); return r; }
__device__ __forceinline__ float silu(float x) { return x * __frcp_rn(1.f + __expf(-x)); }
__device__ __forceinline__ float rbf(float x) { return __bfloat162float(__float2bfloat16_rn(x)); }

__device__ __forceinline__ void wgmma_ss_n128(float* d, uint64_t a, uint64_t b, int sd) {
  asm volatile("{.reg .pred p; setp.ne.b32 p, %66, 0;\n"
    "wgmma.mma_async.sync.aligned.m64n128k16.f32.bf16.bf16 {%0,%1,%2,%3,%4,%5,%6,%7,%8,%9,%10,%11,%12,%13,%14,%15,%16,%17,%18,%19,%20,%21,%22,%23,%24,%25,%26,%27,%28,%29,%30,%31,%32,%33,%34,%35,%36,%37,%38,%39,%40,%41,%42,%43,%44,%45,%46,%47,%48,%49,%50,%51,%52,%53,%54,%55,%56,%57,%58,%59,%60,%61,%62,%63}, %64, %65, p, 1, 1, 0, 1;}\n"
    : "+f"(d[0]),"+f"(d[1]),"+f"(d[2]),"+f"(d[3]),"+f"(d[4]),"+f"(d[5]),"+f"(d[6]),"+f"(d[7]),
      "+f"(d[8]),"+f"(d[9]),"+f"(d[10]),"+f"(d[11]),"+f"(d[12]),"+f"(d[13]),"+f"(d[14]),"+f"(d[15]),
      "+f"(d[16]),"+f"(d[17]),"+f"(d[18]),"+f"(d[19]),"+f"(d[20]),"+f"(d[21]),"+f"(d[22]),"+f"(d[23]),
      "+f"(d[24]),"+f"(d[25]),"+f"(d[26]),"+f"(d[27]),"+f"(d[28]),"+f"(d[29]),"+f"(d[30]),"+f"(d[31]),
      "+f"(d[32]),"+f"(d[33]),"+f"(d[34]),"+f"(d[35]),"+f"(d[36]),"+f"(d[37]),"+f"(d[38]),"+f"(d[39]),
      "+f"(d[40]),"+f"(d[41]),"+f"(d[42]),"+f"(d[43]),"+f"(d[44]),"+f"(d[45]),"+f"(d[46]),"+f"(d[47]),
      "+f"(d[48]),"+f"(d[49]),"+f"(d[50]),"+f"(d[51]),"+f"(d[52]),"+f"(d[53]),"+f"(d[54]),"+f"(d[55]),
      "+f"(d[56]),"+f"(d[57]),"+f"(d[58]),"+f"(d[59]),"+f"(d[60]),"+f"(d[61]),"+f"(d[62]),"+f"(d[63])
    : "l"(a), "l"(b), "r"(sd));
}
__device__ __forceinline__ void wgmma_ss_n192(float* d, uint64_t a, uint64_t b, int sd) {
  asm volatile("{.reg .pred p; setp.ne.b32 p, %98, 0;\n"
    "wgmma.mma_async.sync.aligned.m64n192k16.f32.bf16.bf16 {%0,%1,%2,%3,%4,%5,%6,%7,%8,%9,%10,%11,%12,%13,%14,%15,%16,%17,%18,%19,%20,%21,%22,%23,%24,%25,%26,%27,%28,%29,%30,%31,%32,%33,%34,%35,%36,%37,%38,%39,%40,%41,%42,%43,%44,%45,%46,%47,%48,%49,%50,%51,%52,%53,%54,%55,%56,%57,%58,%59,%60,%61,%62,%63,%64,%65,%66,%67,%68,%69,%70,%71,%72,%73,%74,%75,%76,%77,%78,%79,%80,%81,%82,%83,%84,%85,%86,%87,%88,%89,%90,%91,%92,%93,%94,%95}, %96, %97, p, 1, 1, 0, 1;}\n"
    : "+f"(d[0]),"+f"(d[1]),"+f"(d[2]),"+f"(d[3]),"+f"(d[4]),"+f"(d[5]),"+f"(d[6]),"+f"(d[7]),
      "+f"(d[8]),"+f"(d[9]),"+f"(d[10]),"+f"(d[11]),"+f"(d[12]),"+f"(d[13]),"+f"(d[14]),"+f"(d[15]),
      "+f"(d[16]),"+f"(d[17]),"+f"(d[18]),"+f"(d[19]),"+f"(d[20]),"+f"(d[21]),"+f"(d[22]),"+f"(d[23]),
      "+f"(d[24]),"+f"(d[25]),"+f"(d[26]),"+f"(d[27]),"+f"(d[28]),"+f"(d[29]),"+f"(d[30]),"+f"(d[31]),
      "+f"(d[32]),"+f"(d[33]),"+f"(d[34]),"+f"(d[35]),"+f"(d[36]),"+f"(d[37]),"+f"(d[38]),"+f"(d[39]),
      "+f"(d[40]),"+f"(d[41]),"+f"(d[42]),"+f"(d[43]),"+f"(d[44]),"+f"(d[45]),"+f"(d[46]),"+f"(d[47]),
      "+f"(d[48]),"+f"(d[49]),"+f"(d[50]),"+f"(d[51]),"+f"(d[52]),"+f"(d[53]),"+f"(d[54]),"+f"(d[55]),
      "+f"(d[56]),"+f"(d[57]),"+f"(d[58]),"+f"(d[59]),"+f"(d[60]),"+f"(d[61]),"+f"(d[62]),"+f"(d[63]),
      "+f"(d[64]),"+f"(d[65]),"+f"(d[66]),"+f"(d[67]),"+f"(d[68]),"+f"(d[69]),"+f"(d[70]),"+f"(d[71]),
      "+f"(d[72]),"+f"(d[73]),"+f"(d[74]),"+f"(d[75]),"+f"(d[76]),"+f"(d[77]),"+f"(d[78]),"+f"(d[79]),
      "+f"(d[80]),"+f"(d[81]),"+f"(d[82]),"+f"(d[83]),"+f"(d[84]),"+f"(d[85]),"+f"(d[86]),"+f"(d[87]),
      "+f"(d[88]),"+f"(d[89]),"+f"(d[90]),"+f"(d[91]),"+f"(d[92]),"+f"(d[93]),"+f"(d[94]),"+f"(d[95])
    : "l"(a), "l"(b), "r"(sd));
}
__device__ __forceinline__ void wgmma_rs_n32(float* d, const uint32_t* a, uint64_t b, int sd) {
  asm volatile("{.reg .pred p; setp.ne.b32 p, %21, 0;\n"
    "wgmma.mma_async.sync.aligned.m64n32k16.f32.bf16.bf16 {%0,%1,%2,%3,%4,%5,%6,%7,%8,%9,%10,%11,%12,%13,%14,%15}, {%16,%17,%18,%19}, %20, p, 1, 1, 0;}\n"
    : "+f"(d[0]),"+f"(d[1]),"+f"(d[2]),"+f"(d[3]),"+f"(d[4]),"+f"(d[5]),"+f"(d[6]),"+f"(d[7]),
      "+f"(d[8]),"+f"(d[9]),"+f"(d[10]),"+f"(d[11]),"+f"(d[12]),"+f"(d[13]),"+f"(d[14]),"+f"(d[15])
    : "r"(a[0]), "r"(a[1]), "r"(a[2]), "r"(a[3]), "l"(b), "r"(sd));
}
__device__ __forceinline__ void wgmma_ssT_n32(float* d, uint64_t a, uint64_t b, int sd) {
  asm volatile("{.reg .pred p; setp.ne.b32 p, %18, 0;\n"
    "wgmma.mma_async.sync.aligned.m64n32k16.f32.bf16.bf16 {%0,%1,%2,%3,%4,%5,%6,%7,%8,%9,%10,%11,%12,%13,%14,%15}, %16, %17, p, 1, 1, 1, 0;}\n"
    : "+f"(d[0]),"+f"(d[1]),"+f"(d[2]),"+f"(d[3]),"+f"(d[4]),"+f"(d[5]),"+f"(d[6]),"+f"(d[7]),
      "+f"(d[8]),"+f"(d[9]),"+f"(d[10]),"+f"(d[11]),"+f"(d[12]),"+f"(d[13]),"+f"(d[14]),"+f"(d[15])
    : "l"(a), "l"(b), "r"(sd));
}

__device__ __forceinline__ void wgmma_rs_n32_z(float* d, const uint32_t* a, uint64_t b) {
  asm volatile("{.reg .pred p; setp.ne.b32 p, 0, 0;\n"
    "wgmma.mma_async.sync.aligned.m64n32k16.f32.bf16.bf16 {%0,%1,%2,%3,%4,%5,%6,%7,%8,%9,%10,%11,%12,%13,%14,%15}, {%16,%17,%18,%19}, %20, p, 1, 1, 0;}\n"
    : "=f"(d[0]),"=f"(d[1]),"=f"(d[2]),"=f"(d[3]),"=f"(d[4]),"=f"(d[5]),"=f"(d[6]),"=f"(d[7]),
      "=f"(d[8]),"=f"(d[9]),"=f"(d[10]),"=f"(d[11]),"=f"(d[12]),"=f"(d[13]),"=f"(d[14]),"=f"(d[15])
    : "r"(a[0]), "r"(a[1]), "r"(a[2]), "r"(a[3]), "l"(b));
}

namespace rec {
constexpr int NVR = P_NVR;
constexpr int NVS = 16 - NVR;
constexpr int NWP = P_NWP;
constexpr uint32_t WO = 0;
constexpr uint32_t XB = 65536;
constexpr uint32_t PK = XB + 32768;
constexpr uint32_t VN = PK + 24576;
constexpr uint32_t VX0 = VN + 4096;
constexpr uint32_t WVS = 131072;
constexpr uint32_t MEM = WVS + 2 * NVS * 2048;
constexpr uint32_t ARO = MEM + 10240;
constexpr uint32_t OB = ARO + 5120;
constexpr uint32_t QT = OB + 2048;
constexpr uint32_t KT = QT + 2048;
constexpr uint32_t RQ = KT + 6144;
constexpr uint32_t RK = RQ + 2048;
constexpr uint32_t SC = RK + 2048;
constexpr uint32_t OT = OB;
constexpr uint32_t TF = SC + 2048;
constexpr uint32_t PRE = MEM + 2 * NVR * 2048;
constexpr uint32_t TA = TF + 8192;
constexpr uint32_t RX = TA + 6144;
constexpr uint32_t VX1 = RX + 2048;
constexpr uint32_t BARS = VX1 + 4096;
constexpr uint32_t PACE = BARS + 18 * 8;
constexpr uint32_t SMEM = BARS + 512;
static_assert(PRE + 14336 <= BARS, "staging");
constexpr int NW1 = P_NW1;
static_assert(SMEM <= 232448, "smem");
constexpr int B_E = 2, B_SC = 3, B_S = 4, B_O = 5, B_F = 6, B_W = 7, B_C = 9, B_K = 10, B_Q = 1, B_S2 = 6, B_T2 = 9, B_P = 13, B_T = 14, B_R = 11, B_X = 12, B_V = 8;
constexpr int XC = 16384, X_RING = 131072, X_SC = 65536, X_TOK = 4096;
#define X_VX(i) (((i) >> 1) * 2048 + ((i) & 1) * 512)
#define X_VM(i) (X_VX(i) + 1024)
#define V_RING(n) (((n) & 1) * X_RING + ((n) & 2) * 2048)
#define V_TAG(n) ((~(n) >> 2) & 1)
}
struct RecMaps { CUtensorMap wq, wk, wv, wo, ari; int zero[40]; };

#define F_(x) __uint_as_float(x)
#define U_(x) __float_as_uint(x)
#define AR_R(q) (24 + ((q) & 1) * 16 + ((q) >> 1) * 56)
#define AR_P(q) ((q) >> 1)
#define AR_ROW(i) (24 + ((i) & 1) * 16 + ((i) & 2) * 92 + (((i) >> 2) & 7) + ((i) >> 5) * 128)
constexpr size_t AR_OFF = 32 * 262144;
__device__ __forceinline__ void ar_fetch(uint32_t dst, const CUtensorMap* m, int slot, int half, uint32_t mb) {
  asm volatile("{.reg .pred p; elect.sync _|p, 0xffffffff; @p mbarrier.arrive.expect_tx.shared.b64 _,[%4],10240;\n"
               "@p cp.async.bulk.tensor.3d.shared::cluster.global.mbarrier::complete_tx::bytes [%0],[%1,{%2,%6,%3}],[%4];\n"
               "@p cp.async.bulk.tensor.3d.shared::cluster.global.mbarrier::complete_tx::bytes [%0+5120],[%1,{%2,%7,%5}],[%4];}"
               ::"r"(dst), "l"(m), "r"(slot * 64), "r"(AR_R(half * 2)), "r"(mb), "r"(AR_R(half * 2 + 1)), "r"(AR_P(half * 2)), "r"(AR_P(half * 2 + 1)) : "memory");
}
__device__ __forceinline__ uint4 exch_b128(void* p, uint32_t x, uint32_t y, uint32_t z, uint32_t w) {
  uint4 v;
  asm volatile("{.reg .b128 s, t; .reg .b64 a,b; mov.b64 a,{%5,%6}; mov.b64 b,{%7,%8}; mov.b128 s,{a,b}; atom.relaxed.gpu.global.exch.b128 t,[%4],s;"
               " mov.b128 {a,b},t; mov.b64 {%0,%1},a; mov.b64 {%2,%3},b;}" : "=r"(v.x), "=r"(v.y), "=r"(v.z), "=r"(v.w) : "l"(p), "r"(x), "r"(y), "r"(z), "r"(w) : "memory");
  return v;
}
#define CONSUME(v) do { if ((v) == 0x7fc12345u) sts1(sb + rec::BARS + 96, 0); } while (0)
__device__ __forceinline__ uint2 ldg_b64(const void* p) { uint2 v; asm volatile("{.reg .b64 t; ld.relaxed.gpu.global.b64 t,[%2]; mov.b64 {%0,%1},t;}" : "=r"(v.x), "=r"(v.y) : "l"(p) : "memory"); return v; }
__device__ __forceinline__ void stg_b64(void* p, uint32_t x, uint32_t y) { asm volatile("{.reg .b64 t; mov.b64 t,{%1,%2}; st.relaxed.gpu.global.b64 [%0],t;}" ::"l"(p), "r"(x), "r"(y) : "memory"); }
__device__ __forceinline__ uint32_t tagbad(uint32_t x, uint32_t y, uint32_t tag) { uint32_t r; asm("lop3.b32 %0,%1,%2,%3,0x7e;" : "=r"(r) : "r"(x), "r"(y), "r"(tag)); return r; }

__device__ __forceinline__ bool anybad(uint32_t a, uint32_t b, uint32_t c, uint32_t d, uint32_t e, uint32_t f, uint32_t g, uint32_t h, uint32_t tag) {
  uint32_t r;
  asm volatile("{.reg .b32 t,u,v,w; .reg .pred p; lop3.b32 t,%1,%2,%9,0x7e; lop3.b32 u,%3,%4,%9,0x7e; lop3.b32 v,%5,%6,%9,0x7e; lop3.b32 w,%7,%8,%9,0x7e;"
               " lop3.b32 t,t,u,v,0xfe; lop3.b32 t,t,w,1,0xa8; setp.ne.u32 p,t,0; vote.sync.any.pred p,p,0xffffffff; selp.u32 %0,1,0,p;}"
               : "=r"(r) : "r"(a), "r"(b), "r"(c), "r"(d), "r"(e), "r"(f), "r"(g), "r"(h), "r"(tag));
  return r;
}
__device__ __forceinline__ bool anybad(uint32_t a, uint32_t b, uint32_t c, uint32_t d, uint32_t tag) {
  uint32_t r;
  asm volatile("{.reg .b32 t,u; .reg .pred p; lop3.b32 t,%1,%2,%5,0x7e; lop3.b32 u,%3,%4,%5,0x7e;"
               " lop3.b32 t,t,u,1,0xa8; setp.ne.u32 p,t,0; vote.sync.any.pred p,p,0xffffffff; selp.u32 %0,1,0,p;}"
               : "=r"(r) : "r"(a), "r"(b), "r"(c), "r"(d), "r"(tag));
  return r;
}
#define BADS(r) anybad(r[0].x, r[0].y, r[1].x, r[1].y, r[2].x, r[2].y, r[3].x, r[3].y, tag)
constexpr float SCS = 0.08838834764831845f * 1.4426950408889634f / 16.f;
__device__ __forceinline__ uint32_t pkh(float lo, float hi, uint32_t tag) {
  uint32_t r;
  asm("{.reg .b32 t; cvt.rn.satfinite.f16x2.f32 t,%1,%2; lop3.b32 %0,t,0xfffffffe,%3,0xea;}" : "=r"(r) : "f"(hi), "f"(lo), "r"(tag));
  return r;
}
__device__ __forceinline__ uint32_t addh(uint32_t a, uint32_t b) { uint32_t r; asm("add.rn.f16x2 %0,%1,%2;" : "=r"(r) : "r"(a), "r"(b)); return r; }
__device__ __forceinline__ float hlo(uint32_t v) { float r; asm("{.reg .b16 a,b; mov.b32 {a,b},%1; cvt.f32.f16 %0,a;}" : "=f"(r) : "r"(v)); return r; }
__device__ __forceinline__ float hhi(uint32_t v) { float r; asm("{.reg .b16 a,b; mov.b32 {a,b},%1; cvt.f32.f16 %0,b;}" : "=f"(r) : "r"(v)); return r; }
__device__ __forceinline__ uint32_t ordh(uint32_t v) {
  uint32_t r;
  asm("{.reg .b32 m; prmt.b32 m,%1,0,0xbb99; lop3.b32 %0,%1,m,0x7fff7fff,0x78;}" : "=r"(r) : "r"(v));
  return r;
}
template <bool MASK>
__device__ __forceinline__ float4 softmax2(const uint2 (&r)[4], uint32_t mx, uint32_t my, uint32_t& k) {
  uint32_t x = addh(addh(r[0].x, r[1].x), addh(r[2].x, r[3].x)), y = addh(addh(r[0].y, r[1].y), addh(r[2].y, r[3].y));
  if (MASK) { x = addh(x, mx); y = addh(y, my); }
  asm("max.f16x2 %0,%1,%2;" : "=r"(k) : "r"(x), "r"(y));
  k = ordh(k);
  const int k0 = __reduce_max_sync(~0u, (int)(k << 16)), k1 = __reduce_max_sync(~0u, (int)k);
  const float m0 = hhi(k0 ^ ((k0 >> 31) & 0x7fff0000)) * -16.f, m1 = hhi(k1 ^ ((k1 >> 31) & 0x7fff0000)) * -16.f;
  return make_float4(ex2(fmaf(hlo(x), 16.f, m0)), ex2(fmaf(hhi(x), 16.f, m1)), ex2(fmaf(hlo(y), 16.f, m0)), ex2(fmaf(hhi(y), 16.f, m1)));
}
__device__ __forceinline__ char* mkp(uint32_t lo, uint32_t hi) { uint64_t r; asm("mov.b64 %0,{%1,%2};" : "=l"(r) : "r"(lo), "r"(hi)); return (char*)r; }
#define LO(p) ((uint32_t)(uint64_t)(p))
#define HI(p) ((uint32_t)((uint64_t)(p) >> 32))
__device__ __forceinline__ uint32_t mulbf(uint32_t a, uint32_t b) { uint32_t r; asm("mul.rn.bf16x2 %0,%1,%2;" : "=r"(r) : "r"(a), "r"(b)); return r; }
__device__ __forceinline__ uint32_t fmabf(uint32_t a, uint32_t b, uint32_t c) { uint32_t r; asm("fma.rn.bf16x2 %0,%1,%2,%3;" : "=r"(r) : "r"(a), "r"(b), "r"(c)); return r; }
__device__ __forceinline__ uint32_t addbf(uint32_t a, uint32_t b) { uint32_t r; asm("add.rn.bf16x2 %0,%1,%2;" : "=r"(r) : "r"(a), "r"(b)); return r; }
__device__ __forceinline__ void pv_mem(const uint32_t (&p)[4], uint32_t pm, const uint4 (&v)[4], const uint4 (&vn)[2], uint32_t (&O)[4]) {
  float o[4][4] = {{0, 0, 0, 0}, {0, 0, 0, 0}, {0, 0, 0, 0}, {0, 0, 0, 0}};
  mma16(o[0], v[0].x, v[0].y, v[0].z, v[0].w, p[0], p[1]);
  mma16(o[1], v[2].x, v[2].y, v[2].z, v[2].w, p[0], p[1]);
  mma16(o[2], v[1].x, v[1].y, v[1].z, v[1].w, p[2], p[3]);
  mma16(o[3], v[3].x, v[3].y, v[3].z, v[3].w, p[2], p[3]);
  mma16(o[0], vn[0].x, vn[0].y, vn[0].z, vn[0].w, pm, pm);
  mma16(o[1], vn[1].x, vn[1].y, vn[1].z, vn[1].w, pm, pm);
  O[0] = pk(o[0][0] + o[2][0], o[0][1] + o[2][1]); O[1] = pk(o[0][2] + o[2][2], o[0][3] + o[2][3]);
  O[2] = pk(o[1][0] + o[3][0], o[1][1] + o[3][1]); O[3] = pk(o[1][2] + o[3][2], o[1][3] + o[3][3]);
}
__device__ __forceinline__ void pv_tok(const uint32_t (&p)[4], uint32_t pm, const uint4 (&v)[4], const uint32_t (&vm)[4], uint32_t (&O)[4]) {
  float o[2][4] = {{0, 0, 0, 0}, {0, 0, 0, 0}}, sum[4] = {0, 0, 0, 0};
  const uint32_t one = 0x3f803f80u;
  mma16(sum, one, one, one, one, p[0], p[1]);
  mma16(o[0], v[0].x, v[0].y, v[0].z, v[0].w, p[0], p[1]);
  mma16(o[1], v[2].x, v[2].y, v[2].z, v[2].w, p[0], p[1]);
  mma16(sum, one, one, one, one, p[2], p[3]);
  mma16(o[0], v[1].x, v[1].y, v[1].z, v[1].w, p[2], p[3]);
  mma16(o[1], v[3].x, v[3].y, v[3].z, v[3].w, p[2], p[3]);
  mma8(sum, one, one, pm);
  mma8(o[0], vm[0], vm[1], pm);
  mma8(o[1], vm[2], vm[3], pm);
  float i0, i1;
  asm("rcp.approx.ftz.f32 %0,%1;" : "=f"(i0) : "f"(sum[0]));
  asm("rcp.approx.ftz.f32 %0,%1;" : "=f"(i1) : "f"(sum[1]));
  O[0] = pk(o[0][0] * i0, o[0][1] * i1); O[1] = pk(o[0][2] * i0, o[0][3] * i1);
  O[2] = pk(o[1][0] * i0, o[1][1] * i1); O[3] = pk(o[1][2] * i0, o[1][3] * i1);
}
__device__ __forceinline__ uint32_t sum4bf(uint32_t a, uint32_t b, uint32_t c, uint32_t d) { return addbf(addbf(a, b), addbf(c, d)); }
template <int OFF>
__device__ __forceinline__ void sta1(uint32_t a, uint32_t v, uint32_t mb) {
  asm volatile("st.async.shared::cluster.mbarrier::complete_tx::bytes.b32 [%0+%3],%1,[%2];" ::"r"(a), "r"(v), "r"(mb), "n"(OFF) : "memory");
}

__device__ __forceinline__ void wait_time(uint32_t t) { while ((int)(gtime() - t) < 0) __nanosleep(64); }
__device__ __noinline__ void rec_prefetch(const char* wmod, const char* w1, const char* x, const char* wo) {
  const int hb = blockIdx.x - 128;
  const uint32_t t0 = gtime();
  uint32_t t = t0 + PF0;
#pragma unroll 1
  for (int job = 0; job < (PFT ? 5 : 3); job++) {
    const char* p = job == 0 ? x + (6 + hb) * 65536 : job == 1 ? wmod + hb * 12288 + 4096 : job == 2 ? w1 + hb * 7168 : job == 3 ? x + hb * 8192 : wo + (1020 + hb) * 8192;
    const int n = job == 0 ? 120 - (hb & 2) * 4 : job == 3 ? 128 : 256, d = job == 0 ? 8192 : job == 1 ? 49152 : job == 2 ? 28672 : job == 3 ? 32768 : -32768;
    if (job == 3) t = t0 + PFT;
    PT(8 + job);
#pragma unroll 1
    for (int i = 0; i < n; i++) {
      wait_time(t);
      asm volatile("cp.async.bulk.prefetch.L2.global [%0], %1;" ::"l"(p), "r"(job == 2 ? 7168 : 8192) : "memory");
      p += !job && (i & 7) == 7 ? 204800 : d;
      t += job < 3 ? PFD : PFS;
      if (job && (i & 31) == 31 && ldg_rlx1(&g_fin)) return;
    }
  }
  PT(13);
}
__device__ __noinline__ void rec_helper(uint32_t sb, const bf16* cvec, const bf16* wmod, const char* w1, const bf16* b1, uint32_t t0) {
  const int tid = threadIdx.x, hb = blockIdx.x - 128;
  PT(1);
  for (int i = tid; i < 1024; i += 256) sts1(sb + i * 8, U_(rbf(silu(__bfloat162float(cvec[i])))));
  for (int i = tid; i < 2048; i += 256) g_stat[hb * 2048 + i] = make_uint4(~0u, ~0u, ~0u, ~0u);
  for (int i = tid; i < 512; i += 256) g_cnt[hb * 512 + i] = 0;
#pragma unroll 1
  for (int job = 0; job < 2; job++) {
    wait_time(t0 + PF0 + (job ? 600 : 350) * PFD);
    BAR_SYNC(rec::B_F, 256);
    PT(2 + job * 5);
    const int n8 = job ? 112 : 128, rg = tid >= n8, cg = tid - rg * n8, pitch = job ? 448 : 768;
    const uint4* p = (const uint4*)(job ? w1 + hb * 1792 : (const char*)(wmod + 2048 + hb * 1024)) + rg * pitch + min(cg, n8 - 1);
    float a1[8] = {0, 0, 0, 0, 0, 0, 0, 0}, a2[8] = {0, 0, 0, 0, 0, 0, 0, 0};
#pragma unroll 1
    for (int r0 = rg; r0 < 1024; r0 += 32) {
      uint4 v[16];
#pragma unroll
      for (int i = 0; i < 16; i++) { v[i] = ldg_rlx4(p); p += 2 * pitch; }
#pragma unroll
      for (int i = 0; i < 16; i++) {
        const float2 f = lds2f(sb + (r0 + 2 * i) * 8);
        const float w[8] = {blo(v[i].x), bhi(v[i].x), blo(v[i].y), bhi(v[i].y), blo(v[i].z), bhi(v[i].z), blo(v[i].w), bhi(v[i].w)};
#pragma unroll
        for (int e = 0; e < 8; e++) { a1[e] += f.x * w[e]; a2[e] += f.y * w[e]; }
      }
    }
    const uint32_t rd = sb + 8192;
    if (cg < n8) {
#pragma unroll
      for (int e = 0; e < 8; e++) sts2(rd + rg * 8192 + (cg * 8 + e) * 8, U_(a1[e]), U_(a2[e]));
    }
    BAR_SYNC(rec::B_F, 256);
    if (job == 0) {
      for (int i = tid; i < 1024; i += 256) g_mod[2048 + hb * 1024 + i] = rbf(F_(lds1(rd + i * 8)) + F_(lds1(rd + 8192 + i * 8)));
      BAR_SYNC(rec::B_F, 256);
      PT(6);
      if (tid == 0) { red_rel(&g_mcnt); wait_cnt(&g_mcnt, 4); }
      BAR_SYNC(rec::B_F, 256);
      for (int i = tid; i < 1024; i += 256) sts2(sb + i * 8, U_(rbf(1.f + __ldcg(g_mod + 4096 + i))), U_(__ldcg(g_mod + 3072 + i)));
    } else {
      for (int i = tid; i < 448; i += 256) {
        const int gn = hb * 896 + i * 2;
        const uint32_t bb = *(const uint32_t*)(b1 + gn);
        const float4 u = lds4f(rd + i * 16), w = lds4f(rd + 8192 + i * 16);
        ((uint2*)g_cc)[(gn >> 4) * 8 + ((gn >> 1) & 3) * 2 + ((gn >> 3) & 1)] = make_uint2(pk(u.x + w.x, u.z + w.z), pk(0.5f * (u.y + w.y + blo(bb)), 0.5f * (u.w + w.w + bhi(bb))));
      }
      PT(4);
    }
  }
}

__global__ void __cluster_dims__(2, 1, 1) __launch_bounds__(512, 1)
k_rec(const __grid_constant__ RecMaps mp, const bf16* __restrict__ mem0, const bf16* __restrict__ x, const bf16* __restrict__ cvec,
      const bf16* __restrict__ wmod, const char* __restrict__ w1, const bf16* __restrict__ b1, const char* __restrict__ wo, char* xc, int dF, int dA, int dS, int dM, int dG, int dP, int dX, int dD, int dZ, int dZ2, int dV, int dX2) {
  using namespace rec;
  extern __shared__ __align__(1024) char smem[];
  const uint32_t sb = (uint32_t)__cvta_generic_to_shared(smem);
  if ((sb & 0x3FFFF) != 1024) __trap();
  PH(0); RS(0); if (threadIdx.x == 0) PT(0);
  if (threadIdx.x == 0) {
    int b = blockIdx.x;
    if (b >= 8 && b < 128) {
      const int t = (b >> 1) - 4, u = t - 32;
      b = 2 * (t < 32 ? 4 + (t & 16) + (t & 7) * 2 + ((t >> 3) & 1) : 36 + (u / 14) * 14 + (u % 7) * 2 + ((u / 7) & 1)) + (b & 1);
    }
    sts1(sb + rec::PACE + 24, b);
    const int c = blockIdx.x >> 1, l = c < 36 ? (c - 4) & 7 : (c - 36) % 7, m = c < 4 ? c : c < 36 ? (c - 4) >> 3 : (c - 36) / 7;
    const int g = c < 4 ? 15 : (l >> 1) * 4 + (l & 1) + (c < 36 ? 0 : 2);
    unsigned sm;
    asm("mov.u32 %0,%%smid;" : "=r"(sm));
    if (c < 64) g_slot[sm & 255] = 1 + FMAP;
  }
#define ROLE_REFRESH { asm volatile("mov.u32 %0,%%tid.x;" : "=r"(tid)); wid = __shfl_sync(~0u, tid >> 5, 0); b = __shfl_sync(~0u, lds1(sb + PACE + 24), 0); }
#define ROLE_VARS int tid; asm volatile("mov.u32 %0,%%tid.x;" : "=r"(tid)); \
    int wid = __shfl_sync(~0u, tid >> 5, 0), b = __shfl_sync(~0u, lds1(sb + PACE + 24), 0);
#define wg (wid >> 2)
#define iw (wid & 3)
#define h (b >> 2)
#define j (b & 3)
#define a (b & 1)
#define bb ((b >> 1) & 1)
  const uint32_t wbar = sb + BARS + 48, obar = wbar + 8;
  if (threadIdx.x == 256) {
    for (int i = 0; i < 18; i++) if (i != 12) mbar_init(sb + BARS + i * 8, i == 3 || i == 8 || i == 9 || i == 10 ? 2 : 1);
    for (int i = 0; i < 3; i++) mbar_init(sb + PACE + i * 8, 1);
    asm volatile("fence.mbarrier_init.release.cluster;" ::: "memory");
    FENCE_ASYNC_SMEM();
    mbar_expect(sb + BARS, 2048);
    mbar_expect(sb + BARS + 16, 4096);
    mbar_expect(sb + BARS + 32, 4096);
    mbar_expect(sb + BARS + 40, 4096);
  }
  __syncthreads();
  asm volatile("barrier.cluster.arrive.relaxed.aligned;" ::: "memory");
#define lane ((int)(l16 >> 4))
#define l16 (L16 & 0x1f0)
#define PIN(x) __shfl_xor_sync(~0u, (uint32_t)(x), 0)
#define X_LOAD(n, w, u) \
        asm volatile("{.reg .pred p; elect.sync _|p, 0xffffffff; @p mbarrier.arrive.expect_tx.shared.b64 _,[%2],8192;\n" \
                     "@p cp.async.bulk.shared::cluster.global.mbarrier::complete_tx::bytes [%0],[%1],8192,[%2];}" ::"r"(sb + XB + (w) * 16384 + (u) * 8192), \
                     "l"(g_h + (n) * 4096 + a * 2048 + (w) * 1024 + (u) * 512), "r"(sb + BARS + 64 + (w) * 8) : "memory")
#define lpub ((L16 & 0x30) * 64 + ((L16 >> 3) & 0x38))
#define lrow ((L16 & 0x70) + (((L16 >> 3) ^ L16) & 0x70 & ~((L16 >> 3) & 0x40) ? L16 & 0x180 : 512))

  const int role = __shfl_sync(~0u, threadIdx.x >> 7, 0);
  if (role < 2) {
    asm volatile("setmaxnreg.inc.sync.aligned.u32 %0;" ::"n"(RF_));
    ROLE_VARS
    uint32_t L16 = __shfl_sync(~0u, sb + (tid & 31) * 16, tid & 31);
    uint32_t wQ[16][4], wK[16][4], wV[NVR][4];
    uint32_t frag = sb + ((lane & 7) + (lane >> 4) * 8) * 128 + (((iw * 2 + ((lane >> 3) & 1)) ^ (lane & 7)) << 4);
#define QSW (a ? 0 : 64)
    {
      const bool spare = b >= 128;
      const uint32_t t0 = gtime();
      uint4 xr[16];
      int seg = spare ? b - 126 : wg;
      const int half = spare ? wg : a;
      auto x_fetch = [&]() {
        const uint4* px = (const uint4*)x + (seg * 32 + iw * 8 + (lane >> 2)) * 128 + half * 64 + (lane & 3);
#pragma unroll
        for (int i = 0; i < 16; i++) xr[i] = __ldg(px + i * 4);
      };
      if (!spare) {
        uint4 wm[8];
        const uint4* pw = (const uint4*)(wmod + (size_t)((b >> 5) * 256 + (tid >> 3)) * 6144 + (b & 31) * 64) + (tid & 7);
        const float cs = __bfloat162float(cvec[(b >> 5) * 256 + tid]);
#pragma unroll
        for (int i = 0; i < 8; i++) wm[i] = __ldcs(pw + (size_t)i * 32 * 768);
        float* sc = (float*)(smem + PRE);
        sc[tid] = rbf(silu(cs));
        PT(1);
        BAR_SYNC(B_F, 256);
        float acc[8] = {0, 0, 0, 0, 0, 0, 0, 0};
#pragma unroll
        for (int i = 0; i < 8; i++) {
          const float f = sc[i * 32 + (tid >> 3)];
          acc[0] += f * blo(wm[i].x); acc[1] += f * bhi(wm[i].x); acc[2] += f * blo(wm[i].y); acc[3] += f * bhi(wm[i].y);
          acc[4] += f * blo(wm[i].z); acc[5] += f * bhi(wm[i].z); acc[6] += f * blo(wm[i].w); acc[7] += f * bhi(wm[i].w);
        }
#pragma unroll
        for (int i = 0; i < 8; i++) { acc[i] += __shfl_xor_sync(~0u, acc[i], 8); acc[i] += __shfl_xor_sync(~0u, acc[i], 16); }
        float* red = sc + 1024;
        if ((tid & 31) < 8) {
#pragma unroll
          for (int i = 0; i < 8; i++) red[(tid >> 5) * 64 + (tid & 7) * 8 + i] = acc[i];
        }
        BAR_SYNC(B_F, 256);
        PT(2);
        if (tid < 64) {
          float t = 0;
#pragma unroll
          for (int i = 0; i < 8; i++) t += red[i * 64 + tid];
          asm volatile("st.relaxed.gpu.global.u32 [%0],%1;" ::"l"((unsigned*)g_modp + (b >> 5) * 2048 + (b & 31) * 64 + tid), "r"(U_(t) | 1u) : "memory");
        }
      } else {
        asm volatile("griddepcontrol.launch_dependents;");
      }
      x_fetch();
      const uint32_t md = sb + PRE + 6144, rx = mapa(sb, a ^ !spare);
      asm volatile("barrier.cluster.wait.aligned;" ::: "memory");
      if (!spare) {
        mbar_wait(sb + BARS + 88, 0);
#pragma unroll
        for (int i = 0; i < 16; i++) ldsm4t(wQ[i], (frag ^ QSW) + WO + wg * 32768 + i * 2048);
      }
      PT(4);
#pragma unroll 1
      for (int it = 0;; it++) {
        if (tid == 0) mbar_expect(sb + BARS + 104, 512);
        float c[4][4] = {{0, 0, 0, 0}, {0, 0, 0, 0}, {0, 0, 0, 0}, {0, 0, 0, 0}};
#pragma unroll
        for (int i = 0; i < 16; i++) {
          mma16(c[(i & 1) * 2], xr[i].x, 0x3f803f80u, xr[i].y, 0x3f803f80u, xr[i].x, xr[i].y);
          mma16(c[(i & 1) * 2 + 1], xr[i].z, 0x3f803f80u, xr[i].w, 0x3f803f80u, xr[i].z, xr[i].w);
        }
#pragma unroll
        for (int e = 0; e < 4; e++) c[0][e] = (c[0][e] + c[1][e]) + (c[2][e] + c[3][e]);
        const int src = (lane & 28) + (lane >> 3);
        const float sq = __shfl_sync(~0u, (lane & 4) ? c[0][1] : c[0][0], src), sm = __shfl_sync(~0u, (lane & 4) ? c[0][3] : c[0][2], src);
        if ((lane & 3) < 2) sta1<0>(rx + PRE + 10240 + (wid ^ (spare * 4)) * 64 + (lane >> 2) * 8 + (lane & 1) * 4, U_((lane & 1) ? sm : sq), rx + BARS + 104);
        mbar_wait(sb + BARS + 104, it & 1);
        const float2 ot = lds2f(sb + PRE + 10240 + wid * 64 + (lane >> 2) * 8);
        const float mean = (sm + ot.y) * (1.f / 1024);
        const float rs = rsqrtf(fmaxf((sq + ot.x) * (1.f / 1024) - mean * mean, 0.f) + 1e-5f), nm = -mean * rs;
        const uint32_t rh = pk(rs, rs), rl = pk(rs - blo(rh), rs - blo(rh)), n2 = pk(nm, nm);
#define NRM(v) v = fmabf(v, rh, fmabf(v, rl, n2))
#pragma unroll
        for (int i = 0; i < 16; i++) { NRM(xr[i].x); NRM(xr[i].y); NRM(xr[i].z); NRM(xr[i].w); }
        if (!it) {
          PT(3);
#pragma unroll 1
          for (int i = 0; i < 2; i++) {
            uint4 p[4];
            for (int n = 0;; n++) {
#pragma unroll
              for (int e = 0; e < 4; e++) p[e] = ldg_rlx4(g_modp + e * 512 + i * 256 + tid);
              uint32_t ok = 1;
#pragma unroll
              for (int e = 0; e < 4; e++) ok &= p[e].x & p[e].y & p[e].z & p[e].w;
              if (__all_sync(~0u, ok) || n > SPIN_LIMIT / 16) break;
              __nanosleep(100);
            }
#define MSUM(e) (i + rbf((F_(p[0].e) + F_(p[1].e)) + (F_(p[2].e) + F_(p[3].e))))
            sts2(md + i * 2048 + tid * 8, pk(MSUM(x), MSUM(y)), pk(MSUM(z), MSUM(w)));
          }
          BAR_SYNC(B_F, 256);
          PT(5);
        }
        const int e0 = (iw * 8 + (lane >> 2)) * 8 + ((lane & 3) ^ (lane >> 2));
        uint4* dst = g_h + seg * 4096 + half * 2048;
#pragma unroll
        for (int i = 0; i < 16; i++) {
          const uint32_t ma = md + half * 1024 + (lane & 3) * 16 + i * 64;
          const uint4 sv = lds4(ma), cv = lds4(ma + 2048);
          xr[i] = make_uint4(fmabf(xr[i].x, cv.x, sv.x), fmabf(xr[i].y, cv.y, sv.y), fmabf(xr[i].z, cv.z, sv.z), fmabf(xr[i].w, cv.w, sv.w));
        }
        if (!spare) {
#pragma unroll
          for (int i = 0; i < 16; i++) sts4(sb + WO + wg * 32768 + (e0 ^ ((i & 1) * 4)) * 16 + (i >> 1) * 4096, xr[i].x, xr[i].y, xr[i].z, xr[i].w);
          break;
        }
#pragma unroll
        for (int i = 0; i < 16; i++) dst[(e0 ^ ((i & 1) * 4)) + (i >> 1) * 256] = xr[i];
        seg += 4;
        if (seg < 64) x_fetch();
        FENCE_ASYNC();
        BAR_SYNC(B_F, 256);
        if (tid == 0) red_rlx(g_hf + b - 128);
        if (seg >= 64) break;
      }
      if (spare) { rec_helper(sb, cvec, wmod, w1, b1, t0); return; }
      PH(1); PH(2); PT(6);
    }
    ROLE_REFRESH
#define ownv ((iw >> 1) == a)
#define owner (iw >= 2)
#define oi (wid & 1)
    {
      const uint32_t rsb = mapa(sb, owner ? a : a ^ 1);
      const uint32_t pp = rsb + PK + (owner ? 0 : 12288) + (oi * 2048 + wg * 1024) + l16;
      const uint32_t mb = sb + MEM + wg * 5120;
      sts4(L16 + TF + wid * 512, mb + lrow, owner ? L16 + (lane >> 4) * (RK - RQ - 256) + RQ + oi * 1024 + wg * 256 : rsb + RQ + oi * 1024 + 512 + wg * 256 + (l16 >> 2),
           L16 + OB, frag + wg * NVS * 2048);
      sts4(L16 + TF + 4096 + wid * 512, sb + WO + (wid >> 1) * 16384 + ((lane & 7) + (lane >> 4) * 8) * 128 + ((((wid & 1) * 4 + ((lane >> 3) & 1)) ^ (lane & 7)) << 4),
           sb + ARO + wid * 640 + lrow, pp, LO(xc) + h * 262144 + (bb * 2 + (iw >> 1)) * XC + X_VM(0) + oi * 2048 + a * 256 + (l16 >> 1));
    }
    uint32_t tp = L16 + TF + wid * 512;
    auto park_ptr = [&]() { return lds1(tp + 4096 + 8); };
    auto park_w = [&](const uint32_t* w, int m, uint32_t d) {
      if (m == 2) d += (sb & 0x1000000) ? 0 : owner ? 0x1003000 : -0x1003000;
      if (m == 2 ? ownv : owner) {
        sts4(d + m * 4096, w[0], w[1], w[2], w[3]); sts4(d + m * 4096 + 512, w[4], w[5], w[6], w[7]);
      } else {
        const uint32_t pb = (d & 0xff000000u) | (1024 + BARS + (m ? 24 + m * 8 : 16));
        sta4(d + m * 4096, w, pb); sta4(d + m * 4096 + 512, w + 4, pb);
      }
    };
    auto park = [&](const float* f, int m, int n, uint32_t d) {
      uint32_t w[8];
#pragma unroll
      for (int i = 0; i < 8; i++) w[i] = pk(f[2 * i], f[2 * i + 1]);
      park_w(w, m, d);
    };
#define D64(lo) (0x4000004000000000ull | (uint32_t)(lo))
#define XD(i) D64(x | (((i) >> 2) * 256 + ((i) & 3) * 2))
    auto xdesc = [&](uint32_t xb) { return ((uint32_t)__shfl_sync(~0u, 1024 + xb + wg * 16384, 0) >> 4) | 0x10000u; };
    auto rs_issue = [&](float* acc, const uint32_t (&w)[16][4], uint32_t xb, bool fence) {
      const uint32_t x = xdesc(xb);
      if (fence) WG_FENCE();
      wgmma_rs_n32_z(acc, w[0], XD(0));
#pragma unroll
      for (int i = 1; i < 16; i++) wgmma_rs_n32(acc, w[i], XD(i), 1);
      WG_COMMIT();
    };
    auto v_issue = [&](float* acc, uint32_t xb, bool fence) {
      const uint32_t dv = ((uint32_t)__shfl_sync(~0u, 1024 + WVS + wg * NVS * 2048, 0) >> 4) | 0x10000u, x = xdesc(xb);
      if (fence) WG_FENCE();
      wgmma_rs_n32_z(acc, wV[0], XD(0));
#pragma unroll
      for (int i = 1; i < VRF; i++) wgmma_rs_n32(acc, wV[i], XD(i), 1);
#pragma unroll
      for (int i = NVR; i < 16; i++) wgmma_ssT_n32(acc, D64(dv + (i - NVR) * 128), XD(i), 1);
#pragma unroll
      for (int i = VRF; i < NVR; i++) wgmma_rs_n32(acc, wV[i], XD(i), 1);
      WG_COMMIT();
    };
    uint32_t mA, vP[2][4];
#define V_AHEAD mA = lds1(tp); frag = lds1(tp + 12); ldsm4t(vP[0], frag + WVS + (15 - NVR) * 2048); ldsm4t(vP[1], frag + WVS + (14 - NVR) * 2048);
    auto vk_pass = [&](int n, uint32_t d, uint32_t xb, bool steady, auto between) {
      float acc[16], acc2[16];
      v_issue(acc, xb, true);
      rs_issue(acc2, wK, xb, false);
      between();
      const bool keep = !steady || !UNC || n < 64;
      if (steady ? keep : n) mbar_wait(sb + BARS + 80, (n - 1) & 1);
      WG_WAIT(1);
      if (keep) {
        park(acc, 2, n, d);
        if (steady) BAR_ARRIVE(B_K, 320);
      }
      V_AHEAD
      WG_WAIT(0);
      if (keep) park(acc2, 1, n, d + (VPC ? (vP[1][0] ^ mA) & dZ : 0));
    };
    uint32_t q0[8], q1[8];
    {
      float acc[16], acc2[16];
      FENCE_ASYNC_SMEM();
      BAR_SYNC(B_F, 256);
      rs_issue(acc, wQ, WO, true);
      rs_issue(acc2, wQ, WO + 32768, false);
      WG_WAIT(0);
#pragma unroll
      for (int i = 0; i < 8; i++) { q0[i] = pk(acc[2 * i], acc[2 * i + 1]); q1[i] = pk(acc2[2 * i], acc2[2 * i + 1]); }
    }
    mbar_wait(wbar, 0);
    PT(7);
#pragma unroll
    for (int i = 0; i < 16; i++) ldsm4t(wK[i], (frag ^ QSW) + XB + wg * 32768 + i * 2048);
#pragma unroll
    for (int i = 0; i < NVR; i++) ldsm4t(wV[i], frag + MEM + (wg * NVR + i) * 2048);
    FENCE_ASYNC_SMEM();
    PH(3); PT(8);
    CLUSTER_SYNC();
    PT(9);
    frag += wg * NVS * 2048;
    park_w(q0, 0, park_ptr());
    PT(10);
#pragma unroll 1
    for (int n = 0; n < 2; n++) {
      asm volatile("" : "+r"(wid));
      vk_pass(n, park_ptr(), n * XB, false, [&]() {
        if (n) {
          BAR_SYNC(B_C, 320);
          PT(12);
          mbar_wait(sb + BARS + 24, 0);
          park_w(q1, 0, park_ptr());
        }
      });
      if (n) break;
      PT(11);
      BAR_SYNC(B_C, 448);
      if (tid == 0) {
        mbar_expect(obar, 65536);
#pragma unroll 1
        for (int i = 0; i < 4; i++) tma2d(sb + WO + i * 16384, &mp.wo, j * 256 + i * 64, h * 128, obar);
      }
    }
    static_assert(WO == 0, "x");
    {
      BAR_ARRIVE(B_P, 384); BAR_ARRIVE(B_X, 320); BAR_ARRIVE(B_Q, 288);
    }
    PT(13);
    PH(4); RS(1); PT(14);
    ROLE_REFRESH
    for (int s = 0; s < 64; s++) {
      asm volatile("" : "+r"(tp), "+r"(wid));
      asm volatile("mov.u32 %0,%%cluster_ctarank;" : "=r"(b));
      uint32_t vS[NVS][4], bf[8][4];
      static_assert(NVR == 5, "schedule");
#define VLD(k) ldsm4t(vS[(k) - NVR], frag + WVS + ((k) - NVR) * 2048)
#define BLD(t) ldsm4t(bf[t], mA + (t) * 640)
#define VMMA(c, w, i) mma16(c, (w)[0], (w)[1], (w)[2], (w)[3], bf[(i) >> 1][((i) & 1) * 2], bf[(i) >> 1][((i) & 1) * 2 + 1])
#define VS_(c, k) VMMA(c, vS[(k) - NVR], k)
#define QK(i) VMMA(cQ, wQ[i], i); VMMA(cK, wK[i], i)
#define PREV VLD(13); VLD(12); if (NF > 2) VLD(11);
      if (s > 0) BAR_SYNC(B_R, 320);
      float cV[4] = {0, 0, 0, 0}, cW[4] = {0, 0, 0, 0};
      {
        float cQ[4] = {0, 0, 0, 0}, cK[4] = {0, 0, 0, 0};
        BLD(7); BLD(6); BLD(5); BLD(4); if (NB0 > 4) BLD(3);
        SCHED_FENCE(47);
        QK(15); VMMA(cV, vP[0], 15);
        QK(14); VMMA(cV, vP[1], 14);
        QK(13); QK(12);
        SCHED_FENCE(51);
        if (NB0 < 5) BLD(3);
        BLD(2); BLD(1); BLD(0);
        const uint32_t rm = lds1(tp + 4);
        QK(11); QK(10); QK(9); QK(8); QK(7);
        if (PV0 == 6) { SCHED_FENCE(48); PREV }
        QK(6); QK(5);
        if (PV0 == 4) { QK(4); SCHED_FENCE(48); PREV } else { QK(4); }
        QK(3); QK(2); QK(1); QK(0);
        const uint32_t w0 = pk(cQ[0] * SCS, cQ[1] * SCS), w1 = pk(cQ[2] * SCS, cQ[3] * SCS), w2 = pk(cK[0], cK[1]), w3 = pk(cK[2], cK[3]);
        if (owner) {
          stsm4(rm, w0, w1, w2, w3);
          BAR_ARRIVE(B_E, 256);
        } else {
          const uint32_t mm = (rm & 0xff000000u) | (1024 + BARS);
          sta1<0>(rm, w0, mm); sta1<128>(rm, w1, mm);
          sta1<RK - RQ>(rm, w2, mm); sta1<RK - RQ + 128>(rm, w3, mm);
        }
        if (wid == 2) TS(0);
      }
      uint4 t1;
      uint32_t oA, wo[16][4];
      {
        if (NF < 3) VLD(11);
        VLD(10);
        VS_(cW, 13); VLD(9); VS_(cV, 12); VLD(8); VLD(7); VMMA(cW, wV[0], 0); VMMA(cV, wV[1], 1); VLD(6);
        VMMA(cW, wV[2], 2); VMMA(cV, wV[3], 3); VLD(5); VMMA(cW, wV[4], 4); VS_(cV, 11);
        VS_(cW, 10); VS_(cV, 9); VS_(cW, 8); VS_(cV, 7); VS_(cW, 6); VS_(cV, 5);
#pragma unroll
        for (int e = 0; e < 4; e++) cV[e] += cW[e];
        const uint32_t ex = tp + (RX - TF) - wg * 2048;
        t1 = lds4(tp + 4096 + (T1L ? vS[3][0] & dZ : 0));
        oA = lds1(tp + 8 + (s & dZ));
        if (wg) {
          sts4(ex, U_(cV[0]), U_(cV[1]), U_(cV[2]), U_(cV[3]));
          BAR_ARRIVE(B_T2, 256);
        }
        if (!wg) {
          BAR_SYNC(B_T2, 256);
          DLY(3)
          const float4 u = lds4f(ex);
          stg_b64(mkp(t1.w ^ ((s & 1) * X_RING), HI(xc)), (pk(cV[0] + u.x, cV[1] + u.y) & ~1u) | (((s >> 1) + 1) & 1), pk(cV[2] + u.z, cV[3] + u.w));
        }
      }
      if (s == 63) break;
      if (s == 0) mbar_wait(obar, 0);
      {
        const uint32_t woA = t1.x, woB = woA ^ 32;
#pragma unroll
        for (int i = 0; i < NW0; i++) ldsm4t(wo[i], ((i & 1) ? woB : woA) + (i >= WCH ? wo[(i - WCH + NWP) % NWP][0] & dZ : 0) + (i >> 1) * 2048);
        DLY(2)
        BAR_SYNC(B_S, 416);
        float inv0, inv1;
        uint32_t p[4], pm;
        const uint32_t pa = oA + (SC - OB), one = 0x3f803f80u;
#define P_LOAD ldsm4t(p, pa); asm volatile("ldmatrix.sync.aligned.m8n8.x1.trans.shared.b16 {%0},[%1];" : "=r"(pm) : "r"(pa + 512) : "memory");
        if (s < 62) {
          float acc[16];
          rs_issue(acc, wQ, XB, true);
          mbar_wait(sb + BARS + 24, (s + 1) & 1);
          WG_WAIT(0);
          uint32_t qw[8];
#pragma unroll
          for (int i = 0; i < 8; i++) qw[i] = pk(acc[2 * i], acc[2 * i + 1]);
#pragma unroll
          for (int i = NW0; i < NW1; i++) ldsm4t(wo[i], ((i & 1) ? woB : woA) + (i >> 1) * 2048);
          BAR_SYNC(B_V, 512);
          P_LOAD
          park_w(qw, 0, t1.z);
        } else {
#pragma unroll
          for (int i = NW0; i < NW1; i++) ldsm4t(wo[i], ((i & 1) ? woB : woA) + (i >> 1) * 2048);
          BAR_SYNC(B_V, 512);
          P_LOAD
        }
#pragma unroll
        for (int i = NW1; i < NWP; i++) ldsm4t(wo[i], ((i & 1) ? woB : woA) + (i >> 1) * 2048);
        {
          float sum[4] = {0, 0, 0, 0}, su2[4] = {0, 0, 0, 0};
          mma16(sum, one, one, one, one, p[0], p[1]);
          mma16(su2, one, one, one, one, p[2], p[3]);
          mma8(sum, one, one, pm);
          inv0 = sum[0] + su2[0]; inv1 = sum[1] + su2[1];
          SCHED_FENCE(57);
        }
        DLY(7)
        BAR_SYNC(B_O, 416);
        float c[2][4] = {{0, 0, 0, 0}, {0, 0, 0, 0}};
        uint32_t o[4][4];
#pragma unroll
        for (int i = 0; i < NOP_; i++) ldsm4t(o[i], oA + i * 512);
        SCHED_FENCE(46);
        asm("rcp.approx.ftz.f32 %0,%0;" : "+f"(inv0));
        asm("rcp.approx.ftz.f32 %0,%0;" : "+f"(inv1));
#pragma unroll
        for (int i = 0; i < 16; i++) {
          mma16(c[i & 1], wo[i][0], wo[i][1], wo[i][2], wo[i][3], o[i >> 2][i & 2], o[i >> 2][(i & 2) + 1]);
          if (i == 1 && NOP_ < 3) ldsm4t(o[2], oA + 1024);
          if (i == 3 && NOP_ < 4) ldsm4t(o[3], oA + 1536);
          if (i + NWP < 16) ldsm4t(wo[(i + NWP) & 15], (((i + NWP) & 1) ? woB : woA) + ((i + NWP) >> 1) * 2048);
        }
        stsm4(t1.y, pk(c[0][0] * inv0, c[0][1] * inv1), pk(c[0][2] * inv0, c[0][3] * inv1), pk(c[1][0] * inv0, c[1][1] * inv1), pk(c[1][2] * inv0, c[1][3] * inv1));
      }
      const uint32_t d = park_ptr();
      BAR_SYNC(B_W, 384);
      DLY(1)
      if (UNC || s < 62) {
        vk_pass(s + 2, d, XB, true, []() {});
        if (!UNC || s < 62) { BAR_ARRIVE(B_P, 384); BAR_ARRIVE(B_X, 320); }
        TS(10);
      } else {
        V_AHEAD
        CONSUME(vP[1][0]);
      }
    }
  } else if (role == 3) {
    asm volatile("setmaxnreg.dec.sync.aligned.u32 24;");
    if (blockIdx.x >= 128) return;
    ROLE_VARS
    const uint32_t L16 = sb + (tid & 31) * 16;
    asm volatile("barrier.cluster.wait.aligned;" ::: "memory");
    CLUSTER_SYNC();
    sts1(sb + PACE + 36, LO(xc) + h * 262144 + X_VM(0));
    auto vm_stage = [&](int s) {
      const uint32_t tag = ((s >> 1) + 1) & 1;
      const char* xm = mkp(lds1(sb + PACE + 36) + (s & 1) * X_RING + iw * XC + (l16 >> 1), HI(xc));
      uint2 m[4];
      CONSUME(LO(xm));
      BAR_SYNC(B_S2, 256);
      DLY(4)
      int it = 0;
      while (true) {
#pragma unroll
        for (int i = 0; i < 4; i++) m[i] = ldg_b64(xm + (i >> 1) * 2048 + (i & 1) * 256);
        sts4(L16 + VN + iw * 512, m[0].x, m[0].y, m[1].x, m[1].y);
        sts4(L16 + VN + iw * 512 + 2048, m[2].x, m[2].y, m[3].x, m[3].y);
        if (!anybad(m[0].x, m[1].x, m[2].x, m[3].x, tag)) break;
        RP(2);
        if (++it > SPIN_LIMIT) __trap();
      }
      if (s < 63) BAR_ARRIVE(B_V, 512); else BAR_ARRIVE(B_V, 256);
    };
    if (iw == 0) {
      wait_cnt(&g_hcnt, 128);
#pragma unroll 1
      for (int s = 0; s < 63; s++) {
        if (s < 62) for (int it = 0; ldg_rlx1(g_hf + (s & 3)) <= (s >> 2); it++) if (it > SPIN_LIMIT) __trap();
        if (s) BAR_SYNC(B_R, 320); else BAR_SYNC(B_Q, 288);
        if (s < 62) { X_LOAD(s + 2, 0, 0); X_LOAD(s + 2, 1, 0); X_LOAD(s + 2, 0, 1); X_LOAD(s + 2, 1, 1); }
        if (s >= 7) {
          const uint32_t zo = b * 160 + l16;
          if (l16 < 160) CONSUME(exch_b128(xc + AR_OFF + AR_ROW(zo >> 7) * 1024 + (zo & 127) + ((s + 1) & 7) * 128, 0, 0, 0, 0).x);
          __syncwarp();
        }
        if (s < 62) { mbar_wait(sb + BARS + 64, s & 1); mbar_wait(sb + BARS + 72, s & 1); }
        BAR_ARRIVE(B_S, 416);
        vm_stage(s);
        BAR_ARRIVE(B_O, 416);
        BAR_SYNC(B_W, 384);
        DLY(8)
        FENCE_ASYNC_SMEM();
        asm volatile("{.reg .pred p; elect.sync _|p, 0xffffffff; @p cp.reduce.async.bulk.tensor.3d.global.shared::cta.add.bulk_group [%0,{%1,%4,%2}],[%3];}"
                     ::"l"(&mp.ari), "r"((s & 7) * 64), "r"(AR_R(j)), "r"(sb + ARO), "r"(AR_P(j)) : "memory");
        BULK_COMMIT();
        asm volatile("st.relaxed.gpu.global.u32 [%0],%1;" ::"l"(g_tm + (s & 1) * 128 + b), "r"(gtime()) : "memory");
        TS(3);
        BULK_WAIT_READ(0);
      }
      BAR_ARRIVE(B_R, 320);
    } else if (iw == 1) {
      const uint32_t pc = sb + MEM + (lane >> 2) * 640 + (lane & 3) * 144 + (lane & 12), pd = sb + MEM + (lane & 15) * 640 + 576 + (lane & 3) * 16 + (lane & 12);
      uint32_t T = 0, par = 0;
      int est = dA;
#pragma unroll 1
      for (int s = 0; s < 63; s++) {
        if (s) {
          const uint4 tm = ldg_rlx4((const char*)g_tm + ((s + 1) & 1) * 512 + l16);
          const int t0 = tm.x - T, t1 = tm.y - T, t2 = tm.z - T, t3 = tm.w - T;
          const int e = max(dF + (__reduce_add_sync(~0u, (t0 + t1) + (t2 + t3)) >> 7), dV + __reduce_max_sync(~0u, max(max(t0, t1), max(t2, t3))));
          if (s > 1) est += max(min(e >> 2, dP), -dP);
          T += (s == 1 || e > dM ? e : 0) + est - (s == 62 ? L62 : 0);
        }
        vm_stage(s);
        BAR_SYNC(B_W, 384);
        SCHED_FENCE(70);
        const uint32_t tW = gtime();
        if (s == 0) T = tW + 800;
        const uint32_t te = tW + min(max((int)(T - tW), dD), 2000);
        while ((int)(gtime() - te) < 0) {}
        TS(7);
        int it = 0;
        while (true) {
          ar_fetch(sb + MEM, &mp.ari, s & 7, a, sb + BARS + 112);
          mbar_wait(sb + BARS + 112, par);
          par ^= 1;
          const uint32_t n0 = lds1(pc), n1 = lds1(pc + 5120), n2 = lds1(pd);
          if (!__any_sync(~0u, (tagbad(n0, n1, 0x42004200) | (n2 ^ 0x42004200)) != 0)) break;
          RP(0);
          if (++it > SPIN_LIMIT) __trap();
        }
        BAR_ARRIVE(B_R, 320);
        TS(11);
      }
    } else {
#define V_LOAD(n) do { if (lane == 0) mbar_expect(sb + BARS + 8, 8192); __syncwarp(); \
        if (lane < 16) bulk_ld(sb + ((lane & 2) ? VX1 : VX0) + (lane & 1) * 2048 + (lane >> 2) * 512, \
                               xc + h * 262144 + V_RING(n) + (lane >> 2) * XC + X_VX(lane & 3), 512, sb + BARS + 8); __syncwarp(); } while (0)
      uint32_t src = L16 + PK + (iw & 1) * 2048;
#define qd (L16 + (lane >> 4) * 256 + QT + (iw & 1) * 1024)
#define vd (LO(xc) + h * 262144 + j * XC + (iw & 1) * 2048 + l16)
#define FINISH [&](int n, int m) { \
_Pragma("unroll") \
        for (int i = 1; i >= 0; i--) { \
          const uint32_t p = src + m * 4096 + i * 512; \
          uint4 u = lds4(p); \
          const uint4 w = lds4(p + 1024), y = lds4(p + 12288), z = lds4(p + 13312); \
          u = make_uint4(sum4bf(u.x, w.x, y.x, z.x), sum4bf(u.y, w.y, y.y, z.y), sum4bf(u.z, w.z, y.z, z.z), sum4bf(u.w, w.w, y.w, z.w)); \
          if (m == 2) stg_b128(mkp(vd ^ V_RING(n), HI(xc)) + i * 512, (u.x & ~1u) | V_TAG(n), u.y, u.z, u.w); \
          else stsm4(qd + (n & 1) * 4096 + m * 2048 + i * 256, u.x, u.z, u.y, u.w); \
          SCHED_FENCE(71 + m * 2 + i); \
        } \
      }
#pragma unroll 1
      for (int n = 0; n < 64; n++) {
        src = PIN(src);
        b = __shfl_sync(~0u, lds1(sb + PACE + 24), 0);
        const uint32_t L16 = src - PK - (iw & 1) * 2048;
        auto finish = FINISH;
        if (n < 2) { if (n) BAR_SYNC(B_X, 320); else BAR_SYNC(B_C, 448); }
        mbar_wait(sb + BARS + 16, n & 1);
        finish(n, 0);
        __syncwarp();
        if (lane == 0) mbar_arrive_cl(mapa(sb, a ^ 1) + BARS + 24);
        if (n > 1) BAR_SYNC(B_K, 320);
        mbar_wait(sb + BARS + 40, n & 1);
        finish(n, 2);
        if (n > 1) BAR_SYNC(B_X, 320);
        mbar_wait(sb + BARS + 32, n & 1);
        finish(n, 1);
        BAR_SYNC(B_T, 64);
        if (lane == 0) {
          if (iw == 2 && n < 63) { mbar_expect(sb + BARS + 16, 4096); mbar_expect(sb + BARS + 32, 4096); mbar_expect(sb + BARS + 40, 4096); }
          mbar_arrive_cl(mapa(sb, a ^ 1) + BARS + 80);
        }
        __syncwarp();
        if (n) {
          vm_stage(n - 1);
          BAR_SYNC(B_W, 384);
        } else {
          BAR_SYNC(B_C, 320);
        }
        if (iw == 2) V_LOAD(n);
      }
#undef qd
#undef vd
    }
    { ROLE_REFRESH }
    vm_stage(63);
  } else {
    asm volatile("setmaxnreg.dec.sync.aligned.u32 %0;" ::"n"(RA_));
    if (blockIdx.x >= 128) { if (threadIdx.x == 256) rec_prefetch((const char*)wmod, w1, (const char*)x, wo); return; }
    ROLE_VARS
    uint32_t L16 = __shfl_sync(~0u, sb + (tid & 31) * 16, tid & 31);
    const uint32_t ts = gtime();
    uint2 m0[8];
#pragma unroll
    for (int r = 0; r < 8; r++) m0[r] = *(const uint2*)(mem0 + r * 1024 + a * 512 + (tid - 256) * 4);
    if (wid == 9) {
#pragma unroll 1
      for (int i = b * 80 + (tid & 31); i < b * 80 + 80; i += 32) ((uint4*)(xc + AR_OFF))[AR_ROW(i >> 6) * 64 + (i & 63)] = make_uint4(0, 0, 0, 0);
      if (b == 0) g_fin = 0;
      FENCE_ASYNC();
      __syncwarp();
      if (tid == 288) red_rlx(&g_hcnt);
    }
    if (tid == 256) {
      const int col = h * 128 + bb * 64;
#pragma unroll 1
      for (int c = 0, w = 0; w < 12; c++) {
#pragma unroll 1
        for (; w <= c - (c < WC0 ? 2 : 3); w++) {
          mbar_wait(sb + PACE + (w % 3) * 8, (w / 3) & 1);
          PT(18 + w);
          if (w == 3) asm volatile("mbarrier.arrive.shared.b64 _,[%0];" ::"r"(sb + BARS + 88) : "memory");
        }
        const uint32_t mb = sb + PACE + (c % 3) * 8;
        if (c >= 12 && c < 12 + WPE) tma2d_pf(&mp.wo, j * 256 + (c - 12) * 64, h * 128);
        if (c >= 12) continue;
        mbar_expect(mb, 16384);
        if (c < 8) tma2d(sb + (c >> 2) * XB + (c & 3) * 16384, (c & 4) ? &mp.wk : &mp.wq, col, a * 512 + (c & 3) * 128, mb);
        else
#pragma unroll 1
          for (int i = (c & 1) * 8; i < (c & 1) * 8 + 8; i++) {
            const int w = (c - 8) >> 1;
            tma2d(i < NVR ? sb + MEM + (w * NVR + i) * 2048 : sb + WVS + (w * NVS + i - NVR) * 2048, &mp.wv, col, a * 512 + w * 256 + i * 16, mb);
          }
      }
      asm volatile("mbarrier.arrive.shared.b64 _,[%0];" ::"r"(wbar) : "memory");
      for (int i = 0; i < 3; i++) asm volatile("mbarrier.inval.shared.b64 [%0];" ::"r"(sb + PACE + i * 8) : "memory");
    }
    __syncwarp();
    asm volatile("barrier.cluster.wait.aligned;" ::: "memory");
    CLUSTER_SYNC();
#pragma unroll 4
    for (int i = 0; i < 16; i++) {
      const uint4 v = lds4(L16 + WO + 32768 + iw * 8192 + i * 512);
      sts4(L16 + XB + iw * 8192 + i * 512, v.x, v.y, v.z, v.w);
    }
#pragma unroll
    for (int i = 0; i < 4; i++) {
      const int k = (tid - 256) * 4 + i, m = (k >> 3) & 3, r = k & 7;
#define M0W(r) __byte_perm((i & 2) ? m0[r].y : m0[r].x, (i & 2) ? m0[r + 1].y : m0[r + 1].x, (i & 1) ? 0x7632 : 0x5410)
      sts4(sb + MEM + (k >> 5) * 640 + (r == m ? 512 : m * 128) + r * 16, M0W(0), M0W(2), M0W(4), M0W(6));
    }
#pragma unroll 1
    for (int i = tid - 256; i < 192; i += 128) {
      const uint32_t c = i < 128 ? 0x42004200 : 0x3f803f80;
      sts4(sb + MEM + (i >> 3) * 640 + ((i & 7) < 4 ? (i & 7) * 144 : 512 + (i & 7) * 16), c, c, c, c);
    }
    static_assert(ARO == MEM + 16 * 640, "counters");
    FENCE_ASYNC_SMEM();
    BAR_ARRIVE(B_C, 448);
    if (tid == 256) {
      wait_time(ts + 1);
#pragma unroll 1
      for (int c = WPE; c < 4; c++) tma2d_pf(&mp.wo, j * 256 + c * 64, h * 128);
    }
    __syncwarp();
#define pr (L16 + SC)
    {
      const int lim = j * 8 + iw * 2 - (lane & 7) - (lane & 8) * 2;
      const bool mk = L16 & 256;
      const int rw = lane >> 2;
      sts4(L16 + TA + iw * 512,
           iw != 2 ? L16 + KT + (iw & 1) * 256 + (lane >> 4) * 256 : sb + RK + (L16 & 0x80) * 2 + ((L16 >> 1) & 0x80) + (L16 & 0x70),
           L16 + QT + (lane >> 3) * 384, sb + SC + min(lane >> 3, 2) * 256 + (L16 & 0x70) + iw * 4, L16 + (lane >> 4) * 256 + QT + (iw >> 1) * 1024 + (iw & 1) * 256);
      sts4(L16 + TA + 2048 + iw * 512, mk ? 0u : (lim < 0 ? 0xfc00u : 0u) | (lim < -1 ? 0xfc000000u : 0u),
           mk ? 0xfc00fc00u : (lim < 8 ? 0xfc00u : 0u) | (lim < 7 ? 0xfc000000u : 0u),
           ((h * 2 + (iw >> 1)) * 1024 + (j * 8 + rw) * 8 + (((iw & 1) * 4 + (lane & 3)) ^ rw)) * 16, sb + OT + iw * 512 + (L16 & 0x70) * 4 + ((L16 >> 3) & 0x30));
    }
    {
      const uint32_t xh = LO(xc) + h * 262144, xs = xh + X_SC + iw * 1024 + min(lane, 16 + (lane & 7)) * 8;
      sts4(L16 + TA + 4096 + iw * 512, xh + X_SC + j * 256 + iw * 64 + lpub, xs, dS, iw != 2 ? 0 : U_(SCS));
      sts1(L16 + TA + 12 + iw * 512, xs + X_TOK + j * 4096);
    }
    uint32_t tA = L16 + TA + iw * 512;
#define tw (tA - L16 != TA + 1024)
#define XP_(lo) mkp(lo, HI(xc))
    auto publish = [&](char* d, const uint2& w) { stg_b64(d, w.x, w.y); };
    BAR_SYNC(B_P, 384);
    for (int s = 0; s < 64; s++) {
      asm volatile("" : "+r"(L16), "+r"(tA));
      const uint32_t tag = ((s >> 1) + 1) & 1, ring = (s & 1) * X_RING;
      const uint4 t0 = lds4(tA);
      const uint4 tx = lds4(tA + 4096);
      const uint32_t xo = tx.x ^ ring, xs = tx.y ^ ring;
      const float gm = F_(tx.w);
      const uint32_t qA = t0.y + (ring >> 5);
      uint32_t c0;
      uint2 ts[4];
      uint4 v[4];
      uint32_t af[2][4], qt[4][4];
      {
        const uint32_t aA = t0.x + (tw ? ring >> 5 : 0);
        uint32_t ql[2][4], qr[2][4];
        uint2 pw_;
        float c[4] = {0, 0, 0, 0}, d[4] = {0, 0, 0, 0};
        if (s == PDS) asm volatile("griddepcontrol.launch_dependents;");
#pragma unroll
        for (int i = 0; i < 4; i++) ldsm4t(qt[i], qA + i * 128);
        mbar_wait(sb + BARS + 8, s & 1);
        TS(4);
        BAR_SYNC(B_E, 256);
#define PACK(c) make_uint2(pkh(fmaf(c[2], gm, c[0] * SCS), fmaf(c[3], gm, c[1] * SCS), tag), pkh(c[2] * SCS, c[3] * SCS, tag))
        ldsm4t(ql[0], L16 + RQ); ldsm4t(ql[1], L16 + RQ + 1024); ldsm4t(af[0], aA); ldsm4t(af[1], aA + 1024);
        CONSUME(xo);
#define QSUM(t, i) addbf(addbf(ql[t][i], ql[t][i + 2]), addbf(qr[t][i], qr[t][i + 2]))
#define STAIL mma16(c, af[0][0], af[0][1], af[0][2], af[0][3], QSUM(0, 0), QSUM(0, 1)); mma16(d, af[1][0], af[1][1], af[1][2], af[1][3], QSUM(1, 0), QSUM(1, 1));
        if (tw) {
          mbar_wait(sb + BARS, s & 1);
          TS(8);
          ldsm4t(qr[0], L16 + RQ + 512); ldsm4t(qr[1], L16 + RQ + 1536);
          STAIL
          pw_ = make_uint2(pkh(c[0] + d[0], c[1] + d[1], tag), pkh(c[2] + d[2], c[3] + d[3], tag));
        } else {
          uint32_t ar[2][4];
          mbar_wait(sb + BARS, s & 1);
          ldsm4t(qr[0], L16 + RQ + 512); ldsm4t(ar[0], aA + 512); ldsm4t(qr[1], L16 + RQ + 1536); ldsm4t(ar[1], aA + 1536);
#pragma unroll
          for (int i = 0; i < 8; i++) af[i >> 2][i & 3] = addbf(af[i >> 2][i & 3], ar[i >> 2][i & 3]);
          STAIL
          pw_.x = pw_.y = pkh((c[0] + c[2]) + (d[0] + d[2]), (c[1] + c[3]) + (d[1] + d[3]), tag);
        }
        publish(XP_(xo), pw_);
        c0 = clk() + tx.z;
        TS(1);
      }
      uint2 r[4];
      bool vbad;
      uint4 vn[2];
      {
        float e[4][4];
#pragma unroll
        for (int i = 0; i < 4; i++) {
          e[i][0] = e[i][1] = e[i][2] = e[i][3] = 0.f;
          mma16(e[i], af[0][0], af[0][1], af[0][2], af[0][3], qt[i][0], qt[i][1]);
        }
#pragma unroll
        for (int i = 0; i < 4; i++) mma16(e[i], af[1][0], af[1][1], af[1][2], af[1][3], qt[i][2], qt[i][3]);
        SCHED_FENCE(55);
        if (s < 63) BAR_ARRIVE(B_S, 416);
        SCHED_FENCE(58);
        v[0] = lds4(tA + (VX0 - TA)); v[1] = lds4(tA + (VX0 - TA) + 2048); v[2] = lds4(tA + (VX1 - TA)); v[3] = lds4(tA + (VX1 - TA) + 2048);
#pragma unroll
        for (int i = 0; i < 4; i++) ts[i] = PACK(e[i]);
        vbad = anybad(v[0].x, v[1].x, v[2].x, v[3].x, V_TAG(s));
        while ((int)(clk() - c0) < 0) {}
        TS(5);
#pragma unroll
        for (int u = 0; u < 4; u++) r[u] = ldg_b64(XP_(xs) + u * 256);
        BAR_ARRIVE(B_S2, 256);
      }
      SCHED_FENCE(56);
      uint32_t kk;
      float4 e = softmax2<false>(r, 0, 0, kk);
      if (__builtin_expect(anybad(r[0].x, r[0].y, r[1].x, r[1].y, r[2].x, r[2].y, r[3].x, r[3].y, tag ^ (kk & dZ)), 0)) {
        int it = 0;
        if (s > 8) sts1(tA + 4096 + 8, min(lds1(tA + 4096 + 8) + dX, 500));
        do {
          RP(1);
          if (++it > SPIN_LIMIT) __trap();
#pragma unroll
          for (int u = 0; u < 4; u++) r[u] = ldg_b64(XP_(xs) + u * 256);
        } while (BADS(r));
        e = softmax2<false>(r, 0, 0, kk);
      }
      DLY(5)
      sts1(t0.z, pk(e.x, e.y)); sts1(t0.z + 128, pk(e.z, e.w));
#pragma unroll
      for (int i = 0; i < 4; i++) publish(XP_(xo) + X_TOK + i * 4096, ts[i]);
      TS(6);
      if (s < 63) BAR_SYNC(B_V, 512); else BAR_SYNC(B_V, 256);
      uint32_t O[4];
      {
        uint32_t p[4], pm;
        ldsm4t(p, pr);
        asm volatile("ldmatrix.sync.aligned.m8n8.x1.trans.shared.b16 {%0},[%1];" : "=r"(pm) : "r"(pr + 512) : "memory");
        vn[0] = lds4(tA + (VN - TA)); vn[1] = lds4(tA + (VN - TA) + 2048);
        pv_mem(p, pm, v, vn, O);
        if (__builtin_expect(vbad, 0)) {
          int it = 0;
          const uint32_t xv = LO(xc) + (lds1(sb + PACE + 24) >> 2) * 262144 + ((tA - L16 - TA) >> 9) * XC;
          do {
            RP(2);
            if (++it > SPIN_LIMIT) __trap();
#pragma unroll
            for (int u = 0; u < 4; u++) v[u] = ldg_b128(XP_((xv + l16) ^ V_RING(s)) + X_VX(u));
          } while (anybad(v[0].x, v[1].x, v[2].x, v[3].x, V_TAG(s)));
          pv_mem(p, pm, v, vn, O);
        }
      }
      DLY(6)
      stsm4(tA + (OB - TA), O[0], O[1], O[2], O[3]);
      if (s < 63) BAR_ARRIVE(B_O, 416);
      TS(2);
      c0 = clk() + dG;
      SCHED_FENCE(60);
      if (tA == sb + TA) mbar_expect(sb + BARS, 2048);
      const uint32_t vs[4] = {addbf(vn[0].x, vn[0].z), addbf(vn[0].y, vn[0].w), addbf(vn[1].x, vn[1].z), addbf(vn[1].y, vn[1].w)};
      {
        const char* xt = XP_(lds1(tA + 12) ^ ring);
        const uint2 t1 = lds2u(tA + 2048);
        const uint32_t pw = lds1(tA + 8);
        uint2 rt[4];
        CONSUME(LO(xt) ^ t1.x ^ pw);
        while ((int)(clk() - c0) < 0) {}
        int it = 0;
        do {
          if (++it > SPIN_LIMIT) __trap();
#pragma unroll
          for (int u = 0; u < 4; u++) rt[u] = ldg_b64(xt + u * 256);
        } while (BADS(rt));
        uint32_t kt;
        const float4 et = softmax2<true>(rt, t1.x, t1.y, kt);
        sts1(pw + 1024, pk(et.x, et.y)); sts1(pw + 1024 + 128, pk(et.z, et.w));
      }
      s = PIN(s);
      BAR_SYNC(B_SC, 128);
      {
        uint32_t Ot[4], p[4], pm;
        const uint2 t2 = lds2u(tA + 2048 + 8);
        ldsm4t(p, pr + 1024);
        asm volatile("ldmatrix.sync.aligned.m8n8.x1.trans.shared.b16 {%0},[%1];" : "=r"(pm) : "r"(pr + 1024 + 512) : "memory");
        char* od = (char*)g_O + ((s >> 2) * 1048576 + (s & 3) * 4096) + t2.x;
        CONSUME(LO(od) ^ HI(od) ^ pm ^ p[3]);
        TS(9);
        if (s < 62) BAR_SYNC(B_P, 384);
        pv_tok(p, pm, v, vs, Ot);
        asm volatile("stmatrix.sync.aligned.m8n8.x4.trans.shared.b16 [%0],{%1,%2,%3,%4};" ::"r"(t2.y), "r"(Ot[0]), "r"(Ot[1]), "r"(Ot[2]), "r"(Ot[3]) : "memory");
        __syncwarp();
        *(uint4*)od = lds4(tA + (OT - TA));
      }
    }
    FENCE_ASYNC();
    BAR_SYNC(B_SC, 128);
    if (tA == sb + TA) red_rlx(&g_fin);
  }
  __syncwarp();
  CLUSTER_SYNC();
  PH(5); RS(2);
}
#undef wg
#undef iw
#undef h
#undef j
#undef a
#undef bb
#undef oi
#undef owner
#undef ownv
#undef pr
#undef PIN
#undef XP_
#undef tw
#undef lane
#undef l16
#undef lrow
#undef lpub

namespace ffn {
constexpr uint32_t BR = 98304;
constexpr uint32_t STG = 196608;
constexpr uint32_t PRM = 229376;
constexpr uint32_t BARS = PRM + 2816;
constexpr uint32_t SMEM = BARS + 18 * 8;
}
#define Y_TILE(rb, kt) (((ALIAS & 1) ? g_h : g_h2) + ((rb) * 16 + (kt)) * 1024)
#define U_TILE(rb, kt) ((ALIAS & 2) ? g_O + ((rb) * 64 + (kt)) * 1024 : g_U + ((rb) * 56 + (kt)) * 1024)
struct FfnMaps { CUtensorMap wo, w1a, w1b, w2, x, out; };

template <int N>
__device__ __forceinline__ void wg_ss(float* d, uint64_t a, uint64_t b, int sd) {
  if (N == 128) wgmma_ss_n128(d, a, b, sd);
  if (N == 192) wgmma_ss_n192(d, a, b, sd);
}
template <int N>
__device__ __forceinline__ void acc_fence(float* d) {
#pragma unroll
  for (int i = 0; i < N; i++) asm volatile("" : "+f"(d[i])::"memory");
}
#define UNPK8(d, v) do { (d)[0] = blo(v.x); (d)[1] = bhi(v.x); (d)[2] = blo(v.y); (d)[3] = bhi(v.y); (d)[4] = blo(v.z); (d)[5] = bhi(v.z); (d)[6] = blo(v.w); (d)[7] = bhi(v.w); } while (0)
struct FfnPipe {
  uint32_t full, emp, ph, aoff;
  int st, sB, prev;
  bool leader;
  template <int N, int S = N>
  __device__ __forceinline__ void issue(float* acc, bool first, uint32_t a = 0) {
    mbar_wait(full + st * 8, ph);
    const uint64_t da = mkdesc((a ? a : 1024 + st * 16384) + aoff, 16, 1024), db = mkdesc(1024 + ffn::BR + sB * (S * 128), 8192, 1024);
    WG_FENCE();
#pragma unroll
    for (int j = 0; j < 4; j++) wg_ss<N>(acc, da + j * 2, db + j * 128, j || !first);
    WG_COMMIT();
    if (++sB == 768 / S) sB = 0;
  }
  __device__ __forceinline__ void release() { if (leader) mbar_arrive(emp + prev * 8); }
  __device__ __forceinline__ void next() { prev = st; if (++st == 6) { st = 0; ph ^= 1; } }
  __device__ __forceinline__ void retire() { WG_WAIT(1); release(); next(); }
};
__device__ __forceinline__ float gelu_h(float hx) {
  float u = hx * fmaf(hx * hx, 8.f * 0.0356774081f, 2.f * 0.7978845608f), t;
  asm("tanh.approx.f32 %0,%1;" : "=f"(t) : "f"(u));
  return fmaf(hx, t, hx);
}
struct FfnEpi {
  uint32_t st2, cc, flip, staged, l0;
  uint2 c;
  float n0, n1, s0, s1;
  __device__ __forceinline__ void flush(uint32_t r) {
    __syncwarp();
    asm volatile("{.reg .pred p; setp.ne.u32 p,%1,0; @p mbarrier.arrive.shared.b64 _,[%0];}" ::"r"(staged + (flip >> 11)), "r"(l0 & r) : "memory");
    flip ^= r << 14;
  }
  __device__ __forceinline__ void half(const float* d, int J, int r) {
#define PRE(i, n, c1, c2) gelu_h(fmaf(r ? d[4 + i] : d[i], i < 2 ? s0 : s1, fmaf(n, c1, c2)))
    asm volatile("stmatrix.sync.aligned.m8n8.x2.shared.b16 [%0],{%1,%2};" ::"r"((st2 ^ ((J & 3) * 32 + r * 16)) + flip),
                 "r"(pk(PRE(0, n0, blo(c.x), blo(c.y)), PRE(1, n0, bhi(c.x), bhi(c.y)))), "r"(pk(PRE(2, n1, blo(c.x), blo(c.y)), PRE(3, n1, bhi(c.x), bhi(c.y)))) : "memory");
#undef PRE
    if ((J & 3) == 3) flush(r);
    cc += r ? 56 : 8;
    c = lds2u(cc);
  }
};

__global__ void __launch_bounds__(384, 1)
k_ffn(const __grid_constant__ FfnMaps mp, const bf16* __restrict__ b2) {
  using namespace ffn;
  extern __shared__ __align__(1024) char smem[];
  const uint32_t sb = (uint32_t)__cvta_generic_to_shared(smem);
  if (sb != 1024) __trap();
  const int tid = threadIdx.x, lane = tid & 31, wg = __shfl_sync(~0u, tid >> 7, 0);
  const uint32_t full = sb + BARS, emp = full + 48, xbar = full + 96, staged = full + 104, tile = full + 136;
  uint32_t fin = 0;
  if (tid >= 288 && tid < 320) fin = ld_acq(&g_fin);
  if (tid < 32) {
    unsigned sm, v = 0;
    asm("mov.u32 %0,%%smid;" : "=r"(sm));
    if (tid == 0) {
      v = atomicExch(&g_slot[sm & 255], 0);
      for (int i = 0; i < 6; i++) { mbar_init(full + i * 8, 1); mbar_init(emp + i * 8, 2); }
      mbar_init(xbar, 2);
      for (int i = 0; i < 2; i++) { mbar_init(staged + i * 8, 8); mbar_init(staged + 16 + i * 8, 1); }
      FENCE_ASYNC_SMEM();
    }
    v = __shfl_sync(~0u, v, 0);
    if (!v) {
      wait_cnt(&g_fin, 128);
      for (int it = 0; !v; it++) {
        const uint4 a = ldg_rlx4(g_slot + tid * 8), b = ldg_rlx4(g_slot + tid * 8 + 4);
        const uint32_t open = __ballot_sync(~0u, a.x | a.y | a.z | a.w | b.x | b.y | b.z | b.w);
        if (!open) break;
        if (it < 16) { __nanosleep(500); continue; }
        if (tid == __ffs(open) - 1) v = atomicExch(&g_slot[tid * 8 + (a.x ? 0 : a.y ? 1 : a.z ? 2 : a.w ? 3 : b.x ? 4 : b.y ? 5 : b.z ? 6 : 7)], 0);
        v = __shfl_sync(~0u, v, __ffs(open) - 1);
      }
    }
    if (tid == 0) sts1(tile, v);
  }
  if (tid == 256) asm volatile("prefetch.tensormap [%0];" ::"l"(&mp.wo) : "memory");
  __syncthreads();
  const int bid = __shfl_sync(~0u, lds1(tile), 0) - 1;
  if (bid < 0) return;
  PH(6);
  FT(1);
  const int rb = bid >> 3, nb = bid & 7;
  unsigned* cnt = g_cnt + rb * 128;
  if (wg == 2) {
    asm volatile("setmaxnreg.dec.sync.aligned.u32 " FRP ";");
    const int pw = __shfl_sync(~0u, (tid >> 5) & 3, 0);
    uint32_t ws = emp, wp = 1, fs = full;
    auto wait_free = [&]() { mbar_wait_q(ws, wp); ws += 8; if (ws == emp + 48) { ws = emp; wp ^= 1; } };
    auto step = [&]() { fs += 8; if (fs == full + 48) fs = full; };
#define K3(c) ((0x65230 >> (c) * 4) & 7)
#define KC(k) ((k) < 2 ? nb * 2 + (k) : (k) < 9 ? ((k) - 2 + ((k) - 2 >= nb)) * 2 : ((k) - 9 + ((k) - 9 >= nb)) * 2 + 1)
    if (pw == 0) {
      uint32_t d = sb + BR + 32768;
      auto put = [&](const CUtensorMap* m, int k, int c) {
        e_expect_tma3d(d, m, k * 64, c, fs, 32768);
        step();
        d += 16384;
        if (d == sb + STG) d = sb + BR;
      };
      int n = 0;
      auto stage_free = [&]() { if (!(n & 7) && n < 56) mbar_wait_q(staged + 16 + (n & 8), (n >> 4) & 1); n++; };
      auto align = [&]() {
        if (ALN && !((n - 1) & 7) && ((ALN >> ((n - 1) >> 3)) & 1)) {
          unsigned* c = g_cnt + 64 + ((n - 1) >> 3);
          if (lane == 0) red_rlx(c);
          for (int it = 0; ldg_rlx1(c) < 128 && it < 64; it++) {}
        }
      };
      FTP(3);
#pragma unroll 1
      for (int k = 0; k < 66; k++) { wait_free(); if (k < 64) put(&mp.wo, k, nb * 2); }
#pragma unroll 1
      for (int k = 0; k < 18; k++) {
        const int u = k >= 2 ? k - 2 : k, kt = KC(u);
        const bool ea = (k & ~1) == 2;
        wait_free();
        e_expect_tma3d(sb + BR + (k & 3) * 24576, ea ? &mp.w1a : &mp.w1b, kt * 64, nb * 7 + (ea ? 3 : 0), fs, ea ? 16384 : k < 2 ? 24576 : 40960);
        step();
      }
      d = sb + BR + 49152;
#pragma unroll 1
      for (int k = 2; k < 32; k++) {
        const int kt = k < 16 ? KC(k) : k & 15;
        stage_free();
        if (k == 2 || k == 9) n++;
        if (k != 7 && k != 8) wait_free();
        align();
        put(&mp.w1a, kt, nb * 7 + 3 + (k >> 4) * 2);
      }
#pragma unroll 1
      for (int c = 0; c < 5; c++)
#pragma unroll 1
        for (int k = K3(c), i = 0; k < 56; k += c < 2 && (i ^= 1) ? 1 : c < 2 ? 6 : 7) { stage_free(); wait_free(); align(); put(&mp.w2, k, nb * 2); }
    } else if (pw == 1) {
      FTP(5);
      if (fin < 128) wait_cnt(&g_fin, 128);
      FTP(6);
      uint32_t d = sb;
      auto put = [&](const uint4* A, bool ld) {
        wait_free();
        if (ld) e_bulk_ld(d, A, 16384, fs);
        step();
        d += 16384;
        if (d == sb + BR) d = sb;
      };
      const uint4* A = g_O + rb * 65536;
#pragma unroll 1
      for (int k = 0; k < 68; k++) put(A + k * 1024, k < 64);
      A = Y_TILE(rb, 0);
      uint32_t ready = 0;
#pragma unroll 1
      for (int k = 2; k < 48; k++) {
        if (k == 16) k = 18;
        const int kt = k < 32 ? KC(k & 15) : k & 15;
        for (int it = 0; !(ready >> ((kt >> 1) + (kt & 1) * 8) & 1); it++) {
          ready = __ballot_sync(~0u, ldg_rlx1(cnt + (lane & 7)) & ((lane & 8) ? 1 : 0x10000));
          if (it > SPIN_LIMIT) __trap();
        }
        if (k == 2) FTP(75);
        put(A + kt * 1024, true);
      }
      A = U_TILE(rb, 0);
#pragma unroll 1
      for (int c = 0; c < 5; c++) {
        for (int it = 0; ldg_rlx1(cnt + 32 + c) < 8; it++) if (it > SPIN_LIMIT) __trap();
#pragma unroll 1
        for (int k = K3(c), i = 0; k < 56; k += c < 2 && (i ^= 1) ? 1 : c < 2 ? 6 : 7) put(A + k * 1024, true);
      }
    } else if (pw == 2) {
      for (int i = 0; i < XDL; i++) {
        mbar_wait_q(emp, i & 1);
      }
      if (lane == 0) {
        mbar_expect(xbar, 32768);
        tma2d(sb + STG, &mp.x, nb * 128, rb * 128, xbar);
        tma2d(sb + STG + 16384, &mp.x, nb * 128 + 64, rb * 128, xbar);
      }
      asm volatile("griddepcontrol.wait;" ::: "memory");
      if (lane < 16) g_modp[bid * 16 + lane] = make_uint4(0, 0, 0, 0);
      if (lane >= 16 && bid == 0) { g_hcnt = 0; g_mcnt = 0; g_hf[lane & 3] = 0; }
      if (lane == 0) {
#pragma unroll 1
        for (int g = 1; g < 9; g++) {
          if (g == 1) mbar_wait(staged + 8, 0); else { mbar_wait_q(staged + (g & 1) * 8, (g >> 1) & 1); FENCE_ASYNC_SMEM(); }
          bulk_st(g == 1 ? Y_TILE(rb, nb * 2 + 1) : U_TILE(rb, nb * 7 + ((0x652431000ull >> g * 4) & 7)), sb + STG + (g & 1) * 16384, 16384);
          BULK_COMMIT();
          if (g != 2 && g != 4) { BULK_WAIT(0); red_rlx(g == 1 ? cnt + nb : cnt + 32 + (g < 6 ? g >> 2 : g - 4)); }
          BULK_WAIT_READ(0);
          mbar_arrive(staged + 16 + (g & 1) * 8);
        }
      }
    } else {
      const uint32_t prm = sb + PRM, pp = prm + (lane >> 3) * 64 + (lane & 1) * 32 + (lane & 6) * 2;
      const uint2 v2 = ((const uint2*)(b2 + nb * 128))[lane];
      sts1(pp + 768, v2.x); sts1(pp + 784, v2.y);
      asm volatile("griddepcontrol.wait;" ::: "memory");
      const float4* md = (const float4*)(g_mod + nb * 128) + lane;
      { const float4 ga = md[512]; sts1(pp, pk(ga.x, ga.y)); sts1(pp + 16, pk(ga.z, ga.w)); }
      { const float4 cb = md[1024]; sts1(pp + 256, pk(1.f + cb.x, 1.f + cb.y)); sts1(pp + 272, pk(1.f + cb.z, 1.f + cb.w)); }
      { const float4 gb = md[1280]; sts1(pp + 512, pk(gb.x, gb.y)); sts1(pp + 528, pk(gb.z, gb.w)); }
#pragma unroll 1
      for (int i = lane; i < 112; i += 32) { const uint4 c = g_cc[nb * 112 + i]; sts4(prm + 1024 + i * 16, c.x, c.y, c.z, c.w); }
      __syncwarp();
      if (lane == 0) {
        mbar_arrive(xbar);
        mbar_wait(staged, 0);
        bulk_st(Y_TILE(rb, nb * 2), sb + STG, 16384);
        BULK_COMMIT(); BULK_WAIT(0);
        asm volatile("red.relaxed.gpu.global.add.u32 [%0],0x10000;" ::"l"(cnt + nb) : "memory");
        mbar_arrive(staged + 16);
      }
      __syncwarp();
      mbar_wait_q(staged + 24, 0);
      mbar_wait_q(emp + 8, 1);
#pragma unroll 1
      for (int i = 0; i < 4; i++) {
        const uint4* sp = g_stat + (rb * 128 + i * 32 + lane) * 4;
        uint4 v[4];
        for (int it = 0;; it++) {
          uint32_t m = 0;
#pragma unroll
          for (int u = 0; u < 4; u++) { v[u] = ldg_rlx4(sp + u); m = max(max(m, max(v[u].x, v[u].y)), max(v[u].z, v[u].w)); }
          if (!__any_sync(~0u, m == ~0u)) break;
          if (it > SPIN_LIMIT) __trap();
        }
        float m = 0, q = 0;
#pragma unroll
        for (int u = 0; u < 4; u++) { m += F_(v[u].x) + F_(v[u].z); q += F_(v[u].y) + F_(v[u].w); }
        m *= 1.f / 1024;
        const float r = 0.5f * rsqrtf(fmaxf(q * (1.f / 1024) - m * m, 0.f) + 1e-5f);
        sts2(sb + STG + 16384 + (i * 32 + lane) * 8, U_(r), U_(-m * r));
      }
      __syncwarp();
      if (lane < 2) mbar_arrive(xbar);
    }
  } else {
    asm volatile("setmaxnreg.inc.sync.aligned.u32 " FRC ";");
    const int w = (tid >> 5) & 3, q = lane & 3;
    const uint32_t prm = sb + PRM + q * 16;
    const int row0 = wg * 64 + w * 16;
    FfnPipe p;
    p.full = full; p.emp = emp; p.ph = 0; p.aoff = wg * 8192; p.st = 0; p.sB = 2; p.prev = 0; p.leader = (tid & 127) == 0;
    FfnEpi e;
    const uint32_t stg = sb + STG + row0 * 128;
    e.st2 = stg + (lane & 15) * 128 + ((lane & 7) << 4);
    e.cc = sb + PRM + 1024 + q * 16; e.flip = 0; e.staged = staged; e.l0 = lane == 0;
    const uint32_t stw = e.st2 ^ (lane & 16);
    uint32_t x1[32];
    uint4* sp = g_stat + (rb * 128 + row0 + (lane >> 2)) * 4;
    float old[96], r0_, r1_;
    {
      float acc[64];
      p.issue<128>(acc, true); FT(8); p.next();
#pragma unroll 1
      for (int k = 1; k < 64; k++) { p.issue<128>(acc, false); FT(8 + k); p.retire(); }
      float xf[64], gf[32];
      uint32_t cb[16];
      mbar_wait(xbar, 0);
#pragma unroll
      for (int j = 0; j < 8; j++) {
        uint32_t xv[4];
        ldsm4(xv, (stw ^ ((j & 3) * 32)) + (j >> 2) * 16384);
#pragma unroll
        for (int i = 0; i < 4; i++) { xf[j * 8 + i * 2] = blo(xv[i]); xf[j * 8 + i * 2 + 1] = bhi(xv[i]); }
      }
#pragma unroll
      for (int i = 0; i < 4; i++) {
        const uint4 g = lds4(prm + i * 64), c = lds4(prm + 256 + i * 64);
        UNPK8(gf + i * 8, g);
        cb[i * 4] = c.x; cb[i * 4 + 1] = c.y; cb[i * 4 + 2] = c.z; cb[i * 4 + 3] = c.w;
      }
      acc_fence<64>(xf); acc_fence<32>(gf);
      WG_WAIT(0);
      p.release();
      acc_fence<64>(acc);
      PH(7); FT(72);
#pragma unroll
      for (int j = 0; j < 8; j++) {
        uint32_t* o = x1 + j * 4;
#pragma unroll
        for (int i = 0; i < 4; i++)
          o[i] = pk(fmaf(acc[j * 8 + i * 2], gf[j * 4 + (i & 2)], xf[j * 8 + i * 2]), fmaf(acc[j * 8 + i * 2 + 1], gf[j * 4 + (i & 2) + 1], xf[j * 8 + i * 2 + 1]));
        stsm4((stw ^ ((j & 3) * 32)) + (j >> 2) * 16384, mulbf(o[0], cb[j * 2]), mulbf(o[1], cb[j * 2]), mulbf(o[2], cb[j * 2 + 1]), mulbf(o[3], cb[j * 2 + 1]));
        if ((j & 3) == 3) { FENCE_ASYNC_SMEM(); e.flush(1); }
      }
      if (wg) BAR_SYNC(2, 128); else BAR_SYNC(3, 128);
    }
    PH(8); FT(73);
    float acc[64];
    {
      float* accC = old;
      p.sB = 0;
      p.issue<192>(accC, true, 1024 + STG); FT(80); p.next();
      p.issue<192>(accC, false, 1024 + STG + 16384); FT(81);
      FT(78);
      float s0 = 0, s1 = 0, q0 = 0, q1 = 0;
#define X1_FENCE _Pragma("unroll") for (int j = 0; j < 32; j++) asm volatile("" : "+r"(x1[j]));
      X1_FENCE
#pragma unroll
      for (int j = 0; j < 16; j++) {
        const float a = blo(x1[j * 2]), b = bhi(x1[j * 2]), c = blo(x1[j * 2 + 1]), d = bhi(x1[j * 2 + 1]);
        s0 += a + b; s1 += c + d; q0 = fmaf(a, a, fmaf(b, b, q0)); q1 = fmaf(c, c, fmaf(d, d, q1));
      }
#pragma unroll
      for (int o = 1; o < 4; o *= 2) { s0 += __shfl_xor_sync(~0u, s0, o); s1 += __shfl_xor_sync(~0u, s1, o); q0 += __shfl_xor_sync(~0u, q0, o); q1 += __shfl_xor_sync(~0u, q1, o); }
      if (q < 2) {
        uint32_t m = __float_as_uint(q ? s1 : s0), v = __float_as_uint(q ? q1 : q0);
        if (m == ~0u) m = 0x7fffffffu;
        if (v == ~0u) v = 0x7fffffffu;
        stg_rlx2((uint2*)(sp + q * 32) + nb, m, v);
      }
      X1_FENCE
      p.retire();
#pragma unroll 1
      for (int k = 0; k < 2; k++) { p.issue<128, 192>(acc, !k, 1024 + STG + k * 16384); p.retire(); }
#pragma unroll 1
      for (int k = 2; k < 15; k++) { p.issue<192>(accC, false); FT(80 + k); p.retire(); }
      p.issue<192>(accC, false); FT(95);
      mbar_wait(xbar, 1);
      const float2 u0 = lds2f(sb + STG + 16384 + (row0 + (lane >> 2)) * 8), u1 = lds2f(sb + STG + 16384 + (row0 + (lane >> 2)) * 8 + 64);
      r0_ = u0.x; e.n0 = u0.y; r1_ = u1.x; e.n1 = u1.y;
      e.c = lds2u(e.cc);
      p.retire();
      e.s0 = r0_; e.s1 = r1_;
      p.sB = 3;
    }
    PH(9);
    {
      auto pair = [&](int J, bool first, bool one, int fo) {
#pragma unroll 1
        for (int r = 0; r < 2; r++) {
          if (!(one && r)) { p.issue<128>(acc, first && !r); FT(fo + r); p.retire(); }
          acc_fence<8>(old + J * 8);
          e.half(old + J * 8, J, r);
        }
      };
#pragma unroll 1
      for (int i = 0; i < 3; i++) {
        if (i == 2) {
          e.s0 = r0_; e.s1 = r1_;
#pragma unroll
          for (int J = 8; J < 12; J++) pair(J, J == 8, false, 128 + (J - 8) * 2);
          e.cc += 512; e.c = lds2u(e.cc);
          e.s0 = e.s1 = 1.f;
        }
#pragma unroll
        for (int J = 0; J < 8; J++) pair(J, J == 0 && i == 1, !(J & 3) && !i, 96 + i * 16 + (i >> 1) * 8 + J * 2);
        if (i == 2) break;
        e.cc += i ? -768 : 256; e.c = lds2u(e.cc);
        WG_WAIT(0);
        acc_fence<64>(acc);
#pragma unroll
        for (int k = 0; k < 64; k++) old[k] = acc[k] * ((k & 2) ? r1_ : r0_);
        acc_fence<64>(old);
        e.s0 = e.s1 = 1.f;
        PH(10 + i);
      }
#pragma unroll 1
      for (int k = 24; k < 56; k++) {
        if (SKW && k == 56 - SKW && wg) BAR_SYNC(4, 256);
        p.issue<128>(acc, false); FT(128 + k);
        if (SKW && k == 55 && !wg) BAR_ARRIVE(4, 256);
        p.retire();
      }
      float xf[64], gf[32];
#pragma unroll
      for (int i = 0; i < 4; i++) {
        const uint4 g = lds4(prm + 512 + i * 64), h = lds4(prm + 768 + i * 64);
        float hf[8];
        UNPK8(gf + i * 8, g); UNPK8(hf, h);
#pragma unroll
        for (int u = 0; u < 8; u++) {
          const int c = (u >> 2) * 4 + (u & 2);
          xf[i * 16 + u * 2] = fmaf(gf[i * 8 + c], hf[c], blo(x1[i * 8 + u])); xf[i * 16 + u * 2 + 1] = fmaf(gf[i * 8 + c + 1], hf[c + 1], bhi(x1[i * 8 + u]));
        }
      }
      acc_fence<64>(xf); acc_fence<32>(gf);
      mbar_wait(staged + 24, 1);
      mbar_wait(staged + 16, 0);
      WG_WAIT(0);
      acc_fence<64>(acc);
      PH(13); FT(184);
#pragma unroll
      for (int j = 0; j < 8; j++) {
        uint32_t o[4];
#pragma unroll
        for (int i = 0; i < 4; i++)
          o[i] = pk(fmaf(acc[j * 8 + i * 2], gf[j * 4 + (i & 2)], xf[j * 8 + i * 2]), fmaf(acc[j * 8 + i * 2 + 1], gf[j * 4 + (i & 2) + 1], xf[j * 8 + i * 2 + 1]));
        stsm4((stw ^ ((j & 3) * 32)) + (j >> 2) * 16384, o[0], o[1], o[2], o[3]);
        if ((j & 3) == 3) {
          FENCE_ASYNC_SMEM();
          __syncwarp();
          if (lane == 0) { tma2d_st(&mp.out, nb * 128 + (j >> 2) * 64, rb * 128 + row0, stg + (j >> 2) * 16384); BULK_COMMIT(); }
        }
      }
      if (lane == 0) BULK_WAIT_READ(0);
      __syncwarp();
    }
  }
  PH(14); FT(185);
}

typedef CUresult (*EncFn)(CUtensorMap*, CUtensorMapDataType, cuuint32_t, void*, const cuuint64_t*, const cuuint64_t*, const cuuint32_t*,
                          const cuuint32_t*, CUtensorMapInterleave, CUtensorMapSwizzle, CUtensorMapL2promotion, CUtensorMapFloatOOBfill);
static void map2d(EncFn enc, CUtensorMap* m, const void* p, int rows, int cols, int boxRows) {
  cuuint64_t d[2] = {(cuuint64_t)cols, (cuuint64_t)rows}, s[1] = {(cuuint64_t)cols * 2};
  cuuint32_t b[2] = {64, (cuuint32_t)boxRows}, e[2] = {1, 1};
  enc(m, CU_TENSOR_MAP_DATA_TYPE_BFLOAT16, 2, (void*)p, d, s, b, e, CU_TENSOR_MAP_INTERLEAVE_NONE, CU_TENSOR_MAP_SWIZZLE_128B,
      CU_TENSOR_MAP_L2_PROMOTION_L2_128B, CU_TENSOR_MAP_FLOAT_OOB_FILL_NONE);
}
static void map3d(EncFn enc, CUtensorMap* m, const void* p, int rows, int cols, int nch) {
  cuuint64_t d[3] = {64, (cuuint64_t)rows, (cuuint64_t)(cols / 64)}, s[2] = {(cuuint64_t)cols * 2, 128};
  cuuint32_t b[3] = {64, 64, (cuuint32_t)nch}, e[3] = {1, 1, 1};
  enc(m, CU_TENSOR_MAP_DATA_TYPE_BFLOAT16, 3, (void*)p, d, s, b, e, CU_TENSOR_MAP_INTERLEAVE_NONE, CU_TENSOR_MAP_SWIZZLE_128B,
      CU_TENSOR_MAP_L2_PROMOTION_L2_128B, CU_TENSOR_MAP_FLOAT_OOB_FILL_NONE);
}

extern "C" void kernel_launch(void* const* d_in, const int* in_sizes, int n_in, void* d_out, int out_size) {
  const bf16* x = (const bf16*)d_in[0];
  const bf16* mem0 = (const bf16*)d_in[1];
  void* fn = nullptr;
  cudaDriverEntryPointQueryResult qr;
  cudaGetDriverEntryPoint("cuTensorMapEncodeTiled", &fn, cudaEnableDefault, &qr);
  EncFn enc = (EncFn)fn;
  FfnMaps fm = {};
  map3d(enc, &fm.wo, d_in[5], 4096, 1024, 2);
  map3d(enc, &fm.w1a, d_in[8], 1024, 3584, 2);
  map3d(enc, &fm.w1b, d_in[8], 1024, 3584, 3);
  map3d(enc, &fm.w2, d_in[10], 3584, 1024, 2);
  map2d(enc, &fm.x, x, 2048, 1024, 128);
  map2d(enc, &fm.out, d_out, 2048, 1024, 16);
  RecMaps rm = {};
  map2d(enc, &rm.wq, d_in[2], 1024, 4096, 128);
  map2d(enc, &rm.wk, d_in[3], 1024, 4096, 128);
  map2d(enc, &rm.wv, d_in[4], 1024, 4096, 16);
  map2d(enc, &rm.wo, d_in[5], 4096, 1024, 128);
  char* xc = nullptr;
  cudaGetSymbolAddress((void**)&xc, g_xc);
  xc += (0 - (uintptr_t)xc) & 0x1FFFFF;
  {
    cuuint64_t d[3] = {512, 6, 128}, sd[2] = {131072, 1024};
    cuuint32_t bi[3] = {64, 5, 8}, e[3] = {1, 1, 1};
    enc(&rm.ari, CU_TENSOR_MAP_DATA_TYPE_BFLOAT16, 3, xc + AR_OFF, d, sd, bi, e, CU_TENSOR_MAP_INTERLEAVE_NONE, CU_TENSOR_MAP_SWIZZLE_NONE,
        CU_TENSOR_MAP_L2_PROMOTION_NONE, CU_TENSOR_MAP_FLOAT_OOB_FILL_NONE);
  }
  cudaFuncSetAttribute(k_ffn, cudaFuncAttributeMaxDynamicSharedMemorySize, ffn::SMEM);
  cudaFuncSetAttribute(k_rec, cudaFuncAttributeMaxDynamicSharedMemorySize, rec::SMEM);
  cudaStream_t st = cudaStreamPerThread;
  int dF = 450, dA = 2700, dS = 300, dM = 120, dG = 350, dP = 24, dX = 48, dD = 350, dZ = 0, dZ2 = 1, dV = 370, dX2 = 0;
  k_rec<<<132, 512, rec::SMEM, st>>>(rm, mem0, x, (const bf16*)d_in[12], (const bf16*)d_in[13], (const char*)d_in[8], (const bf16*)d_in[9],
                                     (const char*)d_in[5], xc, dF, dA, dS, dM, dG, dP, dX, dD, dZ, dZ2, dV, dX2);
  cudaLaunchConfig_t cfg = {};
  cfg.gridDim = dim3(132); cfg.blockDim = dim3(384); cfg.dynamicSmemBytes = ffn::SMEM; cfg.stream = st;
  cudaLaunchAttribute at[1];
  at[0].id = cudaLaunchAttributeProgrammaticStreamSerialization;
  at[0].val.programmaticStreamSerializationAllowed = 1;
  cfg.attrs = at; cfg.numAttrs = 1;
  cudaLaunchKernelEx(&cfg, k_ffn, fm, (const bf16*)d_in[11]);
}
```

```cpp
#include <cuda_runtime.h>
#include <cuda.h>
#include <cuda_bf16.h>
#include <stdint.h>

typedef __nv_bfloat16 bf16;

__device__ __align__(16) float g_mod[6144];
__device__ __align__(1024) uint4 g_modp[4 * 512];
__device__ unsigned g_hcnt;
__device__ unsigned g_hf[4];
__device__ __align__(1024) uint4 g_h[2048 * 1024 / 8];
__device__ __align__(1024) uint4 g_O[2048 * 4096 / 8];
__device__ __align__(1024) uint4 g_h2[2048 * 1024 / 8];
__device__ __align__(1024) uint4 g_U[2048 * 3584 / 8];
__device__ __align__(1024) uint4 g_stat[2048 * 4];
__device__ __align__(1024) unsigned g_cnt[16 * 4 * 32];
__device__ unsigned g_mcnt;
__device__ unsigned g_slot[256];
__device__ unsigned g_fin;
__device__ __align__(16) uint4 g_cc[224 * 4];
__device__ __align__(1024) uint4 g_xc[44 * 16384];
__device__ __align__(1024) unsigned g_tm[4 * 256];
#define FT(i)
#define FTP(i)
#define PT(i)
#define PH(i)
#define RS(i)
#define RP(i)
#define RPN(i, s)
#define TSV(i, v)
#define TS(i)

#define FRC "232"
#define FRP "40"
#define FMAP (((g >> 2) * 4 + m) * 8 + ((g & 3) ^ ((g & 4) ? 3 : 0)) * 2 + (blockIdx.x & 1))
#define ALIAS 3
#define PFT 150000
#define PFS 104
#define PF0 13000
#define PFD 128
#define NF 3
#define NB0 4
#define PV0 4
#define T1L 1
#define NW0 5
#define VRF 3
#define VPC 1
#define WC0 10
#define WPE 2
#define ALN 0x80
#define SKW 3
#define L62 200
#define DLY(k)
#define UNC 1
#define XDL 6
#define PDS 61
#define P_NVR 5
#define P_NWP 9
#define P_NW1 7
#define RF_ 208
#define RA_ (488 - 2 * RF_)
#define WCH 2
#define NOP_ 2
#define SPIN_LIMIT (1 << 20)
__device__ __forceinline__ uint64_t mkdesc(uint32_t addr, uint32_t lbo, uint32_t sbo) {
  return (uint64_t)((addr & 0x3FFFF) >> 4) | ((uint64_t)(lbo >> 4) << 16) | ((uint64_t)(sbo >> 4) << 32) | (1ull << 62);
}
__device__ __forceinline__ void mbar_init(uint32_t a, int c) { asm volatile("mbarrier.init.shared.b64 [%0],%1;" ::"r"(a), "r"(c) : "memory"); }
__device__ __forceinline__ void mbar_wait(uint32_t a, uint32_t par) {
  asm volatile(
      "{.reg .pred p; .reg .u32 n;\n"
      "mov.u32 n, 0;\n"
      "W: mbarrier.try_wait.parity.shared.b64 p,[%0],%1;\n"
      "@p bra D;\n"
      "add.u32 n, n, 1;\n"
      "setp.lt.u32 p, n, %2;\n"
      "@p bra W;\n"
      "trap;\n"
      "D:}" ::"r"(a), "r"(par), "n"(SPIN_LIMIT) : "memory");
}
__device__ __forceinline__ void mbar_wait_q(uint32_t a, uint32_t par) {
  asm volatile(
      "{.reg .pred p; .reg .u32 n;\n"
      "mov.u32 n, 0;\n"
      "W: mbarrier.try_wait.parity.shared.b64 p,[%0],%1,4000;\n"
      "@p bra D;\n"
      "add.u32 n, n, 1;\n"
      "setp.lt.u32 p, n, %2;\n"
      "@p bra W;\n"
      "trap;\n"
      "D:}" ::"r"(a), "r"(par), "n"(SPIN_LIMIT / 16) : "memory");
}
__device__ __forceinline__ void mbar_expect(uint32_t a, uint32_t b) { asm volatile("mbarrier.arrive.expect_tx.shared.b64 _,[%0],%1;" ::"r"(a), "r"(b) : "memory"); }
__device__ __forceinline__ void mbar_arrive(uint32_t a) { asm volatile("mbarrier.arrive.shared.b64 _,[%0];" ::"r"(a) : "memory"); }
__device__ __forceinline__ uint32_t mapa(uint32_t a, uint32_t cta) { uint32_t r; asm("mapa.shared::cluster.u32 %0,%1,%2;" : "=r"(r) : "r"(a), "r"(cta)); return r; }
__device__ __forceinline__ void mbar_arrive_cl(uint32_t a) { asm volatile("mbarrier.arrive.shared::cluster.b64 _,[%0];" ::"r"(a) : "memory"); }
__device__ __forceinline__ void tma2d(uint32_t dst, const CUtensorMap* m, int c0, int c1, uint32_t mb) {
  asm volatile("cp.async.bulk.tensor.2d.shared::cluster.global.mbarrier::complete_tx::bytes [%0],[%1,{%2,%3}],[%4];" ::"r"(dst), "l"(m), "r"(c0), "r"(c1), "r"(mb) : "memory");
}
__device__ __forceinline__ void tma2d_pf(const CUtensorMap* m, int c0, int c1) {
  asm volatile("cp.async.bulk.prefetch.tensor.2d.L2.global [%0,{%1,%2}];" ::"l"(m), "r"(c0), "r"(c1) : "memory");
}
__device__ __forceinline__ void tma2d_st(const CUtensorMap* m, int c0, int c1, uint32_t src) {
  asm volatile("cp.async.bulk.tensor.2d.global.shared::cta.bulk_group [%0,{%1,%2}],[%3];" ::"l"(m), "r"(c0), "r"(c1), "r"(src) : "memory");
}
__device__ __forceinline__ void bulk_ld(uint32_t dst, const void* src, uint32_t n, uint32_t mb) {
  asm volatile("cp.async.bulk.shared::cluster.global.mbarrier::complete_tx::bytes [%0],[%1],%2,[%3];" ::"r"(dst), "l"(src), "r"(n), "r"(mb) : "memory");
}
__device__ __forceinline__ void bulk_st(void* dst, uint32_t src, uint32_t n) {
  asm volatile("cp.async.bulk.global.shared::cta.bulk_group [%0],[%1],%2;" ::"l"(dst), "r"(src), "r"(n) : "memory");
}
__device__ __forceinline__ void e_expect_tma3d(uint32_t dst, const CUtensorMap* m, int c1, int c2, uint32_t mb, uint32_t bytes) {
  asm volatile("{.reg .pred p; elect.sync _|p, 0xffffffff; @p mbarrier.arrive.expect_tx.shared.b64 _,[%4],%5;\n"
               "@p cp.async.bulk.tensor.3d.shared::cluster.global.mbarrier::complete_tx::bytes [%0],[%1,{0,%2,%3}],[%4];}" ::"r"(dst), "l"(m), "r"(c1), "r"(c2), "r"(mb), "r"(bytes) : "memory");
}
__device__ __forceinline__ void e_bulk_ld(uint32_t dst, const void* src, uint32_t n, uint32_t mb) {
  asm volatile("{.reg .pred p; elect.sync _|p, 0xffffffff; @p cp.async.bulk.shared::cluster.global.mbarrier::complete_tx::bytes [%0],[%1],%2,[%3];}" ::"r"(dst), "l"(src), "r"(n), "r"(mb) : "memory");
}
#define BULK_COMMIT() asm volatile("cp.async.bulk.commit_group;" ::: "memory")
#define BULK_WAIT_READ(n) asm volatile("cp.async.bulk.wait_group.read " #n ";" ::: "memory")
#define BULK_WAIT(n) asm volatile("cp.async.bulk.wait_group " #n ";" ::: "memory")
#define FENCE_ASYNC_SMEM() asm volatile("fence.proxy.async.shared::cta;" ::: "memory")
#define FENCE_ASYNC() asm volatile("fence.proxy.async;" ::: "memory")
#define WG_FENCE() asm volatile("wgmma.fence.sync.aligned;" ::: "memory")
#define WG_COMMIT() asm volatile("wgmma.commit_group.sync.aligned;" ::: "memory")
#define WG_WAIT(n) asm volatile("wgmma.wait_group.sync.aligned " #n ";" ::: "memory")
#define BAR_SYNC(id, n) asm volatile("bar.sync %0,%1;" ::"n"(id), "n"(n) : "memory")
#define BAR_ARRIVE(id, n) asm volatile("bar.arrive %0,%1;" ::"n"(id), "n"(n) : "memory")
#define SCHED_FENCE(k) asm volatile("{.reg .pred p; setp.ne.u32 p,%0,0; @p trap;}" ::"r"(mp.zero[(k) - 46]) : "memory")
#define CLUSTER_SYNC() asm volatile("barrier.cluster.arrive.relaxed.aligned; barrier.cluster.wait.aligned;" ::: "memory")
__device__ __forceinline__ uint32_t pk(float lo, float hi) { uint32_t r; asm("cvt.rn.bf16x2.f32 %0,%1,%2;" : "=r"(r) : "f"(hi), "f"(lo)); return r; }
__device__ __forceinline__ float blo(uint32_t v) { return __uint_as_float(v << 16); }
__device__ __forceinline__ float bhi(uint32_t v) { return __uint_as_float(v & 0xffff0000u); }
__device__ __forceinline__ void ldsm4(uint32_t* r, uint32_t a) {
  asm volatile("ldmatrix.sync.aligned.m8n8.x4.shared.b16 {%0,%1,%2,%3},[%4];" : "=r"(r[0]), "=r"(r[1]), "=r"(r[2]), "=r"(r[3]) : "r"(a) : "memory");
}
__device__ __forceinline__ void ldsm4t(uint32_t* r, uint32_t a) {
  asm volatile("ldmatrix.sync.aligned.m8n8.x4.trans.shared.b16 {%0,%1,%2,%3},[%4];" : "=r"(r[0]), "=r"(r[1]), "=r"(r[2]), "=r"(r[3]) : "r"(a) : "memory");
}
__device__ __forceinline__ void stsm4(uint32_t a, uint32_t r0, uint32_t r1, uint32_t r2, uint32_t r3) {
  asm volatile("stmatrix.sync.aligned.m8n8.x4.shared.b16 [%0],{%1,%2,%3,%4};" ::"r"(a), "r"(r0), "r"(r1), "r"(r2), "r"(r3) : "memory");
}
__device__ __forceinline__ void mma16(float* d, uint32_t a0, uint32_t a1, uint32_t a2, uint32_t a3, uint32_t b0, uint32_t b1) {
  asm volatile("mma.sync.aligned.m16n8k16.row.col.f32.bf16.bf16.f32 {%0,%1,%2,%3},{%4,%5,%6,%7},{%8,%9},{%0,%1,%2,%3};"
               : "+f"(d[0]), "+f"(d[1]), "+f"(d[2]), "+f"(d[3]) : "r"(a0), "r"(a1), "r"(a2), "r"(a3), "r"(b0), "r"(b1));
}
__device__ __forceinline__ void mma8(float* d, uint32_t a0, uint32_t a1, uint32_t b0) {
  asm volatile("mma.sync.aligned.m16n8k8.row.col.f32.bf16.bf16.f32 {%0,%1,%2,%3},{%4,%5},{%6},{%0,%1,%2,%3};"
               : "+f"(d[0]), "+f"(d[1]), "+f"(d[2]), "+f"(d[3]) : "r"(a0), "r"(a1), "r"(b0));
}
__device__ __forceinline__ float4 lds4f(uint32_t a) { float4 v; asm volatile("ld.shared.v4.f32 {%0,%1,%2,%3},[%4];" : "=f"(v.x), "=f"(v.y), "=f"(v.z), "=f"(v.w) : "r"(a) : "memory"); return v; }
__device__ __forceinline__ float2 lds2f(uint32_t a) { float2 v; asm volatile("ld.shared.v2.f32 {%0,%1},[%2];" : "=f"(v.x), "=f"(v.y) : "r"(a) : "memory"); return v; }
__device__ __forceinline__ uint4 lds4(uint32_t a) { uint4 v; asm volatile("ld.shared.v4.u32 {%0,%1,%2,%3},[%4];" : "=r"(v.x), "=r"(v.y), "=r"(v.z), "=r"(v.w) : "r"(a) : "memory"); return v; }
__device__ __forceinline__ uint2 lds2u(uint32_t a) { uint2 v; asm volatile("ld.shared.v2.u32 {%0,%1},[%2];" : "=r"(v.x), "=r"(v.y) : "r"(a) : "memory"); return v; }
__device__ __forceinline__ uint32_t lds1(uint32_t a) { uint32_t v; asm volatile("ld.shared.u32 %0,[%1];" : "=r"(v) : "r"(a) : "memory"); return v; }
__device__ __forceinline__ void sts4(uint32_t a, uint32_t x, uint32_t y, uint32_t z, uint32_t w) { asm volatile("st.shared.v4.u32 [%0],{%1,%2,%3,%4};" ::"r"(a), "r"(x), "r"(y), "r"(z), "r"(w) : "memory"); }
__device__ __forceinline__ void sts2(uint32_t a, uint32_t x, uint32_t y) { asm volatile("st.shared.v2.u32 [%0],{%1,%2};" ::"r"(a), "r"(x), "r"(y) : "memory"); }
__device__ __forceinline__ void sts1(uint32_t a, uint32_t x) { asm volatile("st.shared.u32 [%0],%1;" ::"r"(a), "r"(x) : "memory"); }
__device__ __forceinline__ void sta4(uint32_t a, const uint32_t* v, uint32_t mb) {
  asm volatile("st.async.shared::cluster.mbarrier::complete_tx::bytes.v4.b32 [%0],{%1,%2,%3,%4},[%5];" ::"r"(a), "r"(v[0]), "r"(v[1]), "r"(v[2]), "r"(v[3]), "r"(mb) : "memory");
}
__device__ __forceinline__ uint4 ldg_rlx4(const void* p) { uint4 v; asm volatile("ld.relaxed.gpu.global.v4.u32 {%0,%1,%2,%3},[%4];" : "=r"(v.x), "=r"(v.y), "=r"(v.z), "=r"(v.w) : "l"(p) : "memory"); return v; }
__device__ __forceinline__ uint32_t ldg_rlx1(const void* p) { uint32_t v; asm volatile("ld.relaxed.gpu.global.u32 %0,[%1];" : "=r"(v) : "l"(p) : "memory"); return v; }
__device__ __forceinline__ uint4 ldg_b128(const void* p) {
  uint4 v;
  asm volatile("{.reg .b128 t; .reg .b64 a,b; ld.relaxed.gpu.global.b128 t,[%4]; mov.b128 {a,b},t; mov.b64 {%0,%1},a; mov.b64 {%2,%3},b;}" : "=r"(v.x), "=r"(v.y), "=r"(v.z), "=r"(v.w) : "l"(p) : "memory");
  return v;
}
__device__ __forceinline__ void stg_b128(void* p, uint32_t x, uint32_t y, uint32_t z, uint32_t w) {
  asm volatile("{.reg .b128 t; .reg .b64 a,b; mov.b64 a,{%1,%2}; mov.b64 b,{%3,%4}; mov.b128 t,{a,b}; st.relaxed.gpu.global.b128 [%0],t;}" ::"l"(p), "r"(x), "r"(y), "r"(z), "r"(w) : "memory");
}
__device__ __forceinline__ void stg_rlx2(void* p, uint32_t x, uint32_t y) { asm volatile("st.relaxed.gpu.global.v2.u32 [%0],{%1,%2};" ::"l"(p), "r"(x), "r"(y) : "memory"); }
__device__ __forceinline__ unsigned ld_acq(const unsigned* p) { unsigned v; asm volatile("ld.acquire.gpu.global.u32 %0,[%1];" : "=r"(v) : "l"(p) : "memory"); return v; }
__device__ __forceinline__ void red_rel(unsigned* p) { asm volatile("red.release.gpu.global.add.u32 [%0],1;" ::"l"(p) : "memory"); }
__device__ __forceinline__ void red_rlx(unsigned* p) { asm volatile("red.relaxed.gpu.global.add.u32 [%0],1;" ::"l"(p) : "memory"); }
__device__ __forceinline__ void wait_cnt(const unsigned* p, unsigned n) { int it = 0; while (ld_acq(p) < n) { if (++it > SPIN_LIMIT) __trap(); } }
__device__ __forceinline__ uint32_t clk() { uint32_t c; asm volatile("mov.u32 %0,%%clock;" : "=r"(c)); return c; }
__device__ __forceinline__ uint32_t gtime() { uint32_t c; asm volatile("mov.u32 %0,%%globaltimer_lo;" : "=r"(c)); return c; }
__device__ __forceinline__ float ex2(float x) { float r; asm("ex2.approx.ftz.f32 %0,%1;" : "=f"(r) : "f"(x)); return r; }
__device__ __forceinline__ float silu(float x) { return x * __frcp_rn(1.f + __expf(-x)); }
__device__ __forceinline__ float rbf(float x) { return __bfloat162float(__float2bfloat16_rn(x)); }

__device__ __forceinline__ void wgmma_ss_n128(float* d, uint64_t a, uint64_t b, int sd) {
  asm volatile("{.reg .pred p; setp.ne.b32 p, %66, 0;\n"
    "wgmma.mma_async.sync.aligned.m64n128k16.f32.bf16.bf16 {%0,%1,%2,%3,%4,%5,%6,%7,%8,%9,%10,%11,%12,%13,%14,%15,%16,%17,%18,%19,%20,%21,%22,%23,%24,%25,%26,%27,%28,%29,%30,%31,%32,%33,%34,%35,%36,%37,%38,%39,%40,%41,%42,%43,%44,%45,%46,%47,%48,%49,%50,%51,%52,%53,%54,%55,%56,%57,%58,%59,%60,%61,%62,%63}, %64, %65, p, 1, 1, 0, 1;}\n"
    : "+f"(d[0]),"+f"(d[1]),"+f"(d[2]),"+f"(d[3]),"+f"(d[4]),"+f"(d[5]),"+f"(d[6]),"+f"(d[7]),
      "+f"(d[8]),"+f"(d[9]),"+f"(d[10]),"+f"(d[11]),"+f"(d[12]),"+f"(d[13]),"+f"(d[14]),"+f"(d[15]),
      "+f"(d[16]),"+f"(d[17]),"+f"(d[18]),"+f"(d[19]),"+f"(d[20]),"+f"(d[21]),"+f"(d[22]),"+f"(d[23]),
      "+f"(d[24]),"+f"(d[25]),"+f"(d[26]),"+f"(d[27]),"+f"(d[28]),"+f"(d[29]),"+f"(d[30]),"+f"(d[31]),
      "+f"(d[32]),"+f"(d[33]),"+f"(d[34]),"+f"(d[35]),"+f"(d[36]),"+f"(d[37]),"+f"(d[38]),"+f"(d[39]),
      "+f"(d[40]),"+f"(d[41]),"+f"(d[42]),"+f"(d[43]),"+f"(d[44]),"+f"(d[45]),"+f"(d[46]),"+f"(d[47]),
      "+f"(d[48]),"+f"(d[49]),"+f"(d[50]),"+f"(d[51]),"+f"(d[52]),"+f"(d[53]),"+f"(d[54]),"+f"(d[55]),
      "+f"(d[56]),"+f"(d[57]),"+f"(d[58]),"+f"(d[59]),"+f"(d[60]),"+f"(d[61]),"+f"(d[62]),"+f"(d[63])
    : "l"(a), "l"(b), "r"(sd));
}
__device__ __forceinline__ void wgmma_ss_n192(float* d, uint64_t a, uint64_t b, int sd) {
  asm volatile("{.reg .pred p; setp.ne.b32 p, %98, 0;\n"
    "wgmma.mma_async.sync.aligned.m64n192k16.f32.bf16.bf16 {%0,%1,%2,%3,%4,%5,%6,%7,%8,%9,%10,%11,%12,%13,%14,%15,%16,%17,%18,%19,%20,%21,%22,%23,%24,%25,%26,%27,%28,%29,%30,%31,%32,%33,%34,%35,%36,%37,%38,%39,%40,%41,%42,%43,%44,%45,%46,%47,%48,%49,%50,%51,%52,%53,%54,%55,%56,%57,%58,%59,%60,%61,%62,%63,%64,%65,%66,%67,%68,%69,%70,%71,%72,%73,%74,%75,%76,%77,%78,%79,%80,%81,%82,%83,%84,%85,%86,%87,%88,%89,%90,%91,%92,%93,%94,%95}, %96, %97, p, 1, 1, 0, 1;}\n"
    : "+f"(d[0]),"+f"(d[1]),"+f"(d[2]),"+f"(d[3]),"+f"(d[4]),"+f"(d[5]),"+f"(d[6]),"+f"(d[7]),
      "+f"(d[8]),"+f"(d[9]),"+f"(d[10]),"+f"(d[11]),"+f"(d[12]),"+f"(d[13]),"+f"(d[14]),"+f"(d[15]),
      "+f"(d[16]),"+f"(d[17]),"+f"(d[18]),"+f"(d[19]),"+f"(d[20]),"+f"(d[21]),"+f"(d[22]),"+f"(d[23]),
      "+f"(d[24]),"+f"(d[25]),"+f"(d[26]),"+f"(d[27]),"+f"(d[28]),"+f"(d[29]),"+f"(d[30]),"+f"(d[31]),
      "+f"(d[32]),"+f"(d[33]),"+f"(d[34]),"+f"(d[35]),"+f"(d[36]),"+f"(d[37]),"+f"(d[38]),"+f"(d[39]),
      "+f"(d[40]),"+f"(d[41]),"+f"(d[42]),"+f"(d[43]),"+f"(d[44]),"+f"(d[45]),"+f"(d[46]),"+f"(d[47]),
      "+f"(d[48]),"+f"(d[49]),"+f"(d[50]),"+f"(d[51]),"+f"(d[52]),"+f"(d[53]),"+f"(d[54]),"+f"(d[55]),
      "+f"(d[56]),"+f"(d[57]),"+f"(d[58]),"+f"(d[59]),"+f"(d[60]),"+f"(d[61]),"+f"(d[62]),"+f"(d[63]),
      "+f"(d[64]),"+f"(d[65]),"+f"(d[66]),"+f"(d[67]),"+f"(d[68]),"+f"(d[69]),"+f"(d[70]),"+f"(d[71]),
      "+f"(d[72]),"+f"(d[73]),"+f"(d[74]),"+f"(d[75]),"+f"(d[76]),"+f"(d[77]),"+f"(d[78]),"+f"(d[79]),
      "+f"(d[80]),"+f"(d[81]),"+f"(d[82]),"+f"(d[83]),"+f"(d[84]),"+f"(d[85]),"+f"(d[86]),"+f"(d[87]),
      "+f"(d[88]),"+f"(d[89]),"+f"(d[90]),"+f"(d[91]),"+f"(d[92]),"+f"(d[93]),"+f"(d[94]),"+f"(d[95])
    : "l"(a), "l"(b), "r"(sd));
}
__device__ __forceinline__ void wgmma_rs_n32(float* d, const uint32_t* a, uint64_t b, int sd) {
  asm volatile("{.reg .pred p; setp.ne.b32 p, %21, 0;\n"
    "wgmma.mma_async.sync.aligned.m64n32k16.f32.bf16.bf16 {%0,%1,%2,%3,%4,%5,%6,%7,%8,%9,%10,%11,%12,%13,%14,%15}, {%16,%17,%18,%19}, %20, p, 1, 1, 0;}\n"
    : "+f"(d[0]),"+f"(d[1]),"+f"(d[2]),"+f"(d[3]),"+f"(d[4]),"+f"(d[5]),"+f"(d[6]),"+f"(d[7]),
      "+f"(d[8]),"+f"(d[9]),"+f"(d[10]),"+f"(d[11]),"+f"(d[12]),"+f"(d[13]),"+f"(d[14]),"+f"(d[15])
    : "r"(a[0]), "r"(a[1]), "r"(a[2]), "r"(a[3]), "l"(b), "r"(sd));
}
__device__ __forceinline__ void wgmma_ssT_n32(float* d, uint64_t a, uint64_t b, int sd) {
  asm volatile("{.reg .pred p; setp.ne.b32 p, %18, 0;\n"
    "wgmma.mma_async.sync.aligned.m64n32k16.f32.bf16.bf16 {%0,%1,%2,%3,%4,%5,%6,%7,%8,%9,%10,%11,%12,%13,%14,%15}, %16, %17, p, 1, 1, 1, 0;}\n"
    : "+f"(d[0]),"+f"(d[1]),"+f"(d[2]),"+f"(d[3]),"+f"(d[4]),"+f"(d[5]),"+f"(d[6]),"+f"(d[7]),
      "+f"(d[8]),"+f"(d[9]),"+f"(d[10]),"+f"(d[11]),"+f"(d[12]),"+f"(d[13]),"+f"(d[14]),"+f"(d[15])
    : "l"(a), "l"(b), "r"(sd));
}

__device__ __forceinline__ void wgmma_rs_n32_z(float* d, const uint32_t* a, uint64_t b) {
  asm volatile("{.reg .pred p; setp.ne.b32 p, 0, 0;\n"
    "wgmma.mma_async.sync.aligned.m64n32k16.f32.bf16.bf16 {%0,%1,%2,%3,%4,%5,%6,%7,%8,%9,%10,%11,%12,%13,%14,%15}, {%16,%17,%18,%19}, %20, p, 1, 1, 0;}\n"
    : "=f"(d[0]),"=f"(d[1]),"=f"(d[2]),"=f"(d[3]),"=f"(d[4]),"=f"(d[5]),"=f"(d[6]),"=f"(d[7]),
      "=f"(d[8]),"=f"(d[9]),"=f"(d[10]),"=f"(d[11]),"=f"(d[12]),"=f"(d[13]),"=f"(d[14]),"=f"(d[15])
    : "r"(a[0]), "r"(a[1]), "r"(a[2]), "r"(a[3]), "l"(b));
}

namespace rec {
constexpr int NVR = P_NVR;
constexpr int NVS = 16 - NVR;
constexpr int NWP = P_NWP;
constexpr uint32_t WO = 0;
constexpr uint32_t XB = 65536;
constexpr uint32_t PK = XB + 32768;
constexpr uint32_t VX0 = PK + 24576;
constexpr uint32_t VX1 = VX0 + 4096;
constexpr uint32_t WVS = 131072;
constexpr uint32_t MEM = WVS + 2 * NVS * 2048;
constexpr uint32_t ARO = MEM + 10240;
constexpr uint32_t OB = ARO + 5120;
constexpr uint32_t QT = OB + 2048;
constexpr uint32_t KT = QT + 2048;
constexpr uint32_t RQ = KT + 6144;
constexpr uint32_t RK = RQ + 2048;
constexpr uint32_t SC = RK + 2048;
constexpr uint32_t OT = OB;
constexpr uint32_t TF = SC + 2048;
constexpr uint32_t PRE = MEM + 2 * NVR * 2048;
constexpr uint32_t TA = TF + 8192;
constexpr uint32_t RX = TA + 6144;
constexpr uint32_t VN = RX + 2048;
constexpr uint32_t BARS = VN + 4096;
constexpr uint32_t PACE = BARS + 18 * 8;
constexpr uint32_t SMEM = BARS + 512;
static_assert(PRE + 14336 <= BARS, "staging");
constexpr int NW1 = P_NW1;
static_assert(SMEM <= 232448, "smem");
constexpr int B_E = 2, B_SC = 3, B_S = 4, B_O = 5, B_F = 6, B_W = 7, B_C = 9, B_K = 10, B_Q = 1, B_S2 = 6, B_T2 = 9, B_P = 13, B_T = 14, B_R = 11, B_X = 12, B_V = 8;
constexpr int XC = 16384, X_RING = 131072, X_SC = 65536, X_TOK = 4096;
#define X_VX(i) (((i) >> 1) * 2048 + ((i) & 1) * 512)
#define X_VM(i) (X_VX(i) + 1024)
#define V_RING(n) (((n) & 1) * X_RING + ((n) & 2) * 2048)
#define V_TAG(n) ((~(n) >> 2) & 1)
}
struct RecMaps { CUtensorMap wq, wk, wv, wo, ari, vx; int zero[40]; };

#define F_(x) __uint_as_float(x)
#define U_(x) __float_as_uint(x)
#define AR_R(q) (24 + ((q) & 1) * 16 + ((q) >> 1) * 56)
#define AR_P(q) ((q) >> 1)
#define AR_ROW(i) (24 + ((i) & 1) * 16 + ((i) & 2) * 92 + (((i) >> 2) & 7) + ((i) >> 5) * 128)
constexpr size_t AR_OFF = 32 * 262144;
__device__ __forceinline__ void ar_fetch(uint32_t dst, const CUtensorMap* m, int slot, int half, uint32_t mb) {
  asm volatile("{.reg .pred p; elect.sync _|p, 0xffffffff; @p mbarrier.arrive.expect_tx.shared.b64 _,[%4],10240;\n"
               "@p cp.async.bulk.tensor.3d.shared::cluster.global.mbarrier::complete_tx::bytes [%0],[%1,{%2,%6,%3}],[%4];\n"
               "@p cp.async.bulk.tensor.3d.shared::cluster.global.mbarrier::complete_tx::bytes [%0+5120],[%1,{%2,%7,%5}],[%4];}"
               ::"r"(dst), "l"(m), "r"(slot * 64), "r"(AR_R(half * 2)), "r"(mb), "r"(AR_R(half * 2 + 1)), "r"(AR_P(half * 2)), "r"(AR_P(half * 2 + 1)) : "memory");
}
__device__ __forceinline__ uint4 exch_b128(void* p, uint32_t x, uint32_t y, uint32_t z, uint32_t w) {
  uint4 v;
  asm volatile("{.reg .b128 s, t; .reg .b64 a,b; mov.b64 a,{%5,%6}; mov.b64 b,{%7,%8}; mov.b128 s,{a,b}; atom.relaxed.gpu.global.exch.b128 t,[%4],s;"
               " mov.b128 {a,b},t; mov.b64 {%0,%1},a; mov.b64 {%2,%3},b;}" : "=r"(v.x), "=r"(v.y), "=r"(v.z), "=r"(v.w) : "l"(p), "r"(x), "r"(y), "r"(z), "r"(w) : "memory");
  return v;
}
#define CONSUME(v) do { if ((v) == 0x7fc12345u) sts1(sb + rec::BARS + 96, 0); } while (0)
__device__ __forceinline__ uint2 ldg_b64(const void* p) { uint2 v; asm volatile("{.reg .b64 t; ld.relaxed.gpu.global.b64 t,[%2]; mov.b64 {%0,%1},t;}" : "=r"(v.x), "=r"(v.y) : "l"(p) : "memory"); return v; }
__device__ __forceinline__ void stg_b64(void* p, uint32_t x, uint32_t y) { asm volatile("{.reg .b64 t; mov.b64 t,{%1,%2}; st.relaxed.gpu.global.b64 [%0],t;}" ::"l"(p), "r"(x), "r"(y) : "memory"); }
__device__ __forceinline__ uint32_t tagbad(uint32_t x, uint32_t y, uint32_t tag) { uint32_t r; asm("lop3.b32 %0,%1,%2,%3,0x7e;" : "=r"(r) : "r"(x), "r"(y), "r"(tag)); return r; }

__device__ __forceinline__ bool anybad(uint32_t a, uint32_t b, uint32_t c, uint32_t d, uint32_t e, uint32_t f, uint32_t g, uint32_t h, uint32_t tag) {
  uint32_t r;
  asm volatile("{.reg .b32 t,u,v,w; .reg .pred p; lop3.b32 t,%1,%2,%9,0x7e; lop3.b32 u,%3,%4,%9,0x7e; lop3.b32 v,%5,%6,%9,0x7e; lop3.b32 w,%7,%8,%9,0x7e;"
               " lop3.b32 t,t,u,v,0xfe; lop3.b32 t,t,w,1,0xa8; setp.ne.u32 p,t,0; vote.sync.any.pred p,p,0xffffffff; selp.u32 %0,1,0,p;}"
               : "=r"(r) : "r"(a), "r"(b), "r"(c), "r"(d), "r"(e), "r"(f), "r"(g), "r"(h), "r"(tag));
  return r;
}
__device__ __forceinline__ bool anybad(uint32_t a, uint32_t b, uint32_t c, uint32_t d, uint32_t tag) {
  uint32_t r;
  asm volatile("{.reg .b32 t,u; .reg .pred p; lop3.b32 t,%1,%2,%5,0x7e; lop3.b32 u,%3,%4,%5,0x7e;"
               " lop3.b32 t,t,u,1,0xa8; setp.ne.u32 p,t,0; vote.sync.any.pred p,p,0xffffffff; selp.u32 %0,1,0,p;}"
               : "=r"(r) : "r"(a), "r"(b), "r"(c), "r"(d), "r"(tag));
  return r;
}
#define BADS(r) anybad(r[0].x, r[0].y, r[1].x, r[1].y, r[2].x, r[2].y, r[3].x, r[3].y, tag)
constexpr float SCS = 0.08838834764831845f * 1.4426950408889634f / 16.f;
__device__ __forceinline__ uint32_t pkh(float lo, float hi, uint32_t tag) {
  uint32_t r;
  asm("{.reg .b32 t; cvt.rn.satfinite.f16x2.f32 t,%1,%2; lop3.b32 %0,t,0xfffffffe,%3,0xea;}" : "=r"(r) : "f"(hi), "f"(lo), "r"(tag));
  return r;
}
__device__ __forceinline__ uint32_t addh(uint32_t a, uint32_t b) { uint32_t r; asm("add.rn.f16x2 %0,%1,%2;" : "=r"(r) : "r"(a), "r"(b)); return r; }
__device__ __forceinline__ float hlo(uint32_t v) { float r; asm("{.reg .b16 a,b; mov.b32 {a,b},%1; cvt.f32.f16 %0,a;}" : "=f"(r) : "r"(v)); return r; }
__device__ __forceinline__ float hhi(uint32_t v) { float r; asm("{.reg .b16 a,b; mov.b32 {a,b},%1; cvt.f32.f16 %0,b;}" : "=f"(r) : "r"(v)); return r; }
__device__ __forceinline__ uint32_t ordh(uint32_t v) {
  uint32_t r;
  asm("{.reg .b32 m; prmt.b32 m,%1,0,0xbb99; lop3.b32 %0,%1,m,0x7fff7fff,0x78;}" : "=r"(r) : "r"(v));
  return r;
}
template <bool MASK>
__device__ __forceinline__ float4 softmax2(const uint2 (&r)[4], uint32_t mx, uint32_t my, uint32_t& k) {
  uint32_t x = addh(addh(r[0].x, r[1].x), addh(r[2].x, r[3].x)), y = addh(addh(r[0].y, r[1].y), addh(r[2].y, r[3].y));
  if (MASK) { x = addh(x, mx); y = addh(y, my); }
  asm("max.f16x2 %0,%1,%2;" : "=r"(k) : "r"(x), "r"(y));
  k = ordh(k);
  const int k0 = __reduce_max_sync(~0u, (int)(k << 16)), k1 = __reduce_max_sync(~0u, (int)k);
  const float m0 = hhi(k0 ^ ((k0 >> 31) & 0x7fff0000)) * -16.f, m1 = hhi(k1 ^ ((k1 >> 31) & 0x7fff0000)) * -16.f;
  return make_float4(ex2(fmaf(hlo(x), 16.f, m0)), ex2(fmaf(hhi(x), 16.f, m1)), ex2(fmaf(hlo(y), 16.f, m0)), ex2(fmaf(hhi(y), 16.f, m1)));
}
__device__ __forceinline__ char* mkp(uint32_t lo, uint32_t hi) { uint64_t r; asm("mov.b64 %0,{%1,%2};" : "=l"(r) : "r"(lo), "r"(hi)); return (char*)r; }
#define LO(p) ((uint32_t)(uint64_t)(p))
#define HI(p) ((uint32_t)((uint64_t)(p) >> 32))
__device__ __forceinline__ uint32_t mulbf(uint32_t a, uint32_t b) { uint32_t r; asm("mul.rn.bf16x2 %0,%1,%2;" : "=r"(r) : "r"(a), "r"(b)); return r; }
__device__ __forceinline__ uint32_t fmabf(uint32_t a, uint32_t b, uint32_t c) { uint32_t r; asm("fma.rn.bf16x2 %0,%1,%2,%3;" : "=r"(r) : "r"(a), "r"(b), "r"(c)); return r; }
__device__ __forceinline__ uint32_t addbf(uint32_t a, uint32_t b) { uint32_t r; asm("add.rn.bf16x2 %0,%1,%2;" : "=r"(r) : "r"(a), "r"(b)); return r; }
__device__ __forceinline__ void pv_mem(const uint32_t (&p)[4], uint32_t pm, const uint4 (&v)[4], const uint4 (&vn)[2], uint32_t (&O)[4]) {
  float o[4][4] = {{0, 0, 0, 0}, {0, 0, 0, 0}, {0, 0, 0, 0}, {0, 0, 0, 0}};
  mma16(o[0], v[0].x, v[0].y, v[0].z, v[0].w, p[0], p[1]);
  mma16(o[1], v[2].x, v[2].y, v[2].z, v[2].w, p[0], p[1]);
  mma16(o[2], v[1].x, v[1].y, v[1].z, v[1].w, p[2], p[3]);
  mma16(o[3], v[3].x, v[3].y, v[3].z, v[3].w, p[2], p[3]);
  mma16(o[0], vn[0].x, vn[0].y, vn[0].z, vn[0].w, pm, pm);
  mma16(o[1], vn[1].x, vn[1].y, vn[1].z, vn[1].w, pm, pm);
  O[0] = pk(o[0][0] + o[2][0], o[0][1] + o[2][1]); O[1] = pk(o[0][2] + o[2][2], o[0][3] + o[2][3]);
  O[2] = pk(o[1][0] + o[3][0], o[1][1] + o[3][1]); O[3] = pk(o[1][2] + o[3][2], o[1][3] + o[3][3]);
}
__device__ __forceinline__ void pv_tok(const uint32_t (&p)[4], uint32_t pm, const uint4 (&v)[4], const uint32_t (&vm)[4], uint32_t (&O)[4]) {
  float o[2][4] = {{0, 0, 0, 0}, {0, 0, 0, 0}}, sum[4] = {0, 0, 0, 0};
  const uint32_t one = 0x3f803f80u;
  mma16(sum, one, one, one, one, p[0], p[1]);
  mma16(o[0], v[0].x, v[0].y, v[0].z, v[0].w, p[0], p[1]);
  mma16(o[1], v[2].x, v[2].y, v[2].z, v[2].w, p[0], p[1]);
  mma16(sum, one, one, one, one, p[2], p[3]);
  mma16(o[0], v[1].x, v[1].y, v[1].z, v[1].w, p[2], p[3]);
  mma16(o[1], v[3].x, v[3].y, v[3].z, v[3].w, p[2], p[3]);
  mma8(sum, one, one, pm);
  mma8(o[0], vm[0], vm[1], pm);
  mma8(o[1], vm[2], vm[3], pm);
  float i0, i1;
  asm("rcp.approx.ftz.f32 %0,%1;" : "=f"(i0) : "f"(sum[0]));
  asm("rcp.approx.ftz.f32 %0,%1;" : "=f"(i1) : "f"(sum[1]));
  O[0] = pk(o[0][0] * i0, o[0][1] * i1); O[1] = pk(o[0][2] * i0, o[0][3] * i1);
  O[2] = pk(o[1][0] * i0, o[1][1] * i1); O[3] = pk(o[1][2] * i0, o[1][3] * i1);
}
__device__ __forceinline__ uint32_t sum4bf(uint32_t a, uint32_t b, uint32_t c, uint32_t d) { return addbf(addbf(a, b), addbf(c, d)); }
template <int OFF>
__device__ __forceinline__ void sta1(uint32_t a, uint32_t v, uint32_t mb) {
  asm volatile("st.async.shared::cluster.mbarrier::complete_tx::bytes.b32 [%0+%3],%1,[%2];" ::"r"(a), "r"(v), "r"(mb), "n"(OFF) : "memory");
}

__device__ __forceinline__ void wait_time(uint32_t t) { while ((int)(gtime() - t) < 0) __nanosleep(64); }
__device__ __noinline__ void rec_prefetch(const char* wmod, const char* w1, const char* x, const char* wo) {
  const int hb = blockIdx.x - 128;
  const uint32_t t0 = gtime();
  uint32_t t = t0 + PF0;
#pragma unroll 1
  for (int job = 0; job < (PFT ? 5 : 3); job++) {
    const char* p = job == 0 ? x + (6 + hb) * 65536 : job == 1 ? wmod + hb * 12288 + 4096 : job == 2 ? w1 + hb * 7168 : job == 3 ? x + hb * 8192 : wo + (1020 + hb) * 8192;
    const int n = job == 0 ? 120 - (hb & 2) * 4 : job == 3 ? 128 : 256, d = job == 0 ? 8192 : job == 1 ? 49152 : job == 2 ? 28672 : job == 3 ? 32768 : -32768;
    if (job == 3) t = t0 + PFT;
    PT(8 + job);
#pragma unroll 1
    for (int i = 0; i < n; i++) {
      wait_time(t);
      asm volatile("cp.async.bulk.prefetch.L2.global [%0], %1;" ::"l"(p), "r"(job == 2 ? 7168 : 8192) : "memory");
      p += !job && (i & 7) == 7 ? 204800 : d;
      t += job < 3 ? PFD : PFS;
      if (job && (i & 31) == 31 && ldg_rlx1(&g_fin)) return;
    }
  }
  PT(13);
}
__device__ __noinline__ void rec_helper(uint32_t sb, const bf16* cvec, const bf16* wmod, const char* w1, const bf16* b1, uint32_t t0) {
  const int tid = threadIdx.x, hb = blockIdx.x - 128;
  PT(1);
  for (int i = tid; i < 1024; i += 256) sts1(sb + i * 8, U_(rbf(silu(__bfloat162float(cvec[i])))));
  for (int i = tid; i < 2048; i += 256) g_stat[hb * 2048 + i] = make_uint4(~0u, ~0u, ~0u, ~0u);
  for (int i = tid; i < 512; i += 256) g_cnt[hb * 512 + i] = 0;
#pragma unroll 1
  for (int job = 0; job < 2; job++) {
    wait_time(t0 + PF0 + (job ? 600 : 350) * PFD);
    BAR_SYNC(rec::B_F, 256);
    PT(2 + job * 5);
    const int n8 = job ? 112 : 128, rg = tid >= n8, cg = tid - rg * n8, pitch = job ? 448 : 768;
    const uint4* p = (const uint4*)(job ? w1 + hb * 1792 : (const char*)(wmod + 2048 + hb * 1024)) + rg * pitch + min(cg, n8 - 1);
    float a1[8] = {0, 0, 0, 0, 0, 0, 0, 0}, a2[8] = {0, 0, 0, 0, 0, 0, 0, 0};
#pragma unroll 1
    for (int r0 = rg; r0 < 1024; r0 += 32) {
      uint4 v[16];
#pragma unroll
      for (int i = 0; i < 16; i++) { v[i] = ldg_rlx4(p); p += 2 * pitch; }
#pragma unroll
      for (int i = 0; i < 16; i++) {
        const float2 f = lds2f(sb + (r0 + 2 * i) * 8);
        const float w[8] = {blo(v[i].x), bhi(v[i].x), blo(v[i].y), bhi(v[i].y), blo(v[i].z), bhi(v[i].z), blo(v[i].w), bhi(v[i].w)};
#pragma unroll
        for (int e = 0; e < 8; e++) { a1[e] += f.x * w[e]; a2[e] += f.y * w[e]; }
      }
    }
    const uint32_t rd = sb + 8192;
    if (cg < n8) {
#pragma unroll
      for (int e = 0; e < 8; e++) sts2(rd + rg * 8192 + (cg * 8 + e) * 8, U_(a1[e]), U_(a2[e]));
    }
    BAR_SYNC(rec::B_F, 256);
    if (job == 0) {
      for (int i = tid; i < 1024; i += 256) g_mod[2048 + hb * 1024 + i] = rbf(F_(lds1(rd + i * 8)) + F_(lds1(rd + 8192 + i * 8)));
      BAR_SYNC(rec::B_F, 256);
      PT(6);
      if (tid == 0) { red_rel(&g_mcnt); wait_cnt(&g_mcnt, 4); }
      BAR_SYNC(rec::B_F, 256);
      for (int i = tid; i < 1024; i += 256) sts2(sb + i * 8, U_(rbf(1.f + __ldcg(g_mod + 4096 + i))), U_(__ldcg(g_mod + 3072 + i)));
    } else {
      for (int i = tid; i < 448; i += 256) {
        const int gn = hb * 896 + i * 2;
        const uint32_t bb = *(const uint32_t*)(b1 + gn);
        const float4 u = lds4f(rd + i * 16), w = lds4f(rd + 8192 + i * 16);
        ((uint2*)g_cc)[(gn >> 4) * 8 + ((gn >> 1) & 3) * 2 + ((gn >> 3) & 1)] = make_uint2(pk(u.x + w.x, u.z + w.z), pk(0.5f * (u.y + w.y + blo(bb)), 0.5f * (u.w + w.w + bhi(bb))));
      }
      PT(4);
    }
  }
}

__global__ void __cluster_dims__(2, 1, 1) __launch_bounds__(512, 1)
k_rec(const __grid_constant__ RecMaps mp, const bf16* __restrict__ mem0, const bf16* __restrict__ x, const bf16* __restrict__ cvec,
      const bf16* __restrict__ wmod, const char* __restrict__ w1, const bf16* __restrict__ b1, const char* __restrict__ wo, char* xc, int dF, int dA, int dS, int dM, int dG, int dP, int dX, int dD, int dZ, int dQ, int dV, int dX2) {
  using namespace rec;
  extern __shared__ __align__(1024) char smem[];
  const uint32_t sb = (uint32_t)__cvta_generic_to_shared(smem);
  if ((sb & 0x3FFFF) != 1024) __trap();
  PH(0); RS(0); if (threadIdx.x == 0) PT(0);
  if (threadIdx.x == 0) {
    int b = blockIdx.x;
    if (b >= 8 && b < 128) {
      const int t = (b >> 1) - 4, u = t - 32;
      b = 2 * (t < 32 ? 4 + (t & 16) + (t & 7) * 2 + ((t >> 3) & 1) : 36 + (u / 14) * 14 + (u % 7) * 2 + ((u / 7) & 1)) + (b & 1);
    }
    sts1(sb + rec::PACE + 24, b);
    const int c = blockIdx.x >> 1, l = c < 36 ? (c - 4) & 7 : (c - 36) % 7, m = c < 4 ? c : c < 36 ? (c - 4) >> 3 : (c - 36) / 7;
    const int g = c < 4 ? 15 : (l >> 1) * 4 + (l & 1) + (c < 36 ? 0 : 2);
    unsigned sm;
    asm("mov.u32 %0,%%smid;" : "=r"(sm));
    if (c < 64) g_slot[sm & 255] = 1 + FMAP;
  }
#define ROLE_REFRESH { asm volatile("mov.u32 %0,%%tid.x;" : "=r"(tid)); wid = __shfl_sync(~0u, tid >> 5, 0); b = __shfl_sync(~0u, lds1(sb + PACE + 24), 0); }
#define ROLE_VARS int tid; asm volatile("mov.u32 %0,%%tid.x;" : "=r"(tid)); \
    int wid = __shfl_sync(~0u, tid >> 5, 0), b = __shfl_sync(~0u, lds1(sb + PACE + 24), 0);
#define wg (wid >> 2)
#define iw (wid & 3)
#define h (b >> 2)
#define j (b & 3)
#define a (b & 1)
#define bb ((b >> 1) & 1)
  const uint32_t wbar = sb + BARS + 48, obar = wbar + 8;
  if (threadIdx.x == 256) {
    for (int i = 0; i < 18; i++) if (i != 12) mbar_init(sb + BARS + i * 8, i == 3 || i == 8 || i == 9 || i == 10 ? 2 : 1);
    for (int i = 0; i < 3; i++) mbar_init(sb + PACE + i * 8, 1);
    asm volatile("fence.mbarrier_init.release.cluster;" ::: "memory");
    FENCE_ASYNC_SMEM();
    mbar_expect(sb + BARS, 2048);
    mbar_expect(sb + BARS + 16, 4096);
    mbar_expect(sb + BARS + 32, 4096);
    mbar_expect(sb + BARS + 40, 4096);
  }
  __syncthreads();
  asm volatile("barrier.cluster.arrive.relaxed.aligned;" ::: "memory");
#define lane ((int)(l16 >> 4))
#define l16 (L16 & 0x1f0)
#define PIN(x) __shfl_xor_sync(~0u, (uint32_t)(x), 0)
#define X_LOAD(n, w, u) \
        asm volatile("{.reg .pred p; elect.sync _|p, 0xffffffff; @p mbarrier.arrive.expect_tx.shared.b64 _,[%2],8192;\n" \
                     "@p cp.async.bulk.shared::cluster.global.mbarrier::complete_tx::bytes [%0],[%1],8192,[%2];}" ::"r"(sb + XB + (w) * 16384 + (u) * 8192), \
                     "l"(g_h + (n) * 4096 + a * 2048 + (w) * 1024 + (u) * 512), "r"(sb + BARS + 64 + (w) * 8) : "memory")
#define lpub ((L16 & 0x30) * 64 + ((L16 >> 3) & 0x38))
#define lrow ((L16 & 0x70) + (((L16 >> 3) ^ L16) & 0x70 & ~((L16 >> 3) & 0x40) ? L16 & 0x180 : 512))

  const int role = __shfl_sync(~0u, threadIdx.x >> 7, 0);
  if (role < 2) {
    asm volatile("setmaxnreg.inc.sync.aligned.u32 %0;" ::"n"(RF_));
    ROLE_VARS
    uint32_t L16 = __shfl_sync(~0u, sb + (tid & 31) * 16, tid & 31);
    uint32_t wQ[16][4], wK[16][4], wV[NVR][4];
    uint32_t frag = sb + ((lane & 7) + (lane >> 4) * 8) * 128 + (((iw * 2 + ((lane >> 3) & 1)) ^ (lane & 7)) << 4);
#define QSW (a ? 0 : 64)
    {
      const bool spare = b >= 128;
      const uint32_t t0 = gtime();
      uint4 xr[16];
      int seg = spare ? b - 126 : wg;
      const int half = spare ? wg : a;
      auto x_fetch = [&]() {
        const uint4* px = (const uint4*)x + (seg * 32 + iw * 8 + (lane >> 2)) * 128 + half * 64 + (lane & 3);
#pragma unroll
        for (int i = 0; i < 16; i++) xr[i] = __ldg(px + i * 4);
      };
      if (!spare) {
        uint4 wm[8];
        const uint4* pw = (const uint4*)(wmod + (size_t)((b >> 5) * 256 + (tid >> 3)) * 6144 + (b & 31) * 64) + (tid & 7);
        const float cs = __bfloat162float(cvec[(b >> 5) * 256 + tid]);
#pragma unroll
        for (int i = 0; i < 8; i++) wm[i] = __ldcs(pw + (size_t)i * 32 * 768);
        float* sc = (float*)(smem + PRE);
        sc[tid] = rbf(silu(cs));
        PT(1);
        BAR_SYNC(B_F, 256);
        float acc[8] = {0, 0, 0, 0, 0, 0, 0, 0};
#pragma unroll
        for (int i = 0; i < 8; i++) {
          const float f = sc[i * 32 + (tid >> 3)];
          acc[0] += f * blo(wm[i].x); acc[1] += f * bhi(wm[i].x); acc[2] += f * blo(wm[i].y); acc[3] += f * bhi(wm[i].y);
          acc[4] += f * blo(wm[i].z); acc[5] += f * bhi(wm[i].z); acc[6] += f * blo(wm[i].w); acc[7] += f * bhi(wm[i].w);
        }
#pragma unroll
        for (int i = 0; i < 8; i++) { acc[i] += __shfl_xor_sync(~0u, acc[i], 8); acc[i] += __shfl_xor_sync(~0u, acc[i], 16); }
        float* red = sc + 1024;
        if ((tid & 31) < 8) {
#pragma unroll
          for (int i = 0; i < 8; i++) red[(tid >> 5) * 64 + (tid & 7) * 8 + i] = acc[i];
        }
        BAR_SYNC(B_F, 256);
        PT(2);
        if (tid < 64) {
          float t = 0;
#pragma unroll
          for (int i = 0; i < 8; i++) t += red[i * 64 + tid];
          asm volatile("st.relaxed.gpu.global.u32 [%0],%1;" ::"l"((unsigned*)g_modp + (b >> 5) * 2048 + (b & 31) * 64 + tid), "r"(U_(t) | 1u) : "memory");
        }
      } else {
        asm volatile("griddepcontrol.launch_dependents;");
      }
      x_fetch();
      const uint32_t md = sb + PRE + 6144, rx = mapa(sb, a ^ !spare);
      asm volatile("barrier.cluster.wait.aligned;" ::: "memory");
      if (!spare) {
        mbar_wait(sb + BARS + 88, 0);
#pragma unroll
        for (int i = 0; i < 16; i++) ldsm4t(wQ[i], (frag ^ QSW) + WO + wg * 32768 + i * 2048);
      }
      PT(4);
#pragma unroll 1
      for (int it = 0;; it++) {
        if (tid == 0) mbar_expect(sb + BARS + 104, 512);
        float c[4][4] = {{0, 0, 0, 0}, {0, 0, 0, 0}, {0, 0, 0, 0}, {0, 0, 0, 0}};
#pragma unroll
        for (int i = 0; i < 16; i++) {
          mma16(c[(i & 1) * 2], xr[i].x, 0x3f803f80u, xr[i].y, 0x3f803f80u, xr[i].x, xr[i].y);
          mma16(c[(i & 1) * 2 + 1], xr[i].z, 0x3f803f80u, xr[i].w, 0x3f803f80u, xr[i].z, xr[i].w);
        }
#pragma unroll
        for (int e = 0; e < 4; e++) c[0][e] = (c[0][e] + c[1][e]) + (c[2][e] + c[3][e]);
        const int src = (lane & 28) + (lane >> 3);
        const float sq = __shfl_sync(~0u, (lane & 4) ? c[0][1] : c[0][0], src), sm = __shfl_sync(~0u, (lane & 4) ? c[0][3] : c[0][2], src);
        if ((lane & 3) < 2) sta1<0>(rx + PRE + 10240 + (wid ^ (spare * 4)) * 64 + (lane >> 2) * 8 + (lane & 1) * 4, U_((lane & 1) ? sm : sq), rx + BARS + 104);
        mbar_wait(sb + BARS + 104, it & 1);
        const float2 ot = lds2f(sb + PRE + 10240 + wid * 64 + (lane >> 2) * 8);
        const float mean = (sm + ot.y) * (1.f / 1024);
        const float rs = rsqrtf(fmaxf((sq + ot.x) * (1.f / 1024) - mean * mean, 0.f) + 1e-5f), nm = -mean * rs;
        const uint32_t rh = pk(rs, rs), rl = pk(rs - blo(rh), rs - blo(rh)), n2 = pk(nm, nm);
#define NRM(v) v = fmabf(v, rh, fmabf(v, rl, n2))
#pragma unroll
        for (int i = 0; i < 16; i++) { NRM(xr[i].x); NRM(xr[i].y); NRM(xr[i].z); NRM(xr[i].w); }
        if (!it) {
          PT(3);
#pragma unroll 1
          for (int i = 0; i < 2; i++) {
            uint4 p[4];
            for (int n = 0;; n++) {
#pragma unroll
              for (int e = 0; e < 4; e++) p[e] = ldg_rlx4(g_modp + e * 512 + i * 256 + tid);
              uint32_t ok = 1;
#pragma unroll
              for (int e = 0; e < 4; e++) ok &= p[e].x & p[e].y & p[e].z & p[e].w;
              if (__all_sync(~0u, ok) || n > SPIN_LIMIT / 16) break;
              __nanosleep(100);
            }
#define MSUM(e) (i + rbf((F_(p[0].e) + F_(p[1].e)) + (F_(p[2].e) + F_(p[3].e))))
            sts2(md + i * 2048 + tid * 8, pk(MSUM(x), MSUM(y)), pk(MSUM(z), MSUM(w)));
          }
          BAR_SYNC(B_F, 256);
          PT(5);
        }
        const int e0 = (iw * 8 + (lane >> 2)) * 8 + ((lane & 3) ^ (lane >> 2));
        uint4* dst = g_h + seg * 4096 + half * 2048;
#pragma unroll
        for (int i = 0; i < 16; i++) {
          const uint32_t ma = md + half * 1024 + (lane & 3) * 16 + i * 64;
          const uint4 sv = lds4(ma), cv = lds4(ma + 2048);
          xr[i] = make_uint4(fmabf(xr[i].x, cv.x, sv.x), fmabf(xr[i].y, cv.y, sv.y), fmabf(xr[i].z, cv.z, sv.z), fmabf(xr[i].w, cv.w, sv.w));
        }
        if (!spare) {
#pragma unroll
          for (int i = 0; i < 16; i++) sts4(sb + WO + wg * 32768 + (e0 ^ ((i & 1) * 4)) * 16 + (i >> 1) * 4096, xr[i].x, xr[i].y, xr[i].z, xr[i].w);
          break;
        }
#pragma unroll
        for (int i = 0; i < 16; i++) dst[(e0 ^ ((i & 1) * 4)) + (i >> 1) * 256] = xr[i];
        seg += 4;
        if (seg < 64) x_fetch();
        FENCE_ASYNC();
        BAR_SYNC(B_F, 256);
        if (tid == 0) red_rlx(g_hf + b - 128);
        if (seg >= 64) break;
      }
      if (spare) { rec_helper(sb, cvec, wmod, w1, b1, t0); return; }
      PH(1); PH(2); PT(6);
    }
    ROLE_REFRESH
#define ownv ((iw >> 1) == a)
#define owner (iw >= 2)
#define oi (wid & 1)
    {
      const uint32_t rsb = mapa(sb, owner ? a : a ^ 1);
      const uint32_t pp = rsb + PK + (owner ? 0 : 12288) + (oi * 2048 + wg * 1024) + l16;
      const uint32_t mb = sb + MEM + wg * 5120;
      sts4(L16 + TF + wid * 512, mb + lrow, owner ? L16 + (lane >> 4) * (RK - RQ - 256) + RQ + oi * 1024 + wg * 256 : rsb + RQ + oi * 1024 + 512 + wg * 256 + (l16 >> 2),
           L16 + OB, frag + wg * NVS * 2048);
      sts4(L16 + TF + 4096 + wid * 512, sb + WO + (wid >> 1) * 16384 + ((lane & 7) + (lane >> 4) * 8) * 128 + ((((wid & 1) * 4 + ((lane >> 3) & 1)) ^ (lane & 7)) << 4),
           sb + ARO + wid * 640 + lrow, pp, LO(xc) + h * 262144 + (bb * 2 + (iw >> 1)) * XC + X_VM(0) + oi * 2048 + a * 256 + (l16 >> 1));
    }
    uint32_t tp = L16 + TF + wid * 512;
    auto park_ptr = [&]() { return lds1(tp + 4096 + 8); };
    auto park_w = [&](const uint32_t* w, int m, uint32_t d) {
      if (m == 2) d += (sb & 0x1000000) ? 0 : owner ? 0x1003000 : -0x1003000;
      if (m == 2 ? ownv : owner) {
        sts4(d + m * 4096, w[0], w[1], w[2], w[3]); sts4(d + m * 4096 + 512, w[4], w[5], w[6], w[7]);
      } else {
        const uint32_t pb = (d & 0xff000000u) | (1024 + BARS + (m ? 24 + m * 8 : 16));
        sta4(d + m * 4096, w, pb); sta4(d + m * 4096 + 512, w + 4, pb);
      }
    };
    auto park = [&](const float* f, int m, int n, uint32_t d) {
      uint32_t w[8];
#pragma unroll
      for (int i = 0; i < 8; i++) w[i] = pk(f[2 * i], f[2 * i + 1]);
      park_w(w, m, d);
    };
#define D64(lo) (0x4000004000000000ull | (uint32_t)(lo))
#define XD(i) D64(x | (((i) >> 2) * 256 + ((i) & 3) * 2))
    auto xdesc = [&](uint32_t xb) { return ((uint32_t)__shfl_sync(~0u, 1024 + xb + wg * 16384, 0) >> 4) | 0x10000u; };
    auto rs_issue = [&](float* acc, const uint32_t (&w)[16][4], uint32_t xb, bool fence) {
      const uint32_t x = xdesc(xb);
      if (fence) WG_FENCE();
      wgmma_rs_n32_z(acc, w[0], XD(0));
#pragma unroll
      for (int i = 1; i < 16; i++) wgmma_rs_n32(acc, w[i], XD(i), 1);
      WG_COMMIT();
    };
    auto v_issue = [&](float* acc, uint32_t xb, bool fence) {
      const uint32_t dv = ((uint32_t)__shfl_sync(~0u, 1024 + WVS + wg * NVS * 2048, 0) >> 4) | 0x10000u, x = xdesc(xb);
      if (fence) WG_FENCE();
      wgmma_rs_n32_z(acc, wV[0], XD(0));
#pragma unroll
      for (int i = 1; i < VRF; i++) wgmma_rs_n32(acc, wV[i], XD(i), 1);
#pragma unroll
      for (int i = NVR; i < 16; i++) wgmma_ssT_n32(acc, D64(dv + (i - NVR) * 128), XD(i), 1);
#pragma unroll
      for (int i = VRF; i < NVR; i++) wgmma_rs_n32(acc, wV[i], XD(i), 1);
      WG_COMMIT();
    };
    uint32_t mA, vP[2][4];
#define V_AHEAD mA = lds1(tp); frag = lds1(tp + 12); ldsm4t(vP[0], frag + WVS + (15 - NVR) * 2048); ldsm4t(vP[1], frag + WVS + (14 - NVR) * 2048);
    auto vk_pass = [&](int n, uint32_t d, uint32_t xb, bool steady, auto between) {
      float acc[16], acc2[16];
      v_issue(acc, xb, true);
      rs_issue(acc2, wK, xb, false);
      between();
      const bool keep = !steady || !UNC || n < 64;
      if (steady ? keep : n) mbar_wait(sb + BARS + 80, (n - 1) & 1);
      WG_WAIT(1);
      if (keep) {
        park(acc, 2, n, d);
        if (steady) BAR_ARRIVE(B_K, 320);
      }
      V_AHEAD
      WG_WAIT(0);
      if (keep) park(acc2, 1, n, d + (VPC ? (vP[1][0] ^ mA) & dZ : 0));
    };
    uint32_t q0[8], q1[8];
    {
      float acc[16], acc2[16];
      FENCE_ASYNC_SMEM();
      BAR_SYNC(B_F, 256);
      rs_issue(acc, wQ, WO, true);
      rs_issue(acc2, wQ, WO + 32768, false);
      WG_WAIT(0);
#pragma unroll
      for (int i = 0; i < 8; i++) { q0[i] = pk(acc[2 * i], acc[2 * i + 1]); q1[i] = pk(acc2[2 * i], acc2[2 * i + 1]); }
    }
    mbar_wait(wbar, 0);
    PT(7);
#pragma unroll
    for (int i = 0; i < 16; i++) ldsm4t(wK[i], (frag ^ QSW) + XB + wg * 32768 + i * 2048);
#pragma unroll
    for (int i = 0; i < NVR; i++) ldsm4t(wV[i], frag + MEM + (wg * NVR + i) * 2048);
    FENCE_ASYNC_SMEM();
    PH(3); PT(8);
    CLUSTER_SYNC();
    PT(9);
    frag += wg * NVS * 2048;
    park_w(q0, 0, park_ptr());
    PT(10);
#pragma unroll 1
    for (int n = 0; n < 2; n++) {
      asm volatile("" : "+r"(wid));
      vk_pass(n, park_ptr(), n * XB, false, [&]() {
        if (n) {
          BAR_SYNC(B_C, 320);
          PT(12);
          mbar_wait(sb + BARS + 24, 0);
          park_w(q1, 0, park_ptr());
        }
      });
      if (n) break;
      PT(11);
      BAR_SYNC(B_C, 448);
      if (tid == 0) {
        mbar_expect(obar, 65536);
#pragma unroll 1
        for (int i = 0; i < 4; i++) tma2d(sb + WO + i * 16384, &mp.wo, j * 256 + i * 64, h * 128, obar);
      }
    }
    static_assert(WO == 0, "x");
    {
      BAR_ARRIVE(B_P, 384); BAR_ARRIVE(B_X, 320); BAR_ARRIVE(B_Q, 288);
    }
    PT(13);
    PH(4); RS(1); PT(14);
    ROLE_REFRESH
    for (int s = 0; s < 64; s++) {
      asm volatile("" : "+r"(tp), "+r"(wid));
      asm volatile("mov.u32 %0,%%cluster_ctarank;" : "=r"(b));
      uint32_t vS[NVS][4], bf[8][4];
      static_assert(NVR == 5, "schedule");
#define VLD(k) ldsm4t(vS[(k) - NVR], frag + WVS + ((k) - NVR) * 2048)
#define BLD(t) ldsm4t(bf[t], mA + (t) * 640)
#define VMMA(c, w, i) mma16(c, (w)[0], (w)[1], (w)[2], (w)[3], bf[(i) >> 1][((i) & 1) * 2], bf[(i) >> 1][((i) & 1) * 2 + 1])
#define VS_(c, k) VMMA(c, vS[(k) - NVR], k)
#define QK(i) VMMA(cQ, wQ[i], i); VMMA(cK, wK[i], i)
#define PREV VLD(13); VLD(12); if (NF > 2) VLD(11);
      if (s > 0) BAR_SYNC(B_R, 320);
      float cV[4] = {0, 0, 0, 0}, cW[4] = {0, 0, 0, 0};
      {
        float cQ[4] = {0, 0, 0, 0}, cK[4] = {0, 0, 0, 0};
        BLD(7); BLD(6); BLD(5); BLD(4); if (NB0 > 4) BLD(3);
        SCHED_FENCE(47);
        QK(15); VMMA(cV, vP[0], 15);
        QK(14); VMMA(cV, vP[1], 14);
        QK(13); QK(12);
        SCHED_FENCE(51);
        if (NB0 < 5) BLD(3);
        BLD(2); BLD(1); BLD(0);
        const uint32_t rm = lds1(tp + 4);
        QK(11); QK(10); QK(9); QK(8); QK(7);
        if (PV0 == 6) { SCHED_FENCE(48); PREV }
        QK(6); QK(5);
        if (PV0 == 4) { QK(4); SCHED_FENCE(48); PREV } else { QK(4); }
        QK(3); QK(2); QK(1); QK(0);
        const uint32_t w0 = pk(cQ[0] * SCS, cQ[1] * SCS), w1 = pk(cQ[2] * SCS, cQ[3] * SCS), w2 = pk(cK[0], cK[1]), w3 = pk(cK[2], cK[3]);
        if (owner) {
          stsm4(rm, w0, w1, w2, w3);
          BAR_ARRIVE(B_E, 256);
        } else {
          const uint32_t mm = (rm & 0xff000000u) | (1024 + BARS);
          sta1<0>(rm, w0, mm); sta1<128>(rm, w1, mm);
          sta1<RK - RQ>(rm, w2, mm); sta1<RK - RQ + 128>(rm, w3, mm);
        }
        if (wid == 2) TS(0);
      }
      uint4 t1;
      uint32_t oA, wo[16][4];
      {
        DLY(10)
        if (NF < 3) VLD(11);
        VLD(10);
        VS_(cW, 13); VLD(9); VS_(cV, 12); VLD(8); VLD(7); VMMA(cW, wV[0], 0); VMMA(cV, wV[1], 1); VLD(6);
        VMMA(cW, wV[2], 2); VMMA(cV, wV[3], 3); VLD(5); VMMA(cW, wV[4], 4); VS_(cV, 11);
        VS_(cW, 10); VS_(cV, 9); VS_(cW, 8); VS_(cV, 7); VS_(cW, 6); VS_(cV, 5);
#pragma unroll
        for (int e = 0; e < 4; e++) cV[e] += cW[e];
        const uint32_t ex = tp + (RX - TF) - wg * 2048;
        t1 = lds4(tp + 4096 + (T1L ? vS[3][0] & dZ : 0));
        oA = lds1(tp + 8 + (s & dZ));
        if (wg) {
          sts4(ex, U_(cV[0]), U_(cV[1]), U_(cV[2]), U_(cV[3]));
          BAR_ARRIVE(B_T2, 256);
        }
        if (!wg) {
          BAR_SYNC(B_T2, 256);
          DLY(3)
          const float4 u = lds4f(ex);
          stg_b64(mkp(t1.w ^ ((s & 1) * X_RING), HI(xc)), (pk(cV[0] + u.x, cV[1] + u.y) & ~1u) | (((s >> 1) + 1) & 1), pk(cV[2] + u.z, cV[3] + u.w));
        }
      }
      if (s == 63) break;
      if (s == 0) mbar_wait(obar, 0);
      {
        const uint32_t woA = t1.x, woB = woA ^ 32;
#pragma unroll
        for (int i = 0; i < NW0; i++) ldsm4t(wo[i], ((i & 1) ? woB : woA) + (i >= WCH ? wo[(i - WCH + NWP) % NWP][0] & dZ : 0) + (i >> 1) * 2048);
        DLY(2)
        BAR_SYNC(B_S, 416);
        float inv0, inv1;
        uint32_t p[4], pm;
        const uint32_t pa = oA + (SC - OB), one = 0x3f803f80u;
#define P_LOAD ldsm4t(p, pa); asm volatile("ldmatrix.sync.aligned.m8n8.x1.trans.shared.b16 {%0},[%1];" : "=r"(pm) : "r"(pa + 512) : "memory");
        if (s < 62) {
          float acc[16];
          rs_issue(acc, wQ, XB, true);
          mbar_wait(sb + BARS + 24, (s + 1) & 1);
          WG_WAIT(0);
          uint32_t qw[8];
#pragma unroll
          for (int i = 0; i < 8; i++) qw[i] = pk(acc[2 * i], acc[2 * i + 1]);
#pragma unroll
          for (int i = NW0; i < NW1; i++) ldsm4t(wo[i], ((i & 1) ? woB : woA) + (i >> 1) * 2048);
          BAR_SYNC(B_V, 512);
          P_LOAD
          park_w(qw, 0, t1.z);
        } else {
#pragma unroll
          for (int i = NW0; i < NW1; i++) ldsm4t(wo[i], ((i & 1) ? woB : woA) + (i >> 1) * 2048);
          BAR_SYNC(B_V, 512);
          P_LOAD
        }
#pragma unroll
        for (int i = NW1; i < NWP; i++) ldsm4t(wo[i], ((i & 1) ? woB : woA) + (i >> 1) * 2048);
        {
          float sum[4] = {0, 0, 0, 0}, su2[4] = {0, 0, 0, 0};
          mma16(sum, one, one, one, one, p[0], p[1]);
          mma16(su2, one, one, one, one, p[2], p[3]);
          mma8(sum, one, one, pm);
          inv0 = sum[0] + su2[0]; inv1 = sum[1] + su2[1];
          SCHED_FENCE(57);
        }
        DLY(7)
        BAR_SYNC(B_O, 416);
        float c[2][4] = {{0, 0, 0, 0}, {0, 0, 0, 0}};
        uint32_t o[4][4];
#pragma unroll
        for (int i = 0; i < NOP_; i++) ldsm4t(o[i], oA + i * 512);
        SCHED_FENCE(46);
        asm("rcp.approx.ftz.f32 %0,%0;" : "+f"(inv0));
        asm("rcp.approx.ftz.f32 %0,%0;" : "+f"(inv1));
#pragma unroll
        for (int i = 0; i < 16; i++) {
          mma16(c[i & 1], wo[i][0], wo[i][1], wo[i][2], wo[i][3], o[i >> 2][i & 2], o[i >> 2][(i & 2) + 1]);
          if (i == 1 && NOP_ < 3) ldsm4t(o[2], oA + 1024);
          if (i == 3 && NOP_ < 4) ldsm4t(o[3], oA + 1536);
          if (i + NWP < 16) ldsm4t(wo[(i + NWP) & 15], (((i + NWP) & 1) ? woB : woA) + ((i + NWP) >> 1) * 2048);
        }
        stsm4(t1.y, pk(c[0][0] * inv0, c[0][1] * inv1), pk(c[0][2] * inv0, c[0][3] * inv1), pk(c[1][0] * inv0, c[1][1] * inv1), pk(c[1][2] * inv0, c[1][3] * inv1));
      }
      const uint32_t d = park_ptr();
      BAR_SYNC(B_W, 384);
      DLY(1)
      if (UNC || s < 62) {
        vk_pass(s + 2, d, XB, true, []() {});
        if (!UNC || s < 62) { BAR_ARRIVE(B_P, 384); BAR_ARRIVE(B_X, 320); }
        TS(10);
      } else {
        V_AHEAD
        CONSUME(vP[1][0]);
      }
    }
  } else if (role == 3) {
    asm volatile("setmaxnreg.dec.sync.aligned.u32 24;");
    if (blockIdx.x >= 128) return;
    ROLE_VARS
    const uint32_t L16 = sb + (tid & 31) * 16;
    asm volatile("barrier.cluster.wait.aligned;" ::: "memory");
    CLUSTER_SYNC();
    sts1(sb + PACE + 36, LO(xc) + h * 262144 + X_VM(0));
    auto vm_stage = [&](int s) {
      const uint32_t tag = ((s >> 1) + 1) & 1;
      const char* xm = mkp(lds1(sb + PACE + 36) + (s & 1) * X_RING + iw * XC + (l16 >> 1), HI(xc));
      uint2 m[4];
      CONSUME(LO(xm));
      BAR_SYNC(B_S2, 256);
      DLY(4)
      int it = 0;
      while (true) {
#pragma unroll
        for (int i = 0; i < 4; i++) m[i] = ldg_b64(xm + (i >> 1) * 2048 + (i & 1) * 256);
        sts4(L16 + VN + iw * 512, m[0].x, m[0].y, m[1].x, m[1].y);
        sts4(L16 + VN + iw * 512 + 2048, m[2].x, m[2].y, m[3].x, m[3].y);
        if (!anybad(m[0].x, m[1].x, m[2].x, m[3].x, tag)) break;
        RP(2);
        if (++it > SPIN_LIMIT) __trap();
      }
      if (s < 63) BAR_ARRIVE(B_V, 512); else BAR_ARRIVE(B_V, 256);
    };
#define V_LOAD(n) asm volatile("{.reg .pred p; elect.sync _|p, 0xffffffff; @p mbarrier.arrive.expect_tx.shared.b64 _,[%3],8192;\n" \
        "@p cp.async.bulk.tensor.5d.shared::cluster.global.mbarrier::complete_tx::bytes [%0],[%1,{0,0,0,0,%2}],[%3];}" \
        ::"r"(sb + VX0), "l"(&mp.vx), "r"(h * 64 + (V_RING(n) >> 12)), "r"(sb + BARS + 8) : "memory")
    if (iw == 0) {
      wait_cnt(&g_hcnt, 128);
#pragma unroll 1
      for (int s = 0; s < 63; s++) {
        if (s < 62) for (int it = 0; ldg_rlx1(g_hf + (s & 3)) <= (s >> 2); it++) if (it > SPIN_LIMIT) __trap();
        if (s) BAR_SYNC(B_R, 320); else BAR_SYNC(B_Q, 288);
        if (s < 62) { X_LOAD(s + 2, 0, 0); X_LOAD(s + 2, 1, 0); X_LOAD(s + 2, 0, 1); X_LOAD(s + 2, 1, 1); }
        if (s >= 7) {
          const uint32_t zo = b * 160 + l16;
          if (l16 < 160) CONSUME(exch_b128(xc + AR_OFF + AR_ROW(zo >> 7) * 1024 + (zo & 127) + ((s + 1) & 7) * 128, 0, 0, 0, 0).x);
          __syncwarp();
        }
        if (s < 62) { mbar_wait(sb + BARS + 64, s & 1); mbar_wait(sb + BARS + 72, s & 1); }
        BAR_ARRIVE(B_S, 416);
        vm_stage(s);
        BAR_ARRIVE(B_O, 416);
        BAR_SYNC(B_W, 384);
        DLY(8)
        FENCE_ASYNC_SMEM();
        asm volatile("{.reg .pred p; elect.sync _|p, 0xffffffff; @p cp.reduce.async.bulk.tensor.3d.global.shared::cta.add.bulk_group [%0,{%1,%4,%2}],[%3];}"
                     ::"l"(&mp.ari), "r"((s & 7) * 64), "r"(AR_R(j)), "r"(sb + ARO), "r"(AR_P(j)) : "memory");
        BULK_COMMIT();
        asm volatile("st.relaxed.gpu.global.u32 [%0],%1;" ::"l"(g_tm + (s & 1) * 128 + b), "r"(gtime()) : "memory");
        TS(3);
        BULK_WAIT_READ(0);
      }
      BAR_ARRIVE(B_R, 320);
    } else if (iw == 1) {
      const uint32_t pc = sb + MEM + (lane >> 2) * 640 + (lane & 3) * 144 + (lane & 12), pd = sb + MEM + (lane & 15) * 640 + 576 + (lane & 3) * 16 + (lane & 12);
      uint32_t T = 0, par = 0;
      int est = dA;
#pragma unroll 1
      for (int s = 0; s < 63; s++) {
        if (s) {
          const uint4 tm = ldg_rlx4((const char*)g_tm + ((s + 1) & 1) * 512 + l16);
          const int t0 = tm.x - T, t1 = tm.y - T, t2 = tm.z - T, t3 = tm.w - T;
          const int e = max(dF + (__reduce_add_sync(~0u, (t0 + t1) + (t2 + t3)) >> 7), dV + __reduce_max_sync(~0u, max(max(t0, t1), max(t2, t3))));
          if (s > 1) est += max(min(e >> 2, dP), -dP);
          T += (s == 1 || e > dM ? e : 0) + est - (s == 62 ? L62 : 0);
        }
        vm_stage(s);
        BAR_SYNC(B_W, 384);
        SCHED_FENCE(70);
        const uint32_t tW = gtime();
        if (s == 0) T = tW + 800;
        const uint32_t te = tW + min(max((int)(T - tW), dD), 2000);
        while ((int)(gtime() - te) < 0) {}
        TS(7);
        int it = 0;
        while (true) {
          ar_fetch(sb + MEM, &mp.ari, s & 7, a, sb + BARS + 112);
          mbar_wait(sb + BARS + 112, par);
          par ^= 1;
          const uint32_t n0 = lds1(pc), n1 = lds1(pc + 5120), n2 = lds1(pd);
          if (!__any_sync(~0u, (tagbad(n0, n1, 0x42004200) | (n2 ^ 0x42004200)) != 0)) break;
          RP(0);
          if (++it > SPIN_LIMIT) __trap();
        }
        BAR_ARRIVE(B_R, 320);
        TS(11);
      }
    } else {
      uint32_t src = L16 + PK + (iw & 1) * 2048;
#define qd (L16 + (lane >> 4) * 256 + QT + (iw & 1) * 1024)
#define vd (LO(xc) + h * 262144 + j * XC + (iw & 1) * 2048 + l16)
#define FINISH [&](int n, int m) { \
_Pragma("unroll") \
        for (int i = 1; i >= 0; i--) { \
          const uint32_t p = src + m * 4096 + i * 512; \
          uint4 u = lds4(p); \
          const uint4 w = lds4(p + 1024), y = lds4(p + 12288), z = lds4(p + 13312); \
          u = make_uint4(sum4bf(u.x, w.x, y.x, z.x), sum4bf(u.y, w.y, y.y, z.y), sum4bf(u.z, w.z, y.z, z.z), sum4bf(u.w, w.w, y.w, z.w)); \
          if (m == 2) stg_b128(mkp(vd ^ V_RING(n), HI(xc)) + i * 512, (u.x & ~1u) | V_TAG(n), u.y, u.z, u.w); \
          else stsm4(qd + (n & 1) * 4096 + m * 2048 + i * 256, u.x, u.z, u.y, u.w); \
          SCHED_FENCE(71 + m * 2 + i); \
        } \
      }
#pragma unroll 1
      for (int n = 0; n < 64; n++) {
        src = PIN(src);
        b = __shfl_sync(~0u, lds1(sb + PACE + 24), 0);
        const uint32_t L16 = src - PK - (iw & 1) * 2048;
        auto finish = FINISH;
        if (n < 2) { if (n) BAR_SYNC(B_X, 320); else BAR_SYNC(B_C, 448); }
        mbar_wait(sb + BARS + 16, n & 1);
        if (n > 1) { const uint32_t c = clk(); while (clk() - c < (uint32_t)dQ) {} }
        finish(n, 0);
        __syncwarp();
        if (lane == 0) mbar_arrive_cl(mapa(sb, a ^ 1) + BARS + 24);
        if (n > 1) BAR_SYNC(B_K, 320);
        mbar_wait(sb + BARS + 40, n & 1);
        finish(n, 2);
        if (n > 1) BAR_SYNC(B_X, 320);
        mbar_wait(sb + BARS + 32, n & 1);
        DLY(11)
        finish(n, 1);
        BAR_SYNC(B_T, 64);
        if (lane == 0) {
          if (iw == 2 && n < 63) { mbar_expect(sb + BARS + 16, 4096); mbar_expect(sb + BARS + 32, 4096); mbar_expect(sb + BARS + 40, 4096); }
          mbar_arrive_cl(mapa(sb, a ^ 1) + BARS + 80);
        }
        __syncwarp();
        if (n) {
          vm_stage(n - 1);
          BAR_SYNC(B_W, 384);
          DLY(15)
        } else {
          BAR_SYNC(B_C, 320);
        }
        if (iw == 2) V_LOAD(n);
      }
#undef qd
#undef vd
    }
    { ROLE_REFRESH }
    vm_stage(63);
  } else {
    asm volatile("setmaxnreg.dec.sync.aligned.u32 %0;" ::"n"(RA_));
    if (blockIdx.x >= 128) { if (threadIdx.x == 256) rec_prefetch((const char*)wmod, w1, (const char*)x, wo); return; }
    ROLE_VARS
    uint32_t L16 = __shfl_sync(~0u, sb + (tid & 31) * 16, tid & 31);
    const uint32_t ts = gtime();
    uint2 m0[8];
#pragma unroll
    for (int r = 0; r < 8; r++) m0[r] = *(const uint2*)(mem0 + r * 1024 + a * 512 + (tid - 256) * 4);
    if (wid == 9) {
#pragma unroll 1
      for (int i = b * 80 + (tid & 31); i < b * 80 + 80; i += 32) ((uint4*)(xc + AR_OFF))[AR_ROW(i >> 6) * 64 + (i & 63)] = make_uint4(0, 0, 0, 0);
      if (b == 0) g_fin = 0;
      FENCE_ASYNC();
      __syncwarp();
      if (tid == 288) red_rlx(&g_hcnt);
    }
    if (tid == 256) {
      const int col = h * 128 + bb * 64;
#pragma unroll 1
      for (int c = 0, w = 0; w < 12; c++) {
#pragma unroll 1
        for (; w <= c - (c < WC0 ? 2 : 3); w++) {
          mbar_wait(sb + PACE + (w % 3) * 8, (w / 3) & 1);
          PT(18 + w);
          if (w == 3) asm volatile("mbarrier.arrive.shared.b64 _,[%0];" ::"r"(sb + BARS + 88) : "memory");
        }
        const uint32_t mb = sb + PACE + (c % 3) * 8;
        if (c >= 12 && c < 12 + WPE) tma2d_pf(&mp.wo, j * 256 + (c - 12) * 64, h * 128);
        if (c >= 12) continue;
        mbar_expect(mb, 16384);
        if (c < 8) tma2d(sb + (c >> 2) * XB + (c & 3) * 16384, (c & 4) ? &mp.wk : &mp.wq, col, a * 512 + (c & 3) * 128, mb);
        else
#pragma unroll 1
          for (int i = (c & 1) * 8; i < (c & 1) * 8 + 8; i++) {
            const int w = (c - 8) >> 1;
            tma2d(i < NVR ? sb + MEM + (w * NVR + i) * 2048 : sb + WVS + (w * NVS + i - NVR) * 2048, &mp.wv, col, a * 512 + w * 256 + i * 16, mb);
          }
      }
      asm volatile("mbarrier.arrive.shared.b64 _,[%0];" ::"r"(wbar) : "memory");
      for (int i = 0; i < 3; i++) asm volatile("mbarrier.inval.shared.b64 [%0];" ::"r"(sb + PACE + i * 8) : "memory");
    }
    __syncwarp();
    asm volatile("barrier.cluster.wait.aligned;" ::: "memory");
    CLUSTER_SYNC();
#pragma unroll 4
    for (int i = 0; i < 16; i++) {
      const uint4 v = lds4(L16 + WO + 32768 + iw * 8192 + i * 512);
      sts4(L16 + XB + iw * 8192 + i * 512, v.x, v.y, v.z, v.w);
    }
#pragma unroll
    for (int i = 0; i < 4; i++) {
      const int k = (tid - 256) * 4 + i, m = (k >> 3) & 3, r = k & 7;
#define M0W(r) __byte_perm((i & 2) ? m0[r].y : m0[r].x, (i & 2) ? m0[r + 1].y : m0[r + 1].x, (i & 1) ? 0x7632 : 0x5410)
      sts4(sb + MEM + (k >> 5) * 640 + (r == m ? 512 : m * 128) + r * 16, M0W(0), M0W(2), M0W(4), M0W(6));
    }
#pragma unroll 1
    for (int i = tid - 256; i < 192; i += 128) {
      const uint32_t c = i < 128 ? 0x42004200 : 0x3f803f80;
      sts4(sb + MEM + (i >> 3) * 640 + ((i & 7) < 4 ? (i & 7) * 144 : 512 + (i & 7) * 16), c, c, c, c);
    }
    static_assert(ARO == MEM + 16 * 640, "counters");
    FENCE_ASYNC_SMEM();
    BAR_ARRIVE(B_C, 448);
    if (tid == 256) {
      wait_time(ts + 1);
#pragma unroll 1
      for (int c = WPE; c < 4; c++) tma2d_pf(&mp.wo, j * 256 + c * 64, h * 128);
    }
    __syncwarp();
#define pr (L16 + SC)
    {
      const int lim = j * 8 + iw * 2 - (lane & 7) - (lane & 8) * 2;
      const bool mk = L16 & 256;
      const int rw = lane >> 2;
      sts4(L16 + TA + iw * 512,
           iw != 2 ? L16 + KT + (iw & 1) * 256 + (lane >> 4) * 256 : sb + RK + (L16 & 0x80) * 2 + ((L16 >> 1) & 0x80) + (L16 & 0x70),
           L16 + QT + (lane >> 3) * 384, sb + SC + min(lane >> 3, 2) * 256 + (L16 & 0x70) + iw * 4, L16 + (lane >> 4) * 256 + QT + (iw >> 1) * 1024 + (iw & 1) * 256);
      sts4(L16 + TA + 2048 + iw * 512, mk ? 0u : (lim < 0 ? 0xfc00u : 0u) | (lim < -1 ? 0xfc000000u : 0u),
           mk ? 0xfc00fc00u : (lim < 8 ? 0xfc00u : 0u) | (lim < 7 ? 0xfc000000u : 0u),
           ((h * 2 + (iw >> 1)) * 1024 + (j * 8 + rw) * 8 + (((iw & 1) * 4 + (lane & 3)) ^ rw)) * 16, sb + OT + iw * 512 + (L16 & 0x70) * 4 + ((L16 >> 3) & 0x30));
    }
    {
      const uint32_t xh = LO(xc) + h * 262144, xs = xh + X_SC + iw * 1024 + min(lane, 16 + (lane & 7)) * 8;
      sts4(L16 + TA + 4096 + iw * 512, xh + X_SC + j * 256 + iw * 64 + lpub, xs, dS, iw != 2 ? 0 : U_(SCS));
      sts1(L16 + TA + 12 + iw * 512, xs + X_TOK + j * 4096);
    }
    uint32_t tA = L16 + TA + iw * 512;
#define tw (tA - L16 != TA + 1024)
#define XP_(lo) mkp(lo, HI(xc))
    auto publish = [&](char* d, const uint2& w) { stg_b64(d, w.x, w.y); };
    BAR_SYNC(B_P, 384);
    for (int s = 0; s < 64; s++) {
      asm volatile("" : "+r"(L16), "+r"(tA));
      const uint32_t tag = ((s >> 1) + 1) & 1, ring = (s & 1) * X_RING;
      const uint4 t0 = lds4(tA);
      const uint4 tx = lds4(tA + 4096);
      const uint32_t xo = tx.x ^ ring, xs = tx.y ^ ring;
      const float gm = F_(tx.w);
      const uint32_t qA = t0.y + (ring >> 5);
      uint32_t c0;
      uint2 ts[4];
      uint4 v[4];
      uint32_t af[2][4], qt[4][4];
      {
        const uint32_t aA = t0.x + (tw ? ring >> 5 : 0);
        uint32_t ql[2][4], qr[2][4];
        uint2 pw_;
        float c[4] = {0, 0, 0, 0}, d[4] = {0, 0, 0, 0};
        if (s == PDS) asm volatile("griddepcontrol.launch_dependents;");
#pragma unroll
        for (int i = 0; i < 4; i++) ldsm4t(qt[i], qA + i * 128);
        mbar_wait(sb + BARS + 8, s & 1);
        TS(4);
        BAR_SYNC(B_E, 256);
        DLY(14)
#define PACK(c) make_uint2(pkh(fmaf(c[2], gm, c[0] * SCS), fmaf(c[3], gm, c[1] * SCS), tag), pkh(c[2] * SCS, c[3] * SCS, tag))
        ldsm4t(ql[0], L16 + RQ); ldsm4t(ql[1], L16 + RQ + 1024); ldsm4t(af[0], aA); ldsm4t(af[1], aA + 1024);
        CONSUME(xo);
#define QSUM(t, i) addbf(addbf(ql[t][i], ql[t][i + 2]), addbf(qr[t][i], qr[t][i + 2]))
#define STAIL mma16(c, af[0][0], af[0][1], af[0][2], af[0][3], QSUM(0, 0), QSUM(0, 1)); mma16(d, af[1][0], af[1][1], af[1][2], af[1][3], QSUM(1, 0), QSUM(1, 1));
        if (tw) {
          mbar_wait(sb + BARS, s & 1);
          TS(8);
          ldsm4t(qr[0], L16 + RQ + 512); ldsm4t(qr[1], L16 + RQ + 1536);
          STAIL
          pw_ = make_uint2(pkh(c[0] + d[0], c[1] + d[1], tag), pkh(c[2] + d[2], c[3] + d[3], tag));
        } else {
          uint32_t ar[2][4];
          mbar_wait(sb + BARS, s & 1);
          ldsm4t(qr[0], L16 + RQ + 512); ldsm4t(ar[0], aA + 512); ldsm4t(qr[1], L16 + RQ + 1536); ldsm4t(ar[1], aA + 1536);
#pragma unroll
          for (int i = 0; i < 8; i++) af[i >> 2][i & 3] = addbf(af[i >> 2][i & 3], ar[i >> 2][i & 3]);
          STAIL
          pw_.x = pw_.y = pkh((c[0] + c[2]) + (d[0] + d[2]), (c[1] + c[3]) + (d[1] + d[3]), tag);
        }
        publish(XP_(xo), pw_);
        c0 = clk() + tx.z;
        TS(1);
      }
      uint2 r[4];
      bool vbad;
      uint4 vn[2];
      {
        float e[4][4];
#pragma unroll
        for (int i = 0; i < 4; i++) {
          e[i][0] = e[i][1] = e[i][2] = e[i][3] = 0.f;
          mma16(e[i], af[0][0], af[0][1], af[0][2], af[0][3], qt[i][0], qt[i][1]);
        }
#pragma unroll
        for (int i = 0; i < 4; i++) mma16(e[i], af[1][0], af[1][1], af[1][2], af[1][3], qt[i][2], qt[i][3]);
        SCHED_FENCE(55);
        if (s < 63) BAR_ARRIVE(B_S, 416);
        SCHED_FENCE(58);
        v[0] = lds4(tA + (VX0 - TA)); v[1] = lds4(tA + (VX0 - TA) + 2048); v[2] = lds4(tA + (VX1 - TA)); v[3] = lds4(tA + (VX1 - TA) + 2048);
#pragma unroll
        for (int i = 0; i < 4; i++) ts[i] = PACK(e[i]);
        vbad = anybad(v[0].x, v[1].x, v[2].x, v[3].x, V_TAG(s));
        while ((int)(clk() - c0) < 0) {}
        TS(5);
#pragma unroll
        for (int u = 0; u < 4; u++) r[u] = ldg_b64(XP_(xs) + u * 256);
        BAR_ARRIVE(B_S2, 256);
      }
      SCHED_FENCE(56);
      uint32_t kk;
      float4 e = softmax2<false>(r, 0, 0, kk);
      if (__builtin_expect(anybad(r[0].x, r[0].y, r[1].x, r[1].y, r[2].x, r[2].y, r[3].x, r[3].y, tag ^ (kk & dZ)), 0)) {
        int it = 0;
        if (s > 8) sts1(tA + 4096 + 8, min(lds1(tA + 4096 + 8) + dX, 500));
        do {
          RP(1);
          if (++it > SPIN_LIMIT) __trap();
#pragma unroll
          for (int u = 0; u < 4; u++) r[u] = ldg_b64(XP_(xs) + u * 256);
        } while (BADS(r));
        e = softmax2<false>(r, 0, 0, kk);
      }
      DLY(5)
      sts1(t0.z, pk(e.x, e.y)); sts1(t0.z + 128, pk(e.z, e.w));
#pragma unroll
      for (int i = 0; i < 4; i++) publish(XP_(xo) + X_TOK + i * 4096, ts[i]);
      TS(6);
      if (s < 63) BAR_SYNC(B_V, 512); else BAR_SYNC(B_V, 256);
      uint32_t O[4];
      {
        uint32_t p[4], pm;
        ldsm4t(p, pr);
        asm volatile("ldmatrix.sync.aligned.m8n8.x1.trans.shared.b16 {%0},[%1];" : "=r"(pm) : "r"(pr + 512) : "memory");
        vn[0] = lds4(tA + (VN - TA)); vn[1] = lds4(tA + (VN - TA) + 2048);
        pv_mem(p, pm, v, vn, O);
        if (__builtin_expect(vbad, 0)) {
          int it = 0;
          const uint32_t xv = LO(xc) + (lds1(sb + PACE + 24) >> 2) * 262144 + ((tA - L16 - TA) >> 9) * XC;
          do {
            RP(2);
            if (++it > SPIN_LIMIT) __trap();
#pragma unroll
            for (int u = 0; u < 4; u++) v[u] = ldg_b128(XP_((xv + l16) ^ V_RING(s)) + X_VX(u));
          } while (anybad(v[0].x, v[1].x, v[2].x, v[3].x, V_TAG(s)));
          pv_mem(p, pm, v, vn, O);
        }
      }
      DLY(6)
      stsm4(tA + (OB - TA), O[0], O[1], O[2], O[3]);
      if (s < 63) BAR_ARRIVE(B_O, 416);
      TS(2);
      c0 = clk() + dG;
      SCHED_FENCE(60);
      if (tA == sb + TA) mbar_expect(sb + BARS, 2048);
      const uint32_t vs[4] = {addbf(vn[0].x, vn[0].z), addbf(vn[0].y, vn[0].w), addbf(vn[1].x, vn[1].z), addbf(vn[1].y, vn[1].w)};
      {
        const char* xt = XP_(lds1(tA + 12) ^ ring);
        const uint2 t1 = lds2u(tA + 2048);
        const uint32_t pw = lds1(tA + 8);
        uint2 rt[4];
        CONSUME(LO(xt) ^ t1.x ^ pw);
        while ((int)(clk() - c0) < 0) {}
        int it = 0;
        do {
          if (++it > SPIN_LIMIT) __trap();
#pragma unroll
          for (int u = 0; u < 4; u++) rt[u] = ldg_b64(xt + u * 256);
        } while (BADS(rt));
        uint32_t kt;
        const float4 et = softmax2<true>(rt, t1.x, t1.y, kt);
        sts1(pw + 1024, pk(et.x, et.y)); sts1(pw + 1024 + 128, pk(et.z, et.w));
      }
      s = PIN(s);
      BAR_SYNC(B_SC, 128);
      {
        uint32_t Ot[4], p[4], pm;
        const uint2 t2 = lds2u(tA + 2048 + 8);
        ldsm4t(p, pr + 1024);
        asm volatile("ldmatrix.sync.aligned.m8n8.x1.trans.shared.b16 {%0},[%1];" : "=r"(pm) : "r"(pr + 1024 + 512) : "memory");
        char* od = (char*)g_O + ((s >> 2) * 1048576 + (s & 3) * 4096) + t2.x;
        CONSUME(LO(od) ^ HI(od) ^ pm ^ p[3]);
        TS(9);
        if (s < 62) BAR_SYNC(B_P, 384);
        DLY(13)
        pv_tok(p, pm, v, vs, Ot);
        asm volatile("stmatrix.sync.aligned.m8n8.x4.trans.shared.b16 [%0],{%1,%2,%3,%4};" ::"r"(t2.y), "r"(Ot[0]), "r"(Ot[1]), "r"(Ot[2]), "r"(Ot[3]) : "memory");
        __syncwarp();
        *(uint4*)od = lds4(tA + (OT - TA));
      }
    }
    FENCE_ASYNC();
    BAR_SYNC(B_SC, 128);
    if (tA == sb + TA) red_rlx(&g_fin);
  }
  __syncwarp();
  CLUSTER_SYNC();
  PH(5); RS(2);
}
#undef wg
#undef iw
#undef h
#undef j
#undef a
#undef bb
#undef oi
#undef owner
#undef ownv
#undef pr
#undef PIN
#undef XP_
#undef tw
#undef lane
#undef l16
#undef lrow
#undef lpub

namespace ffn {
constexpr uint32_t BR = 98304;
constexpr uint32_t STG = 196608;
constexpr uint32_t PRM = 229376;
constexpr uint32_t BARS = PRM + 2816;
constexpr uint32_t SMEM = BARS + 18 * 8;
}
#define Y_TILE(rb, kt) (((ALIAS & 1) ? g_h : g_h2) + ((rb) * 16 + (kt)) * 1024)
#define U_TILE(rb, kt) ((ALIAS & 2) ? g_O + ((rb) * 64 + (kt)) * 1024 : g_U + ((rb) * 56 + (kt)) * 1024)
struct FfnMaps { CUtensorMap wo, w1a, w1b, w2, x, out; };

template <int N>
__device__ __forceinline__ void wg_ss(float* d, uint64_t a, uint64_t b, int sd) {
  if (N == 128) wgmma_ss_n128(d, a, b, sd);
  if (N == 192) wgmma_ss_n192(d, a, b, sd);
}
template <int N>
__device__ __forceinline__ void acc_fence(float* d) {
#pragma unroll
  for (int i = 0; i < N; i++) asm volatile("" : "+f"(d[i])::"memory");
}
#define UNPK8(d, v) do { (d)[0] = blo(v.x); (d)[1] = bhi(v.x); (d)[2] = blo(v.y); (d)[3] = bhi(v.y); (d)[4] = blo(v.z); (d)[5] = bhi(v.z); (d)[6] = blo(v.w); (d)[7] = bhi(v.w); } while (0)
struct FfnPipe {
  uint32_t full, emp, ph, aoff;
  int st, sB, prev;
  bool leader;
  template <int N, int S = N>
  __device__ __forceinline__ void issue(float* acc, bool first, uint32_t a = 0) {
    mbar_wait(full + st * 8, ph);
    const uint64_t da = mkdesc((a ? a : 1024 + st * 16384) + aoff, 16, 1024), db = mkdesc(1024 + ffn::BR + sB * (S * 128), 8192, 1024);
    WG_FENCE();
#pragma unroll
    for (int j = 0; j < 4; j++) wg_ss<N>(acc, da + j * 2, db + j * 128, j || !first);
    WG_COMMIT();
    if (++sB == 768 / S) sB = 0;
  }
  __device__ __forceinline__ void release() { if (leader) mbar_arrive(emp + prev * 8); }
  __device__ __forceinline__ void next() { prev = st; if (++st == 6) { st = 0; ph ^= 1; } }
  __device__ __forceinline__ void retire() { WG_WAIT(1); release(); next(); }
};
__device__ __forceinline__ float gelu_h(float hx) {
  float u = hx * fmaf(hx * hx, 8.f * 0.0356774081f, 2.f * 0.7978845608f), t;
  asm("tanh.approx.f32 %0,%1;" : "=f"(t) : "f"(u));
  return fmaf(hx, t, hx);
}
struct FfnEpi {
  uint32_t st2, cc, flip, staged, l0;
  uint2 c;
  float n0, n1, s0, s1;
  __device__ __forceinline__ void flush(uint32_t r) {
    __syncwarp();
    asm volatile("{.reg .pred p; setp.ne.u32 p,%1,0; @p mbarrier.arrive.shared.b64 _,[%0];}" ::"r"(staged + (flip >> 11)), "r"(l0 & r) : "memory");
    flip ^= r << 14;
  }
  __device__ __forceinline__ void half(const float* d, int J, int r) {
#define PRE(i, n, c1, c2) gelu_h(fmaf(r ? d[4 + i] : d[i], i < 2 ? s0 : s1, fmaf(n, c1, c2)))
    asm volatile("stmatrix.sync.aligned.m8n8.x2.shared.b16 [%0],{%1,%2};" ::"r"((st2 ^ ((J & 3) * 32 + r * 16)) + flip),
                 "r"(pk(PRE(0, n0, blo(c.x), blo(c.y)), PRE(1, n0, bhi(c.x), bhi(c.y)))), "r"(pk(PRE(2, n1, blo(c.x), blo(c.y)), PRE(3, n1, bhi(c.x), bhi(c.y)))) : "memory");
#undef PRE
    if ((J & 3) == 3) flush(r);
    cc += r ? 56 : 8;
    c = lds2u(cc);
  }
};

__global__ void __launch_bounds__(384, 1)
k_ffn(const __grid_constant__ FfnMaps mp, const bf16* __restrict__ b2) {
  using namespace ffn;
  extern __shared__ __align__(1024) char smem[];
  const uint32_t sb = (uint32_t)__cvta_generic_to_shared(smem);
  if (sb != 1024) __trap();
  const int tid = threadIdx.x, lane = tid & 31, wg = __shfl_sync(~0u, tid >> 7, 0);
  const uint32_t full = sb + BARS, emp = full + 48, xbar = full + 96, staged = full + 104, tile = full + 136;
  uint32_t fin = 0;
  if (tid >= 288 && tid < 320) fin = ld_acq(&g_fin);
  if (tid < 32) {
    unsigned sm, v = 0;
    asm("mov.u32 %0,%%smid;" : "=r"(sm));
    if (tid == 0) {
      v = atomicExch(&g_slot[sm & 255], 0);
      for (int i = 0; i < 6; i++) { mbar_init(full + i * 8, 1); mbar_init(emp + i * 8, 2); }
      mbar_init(xbar, 2);
      for (int i = 0; i < 2; i++) { mbar_init(staged + i * 8, 8); mbar_init(staged + 16 + i * 8, 1); }
      FENCE_ASYNC_SMEM();
    }
    v = __shfl_sync(~0u, v, 0);
    if (!v) {
      wait_cnt(&g_fin, 128);
      for (int it = 0; !v; it++) {
        const uint4 a = ldg_rlx4(g_slot + tid * 8), b = ldg_rlx4(g_slot + tid * 8 + 4);
        const uint32_t open = __ballot_sync(~0u, a.x | a.y | a.z | a.w | b.x | b.y | b.z | b.w);
        if (!open) break;
        if (it < 16) { __nanosleep(500); continue; }
        if (tid == __ffs(open) - 1) v = atomicExch(&g_slot[tid * 8 + (a.x ? 0 : a.y ? 1 : a.z ? 2 : a.w ? 3 : b.x ? 4 : b.y ? 5 : b.z ? 6 : 7)], 0);
        v = __shfl_sync(~0u, v, __ffs(open) - 1);
      }
    }
    if (tid == 0) sts1(tile, v);
  }
  if (tid == 256) asm volatile("prefetch.tensormap [%0];" ::"l"(&mp.wo) : "memory");
  __syncthreads();
  const int bid = __shfl_sync(~0u, lds1(tile), 0) - 1;
  if (bid < 0) return;
  PH(6);
  FT(1);
  const int rb = bid >> 3, nb = bid & 7;
  unsigned* cnt = g_cnt + rb * 128;
  if (wg == 2) {
    asm volatile("setmaxnreg.dec.sync.aligned.u32 " FRP ";");
    const int pw = __shfl_sync(~0u, (tid >> 5) & 3, 0);
    uint32_t ws = emp, wp = 1, fs = full;
    auto wait_free = [&]() { mbar_wait_q(ws, wp); ws += 8; if (ws == emp + 48) { ws = emp; wp ^= 1; } };
    auto step = [&]() { fs += 8; if (fs == full + 48) fs = full; };
#define K3(c) ((0x65230 >> (c) * 4) & 7)
#define KC(k) ((k) < 2 ? nb * 2 + (k) : (k) < 9 ? ((k) - 2 + ((k) - 2 >= nb)) * 2 : ((k) - 9 + ((k) - 9 >= nb)) * 2 + 1)
    if (pw == 0) {
      uint32_t d = sb + BR + 32768;
      auto put = [&](const CUtensorMap* m, int k, int c) {
        e_expect_tma3d(d, m, k * 64, c, fs, 32768);
        step();
        d += 16384;
        if (d == sb + STG) d = sb + BR;
      };
      int n = 0;
      auto stage_free = [&]() { if (!(n & 7) && n < 56) mbar_wait_q(staged + 16 + (n & 8), (n >> 4) & 1); n++; };
      auto align = [&]() {
        if (ALN && !((n - 1) & 7) && ((ALN >> ((n - 1) >> 3)) & 1)) {
          unsigned* c = g_cnt + 64 + ((n - 1) >> 3);
          if (lane == 0) red_rlx(c);
          for (int it = 0; ldg_rlx1(c) < 128 && it < 64; it++) {}
        }
      };
      FTP(3);
#pragma unroll 1
      for (int k = 0; k < 66; k++) { wait_free(); if (k < 64) put(&mp.wo, k, nb * 2); }
#pragma unroll 1
      for (int k = 0; k < 18; k++) {
        const int u = k >= 2 ? k - 2 : k, kt = KC(u);
        const bool ea = (k & ~1) == 2;
        wait_free();
        e_expect_tma3d(sb + BR + (k & 3) * 24576, ea ? &mp.w1a : &mp.w1b, kt * 64, nb * 7 + (ea ? 3 : 0), fs, ea ? 16384 : k < 2 ? 24576 : 40960);
        step();
      }
      d = sb + BR + 49152;
#pragma unroll 1
      for (int k = 2; k < 32; k++) {
        const int kt = k < 16 ? KC(k) : k & 15;
        stage_free();
        if (k == 2 || k == 9) n++;
        if (k != 7 && k != 8) wait_free();
        align();
        put(&mp.w1a, kt, nb * 7 + 3 + (k >> 4) * 2);
      }
#pragma unroll 1
      for (int c = 0; c < 5; c++)
#pragma unroll 1
        for (int k = K3(c), i = 0; k < 56; k += c < 2 && (i ^= 1) ? 1 : c < 2 ? 6 : 7) { stage_free(); wait_free(); align(); put(&mp.w2, k, nb * 2); }
    } else if (pw == 1) {
      FTP(5);
      if (fin < 128) wait_cnt(&g_fin, 128);
      FTP(6);
      uint32_t d = sb;
      auto put = [&](const uint4* A, bool ld) {
        wait_free();
        if (ld) e_bulk_ld(d, A, 16384, fs);
        step();
        d += 16384;
        if (d == sb + BR) d = sb;
      };
      const uint4* A = g_O + rb * 65536;
#pragma unroll 1
      for (int k = 0; k < 68; k++) put(A + k * 1024, k < 64);
      A = Y_TILE(rb, 0);
      uint32_t ready = 0;
#pragma unroll 1
      for (int k = 2; k < 48; k++) {
        if (k == 16) k = 18;
        const int kt = k < 32 ? KC(k & 15) : k & 15;
        for (int it = 0; !(ready >> ((kt >> 1) + (kt & 1) * 8) & 1); it++) {
          ready = __ballot_sync(~0u, ldg_rlx1(cnt + (lane & 7)) & ((lane & 8) ? 1 : 0x10000));
          if (it > SPIN_LIMIT) __trap();
        }
        if (k == 2) FTP(75);
        put(A + kt * 1024, true);
      }
      A = U_TILE(rb, 0);
#pragma unroll 1
      for (int c = 0; c < 5; c++) {
        for (int it = 0; ldg_rlx1(cnt + 32 + c) < 8; it++) if (it > SPIN_LIMIT) __trap();
#pragma unroll 1
        for (int k = K3(c), i = 0; k < 56; k += c < 2 && (i ^= 1) ? 1 : c < 2 ? 6 : 7) put(A + k * 1024, true);
      }
    } else if (pw == 2) {
      for (int i = 0; i < XDL; i++) {
        mbar_wait_q(emp, i & 1);
      }
      if (lane == 0) {
        mbar_expect(xbar, 32768);
        tma2d(sb + STG, &mp.x, nb * 128, rb * 128, xbar);
        tma2d(sb + STG + 16384, &mp.x, nb * 128 + 64, rb * 128, xbar);
      }
      asm volatile("griddepcontrol.wait;" ::: "memory");
      if (lane < 16) g_modp[bid * 16 + lane] = make_uint4(0, 0, 0, 0);
      if (lane >= 16 && bid == 0) { g_hcnt = 0; g_mcnt = 0; g_hf[lane & 3] = 0; }
      if (lane == 0) {
#pragma unroll 1
        for (int g = 1; g < 9; g++) {
          if (g == 1) mbar_wait(staged + 8, 0); else { mbar_wait_q(staged + (g & 1) * 8, (g >> 1) & 1); FENCE_ASYNC_SMEM(); }
          bulk_st(g == 1 ? Y_TILE(rb, nb * 2 + 1) : U_TILE(rb, nb * 7 + ((0x652431000ull >> g * 4) & 7)), sb + STG + (g & 1) * 16384, 16384);
          BULK_COMMIT();
          if (g != 2 && g != 4) { BULK_WAIT(0); red_rlx(g == 1 ? cnt + nb : cnt + 32 + (g < 6 ? g >> 2 : g - 4)); }
          BULK_WAIT_READ(0);
          mbar_arrive(staged + 16 + (g & 1) * 8);
        }
      }
    } else {
      const uint32_t prm = sb + PRM, pp = prm + (lane >> 3) * 64 + (lane & 1) * 32 + (lane & 6) * 2;
      const uint2 v2 = ((const uint2*)(b2 + nb * 128))[lane];
      sts1(pp + 768, v2.x); sts1(pp + 784, v2.y);
      asm volatile("griddepcontrol.wait;" ::: "memory");
      const float4* md = (const float4*)(g_mod + nb * 128) + lane;
      { const float4 ga = md[512]; sts1(pp, pk(ga.x, ga.y)); sts1(pp + 16, pk(ga.z, ga.w)); }
      { const float4 cb = md[1024]; sts1(pp + 256, pk(1.f + cb.x, 1.f + cb.y)); sts1(pp + 272, pk(1.f + cb.z, 1.f + cb.w)); }
      { const float4 gb = md[1280]; sts1(pp + 512, pk(gb.x, gb.y)); sts1(pp + 528, pk(gb.z, gb.w)); }
#pragma unroll 1
      for (int i = lane; i < 112; i += 32) { const uint4 c = g_cc[nb * 112 + i]; sts4(prm + 1024 + i * 16, c.x, c.y, c.z, c.w); }
      __syncwarp();
      if (lane == 0) {
        mbar_arrive(xbar);
        mbar_wait(staged, 0);
        bulk_st(Y_TILE(rb, nb * 2), sb + STG, 16384);
        BULK_COMMIT(); BULK_WAIT(0);
        asm volatile("red.relaxed.gpu.global.add.u32 [%0],0x10000;" ::"l"(cnt + nb) : "memory");
        mbar_arrive(staged + 16);
      }
      __syncwarp();
      mbar_wait_q(staged + 24, 0);
      mbar_wait_q(emp + 8, 1);
#pragma unroll 1
      for (int i = 0; i < 4; i++) {
        const uint4* sp = g_stat + (rb * 128 + i * 32 + lane) * 4;
        uint4 v[4];
        for (int it = 0;; it++) {
          uint32_t m = 0;
#pragma unroll
          for (int u = 0; u < 4; u++) { v[u] = ldg_rlx4(sp + u); m = max(max(m, max(v[u].x, v[u].y)), max(v[u].z, v[u].w)); }
          if (!__any_sync(~0u, m == ~0u)) break;
          if (it > SPIN_LIMIT) __trap();
        }
        float m = 0, q = 0;
#pragma unroll
        for (int u = 0; u < 4; u++) { m += F_(v[u].x) + F_(v[u].z); q += F_(v[u].y) + F_(v[u].w); }
        m *= 1.f / 1024;
        const float r = 0.5f * rsqrtf(fmaxf(q * (1.f / 1024) - m * m, 0.f) + 1e-5f);
        sts2(sb + STG + 16384 + (i * 32 + lane) * 8, U_(r), U_(-m * r));
      }
      __syncwarp();
      if (lane < 2) mbar_arrive(xbar);
    }
  } else {
    asm volatile("setmaxnreg.inc.sync.aligned.u32 " FRC ";");
    const int w = (tid >> 5) & 3, q = lane & 3;
    const uint32_t prm = sb + PRM + q * 16;
    const int row0 = wg * 64 + w * 16;
    FfnPipe p;
    p.full = full; p.emp = emp; p.ph = 0; p.aoff = wg * 8192; p.st = 0; p.sB = 2; p.prev = 0; p.leader = (tid & 127) == 0;
    FfnEpi e;
    const uint32_t stg = sb + STG + row0 * 128;
    e.st2 = stg + (lane & 15) * 128 + ((lane & 7) << 4);
    e.cc = sb + PRM + 1024 + q * 16; e.flip = 0; e.staged = staged; e.l0 = lane == 0;
    const uint32_t stw = e.st2 ^ (lane & 16);
    uint32_t x1[32];
    uint4* sp = g_stat + (rb * 128 + row0 + (lane >> 2)) * 4;
    float old[96], r0_, r1_;
    {
      float acc[64];
      p.issue<128>(acc, true); FT(8); p.next();
#pragma unroll 1
      for (int k = 1; k < 64; k++) { p.issue<128>(acc, false); FT(8 + k); p.retire(); }
      float xf[64], gf[32];
      uint32_t cb[16];
      mbar_wait(xbar, 0);
#pragma unroll
      for (int j = 0; j < 8; j++) {
        uint32_t xv[4];
        ldsm4(xv, (stw ^ ((j & 3) * 32)) + (j >> 2) * 16384);
#pragma unroll
        for (int i = 0; i < 4; i++) { xf[j * 8 + i * 2] = blo(xv[i]); xf[j * 8 + i * 2 + 1] = bhi(xv[i]); }
      }
#pragma unroll
      for (int i = 0; i < 4; i++) {
        const uint4 g = lds4(prm + i * 64), c = lds4(prm + 256 + i * 64);
        UNPK8(gf + i * 8, g);
        cb[i * 4] = c.x; cb[i * 4 + 1] = c.y; cb[i * 4 + 2] = c.z; cb[i * 4 + 3] = c.w;
      }
      acc_fence<64>(xf); acc_fence<32>(gf);
      WG_WAIT(0);
      p.release();
      acc_fence<64>(acc);
      PH(7); FT(72);
#pragma unroll
      for (int j = 0; j < 8; j++) {
        uint32_t* o = x1 + j * 4;
#pragma unroll
        for (int i = 0; i < 4; i++)
          o[i] = pk(fmaf(acc[j * 8 + i * 2], gf[j * 4 + (i & 2)], xf[j * 8 + i * 2]), fmaf(acc[j * 8 + i * 2 + 1], gf[j * 4 + (i & 2) + 1], xf[j * 8 + i * 2 + 1]));
        stsm4((stw ^ ((j & 3) * 32)) + (j >> 2) * 16384, mulbf(o[0], cb[j * 2]), mulbf(o[1], cb[j * 2]), mulbf(o[2], cb[j * 2 + 1]), mulbf(o[3], cb[j * 2 + 1]));
        if ((j & 3) == 3) { FENCE_ASYNC_SMEM(); e.flush(1); }
      }
      if (wg) BAR_SYNC(2, 128); else BAR_SYNC(3, 128);
    }
    PH(8); FT(73);
    float acc[64];
    {
      float* accC = old;
      p.sB = 0;
      p.issue<192>(accC, true, 1024 + STG); FT(80); p.next();
      p.issue<192>(accC, false, 1024 + STG + 16384); FT(81);
      FT(78);
      float s0 = 0, s1 = 0, q0 = 0, q1 = 0;
#define X1_FENCE _Pragma("unroll") for (int j = 0; j < 32; j++) asm volatile("" : "+r"(x1[j]));
      X1_FENCE
#pragma unroll
      for (int j = 0; j < 16; j++) {
        const float a = blo(x1[j * 2]), b = bhi(x1[j * 2]), c = blo(x1[j * 2 + 1]), d = bhi(x1[j * 2 + 1]);
        s0 += a + b; s1 += c + d; q0 = fmaf(a, a, fmaf(b, b, q0)); q1 = fmaf(c, c, fmaf(d, d, q1));
      }
#pragma unroll
      for (int o = 1; o < 4; o *= 2) { s0 += __shfl_xor_sync(~0u, s0, o); s1 += __shfl_xor_sync(~0u, s1, o); q0 += __shfl_xor_sync(~0u, q0, o); q1 += __shfl_xor_sync(~0u, q1, o); }
      if (q < 2) {
        uint32_t m = __float_as_uint(q ? s1 : s0), v = __float_as_uint(q ? q1 : q0);
        if (m == ~0u) m = 0x7fffffffu;
        if (v == ~0u) v = 0x7fffffffu;
        stg_rlx2((uint2*)(sp + q * 32) + nb, m, v);
      }
      X1_FENCE
      p.retire();
#pragma unroll 1
      for (int k = 0; k < 2; k++) { p.issue<128, 192>(acc, !k, 1024 + STG + k * 16384); p.retire(); }
#pragma unroll 1
      for (int k = 2; k < 15; k++) { p.issue<192>(accC, false); FT(80 + k); p.retire(); }
      p.issue<192>(accC, false); FT(95);
      mbar_wait(xbar, 1);
      const float2 u0 = lds2f(sb + STG + 16384 + (row0 + (lane >> 2)) * 8), u1 = lds2f(sb + STG + 16384 + (row0 + (lane >> 2)) * 8 + 64);
      r0_ = u0.x; e.n0 = u0.y; r1_ = u1.x; e.n1 = u1.y;
      e.c = lds2u(e.cc);
      p.retire();
      e.s0 = r0_; e.s1 = r1_;
      p.sB = 3;
    }
    PH(9);
    {
      auto pair = [&](int J, bool first, bool one, int fo) {
#pragma unroll 1
        for (int r = 0; r < 2; r++) {
          if (!(one && r)) { p.issue<128>(acc, first && !r); FT(fo + r); p.retire(); }
          acc_fence<8>(old + J * 8);
          e.half(old + J * 8, J, r);
        }
      };
#pragma unroll 1
      for (int i = 0; i < 3; i++) {
        if (i == 2) {
          e.s0 = r0_; e.s1 = r1_;
#pragma unroll
          for (int J = 8; J < 12; J++) pair(J, J == 8, false, 128 + (J - 8) * 2);
          e.cc += 512; e.c = lds2u(e.cc);
          e.s0 = e.s1 = 1.f;
        }
#pragma unroll
        for (int J = 0; J < 8; J++) pair(J, J == 0 && i == 1, !(J & 3) && !i, 96 + i * 16 + (i >> 1) * 8 + J * 2);
        if (i == 2) break;
        e.cc += i ? -768 : 256; e.c = lds2u(e.cc);
        WG_WAIT(0);
        acc_fence<64>(acc);
#pragma unroll
        for (int k = 0; k < 64; k++) old[k] = acc[k] * ((k & 2) ? r1_ : r0_);
        acc_fence<64>(old);
        e.s0 = e.s1 = 1.f;
        PH(10 + i);
      }
#pragma unroll 1
      for (int k = 24; k < 56; k++) {
        if (SKW && k == 56 - SKW && wg) BAR_SYNC(4, 256);
        p.issue<128>(acc, false); FT(128 + k);
        if (SKW && k == 55 && !wg) BAR_ARRIVE(4, 256);
        p.retire();
      }
      float xf[64], gf[32];
#pragma unroll
      for (int i = 0; i < 4; i++) {
        const uint4 g = lds4(prm + 512 + i * 64), h = lds4(prm + 768 + i * 64);
        float hf[8];
        UNPK8(gf + i * 8, g); UNPK8(hf, h);
#pragma unroll
        for (int u = 0; u < 8; u++) {
          const int c = (u >> 2) * 4 + (u & 2);
          xf[i * 16 + u * 2] = fmaf(gf[i * 8 + c], hf[c], blo(x1[i * 8 + u])); xf[i * 16 + u * 2 + 1] = fmaf(gf[i * 8 + c + 1], hf[c + 1], bhi(x1[i * 8 + u]));
        }
      }
      acc_fence<64>(xf); acc_fence<32>(gf);
      mbar_wait(staged + 24, 1);
      mbar_wait(staged + 16, 0);
      WG_WAIT(0);
      acc_fence<64>(acc);
      PH(13); FT(184);
#pragma unroll
      for (int j = 0; j < 8; j++) {
        uint32_t o[4];
#pragma unroll
        for (int i = 0; i < 4; i++)
          o[i] = pk(fmaf(acc[j * 8 + i * 2], gf[j * 4 + (i & 2)], xf[j * 8 + i * 2]), fmaf(acc[j * 8 + i * 2 + 1], gf[j * 4 + (i & 2) + 1], xf[j * 8 + i * 2 + 1]));
        stsm4((stw ^ ((j & 3) * 32)) + (j >> 2) * 16384, o[0], o[1], o[2], o[3]);
        if ((j & 3) == 3) {
          FENCE_ASYNC_SMEM();
          __syncwarp();
          if (lane == 0) { tma2d_st(&mp.out, nb * 128 + (j >> 2) * 64, rb * 128 + row0, stg + (j >> 2) * 16384); BULK_COMMIT(); }
        }
      }
      if (lane == 0) BULK_WAIT_READ(0);
      __syncwarp();
    }
  }
  PH(14); FT(185);
}

typedef CUresult (*EncFn)(CUtensorMap*, CUtensorMapDataType, cuuint32_t, void*, const cuuint64_t*, const cuuint64_t*, const cuuint32_t*,
                          const cuuint32_t*, CUtensorMapInterleave, CUtensorMapSwizzle, CUtensorMapL2promotion, CUtensorMapFloatOOBfill);
static void map2d(EncFn enc, CUtensorMap* m, const void* p, int rows, int cols, int boxRows) {
  cuuint64_t d[2] = {(cuuint64_t)cols, (cuuint64_t)rows}, s[1] = {(cuuint64_t)cols * 2};
  cuuint32_t b[2] = {64, (cuuint32_t)boxRows}, e[2] = {1, 1};
  enc(m, CU_TENSOR_MAP_DATA_TYPE_BFLOAT16, 2, (void*)p, d, s, b, e, CU_TENSOR_MAP_INTERLEAVE_NONE, CU_TENSOR_MAP_SWIZZLE_128B,
      CU_TENSOR_MAP_L2_PROMOTION_L2_128B, CU_TENSOR_MAP_FLOAT_OOB_FILL_NONE);
}
static void map3d(EncFn enc, CUtensorMap* m, const void* p, int rows, int cols, int nch) {
  cuuint64_t d[3] = {64, (cuuint64_t)rows, (cuuint64_t)(cols / 64)}, s[2] = {(cuuint64_t)cols * 2, 128};
  cuuint32_t b[3] = {64, 64, (cuuint32_t)nch}, e[3] = {1, 1, 1};
  enc(m, CU_TENSOR_MAP_DATA_TYPE_BFLOAT16, 3, (void*)p, d, s, b, e, CU_TENSOR_MAP_INTERLEAVE_NONE, CU_TENSOR_MAP_SWIZZLE_128B,
      CU_TENSOR_MAP_L2_PROMOTION_L2_128B, CU_TENSOR_MAP_FLOAT_OOB_FILL_NONE);
}

extern "C" void kernel_launch(void* const* d_in, const int* in_sizes, int n_in, void* d_out, int out_size) {
  const bf16* x = (const bf16*)d_in[0];
  const bf16* mem0 = (const bf16*)d_in[1];
  void* fn = nullptr;
  cudaDriverEntryPointQueryResult qr;
  cudaGetDriverEntryPoint("cuTensorMapEncodeTiled", &fn, cudaEnableDefault, &qr);
  EncFn enc = (EncFn)fn;
  FfnMaps fm = {};
  map3d(enc, &fm.wo, d_in[5], 4096, 1024, 2);
  map3d(enc, &fm.w1a, d_in[8], 1024, 3584, 2);
  map3d(enc, &fm.w1b, d_in[8], 1024, 3584, 3);
  map3d(enc, &fm.w2, d_in[10], 3584, 1024, 2);
  map2d(enc, &fm.x, x, 2048, 1024, 128);
  map2d(enc, &fm.out, d_out, 2048, 1024, 16);
  RecMaps rm = {};
  map2d(enc, &rm.wq, d_in[2], 1024, 4096, 128);
  map2d(enc, &rm.wk, d_in[3], 1024, 4096, 128);
  map2d(enc, &rm.wv, d_in[4], 1024, 4096, 16);
  map2d(enc, &rm.wo, d_in[5], 4096, 1024, 128);
  char* xc = nullptr;
  cudaGetSymbolAddress((void**)&xc, g_xc);
  xc += (0 - (uintptr_t)xc) & 0x1FFFFF;
  {
    cuuint64_t d[3] = {512, 6, 128}, sd[2] = {131072, 1024};
    cuuint32_t bi[3] = {64, 5, 8}, e[3] = {1, 1, 1};
    enc(&rm.ari, CU_TENSOR_MAP_DATA_TYPE_BFLOAT16, 3, xc + AR_OFF, d, sd, bi, e, CU_TENSOR_MAP_INTERLEAVE_NONE, CU_TENSOR_MAP_SWIZZLE_NONE,
        CU_TENSOR_MAP_L2_PROMOTION_NONE, CU_TENSOR_MAP_FLOAT_OOB_FILL_NONE);
  }
  {
    cuuint64_t d[5] = {256, 4, 2, 2, 2048}, sd[4] = {rec::XC, X_VX(1), X_VX(2), 4096};
    cuuint32_t bi[5] = {256, 4, 2, 2, 1}, e[5] = {1, 1, 1, 1, 1};
    enc(&rm.vx, CU_TENSOR_MAP_DATA_TYPE_BFLOAT16, 5, xc, d, sd, bi, e, CU_TENSOR_MAP_INTERLEAVE_NONE, CU_TENSOR_MAP_SWIZZLE_NONE,
        CU_TENSOR_MAP_L2_PROMOTION_NONE, CU_TENSOR_MAP_FLOAT_OOB_FILL_NONE);
  }
  cudaFuncSetAttribute(k_ffn, cudaFuncAttributeMaxDynamicSharedMemorySize, ffn::SMEM);
  cudaFuncSetAttribute(k_rec, cudaFuncAttributeMaxDynamicSharedMemorySize, rec::SMEM);
  cudaStream_t st = cudaStreamPerThread;
  int dF = 450, dA = 2700, dS = 300, dM = 120, dG = 350, dP = 24, dX = 48, dD = 350, dZ = 0, dQ = 750, dV = 370, dX2 = 0;
  k_rec<<<132, 512, rec::SMEM, st>>>(rm, mem0, x, (const bf16*)d_in[12], (const bf16*)d_in[13], (const char*)d_in[8], (const bf16*)d_in[9],
                                     (const char*)d_in[5], xc, dF, dA, dS, dM, dG, dP, dX, dD, dZ, dQ, dV, dX2);
  cudaLaunchConfig_t cfg = {};
  cfg.gridDim = dim3(132); cfg.blockDim = dim3(384); cfg.dynamicSmemBytes = ffn::SMEM; cfg.stream = st;
  cudaLaunchAttribute at[1];
  at[0].id = cudaLaunchAttributeProgrammaticStreamSerialization;
  at[0].val.programmaticStreamSerializationAllowed = 1;
  cfg.attrs = at; cfg.numAttrs = 1;
  cudaLaunchKernelEx(&cfg, k_ffn, fm, (const bf16*)d_in[11]);
}
```

```cpp
#include <cuda_runtime.h>
#include <cuda.h>
#include <cuda_bf16.h>
#include <stdint.h>

typedef __nv_bfloat16 bf16;

__device__ __align__(16) float g_mod[6144];
__device__ __align__(1024) uint4 g_modp[4 * 512];
__device__ unsigned g_hcnt;
__device__ unsigned g_hf[4];
__device__ __align__(1024) uint4 g_h[2048 * 1024 / 8];
__device__ __align__(1024) uint4 g_O[2048 * 4096 / 8];
__device__ __align__(1024) uint4 g_h2[2048 * 1024 / 8];
__device__ __align__(1024) uint4 g_U[2048 * 3584 / 8];
__device__ __align__(1024) uint4 g_stat[2048 * 4];
__device__ __align__(1024) unsigned g_cnt[16 * 4 * 32];
__device__ unsigned g_mcnt;
__device__ unsigned g_slot[256];
__device__ unsigned g_fin;
__device__ __align__(16) uint4 g_cc[224 * 4];
__device__ __align__(1024) uint4 g_xc[44 * 16384];
__device__ __align__(1024) unsigned g_tm[4 * 256];
#define FT(i)
#define FTP(i)
#define PT(i)
#define PH(i)
#define RS(i)
#define RP(i)
#define RPN(i, s)
#define TSV(i, v)
#define TS(i)

#define FRC "232"
#define FRP "40"
#define FMAP (((g >> 2) * 4 + m) * 8 + ((g & 3) ^ ((g & 4) ? 3 : 0)) * 2 + (blockIdx.x & 1))
#define ALIAS 3
#define PFT 150000
#define PFS 104
#define PF0 13000
#define PFD 128
#define NF 3
#define NB0 4
#define PV0 4
#define T1L 1
#define NW0 4
#define VRF 3
#define VPC 1
#define WC0 10
#define WPE 3
#define ALN 0x80
#define SKW 3
#define L62 200
#define DLY(k)
#define UNC 1
#define PKE 0
#define XDL 6
#define PDS 61
#define P_NVR 5
#define P_NWP 9
#define P_NW1 7
#define RF_ 208
#define RA_ (488 - 2 * RF_)
#define WCH 2
#define NOP_ 2
#define SPIN_LIMIT (1 << 20)
__device__ __forceinline__ uint64_t mkdesc(uint32_t addr, uint32_t lbo, uint32_t sbo) {
  return (uint64_t)((addr & 0x3FFFF) >> 4) | ((uint64_t)(lbo >> 4) << 16) | ((uint64_t)(sbo >> 4) << 32) | (1ull << 62);
}
__device__ __forceinline__ void mbar_init(uint32_t a, int c) { asm volatile("mbarrier.init.shared.b64 [%0],%1;" ::"r"(a), "r"(c) : "memory"); }
__device__ __forceinline__ void mbar_wait(uint32_t a, uint32_t par) {
  asm volatile(
      "{.reg .pred p; .reg .u32 n;\n"
      "mov.u32 n, 0;\n"
      "W: mbarrier.try_wait.parity.shared.b64 p,[%0],%1;\n"
      "@p bra D;\n"
      "add.u32 n, n, 1;\n"
      "setp.lt.u32 p, n, %2;\n"
      "@p bra W;\n"
      "trap;\n"
      "D:}" ::"r"(a), "r"(par), "n"(SPIN_LIMIT) : "memory");
}
__device__ __forceinline__ void mbar_wait_q(uint32_t a, uint32_t par) {
  asm volatile(
      "{.reg .pred p; .reg .u32 n;\n"
      "mov.u32 n, 0;\n"
      "W: mbarrier.try_wait.parity.shared.b64 p,[%0],%1,4000;\n"
      "@p bra D;\n"
      "add.u32 n, n, 1;\n"
      "setp.lt.u32 p, n, %2;\n"
      "@p bra W;\n"
      "trap;\n"
      "D:}" ::"r"(a), "r"(par), "n"(SPIN_LIMIT / 16) : "memory");
}
__device__ __forceinline__ void mbar_expect(uint32_t a, uint32_t b) { asm volatile("mbarrier.arrive.expect_tx.shared.b64 _,[%0],%1;" ::"r"(a), "r"(b) : "memory"); }
__device__ __forceinline__ void mbar_arrive(uint32_t a) { asm volatile("mbarrier.arrive.shared.b64 _,[%0];" ::"r"(a) : "memory"); }
__device__ __forceinline__ uint32_t mapa(uint32_t a, uint32_t cta) { uint32_t r; asm("mapa.shared::cluster.u32 %0,%1,%2;" : "=r"(r) : "r"(a), "r"(cta)); return r; }
__device__ __forceinline__ void mbar_arrive_cl(uint32_t a) { asm volatile("mbarrier.arrive.shared::cluster.b64 _,[%0];" ::"r"(a) : "memory"); }
__device__ __forceinline__ void tma2d(uint32_t dst, const CUtensorMap* m, int c0, int c1, uint32_t mb) {
  asm volatile("cp.async.bulk.tensor.2d.shared::cluster.global.mbarrier::complete_tx::bytes [%0],[%1,{%2,%3}],[%4];" ::"r"(dst), "l"(m), "r"(c0), "r"(c1), "r"(mb) : "memory");
}
__device__ __forceinline__ void tma2d_pf(const CUtensorMap* m, int c0, int c1) {
  asm volatile("cp.async.bulk.prefetch.tensor.2d.L2.global [%0,{%1,%2}];" ::"l"(m), "r"(c0), "r"(c1) : "memory");
}
__device__ __forceinline__ void tma2d_st(const CUtensorMap* m, int c0, int c1, uint32_t src) {
  asm volatile("cp.async.bulk.tensor.2d.global.shared::cta.bulk_group [%0,{%1,%2}],[%3];" ::"l"(m), "r"(c0), "r"(c1), "r"(src) : "memory");
}
__device__ __forceinline__ void bulk_ld(uint32_t dst, const void* src, uint32_t n, uint32_t mb) {
  asm volatile("cp.async.bulk.shared::cluster.global.mbarrier::complete_tx::bytes [%0],[%1],%2,[%3];" ::"r"(dst), "l"(src), "r"(n), "r"(mb) : "memory");
}
__device__ __forceinline__ void bulk_st(void* dst, uint32_t src, uint32_t n) {
  asm volatile("cp.async.bulk.global.shared::cta.bulk_group [%0],[%1],%2;" ::"l"(dst), "r"(src), "r"(n) : "memory");
}
__device__ __forceinline__ void e_expect_tma3d(uint32_t dst, const CUtensorMap* m, int c1, int c2, uint32_t mb, uint32_t bytes) {
  asm volatile("{.reg .pred p; elect.sync _|p, 0xffffffff; @p mbarrier.arrive.expect_tx.shared.b64 _,[%4],%5;\n"
               "@p cp.async.bulk.tensor.3d.shared::cluster.global.mbarrier::complete_tx::bytes [%0],[%1,{0,%2,%3}],[%4];}" ::"r"(dst), "l"(m), "r"(c1), "r"(c2), "r"(mb), "r"(bytes) : "memory");
}
__device__ __forceinline__ void e_bulk_ld(uint32_t dst, const void* src, uint32_t n, uint32_t mb) {
  asm volatile("{.reg .pred p; elect.sync _|p, 0xffffffff; @p cp.async.bulk.shared::cluster.global.mbarrier::complete_tx::bytes [%0],[%1],%2,[%3];}" ::"r"(dst), "l"(src), "r"(n), "r"(mb) : "memory");
}
#define BULK_COMMIT() asm volatile("cp.async.bulk.commit_group;" ::: "memory")
#define BULK_WAIT_READ(n) asm volatile("cp.async.bulk.wait_group.read " #n ";" ::: "memory")
#define BULK_WAIT(n) asm volatile("cp.async.bulk.wait_group " #n ";" ::: "memory")
#define FENCE_ASYNC_SMEM() asm volatile("fence.proxy.async.shared::cta;" ::: "memory")
#define FENCE_ASYNC() asm volatile("fence.proxy.async;" ::: "memory")
#define WG_FENCE() asm volatile("wgmma.fence.sync.aligned;" ::: "memory")
#define WG_COMMIT() asm volatile("wgmma.commit_group.sync.aligned;" ::: "memory")
#define WG_WAIT(n) asm volatile("wgmma.wait_group.sync.aligned " #n ";" ::: "memory")
#define BAR_SYNC(id, n) asm volatile("bar.sync %0,%1;" ::"n"(id), "n"(n) : "memory")
#define BAR_ARRIVE(id, n) asm volatile("bar.arrive %0,%1;" ::"n"(id), "n"(n) : "memory")
#define SCHED_FENCE(k) asm volatile("{.reg .pred p; setp.ne.u32 p,%0,0; @p trap;}" ::"r"(mp.zero[(k) - 46]) : "memory")
#define CLUSTER_SYNC() asm volatile("barrier.cluster.arrive.relaxed.aligned; barrier.cluster.wait.aligned;" ::: "memory")
__device__ __forceinline__ uint32_t pk(float lo, float hi) { uint32_t r; asm("cvt.rn.bf16x2.f32 %0,%1,%2;" : "=r"(r) : "f"(hi), "f"(lo)); return r; }
__device__ __forceinline__ float blo(uint32_t v) { return __uint_as_float(v << 16); }
__device__ __forceinline__ float bhi(uint32_t v) { return __uint_as_float(v & 0xffff0000u); }
__device__ __forceinline__ void ldsm4(uint32_t* r, uint32_t a) {
  asm volatile("ldmatrix.sync.aligned.m8n8.x4.shared.b16 {%0,%1,%2,%3},[%4];" : "=r"(r[0]), "=r"(r[1]), "=r"(r[2]), "=r"(r[3]) : "r"(a) : "memory");
}
__device__ __forceinline__ void ldsm4t(uint32_t* r, uint32_t a) {
  asm volatile("ldmatrix.sync.aligned.m8n8.x4.trans.shared.b16 {%0,%1,%2,%3},[%4];" : "=r"(r[0]), "=r"(r[1]), "=r"(r[2]), "=r"(r[3]) : "r"(a) : "memory");
}
__device__ __forceinline__ void stsm4(uint32_t a, uint32_t r0, uint32_t r1, uint32_t r2, uint32_t r3) {
  asm volatile("stmatrix.sync.aligned.m8n8.x4.shared.b16 [%0],{%1,%2,%3,%4};" ::"r"(a), "r"(r0), "r"(r1), "r"(r2), "r"(r3) : "memory");
}
__device__ __forceinline__ void mma16(float* d, uint32_t a0, uint32_t a1, uint32_t a2, uint32_t a3, uint32_t b0, uint32_t b1) {
  asm volatile("mma.sync.aligned.m16n8k16.row.col.f32.bf16.bf16.f32 {%0,%1,%2,%3},{%4,%5,%6,%7},{%8,%9},{%0,%1,%2,%3};"
               : "+f"(d[0]), "+f"(d[1]), "+f"(d[2]), "+f"(d[3]) : "r"(a0), "r"(a1), "r"(a2), "r"(a3), "r"(b0), "r"(b1));
}
__device__ __forceinline__ void mma8(float* d, uint32_t a0, uint32_t a1, uint32_t b0) {
  asm volatile("mma.sync.aligned.m16n8k8.row.col.f32.bf16.bf16.f32 {%0,%1,%2,%3},{%4,%5},{%6},{%0,%1,%2,%3};"
               : "+f"(d[0]), "+f"(d[1]), "+f"(d[2]), "+f"(d[3]) : "r"(a0), "r"(a1), "r"(b0));
}
__device__ __forceinline__ float4 lds4f(uint32_t a) { float4 v; asm volatile("ld.shared.v4.f32 {%0,%1,%2,%3},[%4];" : "=f"(v.x), "=f"(v.y), "=f"(v.z), "=f"(v.w) : "r"(a) : "memory"); return v; }
__device__ __forceinline__ float2 lds2f(uint32_t a) { float2 v; asm volatile("ld.shared.v2.f32 {%0,%1},[%2];" : "=f"(v.x), "=f"(v.y) : "r"(a) : "memory"); return v; }
__device__ __forceinline__ uint4 lds4(uint32_t a) { uint4 v; asm volatile("ld.shared.v4.u32 {%0,%1,%2,%3},[%4];" : "=r"(v.x), "=r"(v.y), "=r"(v.z), "=r"(v.w) : "r"(a) : "memory"); return v; }
__device__ __forceinline__ uint2 lds2u(uint32_t a) { uint2 v; asm volatile("ld.shared.v2.u32 {%0,%1},[%2];" : "=r"(v.x), "=r"(v.y) : "r"(a) : "memory"); return v; }
__device__ __forceinline__ uint32_t lds1(uint32_t a) { uint32_t v; asm volatile("ld.shared.u32 %0,[%1];" : "=r"(v) : "r"(a) : "memory"); return v; }
__device__ __forceinline__ void sts4(uint32_t a, uint32_t x, uint32_t y, uint32_t z, uint32_t w) { asm volatile("st.shared.v4.u32 [%0],{%1,%2,%3,%4};" ::"r"(a), "r"(x), "r"(y), "r"(z), "r"(w) : "memory"); }
__device__ __forceinline__ void sts2(uint32_t a, uint32_t x, uint32_t y) { asm volatile("st.shared.v2.u32 [%0],{%1,%2};" ::"r"(a), "r"(x), "r"(y) : "memory"); }
__device__ __forceinline__ void sts1(uint32_t a, uint32_t x) { asm volatile("st.shared.u32 [%0],%1;" ::"r"(a), "r"(x) : "memory"); }
__device__ __forceinline__ void sta4(uint32_t a, const uint32_t* v, uint32_t mb) {
  asm volatile("st.async.shared::cluster.mbarrier::complete_tx::bytes.v4.b32 [%0],{%1,%2,%3,%4},[%5];" ::"r"(a), "r"(v[0]), "r"(v[1]), "r"(v[2]), "r"(v[3]), "r"(mb) : "memory");
}
__device__ __forceinline__ uint4 ldg_rlx4(const void* p) { uint4 v; asm volatile("ld.relaxed.gpu.global.v4.u32 {%0,%1,%2,%3},[%4];" : "=r"(v.x), "=r"(v.y), "=r"(v.z), "=r"(v.w) : "l"(p) : "memory"); return v; }
__device__ __forceinline__ uint32_t ldg_rlx1(const void* p) { uint32_t v; asm volatile("ld.relaxed.gpu.global.u32 %0,[%1];" : "=r"(v) : "l"(p) : "memory"); return v; }
__device__ __forceinline__ uint4 ldg_b128(const void* p) {
  uint4 v;
  asm volatile("{.reg .b128 t; .reg .b64 a,b; ld.relaxed.gpu.global.b128 t,[%4]; mov.b128 {a,b},t; mov.b64 {%0,%1},a; mov.b64 {%2,%3},b;}" : "=r"(v.x), "=r"(v.y), "=r"(v.z), "=r"(v.w) : "l"(p) : "memory");
  return v;
}
__device__ __forceinline__ void stg_b128(void* p, uint32_t x, uint32_t y, uint32_t z, uint32_t w) {
  asm volatile("{.reg .b128 t; .reg .b64 a,b; mov.b64 a,{%1,%2}; mov.b64 b,{%3,%4}; mov.b128 t,{a,b}; st.relaxed.gpu.global.b128 [%0],t;}" ::"l"(p), "r"(x), "r"(y), "r"(z), "r"(w) : "memory");
}
__device__ __forceinline__ void stg_rlx2(void* p, uint32_t x, uint32_t y) { asm volatile("st.relaxed.gpu.global.v2.u32 [%0],{%1,%2};" ::"l"(p), "r"(x), "r"(y) : "memory"); }
__device__ __forceinline__ unsigned ld_acq(const unsigned* p) { unsigned v; asm volatile("ld.acquire.gpu.global.u32 %0,[%1];" : "=r"(v) : "l"(p) : "memory"); return v; }
__device__ __forceinline__ void red_rel(unsigned* p) { asm volatile("red.release.gpu.global.add.u32 [%0],1;" ::"l"(p) : "memory"); }
__device__ __forceinline__ void red_rlx(unsigned* p) { asm volatile("red.relaxed.gpu.global.add.u32 [%0],1;" ::"l"(p) : "memory"); }
__device__ __forceinline__ void wait_cnt(const unsigned* p, unsigned n) { int it = 0; while (ld_acq(p) < n) { if (++it > SPIN_LIMIT) __trap(); } }
__device__ __forceinline__ uint32_t clk() { uint32_t c; asm volatile("mov.u32 %0,%%clock;" : "=r"(c)); return c; }
__device__ __forceinline__ uint32_t gtime() { uint32_t c; asm volatile("mov.u32 %0,%%globaltimer_lo;" : "=r"(c)); return c; }
__device__ __forceinline__ float ex2(float x) { float r; asm("ex2.approx.ftz.f32 %0,%1;" : "=f"(r) : "f"(x)); return r; }
__device__ __forceinline__ float silu(float x) { return x * __frcp_rn(1.f + __expf(-x)); }
__device__ __forceinline__ float rbf(float x) { return __bfloat162float(__float2bfloat16_rn(x)); }

__device__ __forceinline__ void wgmma_ss_n128(float* d, uint64_t a, uint64_t b, int sd) {
  asm volatile("{.reg .pred p; setp.ne.b32 p, %66, 0;\n"
    "wgmma.mma_async.sync.aligned.m64n128k16.f32.bf16.bf16 {%0,%1,%2,%3,%4,%5,%6,%7,%8,%9,%10,%11,%12,%13,%14,%15,%16,%17,%18,%19,%20,%21,%22,%23,%24,%25,%26,%27,%28,%29,%30,%31,%32,%33,%34,%35,%36,%37,%38,%39,%40,%41,%42,%43,%44,%45,%46,%47,%48,%49,%50,%51,%52,%53,%54,%55,%56,%57,%58,%59,%60,%61,%62,%63}, %64, %65, p, 1, 1, 0, 1;}\n"
    : "+f"(d[0]),"+f"(d[1]),"+f"(d[2]),"+f"(d[3]),"+f"(d[4]),"+f"(d[5]),"+f"(d[6]),"+f"(d[7]),
      "+f"(d[8]),"+f"(d[9]),"+f"(d[10]),"+f"(d[11]),"+f"(d[12]),"+f"(d[13]),"+f"(d[14]),"+f"(d[15]),
      "+f"(d[16]),"+f"(d[17]),"+f"(d[18]),"+f"(d[19]),"+f"(d[20]),"+f"(d[21]),"+f"(d[22]),"+f"(d[23]),
      "+f"(d[24]),"+f"(d[25]),"+f"(d[26]),"+f"(d[27]),"+f"(d[28]),"+f"(d[29]),"+f"(d[30]),"+f"(d[31]),
      "+f"(d[32]),"+f"(d[33]),"+f"(d[34]),"+f"(d[35]),"+f"(d[36]),"+f"(d[37]),"+f"(d[38]),"+f"(d[39]),
      "+f"(d[40]),"+f"(d[41]),"+f"(d[42]),"+f"(d[43]),"+f"(d[44]),"+f"(d[45]),"+f"(d[46]),"+f"(d[47]),
      "+f"(d[48]),"+f"(d[49]),"+f"(d[50]),"+f"(d[51]),"+f"(d[52]),"+f"(d[53]),"+f"(d[54]),"+f"(d[55]),
      "+f"(d[56]),"+f"(d[57]),"+f"(d[58]),"+f"(d[59]),"+f"(d[60]),"+f"(d[61]),"+f"(d[62]),"+f"(d[63])
    : "l"(a), "l"(b), "r"(sd));
}
__device__ __forceinline__ void wgmma_ss_n192(float* d, uint64_t a, uint64_t b, int sd) {
  asm volatile("{.reg .pred p; setp.ne.b32 p, %98, 0;\n"
    "wgmma.mma_async.sync.aligned.m64n192k16.f32.bf16.bf16 {%0,%1,%2,%3,%4,%5,%6,%7,%8,%9,%10,%11,%12,%13,%14,%15,%16,%17,%18,%19,%20,%21,%22,%23,%24,%25,%26,%27,%28,%29,%30,%31,%32,%33,%34,%35,%36,%37,%38,%39,%40,%41,%42,%43,%44,%45,%46,%47,%48,%49,%50,%51,%52,%53,%54,%55,%56,%57,%58,%59,%60,%61,%62,%63,%64,%65,%66,%67,%68,%69,%70,%71,%72,%73,%74,%75,%76,%77,%78,%79,%80,%81,%82,%83,%84,%85,%86,%87,%88,%89,%90,%91,%92,%93,%94,%95}, %96, %97, p, 1, 1, 0, 1;}\n"
    : "+f"(d[0]),"+f"(d[1]),"+f"(d[2]),"+f"(d[3]),"+f"(d[4]),"+f"(d[5]),"+f"(d[6]),"+f"(d[7]),
      "+f"(d[8]),"+f"(d[9]),"+f"(d[10]),"+f"(d[11]),"+f"(d[12]),"+f"(d[13]),"+f"(d[14]),"+f"(d[15]),
      "+f"(d[16]),"+f"(d[17]),"+f"(d[18]),"+f"(d[19]),"+f"(d[20]),"+f"(d[21]),"+f"(d[22]),"+f"(d[23]),
      "+f"(d[24]),"+f"(d[25]),"+f"(d[26]),"+f"(d[27]),"+f"(d[28]),"+f"(d[29]),"+f"(d[30]),"+f"(d[31]),
      "+f"(d[32]),"+f"(d[33]),"+f"(d[34]),"+f"(d[35]),"+f"(d[36]),"+f"(d[37]),"+f"(d[38]),"+f"(d[39]),
      "+f"(d[40]),"+f"(d[41]),"+f"(d[42]),"+f"(d[43]),"+f"(d[44]),"+f"(d[45]),"+f"(d[46]),"+f"(d[47]),
      "+f"(d[48]),"+f"(d[49]),"+f"(d[50]),"+f"(d[51]),"+f"(d[52]),"+f"(d[53]),"+f"(d[54]),"+f"(d[55]),
      "+f"(d[56]),"+f"(d[57]),"+f"(d[58]),"+f"(d[59]),"+f"(d[60]),"+f"(d[61]),"+f"(d[62]),"+f"(d[63]),
      "+f"(d[64]),"+f"(d[65]),"+f"(d[66]),"+f"(d[67]),"+f"(d[68]),"+f"(d[69]),"+f"(d[70]),"+f"(d[71]),
      "+f"(d[72]),"+f"(d[73]),"+f"(d[74]),"+f"(d[75]),"+f"(d[76]),"+f"(d[77]),"+f"(d[78]),"+f"(d[79]),
      "+f"(d[80]),"+f"(d[81]),"+f"(d[82]),"+f"(d[83]),"+f"(d[84]),"+f"(d[85]),"+f"(d[86]),"+f"(d[87]),
      "+f"(d[88]),"+f"(d[89]),"+f"(d[90]),"+f"(d[91]),"+f"(d[92]),"+f"(d[93]),"+f"(d[94]),"+f"(d[95])
    : "l"(a), "l"(b), "r"(sd));
}
__device__ __forceinline__ void wgmma_rs_n32(float* d, const uint32_t* a, uint64_t b, int sd) {
  asm volatile("{.reg .pred p; setp.ne.b32 p, %21, 0;\n"
    "wgmma.mma_async.sync.aligned.m64n32k16.f32.bf16.bf16 {%0,%1,%2,%3,%4,%5,%6,%7,%8,%9,%10,%11,%12,%13,%14,%15}, {%16,%17,%18,%19}, %20, p, 1, 1, 0;}\n"
    : "+f"(d[0]),"+f"(d[1]),"+f"(d[2]),"+f"(d[3]),"+f"(d[4]),"+f"(d[5]),"+f"(d[6]),"+f"(d[7]),
      "+f"(d[8]),"+f"(d[9]),"+f"(d[10]),"+f"(d[11]),"+f"(d[12]),"+f"(d[13]),"+f"(d[14]),"+f"(d[15])
    : "r"(a[0]), "r"(a[1]), "r"(a[2]), "r"(a[3]), "l"(b), "r"(sd));
}
__device__ __forceinline__ void wgmma_ssT_n32(float* d, uint64_t a, uint64_t b, int sd) {
  asm volatile("{.reg .pred p; setp.ne.b32 p, %18, 0;\n"
    "wgmma.mma_async.sync.aligned.m64n32k16.f32.bf16.bf16 {%0,%1,%2,%3,%4,%5,%6,%7,%8,%9,%10,%11,%12,%13,%14,%15}, %16, %17, p, 1, 1, 1, 0;}\n"
    : "+f"(d[0]),"+f"(d[1]),"+f"(d[2]),"+f"(d[3]),"+f"(d[4]),"+f"(d[5]),"+f"(d[6]),"+f"(d[7]),
      "+f"(d[8]),"+f"(d[9]),"+f"(d[10]),"+f"(d[11]),"+f"(d[12]),"+f"(d[13]),"+f"(d[14]),"+f"(d[15])
    : "l"(a), "l"(b), "r"(sd));
}

__device__ __forceinline__ void wgmma_rs_n32_z(float* d, const uint32_t* a, uint64_t b) {
  asm volatile("{.reg .pred p; setp.ne.b32 p, 0, 0;\n"
    "wgmma.mma_async.sync.aligned.m64n32k16.f32.bf16.bf16 {%0,%1,%2,%3,%4,%5,%6,%7,%8,%9,%10,%11,%12,%13,%14,%15}, {%16,%17,%18,%19}, %20, p, 1, 1, 0;}\n"
    : "=f"(d[0]),"=f"(d[1]),"=f"(d[2]),"=f"(d[3]),"=f"(d[4]),"=f"(d[5]),"=f"(d[6]),"=f"(d[7]),
      "=f"(d[8]),"=f"(d[9]),"=f"(d[10]),"=f"(d[11]),"=f"(d[12]),"=f"(d[13]),"=f"(d[14]),"=f"(d[15])
    : "r"(a[0]), "r"(a[1]), "r"(a[2]), "r"(a[3]), "l"(b));
}

namespace rec {
constexpr int NVR = P_NVR;
constexpr int NVS = 16 - NVR;
constexpr int NWP = P_NWP;
constexpr uint32_t WO = 0;
constexpr uint32_t XB = 65536;
constexpr uint32_t PK = XB + 32768;
constexpr uint32_t VX0 = PK + 24576;
constexpr uint32_t VX1 = VX0 + 4096;
constexpr uint32_t WVS = 131072;
constexpr uint32_t MEM = WVS + 2 * NVS * 2048;
constexpr uint32_t ARO = MEM + 10240;
constexpr uint32_t OB = ARO + 5120;
constexpr uint32_t QT = OB + 2048;
constexpr uint32_t KT = QT + 2048;
constexpr uint32_t RQ = KT + 6144;
constexpr uint32_t RK = RQ + 2048;
constexpr uint32_t SC = RK + 2048;
constexpr uint32_t OT = OB;
constexpr uint32_t TF = SC + 2048;
constexpr uint32_t PRE = MEM + 2 * NVR * 2048;
constexpr uint32_t TA = TF + 8192;
constexpr uint32_t RX = TA + 6144;
constexpr uint32_t VN = RX + 2048;
constexpr uint32_t BARS = VN + 4096;
constexpr uint32_t PACE = BARS + 18 * 8;
constexpr uint32_t SMEM = BARS + 512;
static_assert(PRE + 14336 <= BARS, "staging");
constexpr int NW1 = P_NW1;
static_assert(SMEM <= 232448, "smem");
constexpr int B_E = 2, B_SC = 3, B_S = 4, B_O = 5, B_F = 6, B_W = 7, B_C = 9, B_K = 10, B_Q = 1, B_S2 = 6, B_T2 = 9, B_P = 13, B_T = 14, B_R = 11, B_X = 12, B_V = 8;
constexpr int XC = 16384, X_RING = 131072, X_SC = 65536, X_TOK = 4096;
#define X_VX(i) (((i) >> 1) * 2048 + ((i) & 1) * 512)
#define X_VM(i) (X_VX(i) + 1024)
#define V_RING(n) (((n) & 1) * X_RING + ((n) & 2) * 2048)
#define V_TAG(n) ((~(n) >> 2) & 1)
}
struct RecMaps { CUtensorMap wq, wk, wv, wo, ari, vx; int zero[40]; };

#define F_(x) __uint_as_float(x)
#define U_(x) __float_as_uint(x)
#define AR_R(q) (24 + ((q) & 1) * 16 + ((q) >> 1) * 56)
#define AR_P(q) ((q) >> 1)
#define AR_ROW(i) (24 + ((i) & 1) * 16 + ((i) & 2) * 92 + (((i) >> 2) & 7) + ((i) >> 5) * 128)
constexpr size_t AR_OFF = 32 * 262144;
__device__ __forceinline__ void ar_fetch(uint32_t dst, const CUtensorMap* m, int slot, int half, uint32_t mb) {
  asm volatile("{.reg .pred p; elect.sync _|p, 0xffffffff; @p mbarrier.arrive.expect_tx.shared.b64 _,[%4],10240;\n"
               "@p cp.async.bulk.tensor.3d.shared::cluster.global.mbarrier::complete_tx::bytes [%0],[%1,{%2,%6,%3}],[%4];\n"
               "@p cp.async.bulk.tensor.3d.shared::cluster.global.mbarrier::complete_tx::bytes [%0+5120],[%1,{%2,%7,%5}],[%4];}"
               ::"r"(dst), "l"(m), "r"(slot * 64), "r"(AR_R(half * 2)), "r"(mb), "r"(AR_R(half * 2 + 1)), "r"(AR_P(half * 2)), "r"(AR_P(half * 2 + 1)) : "memory");
}
__device__ __forceinline__ uint4 exch_b128(void* p, uint32_t x, uint32_t y, uint32_t z, uint32_t w) {
  uint4 v;
  asm volatile("{.reg .b128 s, t; .reg .b64 a,b; mov.b64 a,{%5,%6}; mov.b64 b,{%7,%8}; mov.b128 s,{a,b}; atom.relaxed.gpu.global.exch.b128 t,[%4],s;"
               " mov.b128 {a,b},t; mov.b64 {%0,%1},a; mov.b64 {%2,%3},b;}" : "=r"(v.x), "=r"(v.y), "=r"(v.z), "=r"(v.w) : "l"(p), "r"(x), "r"(y), "r"(z), "r"(w) : "memory");
  return v;
}
#define CONSUME(v) do { if ((v) == 0x7fc12345u) sts1(sb + rec::BARS + 96, 0); } while (0)
__device__ __forceinline__ uint2 ldg_b64(const void* p) { uint2 v; asm volatile("{.reg .b64 t; ld.relaxed.gpu.global.b64 t,[%2]; mov.b64 {%0,%1},t;}" : "=r"(v.x), "=r"(v.y) : "l"(p) : "memory"); return v; }
__device__ __forceinline__ void stg_b64(void* p, uint32_t x, uint32_t y) { asm volatile("{.reg .b64 t; mov.b64 t,{%1,%2}; st.relaxed.gpu.global.b64 [%0],t;}" ::"l"(p), "r"(x), "r"(y) : "memory"); }
__device__ __forceinline__ uint32_t tagbad(uint32_t x, uint32_t y, uint32_t tag) { uint32_t r; asm("lop3.b32 %0,%1,%2,%3,0x7e;" : "=r"(r) : "r"(x), "r"(y), "r"(tag)); return r; }

__device__ __forceinline__ bool anybad(uint32_t a, uint32_t b, uint32_t c, uint32_t d, uint32_t e, uint32_t f, uint32_t g, uint32_t h, uint32_t tag) {
  uint32_t r;
  asm volatile("{.reg .b32 t,u,v,w; .reg .pred p; lop3.b32 t,%1,%2,%9,0x7e; lop3.b32 u,%3,%4,%9,0x7e; lop3.b32 v,%5,%6,%9,0x7e; lop3.b32 w,%7,%8,%9,0x7e;"
               " lop3.b32 t,t,u,v,0xfe; lop3.b32 t,t,w,1,0xa8; setp.ne.u32 p,t,0; vote.sync.any.pred p,p,0xffffffff; selp.u32 %0,1,0,p;}"
               : "=r"(r) : "r"(a), "r"(b), "r"(c), "r"(d), "r"(e), "r"(f), "r"(g), "r"(h), "r"(tag));
  return r;
}
__device__ __forceinline__ bool anybad(uint32_t a, uint32_t b, uint32_t c, uint32_t d, uint32_t tag) {
  uint32_t r;
  asm volatile("{.reg .b32 t,u; .reg .pred p; lop3.b32 t,%1,%2,%5,0x7e; lop3.b32 u,%3,%4,%5,0x7e;"
               " lop3.b32 t,t,u,1,0xa8; setp.ne.u32 p,t,0; vote.sync.any.pred p,p,0xffffffff; selp.u32 %0,1,0,p;}"
               : "=r"(r) : "r"(a), "r"(b), "r"(c), "r"(d), "r"(tag));
  return r;
}
#define BADS(r) anybad(r[0].x, r[0].y, r[1].x, r[1].y, r[2].x, r[2].y, r[3].x, r[3].y, tag)
constexpr float SCS = 0.08838834764831845f * 1.4426950408889634f / 16.f;
__device__ __forceinline__ uint32_t pkh(float lo, float hi, uint32_t tag) {
  uint32_t r;
  asm("{.reg .b32 t; cvt.rn.satfinite.f16x2.f32 t,%1,%2; lop3.b32 %0,t,0xfffffffe,%3,0xea;}" : "=r"(r) : "f"(hi), "f"(lo), "r"(tag));
  return r;
}
__device__ __forceinline__ uint32_t addh(uint32_t a, uint32_t b) { uint32_t r; asm("add.rn.f16x2 %0,%1,%2;" : "=r"(r) : "r"(a), "r"(b)); return r; }
__device__ __forceinline__ float hlo(uint32_t v) { float r; asm("{.reg .b16 a,b; mov.b32 {a,b},%1; cvt.f32.f16 %0,a;}" : "=f"(r) : "r"(v)); return r; }
__device__ __forceinline__ float hhi(uint32_t v) { float r; asm("{.reg .b16 a,b; mov.b32 {a,b},%1; cvt.f32.f16 %0,b;}" : "=f"(r) : "r"(v)); return r; }
__device__ __forceinline__ uint32_t ordh(uint32_t v) {
  uint32_t r;
  asm("{.reg .b32 m; prmt.b32 m,%1,0,0xbb99; lop3.b32 %0,%1,m,0x7fff7fff,0x78;}" : "=r"(r) : "r"(v));
  return r;
}
template <bool MASK>
__device__ __forceinline__ float4 softmax2(const uint2 (&r)[4], uint32_t mx, uint32_t my, uint32_t& k) {
  uint32_t x = addh(addh(r[0].x, r[1].x), addh(r[2].x, r[3].x)), y = addh(addh(r[0].y, r[1].y), addh(r[2].y, r[3].y));
  if (MASK) { x = addh(x, mx); y = addh(y, my); }
  asm("max.f16x2 %0,%1,%2;" : "=r"(k) : "r"(x), "r"(y));
  k = ordh(k);
  const int k0 = __reduce_max_sync(~0u, (int)(k << 16)), k1 = __reduce_max_sync(~0u, (int)k);
  const float m0 = hhi(k0 ^ ((k0 >> 31) & 0x7fff0000)) * -16.f, m1 = hhi(k1 ^ ((k1 >> 31) & 0x7fff0000)) * -16.f;
  return make_float4(ex2(fmaf(hlo(x), 16.f, m0)), ex2(fmaf(hhi(x), 16.f, m1)), ex2(fmaf(hlo(y), 16.f, m0)), ex2(fmaf(hhi(y), 16.f, m1)));
}
__device__ __forceinline__ char* mkp(uint32_t lo, uint32_t hi) { uint64_t r; asm("mov.b64 %0,{%1,%2};" : "=l"(r) : "r"(lo), "r"(hi)); return (char*)r; }
#define LO(p) ((uint32_t)(uint64_t)(p))
#define HI(p) ((uint32_t)((uint64_t)(p) >> 32))
__device__ __forceinline__ uint32_t mulbf(uint32_t a, uint32_t b) { uint32_t r; asm("mul.rn.bf16x2 %0,%1,%2;" : "=r"(r) : "r"(a), "r"(b)); return r; }
__device__ __forceinline__ uint32_t fmabf(uint32_t a, uint32_t b, uint32_t c) { uint32_t r; asm("fma.rn.bf16x2 %0,%1,%2,%3;" : "=r"(r) : "r"(a), "r"(b), "r"(c)); return r; }
__device__ __forceinline__ uint32_t addbf(uint32_t a, uint32_t b) { uint32_t r; asm("add.rn.bf16x2 %0,%1,%2;" : "=r"(r) : "r"(a), "r"(b)); return r; }
__device__ __forceinline__ void pv_mem(const uint32_t (&p)[4], uint32_t pm, const uint4 (&v)[4], const uint4 (&vn)[2], uint32_t (&O)[4]) {
  float o[4][4] = {{0, 0, 0, 0}, {0, 0, 0, 0}, {0, 0, 0, 0}, {0, 0, 0, 0}};
  mma16(o[0], v[0].x, v[0].y, v[0].z, v[0].w, p[0], p[1]);
  mma16(o[1], v[2].x, v[2].y, v[2].z, v[2].w, p[0], p[1]);
  mma16(o[2], v[1].x, v[1].y, v[1].z, v[1].w, p[2], p[3]);
  mma16(o[3], v[3].x, v[3].y, v[3].z, v[3].w, p[2], p[3]);
  mma16(o[0], vn[0].x, vn[0].y, vn[0].z, vn[0].w, pm, pm);
  mma16(o[1], vn[1].x, vn[1].y, vn[1].z, vn[1].w, pm, pm);
  O[0] = pk(o[0][0] + o[2][0], o[0][1] + o[2][1]); O[1] = pk(o[0][2] + o[2][2], o[0][3] + o[2][3]);
  O[2] = pk(o[1][0] + o[3][0], o[1][1] + o[3][1]); O[3] = pk(o[1][2] + o[3][2], o[1][3] + o[3][3]);
}
__device__ __forceinline__ void pv_tok(const uint32_t (&p)[4], uint32_t pm, const uint4 (&v)[4], const uint32_t (&vm)[4], uint32_t (&O)[4]) {
  float o[2][4] = {{0, 0, 0, 0}, {0, 0, 0, 0}}, sum[4] = {0, 0, 0, 0};
  const uint32_t one = 0x3f803f80u;
  mma16(sum, one, one, one, one, p[0], p[1]);
  mma16(o[0], v[0].x, v[0].y, v[0].z, v[0].w, p[0], p[1]);
  mma16(o[1], v[2].x, v[2].y, v[2].z, v[2].w, p[0], p[1]);
  mma16(sum, one, one, one, one, p[2], p[3]);
  mma16(o[0], v[1].x, v[1].y, v[1].z, v[1].w, p[2], p[3]);
  mma16(o[1], v[3].x, v[3].y, v[3].z, v[3].w, p[2], p[3]);
  mma8(sum, one, one, pm);
  mma8(o[0], vm[0], vm[1], pm);
  mma8(o[1], vm[2], vm[3], pm);
  float i0, i1;
  asm("rcp.approx.ftz.f32 %0,%1;" : "=f"(i0) : "f"(sum[0]));
  asm("rcp.approx.ftz.f32 %0,%1;" : "=f"(i1) : "f"(sum[1]));
  O[0] = pk(o[0][0] * i0, o[0][1] * i1); O[1] = pk(o[0][2] * i0, o[0][3] * i1);
  O[2] = pk(o[1][0] * i0, o[1][1] * i1); O[3] = pk(o[1][2] * i0, o[1][3] * i1);
}
__device__ __forceinline__ uint32_t sum4bf(uint32_t a, uint32_t b, uint32_t c, uint32_t d) { return addbf(addbf(a, b), addbf(c, d)); }
template <int OFF>
__device__ __forceinline__ void sta1(uint32_t a, uint32_t v, uint32_t mb) {
  asm volatile("st.async.shared::cluster.mbarrier::complete_tx::bytes.b32 [%0+%3],%1,[%2];" ::"r"(a), "r"(v), "r"(mb), "n"(OFF) : "memory");
}

__device__ __forceinline__ void wait_time(uint32_t t) { while ((int)(gtime() - t) < 0) __nanosleep(64); }
__device__ __noinline__ void rec_prefetch(const char* wmod, const char* w1, const char* x, const char* wo) {
  const int hb = blockIdx.x - 128;
  const uint32_t t0 = gtime();
  uint32_t t = t0 + PF0;
#pragma unroll 1
  for (int job = 0; job < (PFT ? 5 : 3); job++) {
    const char* p = job == 0 ? x + (6 + hb) * 65536 : job == 1 ? wmod + hb * 12288 + 4096 : job == 2 ? w1 + hb * 7168 : job == 3 ? x + hb * 8192 : wo + (1020 + hb) * 8192;
    const int n = job == 0 ? 120 - (hb & 2) * 4 : job == 3 ? 128 : 256, d = job == 0 ? 8192 : job == 1 ? 49152 : job == 2 ? 28672 : job == 3 ? 32768 : -32768;
    if (job == 3) t = t0 + PFT;
    PT(8 + job);
#pragma unroll 1
    for (int i = 0; i < n; i++) {
      wait_time(t);
      asm volatile("cp.async.bulk.prefetch.L2.global [%0], %1;" ::"l"(p), "r"(job == 2 ? 7168 : 8192) : "memory");
      p += !job && (i & 7) == 7 ? 204800 : d;
      t += job < 3 ? PFD : PFS;
      if (job && (i & 31) == 31 && ldg_rlx1(&g_fin)) return;
    }
  }
  PT(13);
}
__device__ __noinline__ void rec_helper(uint32_t sb, const bf16* cvec, const bf16* wmod, const char* w1, const bf16* b1, uint32_t t0) {
  const int tid = threadIdx.x, hb = blockIdx.x - 128;
  PT(1);
  for (int i = tid; i < 1024; i += 256) sts1(sb + i * 8, U_(rbf(silu(__bfloat162float(cvec[i])))));
  for (int i = tid; i < 2048; i += 256) g_stat[hb * 2048 + i] = make_uint4(~0u, ~0u, ~0u, ~0u);
  for (int i = tid; i < 512; i += 256) g_cnt[hb * 512 + i] = 0;
#pragma unroll 1
  for (int job = 0; job < 2; job++) {
    wait_time(t0 + PF0 + (job ? 600 : 350) * PFD);
    BAR_SYNC(rec::B_F, 256);
    PT(2 + job * 5);
    const int n8 = job ? 112 : 128, rg = tid >= n8, cg = tid - rg * n8, pitch = job ? 448 : 768;
    const uint4* p = (const uint4*)(job ? w1 + hb * 1792 : (const char*)(wmod + 2048 + hb * 1024)) + rg * pitch + min(cg, n8 - 1);
    float a1[8] = {0, 0, 0, 0, 0, 0, 0, 0}, a2[8] = {0, 0, 0, 0, 0, 0, 0, 0};
#pragma unroll 1
    for (int r0 = rg; r0 < 1024; r0 += 32) {
      uint4 v[16];
#pragma unroll
      for (int i = 0; i < 16; i++) { v[i] = ldg_rlx4(p); p += 2 * pitch; }
#pragma unroll
      for (int i = 0; i < 16; i++) {
        const float2 f = lds2f(sb + (r0 + 2 * i) * 8);
        const float w[8] = {blo(v[i].x), bhi(v[i].x), blo(v[i].y), bhi(v[i].y), blo(v[i].z), bhi(v[i].z), blo(v[i].w), bhi(v[i].w)};
#pragma unroll
        for (int e = 0; e < 8; e++) { a1[e] += f.x * w[e]; a2[e] += f.y * w[e]; }
      }
    }
    const uint32_t rd = sb + 8192;
    if (cg < n8) {
#pragma unroll
      for (int e = 0; e < 8; e++) sts2(rd + rg * 8192 + (cg * 8 + e) * 8, U_(a1[e]), U_(a2[e]));
    }
    BAR_SYNC(rec::B_F, 256);
    if (job == 0) {
      for (int i = tid; i < 1024; i += 256) g_mod[2048 + hb * 1024 + i] = rbf(F_(lds1(rd + i * 8)) + F_(lds1(rd + 8192 + i * 8)));
      BAR_SYNC(rec::B_F, 256);
      PT(6);
      if (tid == 0) { red_rel(&g_mcnt); wait_cnt(&g_mcnt, 4); }
      BAR_SYNC(rec::B_F, 256);
      for (int i = tid; i < 1024; i += 256) sts2(sb + i * 8, U_(rbf(1.f + __ldcg(g_mod + 4096 + i))), U_(__ldcg(g_mod + 3072 + i)));
    } else {
      for (int i = tid; i < 448; i += 256) {
        const int gn = hb * 896 + i * 2;
        const uint32_t bb = *(const uint32_t*)(b1 + gn);
        const float4 u = lds4f(rd + i * 16), w = lds4f(rd + 8192 + i * 16);
        ((uint2*)g_cc)[(gn >> 4) * 8 + ((gn >> 1) & 3) * 2 + ((gn >> 3) & 1)] = make_uint2(pk(u.x + w.x, u.z + w.z), pk(0.5f * (u.y + w.y + blo(bb)), 0.5f * (u.w + w.w + bhi(bb))));
      }
      PT(4);
    }
  }
}

__global__ void __cluster_dims__(2, 1, 1) __launch_bounds__(512, 1)
k_rec(const __grid_constant__ RecMaps mp, const bf16* __restrict__ mem0, const bf16* __restrict__ x, const bf16* __restrict__ cvec,
      const bf16* __restrict__ wmod, const char* __restrict__ w1, const bf16* __restrict__ b1, const char* __restrict__ wo, char* xc, int dF, int dA, int dS, int dM, int dG, int dP, int dX, int dD, int dZ, int dQ, int dV, int dX2) {
  using namespace rec;
  extern __shared__ __align__(1024) char smem[];
  const uint32_t sb = (uint32_t)__cvta_generic_to_shared(smem);
  if ((sb & 0x3FFFF) != 1024) __trap();
  PH(0); RS(0); if (threadIdx.x == 0) PT(0);
  if (threadIdx.x == 0) {
    int b = blockIdx.x;
    if (b >= 8 && b < 128) {
      const int t = (b >> 1) - 4, u = t - 32;
      b = 2 * (t < 32 ? 4 + (t & 16) + (t & 7) * 2 + ((t >> 3) & 1) : 36 + (u / 14) * 14 + (u % 7) * 2 + ((u / 7) & 1)) + (b & 1);
    }
    sts1(sb + rec::PACE + 24, b);
    const int c = blockIdx.x >> 1, l = c < 36 ? (c - 4) & 7 : (c - 36) % 7, m = c < 4 ? c : c < 36 ? (c - 4) >> 3 : (c - 36) / 7;
    const int g = c < 4 ? 15 : (l >> 1) * 4 + (l & 1) + (c < 36 ? 0 : 2);
    unsigned sm;
    asm("mov.u32 %0,%%smid;" : "=r"(sm));
    if (c < 64) g_slot[sm & 255] = 1 + FMAP;
  }
#define ROLE_REFRESH { asm volatile("mov.u32 %0,%%tid.x;" : "=r"(tid)); wid = __shfl_sync(~0u, tid >> 5, 0); b = __shfl_sync(~0u, lds1(sb + PACE + 24), 0); }
#define ROLE_VARS int tid; asm volatile("mov.u32 %0,%%tid.x;" : "=r"(tid)); \
    int wid = __shfl_sync(~0u, tid >> 5, 0), b = __shfl_sync(~0u, lds1(sb + PACE + 24), 0);
#define wg (wid >> 2)
#define iw (wid & 3)
#define h (b >> 2)
#define j (b & 3)
#define a (b & 1)
#define bb ((b >> 1) & 1)
  const uint32_t wbar = sb + BARS + 48, obar = wbar + 8;
  if (threadIdx.x == 256) {
    for (int i = 0; i < 18; i++) if (i != 12) mbar_init(sb + BARS + i * 8, i == 3 || i == 8 || i == 9 || i == 10 ? 2 : 1);
    for (int i = 0; i < 3; i++) mbar_init(sb + PACE + i * 8, 1);
    asm volatile("fence.mbarrier_init.release.cluster;" ::: "memory");
    FENCE_ASYNC_SMEM();
    mbar_expect(sb + BARS, 2048);
    mbar_expect(sb + BARS + 16, 4096);
    mbar_expect(sb + BARS + 32, 4096);
    mbar_expect(sb + BARS + 40, 4096);
  }
  __syncthreads();
  asm volatile("barrier.cluster.arrive.relaxed.aligned;" ::: "memory");
#define lane ((int)(l16 >> 4))
#define l16 (L16 & 0x1f0)
#define PIN(x) __shfl_xor_sync(~0u, (uint32_t)(x), 0)
#define X_LOAD(n, w, u) \
        asm volatile("{.reg .pred p; elect.sync _|p, 0xffffffff; @p mbarrier.arrive.expect_tx.shared.b64 _,[%2],8192;\n" \
                     "@p cp.async.bulk.shared::cluster.global.mbarrier::complete_tx::bytes [%0],[%1],8192,[%2];}" ::"r"(sb + XB + (w) * 16384 + (u) * 8192), \
                     "l"(g_h + (n) * 4096 + a * 2048 + (w) * 1024 + (u) * 512), "r"(sb + BARS + 64 + (w) * 8) : "memory")
#define lpub ((L16 & 0x30) * 64 + ((L16 >> 3) & 0x38))
#define lrow ((L16 & 0x70) + (((L16 >> 3) ^ L16) & 0x70 & ~((L16 >> 3) & 0x40) ? L16 & 0x180 : 512))

  const int role = __shfl_sync(~0u, threadIdx.x >> 7, 0);
  if (role < 2) {
    asm volatile("setmaxnreg.inc.sync.aligned.u32 %0;" ::"n"(RF_));
    ROLE_VARS
    uint32_t L16 = __shfl_sync(~0u, sb + (tid & 31) * 16, tid & 31);
    uint32_t wQ[16][4], wK[16][4], wV[NVR][4];
    uint32_t frag = sb + ((lane & 7) + (lane >> 4) * 8) * 128 + (((iw * 2 + ((lane >> 3) & 1)) ^ (lane & 7)) << 4);
#define QSW (a ? 0 : 64)
    {
      const bool spare = b >= 128;
      const uint32_t t0 = gtime();
      uint4 xr[16];
      int seg = spare ? b - 126 : wg;
      const int half = spare ? wg : a;
      auto x_fetch = [&]() {
        const uint4* px = (const uint4*)x + (seg * 32 + iw * 8 + (lane >> 2)) * 128 + half * 64 + (lane & 3);
#pragma unroll
        for (int i = 0; i < 16; i++) xr[i] = __ldg(px + i * 4);
      };
      if (!spare) {
        uint4 wm[8];
        const uint4* pw = (const uint4*)(wmod + (size_t)((b >> 5) * 256 + (tid >> 3)) * 6144 + (b & 31) * 64) + (tid & 7);
        const float cs = __bfloat162float(cvec[(b >> 5) * 256 + tid]);
#pragma unroll
        for (int i = 0; i < 8; i++) wm[i] = __ldcs(pw + (size_t)i * 32 * 768);
        float* sc = (float*)(smem + PRE);
        sc[tid] = rbf(silu(cs));
        PT(1);
        BAR_SYNC(B_F, 256);
        float acc[8] = {0, 0, 0, 0, 0, 0, 0, 0};
#pragma unroll
        for (int i = 0; i < 8; i++) {
          const float f = sc[i * 32 + (tid >> 3)];
          acc[0] += f * blo(wm[i].x); acc[1] += f * bhi(wm[i].x); acc[2] += f * blo(wm[i].y); acc[3] += f * bhi(wm[i].y);
          acc[4] += f * blo(wm[i].z); acc[5] += f * bhi(wm[i].z); acc[6] += f * blo(wm[i].w); acc[7] += f * bhi(wm[i].w);
        }
#pragma unroll
        for (int i = 0; i < 8; i++) { acc[i] += __shfl_xor_sync(~0u, acc[i], 8); acc[i] += __shfl_xor_sync(~0u, acc[i], 16); }
        float* red = sc + 1024;
        if ((tid & 31) < 8) {
#pragma unroll
          for (int i = 0; i < 8; i++) red[(tid >> 5) * 64 + (tid & 7) * 8 + i] = acc[i];
        }
        BAR_SYNC(B_F, 256);
        PT(2);
        if (tid < 64) {
          float t = 0;
#pragma unroll
          for (int i = 0; i < 8; i++) t += red[i * 64 + tid];
          asm volatile("st.relaxed.gpu.global.u32 [%0],%1;" ::"l"((unsigned*)g_modp + (b >> 5) * 2048 + (b & 31) * 64 + tid), "r"(U_(t) | 1u) : "memory");
        }
      } else {
        asm volatile("griddepcontrol.launch_dependents;");
      }
      x_fetch();
      const uint32_t md = sb + PRE + 6144, rx = mapa(sb, a ^ !spare);
      asm volatile("barrier.cluster.wait.aligned;" ::: "memory");
      if (!spare) {
        mbar_wait(sb + BARS + 88, 0);
#pragma unroll
        for (int i = 0; i < 16; i++) ldsm4t(wQ[i], (frag ^ QSW) + WO + wg * 32768 + i * 2048);
      }
      PT(4);
#pragma unroll 1
      for (int it = 0;; it++) {
        if (tid == 0) mbar_expect(sb + BARS + 104, 512);
        float c[4][4] = {{0, 0, 0, 0}, {0, 0, 0, 0}, {0, 0, 0, 0}, {0, 0, 0, 0}};
#pragma unroll
        for (int i = 0; i < 16; i++) {
          mma16(c[(i & 1) * 2], xr[i].x, 0x3f803f80u, xr[i].y, 0x3f803f80u, xr[i].x, xr[i].y);
          mma16(c[(i & 1) * 2 + 1], xr[i].z, 0x3f803f80u, xr[i].w, 0x3f803f80u, xr[i].z, xr[i].w);
        }
#pragma unroll
        for (int e = 0; e < 4; e++) c[0][e] = (c[0][e] + c[1][e]) + (c[2][e] + c[3][e]);
        const int src = (lane & 28) + (lane >> 3);
        const float sq = __shfl_sync(~0u, (lane & 4) ? c[0][1] : c[0][0], src), sm = __shfl_sync(~0u, (lane & 4) ? c[0][3] : c[0][2], src);
        if ((lane & 3) < 2) sta1<0>(rx + PRE + 10240 + (wid ^ (spare * 4)) * 64 + (lane >> 2) * 8 + (lane & 1) * 4, U_((lane & 1) ? sm : sq), rx + BARS + 104);
        mbar_wait(sb + BARS + 104, it & 1);
        const float2 ot = lds2f(sb + PRE + 10240 + wid * 64 + (lane >> 2) * 8);
        const float mean = (sm + ot.y) * (1.f / 1024);
        const float rs = rsqrtf(fmaxf((sq + ot.x) * (1.f / 1024) - mean * mean, 0.f) + 1e-5f), nm = -mean * rs;
        const uint32_t rh = pk(rs, rs), rl = pk(rs - blo(rh), rs - blo(rh)), n2 = pk(nm, nm);
#define NRM(v) v = fmabf(v, rh, fmabf(v, rl, n2))
#pragma unroll
        for (int i = 0; i < 16; i++) { NRM(xr[i].x); NRM(xr[i].y); NRM(xr[i].z); NRM(xr[i].w); }
        if (!it) {
          PT(3);
#pragma unroll 1
          for (int i = 0; i < 2; i++) {
            uint4 p[4];
            for (int n = 0;; n++) {
#pragma unroll
              for (int e = 0; e < 4; e++) p[e] = ldg_rlx4(g_modp + e * 512 + i * 256 + tid);
              uint32_t ok = 1;
#pragma unroll
              for (int e = 0; e < 4; e++) ok &= p[e].x & p[e].y & p[e].z & p[e].w;
              if (__all_sync(~0u, ok) || n > SPIN_LIMIT / 16) break;
              __nanosleep(100);
            }
#define MSUM(e) (i + rbf((F_(p[0].e) + F_(p[1].e)) + (F_(p[2].e) + F_(p[3].e))))
            sts2(md + i * 2048 + tid * 8, pk(MSUM(x), MSUM(y)), pk(MSUM(z), MSUM(w)));
          }
          BAR_SYNC(B_F, 256);
          PT(5);
        }
        const int e0 = (iw * 8 + (lane >> 2)) * 8 + ((lane & 3) ^ (lane >> 2));
        uint4* dst = g_h + seg * 4096 + half * 2048;
#pragma unroll
        for (int i = 0; i < 16; i++) {
          const uint32_t ma = md + half * 1024 + (lane & 3) * 16 + i * 64;
          const uint4 sv = lds4(ma), cv = lds4(ma + 2048);
          xr[i] = make_uint4(fmabf(xr[i].x, cv.x, sv.x), fmabf(xr[i].y, cv.y, sv.y), fmabf(xr[i].z, cv.z, sv.z), fmabf(xr[i].w, cv.w, sv.w));
        }
        if (!spare) {
#pragma unroll
          for (int i = 0; i < 16; i++) sts4(sb + WO + wg * 32768 + (e0 ^ ((i & 1) * 4)) * 16 + (i >> 1) * 4096, xr[i].x, xr[i].y, xr[i].z, xr[i].w);
          break;
        }
#pragma unroll
        for (int i = 0; i < 16; i++) dst[(e0 ^ ((i & 1) * 4)) + (i >> 1) * 256] = xr[i];
        seg += 4;
        if (seg < 64) x_fetch();
        FENCE_ASYNC();
        BAR_SYNC(B_F, 256);
        if (tid == 0) red_rlx(g_hf + b - 128);
        if (seg >= 64) break;
      }
      if (spare) { rec_helper(sb, cvec, wmod, w1, b1, t0); return; }
      PH(1); PH(2); PT(6);
    }
    ROLE_REFRESH
#define ownv ((iw >> 1) == a)
#define owner (iw >= 2)
#define oi (wid & 1)
    {
      const uint32_t rsb = mapa(sb, owner ? a : a ^ 1);
      const uint32_t pp = rsb + PK + (owner ? 0 : 12288) + (oi * 2048 + wg * 1024) + l16;
      const uint32_t mb = sb + MEM + wg * 5120;
      sts4(L16 + TF + wid * 512, mb + lrow, owner ? L16 + (lane >> 4) * (RK - RQ - 256) + RQ + oi * 1024 + wg * 256 : rsb + RQ + oi * 1024 + 512 + wg * 256 + (l16 >> 2),
           L16 + OB, frag + wg * NVS * 2048);
      sts4(L16 + TF + 4096 + wid * 512, sb + WO + (wid >> 1) * 16384 + ((lane & 7) + (lane >> 4) * 8) * 128 + ((((wid & 1) * 4 + ((lane >> 3) & 1)) ^ (lane & 7)) << 4),
           sb + ARO + wid * 640 + lrow, pp, LO(xc) + h * 262144 + (bb * 2 + (iw >> 1)) * XC + X_VM(0) + oi * 2048 + a * 256 + (l16 >> 1));
    }
    uint32_t tp = L16 + TF + wid * 512;
    auto park_ptr = [&]() { return lds1(tp + 4096 + 8); };
    auto park_w = [&](const uint32_t* w, int m, uint32_t d) {
      if (m == 2) d += (sb & 0x1000000) ? 0 : owner ? 0x1003000 : -0x1003000;
      if (m == 2 ? ownv : owner) {
        sts4(d + m * 4096, w[0], w[1], w[2], w[3]); sts4(d + m * 4096 + 512, w[4], w[5], w[6], w[7]);
      } else {
        const uint32_t pb = (d & 0xff000000u) | (1024 + BARS + (m ? 24 + m * 8 : 16));
        sta4(d + m * 4096, w, pb); sta4(d + m * 4096 + 512, w + 4, pb);
      }
    };
    auto park = [&](const float* f, int m, int n, uint32_t d) {
      uint32_t w[8];
#pragma unroll
      for (int i = 0; i < 8; i++) w[i] = pk(f[2 * i], f[2 * i + 1]);
      park_w(w, m, d);
    };
#define D64(lo) (0x4000004000000000ull | (uint32_t)(lo))
#define XD(i) D64(x | (((i) >> 2) * 256 + ((i) & 3) * 2))
    auto xdesc = [&](uint32_t xb) { return ((uint32_t)__shfl_sync(~0u, 1024 + xb + wg * 16384, 0) >> 4) | 0x10000u; };
    auto rs_issue = [&](float* acc, const uint32_t (&w)[16][4], uint32_t xb, bool fence) {
      const uint32_t x = xdesc(xb);
      if (fence) WG_FENCE();
      wgmma_rs_n32_z(acc, w[0], XD(0));
#pragma unroll
      for (int i = 1; i < 16; i++) wgmma_rs_n32(acc, w[i], XD(i), 1);
      WG_COMMIT();
    };
    auto v_issue = [&](float* acc, uint32_t xb, bool fence) {
      const uint32_t dv = ((uint32_t)__shfl_sync(~0u, 1024 + WVS + wg * NVS * 2048, 0) >> 4) | 0x10000u, x = xdesc(xb);
      if (fence) WG_FENCE();
      wgmma_rs_n32_z(acc, wV[0], XD(0));
#pragma unroll
      for (int i = 1; i < VRF; i++) wgmma_rs_n32(acc, wV[i], XD(i), 1);
#pragma unroll
      for (int i = NVR; i < 16; i++) wgmma_ssT_n32(acc, D64(dv + (i - NVR) * 128), XD(i), 1);
#pragma unroll
      for (int i = VRF; i < NVR; i++) wgmma_rs_n32(acc, wV[i], XD(i), 1);
      WG_COMMIT();
    };
    uint32_t mA, vP[2][4];
#define V_AHEAD mA = lds1(tp); frag = lds1(tp + 12); ldsm4t(vP[0], frag + WVS + (15 - NVR) * 2048); ldsm4t(vP[1], frag + WVS + (14 - NVR) * 2048);
    auto vk_pass = [&](int n, uint32_t d, uint32_t xb, bool steady, auto between) {
      float acc[16], acc2[16];
      v_issue(acc, xb, true);
      rs_issue(acc2, wK, xb, false);
      between();
      const bool keep = !steady || !UNC || n < 64;
      if (steady ? keep : n) mbar_wait(sb + BARS + 80, (n - 1) & 1);
      WG_WAIT(1);
      if (keep) {
        park(acc, 2, n, d);
        if (steady) BAR_ARRIVE(B_K, 320);
      }
      V_AHEAD
      WG_WAIT(0);
      if (keep) park(acc2, 1, n, d + (VPC ? (vP[1][0] ^ mA) & dZ : 0));
    };
    uint32_t q0[8], q1[8];
    {
      float acc[16], acc2[16];
      FENCE_ASYNC_SMEM();
      BAR_SYNC(B_F, 256);
      rs_issue(acc, wQ, WO, true);
      rs_issue(acc2, wQ, WO + 32768, false);
      WG_WAIT(0);
#pragma unroll
      for (int i = 0; i < 8; i++) { q0[i] = pk(acc[2 * i], acc[2 * i + 1]); q1[i] = pk(acc2[2 * i], acc2[2 * i + 1]); }
    }
    mbar_wait(wbar, 0);
    PT(7);
#pragma unroll
    for (int i = 0; i < 16; i++) ldsm4t(wK[i], (frag ^ QSW) + XB + wg * 32768 + i * 2048);
#pragma unroll
    for (int i = 0; i < NVR; i++) ldsm4t(wV[i], frag + MEM + (wg * NVR + i) * 2048);
    FENCE_ASYNC_SMEM();
    PH(3); PT(8);
    CLUSTER_SYNC();
    PT(9);
    frag += wg * NVS * 2048;
    park_w(q0, 0, park_ptr());
    PT(10);
#pragma unroll 1
    for (int n = 0; n < 2; n++) {
      asm volatile("" : "+r"(wid));
      vk_pass(n, park_ptr(), n * XB, false, [&]() {
        if (n) {
          BAR_SYNC(B_C, 320);
          PT(12);
          mbar_wait(sb + BARS + 24, 0);
          park_w(q1, 0, park_ptr());
        }
      });
      if (n) break;
      PT(11);
      BAR_SYNC(B_C, 448);
      if (tid == 0) {
        mbar_expect(obar, 65536);
#pragma unroll 1
        for (int i = 0; i < 4; i++) tma2d(sb + WO + i * 16384, &mp.wo, j * 256 + i * 64, h * 128, obar);
      }
    }
    static_assert(WO == 0, "x");
    {
      BAR_ARRIVE(B_P, 384); BAR_ARRIVE(B_X, 320); BAR_ARRIVE(B_Q, 288);
    }
    PT(13);
    PH(4); RS(1); PT(14);
    ROLE_REFRESH
    for (int s = 0; s < 64; s++) {
      asm volatile("" : "+r"(tp), "+r"(wid));
      asm volatile("mov.u32 %0,%%cluster_ctarank;" : "=r"(b));
      uint32_t vS[NVS][4], bf[8][4];
      static_assert(NVR == 5, "schedule");
#define VLD(k) ldsm4t(vS[(k) - NVR], frag + WVS + ((k) - NVR) * 2048)
#define BLD(t) ldsm4t(bf[t], mA + (t) * 640)
#define VMMA(c, w, i) mma16(c, (w)[0], (w)[1], (w)[2], (w)[3], bf[(i) >> 1][((i) & 1) * 2], bf[(i) >> 1][((i) & 1) * 2 + 1])
#define VS_(c, k) VMMA(c, vS[(k) - NVR], k)
#define QK(i) VMMA(cQ, wQ[i], i); VMMA(cK, wK[i], i)
#define PREV VLD(13); VLD(12); if (NF > 2) VLD(11);
      if (s > 0) BAR_SYNC(B_R, 320);
      float cV[4] = {0, 0, 0, 0}, cW[4] = {0, 0, 0, 0};
      {
        float cQ[4] = {0, 0, 0, 0}, cK[4] = {0, 0, 0, 0};
        BLD(7); BLD(6); BLD(5); BLD(4); if (NB0 > 4) BLD(3);
        SCHED_FENCE(47);
        QK(15); VMMA(cV, vP[0], 15);
        QK(14); VMMA(cV, vP[1], 14);
        QK(13); QK(12);
        SCHED_FENCE(51);
        if (NB0 < 5) BLD(3);
        BLD(2); BLD(1); BLD(0);
        const uint32_t rm = lds1(tp + 4);
        QK(11); QK(10); QK(9); QK(8); QK(7);
        if (PV0 == 6) { SCHED_FENCE(48); PREV }
        QK(6); QK(5);
        if (PV0 == 4) { QK(4); SCHED_FENCE(48); PREV } else { QK(4); }
        QK(3); QK(2); QK(1); QK(0);
        const uint32_t w0 = pk(cQ[0] * SCS, cQ[1] * SCS), w1 = pk(cQ[2] * SCS, cQ[3] * SCS), w2 = pk(cK[0], cK[1]), w3 = pk(cK[2], cK[3]);
        if (owner) {
          stsm4(rm, w0, w1, w2, w3);
          BAR_ARRIVE(B_E, 256);
        } else {
          const uint32_t mm = (rm & 0xff000000u) | (1024 + BARS);
          sta1<0>(rm, w0, mm); sta1<128>(rm, w1, mm);
          sta1<RK - RQ>(rm, w2, mm); sta1<RK - RQ + 128>(rm, w3, mm);
        }
        if (wid == 2) TS(0);
      }
      uint4 t1;
      uint32_t oA, wo[16][4];
      {
        DLY(10)
        if (NF < 3) VLD(11);
        VLD(10);
        VS_(cW, 13); VLD(9); VS_(cV, 12); VLD(8); VLD(7); VMMA(cW, wV[0], 0); VMMA(cV, wV[1], 1); VLD(6);
        VMMA(cW, wV[2], 2); VMMA(cV, wV[3], 3); VLD(5); VMMA(cW, wV[4], 4); VS_(cV, 11);
        VS_(cW, 10); VS_(cV, 9); VS_(cW, 8); VS_(cV, 7); VS_(cW, 6); VS_(cV, 5);
#pragma unroll
        for (int e = 0; e < 4; e++) cV[e] += cW[e];
        const uint32_t ex = tp + (RX - TF) - wg * 2048;
        t1 = lds4(tp + 4096 + (T1L ? vS[3][0] & dZ : 0));
        oA = lds1(tp + 8 + (s & dZ));
        if (wg) {
          sts4(ex, U_(cV[0]), U_(cV[1]), U_(cV[2]), U_(cV[3]));
          BAR_ARRIVE(B_T2, 256);
        }
        if (!wg) {
          BAR_SYNC(B_T2, 256);
          DLY(3)
          const float4 u = lds4f(ex);
          stg_b64(mkp(t1.w ^ ((s & 1) * X_RING), HI(xc)), (pk(cV[0] + u.x, cV[1] + u.y) & ~1u) | (((s >> 1) + 1) & 1), pk(cV[2] + u.z, cV[3] + u.w));
        }
      }
      if (s == 63) break;
      if (s == 0) mbar_wait(obar, 0);
      {
        const uint32_t woA = t1.x, woB = woA ^ 32;
#pragma unroll
        for (int i = 0; i < NW0; i++) ldsm4t(wo[i], ((i & 1) ? woB : woA) + (i >= WCH ? wo[(i - WCH + NWP) % NWP][0] & dZ : 0) + (i >> 1) * 2048);
        DLY(2)
        BAR_SYNC(B_S, 416);
        float inv0, inv1;
        uint32_t p[4], pm;
        const uint32_t pa = oA + (SC - OB), one = 0x3f803f80u;
#define P_LOAD ldsm4t(p, pa); asm volatile("ldmatrix.sync.aligned.m8n8.x1.trans.shared.b16 {%0},[%1];" : "=r"(pm) : "r"(pa + 512) : "memory");
        if (s < 62) {
          float acc[16];
          rs_issue(acc, wQ, XB, true);
          mbar_wait(sb + BARS + 24, (s + 1) & 1);
          WG_WAIT(0);
          uint32_t qw[8];
#pragma unroll
          for (int i = 0; i < 8; i++) qw[i] = pk(acc[2 * i], acc[2 * i + 1]);
          if (PKE == 1) park_w(qw, 0, t1.z);
#pragma unroll
          for (int i = NW0; i < NW1; i++) ldsm4t(wo[i], ((i & 1) ? woB : woA) + (i >> 1) * 2048);
          BAR_SYNC(B_V, 512);
          if (PKE == 2) park_w(qw, 0, t1.z);
          P_LOAD
          if (PKE == 0) park_w(qw, 0, t1.z);
        } else {
#pragma unroll
          for (int i = NW0; i < NW1; i++) ldsm4t(wo[i], ((i & 1) ? woB : woA) + (i >> 1) * 2048);
          BAR_SYNC(B_V, 512);
          P_LOAD
        }
#pragma unroll
        for (int i = NW1; i < NWP; i++) ldsm4t(wo[i], ((i & 1) ? woB : woA) + (i >> 1) * 2048);
        {
          float sum[4] = {0, 0, 0, 0}, su2[4] = {0, 0, 0, 0};
          mma16(sum, one, one, one, one, p[0], p[1]);
          mma16(su2, one, one, one, one, p[2], p[3]);
          mma8(sum, one, one, pm);
          inv0 = sum[0] + su2[0]; inv1 = sum[1] + su2[1];
          SCHED_FENCE(57);
        }
        DLY(7)
        BAR_SYNC(B_O, 416);
        float c[2][4] = {{0, 0, 0, 0}, {0, 0, 0, 0}};
        uint32_t o[4][4];
#pragma unroll
        for (int i = 0; i < NOP_; i++) ldsm4t(o[i], oA + i * 512);
        SCHED_FENCE(46);
        asm("rcp.approx.ftz.f32 %0,%0;" : "+f"(inv0));
        asm("rcp.approx.ftz.f32 %0,%0;" : "+f"(inv1));
#pragma unroll
        for (int i = 0; i < 16; i++) {
          mma16(c[i & 1], wo[i][0], wo[i][1], wo[i][2], wo[i][3], o[i >> 2][i & 2], o[i >> 2][(i & 2) + 1]);
          if (i == 1 && NOP_ < 3) ldsm4t(o[2], oA + 1024);
          if (i == 3 && NOP_ < 4) ldsm4t(o[3], oA + 1536);
          if (i + NWP < 16) ldsm4t(wo[(i + NWP) & 15], (((i + NWP) & 1) ? woB : woA) + ((i + NWP) >> 1) * 2048);
        }
        stsm4(t1.y, pk(c[0][0] * inv0, c[0][1] * inv1), pk(c[0][2] * inv0, c[0][3] * inv1), pk(c[1][0] * inv0, c[1][1] * inv1), pk(c[1][2] * inv0, c[1][3] * inv1));
      }
      const uint32_t d = park_ptr();
      BAR_SYNC(B_W, 384);
      DLY(1)
      if (UNC || s < 62) {
        vk_pass(s + 2, d, XB, true, []() {});
        if (!UNC || s < 62) { BAR_ARRIVE(B_P, 384); BAR_ARRIVE(B_X, 320); }
        TS(10);
      } else {
        V_AHEAD
        CONSUME(vP[1][0]);
      }
    }
  } else if (role == 3) {
    asm volatile("setmaxnreg.dec.sync.aligned.u32 24;");
    if (blockIdx.x >= 128) return;
    ROLE_VARS
    const uint32_t L16 = sb + (tid & 31) * 16;
    asm volatile("barrier.cluster.wait.aligned;" ::: "memory");
    CLUSTER_SYNC();
    sts1(sb + PACE + 36, LO(xc) + h * 262144 + X_VM(0));
#define V_LOAD(n) asm volatile("{.reg .pred p; elect.sync _|p, 0xffffffff; @p mbarrier.arrive.expect_tx.shared.b64 _,[%3],8192;\n" \
        "@p cp.async.bulk.tensor.5d.shared::cluster.global.mbarrier::complete_tx::bytes [%0],[%1,{0,0,0,0,%2}],[%3];}" \
        ::"r"(sb + VX0), "l"(&mp.vx), "r"(h * 64 + (V_RING(n) >> 12)), "r"(sb + BARS + 8) : "memory")
    auto vm_stage = [&](int s) {
      const uint32_t tag = ((s >> 1) + 1) & 1;
      const char* xm = mkp(lds1(sb + PACE + 36) + (s & 1) * X_RING + iw * XC + (l16 >> 1), HI(xc));
      uint2 m[4];
      CONSUME(LO(xm));
      BAR_SYNC(B_S2, 256);
      DLY(4)
      int it = 0;
      while (true) {
#pragma unroll
        for (int i = 0; i < 4; i++) m[i] = ldg_b64(xm + (i >> 1) * 2048 + (i & 1) * 256);
        sts4(L16 + VN + iw * 512, m[0].x, m[0].y, m[1].x, m[1].y);
        sts4(L16 + VN + iw * 512 + 2048, m[2].x, m[2].y, m[3].x, m[3].y);
        if (!anybad(m[0].x, m[1].x, m[2].x, m[3].x, tag)) break;
        RP(2);
        if (++it > SPIN_LIMIT) __trap();
      }
      if (s < 63) BAR_ARRIVE(B_V, 512); else BAR_ARRIVE(B_V, 256);
    };
    if (iw == 0) {
      wait_cnt(&g_hcnt, 128);
#pragma unroll 1
      for (int s = 0; s < 63; s++) {
        if (s < 62) for (int it = 0; ldg_rlx1(g_hf + (s & 3)) <= (s >> 2); it++) if (it > SPIN_LIMIT) __trap();
        if (s) BAR_SYNC(B_R, 320); else BAR_SYNC(B_Q, 288);
        if (s < 62) { X_LOAD(s + 2, 0, 0); X_LOAD(s + 2, 1, 0); X_LOAD(s + 2, 0, 1); X_LOAD(s + 2, 1, 1); }
        if (s >= 7) {
          const uint32_t zo = b * 160 + l16;
          if (l16 < 160) CONSUME(exch_b128(xc + AR_OFF + AR_ROW(zo >> 7) * 1024 + (zo & 127) + ((s + 1) & 7) * 128, 0, 0, 0, 0).x);
          __syncwarp();
        }
        if (s < 62) { mbar_wait(sb + BARS + 64, s & 1); mbar_wait(sb + BARS + 72, s & 1); }
        BAR_ARRIVE(B_S, 416);
        vm_stage(s);
        BAR_ARRIVE(B_O, 416);
        BAR_SYNC(B_W, 384);
        DLY(8)
        FENCE_ASYNC_SMEM();
        asm volatile("{.reg .pred p; elect.sync _|p, 0xffffffff; @p cp.reduce.async.bulk.tensor.3d.global.shared::cta.add.bulk_group [%0,{%1,%4,%2}],[%3];}"
                     ::"l"(&mp.ari), "r"((s & 7) * 64), "r"(AR_R(j)), "r"(sb + ARO), "r"(AR_P(j)) : "memory");
        BULK_COMMIT();
        asm volatile("st.relaxed.gpu.global.u32 [%0],%1;" ::"l"(g_tm + (s & 1) * 128 + b), "r"(gtime()) : "memory");
        TS(3);
        BULK_WAIT_READ(0);
      }
      BAR_ARRIVE(B_R, 320);
    } else if (iw == 1) {
      const uint32_t pc = sb + MEM + (lane >> 2) * 640 + (lane & 3) * 144 + (lane & 12), pd = sb + MEM + (lane & 15) * 640 + 576 + (lane & 3) * 16 + (lane & 12);
      uint32_t T = 0, par = 0;
      int est = dA;
#pragma unroll 1
      for (int s = 0; s < 63; s++) {
        if (s) {
          const uint4 tm = ldg_rlx4((const char*)g_tm + ((s + 1) & 1) * 512 + l16);
          const int t0 = tm.x - T, t1 = tm.y - T, t2 = tm.z - T, t3 = tm.w - T;
          const int e = max(dF + (__reduce_add_sync(~0u, (t0 + t1) + (t2 + t3)) >> 7), dV + __reduce_max_sync(~0u, max(max(t0, t1), max(t2, t3))));
          if (s > 1) est += max(min(e >> 2, dP), -dP);
          T += (s == 1 || e > dM ? e : 0) + est - (s == 62 ? L62 : 0);
        }
        vm_stage(s);
        BAR_SYNC(B_W, 384);
        SCHED_FENCE(70);
        const uint32_t tW = gtime();
        if (s == 0) T = tW + 800;
        const uint32_t te = tW + min(max((int)(T - tW), dD), 2000);
        while ((int)(gtime() - te) < 0) {}
        TS(7);
        int it = 0;
        while (true) {
          ar_fetch(sb + MEM, &mp.ari, s & 7, a, sb + BARS + 112);
          mbar_wait(sb + BARS + 112, par);
          par ^= 1;
          const uint32_t n0 = lds1(pc), n1 = lds1(pc + 5120), n2 = lds1(pd);
          if (!__any_sync(~0u, (tagbad(n0, n1, 0x42004200) | (n2 ^ 0x42004200)) != 0)) break;
          RP(0);
          if (++it > SPIN_LIMIT) __trap();
        }
        BAR_ARRIVE(B_R, 320);
        TS(11);
      }
    } else {
      uint32_t src = L16 + PK + (iw & 1) * 2048;
#define qd (L16 + (lane >> 4) * 256 + QT + (iw & 1) * 1024)
#define vd (LO(xc) + h * 262144 + j * XC + (iw & 1) * 2048 + l16)
#define FINISH [&](int n, int m) { \
_Pragma("unroll") \
        for (int i = 1; i >= 0; i--) { \
          const uint32_t p = src + m * 4096 + i * 512; \
          uint4 u = lds4(p); \
          const uint4 w = lds4(p + 1024), y = lds4(p + 12288), z = lds4(p + 13312); \
          u = make_uint4(sum4bf(u.x, w.x, y.x, z.x), sum4bf(u.y, w.y, y.y, z.y), sum4bf(u.z, w.z, y.z, z.z), sum4bf(u.w, w.w, y.w, z.w)); \
          if (m == 2) stg_b128(mkp(vd ^ V_RING(n), HI(xc)) + i * 512, (u.x & ~1u) | V_TAG(n), u.y, u.z, u.w); \
          else stsm4(qd + (n & 1) * 4096 + m * 2048 + i * 256, u.x, u.z, u.y, u.w); \
          SCHED_FENCE(71 + m * 2 + i); \
        } \
      }
#pragma unroll 1
      for (int n = 0; n < 64; n++) {
        src = PIN(src);
        b = __shfl_sync(~0u, lds1(sb + PACE + 24), 0);
        const uint32_t L16 = src - PK - (iw & 1) * 2048;
        auto finish = FINISH;
        if (n < 2) { if (n) BAR_SYNC(B_X, 320); else BAR_SYNC(B_C, 448); }
        mbar_wait(sb + BARS + 16, n & 1);
        if (n > 1) { const uint32_t c = clk(); while (clk() - c < (uint32_t)dQ) {} }
        finish(n, 0);
        __syncwarp();
        if (lane == 0) mbar_arrive_cl(mapa(sb, a ^ 1) + BARS + 24);
        if (n > 1) BAR_SYNC(B_K, 320);
        mbar_wait(sb + BARS + 40, n & 1);
        finish(n, 2);
        if (n > 1) BAR_SYNC(B_X, 320);
        mbar_wait(sb + BARS + 32, n & 1);
        DLY(11)
        finish(n, 1);
        BAR_SYNC(B_T, 64);
        if (lane == 0) {
          if (iw == 2 && n < 63) { mbar_expect(sb + BARS + 16, 4096); mbar_expect(sb + BARS + 32, 4096); mbar_expect(sb + BARS + 40, 4096); }
          mbar_arrive_cl(mapa(sb, a ^ 1) + BARS + 80);
        }
        __syncwarp();
        if (n) {
          vm_stage(n - 1);
          BAR_SYNC(B_W, 384);
          DLY(15)
        } else {
          BAR_SYNC(B_C, 320);
        }
        if (iw == 2) V_LOAD(n);
      }
#undef qd
#undef vd
    }
    { ROLE_REFRESH }
    vm_stage(63);
  } else {
    asm volatile("setmaxnreg.dec.sync.aligned.u32 %0;" ::"n"(RA_));
    if (blockIdx.x >= 128) { if (threadIdx.x == 256) rec_prefetch((const char*)wmod, w1, (const char*)x, wo); return; }
    ROLE_VARS
    uint32_t L16 = __shfl_sync(~0u, sb + (tid & 31) * 16, tid & 31);
    const uint32_t ts = gtime();
    uint2 m0[8];
#pragma unroll
    for (int r = 0; r < 8; r++) m0[r] = *(const uint2*)(mem0 + r * 1024 + a * 512 + (tid - 256) * 4);
    if (wid == 9) {
#pragma unroll 1
      for (int i = b * 80 + (tid & 31); i < b * 80 + 80; i += 32) ((uint4*)(xc + AR_OFF))[AR_ROW(i >> 6) * 64 + (i & 63)] = make_uint4(0, 0, 0, 0);
      if (b == 0) g_fin = 0;
      FENCE_ASYNC();
      __syncwarp();
      if (tid == 288) red_rlx(&g_hcnt);
    }
    if (tid == 256) {
      const int col = h * 128 + bb * 64;
#pragma unroll 1
      for (int c = 0, w = 0; w < 12; c++) {
#pragma unroll 1
        for (; w <= c - (c < WC0 ? 2 : 3); w++) {
          mbar_wait(sb + PACE + (w % 3) * 8, (w / 3) & 1);
          PT(18 + w);
          if (w == 3) asm volatile("mbarrier.arrive.shared.b64 _,[%0];" ::"r"(sb + BARS + 88) : "memory");
        }
        const uint32_t mb = sb + PACE + (c % 3) * 8;
        if (c >= 12 && c < 12 + WPE) tma2d_pf(&mp.wo, j * 256 + (c - 12) * 64, h * 128);
        if (c >= 12) continue;
        mbar_expect(mb, 16384);
        if (c < 8) tma2d(sb + (c >> 2) * XB + (c & 3) * 16384, (c & 4) ? &mp.wk : &mp.wq, col, a * 512 + (c & 3) * 128, mb);
        else
#pragma unroll 1
          for (int i = (c & 1) * 8; i < (c & 1) * 8 + 8; i++) {
            const int w = (c - 8) >> 1;
            tma2d(i < NVR ? sb + MEM + (w * NVR + i) * 2048 : sb + WVS + (w * NVS + i - NVR) * 2048, &mp.wv, col, a * 512 + w * 256 + i * 16, mb);
          }
      }
      asm volatile("mbarrier.arrive.shared.b64 _,[%0];" ::"r"(wbar) : "memory");
      for (int i = 0; i < 3; i++) asm volatile("mbarrier.inval.shared.b64 [%0];" ::"r"(sb + PACE + i * 8) : "memory");
    }
    __syncwarp();
    asm volatile("barrier.cluster.wait.aligned;" ::: "memory");
    CLUSTER_SYNC();
#pragma unroll 4
    for (int i = 0; i < 16; i++) {
      const uint4 v = lds4(L16 + WO + 32768 + iw * 8192 + i * 512);
      sts4(L16 + XB + iw * 8192 + i * 512, v.x, v.y, v.z, v.w);
    }
#pragma unroll
    for (int i = 0; i < 4; i++) {
      const int k = (tid - 256) * 4 + i, m = (k >> 3) & 3, r = k & 7;
#define M0W(r) __byte_perm((i & 2) ? m0[r].y : m0[r].x, (i & 2) ? m0[r + 1].y : m0[r + 1].x, (i & 1) ? 0x7632 : 0x5410)
      sts4(sb + MEM + (k >> 5) * 640 + (r == m ? 512 : m * 128) + r * 16, M0W(0), M0W(2), M0W(4), M0W(6));
    }
#pragma unroll 1
    for (int i = tid - 256; i < 192; i += 128) {
      const uint32_t c = i < 128 ? 0x42004200 : 0x3f803f80;
      sts4(sb + MEM + (i >> 3) * 640 + ((i & 7) < 4 ? (i & 7) * 144 : 512 + (i & 7) * 16), c, c, c, c);
    }
    static_assert(ARO == MEM + 16 * 640, "counters");
    FENCE_ASYNC_SMEM();
    BAR_ARRIVE(B_C, 448);
    if (tid == 256) {
      wait_time(ts + 1);
#pragma unroll 1
      for (int c = WPE; c < 4; c++) tma2d_pf(&mp.wo, j * 256 + c * 64, h * 128);
    }
    __syncwarp();
#define pr (L16 + SC)
    {
      const int lim = j * 8 + iw * 2 - (lane & 7) - (lane & 8) * 2;
      const bool mk = L16 & 256;
      const int rw = lane >> 2;
      sts4(L16 + TA + iw * 512,
           iw != 2 ? L16 + KT + (iw & 1) * 256 + (lane >> 4) * 256 : sb + RK + (L16 & 0x80) * 2 + ((L16 >> 1) & 0x80) + (L16 & 0x70),
           L16 + QT + (lane >> 3) * 384, sb + SC + min(lane >> 3, 2) * 256 + (L16 & 0x70) + iw * 4, L16 + (lane >> 4) * 256 + QT + (iw >> 1) * 1024 + (iw & 1) * 256);
      sts4(L16 + TA + 2048 + iw * 512, mk ? 0u : (lim < 0 ? 0xfc00u : 0u) | (lim < -1 ? 0xfc000000u : 0u),
           mk ? 0xfc00fc00u : (lim < 8 ? 0xfc00u : 0u) | (lim < 7 ? 0xfc000000u : 0u),
           ((h * 2 + (iw >> 1)) * 1024 + (j * 8 + rw) * 8 + (((iw & 1) * 4 + (lane & 3)) ^ rw)) * 16, sb + OT + iw * 512 + (L16 & 0x70) * 4 + ((L16 >> 3) & 0x30));
    }
    {
      const uint32_t xh = LO(xc) + h * 262144, xs = xh + X_SC + iw * 1024 + min(lane, 16 + (lane & 7)) * 8;
      sts4(L16 + TA + 4096 + iw * 512, xh + X_SC + j * 256 + iw * 64 + lpub, xs, dS, iw != 2 ? 0 : U_(SCS));
      sts1(L16 + TA + 12 + iw * 512, xs + X_TOK + j * 4096);
    }
    uint32_t tA = L16 + TA + iw * 512;
#define tw (tA - L16 != TA + 1024)
#define XP_(lo) mkp(lo, HI(xc))
    auto publish = [&](char* d, const uint2& w) { stg_b64(d, w.x, w.y); };
    BAR_SYNC(B_P, 384);
    for (int s = 0; s < 64; s++) {
      asm volatile("" : "+r"(L16), "+r"(tA));
      const uint32_t tag = ((s >> 1) + 1) & 1, ring = (s & 1) * X_RING;
      const uint4 t0 = lds4(tA);
      const uint4 tx = lds4(tA + 4096);
      const uint32_t xo = tx.x ^ ring, xs = tx.y ^ ring;
      const float gm = F_(tx.w);
      const uint32_t qA = t0.y + (ring >> 5);
      uint32_t c0;
      uint2 ts[4];
      uint4 v[4];
      uint32_t af[2][4], qt[4][4];
      {
        const uint32_t aA = t0.x + (tw ? ring >> 5 : 0);
        uint32_t ql[2][4], qr[2][4];
        uint2 pw_;
        float c[4] = {0, 0, 0, 0}, d[4] = {0, 0, 0, 0};
        if (s == PDS) asm volatile("griddepcontrol.launch_dependents;");
#pragma unroll
        for (int i = 0; i < 4; i++) ldsm4t(qt[i], qA + i * 128);
        mbar_wait(sb + BARS + 8, s & 1);
        TS(4);
        BAR_SYNC(B_E, 256);
        DLY(14)
#define PACK(c) make_uint2(pkh(fmaf(c[2], gm, c[0] * SCS), fmaf(c[3], gm, c[1] * SCS), tag), pkh(c[2] * SCS, c[3] * SCS, tag))
        ldsm4t(ql[0], L16 + RQ); ldsm4t(ql[1], L16 + RQ + 1024); ldsm4t(af[0], aA); ldsm4t(af[1], aA + 1024);
        CONSUME(xo);
#define QSUM(t, i) addbf(addbf(ql[t][i], ql[t][i + 2]), addbf(qr[t][i], qr[t][i + 2]))
#define STAIL mma16(c, af[0][0], af[0][1], af[0][2], af[0][3], QSUM(0, 0), QSUM(0, 1)); mma16(d, af[1][0], af[1][1], af[1][2], af[1][3], QSUM(1, 0), QSUM(1, 1));
        if (tw) {
          mbar_wait(sb + BARS, s & 1);
          TS(8);
          ldsm4t(qr[0], L16 + RQ + 512); ldsm4t(qr[1], L16 + RQ + 1536);
          STAIL
          pw_ = make_uint2(pkh(c[0] + d[0], c[1] + d[1], tag), pkh(c[2] + d[2], c[3] + d[3], tag));
        } else {
          uint32_t ar[2][4];
          mbar_wait(sb + BARS, s & 1);
          ldsm4t(qr[0], L16 + RQ + 512); ldsm4t(ar[0], aA + 512); ldsm4t(qr[1], L16 + RQ + 1536); ldsm4t(ar[1], aA + 1536);
#pragma unroll
          for (int i = 0; i < 8; i++) af[i >> 2][i & 3] = addbf(af[i >> 2][i & 3], ar[i >> 2][i & 3]);
          STAIL
          pw_.x = pw_.y = pkh((c[0] + c[2]) + (d[0] + d[2]), (c[1] + c[3]) + (d[1] + d[3]), tag);
        }
        publish(XP_(xo), pw_);
        c0 = clk() + tx.z;
        TS(1);
      }
      uint2 r[4];
      bool vbad;
      uint4 vn[2];
      {
        float e[4][4];
#pragma unroll
        for (int i = 0; i < 4; i++) {
          e[i][0] = e[i][1] = e[i][2] = e[i][3] = 0.f;
          mma16(e[i], af[0][0], af[0][1], af[0][2], af[0][3], qt[i][0], qt[i][1]);
        }
#pragma unroll
        for (int i = 0; i < 4; i++) mma16(e[i], af[1][0], af[1][1], af[1][2], af[1][3], qt[i][2], qt[i][3]);
        SCHED_FENCE(55);
        if (s < 63) BAR_ARRIVE(B_S, 416);
        SCHED_FENCE(58);
        v[0] = lds4(tA + (VX0 - TA)); v[1] = lds4(tA + (VX0 - TA) + 2048); v[2] = lds4(tA + (VX1 - TA)); v[3] = lds4(tA + (VX1 - TA) + 2048);
#pragma unroll
        for (int i = 0; i < 4; i++) ts[i] = PACK(e[i]);
        vbad = anybad(v[0].x, v[1].x, v[2].x, v[3].x, V_TAG(s));
        while ((int)(clk() - c0) < 0) {}
        TS(5);
#pragma unroll
        for (int u = 0; u < 4; u++) r[u] = ldg_b64(XP_(xs) + u * 256);
        BAR_ARRIVE(B_S2, 256);
      }
      SCHED_FENCE(56);
      uint32_t kk;
      float4 e = softmax2<false>(r, 0, 0, kk);
      if (__builtin_expect(anybad(r[0].x, r[0].y, r[1].x, r[1].y, r[2].x, r[2].y, r[3].x, r[3].y, tag ^ (kk & dZ)), 0)) {
        int it = 0;
        if (s > 8) sts1(tA + 4096 + 8, min(lds1(tA + 4096 + 8) + dX, 500));
        do {
          RP(1);
          if (++it > SPIN_LIMIT) __trap();
#pragma unroll
          for (int u = 0; u < 4; u++) r[u] = ldg_b64(XP_(xs) + u * 256);
        } while (BADS(r));
        e = softmax2<false>(r, 0, 0, kk);
      }
      DLY(5)
      sts1(t0.z, pk(e.x, e.y)); sts1(t0.z + 128, pk(e.z, e.w));
#pragma unroll
      for (int i = 0; i < 4; i++) publish(XP_(xo) + X_TOK + i * 4096, ts[i]);
      TS(6);
      if (s < 63) BAR_SYNC(B_V, 512); else BAR_SYNC(B_V, 256);
      uint32_t O[4];
      {
        uint32_t p[4], pm;
        ldsm4t(p, pr);
        asm volatile("ldmatrix.sync.aligned.m8n8.x1.trans.shared.b16 {%0},[%1];" : "=r"(pm) : "r"(pr + 512) : "memory");
        vn[0] = lds4(tA + (VN - TA)); vn[1] = lds4(tA + (VN - TA) + 2048);
        pv_mem(p, pm, v, vn, O);
        if (__builtin_expect(vbad, 0)) {
          int it = 0;
          const uint32_t xv = LO(xc) + (lds1(sb + PACE + 24) >> 2) * 262144 + ((tA - L16 - TA) >> 9) * XC;
          do {
            RP(2);
            if (++it > SPIN_LIMIT) __trap();
#pragma unroll
            for (int u = 0; u < 4; u++) v[u] = ldg_b128(XP_((xv + l16) ^ V_RING(s)) + X_VX(u));
          } while (anybad(v[0].x, v[1].x, v[2].x, v[3].x, V_TAG(s)));
          pv_mem(p, pm, v, vn, O);
        }
      }
      DLY(6)
      stsm4(tA + (OB - TA), O[0], O[1], O[2], O[3]);
      if (s < 63) BAR_ARRIVE(B_O, 416);
      TS(2);
      c0 = clk() + dG;
      SCHED_FENCE(60);
      if (tA == sb + TA) mbar_expect(sb + BARS, 2048);
      const uint32_t vs[4] = {addbf(vn[0].x, vn[0].z), addbf(vn[0].y, vn[0].w), addbf(vn[1].x, vn[1].z), addbf(vn[1].y, vn[1].w)};
      {
        const char* xt = XP_(lds1(tA + 12) ^ ring);
        const uint2 t1 = lds2u(tA + 2048);
        const uint32_t pw = lds1(tA + 8);
        uint2 rt[4];
        CONSUME(LO(xt) ^ t1.x ^ pw);
        while ((int)(clk() - c0) < 0) {}
        int it = 0;
        do {
          if (++it > SPIN_LIMIT) __trap();
#pragma unroll
          for (int u = 0; u < 4; u++) rt[u] = ldg_b64(xt + u * 256);
        } while (BADS(rt));
        uint32_t kt;
        const float4 et = softmax2<true>(rt, t1.x, t1.y, kt);
        sts1(pw + 1024, pk(et.x, et.y)); sts1(pw + 1024 + 128, pk(et.z, et.w));
      }
      s = PIN(s);
      BAR_SYNC(B_SC, 128);
      {
        uint32_t Ot[4], p[4], pm;
        const uint2 t2 = lds2u(tA + 2048 + 8);
        ldsm4t(p, pr + 1024);
        asm volatile("ldmatrix.sync.aligned.m8n8.x1.trans.shared.b16 {%0},[%1];" : "=r"(pm) : "r"(pr + 1024 + 512) : "memory");
        char* od = (char*)g_O + ((s >> 2) * 1048576 + (s & 3) * 4096) + t2.x;
        CONSUME(LO(od) ^ HI(od) ^ pm ^ p[3]);
        TS(9);
        if (s < 62) BAR_SYNC(B_P, 384);
        DLY(13)
        pv_tok(p, pm, v, vs, Ot);
        asm volatile("stmatrix.sync.aligned.m8n8.x4.trans.shared.b16 [%0],{%1,%2,%3,%4};" ::"r"(t2.y), "r"(Ot[0]), "r"(Ot[1]), "r"(Ot[2]), "r"(Ot[3]) : "memory");
        __syncwarp();
        *(uint4*)od = lds4(tA + (OT - TA));
      }
    }
    FENCE_ASYNC();
    BAR_SYNC(B_SC, 128);
    if (tA == sb + TA) red_rlx(&g_fin);
  }
  __syncwarp();
  CLUSTER_SYNC();
  PH(5); RS(2);
}
#undef wg
#undef iw
#undef h
#undef j
#undef a
#undef bb
#undef oi
#undef owner
#undef ownv
#undef pr
#undef PIN
#undef XP_
#undef tw
#undef lane
#undef l16
#undef lrow
#undef lpub

namespace ffn {
constexpr uint32_t BR = 98304;
constexpr uint32_t STG = 196608;
constexpr uint32_t PRM = 229376;
constexpr uint32_t BARS = PRM + 2816;
constexpr uint32_t SMEM = BARS + 18 * 8;
}
#define Y_TILE(rb, kt) (((ALIAS & 1) ? g_h : g_h2) + ((rb) * 16 + (kt)) * 1024)
#define U_TILE(rb, kt) ((ALIAS & 2) ? g_O + ((rb) * 64 + (kt)) * 1024 : g_U + ((rb) * 56 + (kt)) * 1024)
struct FfnMaps { CUtensorMap wo, w1a, w1b, w2, x, out; };

template <int N>
__device__ __forceinline__ void wg_ss(float* d, uint64_t a, uint64_t b, int sd) {
  if (N == 128) wgmma_ss_n128(d, a, b, sd);
  if (N == 192) wgmma_ss_n192(d, a, b, sd);
}
template <int N>
__device__ __forceinline__ void acc_fence(float* d) {
#pragma unroll
  for (int i = 0; i < N; i++) asm volatile("" : "+f"(d[i])::"memory");
}
#define UNPK8(d, v) do { (d)[0] = blo(v.x); (d)[1] = bhi(v.x); (d)[2] = blo(v.y); (d)[3] = bhi(v.y); (d)[4] = blo(v.z); (d)[5] = bhi(v.z); (d)[6] = blo(v.w); (d)[7] = bhi(v.w); } while (0)
struct FfnPipe {
  uint32_t full, emp, ph, aoff;
  int st, sB, prev;
  bool leader;
  template <int N, int S = N>
  __device__ __forceinline__ void issue(float* acc, bool first, uint32_t a = 0) {
    mbar_wait(full + st * 8, ph);
    const uint64_t da = mkdesc((a ? a : 1024 + st * 16384) + aoff, 16, 1024), db = mkdesc(1024 + ffn::BR + sB * (S * 128), 8192, 1024);
    WG_FENCE();
#pragma unroll
    for (int j = 0; j < 4; j++) wg_ss<N>(acc, da + j * 2, db + j * 128, j || !first);
    WG_COMMIT();
    if (++sB == 768 / S) sB = 0;
  }
  __device__ __forceinline__ void release() { if (leader) mbar_arrive(emp + prev * 8); }
  __device__ __forceinline__ void next() { prev = st; if (++st == 6) { st = 0; ph ^= 1; } }
  __device__ __forceinline__ void retire() { WG_WAIT(1); release(); next(); }
};
__device__ __forceinline__ float gelu_h(float hx) {
  float u = hx * fmaf(hx * hx, 8.f * 0.0356774081f, 2.f * 0.7978845608f), t;
  asm("tanh.approx.f32 %0,%1;" : "=f"(t) : "f"(u));
  return fmaf(hx, t, hx);
}
struct FfnEpi {
  uint32_t st2, cc, flip, staged, l0;
  uint2 c;
  float n0, n1, s0, s1;
  __device__ __forceinline__ void flush(uint32_t r) {
    __syncwarp();
    asm volatile("{.reg .pred p; setp.ne.u32 p,%1,0; @p mbarrier.arrive.shared.b64 _,[%0];}" ::"r"(staged + (flip >> 11)), "r"(l0 & r) : "memory");
    flip ^= r << 14;
  }
  __device__ __forceinline__ void half(const float* d, int J, int r) {
#define PRE(i, n, c1, c2) gelu_h(fmaf(r ? d[4 + i] : d[i], i < 2 ? s0 : s1, fmaf(n, c1, c2)))
    asm volatile("stmatrix.sync.aligned.m8n8.x2.shared.b16 [%0],{%1,%2};" ::"r"((st2 ^ ((J & 3) * 32 + r * 16)) + flip),
                 "r"(pk(PRE(0, n0, blo(c.x), blo(c.y)), PRE(1, n0, bhi(c.x), bhi(c.y)))), "r"(pk(PRE(2, n1, blo(c.x), blo(c.y)), PRE(3, n1, bhi(c.x), bhi(c.y)))) : "memory");
#undef PRE
    if ((J & 3) == 3) flush(r);
    cc += r ? 56 : 8;
    c = lds2u(cc);
  }
};

__global__ void __launch_bounds__(384, 1)
k_ffn(const __grid_constant__ FfnMaps mp, const bf16* __restrict__ b2) {
  using namespace ffn;
  extern __shared__ __align__(1024) char smem[];
  const uint32_t sb = (uint32_t)__cvta_generic_to_shared(smem);
  if (sb != 1024) __trap();
  const int tid = threadIdx.x, lane = tid & 31, wg = __shfl_sync(~0u, tid >> 7, 0);
  const uint32_t full = sb + BARS, emp = full + 48, xbar = full + 96, staged = full + 104, tile = full + 136;
  uint32_t fin = 0;
  if (tid >= 288 && tid < 320) fin = ld_acq(&g_fin);
  if (tid < 32) {
    unsigned sm, v = 0;
    asm("mov.u32 %0,%%smid;" : "=r"(sm));
    if (tid == 0) {
      v = atomicExch(&g_slot[sm & 255], 0);
      for (int i = 0; i < 6; i++) { mbar_init(full + i * 8, 1); mbar_init(emp + i * 8, 2); }
      mbar_init(xbar, 2);
      for (int i = 0; i < 2; i++) { mbar_init(staged + i * 8, 8); mbar_init(staged + 16 + i * 8, 1); }
      FENCE_ASYNC_SMEM();
    }
    v = __shfl_sync(~0u, v, 0);
    if (!v) {
      wait_cnt(&g_fin, 128);
      for (int it = 0; !v; it++) {
        const uint4 a = ldg_rlx4(g_slot + tid * 8), b = ldg_rlx4(g_slot + tid * 8 + 4);
        const uint32_t open = __ballot_sync(~0u, a.x | a.y | a.z | a.w | b.x | b.y | b.z | b.w);
        if (!open) break;
        if (it < 16) { __nanosleep(500); continue; }
        if (tid == __ffs(open) - 1) v = atomicExch(&g_slot[tid * 8 + (a.x ? 0 : a.y ? 1 : a.z ? 2 : a.w ? 3 : b.x ? 4 : b.y ? 5 : b.z ? 6 : 7)], 0);
        v = __shfl_sync(~0u, v, __ffs(open) - 1);
      }
    }
    if (tid == 0) sts1(tile, v);
  }
  if (tid == 256) asm volatile("prefetch.tensormap [%0];" ::"l"(&mp.wo) : "memory");
  __syncthreads();
  const int bid = __shfl_sync(~0u, lds1(tile), 0) - 1;
  if (bid < 0) return;
  PH(6);
  FT(1);
  const int rb = bid >> 3, nb = bid & 7;
  unsigned* cnt = g_cnt + rb * 128;
  if (wg == 2) {
    asm volatile("setmaxnreg.dec.sync.aligned.u32 " FRP ";");
    const int pw = __shfl_sync(~0u, (tid >> 5) & 3, 0);
    uint32_t ws = emp, wp = 1, fs = full;
    auto wait_free = [&]() { mbar_wait_q(ws, wp); ws += 8; if (ws == emp + 48) { ws = emp; wp ^= 1; } };
    auto step = [&]() { fs += 8; if (fs == full + 48) fs = full; };
#define K3(c) ((0x65230 >> (c) * 4) & 7)
#define KC(k) ((k) < 2 ? nb * 2 + (k) : (k) < 9 ? ((k) - 2 + ((k) - 2 >= nb)) * 2 : ((k) - 9 + ((k) - 9 >= nb)) * 2 + 1)
    if (pw == 0) {
      uint32_t d = sb + BR + 32768;
      auto put = [&](const CUtensorMap* m, int k, int c) {
        e_expect_tma3d(d, m, k * 64, c, fs, 32768);
        step();
        d += 16384;
        if (d == sb + STG) d = sb + BR;
      };
      int n = 0;
      auto stage_free = [&]() { if (!(n & 7) && n < 56) mbar_wait_q(staged + 16 + (n & 8), (n >> 4) & 1); n++; };
      auto align = [&]() {
        if (ALN && !((n - 1) & 7) && ((ALN >> ((n - 1) >> 3)) & 1)) {
          unsigned* c = g_cnt + 64 + ((n - 1) >> 3);
          if (lane == 0) red_rlx(c);
          for (int it = 0; ldg_rlx1(c) < 128 && it < 64; it++) {}
        }
      };
      FTP(3);
#pragma unroll 1
      for (int k = 0; k < 66; k++) { wait_free(); if (k < 64) put(&mp.wo, k, nb * 2); }
#pragma unroll 1
      for (int k = 0; k < 18; k++) {
        const int u = k >= 2 ? k - 2 : k, kt = KC(u);
        const bool ea = (k & ~1) == 2;
        wait_free();
        e_expect_tma3d(sb + BR + (k & 3) * 24576, ea ? &mp.w1a : &mp.w1b, kt * 64, nb * 7 + (ea ? 3 : 0), fs, ea ? 16384 : k < 2 ? 24576 : 40960);
        step();
      }
      d = sb + BR + 49152;
#pragma unroll 1
      for (int k = 2; k < 32; k++) {
        const int kt = k < 16 ? KC(k) : k & 15;
        stage_free();
        if (k == 2 || k == 9) n++;
        if (k != 7 && k != 8) wait_free();
        align();
        put(&mp.w1a, kt, nb * 7 + 3 + (k >> 4) * 2);
      }
#pragma unroll 1
      for (int c = 0; c < 5; c++)
#pragma unroll 1
        for (int k = K3(c), i = 0; k < 56; k += c < 2 && (i ^= 1) ? 1 : c < 2 ? 6 : 7) { stage_free(); wait_free(); align(); put(&mp.w2, k, nb * 2); }
    } else if (pw == 1) {
      FTP(5);
      if (fin < 128) wait_cnt(&g_fin, 128);
      FTP(6);
      uint32_t d = sb;
      auto put = [&](const uint4* A, bool ld) {
        wait_free();
        if (ld) e_bulk_ld(d, A, 16384, fs);
        step();
        d += 16384;
        if (d == sb + BR) d = sb;
      };
      const uint4* A = g_O + rb * 65536;
#pragma unroll 1
      for (int k = 0; k < 68; k++) put(A + k * 1024, k < 64);
      A = Y_TILE(rb, 0);
      uint32_t ready = 0;
#pragma unroll 1
      for (int k = 2; k < 48; k++) {
        if (k == 16) k = 18;
        const int kt = k < 32 ? KC(k & 15) : k & 15;
        for (int it = 0; !(ready >> ((kt >> 1) + (kt & 1) * 8) & 1); it++) {
          ready = __ballot_sync(~0u, ldg_rlx1(cnt + (lane & 7)) & ((lane & 8) ? 1 : 0x10000));
          if (it > SPIN_LIMIT) __trap();
        }
        if (k == 2) FTP(75);
        put(A + kt * 1024, true);
      }
      A = U_TILE(rb, 0);
#pragma unroll 1
      for (int c = 0; c < 5; c++) {
        for (int it = 0; ldg_rlx1(cnt + 32 + c) < 8; it++) if (it > SPIN_LIMIT) __trap();
#pragma unroll 1
        for (int k = K3(c), i = 0; k < 56; k += c < 2 && (i ^= 1) ? 1 : c < 2 ? 6 : 7) put(A + k * 1024, true);
      }
    } else if (pw == 2) {
      for (int i = 0; i < XDL; i++) {
        mbar_wait_q(emp, i & 1);
      }
      if (lane == 0) {
        mbar_expect(xbar, 32768);
        tma2d(sb + STG, &mp.x, nb * 128, rb * 128, xbar);
        tma2d(sb + STG + 16384, &mp.x, nb * 128 + 64, rb * 128, xbar);
      }
      asm volatile("griddepcontrol.wait;" ::: "memory");
      if (lane < 16) g_modp[bid * 16 + lane] = make_uint4(0, 0, 0, 0);
      if (lane >= 16 && bid == 0) { g_hcnt = 0; g_mcnt = 0; g_hf[lane & 3] = 0; }
      if (lane == 0) {
#pragma unroll 1
        for (int g = 1; g < 9; g++) {
          if (g == 1) mbar_wait(staged + 8, 0); else { mbar_wait_q(staged + (g & 1) * 8, (g >> 1) & 1); FENCE_ASYNC_SMEM(); }
          bulk_st(g == 1 ? Y_TILE(rb, nb * 2 + 1) : U_TILE(rb, nb * 7 + ((0x652431000ull >> g * 4) & 7)), sb + STG + (g & 1) * 16384, 16384);
          BULK_COMMIT();
          if (g != 2 && g != 4) { BULK_WAIT(0); red_rlx(g == 1 ? cnt + nb : cnt + 32 + (g < 6 ? g >> 2 : g - 4)); }
          BULK_WAIT_READ(0);
          mbar_arrive(staged + 16 + (g & 1) * 8);
        }
      }
    } else {
      const uint32_t prm = sb + PRM, pp = prm + (lane >> 3) * 64 + (lane & 1) * 32 + (lane & 6) * 2;
      const uint2 v2 = ((const uint2*)(b2 + nb * 128))[lane];
      sts1(pp + 768, v2.x); sts1(pp + 784, v2.y);
      asm volatile("griddepcontrol.wait;" ::: "memory");
      const float4* md = (const float4*)(g_mod + nb * 128) + lane;
      { const float4 ga = md[512]; sts1(pp, pk(ga.x, ga.y)); sts1(pp + 16, pk(ga.z, ga.w)); }
      { const float4 cb = md[1024]; sts1(pp + 256, pk(1.f + cb.x, 1.f + cb.y)); sts1(pp + 272, pk(1.f + cb.z, 1.f + cb.w)); }
      { const float4 gb = md[1280]; sts1(pp + 512, pk(gb.x, gb.y)); sts1(pp + 528, pk(gb.z, gb.w)); }
#pragma unroll 1
      for (int i = lane; i < 112; i += 32) { const uint4 c = g_cc[nb * 112 + i]; sts4(prm + 1024 + i * 16, c.x, c.y, c.z, c.w); }
      __syncwarp();
      if (lane == 0) {
        mbar_arrive(xbar);
        mbar_wait(staged, 0);
        bulk_st(Y_TILE(rb, nb * 2), sb + STG, 16384);
        BULK_COMMIT(); BULK_WAIT(0);
        asm volatile("red.relaxed.gpu.global.add.u32 [%0],0x10000;" ::"l"(cnt + nb) : "memory");
        mbar_arrive(staged + 16);
      }
      __syncwarp();
      mbar_wait_q(staged + 24, 0);
      mbar_wait_q(emp + 8, 1);
#pragma unroll 1
      for (int i = 0; i < 4; i++) {
        const uint4* sp = g_stat + (rb * 128 + i * 32 + lane) * 4;
        uint4 v[4];
        for (int it = 0;; it++) {
          uint32_t m = 0;
#pragma unroll
          for (int u = 0; u < 4; u++) { v[u] = ldg_rlx4(sp + u); m = max(max(m, max(v[u].x, v[u].y)), max(v[u].z, v[u].w)); }
          if (!__any_sync(~0u, m == ~0u)) break;
          if (it > SPIN_LIMIT) __trap();
        }
        float m = 0, q = 0;
#pragma unroll
        for (int u = 0; u < 4; u++) { m += F_(v[u].x) + F_(v[u].z); q += F_(v[u].y) + F_(v[u].w); }
        m *= 1.f / 1024;
        const float r = 0.5f * rsqrtf(fmaxf(q * (1.f / 1024) - m * m, 0.f) + 1e-5f);
        sts2(sb + STG + 16384 + (i * 32 + lane) * 8, U_(r), U_(-m * r));
      }
      __syncwarp();
      if (lane < 2) mbar_arrive(xbar);
    }
  } else {
    asm volatile("setmaxnreg.inc.sync.aligned.u32 " FRC ";");
    const int w = (tid >> 5) & 3, q = lane & 3;
    const uint32_t prm = sb + PRM + q * 16;
    const int row0 = wg * 64 + w * 16;
    FfnPipe p;
    p.full = full; p.emp = emp; p.ph = 0; p.aoff = wg * 8192; p.st = 0; p.sB = 2; p.prev = 0; p.leader = (tid & 127) == 0;
    FfnEpi e;
    const uint32_t stg = sb + STG + row0 * 128;
    e.st2 = stg + (lane & 15) * 128 + ((lane & 7) << 4);
    e.cc = sb + PRM + 1024 + q * 16; e.flip = 0; e.staged = staged; e.l0 = lane == 0;
    const uint32_t stw = e.st2 ^ (lane & 16);
    uint32_t x1[32];
    uint4* sp = g_stat + (rb * 128 + row0 + (lane >> 2)) * 4;
    float old[96], r0_, r1_;
    {
      float acc[64];
      p.issue<128>(acc, true); FT(8); p.next();
#pragma unroll 1
      for (int k = 1; k < 64; k++) { p.issue<128>(acc, false); FT(8 + k); p.retire(); }
      float xf[64], gf[32];
      uint32_t cb[16];
      mbar_wait(xbar, 0);
#pragma unroll
      for (int j = 0; j < 8; j++) {
        uint32_t xv[4];
        ldsm4(xv, (stw ^ ((j & 3) * 32)) + (j >> 2) * 16384);
#pragma unroll
        for (int i = 0; i < 4; i++) { xf[j * 8 + i * 2] = blo(xv[i]); xf[j * 8 + i * 2 + 1] = bhi(xv[i]); }
      }
#pragma unroll
      for (int i = 0; i < 4; i++) {
        const uint4 g = lds4(prm + i * 64), c = lds4(prm + 256 + i * 64);
        UNPK8(gf + i * 8, g);
        cb[i * 4] = c.x; cb[i * 4 + 1] = c.y; cb[i * 4 + 2] = c.z; cb[i * 4 + 3] = c.w;
      }
      acc_fence<64>(xf); acc_fence<32>(gf);
      WG_WAIT(0);
      p.release();
      acc_fence<64>(acc);
      PH(7); FT(72);
#pragma unroll
      for (int j = 0; j < 8; j++) {
        uint32_t* o = x1 + j * 4;
#pragma unroll
        for (int i = 0; i < 4; i++)
          o[i] = pk(fmaf(acc[j * 8 + i * 2], gf[j * 4 + (i & 2)], xf[j * 8 + i * 2]), fmaf(acc[j * 8 + i * 2 + 1], gf[j * 4 + (i & 2) + 1], xf[j * 8 + i * 2 + 1]));
        stsm4((stw ^ ((j & 3) * 32)) + (j >> 2) * 16384, mulbf(o[0], cb[j * 2]), mulbf(o[1], cb[j * 2]), mulbf(o[2], cb[j * 2 + 1]), mulbf(o[3], cb[j * 2 + 1]));
        if ((j & 3) == 3) { FENCE_ASYNC_SMEM(); e.flush(1); }
      }
      if (wg) BAR_SYNC(2, 128); else BAR_SYNC(3, 128);
    }
    PH(8); FT(73);
    float acc[64];
    {
      float* accC = old;
      p.sB = 0;
      p.issue<192>(accC, true, 1024 + STG); FT(80); p.next();
      p.issue<192>(accC, false, 1024 + STG + 16384); FT(81);
      FT(78);
      float s0 = 0, s1 = 0, q0 = 0, q1 = 0;
#define X1_FENCE _Pragma("unroll") for (int j = 0; j < 32; j++) asm volatile("" : "+r"(x1[j]));
      X1_FENCE
#pragma unroll
      for (int j = 0; j < 16; j++) {
        const float a = blo(x1[j * 2]), b = bhi(x1[j * 2]), c = blo(x1[j * 2 + 1]), d = bhi(x1[j * 2 + 1]);
        s0 += a + b; s1 += c + d; q0 = fmaf(a, a, fmaf(b, b, q0)); q1 = fmaf(c, c, fmaf(d, d, q1));
      }
#pragma unroll
      for (int o = 1; o < 4; o *= 2) { s0 += __shfl_xor_sync(~0u, s0, o); s1 += __shfl_xor_sync(~0u, s1, o); q0 += __shfl_xor_sync(~0u, q0, o); q1 += __shfl_xor_sync(~0u, q1, o); }
      if (q < 2) {
        uint32_t m = __float_as_uint(q ? s1 : s0), v = __float_as_uint(q ? q1 : q0);
        if (m == ~0u) m = 0x7fffffffu;
        if (v == ~0u) v = 0x7fffffffu;
        stg_rlx2((uint2*)(sp + q * 32) + nb, m, v);
      }
      X1_FENCE
      p.retire();
#pragma unroll 1
      for (int k = 0; k < 2; k++) { p.issue<128, 192>(acc, !k, 1024 + STG + k * 16384); p.retire(); }
#pragma unroll 1
      for (int k = 2; k < 15; k++) { p.issue<192>(accC, false); FT(80 + k); p.retire(); }
      p.issue<192>(accC, false); FT(95);
      mbar_wait(xbar, 1);
      const float2 u0 = lds2f(sb + STG + 16384 + (row0 + (lane >> 2)) * 8), u1 = lds2f(sb + STG + 16384 + (row0 + (lane >> 2)) * 8 + 64);
      r0_ = u0.x; e.n0 = u0.y; r1_ = u1.x; e.n1 = u1.y;
      e.c = lds2u(e.cc);
      p.retire();
      e.s0 = r0_; e.s1 = r1_;
      p.sB = 3;
    }
    PH(9);
    {
      auto pair = [&](int J, bool first, bool one, int fo) {
#pragma unroll 1
        for (int r = 0; r < 2; r++) {
          if (!(one && r)) { p.issue<128>(acc, first && !r); FT(fo + r); p.retire(); }
          acc_fence<8>(old + J * 8);
          e.half(old + J * 8, J, r);
        }
      };
#pragma unroll 1
      for (int i = 0; i < 3; i++) {
        if (i == 2) {
          e.s0 = r0_; e.s1 = r1_;
#pragma unroll
          for (int J = 8; J < 12; J++) pair(J, J == 8, false, 128 + (J - 8) * 2);
          e.cc += 512; e.c = lds2u(e.cc);
          e.s0 = e.s1 = 1.f;
        }
#pragma unroll
        for (int J = 0; J < 8; J++) pair(J, J == 0 && i == 1, !(J & 3) && !i, 96 + i * 16 + (i >> 1) * 8 + J * 2);
        if (i == 2) break;
        e.cc += i ? -768 : 256; e.c = lds2u(e.cc);
        WG_WAIT(0);
        acc_fence<64>(acc);
#pragma unroll
        for (int k = 0; k < 64; k++) old[k] = acc[k] * ((k & 2) ? r1_ : r0_);
        acc_fence<64>(old);
        e.s0 = e.s1 = 1.f;
        PH(10 + i);
      }
#pragma unroll 1
      for (int k = 24; k < 56; k++) {
        if (SKW && k == 56 - SKW && wg) BAR_SYNC(4, 256);
        p.issue<128>(acc, false); FT(128 + k);
        if (SKW && k == 55 && !wg) BAR_ARRIVE(4, 256);
        p.retire();
      }
      float xf[64], gf[32];
#pragma unroll
      for (int i = 0; i < 4; i++) {
        const uint4 g = lds4(prm + 512 + i * 64), h = lds4(prm + 768 + i * 64);
        float hf[8];
        UNPK8(gf + i * 8, g); UNPK8(hf, h);
#pragma unroll
        for (int u = 0; u < 8; u++) {
          const int c = (u >> 2) * 4 + (u & 2);
          xf[i * 16 + u * 2] = fmaf(gf[i * 8 + c], hf[c], blo(x1[i * 8 + u])); xf[i * 16 + u * 2 + 1] = fmaf(gf[i * 8 + c + 1], hf[c + 1], bhi(x1[i * 8 + u]));
        }
      }
      acc_fence<64>(xf); acc_fence<32>(gf);
      mbar_wait(staged + 24, 1);
      mbar_wait(staged + 16, 0);
      WG_WAIT(0);
      acc_fence<64>(acc);
      PH(13); FT(184);
#pragma unroll
      for (int j = 0; j < 8; j++) {
        uint32_t o[4];
#pragma unroll
        for (int i = 0; i < 4; i++)
          o[i] = pk(fmaf(acc[j * 8 + i * 2], gf[j * 4 + (i & 2)], xf[j * 8 + i * 2]), fmaf(acc[j * 8 + i * 2 + 1], gf[j * 4 + (i & 2) + 1], xf[j * 8 + i * 2 + 1]));
        stsm4((stw ^ ((j & 3) * 32)) + (j >> 2) * 16384, o[0], o[1], o[2], o[3]);
        if ((j & 3) == 3) {
          FENCE_ASYNC_SMEM();
          __syncwarp();
          if (lane == 0) { tma2d_st(&mp.out, nb * 128 + (j >> 2) * 64, rb * 128 + row0, stg + (j >> 2) * 16384); BULK_COMMIT(); }
        }
      }
      if (lane == 0) BULK_WAIT_READ(0);
      __syncwarp();
    }
  }
  PH(14); FT(185);
}

typedef CUresult (*EncFn)(CUtensorMap*, CUtensorMapDataType, cuuint32_t, void*, const cuuint64_t*, const cuuint64_t*, const cuuint32_t*,
                          const cuuint32_t*, CUtensorMapInterleave, CUtensorMapSwizzle, CUtensorMapL2promotion, CUtensorMapFloatOOBfill);
static void map2d(EncFn enc, CUtensorMap* m, const void* p, int rows, int cols, int boxRows) {
  cuuint64_t d[2] = {(cuuint64_t)cols, (cuuint64_t)rows}, s[1] = {(cuuint64_t)cols * 2};
  cuuint32_t b[2] = {64, (cuuint32_t)boxRows}, e[2] = {1, 1};
  enc(m, CU_TENSOR_MAP_DATA_TYPE_BFLOAT16, 2, (void*)p, d, s, b, e, CU_TENSOR_MAP_INTERLEAVE_NONE, CU_TENSOR_MAP_SWIZZLE_128B,
      CU_TENSOR_MAP_L2_PROMOTION_L2_128B, CU_TENSOR_MAP_FLOAT_OOB_FILL_NONE);
}
static void map3d(EncFn enc, CUtensorMap* m, const void* p, int rows, int cols, int nch) {
  cuuint64_t d[3] = {64, (cuuint64_t)rows, (cuuint64_t)(cols / 64)}, s[2] = {(cuuint64_t)cols * 2, 128};
  cuuint32_t b[3] = {64, 64, (cuuint32_t)nch}, e[3] = {1, 1, 1};
  enc(m, CU_TENSOR_MAP_DATA_TYPE_BFLOAT16, 3, (void*)p, d, s, b, e, CU_TENSOR_MAP_INTERLEAVE_NONE, CU_TENSOR_MAP_SWIZZLE_128B,
      CU_TENSOR_MAP_L2_PROMOTION_L2_128B, CU_TENSOR_MAP_FLOAT_OOB_FILL_NONE);
}

extern "C" void kernel_launch(void* const* d_in, const int* in_sizes, int n_in, void* d_out, int out_size) {
  const bf16* x = (const bf16*)d_in[0];
  const bf16* mem0 = (const bf16*)d_in[1];
  void* fn = nullptr;
  cudaDriverEntryPointQueryResult qr;
  cudaGetDriverEntryPoint("cuTensorMapEncodeTiled", &fn, cudaEnableDefault, &qr);
  EncFn enc = (EncFn)fn;
  FfnMaps fm = {};
  map3d(enc, &fm.wo, d_in[5], 4096, 1024, 2);
  map3d(enc, &fm.w1a, d_in[8], 1024, 3584, 2);
  map3d(enc, &fm.w1b, d_in[8], 1024, 3584, 3);
  map3d(enc, &fm.w2, d_in[10], 3584, 1024, 2);
  map2d(enc, &fm.x, x, 2048, 1024, 128);
  map2d(enc, &fm.out, d_out, 2048, 1024, 16);
  RecMaps rm = {};
  map2d(enc, &rm.wq, d_in[2], 1024, 4096, 128);
  map2d(enc, &rm.wk, d_in[3], 1024, 4096, 128);
  map2d(enc, &rm.wv, d_in[4], 1024, 4096, 16);
  map2d(enc, &rm.wo, d_in[5], 4096, 1024, 128);
  char* xc = nullptr;
  cudaGetSymbolAddress((void**)&xc, g_xc);
  xc += (0 - (uintptr_t)xc) & 0x1FFFFF;
  {
    cuuint64_t d[3] = {512, 6, 128}, sd[2] = {131072, 1024};
    cuuint32_t bi[3] = {64, 5, 8}, e[3] = {1, 1, 1};
    enc(&rm.ari, CU_TENSOR_MAP_DATA_TYPE_BFLOAT16, 3, xc + AR_OFF, d, sd, bi, e, CU_TENSOR_MAP_INTERLEAVE_NONE, CU_TENSOR_MAP_SWIZZLE_NONE,
        CU_TENSOR_MAP_L2_PROMOTION_NONE, CU_TENSOR_MAP_FLOAT_OOB_FILL_NONE);
  }
  {
    cuuint64_t d[5] = {256, 4, 2, 2, 2048}, sd[4] = {rec::XC, X_VX(1), X_VX(2), 4096};
    cuuint32_t bi[5] = {256, 4, 2, 2, 1}, e[5] = {1, 1, 1, 1, 1};
    enc(&rm.vx, CU_TENSOR_MAP_DATA_TYPE_BFLOAT16, 5, xc, d, sd, bi, e, CU_TENSOR_MAP_INTERLEAVE_NONE, CU_TENSOR_MAP_SWIZZLE_NONE,
        CU_TENSOR_MAP_L2_PROMOTION_NONE, CU_TENSOR_MAP_FLOAT_OOB_FILL_NONE);
  }
  cudaFuncSetAttribute(k_ffn, cudaFuncAttributeMaxDynamicSharedMemorySize, ffn::SMEM);
  cudaFuncSetAttribute(k_rec, cudaFuncAttributeMaxDynamicSharedMemorySize, rec::SMEM);
  cudaStream_t st = cudaStreamPerThread;
  int dF = 450, dA = 2700, dS = 320, dM = 120, dG = 250, dP = 24, dX = 48, dD = 350, dZ = 0, dQ = 750, dV = 370, dX2 = 0;
  k_rec<<<132, 512, rec::SMEM, st>>>(rm, mem0, x, (const bf16*)d_in[12], (const bf16*)d_in[13], (const char*)d_in[8], (const bf16*)d_in[9],
                                     (const char*)d_in[5], xc, dF, dA, dS, dM, dG, dP, dX, dD, dZ, dQ, dV, dX2);
  cudaLaunchConfig_t cfg = {};
  cfg.gridDim = dim3(132); cfg.blockDim = dim3(384); cfg.dynamicSmemBytes = ffn::SMEM; cfg.stream = st;
  cudaLaunchAttribute at[1];
  at[0].id = cudaLaunchAttributeProgrammaticStreamSerialization;
  at[0].val.programmaticStreamSerializationAllowed = 1;
  cfg.attrs = at; cfg.numAttrs = 1;
  cudaLaunchKernelEx(&cfg, k_ffn, fm, (const bf16*)d_in[11]);
}
```

```cpp
#include <cuda_runtime.h>
#include <cuda.h>
#include <cuda_bf16.h>
#include <stdint.h>

typedef __nv_bfloat16 bf16;

__device__ __align__(16) float g_mod[6144];
__device__ __align__(1024) uint4 g_modp[4 * 512];
__device__ unsigned g_hcnt;
__device__ unsigned g_hf[4];
__device__ __align__(1024) uint4 g_h[2048 * 1024 / 8];
__device__ __align__(1024) uint4 g_O[2048 * 4096 / 8];
__device__ __align__(1024) uint4 g_h2[2048 * 1024 / 8];
__device__ __align__(1024) uint4 g_U[2048 * 3584 / 8];
__device__ __align__(1024) uint4 g_stat[2048 * 4];
__device__ __align__(1024) unsigned g_cnt[16 * 4 * 32];
__device__ unsigned g_mcnt;
__device__ unsigned g_slot[256];
__device__ unsigned g_fin;
__device__ __align__(16) uint4 g_cc[224 * 4];
__device__ __align__(1024) uint4 g_xc[44 * 16384];
__device__ __align__(1024) unsigned g_tm[4 * 256];
#define FT(i)
#define FTP(i)
#define PT(i)
#define PH(i)
#define RS(i)
#define RP(i)
#define RPN(i, s)
#define TSV(i, v)
#define TS(i)

#define FRC "232"
#define FRP "40"
#define FMAP (((g >> 2) * 4 + m) * 8 + ((g & 3) ^ ((g & 4) ? 3 : 0)) * 2 + (blockIdx.x & 1))
#define ALIAS 3
#define PFT 150000
#define PFS 104
#define PF0 13000
#define PFD 128
#define NF 3
#define NB0 4
#define PV0 4
#define T1L 1
#define NW0 4
#define VRF 3
#define VPC 1
#define WC0 99
#define WPE 3
#define ALN 0x80
#define SKW 5
#define L62 200
#define DLY(k)
#define UNC 1
#define PKE 0
#define USD 150
#define XR 32
#define XTD 500
#define XDL 6
#define PDS 61
#define P_NVR 5
#define P_NWP 9
#define P_NW1 7
#define RF_ 208
#define RA_ (488 - 2 * RF_)
#define WCH 2
#define NOP_ 2
#define SPIN_LIMIT (1 << 20)
__device__ __forceinline__ uint64_t mkdesc(uint32_t addr, uint32_t lbo, uint32_t sbo) {
  return (uint64_t)((addr & 0x3FFFF) >> 4) | ((uint64_t)(lbo >> 4) << 16) | ((uint64_t)(sbo >> 4) << 32) | (1ull << 62);
}
__device__ __forceinline__ void mbar_init(uint32_t a, int c) { asm volatile("mbarrier.init.shared.b64 [%0],%1;" ::"r"(a), "r"(c) : "memory"); }
__device__ __forceinline__ void mbar_wait(uint32_t a, uint32_t par) {
  asm volatile(
      "{.reg .pred p; .reg .u32 n;\n"
      "mov.u32 n, 0;\n"
      "W: mbarrier.try_wait.parity.shared.b64 p,[%0],%1;\n"
      "@p bra D;\n"
      "add.u32 n, n, 1;\n"
      "setp.lt.u32 p, n, %2;\n"
      "@p bra W;\n"
      "trap;\n"
      "D:}" ::"r"(a), "r"(par), "n"(SPIN_LIMIT) : "memory");
}
__device__ __forceinline__ void mbar_wait_q(uint32_t a, uint32_t par) {
  asm volatile(
      "{.reg .pred p; .reg .u32 n;\n"
      "mov.u32 n, 0;\n"
      "W: mbarrier.try_wait.parity.shared.b64 p,[%0],%1,4000;\n"
      "@p bra D;\n"
      "add.u32 n, n, 1;\n"
      "setp.lt.u32 p, n, %2;\n"
      "@p bra W;\n"
      "trap;\n"
      "D:}" ::"r"(a), "r"(par), "n"(SPIN_LIMIT / 16) : "memory");
}
__device__ __forceinline__ void mbar_expect(uint32_t a, uint32_t b) { asm volatile("mbarrier.arrive.expect_tx.shared.b64 _,[%0],%1;" ::"r"(a), "r"(b) : "memory"); }
__device__ __forceinline__ void mbar_arrive(uint32_t a) { asm volatile("mbarrier.arrive.shared.b64 _,[%0];" ::"r"(a) : "memory"); }
__device__ __forceinline__ uint32_t mapa(uint32_t a, uint32_t cta) { uint32_t r; asm("mapa.shared::cluster.u32 %0,%1,%2;" : "=r"(r) : "r"(a), "r"(cta)); return r; }
__device__ __forceinline__ void mbar_arrive_cl(uint32_t a) { asm volatile("mbarrier.arrive.shared::cluster.b64 _,[%0];" ::"r"(a) : "memory"); }
__device__ __forceinline__ void tma2d(uint32_t dst, const CUtensorMap* m, int c0, int c1, uint32_t mb) {
  asm volatile("cp.async.bulk.tensor.2d.shared::cluster.global.mbarrier::complete_tx::bytes [%0],[%1,{%2,%3}],[%4];" ::"r"(dst), "l"(m), "r"(c0), "r"(c1), "r"(mb) : "memory");
}
__device__ __forceinline__ void tma2d_pf(const CUtensorMap* m, int c0, int c1) {
  asm volatile("cp.async.bulk.prefetch.tensor.2d.L2.global [%0,{%1,%2}];" ::"l"(m), "r"(c0), "r"(c1) : "memory");
}
__device__ __forceinline__ void tma2d_st(const CUtensorMap* m, int c0, int c1, uint32_t src) {
  asm volatile("cp.async.bulk.tensor.2d.global.shared::cta.bulk_group [%0,{%1,%2}],[%3];" ::"l"(m), "r"(c0), "r"(c1), "r"(src) : "memory");
}
__device__ __forceinline__ void bulk_ld(uint32_t dst, const void* src, uint32_t n, uint32_t mb) {
  asm volatile("cp.async.bulk.shared::cluster.global.mbarrier::complete_tx::bytes [%0],[%1],%2,[%3];" ::"r"(dst), "l"(src), "r"(n), "r"(mb) : "memory");
}
__device__ __forceinline__ void bulk_st(void* dst, uint32_t src, uint32_t n) {
  asm volatile("cp.async.bulk.global.shared::cta.bulk_group [%0],[%1],%2;" ::"l"(dst), "r"(src), "r"(n) : "memory");
}
__device__ __forceinline__ void e_expect_tma3d(uint32_t dst, const CUtensorMap* m, int c1, int c2, uint32_t mb, uint32_t bytes) {
  asm volatile("{.reg .pred p; elect.sync _|p, 0xffffffff; @p mbarrier.arrive.expect_tx.shared.b64 _,[%4],%5;\n"
               "@p cp.async.bulk.tensor.3d.shared::cluster.global.mbarrier::complete_tx::bytes [%0],[%1,{0,%2,%3}],[%4];}" ::"r"(dst), "l"(m), "r"(c1), "r"(c2), "r"(mb), "r"(bytes) : "memory");
}
__device__ __forceinline__ void e_bulk_ld(uint32_t dst, const void* src, uint32_t n, uint32_t mb) {
  asm volatile("{.reg .pred p; elect.sync _|p, 0xffffffff; @p cp.async.bulk.shared::cluster.global.mbarrier::complete_tx::bytes [%0],[%1],%2,[%3];}" ::"r"(dst), "l"(src), "r"(n), "r"(mb) : "memory");
}
#define BULK_COMMIT() asm volatile("cp.async.bulk.commit_group;" ::: "memory")
#define BULK_WAIT_READ(n) asm volatile("cp.async.bulk.wait_group.read " #n ";" ::: "memory")
#define BULK_WAIT(n) asm volatile("cp.async.bulk.wait_group " #n ";" ::: "memory")
#define FENCE_ASYNC_SMEM() asm volatile("fence.proxy.async.shared::cta;" ::: "memory")
#define FENCE_ASYNC() asm volatile("fence.proxy.async;" ::: "memory")
#define WG_FENCE() asm volatile("wgmma.fence.sync.aligned;" ::: "memory")
#define WG_COMMIT() asm volatile("wgmma.commit_group.sync.aligned;" ::: "memory")
#define WG_WAIT(n) asm volatile("wgmma.wait_group.sync.aligned " #n ";" ::: "memory")
#define BAR_SYNC(id, n) asm volatile("bar.sync %0,%1;" ::"n"(id), "n"(n) : "memory")
#define BAR_ARRIVE(id, n) asm volatile("bar.arrive %0,%1;" ::"n"(id), "n"(n) : "memory")
#define SCHED_FENCE(k) asm volatile("{.reg .pred p; setp.ne.u32 p,%0,0; @p trap;}" ::"r"(mp.zero[(k) - 46]) : "memory")
#define CLUSTER_SYNC() asm volatile("barrier.cluster.arrive.relaxed.aligned; barrier.cluster.wait.aligned;" ::: "memory")
__device__ __forceinline__ uint32_t pk(float lo, float hi) { uint32_t r; asm("cvt.rn.bf16x2.f32 %0,%1,%2;" : "=r"(r) : "f"(hi), "f"(lo)); return r; }
__device__ __forceinline__ float blo(uint32_t v) { return __uint_as_float(v << 16); }
__device__ __forceinline__ float bhi(uint32_t v) { return __uint_as_float(v & 0xffff0000u); }
__device__ __forceinline__ void ldsm4(uint32_t* r, uint32_t a) {
  asm volatile("ldmatrix.sync.aligned.m8n8.x4.shared.b16 {%0,%1,%2,%3},[%4];" : "=r"(r[0]), "=r"(r[1]), "=r"(r[2]), "=r"(r[3]) : "r"(a) : "memory");
}
__device__ __forceinline__ void ldsm4t(uint32_t* r, uint32_t a) {
  asm volatile("ldmatrix.sync.aligned.m8n8.x4.trans.shared.b16 {%0,%1,%2,%3},[%4];" : "=r"(r[0]), "=r"(r[1]), "=r"(r[2]), "=r"(r[3]) : "r"(a) : "memory");
}
__device__ __forceinline__ void stsm4(uint32_t a, uint32_t r0, uint32_t r1, uint32_t r2, uint32_t r3) {
  asm volatile("stmatrix.sync.aligned.m8n8.x4.shared.b16 [%0],{%1,%2,%3,%4};" ::"r"(a), "r"(r0), "r"(r1), "r"(r2), "r"(r3) : "memory");
}
__device__ __forceinline__ void mma16(float* d, uint32_t a0, uint32_t a1, uint32_t a2, uint32_t a3, uint32_t b0, uint32_t b1) {
  asm volatile("mma.sync.aligned.m16n8k16.row.col.f32.bf16.bf16.f32 {%0,%1,%2,%3},{%4,%5,%6,%7},{%8,%9},{%0,%1,%2,%3};"
               : "+f"(d[0]), "+f"(d[1]), "+f"(d[2]), "+f"(d[3]) : "r"(a0), "r"(a1), "r"(a2), "r"(a3), "r"(b0), "r"(b1));
}
__device__ __forceinline__ void mma8(float* d, uint32_t a0, uint32_t a1, uint32_t b0) {
  asm volatile("mma.sync.aligned.m16n8k8.row.col.f32.bf16.bf16.f32 {%0,%1,%2,%3},{%4,%5},{%6},{%0,%1,%2,%3};"
               : "+f"(d[0]), "+f"(d[1]), "+f"(d[2]), "+f"(d[3]) : "r"(a0), "r"(a1), "r"(b0));
}
__device__ __forceinline__ float4 lds4f(uint32_t a) { float4 v; asm volatile("ld.shared.v4.f32 {%0,%1,%2,%3},[%4];" : "=f"(v.x), "=f"(v.y), "=f"(v.z), "=f"(v.w) : "r"(a) : "memory"); return v; }
__device__ __forceinline__ float2 lds2f(uint32_t a) { float2 v; asm volatile("ld.shared.v2.f32 {%0,%1},[%2];" : "=f"(v.x), "=f"(v.y) : "r"(a) : "memory"); return v; }
__device__ __forceinline__ uint4 lds4(uint32_t a) { uint4 v; asm volatile("ld.shared.v4.u32 {%0,%1,%2,%3},[%4];" : "=r"(v.x), "=r"(v.y), "=r"(v.z), "=r"(v.w) : "r"(a) : "memory"); return v; }
__device__ __forceinline__ uint2 lds2u(uint32_t a) { uint2 v; asm volatile("ld.shared.v2.u32 {%0,%1},[%2];" : "=r"(v.x), "=r"(v.y) : "r"(a) : "memory"); return v; }
__device__ __forceinline__ uint32_t lds1(uint32_t a) { uint32_t v; asm volatile("ld.shared.u32 %0,[%1];" : "=r"(v) : "r"(a) : "memory"); return v; }
__device__ __forceinline__ void sts4(uint32_t a, uint32_t x, uint32_t y, uint32_t z, uint32_t w) { asm volatile("st.shared.v4.u32 [%0],{%1,%2,%3,%4};" ::"r"(a), "r"(x), "r"(y), "r"(z), "r"(w) : "memory"); }
__device__ __forceinline__ void sts2(uint32_t a, uint32_t x, uint32_t y) { asm volatile("st.shared.v2.u32 [%0],{%1,%2};" ::"r"(a), "r"(x), "r"(y) : "memory"); }
__device__ __forceinline__ void sts1(uint32_t a, uint32_t x) { asm volatile("st.shared.u32 [%0],%1;" ::"r"(a), "r"(x) : "memory"); }
__device__ __forceinline__ void sta4(uint32_t a, const uint32_t* v, uint32_t mb) {
  asm volatile("st.async.shared::cluster.mbarrier::complete_tx::bytes.v4.b32 [%0],{%1,%2,%3,%4},[%5];" ::"r"(a), "r"(v[0]), "r"(v[1]), "r"(v[2]), "r"(v[3]), "r"(mb) : "memory");
}
__device__ __forceinline__ uint4 ldg_rlx4(const void* p) { uint4 v; asm volatile("ld.relaxed.gpu.global.v4.u32 {%0,%1,%2,%3},[%4];" : "=r"(v.x), "=r"(v.y), "=r"(v.z), "=r"(v.w) : "l"(p) : "memory"); return v; }
__device__ __forceinline__ uint32_t ldg_rlx1(const void* p) { uint32_t v; asm volatile("ld.relaxed.gpu.global.u32 %0,[%1];" : "=r"(v) : "l"(p) : "memory"); return v; }
__device__ __forceinline__ uint4 ldg_b128(const void* p) {
  uint4 v;
  asm volatile("{.reg .b128 t; .reg .b64 a,b; ld.relaxed.gpu.global.b128 t,[%4]; mov.b128 {a,b},t; mov.b64 {%0,%1},a; mov.b64 {%2,%3},b;}" : "=r"(v.x), "=r"(v.y), "=r"(v.z), "=r"(v.w) : "l"(p) : "memory");
  return v;
}
__device__ __forceinline__ void stg_b128(void* p, uint32_t x, uint32_t y, uint32_t z, uint32_t w) {
  asm volatile("{.reg .b128 t; .reg .b64 a,b; mov.b64 a,{%1,%2}; mov.b64 b,{%3,%4}; mov.b128 t,{a,b}; st.relaxed.gpu.global.b128 [%0],t;}" ::"l"(p), "r"(x), "r"(y), "r"(z), "r"(w) : "memory");
}
__device__ __forceinline__ void stg_rlx2(void* p, uint32_t x, uint32_t y) { asm volatile("st.relaxed.gpu.global.v2.u32 [%0],{%1,%2};" ::"l"(p), "r"(x), "r"(y) : "memory"); }
__device__ __forceinline__ unsigned ld_acq(const unsigned* p) { unsigned v; asm volatile("ld.acquire.gpu.global.u32 %0,[%1];" : "=r"(v) : "l"(p) : "memory"); return v; }
__device__ __forceinline__ void red_rel(unsigned* p) { asm volatile("red.release.gpu.global.add.u32 [%0],1;" ::"l"(p) : "memory"); }
__device__ __forceinline__ void red_rlx(unsigned* p) { asm volatile("red.relaxed.gpu.global.add.u32 [%0],1;" ::"l"(p) : "memory"); }
__device__ __forceinline__ void wait_cnt(const unsigned* p, unsigned n) { int it = 0; while (ld_acq(p) < n) { if (++it > SPIN_LIMIT) __trap(); } }
__device__ __forceinline__ uint32_t clk() { uint32_t c; asm volatile("mov.u32 %0,%%clock;" : "=r"(c)); return c; }
__device__ __forceinline__ uint32_t gtime() { uint32_t c; asm volatile("mov.u32 %0,%%globaltimer_lo;" : "=r"(c)); return c; }
__device__ __forceinline__ float ex2(float x) { float r; asm("ex2.approx.ftz.f32 %0,%1;" : "=f"(r) : "f"(x)); return r; }
__device__ __forceinline__ float silu(float x) { return x * __frcp_rn(1.f + __expf(-x)); }
__device__ __forceinline__ float rbf(float x) { return __bfloat162float(__float2bfloat16_rn(x)); }

__device__ __forceinline__ void wgmma_ss_n128(float* d, uint64_t a, uint64_t b, int sd) {
  asm volatile("{.reg .pred p; setp.ne.b32 p, %66, 0;\n"
    "wgmma.mma_async.sync.aligned.m64n128k16.f32.bf16.bf16 {%0,%1,%2,%3,%4,%5,%6,%7,%8,%9,%10,%11,%12,%13,%14,%15,%16,%17,%18,%19,%20,%21,%22,%23,%24,%25,%26,%27,%28,%29,%30,%31,%32,%33,%34,%35,%36,%37,%38,%39,%40,%41,%42,%43,%44,%45,%46,%47,%48,%49,%50,%51,%52,%53,%54,%55,%56,%57,%58,%59,%60,%61,%62,%63}, %64, %65, p, 1, 1, 0, 1;}\n"
    : "+f"(d[0]),"+f"(d[1]),"+f"(d[2]),"+f"(d[3]),"+f"(d[4]),"+f"(d[5]),"+f"(d[6]),"+f"(d[7]),
      "+f"(d[8]),"+f"(d[9]),"+f"(d[10]),"+f"(d[11]),"+f"(d[12]),"+f"(d[13]),"+f"(d[14]),"+f"(d[15]),
      "+f"(d[16]),"+f"(d[17]),"+f"(d[18]),"+f"(d[19]),"+f"(d[20]),"+f"(d[21]),"+f"(d[22]),"+f"(d[23]),
      "+f"(d[24]),"+f"(d[25]),"+f"(d[26]),"+f"(d[27]),"+f"(d[28]),"+f"(d[29]),"+f"(d[30]),"+f"(d[31]),
      "+f"(d[32]),"+f"(d[33]),"+f"(d[34]),"+f"(d[35]),"+f"(d[36]),"+f"(d[37]),"+f"(d[38]),"+f"(d[39]),
      "+f"(d[40]),"+f"(d[41]),"+f"(d[42]),"+f"(d[43]),"+f"(d[44]),"+f"(d[45]),"+f"(d[46]),"+f"(d[47]),
      "+f"(d[48]),"+f"(d[49]),"+f"(d[50]),"+f"(d[51]),"+f"(d[52]),"+f"(d[53]),"+f"(d[54]),"+f"(d[55]),
      "+f"(d[56]),"+f"(d[57]),"+f"(d[58]),"+f"(d[59]),"+f"(d[60]),"+f"(d[61]),"+f"(d[62]),"+f"(d[63])
    : "l"(a), "l"(b), "r"(sd));
}
__device__ __forceinline__ void wgmma_ss_n192(float* d, uint64_t a, uint64_t b, int sd) {
  asm volatile("{.reg .pred p; setp.ne.b32 p, %98, 0;\n"
    "wgmma.mma_async.sync.aligned.m64n192k16.f32.bf16.bf16 {%0,%1,%2,%3,%4,%5,%6,%7,%8,%9,%10,%11,%12,%13,%14,%15,%16,%17,%18,%19,%20,%21,%22,%23,%24,%25,%26,%27,%28,%29,%30,%31,%32,%33,%34,%35,%36,%37,%38,%39,%40,%41,%42,%43,%44,%45,%46,%47,%48,%49,%50,%51,%52,%53,%54,%55,%56,%57,%58,%59,%60,%61,%62,%63,%64,%65,%66,%67,%68,%69,%70,%71,%72,%73,%74,%75,%76,%77,%78,%79,%80,%81,%82,%83,%84,%85,%86,%87,%88,%89,%90,%91,%92,%93,%94,%95}, %96, %97, p, 1, 1, 0, 1;}\n"
    : "+f"(d[0]),"+f"(d[1]),"+f"(d[2]),"+f"(d[3]),"+f"(d[4]),"+f"(d[5]),"+f"(d[6]),"+f"(d[7]),
      "+f"(d[8]),"+f"(d[9]),"+f"(d[10]),"+f"(d[11]),"+f"(d[12]),"+f"(d[13]),"+f"(d[14]),"+f"(d[15]),
      "+f"(d[16]),"+f"(d[17]),"+f"(d[18]),"+f"(d[19]),"+f"(d[20]),"+f"(d[21]),"+f"(d[22]),"+f"(d[23]),
      "+f"(d[24]),"+f"(d[25]),"+f"(d[26]),"+f"(d[27]),"+f"(d[28]),"+f"(d[29]),"+f"(d[30]),"+f"(d[31]),
      "+f"(d[32]),"+f"(d[33]),"+f"(d[34]),"+f"(d[35]),"+f"(d[36]),"+f"(d[37]),"+f"(d[38]),"+f"(d[39]),
      "+f"(d[40]),"+f"(d[41]),"+f"(d[42]),"+f"(d[43]),"+f"(d[44]),"+f"(d[45]),"+f"(d[46]),"+f"(d[47]),
      "+f"(d[48]),"+f"(d[49]),"+f"(d[50]),"+f"(d[51]),"+f"(d[52]),"+f"(d[53]),"+f"(d[54]),"+f"(d[55]),
      "+f"(d[56]),"+f"(d[57]),"+f"(d[58]),"+f"(d[59]),"+f"(d[60]),"+f"(d[61]),"+f"(d[62]),"+f"(d[63]),
      "+f"(d[64]),"+f"(d[65]),"+f"(d[66]),"+f"(d[67]),"+f"(d[68]),"+f"(d[69]),"+f"(d[70]),"+f"(d[71]),
      "+f"(d[72]),"+f"(d[73]),"+f"(d[74]),"+f"(d[75]),"+f"(d[76]),"+f"(d[77]),"+f"(d[78]),"+f"(d[79]),
      "+f"(d[80]),"+f"(d[81]),"+f"(d[82]),"+f"(d[83]),"+f"(d[84]),"+f"(d[85]),"+f"(d[86]),"+f"(d[87]),
      "+f"(d[88]),"+f"(d[89]),"+f"(d[90]),"+f"(d[91]),"+f"(d[92]),"+f"(d[93]),"+f"(d[94]),"+f"(d[95])
    : "l"(a), "l"(b), "r"(sd));
}
__device__ __forceinline__ void wgmma_rs_n32(float* d, const uint32_t* a, uint64_t b, int sd) {
  asm volatile("{.reg .pred p; setp.ne.b32 p, %21, 0;\n"
    "wgmma.mma_async.sync.aligned.m64n32k16.f32.bf16.bf16 {%0,%1,%2,%3,%4,%5,%6,%7,%8,%9,%10,%11,%12,%13,%14,%15}, {%16,%17,%18,%19}, %20, p, 1, 1, 0;}\n"
    : "+f"(d[0]),"+f"(d[1]),"+f"(d[2]),"+f"(d[3]),"+f"(d[4]),"+f"(d[5]),"+f"(d[6]),"+f"(d[7]),
      "+f"(d[8]),"+f"(d[9]),"+f"(d[10]),"+f"(d[11]),"+f"(d[12]),"+f"(d[13]),"+f"(d[14]),"+f"(d[15])
    : "r"(a[0]), "r"(a[1]), "r"(a[2]), "r"(a[3]), "l"(b), "r"(sd));
}
__device__ __forceinline__ void wgmma_ssT_n32(float* d, uint64_t a, uint64_t b, int sd) {
  asm volatile("{.reg .pred p; setp.ne.b32 p, %18, 0;\n"
    "wgmma.mma_async.sync.aligned.m64n32k16.f32.bf16.bf16 {%0,%1,%2,%3,%4,%5,%6,%7,%8,%9,%10,%11,%12,%13,%14,%15}, %16, %17, p, 1, 1, 1, 0;}\n"
    : "+f"(d[0]),"+f"(d[1]),"+f"(d[2]),"+f"(d[3]),"+f"(d[4]),"+f"(d[5]),"+f"(d[6]),"+f"(d[7]),
      "+f"(d[8]),"+f"(d[9]),"+f"(d[10]),"+f"(d[11]),"+f"(d[12]),"+f"(d[13]),"+f"(d[14]),"+f"(d[15])
    : "l"(a), "l"(b), "r"(sd));
}

__device__ __forceinline__ void wgmma_rs_n32_z(float* d, const uint32_t* a, uint64_t b) {
  asm volatile("{.reg .pred p; setp.ne.b32 p, 0, 0;\n"
    "wgmma.mma_async.sync.aligned.m64n32k16.f32.bf16.bf16 {%0,%1,%2,%3,%4,%5,%6,%7,%8,%9,%10,%11,%12,%13,%14,%15}, {%16,%17,%18,%19}, %20, p, 1, 1, 0;}\n"
    : "=f"(d[0]),"=f"(d[1]),"=f"(d[2]),"=f"(d[3]),"=f"(d[4]),"=f"(d[5]),"=f"(d[6]),"=f"(d[7]),
      "=f"(d[8]),"=f"(d[9]),"=f"(d[10]),"=f"(d[11]),"=f"(d[12]),"=f"(d[13]),"=f"(d[14]),"=f"(d[15])
    : "r"(a[0]), "r"(a[1]), "r"(a[2]), "r"(a[3]), "l"(b));
}

namespace rec {
constexpr int NVR = P_NVR;
constexpr int NVS = 16 - NVR;
constexpr int NWP = P_NWP;
constexpr uint32_t WO = 0;
constexpr uint32_t XB = 65536;
constexpr uint32_t PK = XB + 32768;
constexpr uint32_t VX0 = PK + 24576;
constexpr uint32_t VX1 = VX0 + 4096;
constexpr uint32_t WVS = 131072;
constexpr uint32_t MEM = WVS + 2 * NVS * 2048;
constexpr uint32_t ARO = MEM + 10240;
constexpr uint32_t OB = ARO + 5120;
constexpr uint32_t QT = OB + 2048;
constexpr uint32_t KT = QT + 2048;
constexpr uint32_t RQ = KT + 6144;
constexpr uint32_t RK = RQ + 2048;
constexpr uint32_t SC = RK + 2048;
constexpr uint32_t OT = OB;
constexpr uint32_t TF = SC + 2048;
constexpr uint32_t PRE = MEM + 2 * NVR * 2048;
constexpr uint32_t TA = TF + 8192;
constexpr uint32_t RX = TA + 6144;
constexpr uint32_t VN = RX + 2048;
constexpr uint32_t BARS = VN + 4096;
constexpr uint32_t PACE = BARS + 18 * 8;
constexpr uint32_t SMEM = BARS + 512;
static_assert(PRE + 14336 <= BARS, "staging");
constexpr int NW1 = P_NW1;
static_assert(SMEM <= 232448, "smem");
constexpr int B_E = 2, B_SC = 3, B_S = 4, B_O = 5, B_F = 6, B_W = 7, B_C = 9, B_K = 10, B_Q = 1, B_S2 = 6, B_T2 = 9, B_P = 13, B_T = 14, B_R = 11, B_X = 12, B_V = 8;
constexpr int XC = 16384, X_RING = 131072, X_SC = 65536, X_TOK = 4096;
#define X_VX(i) (((i) >> 1) * 2048 + ((i) & 1) * 512)
#define X_VM(i) (X_VX(i) + 1024)
#define V_RING(n) (((n) & 1) * X_RING + ((n) & 2) * 2048)
#define V_TAG(n) ((~(n) >> 2) & 1)
}
struct RecMaps { CUtensorMap wq, wk, wv, wo, ari, vx; int zero[40]; };

#define F_(x) __uint_as_float(x)
#define U_(x) __float_as_uint(x)
#define AR_R(q) (24 + ((q) & 1) * 16 + ((q) >> 1) * 56)
#define AR_P(q) ((q) >> 1)
#define AR_ROW(i) (24 + ((i) & 1) * 16 + ((i) & 2) * 92 + (((i) >> 2) & 7) + ((i) >> 5) * 128)
constexpr size_t AR_OFF = 32 * 262144;
__device__ __forceinline__ void ar_fetch(uint32_t dst, const CUtensorMap* m, int slot, int half, uint32_t mb) {
  asm volatile("{.reg .pred p; elect.sync _|p, 0xffffffff; @p mbarrier.arrive.expect_tx.shared.b64 _,[%4],10240;\n"
               "@p cp.async.bulk.tensor.3d.shared::cluster.global.mbarrier::complete_tx::bytes [%0],[%1,{%2,%6,%3}],[%4];\n"
               "@p cp.async.bulk.tensor.3d.shared::cluster.global.mbarrier::complete_tx::bytes [%0+5120],[%1,{%2,%7,%5}],[%4];}"
               ::"r"(dst), "l"(m), "r"(slot * 64), "r"(AR_R(half * 2)), "r"(mb), "r"(AR_R(half * 2 + 1)), "r"(AR_P(half * 2)), "r"(AR_P(half * 2 + 1)) : "memory");
}
__device__ __forceinline__ uint4 exch_b128(void* p, uint32_t x, uint32_t y, uint32_t z, uint32_t w) {
  uint4 v;
  asm volatile("{.reg .b128 s, t; .reg .b64 a,b; mov.b64 a,{%5,%6}; mov.b64 b,{%7,%8}; mov.b128 s,{a,b}; atom.relaxed.gpu.global.exch.b128 t,[%4],s;"
               " mov.b128 {a,b},t; mov.b64 {%0,%1},a; mov.b64 {%2,%3},b;}" : "=r"(v.x), "=r"(v.y), "=r"(v.z), "=r"(v.w) : "l"(p), "r"(x), "r"(y), "r"(z), "r"(w) : "memory");
  return v;
}
#define CONSUME(v) do { if ((v) == 0x7fc12345u) sts1(sb + rec::BARS + 96, 0); } while (0)
__device__ __forceinline__ uint2 ldg_b64(const void* p) { uint2 v; asm volatile("{.reg .b64 t; ld.relaxed.gpu.global.b64 t,[%2]; mov.b64 {%0,%1},t;}" : "=r"(v.x), "=r"(v.y) : "l"(p) : "memory"); return v; }
__device__ __forceinline__ void stg_b64(void* p, uint32_t x, uint32_t y) { asm volatile("{.reg .b64 t; mov.b64 t,{%1,%2}; st.relaxed.gpu.global.b64 [%0],t;}" ::"l"(p), "r"(x), "r"(y) : "memory"); }
__device__ __forceinline__ uint32_t tagbad(uint32_t x, uint32_t y, uint32_t tag) { uint32_t r; asm("lop3.b32 %0,%1,%2,%3,0x7e;" : "=r"(r) : "r"(x), "r"(y), "r"(tag)); return r; }

__device__ __forceinline__ bool anybad(uint32_t a, uint32_t b, uint32_t c, uint32_t d, uint32_t e, uint32_t f, uint32_t g, uint32_t h, uint32_t tag) {
  uint32_t r;
  asm volatile("{.reg .b32 t,u,v,w; .reg .pred p; lop3.b32 t,%1,%2,%9,0x7e; lop3.b32 u,%3,%4,%9,0x7e; lop3.b32 v,%5,%6,%9,0x7e; lop3.b32 w,%7,%8,%9,0x7e;"
               " lop3.b32 t,t,u,v,0xfe; lop3.b32 t,t,w,1,0xa8; setp.ne.u32 p,t,0; vote.sync.any.pred p,p,0xffffffff; selp.u32 %0,1,0,p;}"
               : "=r"(r) : "r"(a), "r"(b), "r"(c), "r"(d), "r"(e), "r"(f), "r"(g), "r"(h), "r"(tag));
  return r;
}
__device__ __forceinline__ bool anybad(uint32_t a, uint32_t b, uint32_t c, uint32_t d, uint32_t tag) {
  uint32_t r;
  asm volatile("{.reg .b32 t,u; .reg .pred p; lop3.b32 t,%1,%2,%5,0x7e; lop3.b32 u,%3,%4,%5,0x7e;"
               " lop3.b32 t,t,u,1,0xa8; setp.ne.u32 p,t,0; vote.sync.any.pred p,p,0xffffffff; selp.u32 %0,1,0,p;}"
               : "=r"(r) : "r"(a), "r"(b), "r"(c), "r"(d), "r"(tag));
  return r;
}
#define BADS(r) anybad(r[0].x, r[0].y, r[1].x, r[1].y, r[2].x, r[2].y, r[3].x, r[3].y, tag)
constexpr float SCS = 0.08838834764831845f * 1.4426950408889634f / 16.f;
__device__ __forceinline__ uint32_t pkh(float lo, float hi, uint32_t tag) {
  uint32_t r;
  asm("{.reg .b32 t; cvt.rn.satfinite.f16x2.f32 t,%1,%2; lop3.b32 %0,t,0xfffffffe,%3,0xea;}" : "=r"(r) : "f"(hi), "f"(lo), "r"(tag));
  return r;
}
__device__ __forceinline__ uint32_t addh(uint32_t a, uint32_t b) { uint32_t r; asm("add.rn.f16x2 %0,%1,%2;" : "=r"(r) : "r"(a), "r"(b)); return r; }
__device__ __forceinline__ float hlo(uint32_t v) { float r; asm("{.reg .b16 a,b; mov.b32 {a,b},%1; cvt.f32.f16 %0,a;}" : "=f"(r) : "r"(v)); return r; }
__device__ __forceinline__ float hhi(uint32_t v) { float r; asm("{.reg .b16 a,b; mov.b32 {a,b},%1; cvt.f32.f16 %0,b;}" : "=f"(r) : "r"(v)); return r; }
__device__ __forceinline__ uint32_t ordh(uint32_t v) {
  uint32_t r;
  asm("{.reg .b32 m; prmt.b32 m,%1,0,0xbb99; lop3.b32 %0,%1,m,0x7fff7fff,0x78;}" : "=r"(r) : "r"(v));
  return r;
}
template <bool MASK>
__device__ __forceinline__ float4 softmax2(const uint2 (&r)[4], uint32_t mx, uint32_t my, uint32_t& k) {
  uint32_t x = addh(addh(r[0].x, r[1].x), addh(r[2].x, r[3].x)), y = addh(addh(r[0].y, r[1].y), addh(r[2].y, r[3].y));
  if (MASK) { x = addh(x, mx); y = addh(y, my); }
  asm("max.f16x2 %0,%1,%2;" : "=r"(k) : "r"(x), "r"(y));
  k = ordh(k);
  const int k0 = __reduce_max_sync(~0u, (int)(k << 16)), k1 = __reduce_max_sync(~0u, (int)k);
  const float m0 = hhi(k0 ^ ((k0 >> 31) & 0x7fff0000)) * -16.f, m1 = hhi(k1 ^ ((k1 >> 31) & 0x7fff0000)) * -16.f;
  return make_float4(ex2(fmaf(hlo(x), 16.f, m0)), ex2(fmaf(hhi(x), 16.f, m1)), ex2(fmaf(hlo(y), 16.f, m0)), ex2(fmaf(hhi(y), 16.f, m1)));
}
__device__ __forceinline__ char* mkp(uint32_t lo, uint32_t hi) { uint64_t r; asm("mov.b64 %0,{%1,%2};" : "=l"(r) : "r"(lo), "r"(hi)); return (char*)r; }
#define LO(p) ((uint32_t)(uint64_t)(p))
#define HI(p) ((uint32_t)((uint64_t)(p) >> 32))
__device__ __forceinline__ uint32_t mulbf(uint32_t a, uint32_t b) { uint32_t r; asm("mul.rn.bf16x2 %0,%1,%2;" : "=r"(r) : "r"(a), "r"(b)); return r; }
__device__ __forceinline__ uint32_t fmabf(uint32_t a, uint32_t b, uint32_t c) { uint32_t r; asm("fma.rn.bf16x2 %0,%1,%2,%3;" : "=r"(r) : "r"(a), "r"(b), "r"(c)); return r; }
__device__ __forceinline__ uint32_t addbf(uint32_t a, uint32_t b) { uint32_t r; asm("add.rn.bf16x2 %0,%1,%2;" : "=r"(r) : "r"(a), "r"(b)); return r; }
__device__ __forceinline__ void pv_mem(const uint32_t (&p)[4], uint32_t pm, const uint4 (&v)[4], const uint4 (&vn)[2], uint32_t (&O)[4]) {
  float o[4][4] = {{0, 0, 0, 0}, {0, 0, 0, 0}, {0, 0, 0, 0}, {0, 0, 0, 0}};
  mma16(o[0], v[0].x, v[0].y, v[0].z, v[0].w, p[0], p[1]);
  mma16(o[1], v[2].x, v[2].y, v[2].z, v[2].w, p[0], p[1]);
  mma16(o[2], v[1].x, v[1].y, v[1].z, v[1].w, p[2], p[3]);
  mma16(o[3], v[3].x, v[3].y, v[3].z, v[3].w, p[2], p[3]);
  mma16(o[0], vn[0].x, vn[0].y, vn[0].z, vn[0].w, pm, pm);
  mma16(o[1], vn[1].x, vn[1].y, vn[1].z, vn[1].w, pm, pm);
  O[0] = pk(o[0][0] + o[2][0], o[0][1] + o[2][1]); O[1] = pk(o[0][2] + o[2][2], o[0][3] + o[2][3]);
  O[2] = pk(o[1][0] + o[3][0], o[1][1] + o[3][1]); O[3] = pk(o[1][2] + o[3][2], o[1][3] + o[3][3]);
}
__device__ __forceinline__ void pv_tok(const uint32_t (&p)[4], uint32_t pm, const uint4 (&v)[4], const uint32_t (&vm)[4], uint32_t (&O)[4]) {
  float o[2][4] = {{0, 0, 0, 0}, {0, 0, 0, 0}}, sum[4] = {0, 0, 0, 0};
  const uint32_t one = 0x3f803f80u;
  mma16(sum, one, one, one, one, p[0], p[1]);
  mma16(o[0], v[0].x, v[0].y, v[0].z, v[0].w, p[0], p[1]);
  mma16(o[1], v[2].x, v[2].y, v[2].z, v[2].w, p[0], p[1]);
  mma16(sum, one, one, one, one, p[2], p[3]);
  mma16(o[0], v[1].x, v[1].y, v[1].z, v[1].w, p[2], p[3]);
  mma16(o[1], v[3].x, v[3].y, v[3].z, v[3].w, p[2], p[3]);
  mma8(sum, one, one, pm);
  mma8(o[0], vm[0], vm[1], pm);
  mma8(o[1], vm[2], vm[3], pm);
  float i0, i1;
  asm("rcp.approx.ftz.f32 %0,%1;" : "=f"(i0) : "f"(sum[0]));
  asm("rcp.approx.ftz.f32 %0,%1;" : "=f"(i1) : "f"(sum[1]));
  O[0] = pk(o[0][0] * i0, o[0][1] * i1); O[1] = pk(o[0][2] * i0, o[0][3] * i1);
  O[2] = pk(o[1][0] * i0, o[1][1] * i1); O[3] = pk(o[1][2] * i0, o[1][3] * i1);
}
__device__ __forceinline__ uint32_t sum4bf(uint32_t a, uint32_t b, uint32_t c, uint32_t d) { return addbf(addbf(a, b), addbf(c, d)); }
template <int OFF>
__device__ __forceinline__ void sta1(uint32_t a, uint32_t v, uint32_t mb) {
  asm volatile("st.async.shared::cluster.mbarrier::complete_tx::bytes.b32 [%0+%3],%1,[%2];" ::"r"(a), "r"(v), "r"(mb), "n"(OFF) : "memory");
}

__device__ __forceinline__ void wait_time(uint32_t t) { while ((int)(gtime() - t) < 0) __nanosleep(64); }
__device__ __noinline__ void rec_prefetch(const char* wmod, const char* w1, const char* x, const char* wo) {
  const int hb = blockIdx.x - 128;
  const uint32_t t0 = gtime();
  uint32_t t = t0 + PF0;
#pragma unroll 1
  for (int job = 0; job < (PFT ? 5 : 3); job++) {
    const char* p = job == 0 ? x + (6 + hb) * 65536 : job == 1 ? wmod + hb * 12288 + 4096 : job == 2 ? w1 + hb * 7168 : job == 3 ? x + hb * 8192 : wo + (1020 + hb) * 8192;
    const int n = job == 0 ? 120 - (hb & 2) * 4 : job == 3 ? 128 : 256, d = job == 0 ? 8192 : job == 1 ? 49152 : job == 2 ? 28672 : job == 3 ? 32768 : -32768;
    if (job == 3) t = t0 + PFT;
    PT(8 + job);
#pragma unroll 1
    for (int i = 0; i < n; i++) {
      wait_time(t);
      asm volatile("cp.async.bulk.prefetch.L2.global [%0], %1;" ::"l"(p), "r"(job == 2 ? 7168 : 8192) : "memory");
      p += !job && (i & 7) == 7 ? 204800 : d;
      t += job < 3 ? PFD : PFS;
      if (job && (i & 31) == 31 && ldg_rlx1(&g_fin)) return;
    }
  }
  PT(13);
}
__device__ __noinline__ void rec_helper(uint32_t sb, const bf16* cvec, const bf16* wmod, const char* w1, const bf16* b1, uint32_t t0) {
  const int tid = threadIdx.x, hb = blockIdx.x - 128;
  PT(1);
  for (int i = tid; i < 1024; i += 256) sts1(sb + i * 8, U_(rbf(silu(__bfloat162float(cvec[i])))));
  for (int i = tid; i < 2048; i += 256) g_stat[hb * 2048 + i] = make_uint4(~0u, ~0u, ~0u, ~0u);
  for (int i = tid; i < 512; i += 256) g_cnt[hb * 512 + i] = 0;
#pragma unroll 1
  for (int job = 0; job < 2; job++) {
    wait_time(t0 + PF0 + (job ? 600 : 350) * PFD);
    BAR_SYNC(rec::B_F, 256);
    PT(2 + job * 5);
    const int n8 = job ? 112 : 128, rg = tid >= n8, cg = tid - rg * n8, pitch = job ? 448 : 768;
    const uint4* p = (const uint4*)(job ? w1 + hb * 1792 : (const char*)(wmod + 2048 + hb * 1024)) + rg * pitch + min(cg, n8 - 1);
    float a1[8] = {0, 0, 0, 0, 0, 0, 0, 0}, a2[8] = {0, 0, 0, 0, 0, 0, 0, 0};
#pragma unroll 1
    for (int r0 = rg; r0 < 1024; r0 += 32) {
      uint4 v[16];
#pragma unroll
      for (int i = 0; i < 16; i++) { v[i] = ldg_rlx4(p); p += 2 * pitch; }
#pragma unroll
      for (int i = 0; i < 16; i++) {
        const float2 f = lds2f(sb + (r0 + 2 * i) * 8);
        const float w[8] = {blo(v[i].x), bhi(v[i].x), blo(v[i].y), bhi(v[i].y), blo(v[i].z), bhi(v[i].z), blo(v[i].w), bhi(v[i].w)};
#pragma unroll
        for (int e = 0; e < 8; e++) { a1[e] += f.x * w[e]; a2[e] += f.y * w[e]; }
      }
    }
    const uint32_t rd = sb + 8192;
    if (cg < n8) {
#pragma unroll
      for (int e = 0; e < 8; e++) sts2(rd + rg * 8192 + (cg * 8 + e) * 8, U_(a1[e]), U_(a2[e]));
    }
    BAR_SYNC(rec::B_F, 256);
    if (job == 0) {
      for (int i = tid; i < 1024; i += 256) g_mod[2048 + hb * 1024 + i] = rbf(F_(lds1(rd + i * 8)) + F_(lds1(rd + 8192 + i * 8)));
      BAR_SYNC(rec::B_F, 256);
      PT(6);
      if (tid == 0) { red_rel(&g_mcnt); wait_cnt(&g_mcnt, 4); }
      BAR_SYNC(rec::B_F, 256);
      for (int i = tid; i < 1024; i += 256) sts2(sb + i * 8, U_(rbf(1.f + __ldcg(g_mod + 4096 + i))), U_(__ldcg(g_mod + 3072 + i)));
    } else {
      for (int i = tid; i < 448; i += 256) {
        const int gn = hb * 896 + i * 2;
        const uint32_t bb = *(const uint32_t*)(b1 + gn);
        const float4 u = lds4f(rd + i * 16), w = lds4f(rd + 8192 + i * 16);
        ((uint2*)g_cc)[(gn >> 4) * 8 + ((gn >> 1) & 3) * 2 + ((gn >> 3) & 1)] = make_uint2(pk(u.x + w.x, u.z + w.z), pk(0.5f * (u.y + w.y + blo(bb)), 0.5f * (u.w + w.w + bhi(bb))));
      }
      PT(4);
    }
  }
}

__global__ void __cluster_dims__(2, 1, 1) __launch_bounds__(512, 1)
k_rec(const __grid_constant__ RecMaps mp, const bf16* __restrict__ mem0, const bf16* __restrict__ x, const bf16* __restrict__ cvec,
      const bf16* __restrict__ wmod, const char* __restrict__ w1, const bf16* __restrict__ b1, const char* __restrict__ wo, char* xc, int dF, int dA, int dS, int dM, int dG, int dP, int dX, int dD, int dZ, int dQ, int dV, int dX2) {
  using namespace rec;
  extern __shared__ __align__(1024) char smem[];
  const uint32_t sb = (uint32_t)__cvta_generic_to_shared(smem);
  if ((sb & 0x3FFFF) != 1024) __trap();
  PH(0); RS(0); if (threadIdx.x == 0) PT(0);
  if (threadIdx.x == 0) {
    int b = blockIdx.x;
    if (b >= 8 && b < 128) {
      const int t = (b >> 1) - 4, u = t - 32;
      b = 2 * (t < 32 ? 4 + (t & 16) + (t & 7) * 2 + ((t >> 3) & 1) : 36 + (u / 14) * 14 + (u % 7) * 2 + ((u / 7) & 1)) + (b & 1);
    }
    sts1(sb + rec::PACE + 24, b);
    const int c = blockIdx.x >> 1, l = c < 36 ? (c - 4) & 7 : (c - 36) % 7, m = c < 4 ? c : c < 36 ? (c - 4) >> 3 : (c - 36) / 7;
    const int g = c < 4 ? 15 : (l >> 1) * 4 + (l & 1) + (c < 36 ? 0 : 2);
    unsigned sm;
    asm("mov.u32 %0,%%smid;" : "=r"(sm));
    if (c < 64) g_slot[sm & 255] = 1 + FMAP;
  }
#define ROLE_REFRESH { asm volatile("mov.u32 %0,%%tid.x;" : "=r"(tid)); wid = __shfl_sync(~0u, tid >> 5, 0); b = __shfl_sync(~0u, lds1(sb + PACE + 24), 0); }
#define ROLE_VARS int tid; asm volatile("mov.u32 %0,%%tid.x;" : "=r"(tid)); \
    int wid = __shfl_sync(~0u, tid >> 5, 0), b = __shfl_sync(~0u, lds1(sb + PACE + 24), 0);
#define wg (wid >> 2)
#define iw (wid & 3)
#define h (b >> 2)
#define j (b & 3)
#define a (b & 1)
#define bb ((b >> 1) & 1)
  const uint32_t wbar = sb + BARS + 48, obar = wbar + 8;
  if (threadIdx.x == 256) {
    for (int i = 0; i < 18; i++) if (i != 12) mbar_init(sb + BARS + i * 8, i == 3 || i == 8 || i == 9 || i == 10 ? 2 : 1);
    for (int i = 0; i < 3; i++) mbar_init(sb + PACE + i * 8, 1);
    asm volatile("fence.mbarrier_init.release.cluster;" ::: "memory");
    FENCE_ASYNC_SMEM();
    mbar_expect(sb + BARS, 2048);
    mbar_expect(sb + BARS + 16, 4096);
    mbar_expect(sb + BARS + 32, 4096);
    mbar_expect(sb + BARS + 40, 4096);
  }
  __syncthreads();
  asm volatile("barrier.cluster.arrive.relaxed.aligned;" ::: "memory");
#define lane ((int)(l16 >> 4))
#define l16 (L16 & 0x1f0)
#define PIN(x) __shfl_xor_sync(~0u, (uint32_t)(x), 0)
#define X_LOAD(n, w, u) \
        asm volatile("{.reg .pred p; elect.sync _|p, 0xffffffff; @p mbarrier.arrive.expect_tx.shared.b64 _,[%2],8192;\n" \
                     "@p cp.async.bulk.shared::cluster.global.mbarrier::complete_tx::bytes [%0],[%1],8192,[%2];}" ::"r"(sb + XB + (w) * 16384 + (u) * 8192), \
                     "l"(g_h + (n) * 4096 + a * 2048 + (w) * 1024 + (u) * 512), "r"(sb + BARS + 64 + (w) * 8) : "memory")
#define lpub ((L16 & 0x30) * 64 + ((L16 >> 3) & 0x38))
#define lrow ((L16 & 0x70) + (((L16 >> 3) ^ L16) & 0x70 & ~((L16 >> 3) & 0x40) ? L16 & 0x180 : 512))

  const int role = __shfl_sync(~0u, threadIdx.x >> 7, 0);
  if (role < 2) {
    asm volatile("setmaxnreg.inc.sync.aligned.u32 %0;" ::"n"(RF_));
    ROLE_VARS
    uint32_t L16 = __shfl_sync(~0u, sb + (tid & 31) * 16, tid & 31);
    uint32_t wQ[16][4], wK[16][4], wV[NVR][4];
    uint32_t frag = sb + ((lane & 7) + (lane >> 4) * 8) * 128 + (((iw * 2 + ((lane >> 3) & 1)) ^ (lane & 7)) << 4);
#define QSW (a ? 0 : 64)
    {
      const bool spare = b >= 128;
      const uint32_t t0 = gtime();
      uint4 xr[16];
      int seg = spare ? b - 126 : wg;
      const int half = spare ? wg : a;
      auto x_fetch = [&]() {
        const uint4* px = (const uint4*)x + (seg * 32 + iw * 8 + (lane >> 2)) * 128 + half * 64 + (lane & 3);
#pragma unroll
        for (int i = 0; i < 16; i++) xr[i] = __ldg(px + i * 4);
      };
      if (!spare) {
        uint4 wm[8];
        const uint4* pw = (const uint4*)(wmod + (size_t)((b >> 5) * 256 + (tid >> 3)) * 6144 + (b & 31) * 64) + (tid & 7);
        const float cs = __bfloat162float(cvec[(b >> 5) * 256 + tid]);
#pragma unroll
        for (int i = 0; i < 8; i++) wm[i] = __ldcs(pw + (size_t)i * 32 * 768);
        float* sc = (float*)(smem + PRE);
        sc[tid] = rbf(silu(cs));
        PT(1);
        BAR_SYNC(B_F, 256);
        float acc[8] = {0, 0, 0, 0, 0, 0, 0, 0};
#pragma unroll
        for (int i = 0; i < 8; i++) {
          const float f = sc[i * 32 + (tid >> 3)];
          acc[0] += f * blo(wm[i].x); acc[1] += f * bhi(wm[i].x); acc[2] += f * blo(wm[i].y); acc[3] += f * bhi(wm[i].y);
          acc[4] += f * blo(wm[i].z); acc[5] += f * bhi(wm[i].z); acc[6] += f * blo(wm[i].w); acc[7] += f * bhi(wm[i].w);
        }
#pragma unroll
        for (int i = 0; i < 8; i++) { acc[i] += __shfl_xor_sync(~0u, acc[i], 8); acc[i] += __shfl_xor_sync(~0u, acc[i], 16); }
        float* red = sc + 1024;
        if ((tid & 31) < 8) {
#pragma unroll
          for (int i = 0; i < 8; i++) red[(tid >> 5) * 64 + (tid & 7) * 8 + i] = acc[i];
        }
        BAR_SYNC(B_F, 256);
        PT(2);
        if (tid < 64) {
          float t = 0;
#pragma unroll
          for (int i = 0; i < 8; i++) t += red[i * 64 + tid];
          asm volatile("st.relaxed.gpu.global.u32 [%0],%1;" ::"l"((unsigned*)g_modp + (b >> 5) * 2048 + (b & 31) * 64 + tid), "r"(U_(t) | 1u) : "memory");
        }
      } else {
        asm volatile("griddepcontrol.launch_dependents;");
      }
      x_fetch();
      const uint32_t md = sb + PRE + 6144, rx = mapa(sb, a ^ !spare);
      asm volatile("barrier.cluster.wait.aligned;" ::: "memory");
      if (!spare) {
        mbar_wait(sb + BARS + 88, 0);
#pragma unroll
        for (int i = 0; i < 16; i++) ldsm4t(wQ[i], (frag ^ QSW) + WO + wg * 32768 + i * 2048);
      }
      PT(4);
#pragma unroll 1
      for (int it = 0;; it++) {
        if (tid == 0) mbar_expect(sb + BARS + 104, 512);
        float c[4][4] = {{0, 0, 0, 0}, {0, 0, 0, 0}, {0, 0, 0, 0}, {0, 0, 0, 0}};
#pragma unroll
        for (int i = 0; i < 16; i++) {
          mma16(c[(i & 1) * 2], xr[i].x, 0x3f803f80u, xr[i].y, 0x3f803f80u, xr[i].x, xr[i].y);
          mma16(c[(i & 1) * 2 + 1], xr[i].z, 0x3f803f80u, xr[i].w, 0x3f803f80u, xr[i].z, xr[i].w);
        }
#pragma unroll
        for (int e = 0; e < 4; e++) c[0][e] = (c[0][e] + c[1][e]) + (c[2][e] + c[3][e]);
        const int src = (lane & 28) + (lane >> 3);
        const float sq = __shfl_sync(~0u, (lane & 4) ? c[0][1] : c[0][0], src), sm = __shfl_sync(~0u, (lane & 4) ? c[0][3] : c[0][2], src);
        if ((lane & 3) < 2) sta1<0>(rx + PRE + 10240 + (wid ^ (spare * 4)) * 64 + (lane >> 2) * 8 + (lane & 1) * 4, U_((lane & 1) ? sm : sq), rx + BARS + 104);
        mbar_wait(sb + BARS + 104, it & 1);
        const float2 ot = lds2f(sb + PRE + 10240 + wid * 64 + (lane >> 2) * 8);
        const float mean = (sm + ot.y) * (1.f / 1024);
        const float rs = rsqrtf(fmaxf((sq + ot.x) * (1.f / 1024) - mean * mean, 0.f) + 1e-5f), nm = -mean * rs;
        const uint32_t rh = pk(rs, rs), rl = pk(rs - blo(rh), rs - blo(rh)), n2 = pk(nm, nm);
#define NRM(v) v = fmabf(v, rh, fmabf(v, rl, n2))
#pragma unroll
        for (int i = 0; i < 16; i++) { NRM(xr[i].x); NRM(xr[i].y); NRM(xr[i].z); NRM(xr[i].w); }
        if (!it) {
          PT(3);
#pragma unroll 1
          for (int i = 0; i < 2; i++) {
            uint4 p[4];
            for (int n = 0;; n++) {
#pragma unroll
              for (int e = 0; e < 4; e++) p[e] = ldg_rlx4(g_modp + e * 512 + i * 256 + tid);
              uint32_t ok = 1;
#pragma unroll
              for (int e = 0; e < 4; e++) ok &= p[e].x & p[e].y & p[e].z & p[e].w;
              if (__all_sync(~0u, ok) || n > SPIN_LIMIT / 16) break;
              __nanosleep(100);
            }
#define MSUM(e) (i + rbf((F_(p[0].e) + F_(p[1].e)) + (F_(p[2].e) + F_(p[3].e))))
            sts2(md + i * 2048 + tid * 8, pk(MSUM(x), MSUM(y)), pk(MSUM(z), MSUM(w)));
          }
          BAR_SYNC(B_F, 256);
          PT(5);
        }
        const int e0 = (iw * 8 + (lane >> 2)) * 8 + ((lane & 3) ^ (lane >> 2));
        uint4* dst = g_h + seg * 4096 + half * 2048;
#pragma unroll
        for (int i = 0; i < 16; i++) {
          const uint32_t ma = md + half * 1024 + (lane & 3) * 16 + i * 64;
          const uint4 sv = lds4(ma), cv = lds4(ma + 2048);
          xr[i] = make_uint4(fmabf(xr[i].x, cv.x, sv.x), fmabf(xr[i].y, cv.y, sv.y), fmabf(xr[i].z, cv.z, sv.z), fmabf(xr[i].w, cv.w, sv.w));
        }
        if (!spare) {
#pragma unroll
          for (int i = 0; i < 16; i++) sts4(sb + WO + wg * 32768 + (e0 ^ ((i & 1) * 4)) * 16 + (i >> 1) * 4096, xr[i].x, xr[i].y, xr[i].z, xr[i].w);
          break;
        }
#pragma unroll
        for (int i = 0; i < 16; i++) dst[(e0 ^ ((i & 1) * 4)) + (i >> 1) * 256] = xr[i];
        seg += 4;
        if (seg < 64) x_fetch();
        FENCE_ASYNC();
        BAR_SYNC(B_F, 256);
        if (tid == 0) red_rlx(g_hf + b - 128);
        if (seg >= 64) break;
      }
      if (spare) { rec_helper(sb, cvec, wmod, w1, b1, t0); return; }
      PH(1); PH(2); PT(6);
    }
    ROLE_REFRESH
#define ownv ((iw >> 1) == a)
#define owner (iw >= 2)
#define oi (wid & 1)
    {
      const uint32_t rsb = mapa(sb, owner ? a : a ^ 1);
      const uint32_t pp = rsb + PK + (owner ? 0 : 12288) + (oi * 2048 + wg * 1024) + l16;
      const uint32_t mb = sb + MEM + wg * 5120;
      sts4(L16 + TF + wid * 512, mb + lrow, owner ? L16 + (lane >> 4) * (RK - RQ - 256) + RQ + oi * 1024 + wg * 256 : rsb + RQ + oi * 1024 + 512 + wg * 256 + (l16 >> 2),
           L16 + OB, frag + wg * NVS * 2048);
      sts4(L16 + TF + 4096 + wid * 512, sb + WO + (wid >> 1) * 16384 + ((lane & 7) + (lane >> 4) * 8) * 128 + ((((wid & 1) * 4 + ((lane >> 3) & 1)) ^ (lane & 7)) << 4),
           sb + ARO + wid * 640 + lrow, pp, LO(xc) + h * 262144 + (bb * 2 + (iw >> 1)) * XC + X_VM(0) + oi * 2048 + a * 256 + (l16 >> 1));
    }
    uint32_t tp = L16 + TF + wid * 512;
    auto park_ptr = [&]() { return lds1(tp + 4096 + 8); };
    auto park_w = [&](const uint32_t* w, int m, uint32_t d) {
      if (m == 2) d += (sb & 0x1000000) ? 0 : owner ? 0x1003000 : -0x1003000;
      if (m == 2 ? ownv : owner) {
        sts4(d + m * 4096, w[0], w[1], w[2], w[3]); sts4(d + m * 4096 + 512, w[4], w[5], w[6], w[7]);
      } else {
        const uint32_t pb = (d & 0xff000000u) | (1024 + BARS + (m ? 24 + m * 8 : 16));
        sta4(d + m * 4096, w, pb); sta4(d + m * 4096 + 512, w + 4, pb);
      }
    };
    auto park = [&](const float* f, int m, int n, uint32_t d) {
      uint32_t w[8];
#pragma unroll
      for (int i = 0; i < 8; i++) w[i] = pk(f[2 * i], f[2 * i + 1]);
      park_w(w, m, d);
    };
#define D64(lo) (0x4000004000000000ull | (uint32_t)(lo))
#define XD(i) D64(x | (((i) >> 2) * 256 + ((i) & 3) * 2))
    auto xdesc = [&](uint32_t xb) { return ((uint32_t)__shfl_sync(~0u, 1024 + xb + wg * 16384, 0) >> 4) | 0x10000u; };
    auto rs_issue = [&](float* acc, const uint32_t (&w)[16][4], uint32_t xb, bool fence) {
      const uint32_t x = xdesc(xb);
      if (fence) WG_FENCE();
      wgmma_rs_n32_z(acc, w[0], XD(0));
#pragma unroll
      for (int i = 1; i < 16; i++) wgmma_rs_n32(acc, w[i], XD(i), 1);
      WG_COMMIT();
    };
    auto v_issue = [&](float* acc, uint32_t xb, bool fence) {
      const uint32_t dv = ((uint32_t)__shfl_sync(~0u, 1024 + WVS + wg * NVS * 2048, 0) >> 4) | 0x10000u, x = xdesc(xb);
      if (fence) WG_FENCE();
      wgmma_rs_n32_z(acc, wV[0], XD(0));
#pragma unroll
      for (int i = 1; i < VRF; i++) wgmma_rs_n32(acc, wV[i], XD(i), 1);
#pragma unroll
      for (int i = NVR; i < 16; i++) wgmma_ssT_n32(acc, D64(dv + (i - NVR) * 128), XD(i), 1);
#pragma unroll
      for (int i = VRF; i < NVR; i++) wgmma_rs_n32(acc, wV[i], XD(i), 1);
      WG_COMMIT();
    };
    uint32_t mA, vP[2][4];
#define V_AHEAD mA = lds1(tp); frag = lds1(tp + 12); ldsm4t(vP[0], frag + WVS + (15 - NVR) * 2048); ldsm4t(vP[1], frag + WVS + (14 - NVR) * 2048);
    auto vk_pass = [&](int n, uint32_t d, uint32_t xb, bool steady, auto between) {
      float acc[16], acc2[16];
      v_issue(acc, xb, true);
      rs_issue(acc2, wK, xb, false);
      between();
      const bool keep = !steady || !UNC || n < 64;
      if (steady ? keep : n) mbar_wait(sb + BARS + 80, (n - 1) & 1);
      WG_WAIT(1);
      if (keep) {
        park(acc, 2, n, d);
        if (steady) BAR_ARRIVE(B_K, 320);
      }
      V_AHEAD
      WG_WAIT(0);
      if (keep) park(acc2, 1, n, d + (VPC ? (vP[1][0] ^ mA) & dZ : 0));
    };
    uint32_t q0[8], q1[8];
    {
      float acc[16], acc2[16];
      FENCE_ASYNC_SMEM();
      BAR_SYNC(B_F, 256);
      rs_issue(acc, wQ, WO, true);
      rs_issue(acc2, wQ, WO + 32768, false);
      WG_WAIT(0);
#pragma unroll
      for (int i = 0; i < 8; i++) { q0[i] = pk(acc[2 * i], acc[2 * i + 1]); q1[i] = pk(acc2[2 * i], acc2[2 * i + 1]); }
    }
    mbar_wait(wbar, 0);
    PT(7);
#pragma unroll
    for (int i = 0; i < 16; i++) ldsm4t(wK[i], (frag ^ QSW) + XB + wg * 32768 + i * 2048);
#pragma unroll
    for (int i = 0; i < NVR; i++) ldsm4t(wV[i], frag + MEM + (wg * NVR + i) * 2048);
    FENCE_ASYNC_SMEM();
    PH(3); PT(8);
    CLUSTER_SYNC();
    PT(9);
    frag += wg * NVS * 2048;
    park_w(q0, 0, park_ptr());
    PT(10);
#pragma unroll 1
    for (int n = 0; n < 2; n++) {
      asm volatile("" : "+r"(wid));
      vk_pass(n, park_ptr(), n * XB, false, [&]() {
        if (n) {
          BAR_SYNC(B_C, 320);
          PT(12);
          mbar_wait(sb + BARS + 24, 0);
          park_w(q1, 0, park_ptr());
        }
      });
      if (n) break;
      PT(11);
      BAR_SYNC(B_C, 448);
      if (tid == 0) {
        mbar_expect(obar, 65536);
#pragma unroll 1
        for (int i = 0; i < 4; i++) tma2d(sb + WO + i * 16384, &mp.wo, j * 256 + i * 64, h * 128, obar);
      }
    }
    static_assert(WO == 0, "x");
    {
      BAR_ARRIVE(B_P, 384); BAR_ARRIVE(B_X, 320); BAR_ARRIVE(B_Q, 288);
    }
    PT(13);
    PH(4); RS(1); PT(14);
    ROLE_REFRESH
    for (int s = 0; s < 64; s++) {
      asm volatile("" : "+r"(tp), "+r"(wid));
      asm volatile("mov.u32 %0,%%cluster_ctarank;" : "=r"(b));
      uint32_t vS[NVS][4], bf[8][4];
      static_assert(NVR == 5, "schedule");
#define VLD(k) ldsm4t(vS[(k) - NVR], frag + WVS + ((k) - NVR) * 2048)
#define BLD(t) ldsm4t(bf[t], mA + (t) * 640)
#define VMMA(c, w, i) mma16(c, (w)[0], (w)[1], (w)[2], (w)[3], bf[(i) >> 1][((i) & 1) * 2], bf[(i) >> 1][((i) & 1) * 2 + 1])
#define VS_(c, k) VMMA(c, vS[(k) - NVR], k)
#define QK(i) VMMA(cQ, wQ[i], i); VMMA(cK, wK[i], i)
#define PREV VLD(13); VLD(12); if (NF > 2) VLD(11);
      if (s > 0) BAR_SYNC(B_R, 320);
      float cV[4] = {0, 0, 0, 0}, cW[4] = {0, 0, 0, 0};
      {
        float cQ[4] = {0, 0, 0, 0}, cK[4] = {0, 0, 0, 0};
        BLD(7); BLD(6); BLD(5); BLD(4); if (NB0 > 4) BLD(3);
        SCHED_FENCE(47);
        QK(15); VMMA(cV, vP[0], 15);
        QK(14); VMMA(cV, vP[1], 14);
        QK(13); QK(12);
        SCHED_FENCE(51);
        if (NB0 < 5) BLD(3);
        BLD(2); BLD(1); BLD(0);
        const uint32_t rm = lds1(tp + 4);
        QK(11); QK(10); QK(9); QK(8); QK(7);
        if (PV0 == 6) { SCHED_FENCE(48); PREV }
        QK(6); QK(5);
        if (PV0 == 4) { QK(4); SCHED_FENCE(48); PREV } else { QK(4); }
        QK(3); QK(2); QK(1); QK(0);
        const uint32_t w0 = pk(cQ[0] * SCS, cQ[1] * SCS), w1 = pk(cQ[2] * SCS, cQ[3] * SCS), w2 = pk(cK[0], cK[1]), w3 = pk(cK[2], cK[3]);
        if (owner) {
          stsm4(rm, w0, w1, w2, w3);
          BAR_ARRIVE(B_E, 256);
        } else {
          const uint32_t mm = (rm & 0xff000000u) | (1024 + BARS);
          sta1<0>(rm, w0, mm); sta1<128>(rm, w1, mm);
          sta1<RK - RQ>(rm, w2, mm); sta1<RK - RQ + 128>(rm, w3, mm);
        }
        if (wid == 2) TS(0);
      }
      uint4 t1;
      uint32_t oA, wo[16][4];
      {
        DLY(10)
        if (NF < 3) VLD(11);
        VLD(10);
        VS_(cW, 13); VLD(9); VS_(cV, 12); VLD(8); VLD(7); VMMA(cW, wV[0], 0); VMMA(cV, wV[1], 1); VLD(6);
        VMMA(cW, wV[2], 2); VMMA(cV, wV[3], 3); VLD(5); VMMA(cW, wV[4], 4); VS_(cV, 11);
        VS_(cW, 10); VS_(cV, 9); VS_(cW, 8); VS_(cV, 7); VS_(cW, 6); VS_(cV, 5);
#pragma unroll
        for (int e = 0; e < 4; e++) cV[e] += cW[e];
        const uint32_t ex = tp + (RX - TF) - wg * 2048;
        t1 = lds4(tp + 4096 + (T1L ? vS[3][0] & dZ : 0));
        oA = lds1(tp + 8 + (s & dZ));
        if (wg) {
          sts4(ex, U_(cV[0]), U_(cV[1]), U_(cV[2]), U_(cV[3]));
          BAR_ARRIVE(B_T2, 256);
        }
        if (!wg) {
          BAR_SYNC(B_T2, 256);
          DLY(3)
          const float4 u = lds4f(ex);
          stg_b64(mkp(t1.w ^ ((s & 1) * X_RING), HI(xc)), (pk(cV[0] + u.x, cV[1] + u.y) & ~1u) | (((s >> 1) + 1) & 1), pk(cV[2] + u.z, cV[3] + u.w));
        }
      }
      if (s == 63) break;
      if (s == 0) mbar_wait(obar, 0);
      {
        const uint32_t woA = t1.x, woB = woA ^ 32;
#pragma unroll
        for (int i = 0; i < NW0; i++) ldsm4t(wo[i], ((i & 1) ? woB : woA) + (i >= WCH ? wo[(i - WCH + NWP) % NWP][0] & dZ : 0) + (i >> 1) * 2048);
        DLY(2)
        BAR_SYNC(B_S, 416);
        float inv0, inv1;
        uint32_t p[4], pm;
        const uint32_t pa = oA + (SC - OB), one = 0x3f803f80u;
#define P_LOAD ldsm4t(p, pa); asm volatile("ldmatrix.sync.aligned.m8n8.x1.trans.shared.b16 {%0},[%1];" : "=r"(pm) : "r"(pa + 512) : "memory");
        if (s < 62) {
          float acc[16];
          rs_issue(acc, wQ, XB, true);
          mbar_wait(sb + BARS + 24, (s + 1) & 1);
          WG_WAIT(0);
          uint32_t qw[8];
#pragma unroll
          for (int i = 0; i < 8; i++) qw[i] = pk(acc[2 * i], acc[2 * i + 1]);
          if (PKE == 1) park_w(qw, 0, t1.z);
#pragma unroll
          for (int i = NW0; i < NW1; i++) ldsm4t(wo[i], ((i & 1) ? woB : woA) + (i >> 1) * 2048);
          BAR_SYNC(B_V, 512);
          if (PKE == 2) park_w(qw, 0, t1.z);
          P_LOAD
          if (PKE == 0) park_w(qw, 0, t1.z);
        } else {
#pragma unroll
          for (int i = NW0; i < NW1; i++) ldsm4t(wo[i], ((i & 1) ? woB : woA) + (i >> 1) * 2048);
          BAR_SYNC(B_V, 512);
          P_LOAD
        }
#pragma unroll
        for (int i = NW1; i < NWP; i++) ldsm4t(wo[i], ((i & 1) ? woB : woA) + (i >> 1) * 2048);
        {
          float sum[4] = {0, 0, 0, 0}, su2[4] = {0, 0, 0, 0};
          mma16(sum, one, one, one, one, p[0], p[1]);
          mma16(su2, one, one, one, one, p[2], p[3]);
          mma8(sum, one, one, pm);
          inv0 = sum[0] + su2[0]; inv1 = sum[1] + su2[1];
          SCHED_FENCE(57);
        }
        DLY(7)
        BAR_SYNC(B_O, 416);
        float c[2][4] = {{0, 0, 0, 0}, {0, 0, 0, 0}};
        uint32_t o[4][4];
#pragma unroll
        for (int i = 0; i < NOP_; i++) ldsm4t(o[i], oA + i * 512);
        SCHED_FENCE(46);
        asm("rcp.approx.ftz.f32 %0,%0;" : "+f"(inv0));
        asm("rcp.approx.ftz.f32 %0,%0;" : "+f"(inv1));
#pragma unroll
        for (int i = 0; i < 16; i++) {
          mma16(c[i & 1], wo[i][0], wo[i][1], wo[i][2], wo[i][3], o[i >> 2][i & 2], o[i >> 2][(i & 2) + 1]);
          if (i == 1 && NOP_ < 3) ldsm4t(o[2], oA + 1024);
          if (i == 3 && NOP_ < 4) ldsm4t(o[3], oA + 1536);
          if (i + NWP < 16) ldsm4t(wo[(i + NWP) & 15], (((i + NWP) & 1) ? woB : woA) + ((i + NWP) >> 1) * 2048);
        }
        stsm4(t1.y, pk(c[0][0] * inv0, c[0][1] * inv1), pk(c[0][2] * inv0, c[0][3] * inv1), pk(c[1][0] * inv0, c[1][1] * inv1), pk(c[1][2] * inv0, c[1][3] * inv1));
      }
      const uint32_t d = park_ptr();
      BAR_SYNC(B_W, 384);
      DLY(1)
      if (UNC || s < 62) {
        vk_pass(s + 2, d, XB, true, []() {});
        if (!UNC || s < 62) { BAR_ARRIVE(B_P, 384); BAR_ARRIVE(B_X, 320); }
        TS(10);
      } else {
        V_AHEAD
        CONSUME(vP[1][0]);
      }
    }
  } else if (role == 3) {
    asm volatile("setmaxnreg.dec.sync.aligned.u32 24;");
    if (blockIdx.x >= 128) return;
    ROLE_VARS
    const uint32_t L16 = sb + (tid & 31) * 16;
    asm volatile("barrier.cluster.wait.aligned;" ::: "memory");
    CLUSTER_SYNC();
    sts1(sb + PACE + 36, LO(xc) + h * 262144 + X_VM(0));
#define V_LOAD(n) asm volatile("{.reg .pred p; elect.sync _|p, 0xffffffff; @p mbarrier.arrive.expect_tx.shared.b64 _,[%3],8192;\n" \
        "@p cp.async.bulk.tensor.5d.shared::cluster.global.mbarrier::complete_tx::bytes [%0],[%1,{0,0,0,0,%2}],[%3];}" \
        ::"r"(sb + VX0), "l"(&mp.vx), "r"(h * 64 + (V_RING(n) >> 12)), "r"(sb + BARS + 8) : "memory")
    auto vm_stage = [&](int s) {
      const uint32_t tag = ((s >> 1) + 1) & 1;
      const char* xm = mkp(lds1(sb + PACE + 36) + (s & 1) * X_RING + iw * XC + (l16 >> 1), HI(xc));
      uint2 m[4];
      CONSUME(LO(xm));
      BAR_SYNC(B_S2, 256);
      DLY(4)
      int it = 0;
      while (true) {
#pragma unroll
        for (int i = 0; i < 4; i++) m[i] = ldg_b64(xm + (i >> 1) * 2048 + (i & 1) * 256);
        sts4(L16 + VN + iw * 512, m[0].x, m[0].y, m[1].x, m[1].y);
        sts4(L16 + VN + iw * 512 + 2048, m[2].x, m[2].y, m[3].x, m[3].y);
        if (!anybad(m[0].x, m[1].x, m[2].x, m[3].x, tag)) break;
        RP(2);
        if (++it > SPIN_LIMIT) __trap();
      }
      if (s < 63) BAR_ARRIVE(B_V, 512); else BAR_ARRIVE(B_V, 256);
    };
    if (iw == 0) {
      wait_cnt(&g_hcnt, 128);
#pragma unroll 1
      for (int s = 0; s < 63; s++) {
        if (s < 62) for (int it = 0; ldg_rlx1(g_hf + (s & 3)) <= (s >> 2); it++) if (it > SPIN_LIMIT) __trap();
        if (s) BAR_SYNC(B_R, 320); else BAR_SYNC(B_Q, 288);
        if (s < 62) { X_LOAD(s + 2, 0, 0); X_LOAD(s + 2, 1, 0); X_LOAD(s + 2, 0, 1); X_LOAD(s + 2, 1, 1); }
        if (s >= 7) {
          const uint32_t zo = b * 160 + l16;
          if (l16 < 160) CONSUME(exch_b128(xc + AR_OFF + AR_ROW(zo >> 7) * 1024 + (zo & 127) + ((s + 1) & 7) * 128, 0, 0, 0, 0).x);
          __syncwarp();
        }
        if (s < 62) { mbar_wait(sb + BARS + 64, s & 1); mbar_wait(sb + BARS + 72, s & 1); }
        BAR_ARRIVE(B_S, 416);
        vm_stage(s);
        BAR_ARRIVE(B_O, 416);
        BAR_SYNC(B_W, 384);
        DLY(8)
        FENCE_ASYNC_SMEM();
        asm volatile("{.reg .pred p; elect.sync _|p, 0xffffffff; @p cp.reduce.async.bulk.tensor.3d.global.shared::cta.add.bulk_group [%0,{%1,%4,%2}],[%3];}"
                     ::"l"(&mp.ari), "r"((s & 7) * 64), "r"(AR_R(j)), "r"(sb + ARO), "r"(AR_P(j)) : "memory");
        BULK_COMMIT();
        asm volatile("st.relaxed.gpu.global.u32 [%0],%1;" ::"l"(g_tm + (s & 1) * 128 + b), "r"(gtime()) : "memory");
        TS(3);
        BULK_WAIT_READ(0);
      }
      BAR_ARRIVE(B_R, 320);
    } else if (iw == 1) {
      const uint32_t pc = sb + MEM + (lane >> 2) * 640 + (lane & 3) * 144 + (lane & 12), pd = sb + MEM + (lane & 15) * 640 + 576 + (lane & 3) * 16 + (lane & 12);
      uint32_t T = 0, par = 0;
      int est = dA;
#pragma unroll 1
      for (int s = 0; s < 63; s++) {
        if (s) {
          const uint4 tm = ldg_rlx4((const char*)g_tm + ((s + 1) & 1) * 512 + l16);
          const int t0 = tm.x - T, t1 = tm.y - T, t2 = tm.z - T, t3 = tm.w - T;
          const int e = max(dF + (__reduce_add_sync(~0u, (t0 + t1) + (t2 + t3)) >> 7), dV + __reduce_max_sync(~0u, max(max(t0, t1), max(t2, t3))));
          if (s > 1) est += max(min(e >> 2, dP), -dP);
          T += (s == 1 || e > dM ? e : 0) + est - (s == 62 ? L62 : 0);
        }
        vm_stage(s);
        BAR_SYNC(B_W, 384);
        SCHED_FENCE(70);
        const uint32_t tW = gtime();
        if (s == 0) T = tW + 800;
        const uint32_t te = tW + min(max((int)(T - tW), dD), 2000);
        while ((int)(gtime() - te) < 0) {}
        TS(7);
        int it = 0;
        while (true) {
          ar_fetch(sb + MEM, &mp.ari, s & 7, a, sb + BARS + 112);
          mbar_wait(sb + BARS + 112, par);
          par ^= 1;
          const uint32_t n0 = lds1(pc), n1 = lds1(pc + 5120), n2 = lds1(pd);
          if (!__any_sync(~0u, (tagbad(n0, n1, 0x42004200) | (n2 ^ 0x42004200)) != 0)) break;
          RP(0);
          if (++it > SPIN_LIMIT) __trap();
        }
        BAR_ARRIVE(B_R, 320);
        TS(11);
      }
    } else {
      uint32_t src = L16 + PK + (iw & 1) * 2048;
#define qd (L16 + (lane >> 4) * 256 + QT + (iw & 1) * 1024)
#define vd (LO(xc) + h * 262144 + j * XC + (iw & 1) * 2048 + l16)
#define FINISH [&](int n, int m) { \
_Pragma("unroll") \
        for (int i = 1; i >= 0; i--) { \
          const uint32_t p = src + m * 4096 + i * 512; \
          uint4 u = lds4(p); \
          const uint4 w = lds4(p + 1024), y = lds4(p + 12288), z = lds4(p + 13312); \
          u = make_uint4(sum4bf(u.x, w.x, y.x, z.x), sum4bf(u.y, w.y, y.y, z.y), sum4bf(u.z, w.z, y.z, z.z), sum4bf(u.w, w.w, y.w, z.w)); \
          if (m == 2) stg_b128(mkp(vd ^ V_RING(n), HI(xc)) + i * 512, (u.x & ~1u) | V_TAG(n), u.y, u.z, u.w); \
          else stsm4(qd + (n & 1) * 4096 + m * 2048 + i * 256, u.x, u.z, u.y, u.w); \
          SCHED_FENCE(71 + m * 2 + i); \
        } \
      }
#pragma unroll 1
      for (int n = 0; n < 64; n++) {
        src = PIN(src);
        b = __shfl_sync(~0u, lds1(sb + PACE + 24), 0);
        const uint32_t L16 = src - PK - (iw & 1) * 2048;
        auto finish = FINISH;
        if (n < 2) { if (n) BAR_SYNC(B_X, 320); else BAR_SYNC(B_C, 448); }
        mbar_wait(sb + BARS + 16, n & 1);
        if (n > 1) { const uint32_t c = clk(); while (clk() - c < (uint32_t)dQ) {} }
        finish(n, 0);
        __syncwarp();
        if (lane == 0) mbar_arrive_cl(mapa(sb, a ^ 1) + BARS + 24);
        if (n > 1) BAR_SYNC(B_K, 320);
        mbar_wait(sb + BARS + 40, n & 1);
        finish(n, 2);
        if (n > 1) BAR_SYNC(B_X, 320);
        mbar_wait(sb + BARS + 32, n & 1);
        DLY(11)
        finish(n, 1);
        BAR_SYNC(B_T, 64);
        if (lane == 0) {
          if (iw == 2 && n < 63) { mbar_expect(sb + BARS + 16, 4096); mbar_expect(sb + BARS + 32, 4096); mbar_expect(sb + BARS + 40, 4096); }
          mbar_arrive_cl(mapa(sb, a ^ 1) + BARS + 80);
        }
        __syncwarp();
        if (n) {
          vm_stage(n - 1);
          BAR_SYNC(B_W, 384);
          DLY(15)
        } else {
          BAR_SYNC(B_C, 320);
        }
        if (iw == 2) V_LOAD(n);
      }
#undef qd
#undef vd
    }
    { ROLE_REFRESH }
    vm_stage(63);
  } else {
    asm volatile("setmaxnreg.dec.sync.aligned.u32 %0;" ::"n"(RA_));
    if (blockIdx.x >= 128) { if (threadIdx.x == 256) rec_prefetch((const char*)wmod, w1, (const char*)x, wo); return; }
    ROLE_VARS
    uint32_t L16 = __shfl_sync(~0u, sb + (tid & 31) * 16, tid & 31);
    const uint32_t ts = gtime();
    uint2 m0[8];
#pragma unroll
    for (int r = 0; r < 8; r++) m0[r] = *(const uint2*)(mem0 + r * 1024 + a * 512 + (tid - 256) * 4);
    if (wid == 9) {
#pragma unroll 1
      for (int i = b * 80 + (tid & 31); i < b * 80 + 80; i += 32) ((uint4*)(xc + AR_OFF))[AR_ROW(i >> 6) * 64 + (i & 63)] = make_uint4(0, 0, 0, 0);
      if (b == 0) g_fin = 0;
      FENCE_ASYNC();
      __syncwarp();
      if (tid == 288) red_rlx(&g_hcnt);
    }
    if (tid == 256) {
      const int col = h * 128 + bb * 64;
#pragma unroll 1
      for (int c = 0, w = 0; w < 12; c++) {
#pragma unroll 1
        for (; w <= c - (c < WC0 ? 2 : 3); w++) {
          mbar_wait(sb + PACE + (w % 3) * 8, (w / 3) & 1);
          PT(18 + w);
          if (w == 3) asm volatile("mbarrier.arrive.shared.b64 _,[%0];" ::"r"(sb + BARS + 88) : "memory");
        }
        const uint32_t mb = sb + PACE + (c % 3) * 8;
        if (c >= 12 && c < 12 + WPE) tma2d_pf(&mp.wo, j * 256 + (c - 12) * 64, h * 128);
        if (c >= 12) continue;
        mbar_expect(mb, 16384);
        if (c < 8) tma2d(sb + (c >> 2) * XB + (c & 3) * 16384, (c & 4) ? &mp.wk : &mp.wq, col, a * 512 + (c & 3) * 128, mb);
        else
#pragma unroll 1
          for (int i = (c & 1) * 8; i < (c & 1) * 8 + 8; i++) {
            const int w = (c - 8) >> 1;
            tma2d(i < NVR ? sb + MEM + (w * NVR + i) * 2048 : sb + WVS + (w * NVS + i - NVR) * 2048, &mp.wv, col, a * 512 + w * 256 + i * 16, mb);
          }
      }
      asm volatile("mbarrier.arrive.shared.b64 _,[%0];" ::"r"(wbar) : "memory");
      for (int i = 0; i < 3; i++) asm volatile("mbarrier.inval.shared.b64 [%0];" ::"r"(sb + PACE + i * 8) : "memory");
    }
    __syncwarp();
    asm volatile("barrier.cluster.wait.aligned;" ::: "memory");
    CLUSTER_SYNC();
#pragma unroll 4
    for (int i = 0; i < 16; i++) {
      const uint4 v = lds4(L16 + WO + 32768 + iw * 8192 + i * 512);
      sts4(L16 + XB + iw * 8192 + i * 512, v.x, v.y, v.z, v.w);
    }
#pragma unroll
    for (int i = 0; i < 4; i++) {
      const int k = (tid - 256) * 4 + i, m = (k >> 3) & 3, r = k & 7;
#define M0W(r) __byte_perm((i & 2) ? m0[r].y : m0[r].x, (i & 2) ? m0[r + 1].y : m0[r + 1].x, (i & 1) ? 0x7632 : 0x5410)
      sts4(sb + MEM + (k >> 5) * 640 + (r == m ? 512 : m * 128) + r * 16, M0W(0), M0W(2), M0W(4), M0W(6));
    }
#pragma unroll 1
    for (int i = tid - 256; i < 192; i += 128) {
      const uint32_t c = i < 128 ? 0x42004200 : 0x3f803f80;
      sts4(sb + MEM + (i >> 3) * 640 + ((i & 7) < 4 ? (i & 7) * 144 : 512 + (i & 7) * 16), c, c, c, c);
    }
    static_assert(ARO == MEM + 16 * 640, "counters");
    FENCE_ASYNC_SMEM();
    BAR_ARRIVE(B_C, 448);
    if (tid == 256) {
      wait_time(ts + 1);
#pragma unroll 1
      for (int c = WPE; c < 4; c++) tma2d_pf(&mp.wo, j * 256 + c * 64, h * 128);
    }
    __syncwarp();
#define pr (L16 + SC)
    {
      const int lim = j * 8 + iw * 2 - (lane & 7) - (lane & 8) * 2;
      const bool mk = L16 & 256;
      const int rw = lane >> 2;
      sts4(L16 + TA + iw * 512,
           iw != 2 ? L16 + KT + (iw & 1) * 256 + (lane >> 4) * 256 : sb + RK + (L16 & 0x80) * 2 + ((L16 >> 1) & 0x80) + (L16 & 0x70),
           L16 + QT + (lane >> 3) * 384, sb + SC + min(lane >> 3, 2) * 256 + (L16 & 0x70) + iw * 4, L16 + (lane >> 4) * 256 + QT + (iw >> 1) * 1024 + (iw & 1) * 256);
      sts4(L16 + TA + 2048 + iw * 512, mk ? 0u : (lim < 0 ? 0xfc00u : 0u) | (lim < -1 ? 0xfc000000u : 0u),
           mk ? 0xfc00fc00u : (lim < 8 ? 0xfc00u : 0u) | (lim < 7 ? 0xfc000000u : 0u),
           ((h * 2 + (iw >> 1)) * 1024 + (j * 8 + rw) * 8 + (((iw & 1) * 4 + (lane & 3)) ^ rw)) * 16, sb + OT + iw * 512 + (L16 & 0x70) * 4 + ((L16 >> 3) & 0x30));
    }
    {
      const uint32_t xh = LO(xc) + h * 262144, xs = xh + X_SC + iw * 1024 + min(lane, 16 + (lane & 7)) * 8;
      sts4(L16 + TA + 4096 + iw * 512, xh + X_SC + j * 256 + iw * 64 + lpub, xs, dS, iw != 2 ? 0 : U_(SCS));
      sts1(L16 + TA + 12 + iw * 512, xs + X_TOK + j * 4096);
    }
    uint32_t tA = L16 + TA + iw * 512;
#define tw (tA - L16 != TA + 1024)
#define XP_(lo) mkp(lo, HI(xc))
    auto publish = [&](char* d, const uint2& w) { stg_b64(d, w.x, w.y); };
    BAR_SYNC(B_P, 384);
    for (int s = 0; s < 64; s++) {
      asm volatile("" : "+r"(L16), "+r"(tA));
      const uint32_t tag = ((s >> 1) + 1) & 1, ring = (s & 1) * X_RING;
      const uint4 t0 = lds4(tA);
      const uint4 tx = lds4(tA + 4096);
      const uint32_t xo = tx.x ^ ring, xs = tx.y ^ ring;
      const float gm = F_(tx.w);
      const uint32_t qA = t0.y + (ring >> 5);
      uint32_t c0;
      uint2 ts[4];
      uint4 v[4];
      uint32_t af[2][4], qt[4][4];
      {
        const uint32_t aA = t0.x + (tw ? ring >> 5 : 0);
        uint32_t ql[2][4], qr[2][4];
        uint2 pw_;
        float c[4] = {0, 0, 0, 0}, d[4] = {0, 0, 0, 0};
        if (s == PDS) asm volatile("griddepcontrol.launch_dependents;");
#pragma unroll
        for (int i = 0; i < 4; i++) ldsm4t(qt[i], qA + i * 128);
        mbar_wait(sb + BARS + 8, s & 1);
        TS(4);
        BAR_SYNC(B_E, 256);
        DLY(14)
#define PACK(c) make_uint2(pkh(fmaf(c[2], gm, c[0] * SCS), fmaf(c[3], gm, c[1] * SCS), tag), pkh(c[2] * SCS, c[3] * SCS, tag))
        ldsm4t(ql[0], L16 + RQ); ldsm4t(ql[1], L16 + RQ + 1024); ldsm4t(af[0], aA); ldsm4t(af[1], aA + 1024);
        CONSUME(xo);
#define QSUM(t, i) addbf(addbf(ql[t][i], ql[t][i + 2]), addbf(qr[t][i], qr[t][i + 2]))
#define STAIL mma16(c, af[0][0], af[0][1], af[0][2], af[0][3], QSUM(0, 0), QSUM(0, 1)); mma16(d, af[1][0], af[1][1], af[1][2], af[1][3], QSUM(1, 0), QSUM(1, 1));
        if (tw) {
          mbar_wait(sb + BARS, s & 1);
          TS(8);
          ldsm4t(qr[0], L16 + RQ + 512); ldsm4t(qr[1], L16 + RQ + 1536);
          STAIL
          pw_ = make_uint2(pkh(c[0] + d[0], c[1] + d[1], tag), pkh(c[2] + d[2], c[3] + d[3], tag));
        } else {
          uint32_t ar[2][4];
          mbar_wait(sb + BARS, s & 1);
          ldsm4t(qr[0], L16 + RQ + 512); ldsm4t(ar[0], aA + 512); ldsm4t(qr[1], L16 + RQ + 1536); ldsm4t(ar[1], aA + 1536);
#pragma unroll
          for (int i = 0; i < 8; i++) af[i >> 2][i & 3] = addbf(af[i >> 2][i & 3], ar[i >> 2][i & 3]);
          STAIL
          pw_.x = pw_.y = pkh((c[0] + c[2]) + (d[0] + d[2]), (c[1] + c[3]) + (d[1] + d[3]), tag);
        }
        publish(XP_(xo), pw_);
        c0 = clk() + tx.z;
        TS(1);
      }
      uint2 r[4];
      bool vbad;
      uint4 vn[2];
      {
        float e[4][4];
#pragma unroll
        for (int i = 0; i < 4; i++) {
          e[i][0] = e[i][1] = e[i][2] = e[i][3] = 0.f;
          mma16(e[i], af[0][0], af[0][1], af[0][2], af[0][3], qt[i][0], qt[i][1]);
        }
#pragma unroll
        for (int i = 0; i < 4; i++) mma16(e[i], af[1][0], af[1][1], af[1][2], af[1][3], qt[i][2], qt[i][3]);
        SCHED_FENCE(55);
        if (s < 63) BAR_ARRIVE(B_S, 416);
        SCHED_FENCE(58);
        v[0] = lds4(tA + (VX0 - TA)); v[1] = lds4(tA + (VX0 - TA) + 2048); v[2] = lds4(tA + (VX1 - TA)); v[3] = lds4(tA + (VX1 - TA) + 2048);
#pragma unroll
        for (int i = 0; i < 4; i++) ts[i] = PACK(e[i]);
        vbad = anybad(v[0].x, v[1].x, v[2].x, v[3].x, V_TAG(s));
        while ((int)(clk() - c0) < 0) {}
        TS(5);
#pragma unroll
        for (int u = 0; u < 4; u++) r[u] = ldg_b64(XP_(xs) + u * 256);
        BAR_ARRIVE(B_S2, 256);
      }
      SCHED_FENCE(56);
      uint32_t kk;
      float4 e = softmax2<false>(r, 0, 0, kk);
      if (__builtin_expect(anybad(r[0].x, r[0].y, r[1].x, r[1].y, r[2].x, r[2].y, r[3].x, r[3].y, tag ^ (kk & dZ)), 0)) {
        int it = 0;
        if (s > 8) sts1(tA + 4096 + 8, min(lds1(tA + 4096 + 8) + dX, 500));
        do {
          RP(1);
          if (++it > SPIN_LIMIT) __trap();
#pragma unroll
          for (int u = 0; u < 4; u++) r[u] = ldg_b64(XP_(xs) + u * 256);
        } while (BADS(r));
        e = softmax2<false>(r, 0, 0, kk);
      }
      DLY(5)
      sts1(t0.z, pk(e.x, e.y)); sts1(t0.z + 128, pk(e.z, e.w));
#pragma unroll
      for (int i = 0; i < 4; i++) publish(XP_(xo) + X_TOK + i * 4096, ts[i]);
      TS(6);
      if (s < 63) BAR_SYNC(B_V, 512); else BAR_SYNC(B_V, 256);
      uint32_t O[4];
      {
        uint32_t p[4], pm;
        ldsm4t(p, pr);
        asm volatile("ldmatrix.sync.aligned.m8n8.x1.trans.shared.b16 {%0},[%1];" : "=r"(pm) : "r"(pr + 512) : "memory");
        vn[0] = lds4(tA + (VN - TA)); vn[1] = lds4(tA + (VN - TA) + 2048);
        pv_mem(p, pm, v, vn, O);
        if (__builtin_expect(vbad, 0)) {
          int it = 0;
          const uint32_t xv = LO(xc) + (lds1(sb + PACE + 24) >> 2) * 262144 + ((tA - L16 - TA) >> 9) * XC;
          do {
            RP(2);
            if (++it > SPIN_LIMIT) __trap();
#pragma unroll
            for (int u = 0; u < 4; u++) v[u] = ldg_b128(XP_((xv + l16) ^ V_RING(s)) + X_VX(u));
          } while (anybad(v[0].x, v[1].x, v[2].x, v[3].x, V_TAG(s)));
          pv_mem(p, pm, v, vn, O);
        }
      }
      DLY(6)
      stsm4(tA + (OB - TA), O[0], O[1], O[2], O[3]);
      if (s < 63) BAR_ARRIVE(B_O, 416);
      TS(2);
      c0 = clk() + dG;
      SCHED_FENCE(60);
      if (tA == sb + TA) mbar_expect(sb + BARS, 2048);
      const uint32_t vs[4] = {addbf(vn[0].x, vn[0].z), addbf(vn[0].y, vn[0].w), addbf(vn[1].x, vn[1].z), addbf(vn[1].y, vn[1].w)};
      {
        const char* xt = XP_(lds1(tA + 12) ^ ring);
        const uint2 t1 = lds2u(tA + 2048);
        const uint32_t pw = lds1(tA + 8);
        uint2 rt[4];
        CONSUME(LO(xt) ^ t1.x ^ pw);
        while ((int)(clk() - c0) < 0) {}
        int it = 0;
        do {
          if (++it > SPIN_LIMIT) __trap();
#pragma unroll
          for (int u = 0; u < 4; u++) rt[u] = ldg_b64(xt + u * 256);
        } while (BADS(rt));
        uint32_t kt;
        const float4 et = softmax2<true>(rt, t1.x, t1.y, kt);
        sts1(pw + 1024, pk(et.x, et.y)); sts1(pw + 1024 + 128, pk(et.z, et.w));
      }
      s = PIN(s);
      BAR_SYNC(B_SC, 128);
      {
        uint32_t Ot[4], p[4], pm;
        const uint2 t2 = lds2u(tA + 2048 + 8);
        ldsm4t(p, pr + 1024);
        asm volatile("ldmatrix.sync.aligned.m8n8.x1.trans.shared.b16 {%0},[%1];" : "=r"(pm) : "r"(pr + 1024 + 512) : "memory");
        char* od = (char*)g_O + ((s >> 2) * 1048576 + (s & 3) * 4096) + t2.x;
        CONSUME(LO(od) ^ HI(od) ^ pm ^ p[3]);
        TS(9);
        if (s < 62) BAR_SYNC(B_P, 384);
        DLY(13)
        pv_tok(p, pm, v, vs, Ot);
        asm volatile("stmatrix.sync.aligned.m8n8.x4.trans.shared.b16 [%0],{%1,%2,%3,%4};" ::"r"(t2.y), "r"(Ot[0]), "r"(Ot[1]), "r"(Ot[2]), "r"(Ot[3]) : "memory");
        __syncwarp();
        *(uint4*)od = lds4(tA + (OT - TA));
      }
    }
    FENCE_ASYNC();
    BAR_SYNC(B_SC, 128);
    if (tA == sb + TA) red_rlx(&g_fin);
  }
  __syncwarp();
  CLUSTER_SYNC();
  PH(5); RS(2);
}
#undef wg
#undef iw
#undef h
#undef j
#undef a
#undef bb
#undef oi
#undef owner
#undef ownv
#undef pr
#undef PIN
#undef XP_
#undef tw
#undef lane
#undef l16
#undef lrow
#undef lpub

namespace ffn {
constexpr uint32_t BR = 98304;
constexpr uint32_t STG = 196608;
constexpr uint32_t PRM = 229376;
constexpr uint32_t BARS = PRM + 2816;
constexpr uint32_t SMEM = BARS + 18 * 8;
}
#define Y_TILE(rb, kt) (((ALIAS & 1) ? g_h : g_h2) + ((rb) * 16 + (kt)) * 1024)
#define U_TILE(rb, kt) ((ALIAS & 2) ? g_O + ((rb) * 64 + (kt)) * 1024 : g_U + ((rb) * 56 + (kt)) * 1024)
struct FfnMaps { CUtensorMap wo, w1a, w1b, w2, x, out; };

template <int N>
__device__ __forceinline__ void wg_ss(float* d, uint64_t a, uint64_t b, int sd) {
  if (N == 128) wgmma_ss_n128(d, a, b, sd);
  if (N == 192) wgmma_ss_n192(d, a, b, sd);
}
template <int N>
__device__ __forceinline__ void acc_fence(float* d) {
#pragma unroll
  for (int i = 0; i < N; i++) asm volatile("" : "+f"(d[i])::"memory");
}
#define UNPK8(d, v) do { (d)[0] = blo(v.x); (d)[1] = bhi(v.x); (d)[2] = blo(v.y); (d)[3] = bhi(v.y); (d)[4] = blo(v.z); (d)[5] = bhi(v.z); (d)[6] = blo(v.w); (d)[7] = bhi(v.w); } while (0)
struct FfnPipe {
  uint32_t full, emp, ph, aoff;
  int st, sB, prev;
  bool leader;
  template <int N, int S = N>
  __device__ __forceinline__ void issue(float* acc, bool first, uint32_t a = 0) {
    mbar_wait(full + st * 8, ph);
    const uint64_t da = mkdesc((a ? a : 1024 + st * 16384) + aoff, 16, 1024), db = mkdesc(1024 + ffn::BR + sB * (S * 128), 8192, 1024);
    WG_FENCE();
#pragma unroll
    for (int j = 0; j < 4; j++) wg_ss<N>(acc, da + j * 2, db + j * 128, j || !first);
    WG_COMMIT();
    if (++sB == 768 / S) sB = 0;
  }
  __device__ __forceinline__ void release() { if (leader) mbar_arrive(emp + prev * 8); }
  __device__ __forceinline__ void next() { prev = st; if (++st == 6) { st = 0; ph ^= 1; } }
  __device__ __forceinline__ void retire() { WG_WAIT(1); release(); next(); }
};
__device__ __forceinline__ float gelu_h(float hx) {
  float u = hx * fmaf(hx * hx, 8.f * 0.0356774081f, 2.f * 0.7978845608f), t;
  asm("tanh.approx.f32 %0,%1;" : "=f"(t) : "f"(u));
  return fmaf(hx, t, hx);
}
struct FfnEpi {
  uint32_t st2, cc, flip, staged, l0;
  uint2 c;
  float n0, n1, s0, s1;
  __device__ __forceinline__ void flush(uint32_t r) {
    __syncwarp();
    asm volatile("{.reg .pred p; setp.ne.u32 p,%1,0; @p mbarrier.arrive.shared.b64 _,[%0];}" ::"r"(staged + (flip >> 11)), "r"(l0 & r) : "memory");
    flip ^= r << 14;
  }
  __device__ __forceinline__ void half(const float* d, int J, int r) {
#define PRE(i, n, c1, c2) gelu_h(fmaf(r ? d[4 + i] : d[i], i < 2 ? s0 : s1, fmaf(n, c1, c2)))
    asm volatile("stmatrix.sync.aligned.m8n8.x2.shared.b16 [%0],{%1,%2};" ::"r"((st2 ^ ((J & 3) * 32 + r * 16)) + flip),
                 "r"(pk(PRE(0, n0, blo(c.x), blo(c.y)), PRE(1, n0, bhi(c.x), bhi(c.y)))), "r"(pk(PRE(2, n1, blo(c.x), blo(c.y)), PRE(3, n1, bhi(c.x), bhi(c.y)))) : "memory");
#undef PRE
    if ((J & 3) == 3) flush(r);
    cc += r ? 56 : 8;
    c = lds2u(cc);
  }
};

__global__ void __launch_bounds__(384, 1)
k_ffn(const __grid_constant__ FfnMaps mp, const bf16* __restrict__ b2) {
  using namespace ffn;
  extern __shared__ __align__(1024) char smem[];
  const uint32_t sb = (uint32_t)__cvta_generic_to_shared(smem);
  if (sb != 1024) __trap();
  const int tid = threadIdx.x, lane = tid & 31, wg = __shfl_sync(~0u, tid >> 7, 0);
  const uint32_t full = sb + BARS, emp = full + 48, xbar = full + 96, staged = full + 104, tile = full + 136;
  uint32_t fin = 0;
  if (tid >= 288 && tid < 320) fin = ld_acq(&g_fin);
  if (tid < 32) {
    unsigned sm, v = 0;
    asm("mov.u32 %0,%%smid;" : "=r"(sm));
    if (tid == 0) {
      v = atomicExch(&g_slot[sm & 255], 0);
      for (int i = 0; i < 6; i++) { mbar_init(full + i * 8, 1); mbar_init(emp + i * 8, 2); }
      mbar_init(xbar, 2);
      for (int i = 0; i < 2; i++) { mbar_init(staged + i * 8, 8); mbar_init(staged + 16 + i * 8, 1); }
      FENCE_ASYNC_SMEM();
    }
    v = __shfl_sync(~0u, v, 0);
    if (!v) {
      wait_cnt(&g_fin, 128);
      for (int it = 0; !v; it++) {
        const uint4 a = ldg_rlx4(g_slot + tid * 8), b = ldg_rlx4(g_slot + tid * 8 + 4);
        const uint32_t open = __ballot_sync(~0u, a.x | a.y | a.z | a.w | b.x | b.y | b.z | b.w);
        if (!open) break;
        if (it < 16) { __nanosleep(500); continue; }
        if (tid == __ffs(open) - 1) v = atomicExch(&g_slot[tid * 8 + (a.x ? 0 : a.y ? 1 : a.z ? 2 : a.w ? 3 : b.x ? 4 : b.y ? 5 : b.z ? 6 : 7)], 0);
        v = __shfl_sync(~0u, v, __ffs(open) - 1);
      }
    }
    if (tid == 0) sts1(tile, v);
  }
  if (tid == 256) asm volatile("prefetch.tensormap [%0];" ::"l"(&mp.wo) : "memory");
  __syncthreads();
  const int bid = __shfl_sync(~0u, lds1(tile), 0) - 1;
  if (bid < 0) return;
  PH(6);
  FT(1);
  const int rb = bid >> 3, nb = bid & 7;
  unsigned* cnt = g_cnt + rb * 128;
  if (wg == 2) {
    asm volatile("setmaxnreg.dec.sync.aligned.u32 " FRP ";");
    const int pw = __shfl_sync(~0u, (tid >> 5) & 3, 0);
    uint32_t ws = emp, wp = 1, fs = full;
    auto wait_free = [&]() { mbar_wait_q(ws, wp); ws += 8; if (ws == emp + 48) { ws = emp; wp ^= 1; } };
    auto step = [&]() { fs += 8; if (fs == full + 48) fs = full; };
#define K3(c) ((0x65230 >> (c) * 4) & 7)
#define KC(k) ((k) < 2 ? nb * 2 + (k) : (k) < 9 ? ((k) - 2 + ((k) - 2 >= nb)) * 2 : ((k) - 9 + ((k) - 9 >= nb)) * 2 + 1)
    if (pw == 0) {
      uint32_t d = sb + BR + 32768;
      auto put = [&](const CUtensorMap* m, int k, int c) {
        e_expect_tma3d(d, m, k * 64, c, fs, 32768);
        step();
        d += 16384;
        if (d == sb + STG) d = sb + BR;
      };
      int n = 0;
      auto stage_free = [&]() { if (!(n & 7) && n < 56) mbar_wait_q(staged + 16 + (n & 8), (n >> 4) & 1); n++; };
      auto align = [&]() {
        if (ALN && !((n - 1) & 7) && ((ALN >> ((n - 1) >> 3)) & 1)) {
          unsigned* c = g_cnt + 64 + ((n - 1) >> 3);
          if (lane == 0) red_rlx(c);
          for (int it = 0; ldg_rlx1(c) < 128 && it < 64; it++) {}
        }
      };
      FTP(3);
#pragma unroll 1
      for (int k = 0; k < 66; k++) { wait_free(); if (k < 64) put(&mp.wo, k, nb * 2); }
#pragma unroll 1
      for (int k = 0; k < 18; k++) {
        const int u = k >= 2 ? k - 2 : k, kt = KC(u);
        const bool ea = (k & ~1) == 2;
        wait_free();
        e_expect_tma3d(sb + BR + (k & 3) * 24576, ea ? &mp.w1a : &mp.w1b, kt * 64, nb * 7 + (ea ? 3 : 0), fs, ea ? 16384 : k < 2 ? 24576 : 40960);
        step();
      }
      d = sb + BR + 49152;
#pragma unroll 1
      for (int k = 2; k < 32; k++) {
        const int kt = k < 16 ? KC(k) : k & 15;
        stage_free();
        if (k == 2 || k == 9) n++;
        if (k != 7 && k != 8) wait_free();
        align();
        put(&mp.w1a, kt, nb * 7 + 3 + (k >> 4) * 2);
      }
#pragma unroll 1
      for (int c = 0; c < 5; c++)
#pragma unroll 1
        for (int k = K3(c), i = 0; k < 56; k += c < 2 && (i ^= 1) ? 1 : c < 2 ? 6 : 7) { stage_free(); wait_free(); align(); put(&mp.w2, k, nb * 2); }
    } else if (pw == 1) {
      FTP(5);
      if (fin < 128) wait_cnt(&g_fin, 128);
      FTP(6);
      uint32_t d = sb;
      auto put = [&](const uint4* A, bool ld) {
        wait_free();
        if (ld) e_bulk_ld(d, A, 16384, fs);
        step();
        d += 16384;
        if (d == sb + BR) d = sb;
      };
      const uint4* A = g_O + rb * 65536;
#pragma unroll 1
      for (int k = 0; k < 68; k++) put(A + k * 1024, k < 64);
      A = Y_TILE(rb, 0);
      uint32_t ready = 0;
#pragma unroll 1
      for (int k = 2; k < 48; k++) {
        if (k == 16) k = 18;
        const int kt = k < 32 ? KC(k & 15) : k & 15;
        for (int it = 0; !(ready >> ((kt >> 1) + (kt & 1) * 8) & 1); it++) {
          ready = __ballot_sync(~0u, ldg_rlx1(cnt + (lane & 7)) & ((lane & 8) ? 1 : 0x10000));
          if (it > SPIN_LIMIT) __trap();
        }
        if (k == 2) FTP(75);
        put(A + kt * 1024, true);
      }
      A = U_TILE(rb, 0);
#pragma unroll 1
      for (int c = 0; c < 5; c++) {
        for (int it = 0; ldg_rlx1(cnt + 32 + c) < 8; it++) if (it > SPIN_LIMIT) __trap();
#pragma unroll 1
        for (int k = K3(c), i = 0; k < 56; k += c < 2 && (i ^= 1) ? 1 : c < 2 ? 6 : 7) put(A + k * 1024, true);
      }
    } else if (pw == 2) {
#pragma unroll 1
      for (int i = 0; i < XDL; i++) mbar_wait_q(emp, i & 1);
      if (lane == 0) {
        mbar_expect(xbar, 32768);
#pragma unroll 1
        for (int i = 0; i < 256 / XR; i++) {
          tma2d(sb + STG + i * (XR * 128), &mp.x, nb * 128 + (i * XR >> 7) * 64, rb * 128 + ((i * XR) & 127), xbar);
          const uint32_t c = clk();
          while (clk() - c < XTD) {}
        }
      }
      asm volatile("griddepcontrol.wait;" ::: "memory");
      if (lane < 16) g_modp[bid * 16 + lane] = make_uint4(0, 0, 0, 0);
      if (lane >= 16 && bid == 0) { g_hcnt = 0; g_mcnt = 0; g_hf[lane & 3] = 0; }
      if (lane == 0) {
#pragma unroll 1
        for (int g = 1; g < 9; g++) {
          if (g == 1) mbar_wait(staged + 8, 0); else { mbar_wait_q(staged + (g & 1) * 8, (g >> 1) & 1); FENCE_ASYNC_SMEM(); }
          uint4* dst = g == 1 ? Y_TILE(rb, nb * 2 + 1) : U_TILE(rb, nb * 7 + ((0x652431000ull >> g * 4) & 7));
#pragma unroll 1
          for (int i = 0; i < (g > 1 ? 4 : 1); i++) {
            bulk_st(dst + i * 256, sb + STG + (g & 1) * 16384 + i * 4096, g > 1 ? 4096 : 16384);
            const uint32_t c = clk();
            while (g > 1 && clk() - c < USD) {}
          }
          BULK_COMMIT();
          if (g != 2 && g != 4) { BULK_WAIT(0); red_rlx(g == 1 ? cnt + nb : cnt + 32 + (g < 6 ? g >> 2 : g - 4)); }
          BULK_WAIT_READ(0);
          mbar_arrive(staged + 16 + (g & 1) * 8);
        }
      }
    } else {
      const uint32_t prm = sb + PRM, pp = prm + (lane >> 3) * 64 + (lane & 1) * 32 + (lane & 6) * 2;
      const uint2 v2 = ((const uint2*)(b2 + nb * 128))[lane];
      sts1(pp + 768, v2.x); sts1(pp + 784, v2.y);
      asm volatile("griddepcontrol.wait;" ::: "memory");
      const float4* md = (const float4*)(g_mod + nb * 128) + lane;
      { const float4 ga = md[512]; sts1(pp, pk(ga.x, ga.y)); sts1(pp + 16, pk(ga.z, ga.w)); }
      { const float4 cb = md[1024]; sts1(pp + 256, pk(1.f + cb.x, 1.f + cb.y)); sts1(pp + 272, pk(1.f + cb.z, 1.f + cb.w)); }
      { const float4 gb = md[1280]; sts1(pp + 512, pk(gb.x, gb.y)); sts1(pp + 528, pk(gb.z, gb.w)); }
#pragma unroll 1
      for (int i = lane; i < 112; i += 32) { const uint4 c = g_cc[nb * 112 + i]; sts4(prm + 1024 + i * 16, c.x, c.y, c.z, c.w); }
      __syncwarp();
      if (lane == 0) {
        mbar_arrive(xbar);
        mbar_wait(staged, 0);
        bulk_st(Y_TILE(rb, nb * 2), sb + STG, 16384);
        BULK_COMMIT(); BULK_WAIT(0);
        asm volatile("red.relaxed.gpu.global.add.u32 [%0],0x10000;" ::"l"(cnt + nb) : "memory");
        mbar_arrive(staged + 16);
      }
      __syncwarp();
      mbar_wait_q(staged + 24, 0);
      mbar_wait_q(emp + 8, 1);
#pragma unroll 1
      for (int i = 0; i < 4; i++) {
        const uint4* sp = g_stat + (rb * 128 + i * 32 + lane) * 4;
        uint4 v[4];
        for (int it = 0;; it++) {
          uint32_t m = 0;
#pragma unroll
          for (int u = 0; u < 4; u++) { v[u] = ldg_rlx4(sp + u); m = max(max(m, max(v[u].x, v[u].y)), max(v[u].z, v[u].w)); }
          if (!__any_sync(~0u, m == ~0u)) break;
          if (it > SPIN_LIMIT) __trap();
        }
        float m = 0, q = 0;
#pragma unroll
        for (int u = 0; u < 4; u++) { m += F_(v[u].x) + F_(v[u].z); q += F_(v[u].y) + F_(v[u].w); }
        m *= 1.f / 1024;
        const float r = 0.5f * rsqrtf(fmaxf(q * (1.f / 1024) - m * m, 0.f) + 1e-5f);
        sts2(sb + STG + 16384 + (i * 32 + lane) * 8, U_(r), U_(-m * r));
      }
      __syncwarp();
      if (lane < 2) mbar_arrive(xbar);
    }
  } else {
    asm volatile("setmaxnreg.inc.sync.aligned.u32 " FRC ";");
    const int w = (tid >> 5) & 3, q = lane & 3;
    const uint32_t prm = sb + PRM + q * 16;
    const int row0 = wg * 64 + w * 16;
    FfnPipe p;
    p.full = full; p.emp = emp; p.ph = 0; p.aoff = wg * 8192; p.st = 0; p.sB = 2; p.prev = 0; p.leader = (tid & 127) == 0;
    FfnEpi e;
    const uint32_t stg = sb + STG + row0 * 128;
    e.st2 = stg + (lane & 15) * 128 + ((lane & 7) << 4);
    e.cc = sb + PRM + 1024 + q * 16; e.flip = 0; e.staged = staged; e.l0 = lane == 0;
    const uint32_t stw = e.st2 ^ (lane & 16);
    uint32_t x1[32];
    uint4* sp = g_stat + (rb * 128 + row0 + (lane >> 2)) * 4;
    float old[96], r0_, r1_;
    {
      float acc[64];
      p.issue<128>(acc, true); FT(8); p.next();
#pragma unroll 1
      for (int k = 1; k < 64; k++) { p.issue<128>(acc, false); FT(8 + k); p.retire(); }
      float xf[64], gf[32];
      uint32_t cb[16];
      mbar_wait(xbar, 0);
#pragma unroll
      for (int j = 0; j < 8; j++) {
        uint32_t xv[4];
        ldsm4(xv, (stw ^ ((j & 3) * 32)) + (j >> 2) * 16384);
#pragma unroll
        for (int i = 0; i < 4; i++) { xf[j * 8 + i * 2] = blo(xv[i]); xf[j * 8 + i * 2 + 1] = bhi(xv[i]); }
      }
#pragma unroll
      for (int i = 0; i < 4; i++) {
        const uint4 g = lds4(prm + i * 64), c = lds4(prm + 256 + i * 64);
        UNPK8(gf + i * 8, g);
        cb[i * 4] = c.x; cb[i * 4 + 1] = c.y; cb[i * 4 + 2] = c.z; cb[i * 4 + 3] = c.w;
      }
      acc_fence<64>(xf); acc_fence<32>(gf);
      WG_WAIT(0);
      p.release();
      acc_fence<64>(acc);
      PH(7); FT(72);
#pragma unroll
      for (int j = 0; j < 8; j++) {
        uint32_t* o = x1 + j * 4;
#pragma unroll
        for (int i = 0; i < 4; i++)
          o[i] = pk(fmaf(acc[j * 8 + i * 2], gf[j * 4 + (i & 2)], xf[j * 8 + i * 2]), fmaf(acc[j * 8 + i * 2 + 1], gf[j * 4 + (i & 2) + 1], xf[j * 8 + i * 2 + 1]));
        stsm4((stw ^ ((j & 3) * 32)) + (j >> 2) * 16384, mulbf(o[0], cb[j * 2]), mulbf(o[1], cb[j * 2]), mulbf(o[2], cb[j * 2 + 1]), mulbf(o[3], cb[j * 2 + 1]));
        if ((j & 3) == 3) { FENCE_ASYNC_SMEM(); e.flush(1); }
      }
      if (wg) BAR_SYNC(2, 128); else BAR_SYNC(3, 128);
    }
    PH(8); FT(73);
    float acc[64];
    {
      float* accC = old;
      p.sB = 0;
      p.issue<192>(accC, true, 1024 + STG); FT(80); p.next();
      p.issue<192>(accC, false, 1024 + STG + 16384); FT(81);
      FT(78);
      float s0 = 0, s1 = 0, q0 = 0, q1 = 0;
#define X1_FENCE _Pragma("unroll") for (int j = 0; j < 32; j++) asm volatile("" : "+r"(x1[j]));
      X1_FENCE
#pragma unroll
      for (int j = 0; j < 16; j++) {
        const float a = blo(x1[j * 2]), b = bhi(x1[j * 2]), c = blo(x1[j * 2 + 1]), d = bhi(x1[j * 2 + 1]);
        s0 += a + b; s1 += c + d; q0 = fmaf(a, a, fmaf(b, b, q0)); q1 = fmaf(c, c, fmaf(d, d, q1));
      }
#pragma unroll
      for (int o = 1; o < 4; o *= 2) { s0 += __shfl_xor_sync(~0u, s0, o); s1 += __shfl_xor_sync(~0u, s1, o); q0 += __shfl_xor_sync(~0u, q0, o); q1 += __shfl_xor_sync(~0u, q1, o); }
      if (q < 2) {
        uint32_t m = __float_as_uint(q ? s1 : s0), v = __float_as_uint(q ? q1 : q0);
        if (m == ~0u) m = 0x7fffffffu;
        if (v == ~0u) v = 0x7fffffffu;
        stg_rlx2((uint2*)(sp + q * 32) + nb, m, v);
      }
      X1_FENCE
      p.retire();
#pragma unroll 1
      for (int k = 0; k < 2; k++) { p.issue<128, 192>(acc, !k, 1024 + STG + k * 16384); p.retire(); }
#pragma unroll 1
      for (int k = 2; k < 15; k++) { p.issue<192>(accC, false); FT(80 + k); p.retire(); }
      p.issue<192>(accC, false); FT(95);
      mbar_wait(xbar, 1);
      const float2 u0 = lds2f(sb + STG + 16384 + (row0 + (lane >> 2)) * 8), u1 = lds2f(sb + STG + 16384 + (row0 + (lane >> 2)) * 8 + 64);
      r0_ = u0.x; e.n0 = u0.y; r1_ = u1.x; e.n1 = u1.y;
      e.c = lds2u(e.cc);
      p.retire();
      e.s0 = r0_; e.s1 = r1_;
      p.sB = 3;
    }
    PH(9);
    {
      auto pair = [&](int J, bool first, bool one, int fo) {
#pragma unroll 1
        for (int r = 0; r < 2; r++) {
          if (!(one && r)) { p.issue<128>(acc, first && !r); FT(fo + r); p.retire(); }
          acc_fence<8>(old + J * 8);
          e.half(old + J * 8, J, r);
        }
      };
#pragma unroll 1
      for (int i = 0; i < 3; i++) {
        if (i == 2) {
          e.s0 = r0_; e.s1 = r1_;
#pragma unroll
          for (int J = 8; J < 12; J++) pair(J, J == 8, false, 128 + (J - 8) * 2);
          e.cc += 512; e.c = lds2u(e.cc);
          e.s0 = e.s1 = 1.f;
        }
#pragma unroll
        for (int J = 0; J < 8; J++) pair(J, J == 0 && i == 1, !(J & 3) && !i, 96 + i * 16 + (i >> 1) * 8 + J * 2);
        if (i == 2) break;
        e.cc += i ? -768 : 256; e.c = lds2u(e.cc);
        WG_WAIT(0);
        acc_fence<64>(acc);
#pragma unroll
        for (int k = 0; k < 64; k++) old[k] = acc[k] * ((k & 2) ? r1_ : r0_);
        acc_fence<64>(old);
        e.s0 = e.s1 = 1.f;
        PH(10 + i);
      }
#pragma unroll 1
      for (int k = 24; k < 56; k++) {
        if (SKW && k == 56 - SKW && wg) BAR_SYNC(4, 256);
        p.issue<128>(acc, false); FT(128 + k);
        if (SKW && k == 55 && !wg) BAR_ARRIVE(4, 256);
        p.retire();
      }
      float xf[64], gf[32];
#pragma unroll
      for (int i = 0; i < 4; i++) {
        const uint4 g = lds4(prm + 512 + i * 64), h = lds4(prm + 768 + i * 64);
        float hf[8];
        UNPK8(gf + i * 8, g); UNPK8(hf, h);
#pragma unroll
        for (int u = 0; u < 8; u++) {
          const int c = (u >> 2) * 4 + (u & 2);
          xf[i * 16 + u * 2] = fmaf(gf[i * 8 + c], hf[c], blo(x1[i * 8 + u])); xf[i * 16 + u * 2 + 1] = fmaf(gf[i * 8 + c + 1], hf[c + 1], bhi(x1[i * 8 + u]));
        }
      }
      acc_fence<64>(xf); acc_fence<32>(gf);
      mbar_wait(staged + 24, 1);
      mbar_wait(staged + 16, 0);
      WG_WAIT(0);
      acc_fence<64>(acc);
      PH(13); FT(184);
#pragma unroll
      for (int j = 0; j < 8; j++) {
        uint32_t o[4];
#pragma unroll
        for (int i = 0; i < 4; i++)
          o[i] = pk(fmaf(acc[j * 8 + i * 2], gf[j * 4 + (i & 2)], xf[j * 8 + i * 2]), fmaf(acc[j * 8 + i * 2 + 1], gf[j * 4 + (i & 2) + 1], xf[j * 8 + i * 2 + 1]));
        stsm4((stw ^ ((j & 3) * 32)) + (j >> 2) * 16384, o[0], o[1], o[2], o[3]);
        if ((j & 3) == 3) {
          FENCE_ASYNC_SMEM();
          __syncwarp();
          if (lane == 0) { tma2d_st(&mp.out, nb * 128 + (j >> 2) * 64, rb * 128 + row0, stg + (j >> 2) * 16384); BULK_COMMIT(); }
        }
      }
      if (lane == 0) BULK_WAIT_READ(0);
      __syncwarp();
    }
  }
  PH(14); FT(185);
}

typedef CUresult (*EncFn)(CUtensorMap*, CUtensorMapDataType, cuuint32_t, void*, const cuuint64_t*, const cuuint64_t*, const cuuint32_t*,
                          const cuuint32_t*, CUtensorMapInterleave, CUtensorMapSwizzle, CUtensorMapL2promotion, CUtensorMapFloatOOBfill);
static void map2d(EncFn enc, CUtensorMap* m, const void* p, int rows, int cols, int boxRows) {
  cuuint64_t d[2] = {(cuuint64_t)cols, (cuuint64_t)rows}, s[1] = {(cuuint64_t)cols * 2};
  cuuint32_t b[2] = {64, (cuuint32_t)boxRows}, e[2] = {1, 1};
  enc(m, CU_TENSOR_MAP_DATA_TYPE_BFLOAT16, 2, (void*)p, d, s, b, e, CU_TENSOR_MAP_INTERLEAVE_NONE, CU_TENSOR_MAP_SWIZZLE_128B,
      CU_TENSOR_MAP_L2_PROMOTION_L2_128B, CU_TENSOR_MAP_FLOAT_OOB_FILL_NONE);
}
static void map3d(EncFn enc, CUtensorMap* m, const void* p, int rows, int cols, int nch) {
  cuuint64_t d[3] = {64, (cuuint64_t)rows, (cuuint64_t)(cols / 64)}, s[2] = {(cuuint64_t)cols * 2, 128};
  cuuint32_t b[3] = {64, 64, (cuuint32_t)nch}, e[3] = {1, 1, 1};
  enc(m, CU_TENSOR_MAP_DATA_TYPE_BFLOAT16, 3, (void*)p, d, s, b, e, CU_TENSOR_MAP_INTERLEAVE_NONE, CU_TENSOR_MAP_SWIZZLE_128B,
      CU_TENSOR_MAP_L2_PROMOTION_L2_128B, CU_TENSOR_MAP_FLOAT_OOB_FILL_NONE);
}

extern "C" void kernel_launch(void* const* d_in, const int* in_sizes, int n_in, void* d_out, int out_size) {
  const bf16* x = (const bf16*)d_in[0];
  const bf16* mem0 = (const bf16*)d_in[1];
  void* fn = nullptr;
  cudaDriverEntryPointQueryResult qr;
  cudaGetDriverEntryPoint("cuTensorMapEncodeTiled", &fn, cudaEnableDefault, &qr);
  EncFn enc = (EncFn)fn;
  FfnMaps fm = {};
  map3d(enc, &fm.wo, d_in[5], 4096, 1024, 2);
  map3d(enc, &fm.w1a, d_in[8], 1024, 3584, 2);
  map3d(enc, &fm.w1b, d_in[8], 1024, 3584, 3);
  map3d(enc, &fm.w2, d_in[10], 3584, 1024, 2);
  map2d(enc, &fm.x, x, 2048, 1024, XR);
  map2d(enc, &fm.out, d_out, 2048, 1024, 16);
  RecMaps rm = {};
  map2d(enc, &rm.wq, d_in[2], 1024, 4096, 128);
  map2d(enc, &rm.wk, d_in[3], 1024, 4096, 128);
  map2d(enc, &rm.wv, d_in[4], 1024, 4096, 16);
  map2d(enc, &rm.wo, d_in[5], 4096, 1024, 128);
  char* xc = nullptr;
  cudaGetSymbolAddress((void**)&xc, g_xc);
  xc += (0 - (uintptr_t)xc) & 0x1FFFFF;
  {
    cuuint64_t d[3] = {512, 6, 128}, sd[2] = {131072, 1024};
    cuuint32_t bi[3] = {64, 5, 8}, e[3] = {1, 1, 1};
    enc(&rm.ari, CU_TENSOR_MAP_DATA_TYPE_BFLOAT16, 3, xc + AR_OFF, d, sd, bi, e, CU_TENSOR_MAP_INTERLEAVE_NONE, CU_TENSOR_MAP_SWIZZLE_NONE,
        CU_TENSOR_MAP_L2_PROMOTION_NONE, CU_TENSOR_MAP_FLOAT_OOB_FILL_NONE);
  }
  {
    cuuint64_t d[5] = {256, 4, 2, 2, 2048}, sd[4] = {rec::XC, X_VX(1), X_VX(2), 4096};
    cuuint32_t bi[5] = {256, 4, 2, 2, 1}, e[5] = {1, 1, 1, 1, 1};
    enc(&rm.vx, CU_TENSOR_MAP_DATA_TYPE_BFLOAT16, 5, xc, d, sd, bi, e, CU_TENSOR_MAP_INTERLEAVE_NONE, CU_TENSOR_MAP_SWIZZLE_NONE,
        CU_TENSOR_MAP_L2_PROMOTION_NONE, CU_TENSOR_MAP_FLOAT_OOB_FILL_NONE);
  }
  cudaFuncSetAttribute(k_ffn, cudaFuncAttributeMaxDynamicSharedMemorySize, ffn::SMEM);
  cudaFuncSetAttribute(k_rec, cudaFuncAttributeMaxDynamicSharedMemorySize, rec::SMEM);
  cudaStream_t st = cudaStreamPerThread;
  int dF = 450, dA = 2700, dS = 320, dM = 120, dG = 250, dP = 24, dX = 48, dD = 350, dZ = 0, dQ = 750, dV = 370, dX2 = 0;
  k_rec<<<132, 512, rec::SMEM, st>>>(rm, mem0, x, (const bf16*)d_in[12], (const bf16*)d_in[13], (const char*)d_in[8], (const bf16*)d_in[9],
                                     (const char*)d_in[5], xc, dF, dA, dS, dM, dG, dP, dX, dD, dZ, dQ, dV, dX2);
  cudaLaunchConfig_t cfg = {};
  cfg.gridDim = dim3(132); cfg.blockDim = dim3(384); cfg.dynamicSmemBytes = ffn::SMEM; cfg.stream = st;
  cudaLaunchAttribute at[1];
  at[0].id = cudaLaunchAttributeProgrammaticStreamSerialization;
  at[0].val.programmaticStreamSerializationAllowed = 1;
  cfg.attrs = at; cfg.numAttrs = 1;
  cudaLaunchKernelEx(&cfg, k_ffn, fm, (const bf16*)d_in[11]);
}
```

```cpp
#include <cuda_runtime.h>
#include <cuda.h>
#include <cuda_bf16.h>
#include <stdint.h>

typedef __nv_bfloat16 bf16;

__device__ __align__(16) float g_mod[6144];
__device__ __align__(1024) uint4 g_modp[4 * 512];
__device__ unsigned g_hcnt;
__device__ unsigned g_hf[4];
__device__ __align__(1024) uint4 g_h[2048 * 1024 / 8];
__device__ __align__(1024) uint4 g_O[2048 * 4096 / 8];
__device__ __align__(1024) uint4 g_h2[2048 * 1024 / 8];
__device__ __align__(1024) uint4 g_U[2048 * 3584 / 8];
__device__ __align__(1024) uint4 g_stat[2048 * 4];
__device__ __align__(1024) unsigned g_cnt[16 * 4 * 32];
__device__ unsigned g_mcnt;
__device__ unsigned g_slot[256];
__device__ unsigned g_fin;
__device__ __align__(16) uint4 g_cc[224 * 4];
__device__ __align__(1024) uint4 g_xc[44 * 16384];
__device__ __align__(1024) unsigned g_tm[4 * 256];
#define FT(i)
#define FTP(i)
#define PT(i)
#define PH(i)
#define RS(i)
#define RP(i)
#define RPN(i, s)
#define TSV(i, v)
#define TS(i)

#define FRC "232"
#define FRP "40"
#define FMAP (((g >> 2) * 4 + m) * 8 + ((g & 3) ^ ((g & 4) ? 3 : 0)) * 2 + (blockIdx.x & 1))
#define ALIAS 3
#define PFT 150000
#define PFS 104
#define PF0 13000
#define PFD 128
#define NF 3
#define NB0 4
#define PV0 4
#define T1L 1
#define NW0 4
#define VRF 3
#define VPC 1
#define WC0 99
#define WPE 3
#define ALN 0x80
#define SKW 5
#define L62 200
#define DLY(k)
#define PKE 0
#define USD 150
#define XR 32
#define XTD 500
#define XDL 6
#define PDS 61
#define P_NVR 5
#define P_NWP 9
#define P_NW1 7
#define RF_ 208
#define RA_ (488 - 2 * RF_)
#define WCH 2
#define NOP_ 2
#define SPIN_LIMIT (1 << 20)
__device__ __forceinline__ uint64_t mkdesc(uint32_t addr, uint32_t lbo, uint32_t sbo) {
  return (uint64_t)((addr & 0x3FFFF) >> 4) | ((uint64_t)(lbo >> 4) << 16) | ((uint64_t)(sbo >> 4) << 32) | (1ull << 62);
}
__device__ __forceinline__ void mbar_init(uint32_t a, int c) { asm volatile("mbarrier.init.shared.b64 [%0],%1;" ::"r"(a), "r"(c) : "memory"); }
__device__ __forceinline__ void mbar_wait(uint32_t a, uint32_t par) {
  asm volatile(
      "{.reg .pred p; .reg .u32 n;\n"
      "mov.u32 n, 0;\n"
      "W: mbarrier.try_wait.parity.shared.b64 p,[%0],%1;\n"
      "@p bra D;\n"
      "add.u32 n, n, 1;\n"
      "setp.lt.u32 p, n, %2;\n"
      "@p bra W;\n"
      "trap;\n"
      "D:}" ::"r"(a), "r"(par), "n"(SPIN_LIMIT) : "memory");
}
__device__ __forceinline__ void mbar_wait_q(uint32_t a, uint32_t par) {
  asm volatile(
      "{.reg .pred p; .reg .u32 n;\n"
      "mov.u32 n, 0;\n"
      "W: mbarrier.try_wait.parity.shared.b64 p,[%0],%1,4000;\n"
      "@p bra D;\n"
      "add.u32 n, n, 1;\n"
      "setp.lt.u32 p, n, %2;\n"
      "@p bra W;\n"
      "trap;\n"
      "D:}" ::"r"(a), "r"(par), "n"(SPIN_LIMIT / 16) : "memory");
}
__device__ __forceinline__ void mbar_expect(uint32_t a, uint32_t b) { asm volatile("mbarrier.arrive.expect_tx.shared.b64 _,[%0],%1;" ::"r"(a), "r"(b) : "memory"); }
__device__ __forceinline__ void mbar_arrive(uint32_t a) { asm volatile("mbarrier.arrive.shared.b64 _,[%0];" ::"r"(a) : "memory"); }
__device__ __forceinline__ uint32_t mapa(uint32_t a, uint32_t cta) { uint32_t r; asm("mapa.shared::cluster.u32 %0,%1,%2;" : "=r"(r) : "r"(a), "r"(cta)); return r; }
__device__ __forceinline__ void mbar_arrive_cl(uint32_t a) { asm volatile("mbarrier.arrive.shared::cluster.b64 _,[%0];" ::"r"(a) : "memory"); }
__device__ __forceinline__ void tma2d(uint32_t dst, const CUtensorMap* m, int c0, int c1, uint32_t mb) {
  asm volatile("cp.async.bulk.tensor.2d.shared::cluster.global.mbarrier::complete_tx::bytes [%0],[%1,{%2,%3}],[%4];" ::"r"(dst), "l"(m), "r"(c0), "r"(c1), "r"(mb) : "memory");
}
__device__ __forceinline__ void tma2d_pf(const CUtensorMap* m, int c0, int c1) {
  asm volatile("cp.async.bulk.prefetch.tensor.2d.L2.global [%0,{%1,%2}];" ::"l"(m), "r"(c0), "r"(c1) : "memory");
}
__device__ __forceinline__ void tma2d_st(const CUtensorMap* m, int c0, int c1, uint32_t src) {
  asm volatile("cp.async.bulk.tensor.2d.global.shared::cta.bulk_group [%0,{%1,%2}],[%3];" ::"l"(m), "r"(c0), "r"(c1), "r"(src) : "memory");
}
__device__ __forceinline__ void bulk_ld(uint32_t dst, const void* src, uint32_t n, uint32_t mb) {
  asm volatile("cp.async.bulk.shared::cluster.global.mbarrier::complete_tx::bytes [%0],[%1],%2,[%3];" ::"r"(dst), "l"(src), "r"(n), "r"(mb) : "memory");
}
__device__ __forceinline__ void bulk_st(void* dst, uint32_t src, uint32_t n) {
  asm volatile("cp.async.bulk.global.shared::cta.bulk_group [%0],[%1],%2;" ::"l"(dst), "r"(src), "r"(n) : "memory");
}
__device__ __forceinline__ void e_expect_tma3d(uint32_t dst, const CUtensorMap* m, int c1, int c2, uint32_t mb, uint32_t bytes) {
  asm volatile("{.reg .pred p; elect.sync _|p, 0xffffffff; @p mbarrier.arrive.expect_tx.shared.b64 _,[%4],%5;\n"
               "@p cp.async.bulk.tensor.3d.shared::cluster.global.mbarrier::complete_tx::bytes [%0],[%1,{0,%2,%3}],[%4];}" ::"r"(dst), "l"(m), "r"(c1), "r"(c2), "r"(mb), "r"(bytes) : "memory");
}
__device__ __forceinline__ void e_bulk_ld(uint32_t dst, const void* src, uint32_t n, uint32_t mb) {
  asm volatile("{.reg .pred p; elect.sync _|p, 0xffffffff; @p cp.async.bulk.shared::cluster.global.mbarrier::complete_tx::bytes [%0],[%1],%2,[%3];}" ::"r"(dst), "l"(src), "r"(n), "r"(mb) : "memory");
}
#define BULK_COMMIT() asm volatile("cp.async.bulk.commit_group;" ::: "memory")
#define BULK_WAIT_READ(n) asm volatile("cp.async.bulk.wait_group.read " #n ";" ::: "memory")
#define BULK_WAIT(n) asm volatile("cp.async.bulk.wait_group " #n ";" ::: "memory")
#define FENCE_ASYNC_SMEM() asm volatile("fence.proxy.async.shared::cta;" ::: "memory")
#define FENCE_ASYNC() asm volatile("fence.proxy.async;" ::: "memory")
#define WG_FENCE() asm volatile("wgmma.fence.sync.aligned;" ::: "memory")
#define WG_COMMIT() asm volatile("wgmma.commit_group.sync.aligned;" ::: "memory")
#define WG_WAIT(n) asm volatile("wgmma.wait_group.sync.aligned " #n ";" ::: "memory")
#define BAR_SYNC(id, n) asm volatile("bar.sync %0,%1;" ::"n"(id), "n"(n) : "memory")
#define BAR_ARRIVE(id, n) asm volatile("bar.arrive %0,%1;" ::"n"(id), "n"(n) : "memory")
#define SCHED_FENCE(k) asm volatile("{.reg .pred p; setp.ne.u32 p,%0,0; @p trap;}" ::"r"(mp.zero[(k) - 46]) : "memory")
#define CLUSTER_SYNC() asm volatile("barrier.cluster.arrive.relaxed.aligned; barrier.cluster.wait.aligned;" ::: "memory")
__device__ __forceinline__ uint32_t pk(float lo, float hi) { uint32_t r; asm("cvt.rn.bf16x2.f32 %0,%1,%2;" : "=r"(r) : "f"(hi), "f"(lo)); return r; }
__device__ __forceinline__ float blo(uint32_t v) { return __uint_as_float(v << 16); }
__device__ __forceinline__ float bhi(uint32_t v) { return __uint_as_float(v & 0xffff0000u); }
__device__ __forceinline__ void ldsm4(uint32_t* r, uint32_t a) {
  asm volatile("ldmatrix.sync.aligned.m8n8.x4.shared.b16 {%0,%1,%2,%3},[%4];" : "=r"(r[0]), "=r"(r[1]), "=r"(r[2]), "=r"(r[3]) : "r"(a) : "memory");
}
__device__ __forceinline__ void ldsm4t(uint32_t* r, uint32_t a) {
  asm volatile("ldmatrix.sync.aligned.m8n8.x4.trans.shared.b16 {%0,%1,%2,%3},[%4];" : "=r"(r[0]), "=r"(r[1]), "=r"(r[2]), "=r"(r[3]) : "r"(a) : "memory");
}
__device__ __forceinline__ void stsm4(uint32_t a, uint32_t r0, uint32_t r1, uint32_t r2, uint32_t r3) {
  asm volatile("stmatrix.sync.aligned.m8n8.x4.shared.b16 [%0],{%1,%2,%3,%4};" ::"r"(a), "r"(r0), "r"(r1), "r"(r2), "r"(r3) : "memory");
}
__device__ __forceinline__ void mma16(float* d, uint32_t a0, uint32_t a1, uint32_t a2, uint32_t a3, uint32_t b0, uint32_t b1) {
  asm volatile("mma.sync.aligned.m16n8k16.row.col.f32.bf16.bf16.f32 {%0,%1,%2,%3},{%4,%5,%6,%7},{%8,%9},{%0,%1,%2,%3};"
               : "+f"(d[0]), "+f"(d[1]), "+f"(d[2]), "+f"(d[3]) : "r"(a0), "r"(a1), "r"(a2), "r"(a3), "r"(b0), "r"(b1));
}
__device__ __forceinline__ void mma8(float* d, uint32_t a0, uint32_t a1, uint32_t b0) {
  asm volatile("mma.sync.aligned.m16n8k8.row.col.f32.bf16.bf16.f32 {%0,%1,%2,%3},{%4,%5},{%6},{%0,%1,%2,%3};"
               : "+f"(d[0]), "+f"(d[1]), "+f"(d[2]), "+f"(d[3]) : "r"(a0), "r"(a1), "r"(b0));
}
__device__ __forceinline__ float4 lds4f(uint32_t a) { float4 v; asm volatile("ld.shared.v4.f32 {%0,%1,%2,%3},[%4];" : "=f"(v.x), "=f"(v.y), "=f"(v.z), "=f"(v.w) : "r"(a) : "memory"); return v; }
__device__ __forceinline__ float2 lds2f(uint32_t a) { float2 v; asm volatile("ld.shared.v2.f32 {%0,%1},[%2];" : "=f"(v.x), "=f"(v.y) : "r"(a) : "memory"); return v; }
__device__ __forceinline__ uint4 lds4(uint32_t a) { uint4 v; asm volatile("ld.shared.v4.u32 {%0,%1,%2,%3},[%4];" : "=r"(v.x), "=r"(v.y), "=r"(v.z), "=r"(v.w) : "r"(a) : "memory"); return v; }
__device__ __forceinline__ uint2 lds2u(uint32_t a) { uint2 v; asm volatile("ld.shared.v2.u32 {%0,%1},[%2];" : "=r"(v.x), "=r"(v.y) : "r"(a) : "memory"); return v; }
__device__ __forceinline__ uint32_t lds1(uint32_t a) { uint32_t v; asm volatile("ld.shared.u32 %0,[%1];" : "=r"(v) : "r"(a) : "memory"); return v; }
__device__ __forceinline__ void sts4(uint32_t a, uint32_t x, uint32_t y, uint32_t z, uint32_t w) { asm volatile("st.shared.v4.u32 [%0],{%1,%2,%3,%4};" ::"r"(a), "r"(x), "r"(y), "r"(z), "r"(w) : "memory"); }
__device__ __forceinline__ void sts2(uint32_t a, uint32_t x, uint32_t y) { asm volatile("st.shared.v2.u32 [%0],{%1,%2};" ::"r"(a), "r"(x), "r"(y) : "memory"); }
__device__ __forceinline__ void sts1(uint32_t a, uint32_t x) { asm volatile("st.shared.u32 [%0],%1;" ::"r"(a), "r"(x) : "memory"); }
__device__ __forceinline__ void sta4(uint32_t a, const uint32_t* v, uint32_t mb) {
  asm volatile("st.async.shared::cluster.mbarrier::complete_tx::bytes.v4.b32 [%0],{%1,%2,%3,%4},[%5];" ::"r"(a), "r"(v[0]), "r"(v[1]), "r"(v[2]), "r"(v[3]), "r"(mb) : "memory");
}
__device__ __forceinline__ uint4 ldg_rlx4(const void* p) { uint4 v; asm volatile("ld.relaxed.gpu.global.v4.u32 {%0,%1,%2,%3},[%4];" : "=r"(v.x), "=r"(v.y), "=r"(v.z), "=r"(v.w) : "l"(p) : "memory"); return v; }
__device__ __forceinline__ uint32_t ldg_rlx1(const void* p) { uint32_t v; asm volatile("ld.relaxed.gpu.global.u32 %0,[%1];" : "=r"(v) : "l"(p) : "memory"); return v; }
__device__ __forceinline__ uint4 ldg_b128(const void* p) {
  uint4 v;
  asm volatile("{.reg .b128 t; .reg .b64 a,b; ld.relaxed.gpu.global.b128 t,[%4]; mov.b128 {a,b},t; mov.b64 {%0,%1},a; mov.b64 {%2,%3},b;}" : "=r"(v.x), "=r"(v.y), "=r"(v.z), "=r"(v.w) : "l"(p) : "memory");
  return v;
}
__device__ __forceinline__ void stg_b128(void* p, uint32_t x, uint32_t y, uint32_t z, uint32_t w) {
  asm volatile("{.reg .b128 t; .reg .b64 a,b; mov.b64 a,{%1,%2}; mov.b64 b,{%3,%4}; mov.b128 t,{a,b}; st.relaxed.gpu.global.b128 [%0],t;}" ::"l"(p), "r"(x), "r"(y), "r"(z), "r"(w) : "memory");
}
__device__ __forceinline__ void stg_rlx2(void* p, uint32_t x, uint32_t y) { asm volatile("st.relaxed.gpu.global.v2.u32 [%0],{%1,%2};" ::"l"(p), "r"(x), "r"(y) : "memory"); }
__device__ __forceinline__ unsigned ld_acq(const unsigned* p) { unsigned v; asm volatile("ld.acquire.gpu.global.u32 %0,[%1];" : "=r"(v) : "l"(p) : "memory"); return v; }
__device__ __forceinline__ void red_rel(unsigned* p) { asm volatile("red.release.gpu.global.add.u32 [%0],1;" ::"l"(p) : "memory"); }
__device__ __forceinline__ void red_rlx(unsigned* p) { asm volatile("red.relaxed.gpu.global.add.u32 [%0],1;" ::"l"(p) : "memory"); }
__device__ __forceinline__ void wait_cnt(const unsigned* p, unsigned n) { int it = 0; while (ld_acq(p) < n) { if (++it > SPIN_LIMIT) __trap(); } }
__device__ __forceinline__ uint32_t clk() { uint32_t c; asm volatile("mov.u32 %0,%%clock;" : "=r"(c)); return c; }
__device__ __forceinline__ uint32_t gtime() { uint32_t c; asm volatile("mov.u32 %0,%%globaltimer_lo;" : "=r"(c)); return c; }
__device__ __forceinline__ float ex2(float x) { float r; asm("ex2.approx.ftz.f32 %0,%1;" : "=f"(r) : "f"(x)); return r; }
__device__ __forceinline__ float silu(float x) { return x * __frcp_rn(1.f + __expf(-x)); }
__device__ __forceinline__ float rbf(float x) { return __bfloat162float(__float2bfloat16_rn(x)); }

__device__ __forceinline__ void wgmma_ss_n128(float* d, uint64_t a, uint64_t b, int sd) {
  asm volatile("{.reg .pred p; setp.ne.b32 p, %66, 0;\n"
    "wgmma.mma_async.sync.aligned.m64n128k16.f32.bf16.bf16 {%0,%1,%2,%3,%4,%5,%6,%7,%8,%9,%10,%11,%12,%13,%14,%15,%16,%17,%18,%19,%20,%21,%22,%23,%24,%25,%26,%27,%28,%29,%30,%31,%32,%33,%34,%35,%36,%37,%38,%39,%40,%41,%42,%43,%44,%45,%46,%47,%48,%49,%50,%51,%52,%53,%54,%55,%56,%57,%58,%59,%60,%61,%62,%63}, %64, %65, p, 1, 1, 0, 1;}\n"
    : "+f"(d[0]),"+f"(d[1]),"+f"(d[2]),"+f"(d[3]),"+f"(d[4]),"+f"(d[5]),"+f"(d[6]),"+f"(d[7]),
      "+f"(d[8]),"+f"(d[9]),"+f"(d[10]),"+f"(d[11]),"+f"(d[12]),"+f"(d[13]),"+f"(d[14]),"+f"(d[15]),
      "+f"(d[16]),"+f"(d[17]),"+f"(d[18]),"+f"(d[19]),"+f"(d[20]),"+f"(d[21]),"+f"(d[22]),"+f"(d[23]),
      "+f"(d[24]),"+f"(d[25]),"+f"(d[26]),"+f"(d[27]),"+f"(d[28]),"+f"(d[29]),"+f"(d[30]),"+f"(d[31]),
      "+f"(d[32]),"+f"(d[33]),"+f"(d[34]),"+f"(d[35]),"+f"(d[36]),"+f"(d[37]),"+f"(d[38]),"+f"(d[39]),
      "+f"(d[40]),"+f"(d[41]),"+f"(d[42]),"+f"(d[43]),"+f"(d[44]),"+f"(d[45]),"+f"(d[46]),"+f"(d[47]),
      "+f"(d[48]),"+f"(d[49]),"+f"(d[50]),"+f"(d[51]),"+f"(d[52]),"+f"(d[53]),"+f"(d[54]),"+f"(d[55]),
      "+f"(d[56]),"+f"(d[57]),"+f"(d[58]),"+f"(d[59]),"+f"(d[60]),"+f"(d[61]),"+f"(d[62]),"+f"(d[63])
    : "l"(a), "l"(b), "r"(sd));
}
__device__ __forceinline__ void wgmma_ss_n192(float* d, uint64_t a, uint64_t b, int sd) {
  asm volatile("{.reg .pred p; setp.ne.b32 p, %98, 0;\n"
    "wgmma.mma_async.sync.aligned.m64n192k16.f32.bf16.bf16 {%0,%1,%2,%3,%4,%5,%6,%7,%8,%9,%10,%11,%12,%13,%14,%15,%16,%17,%18,%19,%20,%21,%22,%23,%24,%25,%26,%27,%28,%29,%30,%31,%32,%33,%34,%35,%36,%37,%38,%39,%40,%41,%42,%43,%44,%45,%46,%47,%48,%49,%50,%51,%52,%53,%54,%55,%56,%57,%58,%59,%60,%61,%62,%63,%64,%65,%66,%67,%68,%69,%70,%71,%72,%73,%74,%75,%76,%77,%78,%79,%80,%81,%82,%83,%84,%85,%86,%87,%88,%89,%90,%91,%92,%93,%94,%95}, %96, %97, p, 1, 1, 0, 1;}\n"
    : "+f"(d[0]),"+f"(d[1]),"+f"(d[2]),"+f"(d[3]),"+f"(d[4]),"+f"(d[5]),"+f"(d[6]),"+f"(d[7]),
      "+f"(d[8]),"+f"(d[9]),"+f"(d[10]),"+f"(d[11]),"+f"(d[12]),"+f"(d[13]),"+f"(d[14]),"+f"(d[15]),
      "+f"(d[16]),"+f"(d[17]),"+f"(d[18]),"+f"(d[19]),"+f"(d[20]),"+f"(d[21]),"+f"(d[22]),"+f"(d[23]),
      "+f"(d[24]),"+f"(d[25]),"+f"(d[26]),"+f"(d[27]),"+f"(d[28]),"+f"(d[29]),"+f"(d[30]),"+f"(d[31]),
      "+f"(d[32]),"+f"(d[33]),"+f"(d[34]),"+f"(d[35]),"+f"(d[36]),"+f"(d[37]),"+f"(d[38]),"+f"(d[39]),
      "+f"(d[40]),"+f"(d[41]),"+f"(d[42]),"+f"(d[43]),"+f"(d[44]),"+f"(d[45]),"+f"(d[46]),"+f"(d[47]),
      "+f"(d[48]),"+f"(d[49]),"+f"(d[50]),"+f"(d[51]),"+f"(d[52]),"+f"(d[53]),"+f"(d[54]),"+f"(d[55]),
      "+f"(d[56]),"+f"(d[57]),"+f"(d[58]),"+f"(d[59]),"+f"(d[60]),"+f"(d[61]),"+f"(d[62]),"+f"(d[63]),
      "+f"(d[64]),"+f"(d[65]),"+f"(d[66]),"+f"(d[67]),"+f"(d[68]),"+f"(d[69]),"+f"(d[70]),"+f"(d[71]),
      "+f"(d[72]),"+f"(d[73]),"+f"(d[74]),"+f"(d[75]),"+f"(d[76]),"+f"(d[77]),"+f"(d[78]),"+f"(d[79]),
      "+f"(d[80]),"+f"(d[81]),"+f"(d[82]),"+f"(d[83]),"+f"(d[84]),"+f"(d[85]),"+f"(d[86]),"+f"(d[87]),
      "+f"(d[88]),"+f"(d[89]),"+f"(d[90]),"+f"(d[91]),"+f"(d[92]),"+f"(d[93]),"+f"(d[94]),"+f"(d[95])
    : "l"(a), "l"(b), "r"(sd));
}
__device__ __forceinline__ void wgmma_rs_n32(float* d, const uint32_t* a, uint64_t b, int sd) {
  asm volatile("{.reg .pred p; setp.ne.b32 p, %21, 0;\n"
    "wgmma.mma_async.sync.aligned.m64n32k16.f32.bf16.bf16 {%0,%1,%2,%3,%4,%5,%6,%7,%8,%9,%10,%11,%12,%13,%14,%15}, {%16,%17,%18,%19}, %20, p, 1, 1, 0;}\n"
    : "+f"(d[0]),"+f"(d[1]),"+f"(d[2]),"+f"(d[3]),"+f"(d[4]),"+f"(d[5]),"+f"(d[6]),"+f"(d[7]),
      "+f"(d[8]),"+f"(d[9]),"+f"(d[10]),"+f"(d[11]),"+f"(d[12]),"+f"(d[13]),"+f"(d[14]),"+f"(d[15])
    : "r"(a[0]), "r"(a[1]), "r"(a[2]), "r"(a[3]), "l"(b), "r"(sd));
}
__device__ __forceinline__ void wgmma_ssT_n32(float* d, uint64_t a, uint64_t b, int sd) {
  asm volatile("{.reg .pred p; setp.ne.b32 p, %18, 0;\n"
    "wgmma.mma_async.sync.aligned.m64n32k16.f32.bf16.bf16 {%0,%1,%2,%3,%4,%5,%6,%7,%8,%9,%10,%11,%12,%13,%14,%15}, %16, %17, p, 1, 1, 1, 0;}\n"
    : "+f"(d[0]),"+f"(d[1]),"+f"(d[2]),"+f"(d[3]),"+f"(d[4]),"+f"(d[5]),"+f"(d[6]),"+f"(d[7]),
      "+f"(d[8]),"+f"(d[9]),"+f"(d[10]),"+f"(d[11]),"+f"(d[12]),"+f"(d[13]),"+f"(d[14]),"+f"(d[15])
    : "l"(a), "l"(b), "r"(sd));
}

__device__ __forceinline__ void wgmma_rs_n32_z(float* d, const uint32_t* a, uint64_t b) {
  asm volatile("{.reg .pred p; setp.ne.b32 p, 0, 0;\n"
    "wgmma.mma_async.sync.aligned.m64n32k16.f32.bf16.bf16 {%0,%1,%2,%3,%4,%5,%6,%7,%8,%9,%10,%11,%12,%13,%14,%15}, {%16,%17,%18,%19}, %20, p, 1, 1, 0;}\n"
    : "=f"(d[0]),"=f"(d[1]),"=f"(d[2]),"=f"(d[3]),"=f"(d[4]),"=f"(d[5]),"=f"(d[6]),"=f"(d[7]),
      "=f"(d[8]),"=f"(d[9]),"=f"(d[10]),"=f"(d[11]),"=f"(d[12]),"=f"(d[13]),"=f"(d[14]),"=f"(d[15])
    : "r"(a[0]), "r"(a[1]), "r"(a[2]), "r"(a[3]), "l"(b));
}

namespace rec {
constexpr int NVR = P_NVR;
constexpr int NVS = 16 - NVR;
constexpr int NWP = P_NWP;
constexpr uint32_t WO = 0;
constexpr uint32_t XB = 65536;
constexpr uint32_t PK = XB + 32768;
constexpr uint32_t VX0 = PK + 24576;
constexpr uint32_t VX1 = VX0 + 4096;
constexpr uint32_t WVS = 131072;
constexpr uint32_t MEM = WVS + 2 * NVS * 2048;
constexpr uint32_t ARO = MEM + 10240;
constexpr uint32_t OB = ARO + 5120;
constexpr uint32_t QT = OB + 2048;
constexpr uint32_t KT = QT + 2048;
constexpr uint32_t RQ = KT + 6144;
constexpr uint32_t RK = RQ + 2048;
constexpr uint32_t SC = RK + 2048;
constexpr uint32_t OT = OB;
constexpr uint32_t TF = SC + 2048;
constexpr uint32_t PRE = MEM + 2 * NVR * 2048;
constexpr uint32_t TA = TF + 8192;
constexpr uint32_t RX = TA + 6144;
constexpr uint32_t VN = RX + 2048;
constexpr uint32_t BARS = VN + 4096;
constexpr uint32_t PACE = BARS + 18 * 8;
constexpr uint32_t SMEM = BARS + 512;
static_assert(PRE + 14336 <= BARS, "staging");
constexpr int NW1 = P_NW1;
static_assert(SMEM <= 232448, "smem");
constexpr int B_E = 2, B_SC = 3, B_S = 4, B_O = 5, B_F = 6, B_W = 7, B_C = 9, B_K = 10, B_Q = 1, B_S2 = 6, B_T2 = 9, B_P = 13, B_T = 14, B_R = 11, B_X = 12, B_V = 8;
constexpr int XC = 16384, X_RING = 131072, X_SC = 65536, X_TOK = 4096;
#define X_VX(i) (((i) >> 1) * 2048 + ((i) & 1) * 512)
#define X_VM(i) (X_VX(i) + 1024)
#define V_RING(n) (((n) & 1) * X_RING + ((n) & 2) * 2048)
#define V_TAG(n) ((~(n) >> 2) & 1)
}
struct RecMaps { CUtensorMap wq, wk, wv, wo, ari, vx; int zero[40]; };

#define F_(x) __uint_as_float(x)
#define U_(x) __float_as_uint(x)
#define AR_R(q) (24 + ((q) & 1) * 16 + ((q) >> 1) * 56)
#define AR_P(q) ((q) >> 1)
#define AR_ROW(i) (24 + ((i) & 1) * 16 + ((i) & 2) * 92 + (((i) >> 2) & 7) + ((i) >> 5) * 128)
constexpr size_t AR_OFF = 32 * 262144;
__device__ __forceinline__ void ar_fetch(uint32_t dst, const CUtensorMap* m, int slot, int half, uint32_t mb) {
  asm volatile("{.reg .pred p; elect.sync _|p, 0xffffffff; @p mbarrier.arrive.expect_tx.shared.b64 _,[%4],10240;\n"
               "@p cp.async.bulk.tensor.3d.shared::cluster.global.mbarrier::complete_tx::bytes [%0],[%1,{%2,%6,%3}],[%4];\n"
               "@p cp.async.bulk.tensor.3d.shared::cluster.global.mbarrier::complete_tx::bytes [%0+5120],[%1,{%2,%7,%5}],[%4];}"
               ::"r"(dst), "l"(m), "r"(slot * 64), "r"(AR_R(half * 2)), "r"(mb), "r"(AR_R(half * 2 + 1)), "r"(AR_P(half * 2)), "r"(AR_P(half * 2 + 1)) : "memory");
}
__device__ __forceinline__ uint4 exch_b128(void* p, uint32_t x, uint32_t y, uint32_t z, uint32_t w) {
  uint4 v;
  asm volatile("{.reg .b128 s, t; .reg .b64 a,b; mov.b64 a,{%5,%6}; mov.b64 b,{%7,%8}; mov.b128 s,{a,b}; atom.relaxed.gpu.global.exch.b128 t,[%4],s;"
               " mov.b128 {a,b},t; mov.b64 {%0,%1},a; mov.b64 {%2,%3},b;}" : "=r"(v.x), "=r"(v.y), "=r"(v.z), "=r"(v.w) : "l"(p), "r"(x), "r"(y), "r"(z), "r"(w) : "memory");
  return v;
}
#define CONSUME(v) do { if ((v) == 0x7fc12345u) sts1(sb + rec::BARS + 96, 0); } while (0)
__device__ __forceinline__ uint2 ldg_b64(const void* p) { uint2 v; asm volatile("{.reg .b64 t; ld.relaxed.gpu.global.b64 t,[%2]; mov.b64 {%0,%1},t;}" : "=r"(v.x), "=r"(v.y) : "l"(p) : "memory"); return v; }
__device__ __forceinline__ void stg_b64(void* p, uint32_t x, uint32_t y) { asm volatile("{.reg .b64 t; mov.b64 t,{%1,%2}; st.relaxed.gpu.global.b64 [%0],t;}" ::"l"(p), "r"(x), "r"(y) : "memory"); }
__device__ __forceinline__ uint32_t tagbad(uint32_t x, uint32_t y, uint32_t tag) { uint32_t r; asm("lop3.b32 %0,%1,%2,%3,0x7e;" : "=r"(r) : "r"(x), "r"(y), "r"(tag)); return r; }

__device__ __forceinline__ bool anybad(uint32_t a, uint32_t b, uint32_t c, uint32_t d, uint32_t e, uint32_t f, uint32_t g, uint32_t h, uint32_t tag) {
  uint32_t r;
  asm volatile("{.reg .b32 t,u,v,w; .reg .pred p; lop3.b32 t,%1,%2,%9,0x7e; lop3.b32 u,%3,%4,%9,0x7e; lop3.b32 v,%5,%6,%9,0x7e; lop3.b32 w,%7,%8,%9,0x7e;"
               " lop3.b32 t,t,u,v,0xfe; lop3.b32 t,t,w,1,0xa8; setp.ne.u32 p,t,0; vote.sync.any.pred p,p,0xffffffff; selp.u32 %0,1,0,p;}"
               : "=r"(r) : "r"(a), "r"(b), "r"(c), "r"(d), "r"(e), "r"(f), "r"(g), "r"(h), "r"(tag));
  return r;
}
__device__ __forceinline__ bool anybad(uint32_t a, uint32_t b, uint32_t c, uint32_t d, uint32_t tag) {
  uint32_t r;
  asm volatile("{.reg .b32 t,u; .reg .pred p; lop3.b32 t,%1,%2,%5,0x7e; lop3.b32 u,%3,%4,%5,0x7e;"
               " lop3.b32 t,t,u,1,0xa8; setp.ne.u32 p,t,0; vote.sync.any.pred p,p,0xffffffff; selp.u32 %0,1,0,p;}"
               : "=r"(r) : "r"(a), "r"(b), "r"(c), "r"(d), "r"(tag));
  return r;
}
#define BADS(r) anybad(r[0].x, r[0].y, r[1].x, r[1].y, r[2].x, r[2].y, r[3].x, r[3].y, tag)
constexpr float SCS = 0.08838834764831845f * 1.4426950408889634f / 16.f;
__device__ __forceinline__ uint32_t pkh(float lo, float hi, uint32_t tag) {
  uint32_t r;
  asm("{.reg .b32 t; cvt.rn.satfinite.f16x2.f32 t,%1,%2; lop3.b32 %0,t,0xfffffffe,%3,0xea;}" : "=r"(r) : "f"(hi), "f"(lo), "r"(tag));
  return r;
}
__device__ __forceinline__ uint32_t addh(uint32_t a, uint32_t b) { uint32_t r; asm("add.rn.f16x2 %0,%1,%2;" : "=r"(r) : "r"(a), "r"(b)); return r; }
__device__ __forceinline__ float hlo(uint32_t v) { float r; asm("{.reg .b16 a,b; mov.b32 {a,b},%1; cvt.f32.f16 %0,a;}" : "=f"(r) : "r"(v)); return r; }
__device__ __forceinline__ float hhi(uint32_t v) { float r; asm("{.reg .b16 a,b; mov.b32 {a,b},%1; cvt.f32.f16 %0,b;}" : "=f"(r) : "r"(v)); return r; }
__device__ __forceinline__ uint32_t ordh(uint32_t v) {
  uint32_t r;
  asm("{.reg .b32 m; prmt.b32 m,%1,0,0xbb99; lop3.b32 %0,%1,m,0x7fff7fff,0x78;}" : "=r"(r) : "r"(v));
  return r;
}
template <bool MASK>
__device__ __forceinline__ float4 softmax2(const uint2 (&r)[4], uint32_t mx, uint32_t my, uint32_t& k) {
  uint32_t x = addh(addh(r[0].x, r[1].x), addh(r[2].x, r[3].x)), y = addh(addh(r[0].y, r[1].y), addh(r[2].y, r[3].y));
  if (MASK) { x = addh(x, mx); y = addh(y, my); }
  asm("max.f16x2 %0,%1,%2;" : "=r"(k) : "r"(x), "r"(y));
  k = ordh(k);
  const int k0 = __reduce_max_sync(~0u, (int)(k << 16)), k1 = __reduce_max_sync(~0u, (int)k);
  const float m0 = hhi(k0 ^ ((k0 >> 31) & 0x7fff0000)) * -16.f, m1 = hhi(k1 ^ ((k1 >> 31) & 0x7fff0000)) * -16.f;
  return make_float4(ex2(fmaf(hlo(x), 16.f, m0)), ex2(fmaf(hhi(x), 16.f, m1)), ex2(fmaf(hlo(y), 16.f, m0)), ex2(fmaf(hhi(y), 16.f, m1)));
}
__device__ __forceinline__ char* mkp(uint32_t lo, uint32_t hi) { uint64_t r; asm("mov.b64 %0,{%1,%2};" : "=l"(r) : "r"(lo), "r"(hi)); return (char*)r; }
#define LO(p) ((uint32_t)(uint64_t)(p))
#define HI(p) ((uint32_t)((uint64_t)(p) >> 32))
__device__ __forceinline__ uint32_t mulbf(uint32_t a, uint32_t b) { uint32_t r; asm("mul.rn.bf16x2 %0,%1,%2;" : "=r"(r) : "r"(a), "r"(b)); return r; }
__device__ __forceinline__ uint32_t fmabf(uint32_t a, uint32_t b, uint32_t c) { uint32_t r; asm("fma.rn.bf16x2 %0,%1,%2,%3;" : "=r"(r) : "r"(a), "r"(b), "r"(c)); return r; }
__device__ __forceinline__ uint32_t addbf(uint32_t a, uint32_t b) { uint32_t r; asm("add.rn.bf16x2 %0,%1,%2;" : "=r"(r) : "r"(a), "r"(b)); return r; }
__device__ __forceinline__ void pv_mem(const uint32_t (&p)[4], uint32_t pm, const uint4 (&v)[4], const uint4 (&vn)[2], uint32_t (&O)[4]) {
  float o[4][4] = {{0, 0, 0, 0}, {0, 0, 0, 0}, {0, 0, 0, 0}, {0, 0, 0, 0}};
  mma16(o[0], v[0].x, v[0].y, v[0].z, v[0].w, p[0], p[1]);
  mma16(o[1], v[2].x, v[2].y, v[2].z, v[2].w, p[0], p[1]);
  mma16(o[2], v[1].x, v[1].y, v[1].z, v[1].w, p[2], p[3]);
  mma16(o[3], v[3].x, v[3].y, v[3].z, v[3].w, p[2], p[3]);
  mma16(o[0], vn[0].x, vn[0].y, vn[0].z, vn[0].w, pm, pm);
  mma16(o[1], vn[1].x, vn[1].y, vn[1].z, vn[1].w, pm, pm);
  O[0] = pk(o[0][0] + o[2][0], o[0][1] + o[2][1]); O[1] = pk(o[0][2] + o[2][2], o[0][3] + o[2][3]);
  O[2] = pk(o[1][0] + o[3][0], o[1][1] + o[3][1]); O[3] = pk(o[1][2] + o[3][2], o[1][3] + o[3][3]);
}
__device__ __forceinline__ void pv_tok(const uint32_t (&p)[4], uint32_t pm, const uint4 (&v)[4], const uint32_t (&vm)[4], uint32_t (&O)[4]) {
  float o[2][4] = {{0, 0, 0, 0}, {0, 0, 0, 0}}, sum[4] = {0, 0, 0, 0};
  const uint32_t one = 0x3f803f80u;
  mma16(sum, one, one, one, one, p[0], p[1]);
  mma16(o[0], v[0].x, v[0].y, v[0].z, v[0].w, p[0], p[1]);
  mma16(o[1], v[2].x, v[2].y, v[2].z, v[2].w, p[0], p[1]);
  mma16(sum, one, one, one, one, p[2], p[3]);
  mma16(o[0], v[1].x, v[1].y, v[1].z, v[1].w, p[2], p[3]);
  mma16(o[1], v[3].x, v[3].y, v[3].z, v[3].w, p[2], p[3]);
  mma8(sum, one, one, pm);
  mma8(o[0], vm[0], vm[1], pm);
  mma8(o[1], vm[2], vm[3], pm);
  float i0, i1;
  asm("rcp.approx.ftz.f32 %0,%1;" : "=f"(i0) : "f"(sum[0]));
  asm("rcp.approx.ftz.f32 %0,%1;" : "=f"(i1) : "f"(sum[1]));
  O[0] = pk(o[0][0] * i0, o[0][1] * i1); O[1] = pk(o[0][2] * i0, o[0][3] * i1);
  O[2] = pk(o[1][0] * i0, o[1][1] * i1); O[3] = pk(o[1][2] * i0, o[1][3] * i1);
}
__device__ __forceinline__ uint32_t sum4bf(uint32_t a, uint32_t b, uint32_t c, uint32_t d) { return addbf(addbf(a, b), addbf(c, d)); }
template <int OFF>
__device__ __forceinline__ void sta1(uint32_t a, uint32_t v, uint32_t mb) {
  asm volatile("st.async.shared::cluster.mbarrier::complete_tx::bytes.b32 [%0+%3],%1,[%2];" ::"r"(a), "r"(v), "r"(mb), "n"(OFF) : "memory");
}

__device__ __forceinline__ void wait_time(uint32_t t) { while ((int)(gtime() - t) < 0) __nanosleep(64); }
__device__ __noinline__ void rec_prefetch(const char* wmod, const char* w1, const char* x, const char* wo) {
  const int hb = blockIdx.x - 128;
  const uint32_t t0 = gtime();
  uint32_t t = t0 + PF0;
#pragma unroll 1
  for (int job = 0; job < (PFT ? 5 : 3); job++) {
    const char* p = job == 0 ? x + (6 + hb) * 65536 : job == 1 ? wmod + hb * 12288 + 4096 : job == 2 ? w1 + hb * 7168 : job == 3 ? x + hb * 8192 : wo + (1020 + hb) * 8192;
    const int n = job == 0 ? 120 - (hb & 2) * 4 : job == 3 ? 128 : 256, d = job == 0 ? 8192 : job == 1 ? 49152 : job == 2 ? 28672 : job == 3 ? 32768 : -32768;
    if (job == 3) t = t0 + PFT;
    PT(8 + job);
#pragma unroll 1
    for (int i = 0; i < n; i++) {
      wait_time(t);
      asm volatile("cp.async.bulk.prefetch.L2.global [%0], %1;" ::"l"(p), "r"(job == 2 ? 7168 : 8192) : "memory");
      p += !job && (i & 7) == 7 ? 204800 : d;
      t += job < 3 ? PFD : PFS;
      if (job && (i & 31) == 31 && ldg_rlx1(&g_fin)) return;
    }
  }
  PT(13);
}
__device__ __noinline__ void rec_helper(uint32_t sb, const bf16* cvec, const bf16* wmod, const char* w1, const bf16* b1, uint32_t t0) {
  const int tid = threadIdx.x, hb = blockIdx.x - 128;
  PT(1);
  for (int i = tid; i < 1024; i += 256) sts1(sb + i * 8, U_(rbf(silu(__bfloat162float(cvec[i])))));
  for (int i = tid; i < 2048; i += 256) g_stat[hb * 2048 + i] = make_uint4(~0u, ~0u, ~0u, ~0u);
  for (int i = tid; i < 512; i += 256) g_cnt[hb * 512 + i] = 0;
#pragma unroll 1
  for (int job = 0; job < 2; job++) {
    wait_time(t0 + PF0 + (job ? 600 : 350) * PFD);
    BAR_SYNC(rec::B_F, 256);
    PT(2 + job * 5);
    const int n8 = job ? 112 : 128, rg = tid >= n8, cg = tid - rg * n8, pitch = job ? 448 : 768;
    const uint4* p = (const uint4*)(job ? w1 + hb * 1792 : (const char*)(wmod + 2048 + hb * 1024)) + rg * pitch + min(cg, n8 - 1);
    float a1[8] = {0, 0, 0, 0, 0, 0, 0, 0}, a2[8] = {0, 0, 0, 0, 0, 0, 0, 0};
#pragma unroll 1
    for (int r0 = rg; r0 < 1024; r0 += 32) {
      uint4 v[16];
#pragma unroll
      for (int i = 0; i < 16; i++) { v[i] = ldg_rlx4(p); p += 2 * pitch; }
#pragma unroll
      for (int i = 0; i < 16; i++) {
        const float2 f = lds2f(sb + (r0 + 2 * i) * 8);
        const float w[8] = {blo(v[i].x), bhi(v[i].x), blo(v[i].y), bhi(v[i].y), blo(v[i].z), bhi(v[i].z), blo(v[i].w), bhi(v[i].w)};
#pragma unroll
        for (int e = 0; e < 8; e++) { a1[e] += f.x * w[e]; a2[e] += f.y * w[e]; }
      }
    }
    const uint32_t rd = sb + 8192;
    if (cg < n8) {
#pragma unroll
      for (int e = 0; e < 8; e++) sts2(rd + rg * 8192 + (cg * 8 + e) * 8, U_(a1[e]), U_(a2[e]));
    }
    BAR_SYNC(rec::B_F, 256);
    if (job == 0) {
      for (int i = tid; i < 1024; i += 256) g_mod[2048 + hb * 1024 + i] = rbf(F_(lds1(rd + i * 8)) + F_(lds1(rd + 8192 + i * 8)));
      BAR_SYNC(rec::B_F, 256);
      PT(6);
      if (tid == 0) { red_rel(&g_mcnt); wait_cnt(&g_mcnt, 4); }
      BAR_SYNC(rec::B_F, 256);
      for (int i = tid; i < 1024; i += 256) sts2(sb + i * 8, U_(rbf(1.f + __ldcg(g_mod + 4096 + i))), U_(__ldcg(g_mod + 3072 + i)));
    } else {
      for (int i = tid; i < 448; i += 256) {
        const int gn = hb * 896 + i * 2;
        const uint32_t bb = *(const uint32_t*)(b1 + gn);
        const float4 u = lds4f(rd + i * 16), w = lds4f(rd + 8192 + i * 16);
        ((uint2*)g_cc)[(gn >> 4) * 8 + ((gn >> 1) & 3) * 2 + ((gn >> 3) & 1)] = make_uint2(pk(u.x + w.x, u.z + w.z), pk(0.5f * (u.y + w.y + blo(bb)), 0.5f * (u.w + w.w + bhi(bb))));
      }
      PT(4);
    }
  }
}

__global__ void __cluster_dims__(2, 1, 1) __launch_bounds__(512, 1)
k_rec(const __grid_constant__ RecMaps mp, const bf16* __restrict__ mem0, const bf16* __restrict__ x, const bf16* __restrict__ cvec,
      const bf16* __restrict__ wmod, const char* __restrict__ w1, const bf16* __restrict__ b1, const char* __restrict__ wo, char* xc, int dF, int dA, int dS, int dM, int dG, int dP, int dX, int dD, int dZ, int dQ, int dV, int dX2) {
  using namespace rec;
  extern __shared__ __align__(1024) char smem[];
  const uint32_t sb = (uint32_t)__cvta_generic_to_shared(smem);
  if ((sb & 0x3FFFF) != 1024) __trap();
  PH(0); RS(0); if (threadIdx.x == 0) PT(0);
  if (threadIdx.x == 0) {
    int b = blockIdx.x;
    if (b >= 8 && b < 128) {
      const int t = (b >> 1) - 4, u = t - 32;
      b = 2 * (t < 32 ? 4 + (t & 16) + (t & 7) * 2 + ((t >> 3) & 1) : 36 + (u / 14) * 14 + (u % 7) * 2 + ((u / 7) & 1)) + (b & 1);
    }
    sts1(sb + rec::PACE + 24, b);
    const int c = blockIdx.x >> 1, l = c < 36 ? (c - 4) & 7 : (c - 36) % 7, m = c < 4 ? c : c < 36 ? (c - 4) >> 3 : (c - 36) / 7;
    const int g = c < 4 ? 15 : (l >> 1) * 4 + (l & 1) + (c < 36 ? 0 : 2);
    unsigned sm;
    asm("mov.u32 %0,%%smid;" : "=r"(sm));
    if (c < 64) g_slot[sm & 255] = 1 + FMAP;
  }
#define ROLE_REFRESH { asm volatile("mov.u32 %0,%%tid.x;" : "=r"(tid)); wid = __shfl_sync(~0u, tid >> 5, 0); b = __shfl_sync(~0u, lds1(sb + PACE + 24), 0); }
#define ROLE_VARS int tid; asm volatile("mov.u32 %0,%%tid.x;" : "=r"(tid)); \
    int wid = __shfl_sync(~0u, tid >> 5, 0), b = __shfl_sync(~0u, lds1(sb + PACE + 24), 0);
#define wg (wid >> 2)
#define iw (wid & 3)
#define h (b >> 2)
#define j (b & 3)
#define a (b & 1)
#define bb ((b >> 1) & 1)
  const uint32_t wbar = sb + BARS + 48, obar = wbar + 8;
  if (threadIdx.x == 256) {
    for (int i = 0; i < 18; i++) if (i != 12) mbar_init(sb + BARS + i * 8, i == 3 || i == 8 || i == 9 || i == 10 ? 2 : 1);
    for (int i = 0; i < 3; i++) mbar_init(sb + PACE + i * 8, 1);
    asm volatile("fence.mbarrier_init.release.cluster;" ::: "memory");
    FENCE_ASYNC_SMEM();
    mbar_expect(sb + BARS, 2048);
    mbar_expect(sb + BARS + 16, 4096);
    mbar_expect(sb + BARS + 32, 4096);
    mbar_expect(sb + BARS + 40, 4096);
  }
  __syncthreads();
  asm volatile("barrier.cluster.arrive.relaxed.aligned;" ::: "memory");
#define lane ((int)(l16 >> 4))
#define l16 (L16 & 0x1f0)
#define PIN(x) __shfl_xor_sync(~0u, (uint32_t)(x), 0)
#define X_LOAD(n, w, u) \
        asm volatile("{.reg .pred p; elect.sync _|p, 0xffffffff; @p mbarrier.arrive.expect_tx.shared.b64 _,[%2],8192;\n" \
                     "@p cp.async.bulk.shared::cluster.global.mbarrier::complete_tx::bytes [%0],[%1],8192,[%2];}" ::"r"(sb + XB + (w) * 16384 + (u) * 8192), \
                     "l"(g_h + (n) * 4096 + a * 2048 + (w) * 1024 + (u) * 512), "r"(sb + BARS + 64 + (w) * 8) : "memory")
#define lpub ((L16 & 0x30) * 64 + ((L16 >> 3) & 0x38))
#define lrow ((L16 & 0x70) + (((L16 >> 3) ^ L16) & 0x70 & ~((L16 >> 3) & 0x40) ? L16 & 0x180 : 512))

  const int role = __shfl_sync(~0u, threadIdx.x >> 7, 0);
  if (role < 2) {
    asm volatile("setmaxnreg.inc.sync.aligned.u32 %0;" ::"n"(RF_));
    ROLE_VARS
    uint32_t L16 = __shfl_sync(~0u, sb + (tid & 31) * 16, tid & 31);
    uint32_t wQ[16][4], wK[16][4], wV[NVR][4];
    uint32_t frag = sb + ((lane & 7) + (lane >> 4) * 8) * 128 + (((iw * 2 + ((lane >> 3) & 1)) ^ (lane & 7)) << 4);
#define QSW (a ? 0 : 64)
    {
      const bool spare = b >= 128;
      const uint32_t t0 = gtime();
      uint4 xr[16];
      int seg = spare ? b - 126 : wg;
      const int half = spare ? wg : a;
      auto x_fetch = [&]() {
        const uint4* px = (const uint4*)x + (seg * 32 + iw * 8 + (lane >> 2)) * 128 + half * 64 + (lane & 3);
#pragma unroll
        for (int i = 0; i < 16; i++) xr[i] = __ldg(px + i * 4);
      };
      if (!spare) {
        uint4 wm[8];
        const uint4* pw = (const uint4*)(wmod + (size_t)((b >> 5) * 256 + (tid >> 3)) * 6144 + (b & 31) * 64) + (tid & 7);
        const float cs = __bfloat162float(cvec[(b >> 5) * 256 + tid]);
#pragma unroll
        for (int i = 0; i < 8; i++) wm[i] = __ldcs(pw + (size_t)i * 32 * 768);
        float* sc = (float*)(smem + PRE);
        sc[tid] = rbf(silu(cs));
        PT(1);
        BAR_SYNC(B_F, 256);
        float acc[8] = {0, 0, 0, 0, 0, 0, 0, 0};
#pragma unroll
        for (int i = 0; i < 8; i++) {
          const float f = sc[i * 32 + (tid >> 3)];
          acc[0] += f * blo(wm[i].x); acc[1] += f * bhi(wm[i].x); acc[2] += f * blo(wm[i].y); acc[3] += f * bhi(wm[i].y);
          acc[4] += f * blo(wm[i].z); acc[5] += f * bhi(wm[i].z); acc[6] += f * blo(wm[i].w); acc[7] += f * bhi(wm[i].w);
        }
#pragma unroll
        for (int i = 0; i < 8; i++) { acc[i] += __shfl_xor_sync(~0u, acc[i], 8); acc[i] += __shfl_xor_sync(~0u, acc[i], 16); }
        float* red = sc + 1024;
        if ((tid & 31) < 8) {
#pragma unroll
          for (int i = 0; i < 8; i++) red[(tid >> 5) * 64 + (tid & 7) * 8 + i] = acc[i];
        }
        BAR_SYNC(B_F, 256);
        PT(2);
        if (tid < 64) {
          float t = 0;
#pragma unroll
          for (int i = 0; i < 8; i++) t += red[i * 64 + tid];
          asm volatile("st.relaxed.gpu.global.u32 [%0],%1;" ::"l"((unsigned*)g_modp + (b >> 5) * 2048 + (b & 31) * 64 + tid), "r"(U_(t) | 1u) : "memory");
        }
      } else {
        asm volatile("griddepcontrol.launch_dependents;");
      }
      x_fetch();
      const uint32_t md = sb + PRE + 6144, rx = mapa(sb, a ^ !spare);
      asm volatile("barrier.cluster.wait.aligned;" ::: "memory");
      if (!spare) {
        mbar_wait(sb + BARS + 88, 0);
#pragma unroll
        for (int i = 0; i < 16; i++) ldsm4t(wQ[i], (frag ^ QSW) + WO + wg * 32768 + i * 2048);
      }
      PT(4);
#pragma unroll 1
      for (int it = 0;; it++) {
        if (tid == 0) mbar_expect(sb + BARS + 104, 512);
        float c[4][4] = {{0, 0, 0, 0}, {0, 0, 0, 0}, {0, 0, 0, 0}, {0, 0, 0, 0}};
#pragma unroll
        for (int i = 0; i < 16; i++) {
          mma16(c[(i & 1) * 2], xr[i].x, 0x3f803f80u, xr[i].y, 0x3f803f80u, xr[i].x, xr[i].y);
          mma16(c[(i & 1) * 2 + 1], xr[i].z, 0x3f803f80u, xr[i].w, 0x3f803f80u, xr[i].z, xr[i].w);
        }
#pragma unroll
        for (int e = 0; e < 4; e++) c[0][e] = (c[0][e] + c[1][e]) + (c[2][e] + c[3][e]);
        const int src = (lane & 28) + (lane >> 3);
        const float sq = __shfl_sync(~0u, (lane & 4) ? c[0][1] : c[0][0], src), sm = __shfl_sync(~0u, (lane & 4) ? c[0][3] : c[0][2], src);
        if ((lane & 3) < 2) sta1<0>(rx + PRE + 10240 + (wid ^ (spare * 4)) * 64 + (lane >> 2) * 8 + (lane & 1) * 4, U_((lane & 1) ? sm : sq), rx + BARS + 104);
        mbar_wait(sb + BARS + 104, it & 1);
        const float2 ot = lds2f(sb + PRE + 10240 + wid * 64 + (lane >> 2) * 8);
        const float mean = (sm + ot.y) * (1.f / 1024);
        const float rs = rsqrtf(fmaxf((sq + ot.x) * (1.f / 1024) - mean * mean, 0.f) + 1e-5f), nm = -mean * rs;
        const uint32_t rh = pk(rs, rs), rl = pk(rs - blo(rh), rs - blo(rh)), n2 = pk(nm, nm);
#define NRM(v) v = fmabf(v, rh, fmabf(v, rl, n2))
#pragma unroll
        for (int i = 0; i < 16; i++) { NRM(xr[i].x); NRM(xr[i].y); NRM(xr[i].z); NRM(xr[i].w); }
        if (!it) {
          PT(3);
#pragma unroll 1
          for (int i = 0; i < 2; i++) {
            uint4 p[4];
            for (int n = 0;; n++) {
#pragma unroll
              for (int e = 0; e < 4; e++) p[e] = ldg_rlx4(g_modp + e * 512 + i * 256 + tid);
              uint32_t ok = 1;
#pragma unroll
              for (int e = 0; e < 4; e++) ok &= p[e].x & p[e].y & p[e].z & p[e].w;
              if (__all_sync(~0u, ok) || n > SPIN_LIMIT / 16) break;
              __nanosleep(100);
            }
#define MSUM(e) (i + rbf((F_(p[0].e) + F_(p[1].e)) + (F_(p[2].e) + F_(p[3].e))))
            sts2(md + i * 2048 + tid * 8, pk(MSUM(x), MSUM(y)), pk(MSUM(z), MSUM(w)));
          }
          BAR_SYNC(B_F, 256);
          PT(5);
        }
        const int e0 = (iw * 8 + (lane >> 2)) * 8 + ((lane & 3) ^ (lane >> 2));
        uint4* dst = g_h + seg * 4096 + half * 2048;
#pragma unroll
        for (int i = 0; i < 16; i++) {
          const uint32_t ma = md + half * 1024 + (lane & 3) * 16 + i * 64;
          const uint4 sv = lds4(ma), cv = lds4(ma + 2048);
          xr[i] = make_uint4(fmabf(xr[i].x, cv.x, sv.x), fmabf(xr[i].y, cv.y, sv.y), fmabf(xr[i].z, cv.z, sv.z), fmabf(xr[i].w, cv.w, sv.w));
        }
        if (!spare) {
#pragma unroll
          for (int i = 0; i < 16; i++) sts4(sb + WO + wg * 32768 + (e0 ^ ((i & 1) * 4)) * 16 + (i >> 1) * 4096, xr[i].x, xr[i].y, xr[i].z, xr[i].w);
          break;
        }
#pragma unroll
        for (int i = 0; i < 16; i++) dst[(e0 ^ ((i & 1) * 4)) + (i >> 1) * 256] = xr[i];
        seg += 4;
        if (seg < 64) x_fetch();
        FENCE_ASYNC();
        BAR_SYNC(B_F, 256);
        if (tid == 0) red_rlx(g_hf + b - 128);
        if (seg >= 64) break;
      }
      if (spare) { rec_helper(sb, cvec, wmod, w1, b1, t0); return; }
      PH(1); PH(2); PT(6);
    }
    ROLE_REFRESH
#define ownv ((iw >> 1) == a)
#define owner (iw >= 2)
#define oi (wid & 1)
    {
      const uint32_t rsb = mapa(sb, owner ? a : a ^ 1);
      const uint32_t pp = rsb + PK + (owner ? 0 : 12288) + (oi * 2048 + wg * 1024) + l16;
      const uint32_t mb = sb + MEM + wg * 5120;
      sts4(L16 + TF + wid * 512, mb + lrow, owner ? L16 + (lane >> 4) * (RK - RQ - 256) + RQ + oi * 1024 + wg * 256 : rsb + RQ + oi * 1024 + 512 + wg * 256 + (l16 >> 2),
           L16 + OB, frag + wg * NVS * 2048);
      sts4(L16 + TF + 4096 + wid * 512, sb + WO + (wid >> 1) * 16384 + ((lane & 7) + (lane >> 4) * 8) * 128 + ((((wid & 1) * 4 + ((lane >> 3) & 1)) ^ (lane & 7)) << 4),
           sb + ARO + wid * 640 + lrow, pp, LO(xc) + h * 262144 + (bb * 2 + (iw >> 1)) * XC + X_VM(0) + oi * 2048 + a * 256 + (l16 >> 1));
    }
    uint32_t tp = L16 + TF + wid * 512;
    auto park_ptr = [&]() { return lds1(tp + 4096 + 8); };
    auto park_w = [&](const uint32_t* w, int m, uint32_t d) {
      if (m == 2) d += (sb & 0x1000000) ? 0 : owner ? 0x1003000 : -0x1003000;
      if (m == 2 ? ownv : owner) {
        sts4(d + m * 4096, w[0], w[1], w[2], w[3]); sts4(d + m * 4096 + 512, w[4], w[5], w[6], w[7]);
      } else {
        const uint32_t pb = (d & 0xff000000u) | (1024 + BARS + (m ? 24 + m * 8 : 16));
        sta4(d + m * 4096, w, pb); sta4(d + m * 4096 + 512, w + 4, pb);
      }
    };
    auto park = [&](const float* f, int m, int n, uint32_t d) {
      uint32_t w[8];
#pragma unroll
      for (int i = 0; i < 8; i++) w[i] = pk(f[2 * i], f[2 * i + 1]);
      park_w(w, m, d);
    };
#define D64(lo) (0x4000004000000000ull | (uint32_t)(lo))
#define XD(i) D64(x | (((i) >> 2) * 256 + ((i) & 3) * 2))
    auto xdesc = [&](uint32_t xb) { return ((uint32_t)__shfl_sync(~0u, 1024 + xb + wg * 16384, 0) >> 4) | 0x10000u; };
    auto rs_issue = [&](float* acc, const uint32_t (&w)[16][4], uint32_t xb, bool fence) {
      const uint32_t x = xdesc(xb);
      if (fence) WG_FENCE();
      wgmma_rs_n32_z(acc, w[0], XD(0));
#pragma unroll
      for (int i = 1; i < 16; i++) wgmma_rs_n32(acc, w[i], XD(i), 1);
      WG_COMMIT();
    };
    auto v_issue = [&](float* acc, uint32_t xb, bool fence) {
      const uint32_t dv = ((uint32_t)__shfl_sync(~0u, 1024 + WVS + wg * NVS * 2048, 0) >> 4) | 0x10000u, x = xdesc(xb);
      if (fence) WG_FENCE();
      wgmma_rs_n32_z(acc, wV[0], XD(0));
#pragma unroll
      for (int i = 1; i < VRF; i++) wgmma_rs_n32(acc, wV[i], XD(i), 1);
#pragma unroll
      for (int i = NVR; i < 16; i++) wgmma_ssT_n32(acc, D64(dv + (i - NVR) * 128), XD(i), 1);
#pragma unroll
      for (int i = VRF; i < NVR; i++) wgmma_rs_n32(acc, wV[i], XD(i), 1);
      WG_COMMIT();
    };
    uint32_t mA, vP[2][4];
#define V_AHEAD mA = lds1(tp); frag = lds1(tp + 12); ldsm4t(vP[0], frag + WVS + (15 - NVR) * 2048); ldsm4t(vP[1], frag + WVS + (14 - NVR) * 2048);
    auto vk_pass = [&](int n, uint32_t d) {
      float acc[16], acc2[16];
      v_issue(acc, XB, true);
      rs_issue(acc2, wK, XB, false);
      if (n < 64) mbar_wait(sb + BARS + 80, (n - 1) & 1);
      WG_WAIT(1);
      if (n < 64) {
        park(acc, 2, n, d);
        BAR_ARRIVE(B_K, 320);
      }
      V_AHEAD
      WG_WAIT(0);
      if (n < 64) park(acc2, 1, n, d + (VPC ? (vP[1][0] ^ mA) & dZ : 0));
    };
    uint32_t q0[8], q1[8];
    {
      float acc[16], acc2[16];
      FENCE_ASYNC_SMEM();
      BAR_SYNC(B_F, 256);
      rs_issue(acc, wQ, WO, true);
      rs_issue(acc2, wQ, WO + 32768, false);
      WG_WAIT(0);
#pragma unroll
      for (int i = 0; i < 8; i++) { q0[i] = pk(acc[2 * i], acc[2 * i + 1]); q1[i] = pk(acc2[2 * i], acc2[2 * i + 1]); }
    }
    mbar_wait(wbar, 0);
    PT(7);
#pragma unroll
    for (int i = 0; i < 16; i++) ldsm4t(wK[i], (frag ^ QSW) + XB + wg * 32768 + i * 2048);
#pragma unroll
    for (int i = 0; i < NVR; i++) ldsm4t(wV[i], frag + MEM + (wg * NVR + i) * 2048);
    FENCE_ASYNC_SMEM();
    PH(3); PT(8);
    CLUSTER_SYNC();
    PT(9);
    frag += wg * NVS * 2048;
    park_w(q0, 0, park_ptr());
    uint32_t k1[8];
    {
      float acc[16], acc2[16];
      asm volatile("" : "+r"(wid));
      rs_issue(acc, wK, WO, true);
      rs_issue(acc2, wK, WO + 32768, false);
      WG_WAIT(0);
      park(acc, 1, 0, park_ptr());
#pragma unroll
      for (int i = 0; i < 8; i++) k1[i] = pk(acc2[2 * i], acc2[2 * i + 1]);
    }
    mbar_wait(sb + BARS + 120, 0);
    PT(10);
#pragma unroll 1
    for (int n = 0; n < 2; n++) {
      float acc[16];
      asm volatile("" : "+r"(wid));
      v_issue(acc, n * XB, true);
      if (n) {
        BAR_SYNC(B_C, 320);
        PT(12);
        mbar_wait(sb + BARS + 24, 0);
        park_w(q1, 0, park_ptr());
        mbar_wait(sb + BARS + 80, 0);
        park_w(k1, 1, park_ptr());
      }
      WG_WAIT(0);
      park(acc, 2, n, park_ptr());
      if (n) break;
      PT(11);
      BAR_SYNC(B_C, 448);
      if (tid == 0) {
        mbar_expect(obar, 65536);
#pragma unroll 1
        for (int i = 0; i < 4; i++) tma2d(sb + WO + i * 16384, &mp.wo, j * 256 + i * 64, h * 128, obar);
      }
    }
    V_AHEAD
    CONSUME(vP[1][0]);
    static_assert(WO == 0, "x");
    {
      BAR_ARRIVE(B_P, 384); BAR_ARRIVE(B_X, 320); BAR_ARRIVE(B_Q, 288);
    }
    PT(13);
    PH(4); RS(1); PT(14);
    ROLE_REFRESH
    for (int s = 0; s < 64; s++) {
      asm volatile("" : "+r"(tp), "+r"(wid));
      asm volatile("mov.u32 %0,%%cluster_ctarank;" : "=r"(b));
      uint32_t vS[NVS][4], bf[8][4];
      static_assert(NVR == 5, "schedule");
#define VLD(k) ldsm4t(vS[(k) - NVR], frag + WVS + ((k) - NVR) * 2048)
#define BLD(t) ldsm4t(bf[t], mA + (t) * 640)
#define VMMA(c, w, i) mma16(c, (w)[0], (w)[1], (w)[2], (w)[3], bf[(i) >> 1][((i) & 1) * 2], bf[(i) >> 1][((i) & 1) * 2 + 1])
#define VS_(c, k) VMMA(c, vS[(k) - NVR], k)
#define QK(i) VMMA(cQ, wQ[i], i); VMMA(cK, wK[i], i)
#define PREV VLD(13); VLD(12); if (NF > 2) VLD(11);
      if (s > 0) BAR_SYNC(B_R, 320);
      float cV[4] = {0, 0, 0, 0}, cW[4] = {0, 0, 0, 0};
      {
        float cQ[4] = {0, 0, 0, 0}, cK[4] = {0, 0, 0, 0};
        BLD(7); BLD(6); BLD(5); BLD(4); if (NB0 > 4) BLD(3);
        SCHED_FENCE(47);
        QK(15); VMMA(cV, vP[0], 15);
        QK(14); VMMA(cV, vP[1], 14);
        QK(13); QK(12);
        SCHED_FENCE(51);
        if (NB0 < 5) BLD(3);
        BLD(2); BLD(1); BLD(0);
        const uint32_t rm = lds1(tp + 4);
        QK(11); QK(10); QK(9); QK(8); QK(7);
        if (PV0 == 6) { SCHED_FENCE(48); PREV }
        QK(6); QK(5);
        if (PV0 == 4) { QK(4); SCHED_FENCE(48); PREV } else { QK(4); }
        QK(3); QK(2); QK(1); QK(0);
        const uint32_t w0 = pk(cQ[0] * SCS, cQ[1] * SCS), w1 = pk(cQ[2] * SCS, cQ[3] * SCS), w2 = pk(cK[0], cK[1]), w3 = pk(cK[2], cK[3]);
        if (owner) {
          stsm4(rm, w0, w1, w2, w3);
          BAR_ARRIVE(B_E, 256);
        } else {
          const uint32_t mm = (rm & 0xff000000u) | (1024 + BARS);
          sta1<0>(rm, w0, mm); sta1<128>(rm, w1, mm);
          sta1<RK - RQ>(rm, w2, mm); sta1<RK - RQ + 128>(rm, w3, mm);
        }
        if (wid == 2) TS(0);
      }
      uint4 t1;
      uint32_t oA, wo[16][4];
      {
        DLY(10)
        if (NF < 3) VLD(11);
        VLD(10);
        VS_(cW, 13); VLD(9); VS_(cV, 12); VLD(8); VLD(7); VMMA(cW, wV[0], 0); VMMA(cV, wV[1], 1); VLD(6);
        VMMA(cW, wV[2], 2); VMMA(cV, wV[3], 3); VLD(5); VMMA(cW, wV[4], 4); VS_(cV, 11);
        VS_(cW, 10); VS_(cV, 9); VS_(cW, 8); VS_(cV, 7); VS_(cW, 6); VS_(cV, 5);
#pragma unroll
        for (int e = 0; e < 4; e++) cV[e] += cW[e];
        const uint32_t ex = tp + (RX - TF) - wg * 2048;
        t1 = lds4(tp + 4096 + (T1L ? vS[3][0] & dZ : 0));
        oA = lds1(tp + 8 + (s & dZ));
        if (wg) {
          sts4(ex, U_(cV[0]), U_(cV[1]), U_(cV[2]), U_(cV[3]));
          BAR_ARRIVE(B_T2, 256);
        }
        if (!wg) {
          BAR_SYNC(B_T2, 256);
          DLY(3)
          const float4 u = lds4f(ex);
          stg_b64(mkp(t1.w ^ ((s & 1) * X_RING), HI(xc)), (pk(cV[0] + u.x, cV[1] + u.y) & ~1u) | (((s >> 1) + 1) & 1), pk(cV[2] + u.z, cV[3] + u.w));
        }
      }
      if (s == 63) break;
      if (s == 0) mbar_wait(obar, 0);
      {
        const uint32_t woA = t1.x, woB = woA ^ 32;
#pragma unroll
        for (int i = 0; i < NW0; i++) ldsm4t(wo[i], ((i & 1) ? woB : woA) + (i >= WCH ? wo[(i - WCH + NWP) % NWP][0] & dZ : 0) + (i >> 1) * 2048);
        DLY(2)
        BAR_SYNC(B_S, 416);
        float inv0, inv1;
        uint32_t p[4], pm;
        const uint32_t pa = oA + (SC - OB), one = 0x3f803f80u;
#define P_LOAD ldsm4t(p, pa); asm volatile("ldmatrix.sync.aligned.m8n8.x1.trans.shared.b16 {%0},[%1];" : "=r"(pm) : "r"(pa + 512) : "memory");
        if (s < 62) {
          float acc[16];
          rs_issue(acc, wQ, XB, true);
          mbar_wait(sb + BARS + 24, (s + 1) & 1);
          WG_WAIT(0);
          uint32_t qw[8];
#pragma unroll
          for (int i = 0; i < 8; i++) qw[i] = pk(acc[2 * i], acc[2 * i + 1]);
          if (PKE == 1) park_w(qw, 0, t1.z);
#pragma unroll
          for (int i = NW0; i < NW1; i++) ldsm4t(wo[i], ((i & 1) ? woB : woA) + (i >> 1) * 2048);
          BAR_SYNC(B_V, 512);
          if (PKE == 2) park_w(qw, 0, t1.z);
          P_LOAD
          if (PKE == 0) park_w(qw, 0, t1.z);
        } else {
#pragma unroll
          for (int i = NW0; i < NW1; i++) ldsm4t(wo[i], ((i & 1) ? woB : woA) + (i >> 1) * 2048);
          BAR_SYNC(B_V, 512);
          P_LOAD
        }
#pragma unroll
        for (int i = NW1; i < NWP; i++) ldsm4t(wo[i], ((i & 1) ? woB : woA) + (i >> 1) * 2048);
        {
          float sum[4] = {0, 0, 0, 0}, su2[4] = {0, 0, 0, 0};
          mma16(sum, one, one, one, one, p[0], p[1]);
          mma16(su2, one, one, one, one, p[2], p[3]);
          mma8(sum, one, one, pm);
          inv0 = sum[0] + su2[0]; inv1 = sum[1] + su2[1];
          SCHED_FENCE(57);
        }
        DLY(7)
        BAR_SYNC(B_O, 416);
        float c[2][4] = {{0, 0, 0, 0}, {0, 0, 0, 0}};
        uint32_t o[4][4];
#pragma unroll
        for (int i = 0; i < NOP_; i++) ldsm4t(o[i], oA + i * 512);
        SCHED_FENCE(46);
        asm("rcp.approx.ftz.f32 %0,%0;" : "+f"(inv0));
        asm("rcp.approx.ftz.f32 %0,%0;" : "+f"(inv1));
#pragma unroll
        for (int i = 0; i < 16; i++) {
          mma16(c[i & 1], wo[i][0], wo[i][1], wo[i][2], wo[i][3], o[i >> 2][i & 2], o[i >> 2][(i & 2) + 1]);
          if (i == 1 && NOP_ < 3) ldsm4t(o[2], oA + 1024);
          if (i == 3 && NOP_ < 4) ldsm4t(o[3], oA + 1536);
          if (i + NWP < 16) ldsm4t(wo[(i + NWP) & 15], (((i + NWP) & 1) ? woB : woA) + ((i + NWP) >> 1) * 2048);
        }
        stsm4(t1.y, pk(c[0][0] * inv0, c[0][1] * inv1), pk(c[0][2] * inv0, c[0][3] * inv1), pk(c[1][0] * inv0, c[1][1] * inv1), pk(c[1][2] * inv0, c[1][3] * inv1));
      }
      const uint32_t d = park_ptr();
      BAR_SYNC(B_W, 384);
      DLY(1)
      vk_pass(s + 2, d);
      if (s < 62) { BAR_ARRIVE(B_P, 384); BAR_ARRIVE(B_X, 320); }
      TS(10);
    }
  } else if (role == 3) {
    asm volatile("setmaxnreg.dec.sync.aligned.u32 24;");
    if (blockIdx.x >= 128) return;
    ROLE_VARS
    const uint32_t L16 = sb + (tid & 31) * 16;
    asm volatile("barrier.cluster.wait.aligned;" ::: "memory");
    CLUSTER_SYNC();
    sts1(sb + PACE + 36, LO(xc) + h * 262144 + X_VM(0));
#define V_LOAD(n) asm volatile("{.reg .pred p; elect.sync _|p, 0xffffffff; @p mbarrier.arrive.expect_tx.shared.b64 _,[%3],8192;\n" \
        "@p cp.async.bulk.tensor.5d.shared::cluster.global.mbarrier::complete_tx::bytes [%0],[%1,{0,0,0,0,%2}],[%3];}" \
        ::"r"(sb + VX0), "l"(&mp.vx), "r"(h * 64 + (V_RING(n) >> 12)), "r"(sb + BARS + 8) : "memory")
    auto vm_stage = [&](int s) {
      const uint32_t tag = ((s >> 1) + 1) & 1;
      const char* xm = mkp(lds1(sb + PACE + 36) + (s & 1) * X_RING + iw * XC + (l16 >> 1), HI(xc));
      uint2 m[4];
      CONSUME(LO(xm));
      BAR_SYNC(B_S2, 256);
      DLY(4)
      int it = 0;
      while (true) {
#pragma unroll
        for (int i = 0; i < 4; i++) m[i] = ldg_b64(xm + (i >> 1) * 2048 + (i & 1) * 256);
        sts4(L16 + VN + iw * 512, m[0].x, m[0].y, m[1].x, m[1].y);
        sts4(L16 + VN + iw * 512 + 2048, m[2].x, m[2].y, m[3].x, m[3].y);
        if (!anybad(m[0].x, m[1].x, m[2].x, m[3].x, tag)) break;
        RP(2);
        if (++it > SPIN_LIMIT) __trap();
      }
      if (s < 63) BAR_ARRIVE(B_V, 512); else BAR_ARRIVE(B_V, 256);
    };
    if (iw == 0) {
      wait_cnt(&g_hcnt, 128);
#pragma unroll 1
      for (int s = 0; s < 63; s++) {
        if (s < 62) for (int it = 0; ldg_rlx1(g_hf + (s & 3)) <= (s >> 2); it++) if (it > SPIN_LIMIT) __trap();
        if (s) BAR_SYNC(B_R, 320); else BAR_SYNC(B_Q, 288);
        if (s < 62) { X_LOAD(s + 2, 0, 0); X_LOAD(s + 2, 1, 0); X_LOAD(s + 2, 0, 1); X_LOAD(s + 2, 1, 1); }
        if (s >= 7) {
          const uint32_t zo = b * 160 + l16;
          if (l16 < 160) CONSUME(exch_b128(xc + AR_OFF + AR_ROW(zo >> 7) * 1024 + (zo & 127) + ((s + 1) & 7) * 128, 0, 0, 0, 0).x);
          __syncwarp();
        }
        if (s < 62) { mbar_wait(sb + BARS + 64, s & 1); mbar_wait(sb + BARS + 72, s & 1); }
        BAR_ARRIVE(B_S, 416);
        vm_stage(s);
        BAR_ARRIVE(B_O, 416);
        BAR_SYNC(B_W, 384);
        DLY(8)
        FENCE_ASYNC_SMEM();
        asm volatile("{.reg .pred p; elect.sync _|p, 0xffffffff; @p cp.reduce.async.bulk.tensor.3d.global.shared::cta.add.bulk_group [%0,{%1,%4,%2}],[%3];}"
                     ::"l"(&mp.ari), "r"((s & 7) * 64), "r"(AR_R(j)), "r"(sb + ARO), "r"(AR_P(j)) : "memory");
        BULK_COMMIT();
        asm volatile("st.relaxed.gpu.global.u32 [%0],%1;" ::"l"(g_tm + (s & 1) * 128 + b), "r"(gtime()) : "memory");
        TS(3);
        BULK_WAIT_READ(0);
      }
      BAR_ARRIVE(B_R, 320);
    } else if (iw == 1) {
      const uint32_t pc = sb + MEM + (lane >> 2) * 640 + (lane & 3) * 144 + (lane & 12), pd = sb + MEM + (lane & 15) * 640 + 576 + (lane & 3) * 16 + (lane & 12);
      uint32_t T = 0, par = 0;
      int est = dA;
#pragma unroll 1
      for (int s = 0; s < 63; s++) {
        if (s) {
          const uint4 tm = ldg_rlx4((const char*)g_tm + ((s + 1) & 1) * 512 + l16);
          const int t0 = tm.x - T, t1 = tm.y - T, t2 = tm.z - T, t3 = tm.w - T;
          const int e = max(dF + (__reduce_add_sync(~0u, (t0 + t1) + (t2 + t3)) >> 7), dV + __reduce_max_sync(~0u, max(max(t0, t1), max(t2, t3))));
          if (s > 1) est += max(min(e >> 2, dP), -dP);
          T += (s == 1 || e > dM ? e : 0) + est - (s == 62 ? L62 : 0);
        }
        vm_stage(s);
        BAR_SYNC(B_W, 384);
        SCHED_FENCE(70);
        const uint32_t tW = gtime();
        if (s == 0) T = tW + 800;
        const uint32_t te = tW + min(max((int)(T - tW), dD), 2000);
        while ((int)(gtime() - te) < 0) {}
        TS(7);
        int it = 0;
        while (true) {
          ar_fetch(sb + MEM, &mp.ari, s & 7, a, sb + BARS + 112);
          mbar_wait(sb + BARS + 112, par);
          par ^= 1;
          const uint32_t n0 = lds1(pc), n1 = lds1(pc + 5120), n2 = lds1(pd);
          if (!__any_sync(~0u, (tagbad(n0, n1, 0x42004200) | (n2 ^ 0x42004200)) != 0)) break;
          RP(0);
          if (++it > SPIN_LIMIT) __trap();
        }
        BAR_ARRIVE(B_R, 320);
        TS(11);
      }
    } else {
      uint32_t src = L16 + PK + (iw & 1) * 2048;
#define qd (L16 + (lane >> 4) * 256 + QT + (iw & 1) * 1024)
#define vd (LO(xc) + h * 262144 + j * XC + (iw & 1) * 2048 + l16)
#define FINISH [&](int n, int m) { \
_Pragma("unroll") \
        for (int i = 1; i >= 0; i--) { \
          const uint32_t p = src + m * 4096 + i * 512; \
          uint4 u = lds4(p); \
          const uint4 w = lds4(p + 1024), y = lds4(p + 12288), z = lds4(p + 13312); \
          u = make_uint4(sum4bf(u.x, w.x, y.x, z.x), sum4bf(u.y, w.y, y.y, z.y), sum4bf(u.z, w.z, y.z, z.z), sum4bf(u.w, w.w, y.w, z.w)); \
          if (m == 2) stg_b128(mkp(vd ^ V_RING(n), HI(xc)) + i * 512, (u.x & ~1u) | V_TAG(n), u.y, u.z, u.w); \
          else stsm4(qd + (n & 1) * 4096 + m * 2048 + i * 256, u.x, u.z, u.y, u.w); \
          SCHED_FENCE(71 + m * 2 + i); \
        } \
      }
#pragma unroll 1
      for (int n = 0; n < 64; n++) {
        src = PIN(src);
        b = __shfl_sync(~0u, lds1(sb + PACE + 24), 0);
        const uint32_t L16 = src - PK - (iw & 1) * 2048;
        auto finish = FINISH;
        if (n < 2) { if (n) BAR_SYNC(B_X, 320); else BAR_SYNC(B_C, 448); }
        mbar_wait(sb + BARS + 16, n & 1);
        if (n > 1) { const uint32_t c = clk(); while (clk() - c < (uint32_t)dQ) {} }
        finish(n, 0);
        __syncwarp();
        if (lane == 0) mbar_arrive_cl(mapa(sb, a ^ 1) + BARS + 24);
        if (n > 1) BAR_SYNC(B_K, 320);
        mbar_wait(sb + BARS + 40, n & 1);
        finish(n, 2);
        if (n > 1) BAR_SYNC(B_X, 320);
        mbar_wait(sb + BARS + 32, n & 1);
        DLY(11)
        finish(n, 1);
        BAR_SYNC(B_T, 64);
        if (lane == 0) {
          if (iw == 2 && n < 63) { mbar_expect(sb + BARS + 16, 4096); mbar_expect(sb + BARS + 32, 4096); mbar_expect(sb + BARS + 40, 4096); }
          mbar_arrive_cl(mapa(sb, a ^ 1) + BARS + 80);
        }
        __syncwarp();
        if (n) {
          vm_stage(n - 1);
          BAR_SYNC(B_W, 384);
          DLY(15)
        } else {
          BAR_SYNC(B_C, 320);
        }
        if (iw == 2) V_LOAD(n);
      }
#undef qd
#undef vd
    }
    { ROLE_REFRESH }
    vm_stage(63);
  } else {
    asm volatile("setmaxnreg.dec.sync.aligned.u32 %0;" ::"n"(RA_));
    if (blockIdx.x >= 128) { if (threadIdx.x == 256) rec_prefetch((const char*)wmod, w1, (const char*)x, wo); return; }
    ROLE_VARS
    uint32_t L16 = __shfl_sync(~0u, sb + (tid & 31) * 16, tid & 31);
    asm volatile("barrier.cluster.wait.aligned; barrier.cluster.arrive.relaxed.aligned;" ::: "memory");
    const uint32_t ts = gtime();
    uint2 m0[8];
#pragma unroll
    for (int r = 0; r < 8; r++) m0[r] = *(const uint2*)(mem0 + r * 1024 + a * 512 + (tid - 256) * 4);
    if (wid == 9) {
#pragma unroll 1
      for (int i = b * 80 + (tid & 31); i < b * 80 + 80; i += 32) ((uint4*)(xc + AR_OFF))[AR_ROW(i >> 6) * 64 + (i & 63)] = make_uint4(0, 0, 0, 0);
      if (b == 0) g_fin = 0;
      FENCE_ASYNC();
      __syncwarp();
      if (tid == 288) red_rlx(&g_hcnt);
    }
    if (tid == 256) {
      const int col = h * 128 + bb * 64;
#pragma unroll 1
      for (int c = 0, w = 0; w < 12; c++) {
#pragma unroll 1
        for (; w <= c - (c < WC0 ? 2 : 3); w++) {
          mbar_wait(sb + PACE + (w % 3) * 8, (w / 3) & 1);
          PT(18 + w);
          if (w == 3) mbar_arrive(sb + BARS + 88);
          if (w == 8) mbar_arrive(wbar);
        }
        const uint32_t mb = sb + PACE + (c % 3) * 8;
        if (c >= 12 && c < 12 + WPE) tma2d_pf(&mp.wo, j * 256 + (c - 12) * 64, h * 128);
        if (c >= 12) continue;
        if (c < 9 && c != 4) {
          const int u = c > 4 ? c - 5 : c;
          mbar_expect(mb, 16384);
          tma2d(sb + (c > 4) * XB + u * 16384, c > 4 ? &mp.wk : &mp.wq, col, a * 512 + u * 128, mb);
        } else {
          const int n = c == 4 ? NVR : NVS, i0 = c == 4 ? 0 : (c - 9) * 8, i1 = c == 4 ? 2 * NVR : min(i0 + 8, 2 * NVS);
          mbar_expect(mb, (i1 - i0) * 2048);
#pragma unroll 1
          for (int i = i0; i < i1; i++)
            tma2d(sb + (c == 4 ? MEM : WVS) + i * 2048, &mp.wv, col, a * 512 + (i >= n ? 16 - n + i : i) * 16 + (c == 4 ? 0 : NVR * 16), mb);
        }
      }
      mbar_arrive(sb + BARS + 120);
      for (int i = 0; i < 3; i++) asm volatile("mbarrier.inval.shared.b64 [%0];" ::"r"(sb + PACE + i * 8) : "memory");
    }
    __syncwarp();
    asm volatile("barrier.cluster.wait.aligned;" ::: "memory");
#pragma unroll 4
    for (int i = 0; i < 16; i++) {
      const uint4 v = lds4(L16 + WO + 32768 + iw * 8192 + i * 512);
      sts4(L16 + XB + iw * 8192 + i * 512, v.x, v.y, v.z, v.w);
    }
#pragma unroll
    for (int i = 0; i < 4; i++) {
      const int k = (tid - 256) * 4 + i, m = (k >> 3) & 3, r = k & 7;
#define M0W(r) __byte_perm((i & 2) ? m0[r].y : m0[r].x, (i & 2) ? m0[r + 1].y : m0[r + 1].x, (i & 1) ? 0x7632 : 0x5410)
      sts4(sb + MEM + (k >> 5) * 640 + (r == m ? 512 : m * 128) + r * 16, M0W(0), M0W(2), M0W(4), M0W(6));
    }
#pragma unroll 1
    for (int i = tid - 256; i < 192; i += 128) {
      const uint32_t c = i < 128 ? 0x42004200 : 0x3f803f80;
      sts4(sb + MEM + (i >> 3) * 640 + ((i & 7) < 4 ? (i & 7) * 144 : 512 + (i & 7) * 16), c, c, c, c);
    }
    static_assert(ARO == MEM + 16 * 640, "counters");
    FENCE_ASYNC_SMEM();
    BAR_ARRIVE(B_C, 448);
    if (tid == 256) {
      wait_time(ts + 1);
#pragma unroll 1
      for (int c = WPE; c < 4; c++) tma2d_pf(&mp.wo, j * 256 + c * 64, h * 128);
    }
    __syncwarp();
#define pr (L16 + SC)
    {
      const int lim = j * 8 + iw * 2 - (lane & 7) - (lane & 8) * 2;
      const bool mk = L16 & 256;
      const int rw = lane >> 2;
      sts4(L16 + TA + iw * 512,
           iw != 2 ? L16 + KT + (iw & 1) * 256 + (lane >> 4) * 256 : sb + RK + (L16 & 0x80) * 2 + ((L16 >> 1) & 0x80) + (L16 & 0x70),
           L16 + QT + (lane >> 3) * 384, sb + SC + min(lane >> 3, 2) * 256 + (L16 & 0x70) + iw * 4, L16 + (lane >> 4) * 256 + QT + (iw >> 1) * 1024 + (iw & 1) * 256);
      sts4(L16 + TA + 2048 + iw * 512, mk ? 0u : (lim < 0 ? 0xfc00u : 0u) | (lim < -1 ? 0xfc000000u : 0u),
           mk ? 0xfc00fc00u : (lim < 8 ? 0xfc00u : 0u) | (lim < 7 ? 0xfc000000u : 0u),
           ((h * 2 + (iw >> 1)) * 1024 + (j * 8 + rw) * 8 + (((iw & 1) * 4 + (lane & 3)) ^ rw)) * 16, sb + OT + iw * 512 + (L16 & 0x70) * 4 + ((L16 >> 3) & 0x30));
    }
    {
      const uint32_t xh = LO(xc) + h * 262144, xs = xh + X_SC + iw * 1024 + min(lane, 16 + (lane & 7)) * 8;
      sts4(L16 + TA + 4096 + iw * 512, xh + X_SC + j * 256 + iw * 64 + lpub, xs, dS, iw != 2 ? 0 : U_(SCS));
      sts1(L16 + TA + 12 + iw * 512, xs + X_TOK + j * 4096);
    }
    uint32_t tA = L16 + TA + iw * 512;
#define tw (tA - L16 != TA + 1024)
#define XP_(lo) mkp(lo, HI(xc))
    auto publish = [&](char* d, const uint2& w) { stg_b64(d, w.x, w.y); };
    BAR_SYNC(B_P, 384);
    for (int s = 0; s < 64; s++) {
      asm volatile("" : "+r"(L16), "+r"(tA));
      const uint32_t tag = ((s >> 1) + 1) & 1, ring = (s & 1) * X_RING;
      const uint4 t0 = lds4(tA);
      const uint4 tx = lds4(tA + 4096);
      const uint32_t xo = tx.x ^ ring, xs = tx.y ^ ring;
      const float gm = F_(tx.w);
      const uint32_t qA = t0.y + (ring >> 5);
      uint32_t c0;
      uint2 ts[4];
      uint4 v[4];
      uint32_t af[2][4], qt[4][4];
      {
        const uint32_t aA = t0.x + (tw ? ring >> 5 : 0);
        uint32_t ql[2][4], qr[2][4];
        uint2 pw_;
        float c[4] = {0, 0, 0, 0}, d[4] = {0, 0, 0, 0};
        if (s == PDS) asm volatile("griddepcontrol.launch_dependents;");
#pragma unroll
        for (int i = 0; i < 4; i++) ldsm4t(qt[i], qA + i * 128);
        mbar_wait(sb + BARS + 8, s & 1);
        TS(4);
        BAR_SYNC(B_E, 256);
        DLY(14)
#define PACK(c) make_uint2(pkh(fmaf(c[2], gm, c[0] * SCS), fmaf(c[3], gm, c[1] * SCS), tag), pkh(c[2] * SCS, c[3] * SCS, tag))
        ldsm4t(ql[0], L16 + RQ); ldsm4t(ql[1], L16 + RQ + 1024); ldsm4t(af[0], aA); ldsm4t(af[1], aA + 1024);
        CONSUME(xo);
#define QSUM(t, i) addbf(addbf(ql[t][i], ql[t][i + 2]), addbf(qr[t][i], qr[t][i + 2]))
#define STAIL mma16(c, af[0][0], af[0][1], af[0][2], af[0][3], QSUM(0, 0), QSUM(0, 1)); mma16(d, af[1][0], af[1][1], af[1][2], af[1][3], QSUM(1, 0), QSUM(1, 1));
        if (tw) {
          mbar_wait(sb + BARS, s & 1);
          TS(8);
          ldsm4t(qr[0], L16 + RQ + 512); ldsm4t(qr[1], L16 + RQ + 1536);
          STAIL
          pw_ = make_uint2(pkh(c[0] + d[0], c[1] + d[1], tag), pkh(c[2] + d[2], c[3] + d[3], tag));
        } else {
          uint32_t ar[2][4];
          mbar_wait(sb + BARS, s & 1);
          ldsm4t(qr[0], L16 + RQ + 512); ldsm4t(ar[0], aA + 512); ldsm4t(qr[1], L16 + RQ + 1536); ldsm4t(ar[1], aA + 1536);
#pragma unroll
          for (int i = 0; i < 8; i++) af[i >> 2][i & 3] = addbf(af[i >> 2][i & 3], ar[i >> 2][i & 3]);
          STAIL
          pw_.x = pw_.y = pkh((c[0] + c[2]) + (d[0] + d[2]), (c[1] + c[3]) + (d[1] + d[3]), tag);
        }
        publish(XP_(xo), pw_);
        c0 = clk() + tx.z;
        TS(1);
      }
      uint2 r[4];
      bool vbad;
      uint4 vn[2];
      {
        float e[4][4];
#pragma unroll
        for (int i = 0; i < 4; i++) {
          e[i][0] = e[i][1] = e[i][2] = e[i][3] = 0.f;
          mma16(e[i], af[0][0], af[0][1], af[0][2], af[0][3], qt[i][0], qt[i][1]);
        }
#pragma unroll
        for (int i = 0; i < 4; i++) mma16(e[i], af[1][0], af[1][1], af[1][2], af[1][3], qt[i][2], qt[i][3]);
        SCHED_FENCE(55);
        if (s < 63) BAR_ARRIVE(B_S, 416);
        SCHED_FENCE(58);
        v[0] = lds4(tA + (VX0 - TA)); v[1] = lds4(tA + (VX0 - TA) + 2048); v[2] = lds4(tA + (VX1 - TA)); v[3] = lds4(tA + (VX1 - TA) + 2048);
#pragma unroll
        for (int i = 0; i < 4; i++) ts[i] = PACK(e[i]);
        vbad = anybad(v[0].x, v[1].x, v[2].x, v[3].x, V_TAG(s));
        while ((int)(clk() - c0) < 0) {}
        TS(5);
#pragma unroll
        for (int u = 0; u < 4; u++) r[u] = ldg_b64(XP_(xs) + u * 256);
        BAR_ARRIVE(B_S2, 256);
      }
      SCHED_FENCE(56);
      uint32_t kk;
      float4 e = softmax2<false>(r, 0, 0, kk);
      if (__builtin_expect(anybad(r[0].x, r[0].y, r[1].x, r[1].y, r[2].x, r[2].y, r[3].x, r[3].y, tag ^ (kk & dZ)), 0)) {
        int it = 0;
        if (s > 8) sts1(tA + 4096 + 8, min(lds1(tA + 4096 + 8) + dX, 500));
        do {
          RP(1);
          if (++it > SPIN_LIMIT) __trap();
#pragma unroll
          for (int u = 0; u < 4; u++) r[u] = ldg_b64(XP_(xs) + u * 256);
        } while (BADS(r));
        e = softmax2<false>(r, 0, 0, kk);
      }
      DLY(5)
      sts1(t0.z, pk(e.x, e.y)); sts1(t0.z + 128, pk(e.z, e.w));
#pragma unroll
      for (int i = 0; i < 4; i++) publish(XP_(xo) + X_TOK + i * 4096, ts[i]);
      TS(6);
      if (s < 63) BAR_SYNC(B_V, 512); else BAR_SYNC(B_V, 256);
      uint32_t O[4];
      {
        uint32_t p[4], pm;
        ldsm4t(p, pr);
        asm volatile("ldmatrix.sync.aligned.m8n8.x1.trans.shared.b16 {%0},[%1];" : "=r"(pm) : "r"(pr + 512) : "memory");
        vn[0] = lds4(tA + (VN - TA)); vn[1] = lds4(tA + (VN - TA) + 2048);
        pv_mem(p, pm, v, vn, O);
        if (__builtin_expect(vbad, 0)) {
          int it = 0;
          const uint32_t xv = LO(xc) + (lds1(sb + PACE + 24) >> 2) * 262144 + ((tA - L16 - TA) >> 9) * XC;
          do {
            RP(2);
            if (++it > SPIN_LIMIT) __trap();
#pragma unroll
            for (int u = 0; u < 4; u++) v[u] = ldg_b128(XP_((xv + l16) ^ V_RING(s)) + X_VX(u));
          } while (anybad(v[0].x, v[1].x, v[2].x, v[3].x, V_TAG(s)));
          pv_mem(p, pm, v, vn, O);
        }
      }
      DLY(6)
      stsm4(tA + (OB - TA), O[0], O[1], O[2], O[3]);
      if (s < 63) BAR_ARRIVE(B_O, 416);
      TS(2);
      c0 = clk() + dG;
      SCHED_FENCE(60);
      if (tA == sb + TA) mbar_expect(sb + BARS, 2048);
      const uint32_t vs[4] = {addbf(vn[0].x, vn[0].z), addbf(vn[0].y, vn[0].w), addbf(vn[1].x, vn[1].z), addbf(vn[1].y, vn[1].w)};
      {
        const char* xt = XP_(lds1(tA + 12) ^ ring);
        const uint2 t1 = lds2u(tA + 2048);
        const uint32_t pw = lds1(tA + 8);
        uint2 rt[4];
        CONSUME(LO(xt) ^ t1.x ^ pw);
        while ((int)(clk() - c0) < 0) {}
        int it = 0;
        do {
          if (++it > SPIN_LIMIT) __trap();
#pragma unroll
          for (int u = 0; u < 4; u++) rt[u] = ldg_b64(xt + u * 256);
        } while (BADS(rt));
        uint32_t kt;
        const float4 et = softmax2<true>(rt, t1.x, t1.y, kt);
        sts1(pw + 1024, pk(et.x, et.y)); sts1(pw + 1024 + 128, pk(et.z, et.w));
      }
      s = PIN(s);
      BAR_SYNC(B_SC, 128);
      {
        uint32_t Ot[4], p[4], pm;
        const uint2 t2 = lds2u(tA + 2048 + 8);
        ldsm4t(p, pr + 1024);
        asm volatile("ldmatrix.sync.aligned.m8n8.x1.trans.shared.b16 {%0},[%1];" : "=r"(pm) : "r"(pr + 1024 + 512) : "memory");
        char* od = (char*)g_O + ((s >> 2) * 1048576 + (s & 3) * 4096) + t2.x;
        CONSUME(LO(od) ^ HI(od) ^ pm ^ p[3]);
        TS(9);
        if (s < 62) BAR_SYNC(B_P, 384);
        DLY(13)
        pv_tok(p, pm, v, vs, Ot);
        asm volatile("stmatrix.sync.aligned.m8n8.x4.trans.shared.b16 [%0],{%1,%2,%3,%4};" ::"r"(t2.y), "r"(Ot[0]), "r"(Ot[1]), "r"(Ot[2]), "r"(Ot[3]) : "memory");
        __syncwarp();
        *(uint4*)od = lds4(tA + (OT - TA));
      }
    }
    FENCE_ASYNC();
    BAR_SYNC(B_SC, 128);
    if (tA == sb + TA) red_rlx(&g_fin);
  }
  __syncwarp();
  CLUSTER_SYNC();
  PH(5); RS(2);
}
#undef wg
#undef iw
#undef h
#undef j
#undef a
#undef bb
#undef oi
#undef owner
#undef ownv
#undef pr
#undef PIN
#undef XP_
#undef tw
#undef lane
#undef l16
#undef lrow
#undef lpub

namespace ffn {
constexpr uint32_t BR = 98304;
constexpr uint32_t STG = 196608;
constexpr uint32_t PRM = 229376;
constexpr uint32_t BARS = PRM + 2816;
constexpr uint32_t SMEM = BARS + 18 * 8;
}
#define Y_TILE(rb, kt) (((ALIAS & 1) ? g_h : g_h2) + ((rb) * 16 + (kt)) * 1024)
#define U_TILE(rb, kt) ((ALIAS & 2) ? g_O + ((rb) * 64 + (kt)) * 1024 : g_U + ((rb) * 56 + (kt)) * 1024)
struct FfnMaps { CUtensorMap wo, w1a, w1b, w2, x, out; };

template <int N>
__device__ __forceinline__ void wg_ss(float* d, uint64_t a, uint64_t b, int sd) {
  if (N == 128) wgmma_ss_n128(d, a, b, sd);
  if (N == 192) wgmma_ss_n192(d, a, b, sd);
}
template <int N>
__device__ __forceinline__ void acc_fence(float* d) {
#pragma unroll
  for (int i = 0; i < N; i++) asm volatile("" : "+f"(d[i])::"memory");
}
#define UNPK8(d, v) do { (d)[0] = blo(v.x); (d)[1] = bhi(v.x); (d)[2] = blo(v.y); (d)[3] = bhi(v.y); (d)[4] = blo(v.z); (d)[5] = bhi(v.z); (d)[6] = blo(v.w); (d)[7] = bhi(v.w); } while (0)
struct FfnPipe {
  uint32_t full, emp, ph, aoff;
  int st, sB, prev;
  bool leader;
  template <int N, int S = N>
  __device__ __forceinline__ void issue(float* acc, bool first, uint32_t a = 0) {
    mbar_wait(full + st * 8, ph);
    const uint64_t da = mkdesc((a ? a : 1024 + st * 16384) + aoff, 16, 1024), db = mkdesc(1024 + ffn::BR + sB * (S * 128), 8192, 1024);
    WG_FENCE();
#pragma unroll
    for (int j = 0; j < 4; j++) wg_ss<N>(acc, da + j * 2, db + j * 128, j || !first);
    WG_COMMIT();
    if (++sB == 768 / S) sB = 0;
  }
  __device__ __forceinline__ void release() { if (leader) mbar_arrive(emp + prev * 8); }
  __device__ __forceinline__ void next() { prev = st; if (++st == 6) { st = 0; ph ^= 1; } }
  __device__ __forceinline__ void retire() { WG_WAIT(1); release(); next(); }
};
__device__ __forceinline__ float gelu_h(float hx) {
  float u = hx * fmaf(hx * hx, 8.f * 0.0356774081f, 2.f * 0.7978845608f), t;
  asm("tanh.approx.f32 %0,%1;" : "=f"(t) : "f"(u));
  return fmaf(hx, t, hx);
}
struct FfnEpi {
  uint32_t st2, cc, flip, staged, l0;
  uint2 c;
  float n0, n1, s0, s1;
  __device__ __forceinline__ void flush(uint32_t r) {
    __syncwarp();
    asm volatile("{.reg .pred p; setp.ne.u32 p,%1,0; @p mbarrier.arrive.shared.b64 _,[%0];}" ::"r"(staged + (flip >> 11)), "r"(l0 & r) : "memory");
    flip ^= r << 14;
  }
  __device__ __forceinline__ void half(const float* d, int J, int r) {
#define PRE(i, n, c1, c2) gelu_h(fmaf(r ? d[4 + i] : d[i], i < 2 ? s0 : s1, fmaf(n, c1, c2)))
    asm volatile("stmatrix.sync.aligned.m8n8.x2.shared.b16 [%0],{%1,%2};" ::"r"((st2 ^ ((J & 3) * 32 + r * 16)) + flip),
                 "r"(pk(PRE(0, n0, blo(c.x), blo(c.y)), PRE(1, n0, bhi(c.x), bhi(c.y)))), "r"(pk(PRE(2, n1, blo(c.x), blo(c.y)), PRE(3, n1, bhi(c.x), bhi(c.y)))) : "memory");
#undef PRE
    if ((J & 3) == 3) flush(r);
    cc += r ? 56 : 8;
    c = lds2u(cc);
  }
};

__global__ void __launch_bounds__(384, 1)
k_ffn(const __grid_constant__ FfnMaps mp, const bf16* __restrict__ b2) {
  using namespace ffn;
  extern __shared__ __align__(1024) char smem[];
  const uint32_t sb = (uint32_t)__cvta_generic_to_shared(smem);
  if (sb != 1024) __trap();
  const int tid = threadIdx.x, lane = tid & 31, wg = __shfl_sync(~0u, tid >> 7, 0);
  const uint32_t full = sb + BARS, emp = full + 48, xbar = full + 96, staged = full + 104, tile = full + 136;
  uint32_t fin = 0;
  if (tid >= 288 && tid < 320) fin = ld_acq(&g_fin);
  if (tid < 32) {
    unsigned sm, v = 0;
    asm("mov.u32 %0,%%smid;" : "=r"(sm));
    if (tid == 0) {
      v = atomicExch(&g_slot[sm & 255], 0);
      for (int i = 0; i < 6; i++) { mbar_init(full + i * 8, 1); mbar_init(emp + i * 8, 2); }
      mbar_init(xbar, 2);
      for (int i = 0; i < 2; i++) { mbar_init(staged + i * 8, 8); mbar_init(staged + 16 + i * 8, 1); }
      FENCE_ASYNC_SMEM();
    }
    v = __shfl_sync(~0u, v, 0);
    if (!v) {
      wait_cnt(&g_fin, 128);
      for (int it = 0; !v; it++) {
        const uint4 a = ldg_rlx4(g_slot + tid * 8), b = ldg_rlx4(g_slot + tid * 8 + 4);
        const uint32_t open = __ballot_sync(~0u, a.x | a.y | a.z | a.w | b.x | b.y | b.z | b.w);
        if (!open) break;
        if (it < 16) { __nanosleep(500); continue; }
        if (tid == __ffs(open) - 1) v = atomicExch(&g_slot[tid * 8 + (a.x ? 0 : a.y ? 1 : a.z ? 2 : a.w ? 3 : b.x ? 4 : b.y ? 5 : b.z ? 6 : 7)], 0);
        v = __shfl_sync(~0u, v, __ffs(open) - 1);
      }
    }
    if (tid == 0) sts1(tile, v);
  }
  if (tid == 256) asm volatile("prefetch.tensormap [%0];" ::"l"(&mp.wo) : "memory");
  __syncthreads();
  const int bid = __shfl_sync(~0u, lds1(tile), 0) - 1;
  if (bid < 0) return;
  PH(6);
  FT(1);
  const int rb = bid >> 3, nb = bid & 7;
  unsigned* cnt = g_cnt + rb * 128;
  if (wg == 2) {
    asm volatile("setmaxnreg.dec.sync.aligned.u32 " FRP ";");
    const int pw = __shfl_sync(~0u, (tid >> 5) & 3, 0);
    uint32_t ws = emp, wp = 1, fs = full;
    auto wait_free = [&]() { mbar_wait_q(ws, wp); ws += 8; if (ws == emp + 48) { ws = emp; wp ^= 1; } };
    auto step = [&]() { fs += 8; if (fs == full + 48) fs = full; };
#define K3(c) ((0x65230 >> (c) * 4) & 7)
#define KC(k) ((k) < 2 ? nb * 2 + (k) : (k) < 9 ? ((k) - 2 + ((k) - 2 >= nb)) * 2 : ((k) - 9 + ((k) - 9 >= nb)) * 2 + 1)
    if (pw == 0) {
      uint32_t d = sb + BR + 32768;
      auto put = [&](const CUtensorMap* m, int k, int c) {
        e_expect_tma3d(d, m, k * 64, c, fs, 32768);
        step();
        d += 16384;
        if (d == sb + STG) d = sb + BR;
      };
      int n = 0;
      auto stage_free = [&]() { if (!(n & 7) && n < 56) mbar_wait_q(staged + 16 + (n & 8), (n >> 4) & 1); n++; };
      auto align = [&]() {
        if (ALN && !((n - 1) & 7) && ((ALN >> ((n - 1) >> 3)) & 1)) {
          unsigned* c = g_cnt + 64 + ((n - 1) >> 3);
          if (lane == 0) red_rlx(c);
          for (int it = 0; ldg_rlx1(c) < 128 && it < 64; it++) {}
        }
      };
      FTP(3);
#pragma unroll 1
      for (int k = 0; k < 66; k++) { wait_free(); if (k < 64) put(&mp.wo, k, nb * 2); }
#pragma unroll 1
      for (int k = 0; k < 18; k++) {
        const int u = k >= 2 ? k - 2 : k, kt = KC(u);
        const bool ea = (k & ~1) == 2;
        wait_free();
        e_expect_tma3d(sb + BR + (k & 3) * 24576, ea ? &mp.w1a : &mp.w1b, kt * 64, nb * 7 + (ea ? 3 : 0), fs, ea ? 16384 : k < 2 ? 24576 : 40960);
        step();
      }
      d = sb + BR + 49152;
#pragma unroll 1
      for (int k = 2; k < 32; k++) {
        const int kt = k < 16 ? KC(k) : k & 15;
        stage_free();
        if (k == 2 || k == 9) n++;
        if (k != 7 && k != 8) wait_free();
        align();
        put(&mp.w1a, kt, nb * 7 + 3 + (k >> 4) * 2);
      }
#pragma unroll 1
      for (int c = 0; c < 5; c++)
#pragma unroll 1
        for (int k = K3(c), i = 0; k < 56; k += c < 2 && (i ^= 1) ? 1 : c < 2 ? 6 : 7) { stage_free(); wait_free(); align(); put(&mp.w2, k, nb * 2); }
    } else if (pw == 1) {
      FTP(5);
      if (fin < 128) wait_cnt(&g_fin, 128);
      FTP(6);
      uint32_t d = sb;
      auto put = [&](const uint4* A, bool ld) {
        wait_free();
        if (ld) e_bulk_ld(d, A, 16384, fs);
        step();
        d += 16384;
        if (d == sb + BR) d = sb;
      };
      const uint4* A = g_O + rb * 65536;
#pragma unroll 1
      for (int k = 0; k < 68; k++) put(A + k * 1024, k < 64);
      A = Y_TILE(rb, 0);
      uint32_t ready = 0;
#pragma unroll 1
      for (int k = 2; k < 48; k++) {
        if (k == 16) k = 18;
        const int kt = k < 32 ? KC(k & 15) : k & 15;
        for (int it = 0; !(ready >> ((kt >> 1) + (kt & 1) * 8) & 1); it++) {
          ready = __ballot_sync(~0u, ldg_rlx1(cnt + (lane & 7)) & ((lane & 8) ? 1 : 0x10000));
          if (it > SPIN_LIMIT) __trap();
        }
        if (k == 2) FTP(75);
        put(A + kt * 1024, true);
      }
      A = U_TILE(rb, 0);
#pragma unroll 1
      for (int c = 0; c < 5; c++) {
        for (int it = 0; ldg_rlx1(cnt + 32 + c) < 8; it++) if (it > SPIN_LIMIT) __trap();
#pragma unroll 1
        for (int k = K3(c), i = 0; k < 56; k += c < 2 && (i ^= 1) ? 1 : c < 2 ? 6 : 7) put(A + k * 1024, true);
      }
    } else if (pw == 2) {
#pragma unroll 1
      for (int i = 0; i < XDL; i++) mbar_wait_q(emp, i & 1);
      if (lane == 0) {
        mbar_expect(xbar, 32768);
#pragma unroll 1
        for (int i = 0; i < 256 / XR; i++) {
          tma2d(sb + STG + i * (XR * 128), &mp.x, nb * 128 + (i * XR >> 7) * 64, rb * 128 + ((i * XR) & 127), xbar);
          const uint32_t c = clk();
          while (clk() - c < XTD) {}
        }
      }
      asm volatile("griddepcontrol.wait;" ::: "memory");
      if (lane < 16) g_modp[bid * 16 + lane] = make_uint4(0, 0, 0, 0);
      if (lane >= 16 && bid == 0) { g_hcnt = 0; g_mcnt = 0; g_hf[lane & 3] = 0; }
      if (lane == 0) {
#pragma unroll 1
        for (int g = 1; g < 9; g++) {
          if (g == 1) mbar_wait(staged + 8, 0); else { mbar_wait_q(staged + (g & 1) * 8, (g >> 1) & 1); FENCE_ASYNC_SMEM(); }
          uint4* dst = g == 1 ? Y_TILE(rb, nb * 2 + 1) : U_TILE(rb, nb * 7 + ((0x652431000ull >> g * 4) & 7));
#pragma unroll 1
          for (int i = 0; i < (g > 1 ? 4 : 1); i++) {
            bulk_st(dst + i * 256, sb + STG + (g & 1) * 16384 + i * 4096, g > 1 ? 4096 : 16384);
            const uint32_t c = clk();
            while (g > 1 && clk() - c < USD) {}
          }
          BULK_COMMIT();
          if (g != 2 && g != 4) { BULK_WAIT(0); red_rlx(g == 1 ? cnt + nb : cnt + 32 + (g < 6 ? g >> 2 : g - 4)); }
          BULK_WAIT_READ(0);
          mbar_arrive(staged + 16 + (g & 1) * 8);
        }
      }
    } else {
      const uint32_t prm = sb + PRM, pp = prm + (lane >> 3) * 64 + (lane & 1) * 32 + (lane & 6) * 2;
      const uint2 v2 = ((const uint2*)(b2 + nb * 128))[lane];
      sts1(pp + 768, v2.x); sts1(pp + 784, v2.y);
      asm volatile("griddepcontrol.wait;" ::: "memory");
      const float4* md = (const float4*)(g_mod + nb * 128) + lane;
      { const float4 ga = md[512]; sts1(pp, pk(ga.x, ga.y)); sts1(pp + 16, pk(ga.z, ga.w)); }
      { const float4 cb = md[1024]; sts1(pp + 256, pk(1.f + cb.x, 1.f + cb.y)); sts1(pp + 272, pk(1.f + cb.z, 1.f + cb.w)); }
      { const float4 gb = md[1280]; sts1(pp + 512, pk(gb.x, gb.y)); sts1(pp + 528, pk(gb.z, gb.w)); }
#pragma unroll 1
      for (int i = lane; i < 112; i += 32) { const uint4 c = g_cc[nb * 112 + i]; sts4(prm + 1024 + i * 16, c.x, c.y, c.z, c.w); }
      __syncwarp();
      if (lane == 0) {
        mbar_arrive(xbar);
        mbar_wait(staged, 0);
        bulk_st(Y_TILE(rb, nb * 2), sb + STG, 16384);
        BULK_COMMIT(); BULK_WAIT(0);
        asm volatile("red.relaxed.gpu.global.add.u32 [%0],0x10000;" ::"l"(cnt + nb) : "memory");
        mbar_arrive(staged + 16);
      }
      __syncwarp();
      mbar_wait_q(staged + 24, 0);
      mbar_wait_q(emp + 8, 1);
#pragma unroll 1
      for (int i = 0; i < 4; i++) {
        const uint4* sp = g_stat + (rb * 128 + i * 32 + lane) * 4;
        uint4 v[4];
        for (int it = 0;; it++) {
          uint32_t m = 0;
#pragma unroll
          for (int u = 0; u < 4; u++) { v[u] = ldg_rlx4(sp + u); m = max(max(m, max(v[u].x, v[u].y)), max(v[u].z, v[u].w)); }
          if (!__any_sync(~0u, m == ~0u)) break;
          if (it > SPIN_LIMIT) __trap();
        }
        float m = 0, q = 0;
#pragma unroll
        for (int u = 0; u < 4; u++) { m += F_(v[u].x) + F_(v[u].z); q += F_(v[u].y) + F_(v[u].w); }
        m *= 1.f / 1024;
        const float r = 0.5f * rsqrtf(fmaxf(q * (1.f / 1024) - m * m, 0.f) + 1e-5f);
        sts2(sb + STG + 16384 + (i * 32 + lane) * 8, U_(r), U_(-m * r));
      }
      __syncwarp();
      if (lane < 2) mbar_arrive(xbar);
    }
  } else {
    asm volatile("setmaxnreg.inc.sync.aligned.u32 " FRC ";");
    const int w = (tid >> 5) & 3, q = lane & 3;
    const uint32_t prm = sb + PRM + q * 16;
    const int row0 = wg * 64 + w * 16;
    FfnPipe p;
    p.full = full; p.emp = emp; p.ph = 0; p.aoff = wg * 8192; p.st = 0; p.sB = 2; p.prev = 0; p.leader = (tid & 127) == 0;
    FfnEpi e;
    const uint32_t stg = sb + STG + row0 * 128;
    e.st2 = stg + (lane & 15) * 128 + ((lane & 7) << 4);
    e.cc = sb + PRM + 1024 + q * 16; e.flip = 0; e.staged = staged; e.l0 = lane == 0;
    const uint32_t stw = e.st2 ^ (lane & 16);
    uint32_t x1[32];
    uint4* sp = g_stat + (rb * 128 + row0 + (lane >> 2)) * 4;
    float old[96], r0_, r1_;
    {
      float acc[64];
      p.issue<128>(acc, true); FT(8); p.next();
#pragma unroll 1
      for (int k = 1; k < 64; k++) { p.issue<128>(acc, false); FT(8 + k); p.retire(); }
      float xf[64], gf[32];
      uint32_t cb[16];
      mbar_wait(xbar, 0);
#pragma unroll
      for (int j = 0; j < 8; j++) {
        uint32_t xv[4];
        ldsm4(xv, (stw ^ ((j & 3) * 32)) + (j >> 2) * 16384);
#pragma unroll
        for (int i = 0; i < 4; i++) { xf[j * 8 + i * 2] = blo(xv[i]); xf[j * 8 + i * 2 + 1] = bhi(xv[i]); }
      }
#pragma unroll
      for (int i = 0; i < 4; i++) {
        const uint4 g = lds4(prm + i * 64), c = lds4(prm + 256 + i * 64);
        UNPK8(gf + i * 8, g);
        cb[i * 4] = c.x; cb[i * 4 + 1] = c.y; cb[i * 4 + 2] = c.z; cb[i * 4 + 3] = c.w;
      }
      acc_fence<64>(xf); acc_fence<32>(gf);
      WG_WAIT(0);
      p.release();
      acc_fence<64>(acc);
      PH(7); FT(72);
#pragma unroll
      for (int j = 0; j < 8; j++) {
        uint32_t* o = x1 + j * 4;
#pragma unroll
        for (int i = 0; i < 4; i++)
          o[i] = pk(fmaf(acc[j * 8 + i * 2], gf[j * 4 + (i & 2)], xf[j * 8 + i * 2]), fmaf(acc[j * 8 + i * 2 + 1], gf[j * 4 + (i & 2) + 1], xf[j * 8 + i * 2 + 1]));
        stsm4((stw ^ ((j & 3) * 32)) + (j >> 2) * 16384, mulbf(o[0], cb[j * 2]), mulbf(o[1], cb[j * 2]), mulbf(o[2], cb[j * 2 + 1]), mulbf(o[3], cb[j * 2 + 1]));
        if ((j & 3) == 3) { FENCE_ASYNC_SMEM(); e.flush(1); }
      }
      if (wg) BAR_SYNC(2, 128); else BAR_SYNC(3, 128);
    }
    PH(8); FT(73);
    float acc[64];
    {
      float* accC = old;
      p.sB = 0;
      p.issue<192>(accC, true, 1024 + STG); FT(80); p.next();
      p.issue<192>(accC, false, 1024 + STG + 16384); FT(81);
      FT(78);
      float s0 = 0, s1 = 0, q0 = 0, q1 = 0;
#define X1_FENCE _Pragma("unroll") for (int j = 0; j < 32; j++) asm volatile("" : "+r"(x1[j]));
      X1_FENCE
#pragma unroll
      for (int j = 0; j < 16; j++) {
        const float a = blo(x1[j * 2]), b = bhi(x1[j * 2]), c = blo(x1[j * 2 + 1]), d = bhi(x1[j * 2 + 1]);
        s0 += a + b; s1 += c + d; q0 = fmaf(a, a, fmaf(b, b, q0)); q1 = fmaf(c, c, fmaf(d, d, q1));
      }
#pragma unroll
      for (int o = 1; o < 4; o *= 2) { s0 += __shfl_xor_sync(~0u, s0, o); s1 += __shfl_xor_sync(~0u, s1, o); q0 += __shfl_xor_sync(~0u, q0, o); q1 += __shfl_xor_sync(~0u, q1, o); }
      if (q < 2) {
        uint32_t m = __float_as_uint(q ? s1 : s0), v = __float_as_uint(q ? q1 : q0);
        if (m == ~0u) m = 0x7fffffffu;
        if (v == ~0u) v = 0x7fffffffu;
        stg_rlx2((uint2*)(sp + q * 32) + nb, m, v);
      }
      X1_FENCE
      p.retire();
#pragma unroll 1
      for (int k = 0; k < 2; k++) { p.issue<128, 192>(acc, !k, 1024 + STG + k * 16384); p.retire(); }
#pragma unroll 1
      for (int k = 2; k < 15; k++) { p.issue<192>(accC, false); FT(80 + k); p.retire(); }
      p.issue<192>(accC, false); FT(95);
      mbar_wait(xbar, 1);
      const float2 u0 = lds2f(sb + STG + 16384 + (row0 + (lane >> 2)) * 8), u1 = lds2f(sb + STG + 16384 + (row0 + (lane >> 2)) * 8 + 64);
      r0_ = u0.x; e.n0 = u0.y; r1_ = u1.x; e.n1 = u1.y;
      e.c = lds2u(e.cc);
      p.retire();
      e.s0 = r0_; e.s1 = r1_;
      p.sB = 3;
    }
    PH(9);
    {
      auto pair = [&](int J, bool first, bool one, int fo) {
#pragma unroll 1
        for (int r = 0; r < 2; r++) {
          if (!(one && r)) { p.issue<128>(acc, first && !r); FT(fo + r); p.retire(); }
          acc_fence<8>(old + J * 8);
          e.half(old + J * 8, J, r);
        }
      };
#pragma unroll 1
      for (int i = 0; i < 3; i++) {
        if (i == 2) {
          e.s0 = r0_; e.s1 = r1_;
#pragma unroll
          for (int J = 8; J < 12; J++) pair(J, J == 8, false, 128 + (J - 8) * 2);
          e.cc += 512; e.c = lds2u(e.cc);
          e.s0 = e.s1 = 1.f;
        }
#pragma unroll
        for (int J = 0; J < 8; J++) pair(J, J == 0 && i == 1, !(J & 3) && !i, 96 + i * 16 + (i >> 1) * 8 + J * 2);
        if (i == 2) break;
        e.cc += i ? -768 : 256; e.c = lds2u(e.cc);
        WG_WAIT(0);
        acc_fence<64>(acc);
#pragma unroll
        for (int k = 0; k < 64; k++) old[k] = acc[k] * ((k & 2) ? r1_ : r0_);
        acc_fence<64>(old);
        e.s0 = e.s1 = 1.f;
        PH(10 + i);
      }
#pragma unroll 1
      for (int k = 24; k < 56; k++) {
        if (SKW && k == 56 - SKW && wg) BAR_SYNC(4, 256);
        p.issue<128>(acc, false); FT(128 + k);
        if (SKW && k == 55 && !wg) BAR_ARRIVE(4, 256);
        p.retire();
      }
      float xf[64], gf[32];
#pragma unroll
      for (int i = 0; i < 4; i++) {
        const uint4 g = lds4(prm + 512 + i * 64), h = lds4(prm + 768 + i * 64);
        float hf[8];
        UNPK8(gf + i * 8, g); UNPK8(hf, h);
#pragma unroll
        for (int u = 0; u < 8; u++) {
          const int c = (u >> 2) * 4 + (u & 2);
          xf[i * 16 + u * 2] = fmaf(gf[i * 8 + c], hf[c], blo(x1[i * 8 + u])); xf[i * 16 + u * 2 + 1] = fmaf(gf[i * 8 + c + 1], hf[c + 1], bhi(x1[i * 8 + u]));
        }
      }
      acc_fence<64>(xf); acc_fence<32>(gf);
      mbar_wait(staged + 24, 1);
      mbar_wait(staged + 16, 0);
      WG_WAIT(0);
      acc_fence<64>(acc);
      PH(13); FT(184);
#pragma unroll
      for (int j = 0; j < 8; j++) {
        uint32_t o[4];
#pragma unroll
        for (int i = 0; i < 4; i++)
          o[i] = pk(fmaf(acc[j * 8 + i * 2], gf[j * 4 + (i & 2)], xf[j * 8 + i * 2]), fmaf(acc[j * 8 + i * 2 + 1], gf[j * 4 + (i & 2) + 1], xf[j * 8 + i * 2 + 1]));
        stsm4((stw ^ ((j & 3) * 32)) + (j >> 2) * 16384, o[0], o[1], o[2], o[3]);
        if ((j & 3) == 3) {
          FENCE_ASYNC_SMEM();
          __syncwarp();
          if (lane == 0) { tma2d_st(&mp.out, nb * 128 + (j >> 2) * 64, rb * 128 + row0, stg + (j >> 2) * 16384); BULK_COMMIT(); }
        }
      }
      if (lane == 0) BULK_WAIT_READ(0);
      __syncwarp();
    }
  }
  PH(14); FT(185);
}

typedef CUresult (*EncFn)(CUtensorMap*, CUtensorMapDataType, cuuint32_t, void*, const cuuint64_t*, const cuuint64_t*, const cuuint32_t*,
                          const cuuint32_t*, CUtensorMapInterleave, CUtensorMapSwizzle, CUtensorMapL2promotion, CUtensorMapFloatOOBfill);
static void map2d(EncFn enc, CUtensorMap* m, const void* p, int rows, int cols, int boxRows) {
  cuuint64_t d[2] = {(cuuint64_t)cols, (cuuint64_t)rows}, s[1] = {(cuuint64_t)cols * 2};
  cuuint32_t b[2] = {64, (cuuint32_t)boxRows}, e[2] = {1, 1};
  enc(m, CU_TENSOR_MAP_DATA_TYPE_BFLOAT16, 2, (void*)p, d, s, b, e, CU_TENSOR_MAP_INTERLEAVE_NONE, CU_TENSOR_MAP_SWIZZLE_128B,
      CU_TENSOR_MAP_L2_PROMOTION_L2_128B, CU_TENSOR_MAP_FLOAT_OOB_FILL_NONE);
}
static void map3d(EncFn enc, CUtensorMap* m, const void* p, int rows, int cols, int nch) {
  cuuint64_t d[3] = {64, (cuuint64_t)rows, (cuuint64_t)(cols / 64)}, s[2] = {(cuuint64_t)cols * 2, 128};
  cuuint32_t b[3] = {64, 64, (cuuint32_t)nch}, e[3] = {1, 1, 1};
  enc(m, CU_TENSOR_MAP_DATA_TYPE_BFLOAT16, 3, (void*)p, d, s, b, e, CU_TENSOR_MAP_INTERLEAVE_NONE, CU_TENSOR_MAP_SWIZZLE_128B,
      CU_TENSOR_MAP_L2_PROMOTION_L2_128B, CU_TENSOR_MAP_FLOAT_OOB_FILL_NONE);
}

extern "C" void kernel_launch(void* const* d_in, const int* in_sizes, int n_in, void* d_out, int out_size) {
  const bf16* x = (const bf16*)d_in[0];
  const bf16* mem0 = (const bf16*)d_in[1];
  void* fn = nullptr;
  cudaDriverEntryPointQueryResult qr;
  cudaGetDriverEntryPoint("cuTensorMapEncodeTiled", &fn, cudaEnableDefault, &qr);
  EncFn enc = (EncFn)fn;
  FfnMaps fm = {};
  map3d(enc, &fm.wo, d_in[5], 4096, 1024, 2);
  map3d(enc, &fm.w1a, d_in[8], 1024, 3584, 2);
  map3d(enc, &fm.w1b, d_in[8], 1024, 3584, 3);
  map3d(enc, &fm.w2, d_in[10], 3584, 1024, 2);
  map2d(enc, &fm.x, x, 2048, 1024, XR);
  map2d(enc, &fm.out, d_out, 2048, 1024, 16);
  RecMaps rm = {};
  map2d(enc, &rm.wq, d_in[2], 1024, 4096, 128);
  map2d(enc, &rm.wk, d_in[3], 1024, 4096, 128);
  map2d(enc, &rm.wv, d_in[4], 1024, 4096, 16);
  map2d(enc, &rm.wo, d_in[5], 4096, 1024, 128);
  char* xc = nullptr;
  cudaGetSymbolAddress((void**)&xc, g_xc);
  xc += (0 - (uintptr_t)xc) & 0x1FFFFF;
  {
    cuuint64_t d[3] = {512, 6, 128}, sd[2] = {131072, 1024};
    cuuint32_t bi[3] = {64, 5, 8}, e[3] = {1, 1, 1};
    enc(&rm.ari, CU_TENSOR_MAP_DATA_TYPE_BFLOAT16, 3, xc + AR_OFF, d, sd, bi, e, CU_TENSOR_MAP_INTERLEAVE_NONE, CU_TENSOR_MAP_SWIZZLE_NONE,
        CU_TENSOR_MAP_L2_PROMOTION_NONE, CU_TENSOR_MAP_FLOAT_OOB_FILL_NONE);
  }
  {
    cuuint64_t d[5] = {256, 4, 2, 2, 2048}, sd[4] = {rec::XC, X_VX(1), X_VX(2), 4096};
    cuuint32_t bi[5] = {256, 4, 2, 2, 1}, e[5] = {1, 1, 1, 1, 1};
    enc(&rm.vx, CU_TENSOR_MAP_DATA_TYPE_BFLOAT16, 5, xc, d, sd, bi, e, CU_TENSOR_MAP_INTERLEAVE_NONE, CU_TENSOR_MAP_SWIZZLE_NONE,
        CU_TENSOR_MAP_L2_PROMOTION_NONE, CU_TENSOR_MAP_FLOAT_OOB_FILL_NONE);
  }
  cudaFuncSetAttribute(k_ffn, cudaFuncAttributeMaxDynamicSharedMemorySize, ffn::SMEM);
  cudaFuncSetAttribute(k_rec, cudaFuncAttributeMaxDynamicSharedMemorySize, rec::SMEM);
  cudaStream_t st = cudaStreamPerThread;
  int dF = 450, dA = 2700, dS = 320, dM = 120, dG = 250, dP = 24, dX = 48, dD = 350, dZ = 0, dQ = 750, dV = 370, dX2 = 0;
  k_rec<<<132, 512, rec::SMEM, st>>>(rm, mem0, x, (const bf16*)d_in[12], (const bf16*)d_in[13], (const char*)d_in[8], (const bf16*)d_in[9],
                                     (const char*)d_in[5], xc, dF, dA, dS, dM, dG, dP, dX, dD, dZ, dQ, dV, dX2);
  cudaLaunchConfig_t cfg = {};
  cfg.gridDim = dim3(132); cfg.blockDim = dim3(384); cfg.dynamicSmemBytes = ffn::SMEM; cfg.stream = st;
  cudaLaunchAttribute at[1];
  at[0].id = cudaLaunchAttributeProgrammaticStreamSerialization;
  at[0].val.programmaticStreamSerializationAllowed = 1;
  cfg.attrs = at; cfg.numAttrs = 1;
  cudaLaunchKernelEx(&cfg, k_ffn, fm, (const bf16*)d_in[11]);
}
```

```cpp
#include <cuda_runtime.h>
#include <cuda.h>
#include <cuda_bf16.h>
#include <stdint.h>

typedef __nv_bfloat16 bf16;

__device__ __align__(16) float g_mod[6144];
__device__ __align__(1024) uint4 g_modp[4 * 512];
__device__ unsigned g_hcnt;
__device__ unsigned g_hf[4];
__device__ __align__(1024) uint4 g_h[2048 * 1024 / 8];
__device__ __align__(1024) uint4 g_O[2048 * 4096 / 8];
__device__ __align__(1024) uint4 g_h2[2048 * 1024 / 8];
__device__ __align__(1024) uint4 g_U[2048 * 3584 / 8];
__device__ __align__(1024) uint4 g_stat[2048 * 4];
__device__ __align__(1024) unsigned g_cnt[16 * 4 * 32];
__device__ unsigned g_mcnt;
__device__ unsigned g_slot[256];
__device__ unsigned g_fin;
__device__ __align__(16) uint4 g_cc[224 * 4];
__device__ __align__(1024) uint4 g_xc[44 * 16384];
__device__ __align__(1024) unsigned g_tm[4 * 256];
#define FT(i)
#define FTP(i)
#define PT(i)
#define PH(i)
#define RS(i)
#define RP(i)
#define RPN(i, s)
#define TSV(i, v)
#define TS(i)

#define FRC "232"
#define FRP "40"
#define FMAP (((g >> 2) * 4 + m) * 8 + ((g & 3) ^ ((g & 4) ? 3 : 0)) * 2 + (blockIdx.x & 1))
#define ALIAS 3
#define PFT 150000
#define PFS 104
#define PF0 13000
#define PFD 128
#define NF 3
#define NB0 4
#define PV0 4
#define T1L 1
#define NW0 1
#define VRF 3
#define VPC 0
#define WC0 99
#define WPE 3
#define ALN 0x80
#define SKW 5
#define L62 200
#define DLY(k)
#define USD 150
#define XR 32
#define XTD 500
#define XDL 6
#define PDS 61
#define P_NVR 5
#define P_NWP 9
#define P_NW1 7
#define RF_ 208
#define RA_ (488 - 2 * RF_)
#define WCH 2
#define NOP_ 2
#define SPIN_LIMIT (1 << 20)
__device__ __forceinline__ uint64_t mkdesc(uint32_t addr, uint32_t lbo, uint32_t sbo) {
  return (uint64_t)((addr & 0x3FFFF) >> 4) | ((uint64_t)(lbo >> 4) << 16) | ((uint64_t)(sbo >> 4) << 32) | (1ull << 62);
}
__device__ __forceinline__ void mbar_init(uint32_t a, int c) { asm volatile("mbarrier.init.shared.b64 [%0],%1;" ::"r"(a), "r"(c) : "memory"); }
__device__ __forceinline__ void mbar_wait(uint32_t a, uint32_t par) {
  asm volatile(
      "{.reg .pred p; .reg .u32 n;\n"
      "mov.u32 n, 0;\n"
      "W: mbarrier.try_wait.parity.shared.b64 p,[%0],%1;\n"
      "@p bra D;\n"
      "add.u32 n, n, 1;\n"
      "setp.lt.u32 p, n, %2;\n"
      "@p bra W;\n"
      "trap;\n"
      "D:}" ::"r"(a), "r"(par), "n"(SPIN_LIMIT) : "memory");
}
__device__ __forceinline__ void mbar_wait_q(uint32_t a, uint32_t par) {
  asm volatile(
      "{.reg .pred p; .reg .u32 n;\n"
      "mov.u32 n, 0;\n"
      "W: mbarrier.try_wait.parity.shared.b64 p,[%0],%1,4000;\n"
      "@p bra D;\n"
      "add.u32 n, n, 1;\n"
      "setp.lt.u32 p, n, %2;\n"
      "@p bra W;\n"
      "trap;\n"
      "D:}" ::"r"(a), "r"(par), "n"(SPIN_LIMIT / 16) : "memory");
}
__device__ __forceinline__ void mbar_expect(uint32_t a, uint32_t b) { asm volatile("mbarrier.arrive.expect_tx.shared.b64 _,[%0],%1;" ::"r"(a), "r"(b) : "memory"); }
__device__ __forceinline__ void mbar_arrive(uint32_t a) { asm volatile("mbarrier.arrive.shared.b64 _,[%0];" ::"r"(a) : "memory"); }
__device__ __forceinline__ uint32_t mapa(uint32_t a, uint32_t cta) { uint32_t r; asm("mapa.shared::cluster.u32 %0,%1,%2;" : "=r"(r) : "r"(a), "r"(cta)); return r; }
__device__ __forceinline__ void mbar_arrive_cl(uint32_t a) { asm volatile("mbarrier.arrive.shared::cluster.b64 _,[%0];" ::"r"(a) : "memory"); }
__device__ __forceinline__ void tma2d(uint32_t dst, const CUtensorMap* m, int c0, int c1, uint32_t mb) {
  asm volatile("cp.async.bulk.tensor.2d.shared::cluster.global.mbarrier::complete_tx::bytes [%0],[%1,{%2,%3}],[%4];" ::"r"(dst), "l"(m), "r"(c0), "r"(c1), "r"(mb) : "memory");
}
__device__ __forceinline__ void tma2d_pf(const CUtensorMap* m, int c0, int c1) {
  asm volatile("cp.async.bulk.prefetch.tensor.2d.L2.global [%0,{%1,%2}];" ::"l"(m), "r"(c0), "r"(c1) : "memory");
}
__device__ __forceinline__ void tma2d_st(const CUtensorMap* m, int c0, int c1, uint32_t src) {
  asm volatile("cp.async.bulk.tensor.2d.global.shared::cta.bulk_group [%0,{%1,%2}],[%3];" ::"l"(m), "r"(c0), "r"(c1), "r"(src) : "memory");
}
__device__ __forceinline__ void bulk_ld(uint32_t dst, const void* src, uint32_t n, uint32_t mb) {
  asm volatile("cp.async.bulk.shared::cluster.global.mbarrier::complete_tx::bytes [%0],[%1],%2,[%3];" ::"r"(dst), "l"(src), "r"(n), "r"(mb) : "memory");
}
__device__ __forceinline__ void bulk_st(void* dst, uint32_t src, uint32_t n) {
  asm volatile("cp.async.bulk.global.shared::cta.bulk_group [%0],[%1],%2;" ::"l"(dst), "r"(src), "r"(n) : "memory");
}
__device__ __forceinline__ void e_expect_tma3d(uint32_t dst, const CUtensorMap* m, int c1, int c2, uint32_t mb, uint32_t bytes) {
  asm volatile("{.reg .pred p; elect.sync _|p, 0xffffffff; @p mbarrier.arrive.expect_tx.shared.b64 _,[%4],%5;\n"
               "@p cp.async.bulk.tensor.3d.shared::cluster.global.mbarrier::complete_tx::bytes [%0],[%1,{0,%2,%3}],[%4];}" ::"r"(dst), "l"(m), "r"(c1), "r"(c2), "r"(mb), "r"(bytes) : "memory");
}
__device__ __forceinline__ void e_bulk_ld(uint32_t dst, const void* src, uint32_t n, uint32_t mb) {
  asm volatile("{.reg .pred p; elect.sync _|p, 0xffffffff; @p cp.async.bulk.shared::cluster.global.mbarrier::complete_tx::bytes [%0],[%1],%2,[%3];}" ::"r"(dst), "l"(src), "r"(n), "r"(mb) : "memory");
}
#define BULK_COMMIT() asm volatile("cp.async.bulk.commit_group;" ::: "memory")
#define BULK_WAIT_READ(n) asm volatile("cp.async.bulk.wait_group.read " #n ";" ::: "memory")
#define BULK_WAIT(n) asm volatile("cp.async.bulk.wait_group " #n ";" ::: "memory")
#define FENCE_ASYNC_SMEM() asm volatile("fence.proxy.async.shared::cta;" ::: "memory")
#define FENCE_ASYNC() asm volatile("fence.proxy.async;" ::: "memory")
#define WG_FENCE() asm volatile("wgmma.fence.sync.aligned;" ::: "memory")
#define WG_COMMIT() asm volatile("wgmma.commit_group.sync.aligned;" ::: "memory")
#define WG_WAIT(n) asm volatile("wgmma.wait_group.sync.aligned " #n ";" ::: "memory")
#define BAR_SYNC(id, n) asm volatile("bar.sync %0,%1;" ::"n"(id), "n"(n) : "memory")
#define BAR_ARRIVE(id, n) asm volatile("bar.arrive %0,%1;" ::"n"(id), "n"(n) : "memory")
#define SCHED_FENCE(k) asm volatile("{.reg .pred p; setp.ne.u32 p,%0,0; @p trap;}" ::"r"(mp.zero[(k) - 46]) : "memory")
#define CLUSTER_SYNC() asm volatile("barrier.cluster.arrive.relaxed.aligned; barrier.cluster.wait.aligned;" ::: "memory")
__device__ __forceinline__ uint32_t pk(float lo, float hi) { uint32_t r; asm("cvt.rn.bf16x2.f32 %0,%1,%2;" : "=r"(r) : "f"(hi), "f"(lo)); return r; }
__device__ __forceinline__ float blo(uint32_t v) { return __uint_as_float(v << 16); }
__device__ __forceinline__ float bhi(uint32_t v) { return __uint_as_float(v & 0xffff0000u); }
__device__ __forceinline__ void ldsm4(uint32_t* r, uint32_t a) {
  asm volatile("ldmatrix.sync.aligned.m8n8.x4.shared.b16 {%0,%1,%2,%3},[%4];" : "=r"(r[0]), "=r"(r[1]), "=r"(r[2]), "=r"(r[3]) : "r"(a) : "memory");
}
__device__ __forceinline__ void ldsm4t(uint32_t* r, uint32_t a) {
  asm volatile("ldmatrix.sync.aligned.m8n8.x4.trans.shared.b16 {%0,%1,%2,%3},[%4];" : "=r"(r[0]), "=r"(r[1]), "=r"(r[2]), "=r"(r[3]) : "r"(a) : "memory");
}
__device__ __forceinline__ void stsm4(uint32_t a, uint32_t r0, uint32_t r1, uint32_t r2, uint32_t r3) {
  asm volatile("stmatrix.sync.aligned.m8n8.x4.shared.b16 [%0],{%1,%2,%3,%4};" ::"r"(a), "r"(r0), "r"(r1), "r"(r2), "r"(r3) : "memory");
}
__device__ __forceinline__ void mma16(float* d, uint32_t a0, uint32_t a1, uint32_t a2, uint32_t a3, uint32_t b0, uint32_t b1) {
  asm volatile("mma.sync.aligned.m16n8k16.row.col.f32.bf16.bf16.f32 {%0,%1,%2,%3},{%4,%5,%6,%7},{%8,%9},{%0,%1,%2,%3};"
               : "+f"(d[0]), "+f"(d[1]), "+f"(d[2]), "+f"(d[3]) : "r"(a0), "r"(a1), "r"(a2), "r"(a3), "r"(b0), "r"(b1));
}
__device__ __forceinline__ void mma8(float* d, uint32_t a0, uint32_t a1, uint32_t b0) {
  asm volatile("mma.sync.aligned.m16n8k8.row.col.f32.bf16.bf16.f32 {%0,%1,%2,%3},{%4,%5},{%6},{%0,%1,%2,%3};"
               : "+f"(d[0]), "+f"(d[1]), "+f"(d[2]), "+f"(d[3]) : "r"(a0), "r"(a1), "r"(b0));
}
__device__ __forceinline__ float4 lds4f(uint32_t a) { float4 v; asm volatile("ld.shared.v4.f32 {%0,%1,%2,%3},[%4];" : "=f"(v.x), "=f"(v.y), "=f"(v.z), "=f"(v.w) : "r"(a) : "memory"); return v; }
__device__ __forceinline__ float2 lds2f(uint32_t a) { float2 v; asm volatile("ld.shared.v2.f32 {%0,%1},[%2];" : "=f"(v.x), "=f"(v.y) : "r"(a) : "memory"); return v; }
__device__ __forceinline__ uint4 lds4(uint32_t a) { uint4 v; asm volatile("ld.shared.v4.u32 {%0,%1,%2,%3},[%4];" : "=r"(v.x), "=r"(v.y), "=r"(v.z), "=r"(v.w) : "r"(a) : "memory"); return v; }
__device__ __forceinline__ uint2 lds2u(uint32_t a) { uint2 v; asm volatile("ld.shared.v2.u32 {%0,%1},[%2];" : "=r"(v.x), "=r"(v.y) : "r"(a) : "memory"); return v; }
__device__ __forceinline__ uint32_t lds1(uint32_t a) { uint32_t v; asm volatile("ld.shared.u32 %0,[%1];" : "=r"(v) : "r"(a) : "memory"); return v; }
__device__ __forceinline__ void sts4(uint32_t a, uint32_t x, uint32_t y, uint32_t z, uint32_t w) { asm volatile("st.shared.v4.u32 [%0],{%1,%2,%3,%4};" ::"r"(a), "r"(x), "r"(y), "r"(z), "r"(w) : "memory"); }
__device__ __forceinline__ void sts2(uint32_t a, uint32_t x, uint32_t y) { asm volatile("st.shared.v2.u32 [%0],{%1,%2};" ::"r"(a), "r"(x), "r"(y) : "memory"); }
__device__ __forceinline__ void sts1(uint32_t a, uint32_t x) { asm volatile("st.shared.u32 [%0],%1;" ::"r"(a), "r"(x) : "memory"); }
__device__ __forceinline__ void sta4(uint32_t a, const uint32_t* v, uint32_t mb) {
  asm volatile("st.async.shared::cluster.mbarrier::complete_tx::bytes.v4.b32 [%0],{%1,%2,%3,%4},[%5];" ::"r"(a), "r"(v[0]), "r"(v[1]), "r"(v[2]), "r"(v[3]), "r"(mb) : "memory");
}
__device__ __forceinline__ uint4 ldg_rlx4(const void* p) { uint4 v; asm volatile("ld.relaxed.gpu.global.v4.u32 {%0,%1,%2,%3},[%4];" : "=r"(v.x), "=r"(v.y), "=r"(v.z), "=r"(v.w) : "l"(p) : "memory"); return v; }
__device__ __forceinline__ uint32_t ldg_rlx1(const void* p) { uint32_t v; asm volatile("ld.relaxed.gpu.global.u32 %0,[%1];" : "=r"(v) : "l"(p) : "memory"); return v; }
__device__ __forceinline__ uint4 ldg_b128(const void* p) {
  uint4 v;
  asm volatile("{.reg .b128 t; .reg .b64 a,b; ld.relaxed.gpu.global.b128 t,[%4]; mov.b128 {a,b},t; mov.b64 {%0,%1},a; mov.b64 {%2,%3},b;}" : "=r"(v.x), "=r"(v.y), "=r"(v.z), "=r"(v.w) : "l"(p) : "memory");
  return v;
}
__device__ __forceinline__ void stg_b128(void* p, uint32_t x, uint32_t y, uint32_t z, uint32_t w) {
  asm volatile("{.reg .b128 t; .reg .b64 a,b; mov.b64 a,{%1,%2}; mov.b64 b,{%3,%4}; mov.b128 t,{a,b}; st.relaxed.gpu.global.b128 [%0],t;}" ::"l"(p), "r"(x), "r"(y), "r"(z), "r"(w) : "memory");
}
__device__ __forceinline__ void stg_rlx2(void* p, uint32_t x, uint32_t y) { asm volatile("st.relaxed.gpu.global.v2.u32 [%0],{%1,%2};" ::"l"(p), "r"(x), "r"(y) : "memory"); }
__device__ __forceinline__ unsigned ld_acq(const unsigned* p) { unsigned v; asm volatile("ld.acquire.gpu.global.u32 %0,[%1];" : "=r"(v) : "l"(p) : "memory"); return v; }
__device__ __forceinline__ void red_rel(unsigned* p) { asm volatile("red.release.gpu.global.add.u32 [%0],1;" ::"l"(p) : "memory"); }
__device__ __forceinline__ void red_rlx(unsigned* p) { asm volatile("red.relaxed.gpu.global.add.u32 [%0],1;" ::"l"(p) : "memory"); }
__device__ __forceinline__ void wait_cnt(const unsigned* p, unsigned n) { int it = 0; while (ld_acq(p) < n) { if (++it > SPIN_LIMIT) __trap(); } }
__device__ __forceinline__ uint32_t clk() { uint32_t c; asm volatile("mov.u32 %0,%%clock;" : "=r"(c)); return c; }
__device__ __forceinline__ uint32_t gtime() { uint32_t c; asm volatile("mov.u32 %0,%%globaltimer_lo;" : "=r"(c)); return c; }
__device__ __forceinline__ float ex2(float x) { float r; asm("ex2.approx.ftz.f32 %0,%1;" : "=f"(r) : "f"(x)); return r; }
__device__ __forceinline__ float silu(float x) { return x * __frcp_rn(1.f + __expf(-x)); }
__device__ __forceinline__ float rbf(float x) { return __bfloat162float(__float2bfloat16_rn(x)); }

__device__ __forceinline__ void wgmma_ss_n128(float* d, uint64_t a, uint64_t b, int sd) {
  asm volatile("{.reg .pred p; setp.ne.b32 p, %66, 0;\n"
    "wgmma.mma_async.sync.aligned.m64n128k16.f32.bf16.bf16 {%0,%1,%2,%3,%4,%5,%6,%7,%8,%9,%10,%11,%12,%13,%14,%15,%16,%17,%18,%19,%20,%21,%22,%23,%24,%25,%26,%27,%28,%29,%30,%31,%32,%33,%34,%35,%36,%37,%38,%39,%40,%41,%42,%43,%44,%45,%46,%47,%48,%49,%50,%51,%52,%53,%54,%55,%56,%57,%58,%59,%60,%61,%62,%63}, %64, %65, p, 1, 1, 0, 1;}\n"
    : "+f"(d[0]),"+f"(d[1]),"+f"(d[2]),"+f"(d[3]),"+f"(d[4]),"+f"(d[5]),"+f"(d[6]),"+f"(d[7]),
      "+f"(d[8]),"+f"(d[9]),"+f"(d[10]),"+f"(d[11]),"+f"(d[12]),"+f"(d[13]),"+f"(d[14]),"+f"(d[15]),
      "+f"(d[16]),"+f"(d[17]),"+f"(d[18]),"+f"(d[19]),"+f"(d[20]),"+f"(d[21]),"+f"(d[22]),"+f"(d[23]),
      "+f"(d[24]),"+f"(d[25]),"+f"(d[26]),"+f"(d[27]),"+f"(d[28]),"+f"(d[29]),"+f"(d[30]),"+f"(d[31]),
      "+f"(d[32]),"+f"(d[33]),"+f"(d[34]),"+f"(d[35]),"+f"(d[36]),"+f"(d[37]),"+f"(d[38]),"+f"(d[39]),
      "+f"(d[40]),"+f"(d[41]),"+f"(d[42]),"+f"(d[43]),"+f"(d[44]),"+f"(d[45]),"+f"(d[46]),"+f"(d[47]),
      "+f"(d[48]),"+f"(d[49]),"+f"(d[50]),"+f"(d[51]),"+f"(d[52]),"+f"(d[53]),"+f"(d[54]),"+f"(d[55]),
      "+f"(d[56]),"+f"(d[57]),"+f"(d[58]),"+f"(d[59]),"+f"(d[60]),"+f"(d[61]),"+f"(d[62]),"+f"(d[63])
    : "l"(a), "l"(b), "r"(sd));
}
__device__ __forceinline__ void wgmma_ss_n192(float* d, uint64_t a, uint64_t b, int sd) {
  asm volatile("{.reg .pred p; setp.ne.b32 p, %98, 0;\n"
    "wgmma.mma_async.sync.aligned.m64n192k16.f32.bf16.bf16 {%0,%1,%2,%3,%4,%5,%6,%7,%8,%9,%10,%11,%12,%13,%14,%15,%16,%17,%18,%19,%20,%21,%22,%23,%24,%25,%26,%27,%28,%29,%30,%31,%32,%33,%34,%35,%36,%37,%38,%39,%40,%41,%42,%43,%44,%45,%46,%47,%48,%49,%50,%51,%52,%53,%54,%55,%56,%57,%58,%59,%60,%61,%62,%63,%64,%65,%66,%67,%68,%69,%70,%71,%72,%73,%74,%75,%76,%77,%78,%79,%80,%81,%82,%83,%84,%85,%86,%87,%88,%89,%90,%91,%92,%93,%94,%95}, %96, %97, p, 1, 1, 0, 1;}\n"
    : "+f"(d[0]),"+f"(d[1]),"+f"(d[2]),"+f"(d[3]),"+f"(d[4]),"+f"(d[5]),"+f"(d[6]),"+f"(d[7]),
      "+f"(d[8]),"+f"(d[9]),"+f"(d[10]),"+f"(d[11]),"+f"(d[12]),"+f"(d[13]),"+f"(d[14]),"+f"(d[15]),
      "+f"(d[16]),"+f"(d[17]),"+f"(d[18]),"+f"(d[19]),"+f"(d[20]),"+f"(d[21]),"+f"(d[22]),"+f"(d[23]),
      "+f"(d[24]),"+f"(d[25]),"+f"(d[26]),"+f"(d[27]),"+f"(d[28]),"+f"(d[29]),"+f"(d[30]),"+f"(d[31]),
      "+f"(d[32]),"+f"(d[33]),"+f"(d[34]),"+f"(d[35]),"+f"(d[36]),"+f"(d[37]),"+f"(d[38]),"+f"(d[39]),
      "+f"(d[40]),"+f"(d[41]),"+f"(d[42]),"+f"(d[43]),"+f"(d[44]),"+f"(d[45]),"+f"(d[46]),"+f"(d[47]),
      "+f"(d[48]),"+f"(d[49]),"+f"(d[50]),"+f"(d[51]),"+f"(d[52]),"+f"(d[53]),"+f"(d[54]),"+f"(d[55]),
      "+f"(d[56]),"+f"(d[57]),"+f"(d[58]),"+f"(d[59]),"+f"(d[60]),"+f"(d[61]),"+f"(d[62]),"+f"(d[63]),
      "+f"(d[64]),"+f"(d[65]),"+f"(d[66]),"+f"(d[67]),"+f"(d[68]),"+f"(d[69]),"+f"(d[70]),"+f"(d[71]),
      "+f"(d[72]),"+f"(d[73]),"+f"(d[74]),"+f"(d[75]),"+f"(d[76]),"+f"(d[77]),"+f"(d[78]),"+f"(d[79]),
      "+f"(d[80]),"+f"(d[81]),"+f"(d[82]),"+f"(d[83]),"+f"(d[84]),"+f"(d[85]),"+f"(d[86]),"+f"(d[87]),
      "+f"(d[88]),"+f"(d[89]),"+f"(d[90]),"+f"(d[91]),"+f"(d[92]),"+f"(d[93]),"+f"(d[94]),"+f"(d[95])
    : "l"(a), "l"(b), "r"(sd));
}
__device__ __forceinline__ void wgmma_rs_n32(float* d, const uint32_t* a, uint64_t b, int sd) {
  asm volatile("{.reg .pred p; setp.ne.b32 p, %21, 0;\n"
    "wgmma.mma_async.sync.aligned.m64n32k16.f32.bf16.bf16 {%0,%1,%2,%3,%4,%5,%6,%7,%8,%9,%10,%11,%12,%13,%14,%15}, {%16,%17,%18,%19}, %20, p, 1, 1, 0;}\n"
    : "+f"(d[0]),"+f"(d[1]),"+f"(d[2]),"+f"(d[3]),"+f"(d[4]),"+f"(d[5]),"+f"(d[6]),"+f"(d[7]),
      "+f"(d[8]),"+f"(d[9]),"+f"(d[10]),"+f"(d[11]),"+f"(d[12]),"+f"(d[13]),"+f"(d[14]),"+f"(d[15])
    : "r"(a[0]), "r"(a[1]), "r"(a[2]), "r"(a[3]), "l"(b), "r"(sd));
}
__device__ __forceinline__ void wgmma_ssT_n32(float* d, uint64_t a, uint64_t b, int sd) {
  asm volatile("{.reg .pred p; setp.ne.b32 p, %18, 0;\n"
    "wgmma.mma_async.sync.aligned.m64n32k16.f32.bf16.bf16 {%0,%1,%2,%3,%4,%5,%6,%7,%8,%9,%10,%11,%12,%13,%14,%15}, %16, %17, p, 1, 1, 1, 0;}\n"
    : "+f"(d[0]),"+f"(d[1]),"+f"(d[2]),"+f"(d[3]),"+f"(d[4]),"+f"(d[5]),"+f"(d[6]),"+f"(d[7]),
      "+f"(d[8]),"+f"(d[9]),"+f"(d[10]),"+f"(d[11]),"+f"(d[12]),"+f"(d[13]),"+f"(d[14]),"+f"(d[15])
    : "l"(a), "l"(b), "r"(sd));
}

__device__ __forceinline__ void wgmma_rs_n32_z(float* d, const uint32_t* a, uint64_t b) {
  asm volatile("{.reg .pred p; setp.ne.b32 p, 0, 0;\n"
    "wgmma.mma_async.sync.aligned.m64n32k16.f32.bf16.bf16 {%0,%1,%2,%3,%4,%5,%6,%7,%8,%9,%10,%11,%12,%13,%14,%15}, {%16,%17,%18,%19}, %20, p, 1, 1, 0;}\n"
    : "=f"(d[0]),"=f"(d[1]),"=f"(d[2]),"=f"(d[3]),"=f"(d[4]),"=f"(d[5]),"=f"(d[6]),"=f"(d[7]),
      "=f"(d[8]),"=f"(d[9]),"=f"(d[10]),"=f"(d[11]),"=f"(d[12]),"=f"(d[13]),"=f"(d[14]),"=f"(d[15])
    : "r"(a[0]), "r"(a[1]), "r"(a[2]), "r"(a[3]), "l"(b));
}

namespace rec {
constexpr int NVR = P_NVR;
constexpr int NVS = 16 - NVR;
constexpr int NWP = P_NWP;
constexpr uint32_t WO = 0;
constexpr uint32_t XB = 65536;
constexpr uint32_t PK = XB + 32768;
constexpr uint32_t VX0 = PK + 24576;
constexpr uint32_t VX1 = VX0 + 4096;
constexpr uint32_t WVS = 131072;
constexpr uint32_t MEM = WVS + 2 * NVS * 2048;
constexpr uint32_t ARO = MEM + 10240;
constexpr uint32_t OB = ARO + 5120;
constexpr uint32_t QT = OB + 2048;
constexpr uint32_t KT = QT + 2048;
constexpr uint32_t RQ = KT + 6144;
constexpr uint32_t RK = RQ + 2048;
constexpr uint32_t SC = RK + 2048;
constexpr uint32_t OT = OB;
constexpr uint32_t TF = SC + 2048;
constexpr uint32_t PRE = MEM + 2 * NVR * 2048;
constexpr uint32_t TA = TF + 8192;
constexpr uint32_t RX = TA + 6144;
constexpr uint32_t VN = RX + 2048;
constexpr uint32_t BARS = VN + 4096;
constexpr uint32_t PACE = BARS + 18 * 8;
constexpr uint32_t SMEM = BARS + 512;
static_assert(PRE + 14336 <= BARS, "staging");
constexpr int NW1 = P_NW1;
static_assert(SMEM <= 232448, "smem");
constexpr int B_E = 2, B_SC = 3, B_S = 4, B_O = 5, B_F = 6, B_W = 7, B_C = 9, B_K = 10, B_Q = 1, B_S2 = 6, B_T2 = 9, B_P = 13, B_T = 14, B_R = 11, B_X = 12, B_V = 8;
constexpr int XC = 16384, X_RING = 131072, X_SC = 65536, X_TOK = 4096;
#define X_VX(i) (((i) >> 1) * 2048 + ((i) & 1) * 512)
#define X_VM(i) (X_VX(i) + 1024)
#define V_RING(n) (((n) & 1) * X_RING + ((n) & 2) * 2048)
#define V_TAG(n) ((~(n) >> 2) & 1)
}
struct RecMaps { CUtensorMap wq, wk, wv, wo, ari, vx; int zero[40]; };

#define F_(x) __uint_as_float(x)
#define U_(x) __float_as_uint(x)
#define AR_R(q) (24 + ((q) & 1) * 16 + ((q) >> 1) * 56)
#define AR_P(q) ((q) >> 1)
#define AR_ROW(i) (24 + ((i) & 1) * 16 + ((i) & 2) * 92 + (((i) >> 2) & 7) + ((i) >> 5) * 128)
constexpr size_t AR_OFF = 32 * 262144;
__device__ __forceinline__ void ar_fetch(uint32_t dst, const CUtensorMap* m, int slot, int half, uint32_t mb) {
  asm volatile("{.reg .pred p; elect.sync _|p, 0xffffffff; @p mbarrier.arrive.expect_tx.shared.b64 _,[%4],10240;\n"
               "@p cp.async.bulk.tensor.3d.shared::cluster.global.mbarrier::complete_tx::bytes [%0],[%1,{%2,%6,%3}],[%4];\n"
               "@p cp.async.bulk.tensor.3d.shared::cluster.global.mbarrier::complete_tx::bytes [%0+5120],[%1,{%2,%7,%5}],[%4];}"
               ::"r"(dst), "l"(m), "r"(slot * 64), "r"(AR_R(half * 2)), "r"(mb), "r"(AR_R(half * 2 + 1)), "r"(AR_P(half * 2)), "r"(AR_P(half * 2 + 1)) : "memory");
}
__device__ __forceinline__ uint4 exch_b128(void* p, uint32_t x, uint32_t y, uint32_t z, uint32_t w) {
  uint4 v;
  asm volatile("{.reg .b128 s, t; .reg .b64 a,b; mov.b64 a,{%5,%6}; mov.b64 b,{%7,%8}; mov.b128 s,{a,b}; atom.relaxed.gpu.global.exch.b128 t,[%4],s;"
               " mov.b128 {a,b},t; mov.b64 {%0,%1},a; mov.b64 {%2,%3},b;}" : "=r"(v.x), "=r"(v.y), "=r"(v.z), "=r"(v.w) : "l"(p), "r"(x), "r"(y), "r"(z), "r"(w) : "memory");
  return v;
}
#define CONSUME(v) do { if ((v) == 0x7fc12345u) sts1(sb + rec::BARS + 96, 0); } while (0)
__device__ __forceinline__ uint2 ldg_b64(const void* p) { uint2 v; asm volatile("{.reg .b64 t; ld.relaxed.gpu.global.b64 t,[%2]; mov.b64 {%0,%1},t;}" : "=r"(v.x), "=r"(v.y) : "l"(p) : "memory"); return v; }
__device__ __forceinline__ void stg_b64(void* p, uint32_t x, uint32_t y) { asm volatile("{.reg .b64 t; mov.b64 t,{%1,%2}; st.relaxed.gpu.global.b64 [%0],t;}" ::"l"(p), "r"(x), "r"(y) : "memory"); }
__device__ __forceinline__ uint32_t tagbad(uint32_t x, uint32_t y, uint32_t tag) { uint32_t r; asm("lop3.b32 %0,%1,%2,%3,0x7e;" : "=r"(r) : "r"(x), "r"(y), "r"(tag)); return r; }

__device__ __forceinline__ bool anybad(uint32_t a, uint32_t b, uint32_t c, uint32_t d, uint32_t e, uint32_t f, uint32_t g, uint32_t h, uint32_t tag) {
  uint32_t r;
  asm volatile("{.reg .b32 t,u,v,w; .reg .pred p; lop3.b32 t,%1,%2,%9,0x7e; lop3.b32 u,%3,%4,%9,0x7e; lop3.b32 v,%5,%6,%9,0x7e; lop3.b32 w,%7,%8,%9,0x7e;"
               " lop3.b32 t,t,u,v,0xfe; lop3.b32 t,t,w,1,0xa8; setp.ne.u32 p,t,0; vote.sync.any.pred p,p,0xffffffff; selp.u32 %0,1,0,p;}"
               : "=r"(r) : "r"(a), "r"(b), "r"(c), "r"(d), "r"(e), "r"(f), "r"(g), "r"(h), "r"(tag));
  return r;
}
__device__ __forceinline__ bool anybad(uint32_t a, uint32_t b, uint32_t c, uint32_t d, uint32_t tag) {
  uint32_t r;
  asm volatile("{.reg .b32 t,u; .reg .pred p; lop3.b32 t,%1,%2,%5,0x7e; lop3.b32 u,%3,%4,%5,0x7e;"
               " lop3.b32 t,t,u,1,0xa8; setp.ne.u32 p,t,0; vote.sync.any.pred p,p,0xffffffff; selp.u32 %0,1,0,p;}"
               : "=r"(r) : "r"(a), "r"(b), "r"(c), "r"(d), "r"(tag));
  return r;
}
#define BADS(r) anybad(r[0].x, r[0].y, r[1].x, r[1].y, r[2].x, r[2].y, r[3].x, r[3].y, tag)
constexpr float SCS = 0.08838834764831845f * 1.4426950408889634f / 16.f;
__device__ __forceinline__ uint32_t pkh(float lo, float hi, uint32_t tag) {
  uint32_t r;
  asm("{.reg .b32 t; cvt.rn.satfinite.f16x2.f32 t,%1,%2; lop3.b32 %0,t,0xfffffffe,%3,0xea;}" : "=r"(r) : "f"(hi), "f"(lo), "r"(tag));
  return r;
}
__device__ __forceinline__ uint32_t addh(uint32_t a, uint32_t b) { uint32_t r; asm("add.rn.f16x2 %0,%1,%2;" : "=r"(r) : "r"(a), "r"(b)); return r; }
__device__ __forceinline__ float hlo(uint32_t v) { float r; asm("{.reg .b16 a,b; mov.b32 {a,b},%1; cvt.f32.f16 %0,a;}" : "=f"(r) : "r"(v)); return r; }
__device__ __forceinline__ float hhi(uint32_t v) { float r; asm("{.reg .b16 a,b; mov.b32 {a,b},%1; cvt.f32.f16 %0,b;}" : "=f"(r) : "r"(v)); return r; }
__device__ __forceinline__ uint32_t ordh(uint32_t v) {
  uint32_t r;
  asm("{.reg .b32 m; prmt.b32 m,%1,0,0xbb99; lop3.b32 %0,%1,m,0x7fff7fff,0x78;}" : "=r"(r) : "r"(v));
  return r;
}
template <bool MASK>
__device__ __forceinline__ float4 softmax2(const uint2 (&r)[4], uint32_t mx, uint32_t my, uint32_t& k) {
  uint32_t x = addh(addh(r[0].x, r[1].x), addh(r[2].x, r[3].x)), y = addh(addh(r[0].y, r[1].y), addh(r[2].y, r[3].y));
  if (MASK) { x = addh(x, mx); y = addh(y, my); }
  asm("max.f16x2 %0,%1,%2;" : "=r"(k) : "r"(x), "r"(y));
  k = ordh(k);
  const int k0 = __reduce_max_sync(~0u, (int)(k << 16)), k1 = __reduce_max_sync(~0u, (int)k);
  const float m0 = hhi(k0 ^ ((k0 >> 31) & 0x7fff0000)) * -16.f, m1 = hhi(k1 ^ ((k1 >> 31) & 0x7fff0000)) * -16.f;
  return make_float4(ex2(fmaf(hlo(x), 16.f, m0)), ex2(fmaf(hhi(x), 16.f, m1)), ex2(fmaf(hlo(y), 16.f, m0)), ex2(fmaf(hhi(y), 16.f, m1)));
}
__device__ __forceinline__ char* mkp(uint32_t lo, uint32_t hi) { uint64_t r; asm("mov.b64 %0,{%1,%2};" : "=l"(r) : "r"(lo), "r"(hi)); return (char*)r; }
#define LO(p) ((uint32_t)(uint64_t)(p))
#define HI(p) ((uint32_t)((uint64_t)(p) >> 32))
__device__ __forceinline__ uint32_t mulbf(uint32_t a, uint32_t b) { uint32_t r; asm("mul.rn.bf16x2 %0,%1,%2;" : "=r"(r) : "r"(a), "r"(b)); return r; }
__device__ __forceinline__ uint32_t fmabf(uint32_t a, uint32_t b, uint32_t c) { uint32_t r; asm("fma.rn.bf16x2 %0,%1,%2,%3;" : "=r"(r) : "r"(a), "r"(b), "r"(c)); return r; }
__device__ __forceinline__ uint32_t addbf(uint32_t a, uint32_t b) { uint32_t r; asm("add.rn.bf16x2 %0,%1,%2;" : "=r"(r) : "r"(a), "r"(b)); return r; }
__device__ __forceinline__ void pv_mem(const uint32_t (&p)[4], uint32_t pm, const uint4 (&v)[4], const uint4 (&vn)[2], uint32_t (&O)[4]) {
  float o[4][4] = {{0, 0, 0, 0}, {0, 0, 0, 0}, {0, 0, 0, 0}, {0, 0, 0, 0}};
  mma16(o[0], v[0].x, v[0].y, v[0].z, v[0].w, p[0], p[1]);
  mma16(o[1], v[2].x, v[2].y, v[2].z, v[2].w, p[0], p[1]);
  mma16(o[2], v[1].x, v[1].y, v[1].z, v[1].w, p[2], p[3]);
  mma16(o[3], v[3].x, v[3].y, v[3].z, v[3].w, p[2], p[3]);
  mma16(o[0], vn[0].x, vn[0].y, vn[0].z, vn[0].w, pm, pm);
  mma16(o[1], vn[1].x, vn[1].y, vn[1].z, vn[1].w, pm, pm);
  O[0] = pk(o[0][0] + o[2][0], o[0][1] + o[2][1]); O[1] = pk(o[0][2] + o[2][2], o[0][3] + o[2][3]);
  O[2] = pk(o[1][0] + o[3][0], o[1][1] + o[3][1]); O[3] = pk(o[1][2] + o[3][2], o[1][3] + o[3][3]);
}
__device__ __forceinline__ void pv_tok(const uint32_t (&p)[4], uint32_t pm, const uint4 (&v)[4], const uint32_t (&vm)[4], uint32_t (&O)[4]) {
  float o[2][4] = {{0, 0, 0, 0}, {0, 0, 0, 0}}, sum[4] = {0, 0, 0, 0};
  const uint32_t one = 0x3f803f80u;
  mma16(sum, one, one, one, one, p[0], p[1]);
  mma16(o[0], v[0].x, v[0].y, v[0].z, v[0].w, p[0], p[1]);
  mma16(o[1], v[2].x, v[2].y, v[2].z, v[2].w, p[0], p[1]);
  mma16(sum, one, one, one, one, p[2], p[3]);
  mma16(o[0], v[1].x, v[1].y, v[1].z, v[1].w, p[2], p[3]);
  mma16(o[1], v[3].x, v[3].y, v[3].z, v[3].w, p[2], p[3]);
  mma8(sum, one, one, pm);
  mma8(o[0], vm[0], vm[1], pm);
  mma8(o[1], vm[2], vm[3], pm);
  float i0, i1;
  asm("rcp.approx.ftz.f32 %0,%1;" : "=f"(i0) : "f"(sum[0]));
  asm("rcp.approx.ftz.f32 %0,%1;" : "=f"(i1) : "f"(sum[1]));
  O[0] = pk(o[0][0] * i0, o[0][1] * i1); O[1] = pk(o[0][2] * i0, o[0][3] * i1);
  O[2] = pk(o[1][0] * i0, o[1][1] * i1); O[3] = pk(o[1][2] * i0, o[1][3] * i1);
}
__device__ __forceinline__ uint32_t sum4bf(uint32_t a, uint32_t b, uint32_t c, uint32_t d) { return addbf(addbf(a, b), addbf(c, d)); }
template <int OFF>
__device__ __forceinline__ void sta1(uint32_t a, uint32_t v, uint32_t mb) {
  asm volatile("st.async.shared::cluster.mbarrier::complete_tx::bytes.b32 [%0+%3],%1,[%2];" ::"r"(a), "r"(v), "r"(mb), "n"(OFF) : "memory");
}

__device__ __forceinline__ void wait_time(uint32_t t) { while ((int)(gtime() - t) < 0) __nanosleep(64); }
__device__ __noinline__ void rec_prefetch(const char* wmod, const char* w1, const char* x, const char* wo) {
  const int hb = blockIdx.x - 128;
  const uint32_t t0 = gtime();
  uint32_t t = t0 + PF0;
#pragma unroll 1
  for (int job = 0; job < (PFT ? 5 : 3); job++) {
    const char* p = job == 0 ? x + (6 + hb) * 65536 : job == 1 ? wmod + hb * 12288 + 4096 : job == 2 ? w1 + hb * 7168 : job == 3 ? x + hb * 8192 : wo + (1020 + hb) * 8192;
    const int n = job == 0 ? 120 - (hb & 2) * 4 : job == 3 ? 128 : 256, d = job == 0 ? 8192 : job == 1 ? 49152 : job == 2 ? 28672 : job == 3 ? 32768 : -32768;
    if (job == 3) t = t0 + PFT;
    PT(8 + job);
#pragma unroll 1
    for (int i = 0; i < n; i++) {
      wait_time(t);
      asm volatile("cp.async.bulk.prefetch.L2.global [%0], %1;" ::"l"(p), "r"(job == 2 ? 7168 : 8192) : "memory");
      p += !job && (i & 7) == 7 ? 204800 : d;
      t += job < 3 ? PFD : PFS;
      if (job && (i & 31) == 31 && ldg_rlx1(&g_fin)) return;
    }
  }
  PT(13);
}
__device__ __noinline__ void rec_helper(uint32_t sb, const bf16* cvec, const bf16* wmod, const char* w1, const bf16* b1, uint32_t t0) {
  const int tid = threadIdx.x, hb = blockIdx.x - 128;
  PT(1);
  for (int i = tid; i < 1024; i += 256) sts1(sb + i * 8, U_(rbf(silu(__bfloat162float(cvec[i])))));
  for (int i = tid; i < 2048; i += 256) g_stat[hb * 2048 + i] = make_uint4(~0u, ~0u, ~0u, ~0u);
  for (int i = tid; i < 512; i += 256) g_cnt[hb * 512 + i] = 0;
#pragma unroll 1
  for (int job = 0; job < 2; job++) {
    wait_time(t0 + PF0 + (job ? 600 : 350) * PFD);
    BAR_SYNC(rec::B_F, 256);
    PT(2 + job * 5);
    const int n8 = job ? 112 : 128, rg = tid >= n8, cg = tid - rg * n8, pitch = job ? 448 : 768;
    const uint4* p = (const uint4*)(job ? w1 + hb * 1792 : (const char*)(wmod + 2048 + hb * 1024)) + rg * pitch + min(cg, n8 - 1);
    float a1[8] = {0, 0, 0, 0, 0, 0, 0, 0}, a2[8] = {0, 0, 0, 0, 0, 0, 0, 0};
#pragma unroll 1
    for (int r0 = rg; r0 < 1024; r0 += 32) {
      uint4 v[16];
#pragma unroll
      for (int i = 0; i < 16; i++) { v[i] = ldg_rlx4(p); p += 2 * pitch; }
#pragma unroll
      for (int i = 0; i < 16; i++) {
        const float2 f = lds2f(sb + (r0 + 2 * i) * 8);
        const float w[8] = {blo(v[i].x), bhi(v[i].x), blo(v[i].y), bhi(v[i].y), blo(v[i].z), bhi(v[i].z), blo(v[i].w), bhi(v[i].w)};
#pragma unroll
        for (int e = 0; e < 8; e++) { a1[e] += f.x * w[e]; a2[e] += f.y * w[e]; }
      }
    }
    const uint32_t rd = sb + 8192;
    if (cg < n8) {
#pragma unroll
      for (int e = 0; e < 8; e++) sts2(rd + rg * 8192 + (cg * 8 + e) * 8, U_(a1[e]), U_(a2[e]));
    }
    BAR_SYNC(rec::B_F, 256);
    if (job == 0) {
      for (int i = tid; i < 1024; i += 256) g_mod[2048 + hb * 1024 + i] = rbf(F_(lds1(rd + i * 8)) + F_(lds1(rd + 8192 + i * 8)));
      BAR_SYNC(rec::B_F, 256);
      PT(6);
      if (tid == 0) { red_rel(&g_mcnt); wait_cnt(&g_mcnt, 4); }
      BAR_SYNC(rec::B_F, 256);
      for (int i = tid; i < 1024; i += 256) sts2(sb + i * 8, U_(rbf(1.f + __ldcg(g_mod + 4096 + i))), U_(__ldcg(g_mod + 3072 + i)));
    } else {
      for (int i = tid; i < 448; i += 256) {
        const int gn = hb * 896 + i * 2;
        const uint32_t bb = *(const uint32_t*)(b1 + gn);
        const float4 u = lds4f(rd + i * 16), w = lds4f(rd + 8192 + i * 16);
        ((uint2*)g_cc)[(gn >> 4) * 8 + ((gn >> 1) & 3) * 2 + ((gn >> 3) & 1)] = make_uint2(pk(u.x + w.x, u.z + w.z), pk(0.5f * (u.y + w.y + blo(bb)), 0.5f * (u.w + w.w + bhi(bb))));
      }
      PT(4);
    }
  }
}

__global__ void __cluster_dims__(2, 1, 1) __launch_bounds__(512, 1)
k_rec(const __grid_constant__ RecMaps mp, const bf16* __restrict__ mem0, const bf16* __restrict__ x, const bf16* __restrict__ cvec,
      const bf16* __restrict__ wmod, const char* __restrict__ w1, const bf16* __restrict__ b1, const char* __restrict__ wo, char* xc, int dF, int dA, int dS, int dM, int dG, int dP, int dX, int dD, int dZ, int dQ, int dV, int dX2) {
  using namespace rec;
  extern __shared__ __align__(1024) char smem[];
  const uint32_t sb = (uint32_t)__cvta_generic_to_shared(smem);
  if ((sb & 0x3FFFF) != 1024) __trap();
  PH(0); RS(0); if (threadIdx.x == 0) PT(0);
  if (threadIdx.x == 0) {
    int b = blockIdx.x;
    if (b >= 8 && b < 128) {
      const int t = (b >> 1) - 4, u = t - 32;
      b = 2 * (t < 32 ? 4 + (t & 16) + (t & 7) * 2 + ((t >> 3) & 1) : 36 + (u / 14) * 14 + (u % 7) * 2 + ((u / 7) & 1)) + (b & 1);
    }
    sts1(sb + rec::PACE + 24, b);
    const int c = blockIdx.x >> 1, l = c < 36 ? (c - 4) & 7 : (c - 36) % 7, m = c < 4 ? c : c < 36 ? (c - 4) >> 3 : (c - 36) / 7;
    const int g = c < 4 ? 15 : (l >> 1) * 4 + (l & 1) + (c < 36 ? 0 : 2);
    unsigned sm;
    asm("mov.u32 %0,%%smid;" : "=r"(sm));
    if (c < 64) g_slot[sm & 255] = 1 + FMAP;
  }
#define ROLE_REFRESH { asm volatile("mov.u32 %0,%%tid.x;" : "=r"(tid)); wid = __shfl_sync(~0u, tid >> 5, 0); b = __shfl_sync(~0u, lds1(sb + PACE + 24), 0); }
#define ROLE_VARS int tid; asm volatile("mov.u32 %0,%%tid.x;" : "=r"(tid)); \
    int wid = __shfl_sync(~0u, tid >> 5, 0), b = __shfl_sync(~0u, lds1(sb + PACE + 24), 0);
#define wg (wid >> 2)
#define iw (wid & 3)
#define h (b >> 2)
#define j (b & 3)
#define a (b & 1)
#define bb ((b >> 1) & 1)
  const uint32_t wbar = sb + BARS + 48, obar = wbar + 8;
  if (threadIdx.x == 256) {
    for (int i = 0; i < 18; i++) if (i != 12) mbar_init(sb + BARS + i * 8, i == 3 || i == 8 || i == 9 || i == 10 ? 2 : 1);
    for (int i = 0; i < 3; i++) mbar_init(sb + PACE + i * 8, 1);
    asm volatile("fence.mbarrier_init.release.cluster;" ::: "memory");
    FENCE_ASYNC_SMEM();
    mbar_expect(sb + BARS, 2048);
    mbar_expect(sb + BARS + 16, 4096);
    mbar_expect(sb + BARS + 32, 4096);
    mbar_expect(sb + BARS + 40, 4096);
  }
  __syncthreads();
  asm volatile("barrier.cluster.arrive.relaxed.aligned;" ::: "memory");
#define lane ((int)(l16 >> 4))
#define l16 (L16 & 0x1f0)
#define PIN(x) __shfl_xor_sync(~0u, (uint32_t)(x), 0)
#define X_LOAD(n, w, u) \
        asm volatile("{.reg .pred p; elect.sync _|p, 0xffffffff; @p mbarrier.arrive.expect_tx.shared.b64 _,[%2],8192;\n" \
                     "@p cp.async.bulk.shared::cluster.global.mbarrier::complete_tx::bytes [%0],[%1],8192,[%2];}" ::"r"(sb + XB + (w) * 16384 + (u) * 8192), \
                     "l"(g_h + (n) * 4096 + a * 2048 + (w) * 1024 + (u) * 512), "r"(sb + BARS + 64 + (w) * 8) : "memory")
#define lpub ((L16 & 0x30) * 64 + ((L16 >> 3) & 0x38))
#define lrow ((L16 & 0x70) + (((L16 >> 3) ^ L16) & 0x70 & ~((L16 >> 3) & 0x40) ? L16 & 0x180 : 512))

  const int role = __shfl_sync(~0u, threadIdx.x >> 7, 0);
  if (role < 2) {
    asm volatile("setmaxnreg.inc.sync.aligned.u32 %0;" ::"n"(RF_));
    ROLE_VARS
    uint32_t L16 = __shfl_sync(~0u, sb + (tid & 31) * 16, tid & 31);
    uint32_t wQ[16][4], wK[16][4], wV[NVR][4];
    uint32_t frag = sb + ((lane & 7) + (lane >> 4) * 8) * 128 + (((iw * 2 + ((lane >> 3) & 1)) ^ (lane & 7)) << 4);
#define QSW (a ? 0 : 64)
    {
      const bool spare = b >= 128;
      const uint32_t t0 = gtime();
      uint4 xr[16];
      int seg = spare ? b - 126 : wg;
      const int half = spare ? wg : a;
      auto x_fetch = [&]() {
        const uint4* px = (const uint4*)x + (seg * 32 + iw * 8 + (lane >> 2)) * 128 + half * 64 + (lane & 3);
#pragma unroll
        for (int i = 0; i < 16; i++) xr[i] = __ldg(px + i * 4);
      };
      if (!spare) {
        uint4 wm[8];
        const uint4* pw = (const uint4*)(wmod + (size_t)((b >> 5) * 256 + (tid >> 3)) * 6144 + (b & 31) * 64) + (tid & 7);
        const float cs = __bfloat162float(cvec[(b >> 5) * 256 + tid]);
#pragma unroll
        for (int i = 0; i < 8; i++) wm[i] = __ldcs(pw + (size_t)i * 32 * 768);
        float* sc = (float*)(smem + PRE);
        sc[tid] = rbf(silu(cs));
        PT(1);
        BAR_SYNC(B_F, 256);
        float acc[8] = {0, 0, 0, 0, 0, 0, 0, 0};
#pragma unroll
        for (int i = 0; i < 8; i++) {
          const float f = sc[i * 32 + (tid >> 3)];
          acc[0] += f * blo(wm[i].x); acc[1] += f * bhi(wm[i].x); acc[2] += f * blo(wm[i].y); acc[3] += f * bhi(wm[i].y);
          acc[4] += f * blo(wm[i].z); acc[5] += f * bhi(wm[i].z); acc[6] += f * blo(wm[i].w); acc[7] += f * bhi(wm[i].w);
        }
#pragma unroll
        for (int i = 0; i < 8; i++) { acc[i] += __shfl_xor_sync(~0u, acc[i], 8); acc[i] += __shfl_xor_sync(~0u, acc[i], 16); }
        float* red = sc + 1024;
        if ((tid & 31) < 8) {
#pragma unroll
          for (int i = 0; i < 8; i++) red[(tid >> 5) * 64 + (tid & 7) * 8 + i] = acc[i];
        }
        BAR_SYNC(B_F, 256);
        PT(2);
        if (tid < 64) {
          float t = 0;
#pragma unroll
          for (int i = 0; i < 8; i++) t += red[i * 64 + tid];
          asm volatile("st.relaxed.gpu.global.u32 [%0],%1;" ::"l"((unsigned*)g_modp + (b >> 5) * 2048 + (b & 31) * 64 + tid), "r"(U_(t) | 1u) : "memory");
        }
      } else {
        asm volatile("griddepcontrol.launch_dependents;");
      }
      x_fetch();
      const uint32_t md = sb + PRE + 6144, rx = mapa(sb, a ^ !spare);
      asm volatile("barrier.cluster.wait.aligned;" ::: "memory");
      if (!spare) {
        mbar_wait(sb + BARS + 88, 0);
#pragma unroll
        for (int i = 0; i < 16; i++) ldsm4t(wQ[i], (frag ^ QSW) + WO + wg * 32768 + i * 2048);
      }
      PT(4);
#pragma unroll 1
      for (int it = 0;; it++) {
        if (tid == 0) mbar_expect(sb + BARS + 104, 512);
        float c[4][4] = {{0, 0, 0, 0}, {0, 0, 0, 0}, {0, 0, 0, 0}, {0, 0, 0, 0}};
#pragma unroll
        for (int i = 0; i < 16; i++) {
          mma16(c[(i & 1) * 2], xr[i].x, 0x3f803f80u, xr[i].y, 0x3f803f80u, xr[i].x, xr[i].y);
          mma16(c[(i & 1) * 2 + 1], xr[i].z, 0x3f803f80u, xr[i].w, 0x3f803f80u, xr[i].z, xr[i].w);
        }
#pragma unroll
        for (int e = 0; e < 4; e++) c[0][e] = (c[0][e] + c[1][e]) + (c[2][e] + c[3][e]);
        const int src = (lane & 28) + (lane >> 3);
        const float sq = __shfl_sync(~0u, (lane & 4) ? c[0][1] : c[0][0], src), sm = __shfl_sync(~0u, (lane & 4) ? c[0][3] : c[0][2], src);
        if ((lane & 3) < 2) sta1<0>(rx + PRE + 10240 + (wid ^ (spare * 4)) * 64 + (lane >> 2) * 8 + (lane & 1) * 4, U_((lane & 1) ? sm : sq), rx + BARS + 104);
        mbar_wait(sb + BARS + 104, it & 1);
        const float2 ot = lds2f(sb + PRE + 10240 + wid * 64 + (lane >> 2) * 8);
        const float mean = (sm + ot.y) * (1.f / 1024);
        const float rs = rsqrtf(fmaxf((sq + ot.x) * (1.f / 1024) - mean * mean, 0.f) + 1e-5f), nm = -mean * rs;
        const uint32_t rh = pk(rs, rs), rl = pk(rs - blo(rh), rs - blo(rh)), n2 = pk(nm, nm);
#define NRM(v) v = fmabf(v, rh, fmabf(v, rl, n2))
#pragma unroll
        for (int i = 0; i < 16; i++) { NRM(xr[i].x); NRM(xr[i].y); NRM(xr[i].z); NRM(xr[i].w); }
        if (!it) {
          PT(3);
#pragma unroll 1
          for (int i = 0; i < 2; i++) {
            uint4 p[4];
            for (int n = 0;; n++) {
#pragma unroll
              for (int e = 0; e < 4; e++) p[e] = ldg_rlx4(g_modp + e * 512 + i * 256 + tid);
              uint32_t ok = 1;
#pragma unroll
              for (int e = 0; e < 4; e++) ok &= p[e].x & p[e].y & p[e].z & p[e].w;
              if (__all_sync(~0u, ok) || n > SPIN_LIMIT / 16) break;
              __nanosleep(100);
            }
#define MSUM(e) (i + rbf((F_(p[0].e) + F_(p[1].e)) + (F_(p[2].e) + F_(p[3].e))))
            sts2(md + i * 2048 + tid * 8, pk(MSUM(x), MSUM(y)), pk(MSUM(z), MSUM(w)));
          }
          BAR_SYNC(B_F, 256);
          PT(5);
        }
        const int e0 = (iw * 8 + (lane >> 2)) * 8 + ((lane & 3) ^ (lane >> 2));
        uint4* dst = g_h + seg * 4096 + half * 2048;
#pragma unroll
        for (int i = 0; i < 16; i++) {
          const uint32_t ma = md + half * 1024 + (lane & 3) * 16 + i * 64;
          const uint4 sv = lds4(ma), cv = lds4(ma + 2048);
          xr[i] = make_uint4(fmabf(xr[i].x, cv.x, sv.x), fmabf(xr[i].y, cv.y, sv.y), fmabf(xr[i].z, cv.z, sv.z), fmabf(xr[i].w, cv.w, sv.w));
        }
        if (!spare) {
#pragma unroll
          for (int i = 0; i < 16; i++) sts4(sb + WO + wg * 32768 + (e0 ^ ((i & 1) * 4)) * 16 + (i >> 1) * 4096, xr[i].x, xr[i].y, xr[i].z, xr[i].w);
          break;
        }
#pragma unroll
        for (int i = 0; i < 16; i++) dst[(e0 ^ ((i & 1) * 4)) + (i >> 1) * 256] = xr[i];
        seg += 4;
        if (seg < 64) x_fetch();
        FENCE_ASYNC();
        BAR_SYNC(B_F, 256);
        if (tid == 0) red_rlx(g_hf + b - 128);
        if (seg >= 64) break;
      }
      if (spare) { rec_helper(sb, cvec, wmod, w1, b1, t0); return; }
      PH(1); PH(2); PT(6);
    }
    ROLE_REFRESH
#define ownv ((iw >> 1) == a)
#define owner (iw >= 2)
#define oi (wid & 1)
    {
      const uint32_t rsb = mapa(sb, owner ? a : a ^ 1);
      const uint32_t pp = rsb + PK + (owner ? 0 : 12288) + (oi * 2048 + wg * 1024) + l16;
      const uint32_t mb = sb + MEM + wg * 5120;
      sts4(L16 + TF + wid * 512, mb + lrow, owner ? L16 + (lane >> 4) * (RK - RQ - 256) + RQ + oi * 1024 + wg * 256 : rsb + RQ + oi * 1024 + 512 + wg * 256 + (l16 >> 2),
           L16 + OB, frag + wg * NVS * 2048);
      sts4(L16 + TF + 4096 + wid * 512, sb + WO + (wid >> 1) * 16384 + ((lane & 7) + (lane >> 4) * 8) * 128 + ((((wid & 1) * 4 + ((lane >> 3) & 1)) ^ (lane & 7)) << 4),
           sb + ARO + wid * 640 + lrow, pp, LO(xc) + h * 262144 + (bb * 2 + (iw >> 1)) * XC + X_VM(0) + oi * 2048 + a * 256 + (l16 >> 1));
    }
    uint32_t tp = L16 + TF + wid * 512;
    auto park_ptr = [&]() { return lds1(tp + 4096 + 8); };
    auto park_w = [&](const uint32_t* w, int m, uint32_t d) {
      if (m == 2) d += (sb & 0x1000000) ? 0 : owner ? 0x1003000 : -0x1003000;
      if (m == 2 ? ownv : owner) {
        sts4(d + m * 4096, w[0], w[1], w[2], w[3]); sts4(d + m * 4096 + 512, w[4], w[5], w[6], w[7]);
      } else {
        const uint32_t pb = (d & 0xff000000u) | (1024 + BARS + (m ? 24 + m * 8 : 16));
        sta4(d + m * 4096, w, pb); sta4(d + m * 4096 + 512, w + 4, pb);
      }
    };
    auto park = [&](const float* f, int m, int n, uint32_t d) {
      uint32_t w[8];
#pragma unroll
      for (int i = 0; i < 8; i++) w[i] = pk(f[2 * i], f[2 * i + 1]);
      park_w(w, m, d);
    };
#define D64(lo) (0x4000004000000000ull | (uint32_t)(lo))
#define XD(i) D64(x | (((i) >> 2) * 256 + ((i) & 3) * 2))
    auto xdesc = [&](uint32_t xb) { return ((uint32_t)__shfl_sync(~0u, 1024 + xb + wg * 16384, 0) >> 4) | 0x10000u; };
    auto rs_issue = [&](float* acc, const uint32_t (&w)[16][4], uint32_t xb, bool fence) {
      const uint32_t x = xdesc(xb);
      if (fence) WG_FENCE();
      wgmma_rs_n32_z(acc, w[0], XD(0));
#pragma unroll
      for (int i = 1; i < 16; i++) wgmma_rs_n32(acc, w[i], XD(i), 1);
      WG_COMMIT();
    };
    auto v_issue = [&](float* acc, uint32_t xb, bool fence) {
      const uint32_t dv = ((uint32_t)__shfl_sync(~0u, 1024 + WVS + wg * NVS * 2048, 0) >> 4) | 0x10000u, x = xdesc(xb);
      if (fence) WG_FENCE();
      wgmma_rs_n32_z(acc, wV[0], XD(0));
#pragma unroll
      for (int i = 1; i < VRF; i++) wgmma_rs_n32(acc, wV[i], XD(i), 1);
#pragma unroll
      for (int i = NVR; i < 16; i++) wgmma_ssT_n32(acc, D64(dv + (i - NVR) * 128), XD(i), 1);
#pragma unroll
      for (int i = VRF; i < NVR; i++) wgmma_rs_n32(acc, wV[i], XD(i), 1);
      WG_COMMIT();
    };
    uint32_t mA, vP[2][4];
#define V_AHEAD mA = lds1(tp); frag = lds1(tp + 12); ldsm4t(vP[0], frag + WVS + (15 - NVR) * 2048); ldsm4t(vP[1], frag + WVS + (14 - NVR) * 2048);
    auto vk_pass = [&](int n, uint32_t d) {
      float acc[16], acc2[16];
      v_issue(acc, XB, true);
      rs_issue(acc2, wK, XB, false);
      if (n < 64) mbar_wait(sb + BARS + 80, (n - 1) & 1);
      WG_WAIT(1);
      if (n < 64) {
        park(acc, 2, n, d);
        BAR_ARRIVE(B_K, 320);
      }
      V_AHEAD
      WG_WAIT(0);
      if (n < 64) park(acc2, 1, n, d + (VPC ? (vP[1][0] ^ mA) & dZ : 0));
    };
    uint32_t q0[8], q1[8];
    {
      float acc[16], acc2[16];
      FENCE_ASYNC_SMEM();
      BAR_SYNC(B_F, 256);
      rs_issue(acc, wQ, WO, true);
      rs_issue(acc2, wQ, WO + 32768, false);
      WG_WAIT(0);
#pragma unroll
      for (int i = 0; i < 8; i++) { q0[i] = pk(acc[2 * i], acc[2 * i + 1]); q1[i] = pk(acc2[2 * i], acc2[2 * i + 1]); }
    }
    mbar_wait(wbar, 0);
    PT(7);
#pragma unroll
    for (int i = 0; i < 16; i++) ldsm4t(wK[i], (frag ^ QSW) + XB + wg * 32768 + i * 2048);
#pragma unroll
    for (int i = 0; i < NVR; i++) ldsm4t(wV[i], frag + MEM + (wg * NVR + i) * 2048);
    FENCE_ASYNC_SMEM();
    PH(3); PT(8);
    CLUSTER_SYNC();
    PT(9);
    frag += wg * NVS * 2048;
    park_w(q0, 0, park_ptr());
    uint32_t k1[8];
    {
      float acc[16], acc2[16];
      asm volatile("" : "+r"(wid));
      rs_issue(acc, wK, WO, true);
      rs_issue(acc2, wK, WO + 32768, false);
      WG_WAIT(0);
      park(acc, 1, 0, park_ptr());
#pragma unroll
      for (int i = 0; i < 8; i++) k1[i] = pk(acc2[2 * i], acc2[2 * i + 1]);
    }
    mbar_wait(sb + BARS + 120, 0);
    PT(10);
#pragma unroll 1
    for (int n = 0; n < 2; n++) {
      float acc[16];
      asm volatile("" : "+r"(wid));
      v_issue(acc, n * XB, true);
      if (n) {
        BAR_SYNC(B_C, 320);
        PT(12);
        mbar_wait(sb + BARS + 24, 0);
        park_w(q1, 0, park_ptr());
        mbar_wait(sb + BARS + 80, 0);
        park_w(k1, 1, park_ptr());
      }
      WG_WAIT(0);
      park(acc, 2, n, park_ptr());
      if (n) break;
      PT(11);
      BAR_SYNC(B_C, 448);
      if (tid == 0) {
        mbar_expect(obar, 65536);
#pragma unroll 1
        for (int i = 0; i < 4; i++) tma2d(sb + WO + i * 16384, &mp.wo, j * 256 + i * 64, h * 128, obar);
      }
    }
    V_AHEAD
    CONSUME(vP[1][0]);
    static_assert(WO == 0, "x");
    {
      BAR_ARRIVE(B_P, 384); BAR_ARRIVE(B_X, 320); BAR_ARRIVE(B_Q, 288);
    }
    PT(13);
    PH(4); RS(1); PT(14);
    ROLE_REFRESH
    for (int s = 0; s < 64; s++) {
      asm volatile("" : "+r"(tp), "+r"(wid));
      asm volatile("mov.u32 %0,%%cluster_ctarank;" : "=r"(b));
      uint32_t vS[NVS][4], bf[8][4];
      static_assert(NVR == 5, "schedule");
#define VLD(k) ldsm4t(vS[(k) - NVR], frag + WVS + ((k) - NVR) * 2048)
#define BLD(t) ldsm4t(bf[t], mA + (t) * 640)
#define VMMA(c, w, i) mma16(c, (w)[0], (w)[1], (w)[2], (w)[3], bf[(i) >> 1][((i) & 1) * 2], bf[(i) >> 1][((i) & 1) * 2 + 1])
#define VS_(c, k) VMMA(c, vS[(k) - NVR], k)
#define QK(i) VMMA(cQ, wQ[i], i); VMMA(cK, wK[i], i)
#define PREV VLD(13); VLD(12); if (NF > 2) VLD(11);
      if (s > 0) BAR_SYNC(B_R, 320);
      float cV[4] = {0, 0, 0, 0}, cW[4] = {0, 0, 0, 0};
      {
        float cQ[4] = {0, 0, 0, 0}, cK[4] = {0, 0, 0, 0};
        BLD(7); BLD(6); BLD(5); BLD(4); if (NB0 > 4) BLD(3);
        SCHED_FENCE(47);
        QK(15); VMMA(cV, vP[0], 15);
        QK(14); VMMA(cV, vP[1], 14);
        QK(13); QK(12);
        SCHED_FENCE(51);
        if (NB0 < 5) BLD(3);
        BLD(2); BLD(1); BLD(0);
        const uint32_t rm = lds1(tp + 4);
        QK(11); QK(10); QK(9); QK(8); QK(7);
        if (PV0 == 6) { SCHED_FENCE(48); PREV }
        QK(6); QK(5);
        if (PV0 == 4) { QK(4); SCHED_FENCE(48); PREV } else { QK(4); }
        QK(3); QK(2); QK(1); QK(0);
        const uint32_t w0 = pk(cQ[0] * SCS, cQ[1] * SCS), w1 = pk(cQ[2] * SCS, cQ[3] * SCS), w2 = pk(cK[0], cK[1]), w3 = pk(cK[2], cK[3]);
        if (owner) {
          stsm4(rm, w0, w1, w2, w3);
          BAR_ARRIVE(B_E, 256);
        } else {
          const uint32_t mm = (rm & 0xff000000u) | (1024 + BARS);
          sta1<0>(rm, w0, mm); sta1<128>(rm, w1, mm);
          sta1<RK - RQ>(rm, w2, mm); sta1<RK - RQ + 128>(rm, w3, mm);
        }
        if (wid == 2) TS(0);
      }
      uint4 t1;
      uint32_t oA, wo[16][4];
      {
        DLY(10)
        if (NF < 3) VLD(11);
        VLD(10);
        VS_(cW, 13); VLD(9); VS_(cV, 12); VLD(8); VLD(7); VMMA(cW, wV[0], 0); VMMA(cV, wV[1], 1); VLD(6);
        VMMA(cW, wV[2], 2); VMMA(cV, wV[3], 3); VLD(5); VMMA(cW, wV[4], 4); VS_(cV, 11);
        VS_(cW, 10); VS_(cV, 9); VS_(cW, 8); VS_(cV, 7); VS_(cW, 6); VS_(cV, 5);
#pragma unroll
        for (int e = 0; e < 4; e++) cV[e] += cW[e];
        const uint32_t ex = tp + (RX - TF) - wg * 2048;
        t1 = lds4(tp + 4096 + (T1L ? vS[3][0] & dZ : 0));
        oA = lds1(tp + 8 + (s & dZ));
        if (wg) {
          sts4(ex, U_(cV[0]), U_(cV[1]), U_(cV[2]), U_(cV[3]));
          BAR_ARRIVE(B_T2, 256);
        }
        if (!wg) {
          BAR_SYNC(B_T2, 256);
          DLY(3)
          const float4 u = lds4f(ex);
          stg_b64(mkp(t1.w ^ ((s & 1) * X_RING), HI(xc)), (pk(cV[0] + u.x, cV[1] + u.y) & ~1u) | (((s >> 1) + 1) & 1), pk(cV[2] + u.z, cV[3] + u.w));
        }
      }
      if (s == 63) break;
      if (s == 0) mbar_wait(obar, 0);
      {
        const uint32_t woA = t1.x, woB = woA ^ 32;
#pragma unroll
        for (int i = 0; i < NW0; i++) ldsm4t(wo[i], ((i & 1) ? woB : woA) + (i >= WCH ? wo[(i - WCH + NWP) % NWP][0] & dZ : 0) + (i >> 1) * 2048);
        DLY(2)
        BAR_SYNC(B_S, 416);
        float inv0, inv1;
        uint32_t p[4], pm;
        const uint32_t pa = oA + (SC - OB), one = 0x3f803f80u;
#define P_LOAD ldsm4t(p, pa); asm volatile("ldmatrix.sync.aligned.m8n8.x1.trans.shared.b16 {%0},[%1];" : "=r"(pm) : "r"(pa + 512) : "memory");
        if (s < 62) {
          float acc[16];
          rs_issue(acc, wQ, XB, true);
          mbar_wait(sb + BARS + 24, (s + 1) & 1);
          WG_WAIT(0);
          uint32_t qw[8];
#pragma unroll
          for (int i = 0; i < 8; i++) qw[i] = pk(acc[2 * i], acc[2 * i + 1]);
#pragma unroll
          for (int i = NW0; i < NW1; i++) ldsm4t(wo[i], ((i & 1) ? woB : woA) + (i >> 1) * 2048);
          BAR_SYNC(B_V, 512);
          P_LOAD
          park_w(qw, 0, t1.z);
        } else {
#pragma unroll
          for (int i = NW0; i < NW1; i++) ldsm4t(wo[i], ((i & 1) ? woB : woA) + (i >> 1) * 2048);
          BAR_SYNC(B_V, 512);
          P_LOAD
        }
#pragma unroll
        for (int i = NW1; i < NWP; i++) ldsm4t(wo[i], ((i & 1) ? woB : woA) + (i >> 1) * 2048);
        {
          float sum[4] = {0, 0, 0, 0}, su2[4] = {0, 0, 0, 0};
          mma16(sum, one, one, one, one, p[0], p[1]);
          mma16(su2, one, one, one, one, p[2], p[3]);
          mma8(sum, one, one, pm);
          inv0 = sum[0] + su2[0]; inv1 = sum[1] + su2[1];
          SCHED_FENCE(57);
        }
        DLY(7)
        BAR_SYNC(B_O, 416);
        float c[2][4] = {{0, 0, 0, 0}, {0, 0, 0, 0}};
        uint32_t o[4][4];
#pragma unroll
        for (int i = 0; i < NOP_; i++) ldsm4t(o[i], oA + i * 512);
        SCHED_FENCE(46);
        asm("rcp.approx.ftz.f32 %0,%0;" : "+f"(inv0));
        asm("rcp.approx.ftz.f32 %0,%0;" : "+f"(inv1));
#pragma unroll
        for (int i = 0; i < 16; i++) {
          mma16(c[i & 1], wo[i][0], wo[i][1], wo[i][2], wo[i][3], o[i >> 2][i & 2], o[i >> 2][(i & 2) + 1]);
          if (i == 1 && NOP_ < 3) ldsm4t(o[2], oA + 1024);
          if (i == 3 && NOP_ < 4) ldsm4t(o[3], oA + 1536);
          if (i + NWP < 16) ldsm4t(wo[(i + NWP) & 15], (((i + NWP) & 1) ? woB : woA) + ((i + NWP) >> 1) * 2048);
        }
        stsm4(t1.y, pk(c[0][0] * inv0, c[0][1] * inv1), pk(c[0][2] * inv0, c[0][3] * inv1), pk(c[1][0] * inv0, c[1][1] * inv1), pk(c[1][2] * inv0, c[1][3] * inv1));
      }
      const uint32_t d = park_ptr();
      BAR_SYNC(B_W, 384);
      DLY(1)
      vk_pass(s + 2, d);
      if (s < 62) { BAR_ARRIVE(B_P, 384); BAR_ARRIVE(B_X, 320); }
      TS(10);
    }
  } else if (role == 3) {
    asm volatile("setmaxnreg.dec.sync.aligned.u32 24;");
    if (blockIdx.x >= 128) return;
    ROLE_VARS
    const uint32_t L16 = sb + (tid & 31) * 16;
    asm volatile("barrier.cluster.wait.aligned;" ::: "memory");
    CLUSTER_SYNC();
    sts1(sb + PACE + 36, LO(xc) + h * 262144 + X_VM(0));
#define V_LOAD(n) asm volatile("{.reg .pred p; elect.sync _|p, 0xffffffff; @p mbarrier.arrive.expect_tx.shared.b64 _,[%3],8192;\n" \
        "@p cp.async.bulk.tensor.5d.shared::cluster.global.mbarrier::complete_tx::bytes [%0],[%1,{0,0,0,0,%2}],[%3];}" \
        ::"r"(sb + VX0), "l"(&mp.vx), "r"(h * 64 + (V_RING(n) >> 12)), "r"(sb + BARS + 8) : "memory")
    auto vm_stage = [&](int s) {
      const uint32_t tag = ((s >> 1) + 1) & 1;
      const char* xm = mkp(lds1(sb + PACE + 36) + (s & 1) * X_RING + iw * XC + (l16 >> 1), HI(xc));
      uint2 m[4];
      CONSUME(LO(xm));
      BAR_SYNC(B_S2, 256);
      DLY(4)
      int it = 0;
      while (true) {
#pragma unroll
        for (int i = 0; i < 4; i++) m[i] = ldg_b64(xm + (i >> 1) * 2048 + (i & 1) * 256);
        sts4(L16 + VN + iw * 512, m[0].x, m[0].y, m[1].x, m[1].y);
        sts4(L16 + VN + iw * 512 + 2048, m[2].x, m[2].y, m[3].x, m[3].y);
        if (!anybad(m[0].x, m[1].x, m[2].x, m[3].x, tag)) break;
        RP(2);
        if (++it > SPIN_LIMIT) __trap();
      }
      if (s < 63) BAR_ARRIVE(B_V, 512); else BAR_ARRIVE(B_V, 256);
    };
    if (iw == 0) {
      wait_cnt(&g_hcnt, 128);
#pragma unroll 1
      for (int s = 0; s < 63; s++) {
        if (s < 62) for (int it = 0; ldg_rlx1(g_hf + (s & 3)) <= (s >> 2); it++) if (it > SPIN_LIMIT) __trap();
        if (s) BAR_SYNC(B_R, 320); else BAR_SYNC(B_Q, 288);
        if (s < 62) { X_LOAD(s + 2, 0, 0); X_LOAD(s + 2, 1, 0); X_LOAD(s + 2, 0, 1); X_LOAD(s + 2, 1, 1); }
        if (s >= 7) {
          const uint32_t zo = b * 160 + l16;
          if (l16 < 160) CONSUME(exch_b128(xc + AR_OFF + AR_ROW(zo >> 7) * 1024 + (zo & 127) + ((s + 1) & 7) * 128, 0, 0, 0, 0).x);
          __syncwarp();
        }
        if (s < 62) { mbar_wait(sb + BARS + 64, s & 1); mbar_wait(sb + BARS + 72, s & 1); }
        BAR_ARRIVE(B_S, 416);
        vm_stage(s);
        BAR_ARRIVE(B_O, 416);
        BAR_SYNC(B_W, 384);
        DLY(8)
        FENCE_ASYNC_SMEM();
        asm volatile("{.reg .pred p; elect.sync _|p, 0xffffffff; @p cp.reduce.async.bulk.tensor.3d.global.shared::cta.add.bulk_group [%0,{%1,%4,%2}],[%3];}"
                     ::"l"(&mp.ari), "r"((s & 7) * 64), "r"(AR_R(j)), "r"(sb + ARO), "r"(AR_P(j)) : "memory");
        BULK_COMMIT();
        asm volatile("st.relaxed.gpu.global.u32 [%0],%1;" ::"l"(g_tm + (s & 1) * 128 + b), "r"(gtime()) : "memory");
        TS(3);
        BULK_WAIT_READ(0);
      }
      BAR_ARRIVE(B_R, 320);
    } else if (iw == 1) {
      const uint32_t pc = sb + MEM + (lane >> 2) * 640 + (lane & 3) * 144 + (lane & 12), pd = sb + MEM + (lane & 15) * 640 + 576 + (lane & 3) * 16 + (lane & 12);
      uint32_t T = 0, par = 0;
      int est = dA;
#pragma unroll 1
      for (int s = 0; s < 63; s++) {
        if (s) {
          const uint4 tm = ldg_rlx4((const char*)g_tm + ((s + 1) & 1) * 512 + l16);
          const int t0 = tm.x - T, t1 = tm.y - T, t2 = tm.z - T, t3 = tm.w - T;
          const int e = max(dF + (__reduce_add_sync(~0u, (t0 + t1) + (t2 + t3)) >> 7), dV + __reduce_max_sync(~0u, max(max(t0, t1), max(t2, t3))));
          if (s > 1) est += max(min(e >> 2, dP), -dP);
          T += (s == 1 || e > dM ? e : 0) + est - (s == 62 ? L62 : 0);
        }
        vm_stage(s);
        BAR_SYNC(B_W, 384);
        SCHED_FENCE(70);
        const uint32_t tW = gtime();
        if (s == 0) T = tW + 800;
        const uint32_t te = tW + min(max((int)(T - tW), dD), 2000);
        while ((int)(gtime() - te) < 0) {}
        TS(7);
        int it = 0;
        while (true) {
          ar_fetch(sb + MEM, &mp.ari, s & 7, a, sb + BARS + 112);
          mbar_wait(sb + BARS + 112, par);
          par ^= 1;
          const uint32_t n0 = lds1(pc), n1 = lds1(pc + 5120), n2 = lds1(pd);
          if (!__any_sync(~0u, (tagbad(n0, n1, 0x42004200) | (n2 ^ 0x42004200)) != 0)) break;
          RP(0);
          if (++it > SPIN_LIMIT) __trap();
        }
        BAR_ARRIVE(B_R, 320);
        TS(11);
      }
    } else {
      uint32_t src = L16 + PK + (iw & 1) * 2048;
#define qd (L16 + (lane >> 4) * 256 + QT + (iw & 1) * 1024)
#define vd (LO(xc) + h * 262144 + j * XC + (iw & 1) * 2048 + l16)
#define FINISH [&](int n, int m) { \
_Pragma("unroll") \
        for (int i = 1; i >= 0; i--) { \
          const uint32_t p = src + m * 4096 + i * 512; \
          uint4 u = lds4(p); \
          const uint4 w = lds4(p + 1024), y = lds4(p + 12288), z = lds4(p + 13312); \
          u = make_uint4(sum4bf(u.x, w.x, y.x, z.x), sum4bf(u.y, w.y, y.y, z.y), sum4bf(u.z, w.z, y.z, z.z), sum4bf(u.w, w.w, y.w, z.w)); \
          if (m == 2) stg_b128(mkp(vd ^ V_RING(n), HI(xc)) + i * 512, (u.x & ~1u) | V_TAG(n), u.y, u.z, u.w); \
          else stsm4(qd + (n & 1) * 4096 + m * 2048 + i * 256, u.x, u.z, u.y, u.w); \
          SCHED_FENCE(71 + m * 2 + i); \
        } \
      }
#pragma unroll 1
      for (int n = 0; n < 64; n++) {
        src = PIN(src);
        b = __shfl_sync(~0u, lds1(sb + PACE + 24), 0);
        const uint32_t L16 = src - PK - (iw & 1) * 2048;
        auto finish = FINISH;
        if (n < 2) { if (n) BAR_SYNC(B_X, 320); else BAR_SYNC(B_C, 448); }
        mbar_wait(sb + BARS + 16, n & 1);
        if (n > 1) { const uint32_t c = clk(); while (clk() - c < (uint32_t)dQ) {} }
        finish(n, 0);
        __syncwarp();
        if (lane == 0) mbar_arrive_cl(mapa(sb, a ^ 1) + BARS + 24);
        if (n > 1) BAR_SYNC(B_K, 320);
        mbar_wait(sb + BARS + 40, n & 1);
        finish(n, 2);
        if (n > 1) BAR_SYNC(B_X, 320);
        mbar_wait(sb + BARS + 32, n & 1);
        DLY(11)
        finish(n, 1);
        BAR_SYNC(B_T, 64);
        if (lane == 0) {
          if (iw == 2 && n < 63) { mbar_expect(sb + BARS + 16, 4096); mbar_expect(sb + BARS + 32, 4096); mbar_expect(sb + BARS + 40, 4096); }
          mbar_arrive_cl(mapa(sb, a ^ 1) + BARS + 80);
        }
        __syncwarp();
        if (n) {
          vm_stage(n - 1);
          BAR_SYNC(B_W, 384);
          DLY(15)
        } else {
          BAR_SYNC(B_C, 320);
        }
        if (iw == 2) V_LOAD(n);
      }
#undef qd
#undef vd
    }
    { ROLE_REFRESH }
    vm_stage(63);
  } else {
    asm volatile("setmaxnreg.dec.sync.aligned.u32 %0;" ::"n"(RA_));
    if (blockIdx.x >= 128) { if (threadIdx.x == 256) rec_prefetch((const char*)wmod, w1, (const char*)x, wo); return; }
    ROLE_VARS
    uint32_t L16 = __shfl_sync(~0u, sb + (tid & 31) * 16, tid & 31);
    asm volatile("barrier.cluster.wait.aligned; barrier.cluster.arrive.relaxed.aligned;" ::: "memory");
    const uint32_t ts = gtime();
    uint2 m0[8];
#pragma unroll
    for (int r = 0; r < 8; r++) m0[r] = *(const uint2*)(mem0 + r * 1024 + a * 512 + (tid - 256) * 4);
    if (wid == 9) {
#pragma unroll 1
      for (int i = b * 80 + (tid & 31); i < b * 80 + 80; i += 32) ((uint4*)(xc + AR_OFF))[AR_ROW(i >> 6) * 64 + (i & 63)] = make_uint4(0, 0, 0, 0);
      if (b == 0) g_fin = 0;
      FENCE_ASYNC();
      __syncwarp();
      if (tid == 288) red_rlx(&g_hcnt);
    }
    if (tid == 256) {
      const int col = h * 128 + bb * 64;
#pragma unroll 1
      for (int c = 0, w = 0; w < 12; c++) {
#pragma unroll 1
        for (; w <= c - (c < WC0 ? 2 : 3); w++) {
          mbar_wait(sb + PACE + (w % 3) * 8, (w / 3) & 1);
          PT(18 + w);
          if (w == 3) mbar_arrive(sb + BARS + 88);
          if (w == 8) mbar_arrive(wbar);
        }
        const uint32_t mb = sb + PACE + (c % 3) * 8;
        if (c >= 12 && c < 12 + WPE) tma2d_pf(&mp.wo, j * 256 + (c - 12) * 64, h * 128);
        if (c >= 12) continue;
        if (c < 9 && c != 4) {
          const int u = c > 4 ? c - 5 : c;
          mbar_expect(mb, 16384);
          tma2d(sb + (c > 4) * XB + u * 16384, c > 4 ? &mp.wk : &mp.wq, col, a * 512 + u * 128, mb);
        } else {
          const int n = c == 4 ? NVR : NVS, i0 = c == 4 ? 0 : (c - 9) * 8, i1 = c == 4 ? 2 * NVR : min(i0 + 8, 2 * NVS);
          mbar_expect(mb, (i1 - i0) * 2048);
#pragma unroll 1
          for (int i = i0; i < i1; i++)
            tma2d(sb + (c == 4 ? MEM : WVS) + i * 2048, &mp.wv, col, a * 512 + (i >= n ? 16 - n + i : i) * 16 + (c == 4 ? 0 : NVR * 16), mb);
        }
      }
      mbar_arrive(sb + BARS + 120);
      for (int i = 0; i < 3; i++) asm volatile("mbarrier.inval.shared.b64 [%0];" ::"r"(sb + PACE + i * 8) : "memory");
    }
    __syncwarp();
    asm volatile("barrier.cluster.wait.aligned;" ::: "memory");
#pragma unroll 4
    for (int i = 0; i < 16; i++) {
      const uint4 v = lds4(L16 + WO + 32768 + iw * 8192 + i * 512);
      sts4(L16 + XB + iw * 8192 + i * 512, v.x, v.y, v.z, v.w);
    }
#pragma unroll
    for (int i = 0; i < 4; i++) {
      const int k = (tid - 256) * 4 + i, m = (k >> 3) & 3, r = k & 7;
#define M0W(r) __byte_perm((i & 2) ? m0[r].y : m0[r].x, (i & 2) ? m0[r + 1].y : m0[r + 1].x, (i & 1) ? 0x7632 : 0x5410)
      sts4(sb + MEM + (k >> 5) * 640 + (r == m ? 512 : m * 128) + r * 16, M0W(0), M0W(2), M0W(4), M0W(6));
    }
#pragma unroll 1
    for (int i = tid - 256; i < 192; i += 128) {
      const uint32_t c = i < 128 ? 0x42004200 : 0x3f803f80;
      sts4(sb + MEM + (i >> 3) * 640 + ((i & 7) < 4 ? (i & 7) * 144 : 512 + (i & 7) * 16), c, c, c, c);
    }
    static_assert(ARO == MEM + 16 * 640, "counters");
    FENCE_ASYNC_SMEM();
    BAR_ARRIVE(B_C, 448);
    if (tid == 256) {
      wait_time(ts + 1);
#pragma unroll 1
      for (int c = WPE; c < 4; c++) tma2d_pf(&mp.wo, j * 256 + c * 64, h * 128);
    }
    __syncwarp();
#define pr (L16 + SC)
    {
      const int lim = j * 8 + iw * 2 - (lane & 7) - (lane & 8) * 2;
      const bool mk = L16 & 256;
      const int rw = lane >> 2;
      sts4(L16 + TA + iw * 512,
           iw != 2 ? L16 + KT + (iw & 1) * 256 + (lane >> 4) * 256 : sb + RK + (L16 & 0x80) * 2 + ((L16 >> 1) & 0x80) + (L16 & 0x70),
           L16 + QT + (lane >> 3) * 384, sb + SC + min(lane >> 3, 2) * 256 + (L16 & 0x70) + iw * 4, L16 + (lane >> 4) * 256 + QT + (iw >> 1) * 1024 + (iw & 1) * 256);
      sts4(L16 + TA + 2048 + iw * 512, mk ? 0u : (lim < 0 ? 0xfc00u : 0u) | (lim < -1 ? 0xfc000000u : 0u),
           mk ? 0xfc00fc00u : (lim < 8 ? 0xfc00u : 0u) | (lim < 7 ? 0xfc000000u : 0u),
           ((h * 2 + (iw >> 1)) * 1024 + (j * 8 + rw) * 8 + (((iw & 1) * 4 + (lane & 3)) ^ rw)) * 16, sb + OT + iw * 512 + (L16 & 0x70) * 4 + ((L16 >> 3) & 0x30));
    }
    {
      const uint32_t xh = LO(xc) + h * 262144, xs = xh + X_SC + iw * 1024 + min(lane, 16 + (lane & 7)) * 8;
      sts4(L16 + TA + 4096 + iw * 512, xh + X_SC + j * 256 + iw * 64 + lpub, xs, dS, iw != 2 ? 0 : U_(SCS));
      sts1(L16 + TA + 12 + iw * 512, xs + X_TOK + j * 4096);
    }
    uint32_t tA = L16 + TA + iw * 512;
#define tw (tA - L16 != TA + 1024)
#define XP_(lo) mkp(lo, HI(xc))
    auto publish = [&](char* d, const uint2& w) {
      asm volatile("{.reg .pred p; .reg .b64 t; setp.ne.u32 p,%3,%4; mov.b64 t,{%1,%2}; @p st.relaxed.gpu.global.b64 [%0],t;}" ::"l"(d), "r"(w.x), "r"(w.y), "r"(tA - L16), "n"(TA + 1536) : "memory");
    };
    BAR_SYNC(B_P, 384);
    for (int s = 0; s < 64; s++) {
      asm volatile("" : "+r"(L16), "+r"(tA));
      const uint32_t tag = ((s >> 1) + 1) & 1, ring = (s & 1) * X_RING;
      const uint4 t0 = lds4(tA);
      const uint4 tx = lds4(tA + 4096);
      const uint32_t xo = tx.x ^ ring, xs = tx.y ^ ring;
      const float gm = F_(tx.w);
      const uint32_t qA = t0.y + (ring >> 5);
      uint32_t c0;
      uint2 ts[4];
      uint4 v[4];
      uint32_t af[2][4], qt[4][4];
      {
        const uint32_t aA = t0.x + (tw ? ring >> 5 : 0);
        uint32_t ql[2][4], qr[2][4];
        uint2 pw_;
        float c[4] = {0, 0, 0, 0}, d[4] = {0, 0, 0, 0};
        if (s == PDS) asm volatile("griddepcontrol.launch_dependents;");
#pragma unroll
        for (int i = 0; i < 4; i++) ldsm4t(qt[i], qA + i * 128);
        mbar_wait(sb + BARS + 8, s & 1);
        TS(4);
        BAR_SYNC(B_E, 256);
        DLY(14)
#define PACK(c) make_uint2(pkh(fmaf(c[2], gm, c[0] * SCS), fmaf(c[3], gm, c[1] * SCS), tag), pkh(c[2] * SCS, c[3] * SCS, tag))
        ldsm4t(ql[0], L16 + RQ); ldsm4t(ql[1], L16 + RQ + 1024); ldsm4t(af[0], aA); ldsm4t(af[1], aA + 1024);
        CONSUME(xo);
#define QSUM(t, i) addbf(addbf(ql[t][i], ql[t][i + 2]), addbf(qr[t][i], qr[t][i + 2]))
#define STAIL mma16(c, af[0][0], af[0][1], af[0][2], af[0][3], QSUM(0, 0), QSUM(0, 1)); mma16(d, af[1][0], af[1][1], af[1][2], af[1][3], QSUM(1, 0), QSUM(1, 1));
        if (tw) {
          mbar_wait(sb + BARS, s & 1);
          TS(8);
          ldsm4t(qr[0], L16 + RQ + 512); ldsm4t(qr[1], L16 + RQ + 1536);
          STAIL
          pw_ = make_uint2(pkh(c[0] + d[0], c[1] + d[1], tag), pkh(c[2] + d[2], c[3] + d[3], tag));
        } else {
          uint32_t ar[2][4];
          mbar_wait(sb + BARS, s & 1);
          ldsm4t(qr[0], L16 + RQ + 512); ldsm4t(ar[0], aA + 512); ldsm4t(qr[1], L16 + RQ + 1536); ldsm4t(ar[1], aA + 1536);
#pragma unroll
          for (int i = 0; i < 8; i++) af[i >> 2][i & 3] = addbf(af[i >> 2][i & 3], ar[i >> 2][i & 3]);
          STAIL
          pw_.x = pw_.y = pkh((c[0] + c[2]) + (d[0] + d[2]), (c[1] + c[3]) + (d[1] + d[3]), tag);
        }
        publish(XP_(xo), pw_);
        c0 = clk() + tx.z;
        TS(1);
      }
      uint2 r[4];
      bool vbad;
      uint4 vn[2];
      {
        float e[4][4];
#pragma unroll
        for (int i = 0; i < 4; i++) {
          e[i][0] = e[i][1] = e[i][2] = e[i][3] = 0.f;
          mma16(e[i], af[0][0], af[0][1], af[0][2], af[0][3], qt[i][0], qt[i][1]);
        }
#pragma unroll
        for (int i = 0; i < 4; i++) mma16(e[i], af[1][0], af[1][1], af[1][2], af[1][3], qt[i][2], qt[i][3]);
        SCHED_FENCE(55);
        if (s < 63) BAR_ARRIVE(B_S, 416);
        SCHED_FENCE(58);
        v[0] = lds4(tA + (VX0 - TA)); v[1] = lds4(tA + (VX0 - TA) + 2048); v[2] = lds4(tA + (VX1 - TA)); v[3] = lds4(tA + (VX1 - TA) + 2048);
#pragma unroll
        for (int i = 0; i < 4; i++) ts[i] = PACK(e[i]);
        vbad = anybad(v[0].x, v[1].x, v[2].x, v[3].x, V_TAG(s));
#pragma unroll
        for (int i = 0; i < 4; i++) publish(XP_(xo) + X_TOK + i * 4096, ts[i]);
        while ((int)(clk() - c0) < 0) {}
        TS(5);
#pragma unroll
        for (int u = 0; u < 4; u++) r[u] = ldg_b64(XP_(xs) + u * 256);
        BAR_ARRIVE(B_S2, 256);
      }
      SCHED_FENCE(56);
      uint32_t kk;
      float4 e = softmax2<false>(r, 0, 0, kk);
      if (__builtin_expect(anybad(r[0].x, r[0].y, r[1].x, r[1].y, r[2].x, r[2].y, r[3].x, r[3].y, tag ^ (kk & dZ)), 0)) {
        int it = 0;
        if (s > 8) sts1(tA + 4096 + 8, min(lds1(tA + 4096 + 8) + dX, 500));
        do {
          RP(1);
          if (++it > SPIN_LIMIT) __trap();
#pragma unroll
          for (int u = 0; u < 4; u++) r[u] = ldg_b64(XP_(xs) + u * 256);
        } while (BADS(r));
        e = softmax2<false>(r, 0, 0, kk);
      }
      DLY(5)
      sts1(t0.z, pk(e.x, e.y)); sts1(t0.z + 128, pk(e.z, e.w));
      TS(6);
      if (s < 63) BAR_SYNC(B_V, 512); else BAR_SYNC(B_V, 256);
      uint32_t O[4];
      {
        uint32_t p[4], pm;
        ldsm4t(p, pr);
        asm volatile("ldmatrix.sync.aligned.m8n8.x1.trans.shared.b16 {%0},[%1];" : "=r"(pm) : "r"(pr + 512) : "memory");
        vn[0] = lds4(tA + (VN - TA)); vn[1] = lds4(tA + (VN - TA) + 2048);
        pv_mem(p, pm, v, vn, O);
        if (__builtin_expect(vbad, 0)) {
          int it = 0;
          const uint32_t xv = LO(xc) + (lds1(sb + PACE + 24) >> 2) * 262144 + ((tA - L16 - TA) >> 9) * XC;
          do {
            RP(2);
            if (++it > SPIN_LIMIT) __trap();
#pragma unroll
            for (int u = 0; u < 4; u++) v[u] = ldg_b128(XP_((xv + l16) ^ V_RING(s)) + X_VX(u));
          } while (anybad(v[0].x, v[1].x, v[2].x, v[3].x, V_TAG(s)));
          pv_mem(p, pm, v, vn, O);
        }
      }
      DLY(6)
      stsm4(tA + (OB - TA), O[0], O[1], O[2], O[3]);
      if (s < 63) BAR_ARRIVE(B_O, 416);
      TS(2);
      c0 = clk() + dG;
      SCHED_FENCE(60);
      if (tA == sb + TA) mbar_expect(sb + BARS, 2048);
      const uint32_t vs[4] = {addbf(vn[0].x, vn[0].z), addbf(vn[0].y, vn[0].w), addbf(vn[1].x, vn[1].z), addbf(vn[1].y, vn[1].w)};
      {
        const char* xt = XP_(lds1(tA + 12) ^ ring);
        const uint2 t1 = lds2u(tA + 2048);
        const uint32_t pw = lds1(tA + 8);
        uint2 rt[4];
        CONSUME(LO(xt) ^ t1.x ^ pw);
        while ((int)(clk() - c0) < 0) {}
        int it = 0;
        do {
          if (++it > SPIN_LIMIT) __trap();
#pragma unroll
          for (int u = 0; u < 4; u++) rt[u] = ldg_b64(xt + u * 256);
        } while (BADS(rt));
        uint32_t kt;
        const float4 et = softmax2<true>(rt, t1.x, t1.y, kt);
        sts1(pw + 1024, pk(et.x, et.y)); sts1(pw + 1024 + 128, pk(et.z, et.w));
      }
      s = PIN(s);
      BAR_SYNC(B_SC, 128);
      {
        uint32_t Ot[4], p[4], pm;
        const uint2 t2 = lds2u(tA + 2048 + 8);
        ldsm4t(p, pr + 1024);
        asm volatile("ldmatrix.sync.aligned.m8n8.x1.trans.shared.b16 {%0},[%1];" : "=r"(pm) : "r"(pr + 1024 + 512) : "memory");
        char* od = (char*)g_O + ((s >> 2) * 1048576 + (s & 3) * 4096) + t2.x;
        CONSUME(LO(od) ^ HI(od) ^ pm ^ p[3]);
        TS(9);
        if (s < 62) BAR_SYNC(B_P, 384);
        DLY(13)
        pv_tok(p, pm, v, vs, Ot);
        asm volatile("stmatrix.sync.aligned.m8n8.x4.trans.shared.b16 [%0],{%1,%2,%3,%4};" ::"r"(t2.y), "r"(Ot[0]), "r"(Ot[1]), "r"(Ot[2]), "r"(Ot[3]) : "memory");
        __syncwarp();
        *(uint4*)od = lds4(tA + (OT - TA));
      }
    }
    FENCE_ASYNC();
    BAR_SYNC(B_SC, 128);
    if (tA == sb + TA) red_rlx(&g_fin);
  }
  __syncwarp();
  CLUSTER_SYNC();
  PH(5); RS(2);
}
#undef wg
#undef iw
#undef h
#undef j
#undef a
#undef bb
#undef oi
#undef owner
#undef ownv
#undef pr
#undef PIN
#undef XP_
#undef tw
#undef lane
#undef l16
#undef lrow
#undef lpub

namespace ffn {
constexpr uint32_t BR = 98304;
constexpr uint32_t STG = 196608;
constexpr uint32_t PRM = 229376;
constexpr uint32_t BARS = PRM + 2816;
constexpr uint32_t SMEM = BARS + 18 * 8;
}
#define Y_TILE(rb, kt) (((ALIAS & 1) ? g_h : g_h2) + ((rb) * 16 + (kt)) * 1024)
#define U_TILE(rb, kt) ((ALIAS & 2) ? g_O + ((rb) * 64 + (kt)) * 1024 : g_U + ((rb) * 56 + (kt)) * 1024)
struct FfnMaps { CUtensorMap wo, w1a, w1b, w2, x, out; };

template <int N>
__device__ __forceinline__ void wg_ss(float* d, uint64_t a, uint64_t b, int sd) {
  if (N == 128) wgmma_ss_n128(d, a, b, sd);
  if (N == 192) wgmma_ss_n192(d, a, b, sd);
}
template <int N>
__device__ __forceinline__ void acc_fence(float* d) {
#pragma unroll
  for (int i = 0; i < N; i++) asm volatile("" : "+f"(d[i])::"memory");
}
#define UNPK8(d, v) do { (d)[0] = blo(v.x); (d)[1] = bhi(v.x); (d)[2] = blo(v.y); (d)[3] = bhi(v.y); (d)[4] = blo(v.z); (d)[5] = bhi(v.z); (d)[6] = blo(v.w); (d)[7] = bhi(v.w); } while (0)
struct FfnPipe {
  uint32_t full, emp, ph, aoff;
  int st, sB, prev;
  bool leader;
  template <int N, int S = N>
  __device__ __forceinline__ void issue(float* acc, bool first, uint32_t a = 0) {
    mbar_wait(full + st * 8, ph);
    const uint64_t da = mkdesc((a ? a : 1024 + st * 16384) + aoff, 16, 1024), db = mkdesc(1024 + ffn::BR + sB * (S * 128), 8192, 1024);
    WG_FENCE();
#pragma unroll
    for (int j = 0; j < 4; j++) wg_ss<N>(acc, da + j * 2, db + j * 128, j || !first);
    WG_COMMIT();
    if (++sB == 768 / S) sB = 0;
  }
  __device__ __forceinline__ void release() { if (leader) mbar_arrive(emp + prev * 8); }
  __device__ __forceinline__ void next() { prev = st; if (++st == 6) { st = 0; ph ^= 1; } }
  __device__ __forceinline__ void retire() { WG_WAIT(1); release(); next(); }
};
__device__ __forceinline__ float gelu_h(float hx) {
  float u = hx * fmaf(hx * hx, 8.f * 0.0356774081f, 2.f * 0.7978845608f), t;
  asm("tanh.approx.f32 %0,%1;" : "=f"(t) : "f"(u));
  return fmaf(hx, t, hx);
}
struct FfnEpi {
  uint32_t st2, cc, flip, staged, l0;
  uint2 c;
  float n0, n1, s0, s1;
  __device__ __forceinline__ void flush(uint32_t r) {
    __syncwarp();
    asm volatile("{.reg .pred p; setp.ne.u32 p,%1,0; @p mbarrier.arrive.shared.b64 _,[%0];}" ::"r"(staged + (flip >> 11)), "r"(l0 & r) : "memory");
    flip ^= r << 14;
  }
  __device__ __forceinline__ void half(const float* d, int J, int r) {
#define PRE(i, n, c1, c2) gelu_h(fmaf(r ? d[4 + i] : d[i], i < 2 ? s0 : s1, fmaf(n, c1, c2)))
    asm volatile("stmatrix.sync.aligned.m8n8.x2.shared.b16 [%0],{%1,%2};" ::"r"((st2 ^ ((J & 3) * 32 + r * 16)) + flip),
                 "r"(pk(PRE(0, n0, blo(c.x), blo(c.y)), PRE(1, n0, bhi(c.x), bhi(c.y)))), "r"(pk(PRE(2, n1, blo(c.x), blo(c.y)), PRE(3, n1, bhi(c.x), bhi(c.y)))) : "memory");
#undef PRE
    if ((J & 3) == 3) flush(r);
    cc += r ? 56 : 8;
    c = lds2u(cc);
  }
};

__global__ void __launch_bounds__(384, 1)
k_ffn(const __grid_constant__ FfnMaps mp, const bf16* __restrict__ b2) {
  using namespace ffn;
  extern __shared__ __align__(1024) char smem[];
  const uint32_t sb = (uint32_t)__cvta_generic_to_shared(smem);
  if (sb != 1024) __trap();
  const int tid = threadIdx.x, lane = tid & 31, wg = __shfl_sync(~0u, tid >> 7, 0);
  const uint32_t full = sb + BARS, emp = full + 48, xbar = full + 96, staged = full + 104, tile = full + 136;
  uint32_t fin = 0;
  if (tid >= 288 && tid < 320) fin = ld_acq(&g_fin);
  if (tid < 32) {
    unsigned sm, v = 0;
    asm("mov.u32 %0,%%smid;" : "=r"(sm));
    if (tid == 0) {
      v = atomicExch(&g_slot[sm & 255], 0);
      for (int i = 0; i < 6; i++) { mbar_init(full + i * 8, 1); mbar_init(emp + i * 8, 2); }
      mbar_init(xbar, 2);
      for (int i = 0; i < 2; i++) { mbar_init(staged + i * 8, 8); mbar_init(staged + 16 + i * 8, 1); }
      FENCE_ASYNC_SMEM();
    }
    v = __shfl_sync(~0u, v, 0);
    if (!v) {
      wait_cnt(&g_fin, 128);
      for (int it = 0; !v; it++) {
        const uint4 a = ldg_rlx4(g_slot + tid * 8), b = ldg_rlx4(g_slot + tid * 8 + 4);
        const uint32_t open = __ballot_sync(~0u, a.x | a.y | a.z | a.w | b.x | b.y | b.z | b.w);
        if (!open) break;
        if (it < 16) { __nanosleep(500); continue; }
        if (tid == __ffs(open) - 1) v = atomicExch(&g_slot[tid * 8 + (a.x ? 0 : a.y ? 1 : a.z ? 2 : a.w ? 3 : b.x ? 4 : b.y ? 5 : b.z ? 6 : 7)], 0);
        v = __shfl_sync(~0u, v, __ffs(open) - 1);
      }
    }
    if (tid == 0) sts1(tile, v);
  }
  if (tid == 256) asm volatile("prefetch.tensormap [%0];" ::"l"(&mp.wo) : "memory");
  __syncthreads();
  const int bid = __shfl_sync(~0u, lds1(tile), 0) - 1;
  if (bid < 0) return;
  PH(6);
  FT(1);
  const int rb = bid >> 3, nb = bid & 7;
  unsigned* cnt = g_cnt + rb * 128;
  if (wg == 2) {
    asm volatile("setmaxnreg.dec.sync.aligned.u32 " FRP ";");
    const int pw = __shfl_sync(~0u, (tid >> 5) & 3, 0);
    uint32_t ws = emp, wp = 1, fs = full;
    auto wait_free = [&]() { mbar_wait_q(ws, wp); ws += 8; if (ws == emp + 48) { ws = emp; wp ^= 1; } };
    auto step = [&]() { fs += 8; if (fs == full + 48) fs = full; };
#define K3(c) ((0x65230 >> (c) * 4) & 7)
#define KC(k) ((k) < 2 ? nb * 2 + (k) : (k) < 9 ? ((k) - 2 + ((k) - 2 >= nb)) * 2 : ((k) - 9 + ((k) - 9 >= nb)) * 2 + 1)
    if (pw == 0) {
      uint32_t d = sb + BR + 32768;
      auto put = [&](const CUtensorMap* m, int k, int c) {
        e_expect_tma3d(d, m, k * 64, c, fs, 32768);
        step();
        d += 16384;
        if (d == sb + STG) d = sb + BR;
      };
      int n = 0;
      auto stage_free = [&]() { if (!(n & 7) && n < 56) mbar_wait_q(staged + 16 + (n & 8), (n >> 4) & 1); n++; };
      auto align = [&]() {
        if (ALN && !((n - 1) & 7) && ((ALN >> ((n - 1) >> 3)) & 1)) {
          unsigned* c = g_cnt + 64 + ((n - 1) >> 3);
          if (lane == 0) red_rlx(c);
          for (int it = 0; ldg_rlx1(c) < 128 && it < 64; it++) {}
        }
      };
      FTP(3);
#pragma unroll 1
      for (int k = 0; k < 66; k++) { wait_free(); if (k < 64) put(&mp.wo, k, nb * 2); }
#pragma unroll 1
      for (int k = 0; k < 18; k++) {
        const int u = k >= 2 ? k - 2 : k, kt = KC(u);
        const bool ea = (k & ~1) == 2;
        wait_free();
        e_expect_tma3d(sb + BR + (k & 3) * 24576, ea ? &mp.w1a : &mp.w1b, kt * 64, nb * 7 + (ea ? 3 : 0), fs, ea ? 16384 : k < 2 ? 24576 : 40960);
        step();
      }
      d = sb + BR + 49152;
#pragma unroll 1
      for (int k = 2; k < 32; k++) {
        const int kt = k < 16 ? KC(k) : k & 15;
        stage_free();
        if (k == 2 || k == 9) n++;
        if (k != 7 && k != 8) wait_free();
        align();
        put(&mp.w1a, kt, nb * 7 + 3 + (k >> 4) * 2);
      }
#pragma unroll 1
      for (int c = 0; c < 5; c++)
#pragma unroll 1
        for (int k = K3(c), i = 0; k < 56; k += c < 2 && (i ^= 1) ? 1 : c < 2 ? 6 : 7) { stage_free(); wait_free(); align(); put(&mp.w2, k, nb * 2); }
    } else if (pw == 1) {
      FTP(5);
      if (fin < 128) wait_cnt(&g_fin, 128);
      FTP(6);
      uint32_t d = sb;
      auto put = [&](const uint4* A, bool ld) {
        wait_free();
        if (ld) e_bulk_ld(d, A, 16384, fs);
        step();
        d += 16384;
        if (d == sb + BR) d = sb;
      };
      const uint4* A = g_O + rb * 65536;
#pragma unroll 1
      for (int k = 0; k < 68; k++) put(A + k * 1024, k < 64);
      A = Y_TILE(rb, 0);
      uint32_t ready = 0;
#pragma unroll 1
      for (int k = 2; k < 48; k++) {
        if (k == 16) k = 18;
        const int kt = k < 32 ? KC(k & 15) : k & 15;
        for (int it = 0; !(ready >> ((kt >> 1) + (kt & 1) * 8) & 1); it++) {
          ready = __ballot_sync(~0u, ldg_rlx1(cnt + (lane & 7)) & ((lane & 8) ? 1 : 0x10000));
          if (it > SPIN_LIMIT) __trap();
        }
        if (k == 2) FTP(75);
        put(A + kt * 1024, true);
      }
      A = U_TILE(rb, 0);
#pragma unroll 1
      for (int c = 0; c < 5; c++) {
        for (int it = 0; ldg_rlx1(cnt + 32 + c) < 8; it++) if (it > SPIN_LIMIT) __trap();
#pragma unroll 1
        for (int k = K3(c), i = 0; k < 56; k += c < 2 && (i ^= 1) ? 1 : c < 2 ? 6 : 7) put(A + k * 1024, true);
      }
    } else if (pw == 2) {
#pragma unroll 1
      for (int i = 0; i < XDL; i++) mbar_wait_q(emp, i & 1);
      if (lane == 0) {
        mbar_expect(xbar, 32768);
#pragma unroll 1
        for (int i = 0; i < 256 / XR; i++) {
          tma2d(sb + STG + i * (XR * 128), &mp.x, nb * 128 + (i * XR >> 7) * 64, rb * 128 + ((i * XR) & 127), xbar);
          const uint32_t c = clk();
          while (clk() - c < XTD) {}
        }
      }
      asm volatile("griddepcontrol.wait;" ::: "memory");
      if (lane < 16) g_modp[bid * 16 + lane] = make_uint4(0, 0, 0, 0);
      if (lane >= 16 && bid == 0) { g_hcnt = 0; g_mcnt = 0; g_hf[lane & 3] = 0; }
      if (lane == 0) {
#pragma unroll 1
        for (int g = 1; g < 9; g++) {
          if (g == 1) mbar_wait(staged + 8, 0); else { mbar_wait_q(staged + (g & 1) * 8, (g >> 1) & 1); FENCE_ASYNC_SMEM(); }
          uint4* dst = g == 1 ? Y_TILE(rb, nb * 2 + 1) : U_TILE(rb, nb * 7 + ((0x652431000ull >> g * 4) & 7));
#pragma unroll 1
          for (int i = 0; i < (g > 1 ? 4 : 1); i++) {
            bulk_st(dst + i * 256, sb + STG + (g & 1) * 16384 + i * 4096, g > 1 ? 4096 : 16384);
            const uint32_t c = clk();
            while (g > 1 && clk() - c < USD) {}
          }
          BULK_COMMIT();
          if (g != 2 && g != 4) { BULK_WAIT(0); red_rlx(g == 1 ? cnt + nb : cnt + 32 + (g < 6 ? g >> 2 : g - 4)); }
          BULK_WAIT_READ(0);
          mbar_arrive(staged + 16 + (g & 1) * 8);
        }
      }
    } else {
      const uint32_t prm = sb + PRM, pp = prm + (lane >> 3) * 64 + (lane & 1) * 32 + (lane & 6) * 2;
      const uint2 v2 = ((const uint2*)(b2 + nb * 128))[lane];
      sts1(pp + 768, v2.x); sts1(pp + 784, v2.y);
      asm volatile("griddepcontrol.wait;" ::: "memory");
      const float4* md = (const float4*)(g_mod + nb * 128) + lane;
      { const float4 ga = md[512]; sts1(pp, pk(ga.x, ga.y)); sts1(pp + 16, pk(ga.z, ga.w)); }
      { const float4 cb = md[1024]; sts1(pp + 256, pk(1.f + cb.x, 1.f + cb.y)); sts1(pp + 272, pk(1.f + cb.z, 1.f + cb.w)); }
      { const float4 gb = md[1280]; sts1(pp + 512, pk(gb.x, gb.y)); sts1(pp + 528, pk(gb.z, gb.w)); }
#pragma unroll 1
      for (int i = lane; i < 112; i += 32) { const uint4 c = g_cc[nb * 112 + i]; sts4(prm + 1024 + i * 16, c.x, c.y, c.z, c.w); }
      __syncwarp();
      if (lane == 0) {
        mbar_arrive(xbar);
        mbar_wait(staged, 0);
        bulk_st(Y_TILE(rb, nb * 2), sb + STG, 16384);
        BULK_COMMIT(); BULK_WAIT(0);
        asm volatile("red.relaxed.gpu.global.add.u32 [%0],0x10000;" ::"l"(cnt + nb) : "memory");
        mbar_arrive(staged + 16);
      }
      __syncwarp();
      mbar_wait_q(staged + 24, 0);
      mbar_wait_q(emp + 8, 1);
#pragma unroll 1
      for (int i = 0; i < 4; i++) {
        const uint4* sp = g_stat + (rb * 128 + i * 32 + lane) * 4;
        uint4 v[4];
        for (int it = 0;; it++) {
          uint32_t m = 0;
#pragma unroll
          for (int u = 0; u < 4; u++) { v[u] = ldg_rlx4(sp + u); m = max(max(m, max(v[u].x, v[u].y)), max(v[u].z, v[u].w)); }
          if (!__any_sync(~0u, m == ~0u)) break;
          if (it > SPIN_LIMIT) __trap();
        }
        float m = 0, q = 0;
#pragma unroll
        for (int u = 0; u < 4; u++) { m += F_(v[u].x) + F_(v[u].z); q += F_(v[u].y) + F_(v[u].w); }
        m *= 1.f / 1024;
        const float r = 0.5f * rsqrtf(fmaxf(q * (1.f / 1024) - m * m, 0.f) + 1e-5f);
        sts2(sb + STG + 16384 + (i * 32 + lane) * 8, U_(r), U_(-m * r));
      }
      __syncwarp();
      if (lane < 2) mbar_arrive(xbar);
    }
  } else {
    asm volatile("setmaxnreg.inc.sync.aligned.u32 " FRC ";");
    const int w = (tid >> 5) & 3, q = lane & 3;
    const uint32_t prm = sb + PRM + q * 16;
    const int row0 = wg * 64 + w * 16;
    FfnPipe p;
    p.full = full; p.emp = emp; p.ph = 0; p.aoff = wg * 8192; p.st = 0; p.sB = 2; p.prev = 0; p.leader = (tid & 127) == 0;
    FfnEpi e;
    const uint32_t stg = sb + STG + row0 * 128;
    e.st2 = stg + (lane & 15) * 128 + ((lane & 7) << 4);
    e.cc = sb + PRM + 1024 + q * 16; e.flip = 0; e.staged = staged; e.l0 = lane == 0;
    const uint32_t stw = e.st2 ^ (lane & 16);
    uint32_t x1[32];
    uint4* sp = g_stat + (rb * 128 + row0 + (lane >> 2)) * 4;
    float old[96], r0_, r1_;
    {
      float acc[64];
      p.issue<128>(acc, true); FT(8); p.next();
#pragma unroll 1
      for (int k = 1; k < 64; k++) { p.issue<128>(acc, false); FT(8 + k); p.retire(); }
      float xf[64], gf[32];
      uint32_t cb[16];
      mbar_wait(xbar, 0);
#pragma unroll
      for (int j = 0; j < 8; j++) {
        uint32_t xv[4];
        ldsm4(xv, (stw ^ ((j & 3) * 32)) + (j >> 2) * 16384);
#pragma unroll
        for (int i = 0; i < 4; i++) { xf[j * 8 + i * 2] = blo(xv[i]); xf[j * 8 + i * 2 + 1] = bhi(xv[i]); }
      }
#pragma unroll
      for (int i = 0; i < 4; i++) {
        const uint4 g = lds4(prm + i * 64), c = lds4(prm + 256 + i * 64);
        UNPK8(gf + i * 8, g);
        cb[i * 4] = c.x; cb[i * 4 + 1] = c.y; cb[i * 4 + 2] = c.z; cb[i * 4 + 3] = c.w;
      }
      acc_fence<64>(xf); acc_fence<32>(gf);
      WG_WAIT(0);
      p.release();
      acc_fence<64>(acc);
      PH(7); FT(72);
#pragma unroll
      for (int j = 0; j < 8; j++) {
        uint32_t* o = x1 + j * 4;
#pragma unroll
        for (int i = 0; i < 4; i++)
          o[i] = pk(fmaf(acc[j * 8 + i * 2], gf[j * 4 + (i & 2)], xf[j * 8 + i * 2]), fmaf(acc[j * 8 + i * 2 + 1], gf[j * 4 + (i & 2) + 1], xf[j * 8 + i * 2 + 1]));
        stsm4((stw ^ ((j & 3) * 32)) + (j >> 2) * 16384, mulbf(o[0], cb[j * 2]), mulbf(o[1], cb[j * 2]), mulbf(o[2], cb[j * 2 + 1]), mulbf(o[3], cb[j * 2 + 1]));
        if ((j & 3) == 3) { FENCE_ASYNC_SMEM(); e.flush(1); }
      }
      if (wg) BAR_SYNC(2, 128); else BAR_SYNC(3, 128);
    }
    PH(8); FT(73);
    float acc[64];
    {
      float* accC = old;
      p.sB = 0;
      p.issue<192>(accC, true, 1024 + STG); FT(80); p.next();
      p.issue<192>(accC, false, 1024 + STG + 16384); FT(81);
      FT(78);
      float s0 = 0, s1 = 0, q0 = 0, q1 = 0;
#define X1_FENCE _Pragma("unroll") for (int j = 0; j < 32; j++) asm volatile("" : "+r"(x1[j]));
      X1_FENCE
#pragma unroll
      for (int j = 0; j < 16; j++) {
        const float a = blo(x1[j * 2]), b = bhi(x1[j * 2]), c = blo(x1[j * 2 + 1]), d = bhi(x1[j * 2 + 1]);
        s0 += a + b; s1 += c + d; q0 = fmaf(a, a, fmaf(b, b, q0)); q1 = fmaf(c, c, fmaf(d, d, q1));
      }
#pragma unroll
      for (int o = 1; o < 4; o *= 2) { s0 += __shfl_xor_sync(~0u, s0, o); s1 += __shfl_xor_sync(~0u, s1, o); q0 += __shfl_xor_sync(~0u, q0, o); q1 += __shfl_xor_sync(~0u, q1, o); }
      if (q < 2) {
        uint32_t m = __float_as_uint(q ? s1 : s0), v = __float_as_uint(q ? q1 : q0);
        if (m == ~0u) m = 0x7fffffffu;
        if (v == ~0u) v = 0x7fffffffu;
        stg_rlx2((uint2*)(sp + q * 32) + nb, m, v);
      }
      X1_FENCE
      p.retire();
#pragma unroll 1
      for (int k = 0; k < 2; k++) { p.issue<128, 192>(acc, !k, 1024 + STG + k * 16384); p.retire(); }
#pragma unroll 1
      for (int k = 2; k < 15; k++) { p.issue<192>(accC, false); FT(80 + k); p.retire(); }
      p.issue<192>(accC, false); FT(95);
      mbar_wait(xbar, 1);
      const float2 u0 = lds2f(sb + STG + 16384 + (row0 + (lane >> 2)) * 8), u1 = lds2f(sb + STG + 16384 + (row0 + (lane >> 2)) * 8 + 64);
      r0_ = u0.x; e.n0 = u0.y; r1_ = u1.x; e.n1 = u1.y;
      e.c = lds2u(e.cc);
      p.retire();
      e.s0 = r0_; e.s1 = r1_;
      p.sB = 3;
    }
    PH(9);
    {
      auto pair = [&](int J, bool first, bool one, int fo) {
#pragma unroll 1
        for (int r = 0; r < 2; r++) {
          if (!(one && r)) { p.issue<128>(acc, first && !r); FT(fo + r); p.retire(); }
          acc_fence<8>(old + J * 8);
          e.half(old + J * 8, J, r);
        }
      };
#pragma unroll 1
      for (int i = 0; i < 3; i++) {
        if (i == 2) {
          e.s0 = r0_; e.s1 = r1_;
#pragma unroll
          for (int J = 8; J < 12; J++) pair(J, J == 8, false, 128 + (J - 8) * 2);
          e.cc += 512; e.c = lds2u(e.cc);
          e.s0 = e.s1 = 1.f;
        }
#pragma unroll
        for (int J = 0; J < 8; J++) pair(J, J == 0 && i == 1, !(J & 3) && !i, 96 + i * 16 + (i >> 1) * 8 + J * 2);
        if (i == 2) break;
        e.cc += i ? -768 : 256; e.c = lds2u(e.cc);
        WG_WAIT(0);
        acc_fence<64>(acc);
#pragma unroll
        for (int k = 0; k < 64; k++) old[k] = acc[k] * ((k & 2) ? r1_ : r0_);
        acc_fence<64>(old);
        e.s0 = e.s1 = 1.f;
        PH(10 + i);
      }
#pragma unroll 1
      for (int k = 24; k < 56; k++) {
        if (SKW && k == 56 - SKW && wg) BAR_SYNC(4, 256);
        p.issue<128>(acc, false); FT(128 + k);
        if (SKW && k == 55 && !wg) BAR_ARRIVE(4, 256);
        p.retire();
      }
      float xf[64], gf[32];
#pragma unroll
      for (int i = 0; i < 4; i++) {
        const uint4 g = lds4(prm + 512 + i * 64), h = lds4(prm + 768 + i * 64);
        float hf[8];
        UNPK8(gf + i * 8, g); UNPK8(hf, h);
#pragma unroll
        for (int u = 0; u < 8; u++) {
          const int c = (u >> 2) * 4 + (u & 2);
          xf[i * 16 + u * 2] = fmaf(gf[i * 8 + c], hf[c], blo(x1[i * 8 + u])); xf[i * 16 + u * 2 + 1] = fmaf(gf[i * 8 + c + 1], hf[c + 1], bhi(x1[i * 8 + u]));
        }
      }
      acc_fence<64>(xf); acc_fence<32>(gf);
      mbar_wait(staged + 24, 1);
      mbar_wait(staged + 16, 0);
      WG_WAIT(0);
      acc_fence<64>(acc);
      PH(13); FT(184);
#pragma unroll
      for (int j = 0; j < 8; j++) {
        uint32_t o[4];
#pragma unroll
        for (int i = 0; i < 4; i++)
          o[i] = pk(fmaf(acc[j * 8 + i * 2], gf[j * 4 + (i & 2)], xf[j * 8 + i * 2]), fmaf(acc[j * 8 + i * 2 + 1], gf[j * 4 + (i & 2) + 1], xf[j * 8 + i * 2 + 1]));
        stsm4((stw ^ ((j & 3) * 32)) + (j >> 2) * 16384, o[0], o[1], o[2], o[3]);
        if ((j & 3) == 3) {
          FENCE_ASYNC_SMEM();
          __syncwarp();
          if (lane == 0) { tma2d_st(&mp.out, nb * 128 + (j >> 2) * 64, rb * 128 + row0, stg + (j >> 2) * 16384); BULK_COMMIT(); }
        }
      }
      if (lane == 0) BULK_WAIT_READ(0);
      __syncwarp();
    }
  }
  PH(14); FT(185);
}

typedef CUresult (*EncFn)(CUtensorMap*, CUtensorMapDataType, cuuint32_t, void*, const cuuint64_t*, const cuuint64_t*, const cuuint32_t*,
                          const cuuint32_t*, CUtensorMapInterleave, CUtensorMapSwizzle, CUtensorMapL2promotion, CUtensorMapFloatOOBfill);
static void map2d(EncFn enc, CUtensorMap* m, const void* p, int rows, int cols, int boxRows) {
  cuuint64_t d[2] = {(cuuint64_t)cols, (cuuint64_t)rows}, s[1] = {(cuuint64_t)cols * 2};
  cuuint32_t b[2] = {64, (cuuint32_t)boxRows}, e[2] = {1, 1};
  enc(m, CU_TENSOR_MAP_DATA_TYPE_BFLOAT16, 2, (void*)p, d, s, b, e, CU_TENSOR_MAP_INTERLEAVE_NONE, CU_TENSOR_MAP_SWIZZLE_128B,
      CU_TENSOR_MAP_L2_PROMOTION_L2_128B, CU_TENSOR_MAP_FLOAT_OOB_FILL_NONE);
}
static void map3d(EncFn enc, CUtensorMap* m, const void* p, int rows, int cols, int nch) {
  cuuint64_t d[3] = {64, (cuuint64_t)rows, (cuuint64_t)(cols / 64)}, s[2] = {(cuuint64_t)cols * 2, 128};
  cuuint32_t b[3] = {64, 64, (cuuint32_t)nch}, e[3] = {1, 1, 1};
  enc(m, CU_TENSOR_MAP_DATA_TYPE_BFLOAT16, 3, (void*)p, d, s, b, e, CU_TENSOR_MAP_INTERLEAVE_NONE, CU_TENSOR_MAP_SWIZZLE_128B,
      CU_TENSOR_MAP_L2_PROMOTION_L2_128B, CU_TENSOR_MAP_FLOAT_OOB_FILL_NONE);
}

extern "C" void kernel_launch(void* const* d_in, const int* in_sizes, int n_in, void* d_out, int out_size) {
  const bf16* x = (const bf16*)d_in[0];
  const bf16* mem0 = (const bf16*)d_in[1];
  void* fn = nullptr;
  cudaDriverEntryPointQueryResult qr;
  cudaGetDriverEntryPoint("cuTensorMapEncodeTiled", &fn, cudaEnableDefault, &qr);
  EncFn enc = (EncFn)fn;
  FfnMaps fm = {};
  map3d(enc, &fm.wo, d_in[5], 4096, 1024, 2);
  map3d(enc, &fm.w1a, d_in[8], 1024, 3584, 2);
  map3d(enc, &fm.w1b, d_in[8], 1024, 3584, 3);
  map3d(enc, &fm.w2, d_in[10], 3584, 1024, 2);
  map2d(enc, &fm.x, x, 2048, 1024, XR);
  map2d(enc, &fm.out, d_out, 2048, 1024, 16);
  RecMaps rm = {};
  map2d(enc, &rm.wq, d_in[2], 1024, 4096, 128);
  map2d(enc, &rm.wk, d_in[3], 1024, 4096, 128);
  map2d(enc, &rm.wv, d_in[4], 1024, 4096, 16);
  map2d(enc, &rm.wo, d_in[5], 4096, 1024, 128);
  char* xc = nullptr;
  cudaGetSymbolAddress((void**)&xc, g_xc);
  xc += (0 - (uintptr_t)xc) & 0x1FFFFF;
  {
    cuuint64_t d[3] = {512, 6, 128}, sd[2] = {131072, 1024};
    cuuint32_t bi[3] = {64, 5, 8}, e[3] = {1, 1, 1};
    enc(&rm.ari, CU_TENSOR_MAP_DATA_TYPE_BFLOAT16, 3, xc + AR_OFF, d, sd, bi, e, CU_TENSOR_MAP_INTERLEAVE_NONE, CU_TENSOR_MAP_SWIZZLE_NONE,
        CU_TENSOR_MAP_L2_PROMOTION_NONE, CU_TENSOR_MAP_FLOAT_OOB_FILL_NONE);
  }
  {
    cuuint64_t d[5] = {256, 4, 2, 2, 2048}, sd[4] = {rec::XC, X_VX(1), X_VX(2), 4096};
    cuuint32_t bi[5] = {256, 4, 2, 2, 1}, e[5] = {1, 1, 1, 1, 1};
    enc(&rm.vx, CU_TENSOR_MAP_DATA_TYPE_BFLOAT16, 5, xc, d, sd, bi, e, CU_TENSOR_MAP_INTERLEAVE_NONE, CU_TENSOR_MAP_SWIZZLE_NONE,
        CU_TENSOR_MAP_L2_PROMOTION_NONE, CU_TENSOR_MAP_FLOAT_OOB_FILL_NONE);
  }
  cudaFuncSetAttribute(k_ffn, cudaFuncAttributeMaxDynamicSharedMemorySize, ffn::SMEM);
  cudaFuncSetAttribute(k_rec, cudaFuncAttributeMaxDynamicSharedMemorySize, rec::SMEM);
  cudaStream_t st = cudaStreamPerThread;
  int dF = 450, dA = 2700, dS = 250, dM = 120, dG = 250, dP = 24, dX = 48, dD = 350, dZ = 0, dQ = 750, dV = 370, dX2 = 0;
  k_rec<<<132, 512, rec::SMEM, st>>>(rm, mem0, x, (const bf16*)d_in[12], (const bf16*)d_in[13], (const char*)d_in[8], (const bf16*)d_in[9],
                                     (const char*)d_in[5], xc, dF, dA, dS, dM, dG, dP, dX, dD, dZ, dQ, dV, dX2);
  cudaLaunchConfig_t cfg = {};
  cfg.gridDim = dim3(132); cfg.blockDim = dim3(384); cfg.dynamicSmemBytes = ffn::SMEM; cfg.stream = st;
  cudaLaunchAttribute at[1];
  at[0].id = cudaLaunchAttributeProgrammaticStreamSerialization;
  at[0].val.programmaticStreamSerializationAllowed = 1;
  cfg.attrs = at; cfg.numAttrs = 1;
  cudaLaunchKernelEx(&cfg, k_ffn, fm, (const bf16*)d_in[11]);
}
```

```cpp
#include <cuda_runtime.h>
#include <cuda.h>
#include <cuda_bf16.h>
#include <stdint.h>

typedef __nv_bfloat16 bf16;

__device__ __align__(16) float g_mod[6144];
__device__ __align__(1024) uint4 g_modp[4 * 512];
__device__ unsigned g_hcnt;
__device__ unsigned g_hf[4];
__device__ __align__(1024) uint4 g_h[2048 * 1024 / 8];
__device__ __align__(1024) uint4 g_O[2048 * 4096 / 8];
__device__ __align__(1024) uint4 g_h2[2048 * 1024 / 8];
__device__ __align__(1024) uint4 g_U[2048 * 3584 / 8];
__device__ __align__(1024) uint4 g_stat[2048 * 4];
__device__ __align__(1024) unsigned g_cnt[16 * 4 * 32];
__device__ unsigned g_mcnt;
__device__ unsigned g_slot[256];
__device__ unsigned g_fin;
__device__ __align__(16) uint4 g_cc[224 * 4];
__device__ __align__(1024) uint4 g_xc[44 * 16384];
__device__ __align__(1024) unsigned g_tm[4 * 256];
#define FT(i)
#define FTP(i)
#define PT(i)
#define PH(i)
#define RS(i)
#define RP(i)
#define RPN(i, s)
#define TSV(i, v)
#define TS(i)

#define FRC "232"
#define FRP "40"
#define FMAP (((g >> 2) * 4 + m) * 8 + ((g & 3) ^ ((g & 4) ? 3 : 0)) * 2 + (blockIdx.x & 1))
#define ALIAS 3
#define PFT 150000
#define PFS 104
#define PF0 13000
#define PFD 128
#define NF 3
#define NB0 4
#define PV0 4
#define T1L 1
#define NW0 1
#define VRF 3
#define VPC 0
#define WC0 99
#define WPE 3
#define ALN 0x80
#define SKW 5
#define L62 200
#define DLY(k)
#define USD 150
#define XR 32
#define XTD 500
#define CM 1
#define XDL 6
#define PDS 61
#define P_NVR 5
#define P_NWP 9
#define P_NW1 7
#define RF_ 208
#define RA_ (488 - 2 * RF_)
#define WCH 2
#define NOP_ 2
#define SPIN_LIMIT (1 << 20)
__device__ __forceinline__ uint64_t mkdesc(uint32_t addr, uint32_t lbo, uint32_t sbo) {
  return (uint64_t)((addr & 0x3FFFF) >> 4) | ((uint64_t)(lbo >> 4) << 16) | ((uint64_t)(sbo >> 4) << 32) | (1ull << 62);
}
__device__ __forceinline__ void mbar_init(uint32_t a, int c) { asm volatile("mbarrier.init.shared.b64 [%0],%1;" ::"r"(a), "r"(c) : "memory"); }
__device__ __forceinline__ void mbar_wait(uint32_t a, uint32_t par) {
  asm volatile(
      "{.reg .pred p; .reg .u32 n;\n"
      "mov.u32 n, 0;\n"
      "W: mbarrier.try_wait.parity.shared.b64 p,[%0],%1;\n"
      "@p bra D;\n"
      "add.u32 n, n, 1;\n"
      "setp.lt.u32 p, n, %2;\n"
      "@p bra W;\n"
      "trap;\n"
      "D:}" ::"r"(a), "r"(par), "n"(SPIN_LIMIT) : "memory");
}
__device__ __forceinline__ void mbar_wait_q(uint32_t a, uint32_t par) {
  asm volatile(
      "{.reg .pred p; .reg .u32 n;\n"
      "mov.u32 n, 0;\n"
      "W: mbarrier.try_wait.parity.shared.b64 p,[%0],%1,4000;\n"
      "@p bra D;\n"
      "add.u32 n, n, 1;\n"
      "setp.lt.u32 p, n, %2;\n"
      "@p bra W;\n"
      "trap;\n"
      "D:}" ::"r"(a), "r"(par), "n"(SPIN_LIMIT / 16) : "memory");
}
__device__ __forceinline__ void mbar_expect(uint32_t a, uint32_t b) { asm volatile("mbarrier.arrive.expect_tx.shared.b64 _,[%0],%1;" ::"r"(a), "r"(b) : "memory"); }
__device__ __forceinline__ void mbar_arrive(uint32_t a) { asm volatile("mbarrier.arrive.shared.b64 _,[%0];" ::"r"(a) : "memory"); }
__device__ __forceinline__ uint32_t mapa(uint32_t a, uint32_t cta) { uint32_t r; asm("mapa.shared::cluster.u32 %0,%1,%2;" : "=r"(r) : "r"(a), "r"(cta)); return r; }
__device__ __forceinline__ void mbar_arrive_cl(uint32_t a) { asm volatile("mbarrier.arrive.shared::cluster.b64 _,[%0];" ::"r"(a) : "memory"); }
__device__ __forceinline__ void tma2d(uint32_t dst, const CUtensorMap* m, int c0, int c1, uint32_t mb) {
  asm volatile("cp.async.bulk.tensor.2d.shared::cluster.global.mbarrier::complete_tx::bytes [%0],[%1,{%2,%3}],[%4];" ::"r"(dst), "l"(m), "r"(c0), "r"(c1), "r"(mb) : "memory");
}
__device__ __forceinline__ void tma2d_pf(const CUtensorMap* m, int c0, int c1) {
  asm volatile("cp.async.bulk.prefetch.tensor.2d.L2.global [%0,{%1,%2}];" ::"l"(m), "r"(c0), "r"(c1) : "memory");
}
__device__ __forceinline__ void tma2d_st(const CUtensorMap* m, int c0, int c1, uint32_t src) {
  asm volatile("cp.async.bulk.tensor.2d.global.shared::cta.bulk_group [%0,{%1,%2}],[%3];" ::"l"(m), "r"(c0), "r"(c1), "r"(src) : "memory");
}
__device__ __forceinline__ void bulk_ld(uint32_t dst, const void* src, uint32_t n, uint32_t mb) {
  asm volatile("cp.async.bulk.shared::cluster.global.mbarrier::complete_tx::bytes [%0],[%1],%2,[%3];" ::"r"(dst), "l"(src), "r"(n), "r"(mb) : "memory");
}
__device__ __forceinline__ void bulk_st(void* dst, uint32_t src, uint32_t n) {
  asm volatile("cp.async.bulk.global.shared::cta.bulk_group [%0],[%1],%2;" ::"l"(dst), "r"(src), "r"(n) : "memory");
}
__device__ __forceinline__ void e_expect_tma3d(uint32_t dst, const CUtensorMap* m, int c1, int c2, uint32_t mb, uint32_t bytes) {
  asm volatile("{.reg .pred p; elect.sync _|p, 0xffffffff; @p mbarrier.arrive.expect_tx.shared.b64 _,[%4],%5;\n"
               "@p cp.async.bulk.tensor.3d.shared::cluster.global.mbarrier::complete_tx::bytes [%0],[%1,{0,%2,%3}],[%4];}" ::"r"(dst), "l"(m), "r"(c1), "r"(c2), "r"(mb), "r"(bytes) : "memory");
}
__device__ __forceinline__ void e_bulk_ld(uint32_t dst, const void* src, uint32_t n, uint32_t mb) {
  asm volatile("{.reg .pred p; elect.sync _|p, 0xffffffff; @p cp.async.bulk.shared::cluster.global.mbarrier::complete_tx::bytes [%0],[%1],%2,[%3];}" ::"r"(dst), "l"(src), "r"(n), "r"(mb) : "memory");
}
#define BULK_COMMIT() asm volatile("cp.async.bulk.commit_group;" ::: "memory")
#define BULK_WAIT_READ(n) asm volatile("cp.async.bulk.wait_group.read " #n ";" ::: "memory")
#define BULK_WAIT(n) asm volatile("cp.async.bulk.wait_group " #n ";" ::: "memory")
#define FENCE_ASYNC_SMEM() asm volatile("fence.proxy.async.shared::cta;" ::: "memory")
#define FENCE_ASYNC() asm volatile("fence.proxy.async;" ::: "memory")
#define WG_FENCE() asm volatile("wgmma.fence.sync.aligned;" ::: "memory")
#define WG_COMMIT() asm volatile("wgmma.commit_group.sync.aligned;" ::: "memory")
#define WG_WAIT(n) asm volatile("wgmma.wait_group.sync.aligned " #n ";" ::: "memory")
#define BAR_SYNC(id, n) asm volatile("bar.sync %0,%1;" ::"n"(id), "n"(n) : "memory")
#define BAR_ARRIVE(id, n) asm volatile("bar.arrive %0,%1;" ::"n"(id), "n"(n) : "memory")
#define SCHED_FENCE(k) asm volatile("{.reg .pred p; setp.ne.u32 p,%0,0; @p trap;}" ::"r"(mp.zero[(k) - 46]) : "memory")
#define CLUSTER_SYNC() asm volatile("barrier.cluster.arrive.relaxed.aligned; barrier.cluster.wait.aligned;" ::: "memory")
__device__ __forceinline__ uint32_t pk(float lo, float hi) { uint32_t r; asm("cvt.rn.bf16x2.f32 %0,%1,%2;" : "=r"(r) : "f"(hi), "f"(lo)); return r; }
__device__ __forceinline__ float blo(uint32_t v) { return __uint_as_float(v << 16); }
__device__ __forceinline__ float bhi(uint32_t v) { return __uint_as_float(v & 0xffff0000u); }
__device__ __forceinline__ void ldsm4(uint32_t* r, uint32_t a) {
  asm volatile("ldmatrix.sync.aligned.m8n8.x4.shared.b16 {%0,%1,%2,%3},[%4];" : "=r"(r[0]), "=r"(r[1]), "=r"(r[2]), "=r"(r[3]) : "r"(a) : "memory");
}
__device__ __forceinline__ void ldsm4t(uint32_t* r, uint32_t a) {
  asm volatile("ldmatrix.sync.aligned.m8n8.x4.trans.shared.b16 {%0,%1,%2,%3},[%4];" : "=r"(r[0]), "=r"(r[1]), "=r"(r[2]), "=r"(r[3]) : "r"(a) : "memory");
}
__device__ __forceinline__ void stsm4(uint32_t a, uint32_t r0, uint32_t r1, uint32_t r2, uint32_t r3) {
  asm volatile("stmatrix.sync.aligned.m8n8.x4.shared.b16 [%0],{%1,%2,%3,%4};" ::"r"(a), "r"(r0), "r"(r1), "r"(r2), "r"(r3) : "memory");
}
__device__ __forceinline__ void mma16(float* d, uint32_t a0, uint32_t a1, uint32_t a2, uint32_t a3, uint32_t b0, uint32_t b1) {
  asm volatile("mma.sync.aligned.m16n8k16.row.col.f32.bf16.bf16.f32 {%0,%1,%2,%3},{%4,%5,%6,%7},{%8,%9},{%0,%1,%2,%3};"
               : "+f"(d[0]), "+f"(d[1]), "+f"(d[2]), "+f"(d[3]) : "r"(a0), "r"(a1), "r"(a2), "r"(a3), "r"(b0), "r"(b1));
}
__device__ __forceinline__ void mma8(float* d, uint32_t a0, uint32_t a1, uint32_t b0) {
  asm volatile("mma.sync.aligned.m16n8k8.row.col.f32.bf16.bf16.f32 {%0,%1,%2,%3},{%4,%5},{%6},{%0,%1,%2,%3};"
               : "+f"(d[0]), "+f"(d[1]), "+f"(d[2]), "+f"(d[3]) : "r"(a0), "r"(a1), "r"(b0));
}
__device__ __forceinline__ float4 lds4f(uint32_t a) { float4 v; asm volatile("ld.shared.v4.f32 {%0,%1,%2,%3},[%4];" : "=f"(v.x), "=f"(v.y), "=f"(v.z), "=f"(v.w) : "r"(a) : "memory"); return v; }
__device__ __forceinline__ float2 lds2f(uint32_t a) { float2 v; asm volatile("ld.shared.v2.f32 {%0,%1},[%2];" : "=f"(v.x), "=f"(v.y) : "r"(a) : "memory"); return v; }
__device__ __forceinline__ uint4 lds4(uint32_t a) { uint4 v; asm volatile("ld.shared.v4.u32 {%0,%1,%2,%3},[%4];" : "=r"(v.x), "=r"(v.y), "=r"(v.z), "=r"(v.w) : "r"(a) : "memory"); return v; }
__device__ __forceinline__ uint2 lds2u(uint32_t a) { uint2 v; asm volatile("ld.shared.v2.u32 {%0,%1},[%2];" : "=r"(v.x), "=r"(v.y) : "r"(a) : "memory"); return v; }
__device__ __forceinline__ uint32_t lds1(uint32_t a) { uint32_t v; asm volatile("ld.shared.u32 %0,[%1];" : "=r"(v) : "r"(a) : "memory"); return v; }
__device__ __forceinline__ void sts4(uint32_t a, uint32_t x, uint32_t y, uint32_t z, uint32_t w) { asm volatile("st.shared.v4.u32 [%0],{%1,%2,%3,%4};" ::"r"(a), "r"(x), "r"(y), "r"(z), "r"(w) : "memory"); }
__device__ __forceinline__ void sts2(uint32_t a, uint32_t x, uint32_t y) { asm volatile("st.shared.v2.u32 [%0],{%1,%2};" ::"r"(a), "r"(x), "r"(y) : "memory"); }
__device__ __forceinline__ void sts1(uint32_t a, uint32_t x) { asm volatile("st.shared.u32 [%0],%1;" ::"r"(a), "r"(x) : "memory"); }
__device__ __forceinline__ void sta4(uint32_t a, const uint32_t* v, uint32_t mb) {
  asm volatile("st.async.shared::cluster.mbarrier::complete_tx::bytes.v4.b32 [%0],{%1,%2,%3,%4},[%5];" ::"r"(a), "r"(v[0]), "r"(v[1]), "r"(v[2]), "r"(v[3]), "r"(mb) : "memory");
}
__device__ __forceinline__ uint4 ldg_rlx4(const void* p) { uint4 v; asm volatile("ld.relaxed.gpu.global.v4.u32 {%0,%1,%2,%3},[%4];" : "=r"(v.x), "=r"(v.y), "=r"(v.z), "=r"(v.w) : "l"(p) : "memory"); return v; }
__device__ __forceinline__ uint32_t ldg_rlx1(const void* p) { uint32_t v; asm volatile("ld.relaxed.gpu.global.u32 %0,[%1];" : "=r"(v) : "l"(p) : "memory"); return v; }
__device__ __forceinline__ uint4 ldg_b128(const void* p) {
  uint4 v;
  asm volatile("{.reg .b128 t; .reg .b64 a,b; ld.relaxed.gpu.global.b128 t,[%4]; mov.b128 {a,b},t; mov.b64 {%0,%1},a; mov.b64 {%2,%3},b;}" : "=r"(v.x), "=r"(v.y), "=r"(v.z), "=r"(v.w) : "l"(p) : "memory");
  return v;
}
__device__ __forceinline__ void stg_b128(void* p, uint32_t x, uint32_t y, uint32_t z, uint32_t w) {
  asm volatile("{.reg .b128 t; .reg .b64 a,b; mov.b64 a,{%1,%2}; mov.b64 b,{%3,%4}; mov.b128 t,{a,b}; st.relaxed.gpu.global.b128 [%0],t;}" ::"l"(p), "r"(x), "r"(y), "r"(z), "r"(w) : "memory");
}
__device__ __forceinline__ void stg_rlx2(void* p, uint32_t x, uint32_t y) { asm volatile("st.relaxed.gpu.global.v2.u32 [%0],{%1,%2};" ::"l"(p), "r"(x), "r"(y) : "memory"); }
__device__ __forceinline__ unsigned ld_acq(const unsigned* p) { unsigned v; asm volatile("ld.acquire.gpu.global.u32 %0,[%1];" : "=r"(v) : "l"(p) : "memory"); return v; }
__device__ __forceinline__ void red_rel(unsigned* p) { asm volatile("red.release.gpu.global.add.u32 [%0],1;" ::"l"(p) : "memory"); }
__device__ __forceinline__ void red_rlx(unsigned* p) { asm volatile("red.relaxed.gpu.global.add.u32 [%0],1;" ::"l"(p) : "memory"); }
__device__ __forceinline__ void wait_cnt(const unsigned* p, unsigned n) { int it = 0; while (ld_acq(p) < n) { if (++it > SPIN_LIMIT) __trap(); } }
__device__ __forceinline__ uint32_t clk() { uint32_t c; asm volatile("mov.u32 %0,%%clock;" : "=r"(c)); return c; }
__device__ __forceinline__ uint32_t gtime() { uint32_t c; asm volatile("mov.u32 %0,%%globaltimer_lo;" : "=r"(c)); return c; }
__device__ __forceinline__ float ex2(float x) { float r; asm("ex2.approx.ftz.f32 %0,%1;" : "=f"(r) : "f"(x)); return r; }
__device__ __forceinline__ float silu(float x) { return x * __frcp_rn(1.f + __expf(-x)); }
__device__ __forceinline__ float rbf(float x) { return __bfloat162float(__float2bfloat16_rn(x)); }

__device__ __forceinline__ void wgmma_ss_n128(float* d, uint64_t a, uint64_t b, int sd) {
  asm volatile("{.reg .pred p; setp.ne.b32 p, %66, 0;\n"
    "wgmma.mma_async.sync.aligned.m64n128k16.f32.bf16.bf16 {%0,%1,%2,%3,%4,%5,%6,%7,%8,%9,%10,%11,%12,%13,%14,%15,%16,%17,%18,%19,%20,%21,%22,%23,%24,%25,%26,%27,%28,%29,%30,%31,%32,%33,%34,%35,%36,%37,%38,%39,%40,%41,%42,%43,%44,%45,%46,%47,%48,%49,%50,%51,%52,%53,%54,%55,%56,%57,%58,%59,%60,%61,%62,%63}, %64, %65, p, 1, 1, 0, 1;}\n"
    : "+f"(d[0]),"+f"(d[1]),"+f"(d[2]),"+f"(d[3]),"+f"(d[4]),"+f"(d[5]),"+f"(d[6]),"+f"(d[7]),
      "+f"(d[8]),"+f"(d[9]),"+f"(d[10]),"+f"(d[11]),"+f"(d[12]),"+f"(d[13]),"+f"(d[14]),"+f"(d[15]),
      "+f"(d[16]),"+f"(d[17]),"+f"(d[18]),"+f"(d[19]),"+f"(d[20]),"+f"(d[21]),"+f"(d[22]),"+f"(d[23]),
      "+f"(d[24]),"+f"(d[25]),"+f"(d[26]),"+f"(d[27]),"+f"(d[28]),"+f"(d[29]),"+f"(d[30]),"+f"(d[31]),
      "+f"(d[32]),"+f"(d[33]),"+f"(d[34]),"+f"(d[35]),"+f"(d[36]),"+f"(d[37]),"+f"(d[38]),"+f"(d[39]),
      "+f"(d[40]),"+f"(d[41]),"+f"(d[42]),"+f"(d[43]),"+f"(d[44]),"+f"(d[45]),"+f"(d[46]),"+f"(d[47]),
      "+f"(d[48]),"+f"(d[49]),"+f"(d[50]),"+f"(d[51]),"+f"(d[52]),"+f"(d[53]),"+f"(d[54]),"+f"(d[55]),
      "+f"(d[56]),"+f"(d[57]),"+f"(d[58]),"+f"(d[59]),"+f"(d[60]),"+f"(d[61]),"+f"(d[62]),"+f"(d[63])
    : "l"(a), "l"(b), "r"(sd));
}
__device__ __forceinline__ void wgmma_ss_n192(float* d, uint64_t a, uint64_t b, int sd) {
  asm volatile("{.reg .pred p; setp.ne.b32 p, %98, 0;\n"
    "wgmma.mma_async.sync.aligned.m64n192k16.f32.bf16.bf16 {%0,%1,%2,%3,%4,%5,%6,%7,%8,%9,%10,%11,%12,%13,%14,%15,%16,%17,%18,%19,%20,%21,%22,%23,%24,%25,%26,%27,%28,%29,%30,%31,%32,%33,%34,%35,%36,%37,%38,%39,%40,%41,%42,%43,%44,%45,%46,%47,%48,%49,%50,%51,%52,%53,%54,%55,%56,%57,%58,%59,%60,%61,%62,%63,%64,%65,%66,%67,%68,%69,%70,%71,%72,%73,%74,%75,%76,%77,%78,%79,%80,%81,%82,%83,%84,%85,%86,%87,%88,%89,%90,%91,%92,%93,%94,%95}, %96, %97, p, 1, 1, 0, 1;}\n"
    : "+f"(d[0]),"+f"(d[1]),"+f"(d[2]),"+f"(d[3]),"+f"(d[4]),"+f"(d[5]),"+f"(d[6]),"+f"(d[7]),
      "+f"(d[8]),"+f"(d[9]),"+f"(d[10]),"+f"(d[11]),"+f"(d[12]),"+f"(d[13]),"+f"(d[14]),"+f"(d[15]),
      "+f"(d[16]),"+f"(d[17]),"+f"(d[18]),"+f"(d[19]),"+f"(d[20]),"+f"(d[21]),"+f"(d[22]),"+f"(d[23]),
      "+f"(d[24]),"+f"(d[25]),"+f"(d[26]),"+f"(d[27]),"+f"(d[28]),"+f"(d[29]),"+f"(d[30]),"+f"(d[31]),
      "+f"(d[32]),"+f"(d[33]),"+f"(d[34]),"+f"(d[35]),"+f"(d[36]),"+f"(d[37]),"+f"(d[38]),"+f"(d[39]),
      "+f"(d[40]),"+f"(d[41]),"+f"(d[42]),"+f"(d[43]),"+f"(d[44]),"+f"(d[45]),"+f"(d[46]),"+f"(d[47]),
      "+f"(d[48]),"+f"(d[49]),"+f"(d[50]),"+f"(d[51]),"+f"(d[52]),"+f"(d[53]),"+f"(d[54]),"+f"(d[55]),
      "+f"(d[56]),"+f"(d[57]),"+f"(d[58]),"+f"(d[59]),"+f"(d[60]),"+f"(d[61]),"+f"(d[62]),"+f"(d[63]),
      "+f"(d[64]),"+f"(d[65]),"+f"(d[66]),"+f"(d[67]),"+f"(d[68]),"+f"(d[69]),"+f"(d[70]),"+f"(d[71]),
      "+f"(d[72]),"+f"(d[73]),"+f"(d[74]),"+f"(d[75]),"+f"(d[76]),"+f"(d[77]),"+f"(d[78]),"+f"(d[79]),
      "+f"(d[80]),"+f"(d[81]),"+f"(d[82]),"+f"(d[83]),"+f"(d[84]),"+f"(d[85]),"+f"(d[86]),"+f"(d[87]),
      "+f"(d[88]),"+f"(d[89]),"+f"(d[90]),"+f"(d[91]),"+f"(d[92]),"+f"(d[93]),"+f"(d[94]),"+f"(d[95])
    : "l"(a), "l"(b), "r"(sd));
}
__device__ __forceinline__ void wgmma_rs_n32(float* d, const uint32_t* a, uint64_t b, int sd) {
  asm volatile("{.reg .pred p; setp.ne.b32 p, %21, 0;\n"
    "wgmma.mma_async.sync.aligned.m64n32k16.f32.bf16.bf16 {%0,%1,%2,%3,%4,%5,%6,%7,%8,%9,%10,%11,%12,%13,%14,%15}, {%16,%17,%18,%19}, %20, p, 1, 1, 0;}\n"
    : "+f"(d[0]),"+f"(d[1]),"+f"(d[2]),"+f"(d[3]),"+f"(d[4]),"+f"(d[5]),"+f"(d[6]),"+f"(d[7]),
      "+f"(d[8]),"+f"(d[9]),"+f"(d[10]),"+f"(d[11]),"+f"(d[12]),"+f"(d[13]),"+f"(d[14]),"+f"(d[15])
    : "r"(a[0]), "r"(a[1]), "r"(a[2]), "r"(a[3]), "l"(b), "r"(sd));
}
__device__ __forceinline__ void wgmma_ssT_n32(float* d, uint64_t a, uint64_t b, int sd) {
  asm volatile("{.reg .pred p; setp.ne.b32 p, %18, 0;\n"
    "wgmma.mma_async.sync.aligned.m64n32k16.f32.bf16.bf16 {%0,%1,%2,%3,%4,%5,%6,%7,%8,%9,%10,%11,%12,%13,%14,%15}, %16, %17, p, 1, 1, 1, 0;}\n"
    : "+f"(d[0]),"+f"(d[1]),"+f"(d[2]),"+f"(d[3]),"+f"(d[4]),"+f"(d[5]),"+f"(d[6]),"+f"(d[7]),
      "+f"(d[8]),"+f"(d[9]),"+f"(d[10]),"+f"(d[11]),"+f"(d[12]),"+f"(d[13]),"+f"(d[14]),"+f"(d[15])
    : "l"(a), "l"(b), "r"(sd));
}

__device__ __forceinline__ void wgmma_rs_n32_z(float* d, const uint32_t* a, uint64_t b) {
  asm volatile("{.reg .pred p; setp.ne.b32 p, 0, 0;\n"
    "wgmma.mma_async.sync.aligned.m64n32k16.f32.bf16.bf16 {%0,%1,%2,%3,%4,%5,%6,%7,%8,%9,%10,%11,%12,%13,%14,%15}, {%16,%17,%18,%19}, %20, p, 1, 1, 0;}\n"
    : "=f"(d[0]),"=f"(d[1]),"=f"(d[2]),"=f"(d[3]),"=f"(d[4]),"=f"(d[5]),"=f"(d[6]),"=f"(d[7]),
      "=f"(d[8]),"=f"(d[9]),"=f"(d[10]),"=f"(d[11]),"=f"(d[12]),"=f"(d[13]),"=f"(d[14]),"=f"(d[15])
    : "r"(a[0]), "r"(a[1]), "r"(a[2]), "r"(a[3]), "l"(b));
}

namespace rec {
constexpr int NVR = P_NVR;
constexpr int NVS = 16 - NVR;
constexpr int NWP = P_NWP;
constexpr uint32_t WO = 0;
constexpr uint32_t XB = 65536;
constexpr uint32_t PK = XB + 32768;
constexpr uint32_t VX0 = PK + 24576;
constexpr uint32_t VX1 = VX0 + 4096;
constexpr uint32_t WVS = 131072;
constexpr uint32_t MEM = WVS + 2 * NVS * 2048;
constexpr uint32_t ARO = MEM + 10240;
constexpr uint32_t OB = ARO + 5120;
constexpr uint32_t QT = OB + 2048;
constexpr uint32_t KT = QT + 2048;
constexpr uint32_t RQ = KT + 6144;
constexpr uint32_t RK = RQ + 2048;
constexpr uint32_t SC = RK + 2048;
constexpr uint32_t OT = OB;
constexpr uint32_t TF = SC + 2048;
constexpr uint32_t PRE = MEM + 2 * NVR * 2048;
constexpr uint32_t TA = TF + 8192;
constexpr uint32_t RX = TA + 6144;
constexpr uint32_t VN = RX + 2048;
constexpr uint32_t BARS = VN + 4096;
constexpr uint32_t PACE = BARS + 18 * 8;
constexpr uint32_t SMEM = BARS + 512;
static_assert(PRE + 14336 <= BARS, "staging");
constexpr int NW1 = P_NW1;
static_assert(SMEM <= 232448, "smem");
constexpr int B_E = 2, B_SC = 3, B_S = 4, B_O = 5, B_F = 6, B_W = 7, B_C = 9, B_K = 10, B_Q = 1, B_S2 = 6, B_T2 = 9, B_P = 13, B_T = 14, B_R = 11, B_X = 12, B_V = 8;
constexpr int XC = 16384, X_RING = 131072, X_SC = 65536, X_TOK = 4096;
#define X_VX(i) (((i) >> 1) * 2048 + ((i) & 1) * 512)
#define X_VM(i) (X_VX(i) + 1024)
#define V_RING(n) (((n) & 1) * X_RING + ((n) & 2) * 2048)
#define V_TAG(n) ((~(n) >> 2) & 1)
}
struct RecMaps { CUtensorMap wq, wk, wv, wo, ari, vx; int zero[40]; };

#define F_(x) __uint_as_float(x)
#define U_(x) __float_as_uint(x)
#define AR_R(q) (24 + ((q) & 1) * 16 + ((q) >> 1) * 56)
#define AR_P(q) ((q) >> 1)
#define AR_ROW(i) (24 + ((i) & 1) * 16 + ((i) & 2) * 92 + (((i) >> 2) & 7) + ((i) >> 5) * 128)
constexpr size_t AR_OFF = 32 * 262144;
__device__ __forceinline__ void ar_fetch(uint32_t dst, const CUtensorMap* m, int slot, int half, uint32_t mb) {
  asm volatile("{.reg .pred p; elect.sync _|p, 0xffffffff; @p mbarrier.arrive.expect_tx.shared.b64 _,[%4],10240;\n"
               "@p cp.async.bulk.tensor.3d.shared::cluster.global.mbarrier::complete_tx::bytes [%0],[%1,{%2,%6,%3}],[%4];\n"
               "@p cp.async.bulk.tensor.3d.shared::cluster.global.mbarrier::complete_tx::bytes [%0+5120],[%1,{%2,%7,%5}],[%4];}"
               ::"r"(dst), "l"(m), "r"(slot * 64), "r"(AR_R(half * 2)), "r"(mb), "r"(AR_R(half * 2 + 1)), "r"(AR_P(half * 2)), "r"(AR_P(half * 2 + 1)) : "memory");
}
__device__ __forceinline__ uint4 exch_b128(void* p, uint32_t x, uint32_t y, uint32_t z, uint32_t w) {
  uint4 v;
  asm volatile("{.reg .b128 s, t; .reg .b64 a,b; mov.b64 a,{%5,%6}; mov.b64 b,{%7,%8}; mov.b128 s,{a,b}; atom.relaxed.gpu.global.exch.b128 t,[%4],s;"
               " mov.b128 {a,b},t; mov.b64 {%0,%1},a; mov.b64 {%2,%3},b;}" : "=r"(v.x), "=r"(v.y), "=r"(v.z), "=r"(v.w) : "l"(p), "r"(x), "r"(y), "r"(z), "r"(w) : "memory");
  return v;
}
#define CONSUME(v) do { if ((v) == 0x7fc12345u) sts1(sb + rec::BARS + 96, 0); } while (0)
__device__ __forceinline__ uint2 ldg_b64(const void* p) { uint2 v; asm volatile("{.reg .b64 t; ld.relaxed.gpu.global.b64 t,[%2]; mov.b64 {%0,%1},t;}" : "=r"(v.x), "=r"(v.y) : "l"(p) : "memory"); return v; }
__device__ __forceinline__ void stg_b64(void* p, uint32_t x, uint32_t y) { asm volatile("{.reg .b64 t; mov.b64 t,{%1,%2}; st.relaxed.gpu.global.b64 [%0],t;}" ::"l"(p), "r"(x), "r"(y) : "memory"); }
__device__ __forceinline__ uint32_t tagbad(uint32_t x, uint32_t y, uint32_t tag) { uint32_t r; asm("lop3.b32 %0,%1,%2,%3,0x7e;" : "=r"(r) : "r"(x), "r"(y), "r"(tag)); return r; }

__device__ __forceinline__ bool anybad(uint32_t a, uint32_t b, uint32_t c, uint32_t d, uint32_t e, uint32_t f, uint32_t g, uint32_t h, uint32_t tag) {
  uint32_t r;
  asm volatile("{.reg .b32 t,u,v,w; .reg .pred p; lop3.b32 t,%1,%2,%9,0x7e; lop3.b32 u,%3,%4,%9,0x7e; lop3.b32 v,%5,%6,%9,0x7e; lop3.b32 w,%7,%8,%9,0x7e;"
               " lop3.b32 t,t,u,v,0xfe; lop3.b32 t,t,w,1,0xa8; setp.ne.u32 p,t,0; vote.sync.any.pred p,p,0xffffffff; selp.u32 %0,1,0,p;}"
               : "=r"(r) : "r"(a), "r"(b), "r"(c), "r"(d), "r"(e), "r"(f), "r"(g), "r"(h), "r"(tag));
  return r;
}
__device__ __forceinline__ bool anybad(uint32_t a, uint32_t b, uint32_t c, uint32_t d, uint32_t tag) {
  uint32_t r;
  asm volatile("{.reg .b32 t,u; .reg .pred p; lop3.b32 t,%1,%2,%5,0x7e; lop3.b32 u,%3,%4,%5,0x7e;"
               " lop3.b32 t,t,u,1,0xa8; setp.ne.u32 p,t,0; vote.sync.any.pred p,p,0xffffffff; selp.u32 %0,1,0,p;}"
               : "=r"(r) : "r"(a), "r"(b), "r"(c), "r"(d), "r"(tag));
  return r;
}
#define BADS(r) anybad(r[0].x, r[0].y, r[1].x, r[1].y, r[2].x, r[2].y, r[3].x, r[3].y, tag)
constexpr float SCS = 0.08838834764831845f * 1.4426950408889634f / 16.f;
__device__ __forceinline__ uint32_t pkh(float lo, float hi, uint32_t tag) {
  uint32_t r;
  asm("{.reg .b32 t; cvt.rn.satfinite.f16x2.f32 t,%1,%2; lop3.b32 %0,t,0xfffffffe,%3,0xea;}" : "=r"(r) : "f"(hi), "f"(lo), "r"(tag));
  return r;
}
__device__ __forceinline__ uint32_t addh(uint32_t a, uint32_t b) { uint32_t r; asm("add.rn.f16x2 %0,%1,%2;" : "=r"(r) : "r"(a), "r"(b)); return r; }
__device__ __forceinline__ float hlo(uint32_t v) { float r; asm("{.reg .b16 a,b; mov.b32 {a,b},%1; cvt.f32.f16 %0,a;}" : "=f"(r) : "r"(v)); return r; }
__device__ __forceinline__ float hhi(uint32_t v) { float r; asm("{.reg .b16 a,b; mov.b32 {a,b},%1; cvt.f32.f16 %0,b;}" : "=f"(r) : "r"(v)); return r; }
__device__ __forceinline__ uint32_t ordh(uint32_t v) {
  uint32_t r;
  asm("{.reg .b32 m; prmt.b32 m,%1,0,0xbb99; lop3.b32 %0,%1,m,0x7fff7fff,0x78;}" : "=r"(r) : "r"(v));
  return r;
}
template <bool MASK>
__device__ __forceinline__ float4 softmax2(const uint2 (&r)[4], uint32_t mx, uint32_t my, uint32_t& k) {
  uint32_t x = addh(addh(r[0].x, r[1].x), addh(r[2].x, r[3].x)), y = addh(addh(r[0].y, r[1].y), addh(r[2].y, r[3].y));
  if (MASK) { x = addh(x, mx); y = addh(y, my); }
  asm("max.f16x2 %0,%1,%2;" : "=r"(k) : "r"(x), "r"(y));
  k = ordh(k);
  const int k0 = __reduce_max_sync(~0u, (int)(k << 16)), k1 = __reduce_max_sync(~0u, (int)k);
  const float m0 = hhi(k0 ^ ((k0 >> 31) & 0x7fff0000)) * -16.f, m1 = hhi(k1 ^ ((k1 >> 31) & 0x7fff0000)) * -16.f;
  return make_float4(ex2(fmaf(hlo(x), 16.f, m0)), ex2(fmaf(hhi(x), 16.f, m1)), ex2(fmaf(hlo(y), 16.f, m0)), ex2(fmaf(hhi(y), 16.f, m1)));
}
__device__ __forceinline__ char* mkp(uint32_t lo, uint32_t hi) { uint64_t r; asm("mov.b64 %0,{%1,%2};" : "=l"(r) : "r"(lo), "r"(hi)); return (char*)r; }
#define LO(p) ((uint32_t)(uint64_t)(p))
#define HI(p) ((uint32_t)((uint64_t)(p) >> 32))
__device__ __forceinline__ uint32_t mulbf(uint32_t a, uint32_t b) { uint32_t r; asm("mul.rn.bf16x2 %0,%1,%2;" : "=r"(r) : "r"(a), "r"(b)); return r; }
__device__ __forceinline__ uint32_t fmabf(uint32_t a, uint32_t b, uint32_t c) { uint32_t r; asm("fma.rn.bf16x2 %0,%1,%2,%3;" : "=r"(r) : "r"(a), "r"(b), "r"(c)); return r; }
__device__ __forceinline__ uint32_t addbf(uint32_t a, uint32_t b) { uint32_t r; asm("add.rn.bf16x2 %0,%1,%2;" : "=r"(r) : "r"(a), "r"(b)); return r; }
__device__ __forceinline__ void pv_mem(const uint32_t (&p)[4], uint32_t pm, const uint4 (&v)[4], const uint4 (&vn)[2], uint32_t (&O)[4]) {
  float o[4][4] = {{0, 0, 0, 0}, {0, 0, 0, 0}, {0, 0, 0, 0}, {0, 0, 0, 0}};
  mma16(o[0], v[0].x, v[0].y, v[0].z, v[0].w, p[0], p[1]);
  mma16(o[1], v[2].x, v[2].y, v[2].z, v[2].w, p[0], p[1]);
  mma16(o[2], v[1].x, v[1].y, v[1].z, v[1].w, p[2], p[3]);
  mma16(o[3], v[3].x, v[3].y, v[3].z, v[3].w, p[2], p[3]);
  mma16(o[0], vn[0].x, vn[0].y, vn[0].z, vn[0].w, pm, pm);
  mma16(o[1], vn[1].x, vn[1].y, vn[1].z, vn[1].w, pm, pm);
  O[0] = pk(o[0][0] + o[2][0], o[0][1] + o[2][1]); O[1] = pk(o[0][2] + o[2][2], o[0][3] + o[2][3]);
  O[2] = pk(o[1][0] + o[3][0], o[1][1] + o[3][1]); O[3] = pk(o[1][2] + o[3][2], o[1][3] + o[3][3]);
}
__device__ __forceinline__ void pv_tok(const uint32_t (&p)[4], uint32_t pm, const uint4 (&v)[4], const uint32_t (&vm)[4], uint32_t (&O)[4]) {
  float o[2][4] = {{0, 0, 0, 0}, {0, 0, 0, 0}}, sum[4] = {0, 0, 0, 0};
  const uint32_t one = 0x3f803f80u;
  mma16(sum, one, one, one, one, p[0], p[1]);
  mma16(o[0], v[0].x, v[0].y, v[0].z, v[0].w, p[0], p[1]);
  mma16(o[1], v[2].x, v[2].y, v[2].z, v[2].w, p[0], p[1]);
  mma16(sum, one, one, one, one, p[2], p[3]);
  mma16(o[0], v[1].x, v[1].y, v[1].z, v[1].w, p[2], p[3]);
  mma16(o[1], v[3].x, v[3].y, v[3].z, v[3].w, p[2], p[3]);
  mma8(sum, one, one, pm);
  mma8(o[0], vm[0], vm[1], pm);
  mma8(o[1], vm[2], vm[3], pm);
  float i0, i1;
  asm("rcp.approx.ftz.f32 %0,%1;" : "=f"(i0) : "f"(sum[0]));
  asm("rcp.approx.ftz.f32 %0,%1;" : "=f"(i1) : "f"(sum[1]));
  O[0] = pk(o[0][0] * i0, o[0][1] * i1); O[1] = pk(o[0][2] * i0, o[0][3] * i1);
  O[2] = pk(o[1][0] * i0, o[1][1] * i1); O[3] = pk(o[1][2] * i0, o[1][3] * i1);
}
__device__ __forceinline__ uint32_t sum4bf(uint32_t a, uint32_t b, uint32_t c, uint32_t d) { return addbf(addbf(a, b), addbf(c, d)); }
template <int OFF>
__device__ __forceinline__ void sta1(uint32_t a, uint32_t v, uint32_t mb) {
  asm volatile("st.async.shared::cluster.mbarrier::complete_tx::bytes.b32 [%0+%3],%1,[%2];" ::"r"(a), "r"(v), "r"(mb), "n"(OFF) : "memory");
}

__device__ __forceinline__ void wait_time(uint32_t t) { while ((int)(gtime() - t) < 0) __nanosleep(64); }
__device__ __noinline__ void rec_prefetch(const char* wmod, const char* w1, const char* x, const char* wo) {
  const int hb = blockIdx.x - 128;
  const uint32_t t0 = gtime();
  uint32_t t = t0 + PF0;
#pragma unroll 1
  for (int job = 0; job < (PFT ? 5 : 3); job++) {
    const char* p = job == 0 ? x + (6 + hb) * 65536 : job == 1 ? wmod + hb * 12288 + 4096 : job == 2 ? w1 + hb * 7168 : job == 3 ? x + hb * 8192 : wo + (1020 + hb) * 8192;
    const int n = job == 0 ? 120 - (hb & 2) * 4 : job == 3 ? 128 : 256, d = job == 0 ? 8192 : job == 1 ? 49152 : job == 2 ? 28672 : job == 3 ? 32768 : -32768;
    if (job == 3) t = t0 + PFT;
    PT(8 + job);
#pragma unroll 1
    for (int i = 0; i < n; i++) {
      wait_time(t);
      asm volatile("cp.async.bulk.prefetch.L2.global [%0], %1;" ::"l"(p), "r"(job == 2 ? 7168 : 8192) : "memory");
      p += !job && (i & 7) == 7 ? 204800 : d;
      t += job < 3 ? PFD : PFS;
      if (job && (i & 31) == 31 && ldg_rlx1(&g_fin)) return;
    }
  }
  PT(13);
}
__device__ __noinline__ void rec_helper(uint32_t sb, const bf16* cvec, const bf16* wmod, const char* w1, const bf16* b1, uint32_t t0) {
  const int tid = threadIdx.x, hb = blockIdx.x - 128;
  PT(1);
  for (int i = tid; i < 1024; i += 256) sts1(sb + i * 8, U_(rbf(silu(__bfloat162float(cvec[i])))));
  for (int i = tid; i < 2048; i += 256) g_stat[hb * 2048 + i] = make_uint4(~0u, ~0u, ~0u, ~0u);
  for (int i = tid; i < 512; i += 256) g_cnt[hb * 512 + i] = 0;
#pragma unroll 1
  for (int job = 0; job < 2; job++) {
    wait_time(t0 + PF0 + (job ? 600 : 350) * PFD);
    BAR_SYNC(rec::B_F, 256);
    PT(2 + job * 5);
    const int n8 = job ? 112 : 128, rg = tid >= n8, cg = tid - rg * n8, pitch = job ? 448 : 768;
    const uint4* p = (const uint4*)(job ? w1 + hb * 1792 : (const char*)(wmod + 2048 + hb * 1024)) + rg * pitch + min(cg, n8 - 1);
    float a1[8] = {0, 0, 0, 0, 0, 0, 0, 0}, a2[8] = {0, 0, 0, 0, 0, 0, 0, 0};
#pragma unroll 1
    for (int r0 = rg; r0 < 1024; r0 += 32) {
      uint4 v[16];
#pragma unroll
      for (int i = 0; i < 16; i++) { v[i] = ldg_rlx4(p); p += 2 * pitch; }
#pragma unroll
      for (int i = 0; i < 16; i++) {
        const float2 f = lds2f(sb + (r0 + 2 * i) * 8);
        const float w[8] = {blo(v[i].x), bhi(v[i].x), blo(v[i].y), bhi(v[i].y), blo(v[i].z), bhi(v[i].z), blo(v[i].w), bhi(v[i].w)};
#pragma unroll
        for (int e = 0; e < 8; e++) { a1[e] += f.x * w[e]; a2[e] += f.y * w[e]; }
      }
    }
    const uint32_t rd = sb + 8192;
    if (cg < n8) {
#pragma unroll
      for (int e = 0; e < 8; e++) sts2(rd + rg * 8192 + (cg * 8 + e) * 8, U_(a1[e]), U_(a2[e]));
    }
    BAR_SYNC(rec::B_F, 256);
    if (job == 0) {
      for (int i = tid; i < 1024; i += 256) g_mod[2048 + hb * 1024 + i] = rbf(F_(lds1(rd + i * 8)) + F_(lds1(rd + 8192 + i * 8)));
      BAR_SYNC(rec::B_F, 256);
      PT(6);
      if (tid == 0) { red_rel(&g_mcnt); wait_cnt(&g_mcnt, 4); }
      BAR_SYNC(rec::B_F, 256);
      for (int i = tid; i < 1024; i += 256) sts2(sb + i * 8, U_(rbf(1.f + __ldcg(g_mod + 4096 + i))), U_(__ldcg(g_mod + 3072 + i)));
    } else {
      for (int i = tid; i < 448; i += 256) {
        const int gn = hb * 896 + i * 2;
        const uint32_t bb = *(const uint32_t*)(b1 + gn);
        const float4 u = lds4f(rd + i * 16), w = lds4f(rd + 8192 + i * 16);
        ((uint2*)g_cc)[(gn >> 4) * 8 + ((gn >> 1) & 3) * 2 + ((gn >> 3) & 1)] = make_uint2(pk(u.x + w.x, u.z + w.z), pk(0.5f * (u.y + w.y + blo(bb)), 0.5f * (u.w + w.w + bhi(bb))));
      }
      PT(4);
    }
  }
}

__global__ void __cluster_dims__(2, 1, 1) __launch_bounds__(512, 1)
k_rec(const __grid_constant__ RecMaps mp, const bf16* __restrict__ mem0, const bf16* __restrict__ x, const bf16* __restrict__ cvec,
      const bf16* __restrict__ wmod, const char* __restrict__ w1, const bf16* __restrict__ b1, const char* __restrict__ wo, char* xc, int dF, int dA, int dS, int dM, int dG, int dP, int dX, int dD, int dZ, int dQ, int dV, int dX2) {
  using namespace rec;
  extern __shared__ __align__(1024) char smem[];
  const uint32_t sb = (uint32_t)__cvta_generic_to_shared(smem);
  if ((sb & 0x3FFFF) != 1024) __trap();
  PH(0); RS(0); if (threadIdx.x == 0) PT(0);
  if (threadIdx.x == 0) {
    int b = blockIdx.x;
    if (b >= 8 && b < 128) {
      const int t = (b >> 1) - 4, u = t - 32;
      b = 2 * (t < 32 ? 4 + (t & 16) + (t & 7) * 2 + ((t >> 3) & 1) : 36 + (u / 14) * 14 + (u % 7) * 2 + ((u / 7) & 1)) + (b & 1);
    }
    sts1(sb + rec::PACE + 24, b);
    const int c = blockIdx.x >> 1, l = c < 36 ? (c - 4) & 7 : (c - 36) % 7, m = c < 4 ? c : c < 36 ? (c - 4) >> 3 : (c - 36) / 7;
    const int g = c < 4 ? 15 : (l >> 1) * 4 + (l & 1) + (c < 36 ? 0 : 2);
    unsigned sm;
    asm("mov.u32 %0,%%smid;" : "=r"(sm));
    if (c < 64) g_slot[sm & 255] = 1 + FMAP;
  }
#define ROLE_REFRESH { asm volatile("mov.u32 %0,%%tid.x;" : "=r"(tid)); wid = __shfl_sync(~0u, tid >> 5, 0); b = __shfl_sync(~0u, lds1(sb + PACE + 24), 0); }
#define ROLE_VARS int tid; asm volatile("mov.u32 %0,%%tid.x;" : "=r"(tid)); \
    int wid = __shfl_sync(~0u, tid >> 5, 0), b = __shfl_sync(~0u, lds1(sb + PACE + 24), 0);
#define wg (wid >> 2)
#define iw (wid & 3)
#define h (b >> 2)
#define j (b & 3)
#define a (b & 1)
#define bb ((b >> 1) & 1)
  const uint32_t wbar = sb + BARS + 48, obar = wbar + 8;
  if (threadIdx.x == 256) {
    for (int i = 0; i < 18; i++) if (i != 12) mbar_init(sb + BARS + i * 8, i == 3 || i == 8 || i == 9 || i == 10 ? 2 : 1);
    for (int i = 0; i < 3; i++) mbar_init(sb + PACE + i * 8, 1);
    asm volatile("fence.mbarrier_init.release.cluster;" ::: "memory");
    FENCE_ASYNC_SMEM();
    mbar_expect(sb + BARS, 2048);
    mbar_expect(sb + BARS + 16, 4096);
    mbar_expect(sb + BARS + 32, 4096);
    mbar_expect(sb + BARS + 40, 4096);
  }
  __syncthreads();
  asm volatile("barrier.cluster.arrive.relaxed.aligned;" ::: "memory");
#define lane ((int)(l16 >> 4))
#define l16 (L16 & 0x1f0)
#define PIN(x) __shfl_xor_sync(~0u, (uint32_t)(x), 0)
#define X_LOAD(n, w, u) \
        asm volatile("{.reg .pred p; elect.sync _|p, 0xffffffff; @p mbarrier.arrive.expect_tx.shared.b64 _,[%2],8192;\n" \
                     "@p cp.async.bulk.shared::cluster.global.mbarrier::complete_tx::bytes [%0],[%1],8192,[%2];}" ::"r"(sb + XB + (w) * 16384 + (u) * 8192), \
                     "l"(g_h + (n) * 4096 + a * 2048 + (w) * 1024 + (u) * 512), "r"(sb + BARS + 64 + (w) * 8) : "memory")
#define lpub ((L16 & 0x30) * 64 + ((L16 >> 3) & 0x38))
#define lrow ((L16 & 0x70) + (((L16 >> 3) ^ L16) & 0x70 & ~((L16 >> 3) & 0x40) ? L16 & 0x180 : 512))

  const int role = __shfl_sync(~0u, threadIdx.x >> 7, 0);
  if (role < 2) {
    asm volatile("setmaxnreg.inc.sync.aligned.u32 %0;" ::"n"(RF_));
    ROLE_VARS
    uint32_t L16 = __shfl_sync(~0u, sb + (tid & 31) * 16, tid & 31);
    uint32_t wQ[16][4], wK[16][4], wV[NVR][4];
    uint32_t frag = sb + ((lane & 7) + (lane >> 4) * 8) * 128 + (((iw * 2 + ((lane >> 3) & 1)) ^ (lane & 7)) << 4);
#define QSW (a ? 0 : 64)
    {
      const bool spare = b >= 128;
      const uint32_t t0 = gtime();
      uint4 xr[16];
      int seg = spare ? b - 126 : wg;
      const int half = spare ? wg : a;
      auto x_fetch = [&]() {
        const uint4* px = (const uint4*)x + (seg * 32 + iw * 8 + (lane >> 2)) * 128 + half * 64 + (lane & 3);
#pragma unroll
        for (int i = 0; i < 16; i++) xr[i] = __ldg(px + i * 4);
      };
      if (!spare) {
        uint4 wm[8];
        const uint4* pw = (const uint4*)(wmod + (size_t)((b >> 5) * 256 + (tid >> 3)) * 6144 + (b & 31) * 64) + (tid & 7);
        const float cs = __bfloat162float(cvec[(b >> 5) * 256 + tid]);
#pragma unroll
        for (int i = 0; i < 8; i++) wm[i] = __ldcs(pw + (size_t)i * 32 * 768);
        float* sc = (float*)(smem + PRE);
        sc[tid] = rbf(silu(cs));
        PT(1);
        BAR_SYNC(B_F, 256);
        float acc[8] = {0, 0, 0, 0, 0, 0, 0, 0};
#pragma unroll
        for (int i = 0; i < 8; i++) {
          const float f = sc[i * 32 + (tid >> 3)];
          acc[0] += f * blo(wm[i].x); acc[1] += f * bhi(wm[i].x); acc[2] += f * blo(wm[i].y); acc[3] += f * bhi(wm[i].y);
          acc[4] += f * blo(wm[i].z); acc[5] += f * bhi(wm[i].z); acc[6] += f * blo(wm[i].w); acc[7] += f * bhi(wm[i].w);
        }
#pragma unroll
        for (int i = 0; i < 8; i++) { acc[i] += __shfl_xor_sync(~0u, acc[i], 8); acc[i] += __shfl_xor_sync(~0u, acc[i], 16); }
        float* red = sc + 1024;
        if ((tid & 31) < 8) {
#pragma unroll
          for (int i = 0; i < 8; i++) red[(tid >> 5) * 64 + (tid & 7) * 8 + i] = acc[i];
        }
        BAR_SYNC(B_F, 256);
        PT(2);
        if (tid < 64) {
          float t = 0;
#pragma unroll
          for (int i = 0; i < 8; i++) t += red[i * 64 + tid];
          asm volatile("st.relaxed.gpu.global.u32 [%0],%1;" ::"l"((unsigned*)g_modp + (b >> 5) * 2048 + (b & 31) * 64 + tid), "r"(U_(t) | 1u) : "memory");
        }
      } else {
        asm volatile("griddepcontrol.launch_dependents;");
      }
      x_fetch();
      const uint32_t md = sb + PRE + 6144, rx = mapa(sb, a ^ !spare);
      asm volatile("barrier.cluster.wait.aligned;" ::: "memory");
      if (!spare) {
        mbar_wait(sb + BARS + 88, 0);
#pragma unroll
        for (int i = 0; i < 16; i++) ldsm4t(wQ[i], (frag ^ QSW) + WO + wg * 32768 + i * 2048);
      }
      PT(4);
#pragma unroll 1
      for (int it = 0;; it++) {
        if (tid == 0) mbar_expect(sb + BARS + 104, 512);
        float c[4][4] = {{0, 0, 0, 0}, {0, 0, 0, 0}, {0, 0, 0, 0}, {0, 0, 0, 0}};
#pragma unroll
        for (int i = 0; i < 16; i++) {
          mma16(c[(i & 1) * 2], xr[i].x, 0x3f803f80u, xr[i].y, 0x3f803f80u, xr[i].x, xr[i].y);
          mma16(c[(i & 1) * 2 + 1], xr[i].z, 0x3f803f80u, xr[i].w, 0x3f803f80u, xr[i].z, xr[i].w);
        }
#pragma unroll
        for (int e = 0; e < 4; e++) c[0][e] = (c[0][e] + c[1][e]) + (c[2][e] + c[3][e]);
        const int src = (lane & 28) + (lane >> 3);
        const float sq = __shfl_sync(~0u, (lane & 4) ? c[0][1] : c[0][0], src), sm = __shfl_sync(~0u, (lane & 4) ? c[0][3] : c[0][2], src);
        if ((lane & 3) < 2) sta1<0>(rx + PRE + 10240 + (wid ^ (spare * 4)) * 64 + (lane >> 2) * 8 + (lane & 1) * 4, U_((lane & 1) ? sm : sq), rx + BARS + 104);
        mbar_wait(sb + BARS + 104, it & 1);
        const float2 ot = lds2f(sb + PRE + 10240 + wid * 64 + (lane >> 2) * 8);
        const float mean = (sm + ot.y) * (1.f / 1024);
        const float rs = rsqrtf(fmaxf((sq + ot.x) * (1.f / 1024) - mean * mean, 0.f) + 1e-5f), nm = -mean * rs;
        const uint32_t rh = pk(rs, rs), rl = pk(rs - blo(rh), rs - blo(rh)), n2 = pk(nm, nm);
#define NRM(v) v = fmabf(v, rh, fmabf(v, rl, n2))
#pragma unroll
        for (int i = 0; i < 16; i++) { NRM(xr[i].x); NRM(xr[i].y); NRM(xr[i].z); NRM(xr[i].w); }
        if (!it) {
          PT(3);
#pragma unroll 1
          for (int i = 0; i < 2; i++) {
            uint4 p[4];
            for (int n = 0;; n++) {
#pragma unroll
              for (int e = 0; e < 4; e++) p[e] = ldg_rlx4(g_modp + e * 512 + i * 256 + tid);
              uint32_t ok = 1;
#pragma unroll
              for (int e = 0; e < 4; e++) ok &= p[e].x & p[e].y & p[e].z & p[e].w;
              if (__all_sync(~0u, ok) || n > SPIN_LIMIT / 16) break;
              __nanosleep(100);
            }
#define MSUM(e) (i + rbf((F_(p[0].e) + F_(p[1].e)) + (F_(p[2].e) + F_(p[3].e))))
            sts2(md + i * 2048 + tid * 8, pk(MSUM(x), MSUM(y)), pk(MSUM(z), MSUM(w)));
          }
          BAR_SYNC(B_F, 256);
          PT(5);
        }
        const int e0 = (iw * 8 + (lane >> 2)) * 8 + ((lane & 3) ^ (lane >> 2));
        uint4* dst = g_h + seg * 4096 + half * 2048;
#pragma unroll
        for (int i = 0; i < 16; i++) {
          const uint32_t ma = md + half * 1024 + (lane & 3) * 16 + i * 64;
          const uint4 sv = lds4(ma), cv = lds4(ma + 2048);
          xr[i] = make_uint4(fmabf(xr[i].x, cv.x, sv.x), fmabf(xr[i].y, cv.y, sv.y), fmabf(xr[i].z, cv.z, sv.z), fmabf(xr[i].w, cv.w, sv.w));
        }
        if (!spare) {
#pragma unroll
          for (int i = 0; i < 16; i++) sts4(sb + WO + wg * 32768 + (e0 ^ ((i & 1) * 4)) * 16 + (i >> 1) * 4096, xr[i].x, xr[i].y, xr[i].z, xr[i].w);
          break;
        }
#pragma unroll
        for (int i = 0; i < 16; i++) dst[(e0 ^ ((i & 1) * 4)) + (i >> 1) * 256] = xr[i];
        seg += 4;
        if (seg < 64) x_fetch();
        FENCE_ASYNC();
        BAR_SYNC(B_F, 256);
        if (tid == 0) red_rlx(g_hf + b - 128);
        if (seg >= 64) break;
      }
      if (spare) { rec_helper(sb, cvec, wmod, w1, b1, t0); return; }
      PH(1); PH(2); PT(6);
    }
    ROLE_REFRESH
#define ownv ((iw >> 1) == a)
#define owner (iw >= 2)
#define oi (wid & 1)
    {
      const uint32_t rsb = mapa(sb, owner ? a : a ^ 1);
      const uint32_t pp = rsb + PK + (owner ? 0 : 12288) + (oi * 2048 + wg * 1024) + l16;
      const uint32_t mb = sb + MEM + wg * 5120;
      sts4(L16 + TF + wid * 512, mb + lrow, owner ? L16 + (lane >> 4) * (RK - RQ - 256) + RQ + oi * 1024 + wg * 256 : rsb + RQ + oi * 1024 + 512 + wg * 256 + (l16 >> 2),
           L16 + OB, frag + wg * NVS * 2048);
      sts4(L16 + TF + 4096 + wid * 512, sb + WO + (wid >> 1) * 16384 + ((lane & 7) + (lane >> 4) * 8) * 128 + ((((wid & 1) * 4 + ((lane >> 3) & 1)) ^ (lane & 7)) << 4),
           sb + ARO + wid * 640 + lrow, pp, LO(xc) + h * 262144 + (bb * 2 + (iw >> 1)) * XC + X_VM(0) + oi * 2048 + a * 256 + (l16 >> 1));
    }
    uint32_t tp = L16 + TF + wid * 512;
    auto park_ptr = [&]() { return lds1(tp + 4096 + 8); };
    auto park_w = [&](const uint32_t* w, int m, uint32_t d) {
      if (m == 2) d += (sb & 0x1000000) ? 0 : owner ? 0x1003000 : -0x1003000;
      if (m == 2 ? ownv : owner) {
        sts4(d + m * 4096, w[0], w[1], w[2], w[3]); sts4(d + m * 4096 + 512, w[4], w[5], w[6], w[7]);
      } else {
        const uint32_t pb = (d & 0xff000000u) | (1024 + BARS + (m ? 24 + m * 8 : 16));
        sta4(d + m * 4096, w, pb); sta4(d + m * 4096 + 512, w + 4, pb);
      }
    };
    auto park = [&](const float* f, int m, int n, uint32_t d) {
      uint32_t w[8];
#pragma unroll
      for (int i = 0; i < 8; i++) w[i] = pk(f[2 * i], f[2 * i + 1]);
      park_w(w, m, d);
    };
#define D64(lo) (0x4000004000000000ull | (uint32_t)(lo))
#define XD(i) D64(x | (((i) >> 2) * 256 + ((i) & 3) * 2))
    auto xdesc = [&](uint32_t xb) { return ((uint32_t)__shfl_sync(~0u, 1024 + xb + wg * 16384, 0) >> 4) | 0x10000u; };
    auto rs_issue = [&](float* acc, const uint32_t (&w)[16][4], uint32_t xb, bool fence) {
      const uint32_t x = xdesc(xb);
      if (fence) WG_FENCE();
      wgmma_rs_n32_z(acc, w[0], XD(0));
#pragma unroll
      for (int i = 1; i < 16; i++) wgmma_rs_n32(acc, w[i], XD(i), 1);
      WG_COMMIT();
    };
    auto v_issue = [&](float* acc, uint32_t xb, bool fence) {
      const uint32_t dv = ((uint32_t)__shfl_sync(~0u, 1024 + WVS + wg * NVS * 2048, 0) >> 4) | 0x10000u, x = xdesc(xb);
      if (fence) WG_FENCE();
      wgmma_rs_n32_z(acc, wV[0], XD(0));
#pragma unroll
      for (int i = 1; i < VRF; i++) wgmma_rs_n32(acc, wV[i], XD(i), 1);
#pragma unroll
      for (int i = NVR; i < 16; i++) wgmma_ssT_n32(acc, D64(dv + (i - NVR) * 128), XD(i), 1);
#pragma unroll
      for (int i = VRF; i < NVR; i++) wgmma_rs_n32(acc, wV[i], XD(i), 1);
      WG_COMMIT();
    };
    uint32_t mA, vP[2][4];
#define V_AHEAD mA = lds1(tp); frag = lds1(tp + 12); ldsm4t(vP[0], frag + WVS + (15 - NVR) * 2048); ldsm4t(vP[1], frag + WVS + (14 - NVR) * 2048);
    auto vk_pass = [&](int n, uint32_t d) {
      float acc[16], acc2[16];
      v_issue(acc, XB, true);
      rs_issue(acc2, wK, XB, false);
      if (n < 64) mbar_wait(sb + BARS + 80, (n - 1) & 1);
      WG_WAIT(1);
      if (n < 64) {
        park(acc, 2, n, d);
        BAR_ARRIVE(B_K, 320);
      }
      V_AHEAD
      WG_WAIT(0);
      if (n < 64) park(acc2, 1, n, d + (VPC ? (vP[1][0] ^ mA) & dZ : 0));
    };
    uint32_t q0[8], q1[8];
    {
      float acc[16], acc2[16];
      FENCE_ASYNC_SMEM();
      BAR_SYNC(B_F, 256);
      rs_issue(acc, wQ, WO, true);
      rs_issue(acc2, wQ, WO + 32768, false);
      WG_WAIT(0);
#pragma unroll
      for (int i = 0; i < 8; i++) { q0[i] = pk(acc[2 * i], acc[2 * i + 1]); q1[i] = pk(acc2[2 * i], acc2[2 * i + 1]); }
    }
    mbar_wait(wbar, 0);
    PT(7);
#pragma unroll
    for (int i = 0; i < 16; i++) ldsm4t(wK[i], (frag ^ QSW) + XB + wg * 32768 + i * 2048);
#pragma unroll
    for (int i = 0; i < NVR; i++) ldsm4t(wV[i], frag + MEM + (wg * NVR + i) * 2048);
    FENCE_ASYNC_SMEM();
    PH(3); PT(8);
    CLUSTER_SYNC();
    PT(9);
    frag += wg * NVS * 2048;
    park_w(q0, 0, park_ptr());
    uint32_t k1[8];
    {
      float acc[16], acc2[16];
      asm volatile("" : "+r"(wid));
      rs_issue(acc, wK, WO, true);
      rs_issue(acc2, wK, WO + 32768, false);
      WG_WAIT(0);
      park(acc, 1, 0, park_ptr());
#pragma unroll
      for (int i = 0; i < 8; i++) k1[i] = pk(acc2[2 * i], acc2[2 * i + 1]);
    }
    mbar_wait(sb + BARS + 120, 0);
    PT(10);
#pragma unroll 1
    for (int n = 0; n < 2; n++) {
      float acc[16];
      asm volatile("" : "+r"(wid));
      v_issue(acc, n * XB, true);
      if (n) {
        BAR_SYNC(B_C, 320);
        PT(12);
        mbar_wait(sb + BARS + 24, 0);
        park_w(q1, 0, park_ptr());
        mbar_wait(sb + BARS + 80, 0);
        park_w(k1, 1, park_ptr());
      }
      WG_WAIT(0);
      park(acc, 2, n, park_ptr());
      if (n) break;
      PT(11);
      BAR_SYNC(B_C, 448);
      if (tid == 0) {
        mbar_expect(obar, 65536);
#pragma unroll 1
        for (int i = 0; i < 4; i++) tma2d(sb + WO + i * 16384, &mp.wo, j * 256 + i * 64, h * 128, obar);
      }
    }
    V_AHEAD
    CONSUME(vP[1][0]);
    static_assert(WO == 0, "x");
    {
      BAR_ARRIVE(B_P, 384); BAR_ARRIVE(B_X, 320); BAR_ARRIVE(B_Q, 288);
    }
    PT(13);
    PH(4); RS(1); PT(14);
    ROLE_REFRESH
    for (int s = 0; s < 64; s++) {
      asm volatile("" : "+r"(tp), "+r"(wid));
      asm volatile("mov.u32 %0,%%cluster_ctarank;" : "=r"(b));
      uint32_t vS[NVS][4], bf[8][4];
      static_assert(NVR == 5, "schedule");
#define VLD(k) ldsm4t(vS[(k) - NVR], frag + WVS + ((k) - NVR) * 2048)
#define BLD(t) ldsm4t(bf[t], mA + (t) * 640)
#define VMMA(c, w, i) mma16(c, (w)[0], (w)[1], (w)[2], (w)[3], bf[(i) >> 1][((i) & 1) * 2], bf[(i) >> 1][((i) & 1) * 2 + 1])
#define VS_(c, k) VMMA(c, vS[(k) - NVR], k)
#define QK(i) VMMA(cQ, wQ[i], i); VMMA(cK, wK[i], i)
#define PREV VLD(13); VLD(12); if (NF > 2) VLD(11);
      if (s > 0) BAR_SYNC(B_R, 320);
      float cV[4] = {0, 0, 0, 0}, cW[4] = {0, 0, 0, 0};
      {
        float cQ[4] = {0, 0, 0, 0}, cK[4] = {0, 0, 0, 0};
        BLD(7); BLD(6); BLD(5); BLD(4); if (NB0 > 4) BLD(3);
        SCHED_FENCE(47);
        QK(15); VMMA(cV, vP[0], 15);
        QK(14); VMMA(cV, vP[1], 14);
        QK(13); QK(12);
        SCHED_FENCE(51);
        if (NB0 < 5) BLD(3);
        BLD(2); BLD(1); BLD(0);
        const uint32_t rm = lds1(tp + 4);
        QK(11); QK(10); QK(9); QK(8); QK(7);
        if (PV0 == 6) { SCHED_FENCE(48); PREV }
        QK(6); QK(5);
        if (PV0 == 4) { QK(4); SCHED_FENCE(48); PREV } else { QK(4); }
        QK(3); QK(2); QK(1); QK(0);
        const uint32_t w0 = pk(cQ[0] * SCS, cQ[1] * SCS), w1 = pk(cQ[2] * SCS, cQ[3] * SCS), w2 = pk(cK[0], cK[1]), w3 = pk(cK[2], cK[3]);
        if (owner) {
          stsm4(rm, w0, w1, w2, w3);
          BAR_ARRIVE(B_E, 256);
        } else {
          const uint32_t mm = (rm & 0xff000000u) | (1024 + BARS);
          sta1<0>(rm, w0, mm); sta1<128>(rm, w1, mm);
          sta1<RK - RQ>(rm, w2, mm); sta1<RK - RQ + 128>(rm, w3, mm);
        }
        if (wid == 2) TS(0);
      }
      uint4 t1;
      uint32_t oA, wo[16][4];
      {
        DLY(10)
        if (NF < 3) VLD(11);
        VLD(10);
        VS_(cW, 13); VLD(9); VS_(cV, 12); VLD(8); VLD(7); VMMA(cW, wV[0], 0); VMMA(cV, wV[1], 1); VLD(6);
        VMMA(cW, wV[2], 2); VMMA(cV, wV[3], 3); VLD(5); VMMA(cW, wV[4], 4); VS_(cV, 11);
        VS_(cW, 10); VS_(cV, 9); VS_(cW, 8); VS_(cV, 7); VS_(cW, 6); VS_(cV, 5);
#pragma unroll
        for (int e = 0; e < 4; e++) cV[e] += cW[e];
        const uint32_t ex = tp + (RX - TF) - wg * 2048;
        t1 = lds4(tp + 4096 + (T1L ? vS[3][0] & dZ : 0));
        oA = lds1(tp + 8 + (s & dZ));
        if (wg) {
          sts4(ex, U_(cV[0]), U_(cV[1]), U_(cV[2]), U_(cV[3]));
          BAR_ARRIVE(B_T2, 256);
        }
        if (!wg) {
          BAR_SYNC(B_T2, 256);
          DLY(3)
          const float4 u = lds4f(ex);
          stg_b64(mkp(t1.w ^ ((s & 1) * X_RING), HI(xc)), (pk(cV[0] + u.x, cV[1] + u.y) & ~1u) | (((s >> 1) + 1) & 1), pk(cV[2] + u.z, cV[3] + u.w));
        }
      }
      if (s == 63) break;
      if (s == 0) mbar_wait(obar, 0);
      {
        const uint32_t woA = t1.x, woB = woA ^ 32;
#pragma unroll
        for (int i = 0; i < NW0; i++) ldsm4t(wo[i], ((i & 1) ? woB : woA) + (i >= WCH ? wo[(i - WCH + NWP) % NWP][0] & dZ : 0) + (i >> 1) * 2048);
        DLY(2)
        BAR_SYNC(B_S, 416);
        float inv0, inv1;
        uint32_t p[4], pm;
        const uint32_t pa = oA + (SC - OB), one = 0x3f803f80u;
#define P_LOAD ldsm4t(p, pa); asm volatile("ldmatrix.sync.aligned.m8n8.x1.trans.shared.b16 {%0},[%1];" : "=r"(pm) : "r"(pa + 512) : "memory");
        if (s < 62) {
          float acc[16];
          rs_issue(acc, wQ, XB, true);
          mbar_wait(sb + BARS + 24, (s + 1) & 1);
          WG_WAIT(0);
          uint32_t qw[8];
#pragma unroll
          for (int i = 0; i < 8; i++) qw[i] = pk(acc[2 * i], acc[2 * i + 1]);
#pragma unroll
          for (int i = NW0; i < NW1; i++) ldsm4t(wo[i], ((i & 1) ? woB : woA) + (i >> 1) * 2048);
          BAR_SYNC(B_V, 512);
          P_LOAD
          park_w(qw, 0, t1.z);
        } else {
#pragma unroll
          for (int i = NW0; i < NW1; i++) ldsm4t(wo[i], ((i & 1) ? woB : woA) + (i >> 1) * 2048);
          BAR_SYNC(B_V, 512);
          P_LOAD
        }
#pragma unroll
        for (int i = NW1; i < NWP; i++) ldsm4t(wo[i], ((i & 1) ? woB : woA) + (i >> 1) * 2048);
        {
          float sum[4] = {0, 0, 0, 0}, su2[4] = {0, 0, 0, 0};
          mma16(sum, one, one, one, one, p[0], p[1]);
          mma16(su2, one, one, one, one, p[2], p[3]);
          mma8(sum, one, one, pm);
          inv0 = sum[0] + su2[0]; inv1 = sum[1] + su2[1];
          SCHED_FENCE(57);
        }
        DLY(7)
        BAR_SYNC(B_O, 416);
        float c[2][4] = {{0, 0, 0, 0}, {0, 0, 0, 0}};
        uint32_t o[4][4];
#pragma unroll
        for (int i = 0; i < NOP_; i++) ldsm4t(o[i], oA + i * 512);
        SCHED_FENCE(46);
        asm("rcp.approx.ftz.f32 %0,%0;" : "+f"(inv0));
        asm("rcp.approx.ftz.f32 %0,%0;" : "+f"(inv1));
#pragma unroll
        for (int i = 0; i < 16; i++) {
          mma16(c[i & 1], wo[i][0], wo[i][1], wo[i][2], wo[i][3], o[i >> 2][i & 2], o[i >> 2][(i & 2) + 1]);
          if (i == 1 && NOP_ < 3) ldsm4t(o[2], oA + 1024);
          if (i == 3 && NOP_ < 4) ldsm4t(o[3], oA + 1536);
          if (i + NWP < 16) ldsm4t(wo[(i + NWP) & 15], (((i + NWP) & 1) ? woB : woA) + ((i + NWP) >> 1) * 2048);
        }
        stsm4(t1.y, pk(c[0][0] * inv0, c[0][1] * inv1), pk(c[0][2] * inv0, c[0][3] * inv1), pk(c[1][0] * inv0, c[1][1] * inv1), pk(c[1][2] * inv0, c[1][3] * inv1));
      }
      const uint32_t d = park_ptr();
      BAR_SYNC(B_W, 384);
      DLY(1)
      vk_pass(s + 2, d);
      if (s < 62) { BAR_ARRIVE(B_P, 384); BAR_ARRIVE(B_X, 320); }
      TS(10);
    }
  } else if (role == 3) {
    asm volatile("setmaxnreg.dec.sync.aligned.u32 24;");
    if (blockIdx.x >= 128) return;
    ROLE_VARS
    const uint32_t L16 = sb + (tid & 31) * 16;
    asm volatile("barrier.cluster.wait.aligned;" ::: "memory");
    CLUSTER_SYNC();
    sts1(sb + PACE + 36, LO(xc) + h * 262144 + X_VM(0));
#define V_LOAD(n) asm volatile("{.reg .pred p; elect.sync _|p, 0xffffffff; @p mbarrier.arrive.expect_tx.shared.b64 _,[%3],8192;\n" \
        "@p cp.async.bulk.tensor.5d.shared::cluster.global.mbarrier::complete_tx::bytes [%0],[%1,{0,0,0,0,%2}],[%3];}" \
        ::"r"(sb + VX0), "l"(&mp.vx), "r"(h * 64 + (V_RING(n) >> 12)), "r"(sb + BARS + 8) : "memory")
    auto vm_stage = [&](int s) {
      const uint32_t tag = ((s >> 1) + 1) & 1;
      const char* xm = mkp(lds1(sb + PACE + 36) + (s & 1) * X_RING + iw * XC + (l16 >> 1), HI(xc));
      uint2 m[4];
      CONSUME(LO(xm));
      BAR_SYNC(B_S2, 256);
      DLY(4)
      int it = 0;
      while (true) {
#pragma unroll
        for (int i = 0; i < 4; i++) m[i] = ldg_b64(xm + (i >> 1) * 2048 + (i & 1) * 256);
        sts4(L16 + VN + iw * 512, m[0].x, m[0].y, m[1].x, m[1].y);
        sts4(L16 + VN + iw * 512 + 2048, m[2].x, m[2].y, m[3].x, m[3].y);
        if (!anybad(m[0].x, m[1].x, m[2].x, m[3].x, tag)) break;
        RP(2);
        if (++it > SPIN_LIMIT) __trap();
      }
      if (s < 63) BAR_ARRIVE(B_V, 512); else BAR_ARRIVE(B_V, 256);
    };
    if (iw == 0) {
      wait_cnt(&g_hcnt, 128);
#pragma unroll 1
      for (int s = 0; s < 63; s++) {
        if (s < 62) for (int it = 0; ldg_rlx1(g_hf + (s & 3)) <= (s >> 2); it++) if (it > SPIN_LIMIT) __trap();
        if (s) BAR_SYNC(B_R, 320); else BAR_SYNC(B_Q, 288);
        if (s < 62) { X_LOAD(s + 2, 0, 0); X_LOAD(s + 2, 1, 0); X_LOAD(s + 2, 0, 1); X_LOAD(s + 2, 1, 1); }
        if (s >= 7) {
          const uint32_t zo = b * 160 + l16;
          if (l16 < 160) CONSUME(exch_b128(xc + AR_OFF + AR_ROW(zo >> 7) * 1024 + (zo & 127) + ((s + 1) & 7) * 128, 0, 0, 0, 0).x);
          __syncwarp();
        }
        if (s < 62) { mbar_wait(sb + BARS + 64, s & 1); mbar_wait(sb + BARS + 72, s & 1); }
        BAR_ARRIVE(B_S, 416);
        vm_stage(s);
        BAR_ARRIVE(B_O, 416);
        BAR_SYNC(B_W, 384);
        DLY(8)
        FENCE_ASYNC_SMEM();
        asm volatile("{.reg .pred p; elect.sync _|p, 0xffffffff; @p cp.reduce.async.bulk.tensor.3d.global.shared::cta.add.bulk_group [%0,{%1,%4,%2}],[%3];}"
                     ::"l"(&mp.ari), "r"((s & 7) * 64), "r"(AR_R(j)), "r"(sb + ARO), "r"(AR_P(j)) : "memory");
        BULK_COMMIT();
        asm volatile("st.relaxed.gpu.global.u32 [%0],%1;" ::"l"(g_tm + (s & 1) * 128 + b), "r"(gtime()) : "memory");
        TS(3);
        BULK_WAIT_READ(0);
      }
      BAR_ARRIVE(B_R, 320);
    } else if (iw == 1) {
      const uint32_t pc = sb + MEM + (lane >> 2) * 640 + (lane & 3) * 144 + (lane & 12), pd = sb + MEM + (lane & 15) * 640 + 576 + (lane & 3) * 16 + (lane & 12);
      uint32_t T = 0, par = 0;
      int est = dA;
#pragma unroll 1
      for (int s = 0; s < 63; s++) {
        if (s) {
          const uint4 tm = ldg_rlx4((const char*)g_tm + ((s + 1) & 1) * 512 + l16);
          const int t0 = tm.x - T, t1 = tm.y - T, t2 = tm.z - T, t3 = tm.w - T;
          const int e = max(dF + (__reduce_add_sync(~0u, (t0 + t1) + (t2 + t3)) >> 7), dV + __reduce_max_sync(~0u, max(max(t0, t1), max(t2, t3))));
          if (s > 1) est += max(min(e >> 2, dP), -dP);
          T += (s == 1 || e > dM ? e : 0) + est - (s == 62 ? L62 : 0);
        }
        vm_stage(s);
        BAR_SYNC(B_W, 384);
        SCHED_FENCE(70);
        const uint32_t tW = gtime();
        if (s == 0) T = tW + 800;
        const uint32_t te = tW + min(max((int)(T - tW), dD), 2000);
        while ((int)(gtime() - te) < 0) {}
        TS(7);
        int it = 0;
        while (true) {
          ar_fetch(sb + MEM, &mp.ari, s & 7, a, sb + BARS + 112);
          mbar_wait(sb + BARS + 112, par);
          par ^= 1;
          const uint32_t n0 = lds1(pc), n1 = lds1(pc + 5120), n2 = lds1(pd);
          if (!__any_sync(~0u, (tagbad(n0, n1, 0x42004200) | (n2 ^ 0x42004200)) != 0)) break;
          RP(0);
          if (++it > SPIN_LIMIT) __trap();
        }
        BAR_ARRIVE(B_R, 320);
        TS(11);
      }
    } else {
      uint32_t src = L16 + PK + (iw & 1) * 2048;
#define qd (L16 + (lane >> 4) * 256 + QT + (iw & 1) * 1024)
#define vd (LO(xc) + h * 262144 + j * XC + (iw & 1) * 2048 + l16)
#define FINISH [&](int n, int m) { \
_Pragma("unroll") \
        for (int i = 1; i >= 0; i--) { \
          const uint32_t p = src + m * 4096 + i * 512; \
          uint4 u = lds4(p); \
          const uint4 w = lds4(p + 1024), y = lds4(p + 12288), z = lds4(p + 13312); \
          u = make_uint4(sum4bf(u.x, w.x, y.x, z.x), sum4bf(u.y, w.y, y.y, z.y), sum4bf(u.z, w.z, y.z, z.z), sum4bf(u.w, w.w, y.w, z.w)); \
          if (m == 2) stg_b128(mkp(vd ^ V_RING(n), HI(xc)) + i * 512, (u.x & ~1u) | V_TAG(n), u.y, u.z, u.w); \
          else stsm4(qd + (n & 1) * 4096 + m * 2048 + i * 256, u.x, u.z, u.y, u.w); \
          SCHED_FENCE(71 + m * 2 + i); \
        } \
      }
#pragma unroll 1
      for (int n = 0; n < 64; n++) {
        src = PIN(src);
        b = __shfl_sync(~0u, lds1(sb + PACE + 24), 0);
        const uint32_t L16 = src - PK - (iw & 1) * 2048;
        auto finish = FINISH;
        if (n < 2) { if (n) BAR_SYNC(B_X, 320); else BAR_SYNC(B_C, 448); }
        mbar_wait(sb + BARS + 16, n & 1);
        if (n > 1) { const uint32_t c = clk(); while (clk() - c < (uint32_t)dQ) {} }
        finish(n, 0);
        __syncwarp();
        if (lane == 0) mbar_arrive_cl(mapa(sb, a ^ 1) + BARS + 24);
        if (n > 1) BAR_SYNC(B_K, 320);
        mbar_wait(sb + BARS + 40, n & 1);
        finish(n, 2);
        if (n > 1) BAR_SYNC(B_X, 320);
        mbar_wait(sb + BARS + 32, n & 1);
        DLY(11)
        finish(n, 1);
        BAR_SYNC(B_T, 64);
        if (lane == 0) {
          if (iw == 2 && n < 63) { mbar_expect(sb + BARS + 16, 4096); mbar_expect(sb + BARS + 32, 4096); mbar_expect(sb + BARS + 40, 4096); }
          mbar_arrive_cl(mapa(sb, a ^ 1) + BARS + 80);
        }
        __syncwarp();
        if (n) {
          vm_stage(n - 1);
          BAR_SYNC(B_W, 384);
          DLY(15)
        } else {
          BAR_SYNC(B_C, 320);
        }
        if (iw == 2) V_LOAD(n);
      }
#undef qd
#undef vd
    }
    { ROLE_REFRESH }
    vm_stage(63);
  } else {
    asm volatile("setmaxnreg.dec.sync.aligned.u32 %0;" ::"n"(RA_));
    if (blockIdx.x >= 128) { if (threadIdx.x == 256) rec_prefetch((const char*)wmod, w1, (const char*)x, wo); return; }
    ROLE_VARS
    uint32_t L16 = __shfl_sync(~0u, sb + (tid & 31) * 16, tid & 31);
    asm volatile("barrier.cluster.wait.aligned; barrier.cluster.arrive.relaxed.aligned;" ::: "memory");
    const uint32_t ts = gtime();
    uint2 m0[8];
#pragma unroll
    for (int r = 0; r < 8; r++) m0[r] = *(const uint2*)(mem0 + r * 1024 + a * 512 + (tid - 256) * 4);
    if (wid == 9) {
#pragma unroll 1
      for (int i = b * 80 + (tid & 31); i < b * 80 + 80; i += 32) ((uint4*)(xc + AR_OFF))[AR_ROW(i >> 6) * 64 + (i & 63)] = make_uint4(0, 0, 0, 0);
      if (b == 0) g_fin = 0;
      FENCE_ASYNC();
      __syncwarp();
      if (tid == 288) red_rlx(&g_hcnt);
    }
    if (tid == 256) {
      const int col = h * 128 + bb * 64;
#pragma unroll 1
      for (int c = 0, w = 0; w < 12; c++) {
#pragma unroll 1
        for (; w <= c - (c < WC0 ? 2 : 3); w++) {
          mbar_wait(sb + PACE + (w % 3) * 8, (w / 3) & 1);
          PT(18 + w);
          if (w == 3) mbar_arrive(sb + BARS + 88);
          if (w == 8) mbar_arrive(wbar);
        }
        const uint32_t mb = sb + PACE + (c % 3) * 8;
        if (c >= 12 && c < 12 + WPE) tma2d_pf(&mp.wo, j * 256 + (c - 12) * 64, h * 128);
        if (c >= 12) continue;
        if (c < 9 && c != 4) {
          const int u = c > 4 ? c - 5 : c;
          mbar_expect(mb, 16384);
          tma2d(sb + (c > 4) * XB + u * 16384, c > 4 ? &mp.wk : &mp.wq, col, a * 512 + u * 128, mb);
        } else {
          const int n = c == 4 ? NVR : NVS, i0 = c == 4 ? 0 : (c - 9) * 8, i1 = c == 4 ? 2 * NVR : min(i0 + 8, 2 * NVS);
          mbar_expect(mb, (i1 - i0) * 2048);
#pragma unroll 1
          for (int i = i0; i < i1; i++)
            tma2d(sb + (c == 4 ? MEM : WVS) + i * 2048, &mp.wv, col, a * 512 + (i >= n ? 16 - n + i : i) * 16 + (c == 4 ? 0 : NVR * 16), mb);
        }
      }
      mbar_arrive(sb + BARS + 120);
      for (int i = 0; i < 3; i++) asm volatile("mbarrier.inval.shared.b64 [%0];" ::"r"(sb + PACE + i * 8) : "memory");
    }
    __syncwarp();
    asm volatile("barrier.cluster.wait.aligned;" ::: "memory");
#pragma unroll 4
    for (int i = 0; i < 16; i++) {
      const uint4 v = lds4(L16 + WO + 32768 + iw * 8192 + i * 512);
      sts4(L16 + XB + iw * 8192 + i * 512, v.x, v.y, v.z, v.w);
    }
#pragma unroll
    for (int i = 0; i < 4; i++) {
      const int k = (tid - 256) * 4 + i, m = (k >> 3) & 3, r = k & 7;
#define M0W(r) __byte_perm((i & 2) ? m0[r].y : m0[r].x, (i & 2) ? m0[r + 1].y : m0[r + 1].x, (i & 1) ? 0x7632 : 0x5410)
      sts4(sb + MEM + (k >> 5) * 640 + (r == m ? 512 : m * 128) + r * 16, M0W(0), M0W(2), M0W(4), M0W(6));
    }
#pragma unroll 1
    for (int i = tid - 256; i < 192; i += 128) {
      const uint32_t c = i < 128 ? 0x42004200 : 0x3f803f80;
      sts4(sb + MEM + (i >> 3) * 640 + ((i & 7) < 4 ? (i & 7) * 144 : 512 + (i & 7) * 16), c, c, c, c);
    }
    static_assert(ARO == MEM + 16 * 640, "counters");
    FENCE_ASYNC_SMEM();
    BAR_ARRIVE(B_C, 448);
    if (tid == 256) {
      wait_time(ts + 1);
#pragma unroll 1
      for (int c = WPE; c < 4; c++) tma2d_pf(&mp.wo, j * 256 + c * 64, h * 128);
    }
    __syncwarp();
#define pr (L16 + SC)
    {
      const int lim = j * 8 + iw * 2 - (lane & 7) - (lane & 8) * 2;
      const bool mk = L16 & 256;
      const int rw = lane >> 2;
      sts4(L16 + TA + iw * 512,
           iw != 2 ? L16 + KT + (iw & 1) * 256 + (lane >> 4) * 256 : sb + RK + (L16 & 0x80) * 2 + ((L16 >> 1) & 0x80) + (L16 & 0x70),
           L16 + QT + (lane >> 3) * 384, sb + SC + min(lane >> 3, 2) * 256 + (L16 & 0x70) + iw * 4, L16 + (lane >> 4) * 256 + QT + (iw >> 1) * 1024 + (iw & 1) * 256);
      sts4(L16 + TA + 2048 + iw * 512, mk ? 0u : (lim < 0 ? 0xfc00u : 0u) | (lim < -1 ? 0xfc000000u : 0u),
           mk ? 0xfc00fc00u : (lim < 8 ? 0xfc00u : 0u) | (lim < 7 ? 0xfc000000u : 0u),
           ((h * 2 + (iw >> 1)) * 1024 + (j * 8 + rw) * 8 + (((iw & 1) * 4 + (lane & 3)) ^ rw)) * 16, sb + OT + iw * 512 + (L16 & 0x70) * 4 + ((L16 >> 3) & 0x30));
    }
    {
      const uint32_t xh = LO(xc) + h * 262144, xs = xh + X_SC + iw * 1024 + min(lane, 16 + (lane & 7)) * 8;
      sts4(L16 + TA + 4096 + iw * 512, xh + X_SC + j * 256 + iw * 64 + lpub, xs, dS, iw != 2 ? 0 : U_(SCS));
      static_assert(TA % 1024 == 0, "warp index");
      sts1(L16 + TA + 12 + iw * 512, xs + X_TOK + j * 4096 - (CM && j < 2 && (lane >> 3) == 1 ? 64 : 0));
    }
    uint32_t tA = L16 + TA + iw * 512;
#define tw (tA - L16 != TA + 1024)
#define XP_(lo) mkp(lo, HI(xc))
    auto publish = [&](char* d, const uint2& w) {
      asm volatile("{.reg .pred p; .reg .b64 t; setp.ne.u32 p,%3,%4; mov.b64 t,{%1,%2}; @p st.relaxed.gpu.global.b64 [%0],t;}" ::"l"(d), "r"(w.x), "r"(w.y), "r"(tA - L16), "n"(TA + 1536) : "memory");
    };
    BAR_SYNC(B_P, 384);
    for (int s = 0; s < 64; s++) {
      asm volatile("" : "+r"(L16), "+r"(tA));
      const uint32_t tag = ((s >> 1) + 1) & 1, ring = (s & 1) * X_RING;
      const uint4 t0 = lds4(tA);
      const uint4 tx = lds4(tA + 4096);
      const uint32_t xo = tx.x ^ ring, xs = tx.y ^ ring;
      const float gm = F_(tx.w);
      const uint32_t qA = t0.y + (ring >> 5);
      uint32_t c0;
      uint2 ts[4];
      uint4 v[4];
      uint32_t af[2][4], qt[4][4];
      {
        const uint32_t aA = t0.x + (tw ? ring >> 5 : 0);
        uint32_t ql[2][4], qr[2][4];
        uint2 pw_;
        float c[4] = {0, 0, 0, 0}, d[4] = {0, 0, 0, 0};
        if (s == PDS) asm volatile("griddepcontrol.launch_dependents;");
#pragma unroll
        for (int i = 0; i < 4; i++) ldsm4t(qt[i], qA + i * 128);
        mbar_wait(sb + BARS + 8, s & 1);
        TS(4);
        BAR_SYNC(B_E, 256);
        DLY(14)
#define PACK(c) make_uint2(pkh(fmaf(c[2], gm, c[0] * SCS), fmaf(c[3], gm, c[1] * SCS), tag), pkh(c[2] * SCS, c[3] * SCS, tag))
        ldsm4t(ql[0], L16 + RQ); ldsm4t(ql[1], L16 + RQ + 1024); ldsm4t(af[0], aA); ldsm4t(af[1], aA + 1024);
        CONSUME(xo);
#define QSUM(t, i) addbf(addbf(ql[t][i], ql[t][i + 2]), addbf(qr[t][i], qr[t][i + 2]))
#define STAIL mma16(c, af[0][0], af[0][1], af[0][2], af[0][3], QSUM(0, 0), QSUM(0, 1)); mma16(d, af[1][0], af[1][1], af[1][2], af[1][3], QSUM(1, 0), QSUM(1, 1));
        if (tw) {
          mbar_wait(sb + BARS, s & 1);
          TS(8);
          ldsm4t(qr[0], L16 + RQ + 512); ldsm4t(qr[1], L16 + RQ + 1536);
          STAIL
          pw_ = make_uint2(pkh(c[0] + d[0], c[1] + d[1], tag), pkh(c[2] + d[2], c[3] + d[3], tag));
        } else {
          uint32_t ar[2][4];
          mbar_wait(sb + BARS, s & 1);
          ldsm4t(qr[0], L16 + RQ + 512); ldsm4t(ar[0], aA + 512); ldsm4t(qr[1], L16 + RQ + 1536); ldsm4t(ar[1], aA + 1536);
#pragma unroll
          for (int i = 0; i < 8; i++) af[i >> 2][i & 3] = addbf(af[i >> 2][i & 3], ar[i >> 2][i & 3]);
          STAIL
          pw_.x = pw_.y = pkh((c[0] + c[2]) + (d[0] + d[2]), (c[1] + c[3]) + (d[1] + d[3]), tag);
        }
        publish(XP_(xo), pw_);
        c0 = clk() + tx.z;
        TS(1);
      }
      uint2 r[4];
      bool vbad;
      uint4 vn[2];
      {
        float e[4][4];
#pragma unroll
        for (int i = 0; i < 4; i++) {
          e[i][0] = e[i][1] = e[i][2] = e[i][3] = 0.f;
          mma16(e[i], af[0][0], af[0][1], af[0][2], af[0][3], qt[i][0], qt[i][1]);
        }
#pragma unroll
        for (int i = 0; i < 4; i++) mma16(e[i], af[1][0], af[1][1], af[1][2], af[1][3], qt[i][2], qt[i][3]);
        SCHED_FENCE(55);
        if (s < 63) BAR_ARRIVE(B_S, 416);
        SCHED_FENCE(58);
        v[0] = lds4(tA + (VX0 - TA)); v[1] = lds4(tA + (VX0 - TA) + 2048); v[2] = lds4(tA + (VX1 - TA)); v[3] = lds4(tA + (VX1 - TA) + 2048);
#pragma unroll
        for (int i = 0; i < 4; i++) ts[i] = PACK(e[i]);
        vbad = anybad(v[0].x, v[1].x, v[2].x, v[3].x, V_TAG(s));
#pragma unroll
        for (int i = 3; i >= 0; i--) {
          if (CM && i < 2)
            asm volatile("{.reg .pred p; .reg .b64 t; .reg .b32 u; and.b32 u,%3,512; setp.eq.u32 p,u,0; mov.b64 t,{%1,%2}; @p st.relaxed.gpu.global.b64 [%0],t;}"
                         ::"l"(XP_(xo) + X_TOK + i * 4096), "r"(ts[i].x), "r"(ts[i].y), "r"(tA - L16) : "memory");
          else publish(XP_(xo) + X_TOK + i * 4096, ts[i]);
        }
        while ((int)(clk() - c0) < 0) {}
        TS(5);
#pragma unroll
        for (int u = 0; u < 4; u++) r[u] = ldg_b64(XP_(xs) + u * 256);
        BAR_ARRIVE(B_S2, 256);
      }
      SCHED_FENCE(56);
      uint32_t kk;
      float4 e = softmax2<false>(r, 0, 0, kk);
      if (__builtin_expect(anybad(r[0].x, r[0].y, r[1].x, r[1].y, r[2].x, r[2].y, r[3].x, r[3].y, tag ^ (kk & dZ)), 0)) {
        int it = 0;
        if (s > 8) sts1(tA + 4096 + 8, min(lds1(tA + 4096 + 8) + dX, 500));
        do {
          RP(1);
          if (++it > SPIN_LIMIT) __trap();
#pragma unroll
          for (int u = 0; u < 4; u++) r[u] = ldg_b64(XP_(xs) + u * 256);
        } while (BADS(r));
        e = softmax2<false>(r, 0, 0, kk);
      }
      DLY(5)
      sts1(t0.z, pk(e.x, e.y)); sts1(t0.z + 128, pk(e.z, e.w));
      TS(6);
      if (s < 63) BAR_SYNC(B_V, 512); else BAR_SYNC(B_V, 256);
      uint32_t O[4];
      {
        uint32_t p[4], pm;
        ldsm4t(p, pr);
        asm volatile("ldmatrix.sync.aligned.m8n8.x1.trans.shared.b16 {%0},[%1];" : "=r"(pm) : "r"(pr + 512) : "memory");
        vn[0] = lds4(tA + (VN - TA)); vn[1] = lds4(tA + (VN - TA) + 2048);
        pv_mem(p, pm, v, vn, O);
        if (__builtin_expect(vbad, 0)) {
          int it = 0;
          const uint32_t xv = LO(xc) + (lds1(sb + PACE + 24) >> 2) * 262144 + ((tA - L16 - TA) >> 9) * XC;
          do {
            RP(2);
            if (++it > SPIN_LIMIT) __trap();
#pragma unroll
            for (int u = 0; u < 4; u++) v[u] = ldg_b128(XP_((xv + l16) ^ V_RING(s)) + X_VX(u));
          } while (anybad(v[0].x, v[1].x, v[2].x, v[3].x, V_TAG(s)));
          pv_mem(p, pm, v, vn, O);
        }
      }
      DLY(6)
      stsm4(tA + (OB - TA), O[0], O[1], O[2], O[3]);
      if (s < 63) BAR_ARRIVE(B_O, 416);
      TS(2);
      c0 = clk() + dG;
      SCHED_FENCE(60);
      if (tA == sb + TA) mbar_expect(sb + BARS, 2048);
      const uint32_t vs[4] = {addbf(vn[0].x, vn[0].z), addbf(vn[0].y, vn[0].w), addbf(vn[1].x, vn[1].z), addbf(vn[1].y, vn[1].w)};
      {
        const char* xt = XP_(lds1(tA + 12) ^ ring);
        const uint2 t1 = lds2u(tA + 2048);
        const uint32_t pw = lds1(tA + 8);
        uint2 rt[4];
        CONSUME(LO(xt) ^ t1.x ^ pw);
        while ((int)(clk() - c0) < 0) {}
        int it = 0;
        do {
          if (++it > SPIN_LIMIT) __trap();
#pragma unroll
          for (int u = 0; u < 4; u++) rt[u] = ldg_b64(xt + u * 256);
        } while (BADS(rt));
        uint32_t kt;
        const float4 et = softmax2<true>(rt, t1.x, t1.y, kt);
        sts1(pw + 1024, pk(et.x, et.y)); sts1(pw + 1024 + 128, pk(et.z, et.w));
      }
      s = PIN(s);
      BAR_SYNC(B_SC, 128);
      {
        uint32_t Ot[4], p[4], pm;
        const uint2 t2 = lds2u(tA + 2048 + 8);
        ldsm4t(p, pr + 1024);
        asm volatile("ldmatrix.sync.aligned.m8n8.x1.trans.shared.b16 {%0},[%1];" : "=r"(pm) : "r"(pr + 1024 + 512) : "memory");
        char* od = (char*)g_O + ((s >> 2) * 1048576 + (s & 3) * 4096) + t2.x;
        CONSUME(LO(od) ^ HI(od) ^ pm ^ p[3]);
        TS(9);
        if (s < 62) BAR_SYNC(B_P, 384);
        DLY(13)
        pv_tok(p, pm, v, vs, Ot);
        asm volatile("stmatrix.sync.aligned.m8n8.x4.trans.shared.b16 [%0],{%1,%2,%3,%4};" ::"r"(t2.y), "r"(Ot[0]), "r"(Ot[1]), "r"(Ot[2]), "r"(Ot[3]) : "memory");
        __syncwarp();
        *(uint4*)od = lds4(tA + (OT - TA));
      }
    }
    FENCE_ASYNC();
    BAR_SYNC(B_SC, 128);
    if (tA == sb + TA) red_rlx(&g_fin);
  }
  __syncwarp();
  CLUSTER_SYNC();
  PH(5); RS(2);
}
#undef wg
#undef iw
#undef h
#undef j
#undef a
#undef bb
#undef oi
#undef owner
#undef ownv
#undef pr
#undef PIN
#undef XP_
#undef tw
#undef lane
#undef l16
#undef lrow
#undef lpub

namespace ffn {
constexpr uint32_t BR = 98304;
constexpr uint32_t STG = 196608;
constexpr uint32_t PRM = 229376;
constexpr uint32_t BARS = PRM + 2816;
constexpr uint32_t SMEM = BARS + 18 * 8;
}
#define Y_TILE(rb, kt) (((ALIAS & 1) ? g_h : g_h2) + ((rb) * 16 + (kt)) * 1024)
#define U_TILE(rb, kt) ((ALIAS & 2) ? g_O + ((rb) * 64 + (kt)) * 1024 : g_U + ((rb) * 56 + (kt)) * 1024)
struct FfnMaps { CUtensorMap wo, w1a, w1b, w2, x, out; };

template <int N>
__device__ __forceinline__ void wg_ss(float* d, uint64_t a, uint64_t b, int sd) {
  if (N == 128) wgmma_ss_n128(d, a, b, sd);
  if (N == 192) wgmma_ss_n192(d, a, b, sd);
}
template <int N>
__device__ __forceinline__ void acc_fence(float* d) {
#pragma unroll
  for (int i = 0; i < N; i++) asm volatile("" : "+f"(d[i])::"memory");
}
#define UNPK8(d, v) do { (d)[0] = blo(v.x); (d)[1] = bhi(v.x); (d)[2] = blo(v.y); (d)[3] = bhi(v.y); (d)[4] = blo(v.z); (d)[5] = bhi(v.z); (d)[6] = blo(v.w); (d)[7] = bhi(v.w); } while (0)
struct FfnPipe {
  uint32_t full, emp, ph, aoff;
  int st, sB, prev;
  bool leader;
  template <int N, int S = N>
  __device__ __forceinline__ void issue(float* acc, bool first, uint32_t a = 0) {
    mbar_wait(full + st * 8, ph);
    const uint64_t da = mkdesc((a ? a : 1024 + st * 16384) + aoff, 16, 1024), db = mkdesc(1024 + ffn::BR + sB * (S * 128), 8192, 1024);
    WG_FENCE();
#pragma unroll
    for (int j = 0; j < 4; j++) wg_ss<N>(acc, da + j * 2, db + j * 128, j || !first);
    WG_COMMIT();
    if (++sB == 768 / S) sB = 0;
  }
  __device__ __forceinline__ void release() { if (leader) mbar_arrive(emp + prev * 8); }
  __device__ __forceinline__ void next() { prev = st; if (++st == 6) { st = 0; ph ^= 1; } }
  __device__ __forceinline__ void retire() { WG_WAIT(1); release(); next(); }
};
__device__ __forceinline__ float gelu_h(float hx) {
  float u = hx * fmaf(hx * hx, 8.f * 0.0356774081f, 2.f * 0.7978845608f), t;
  asm("tanh.approx.f32 %0,%1;" : "=f"(t) : "f"(u));
  return fmaf(hx, t, hx);
}
struct FfnEpi {
  uint32_t st2, cc, flip, staged, l0;
  uint2 c;
  float n0, n1, s0, s1;
  __device__ __forceinline__ void flush(uint32_t r) {
    __syncwarp();
    asm volatile("{.reg .pred p; setp.ne.u32 p,%1,0; @p mbarrier.arrive.shared.b64 _,[%0];}" ::"r"(staged + (flip >> 11)), "r"(l0 & r) : "memory");
    flip ^= r << 14;
  }
  __device__ __forceinline__ void half(const float* d, int J, int r) {
#define PRE(i, n, c1, c2) gelu_h(fmaf(r ? d[4 + i] : d[i], i < 2 ? s0 : s1, fmaf(n, c1, c2)))
    asm volatile("stmatrix.sync.aligned.m8n8.x2.shared.b16 [%0],{%1,%2};" ::"r"((st2 ^ ((J & 3) * 32 + r * 16)) + flip),
                 "r"(pk(PRE(0, n0, blo(c.x), blo(c.y)), PRE(1, n0, bhi(c.x), bhi(c.y)))), "r"(pk(PRE(2, n1, blo(c.x), blo(c.y)), PRE(3, n1, bhi(c.x), bhi(c.y)))) : "memory");
#undef PRE
    if ((J & 3) == 3) flush(r);
    cc += r ? 56 : 8;
    c = lds2u(cc);
  }
};

__global__ void __launch_bounds__(384, 1)
k_ffn(const __grid_constant__ FfnMaps mp, const bf16* __restrict__ b2) {
  using namespace ffn;
  extern __shared__ __align__(1024) char smem[];
  const uint32_t sb = (uint32_t)__cvta_generic_to_shared(smem);
  if (sb != 1024) __trap();
  const int tid = threadIdx.x, lane = tid & 31, wg = __shfl_sync(~0u, tid >> 7, 0);
  const uint32_t full = sb + BARS, emp = full + 48, xbar = full + 96, staged = full + 104, tile = full + 136;
  uint32_t fin = 0;
  if (tid >= 288 && tid < 320) fin = ld_acq(&g_fin);
  if (tid < 32) {
    unsigned sm, v = 0;
    asm("mov.u32 %0,%%smid;" : "=r"(sm));
    if (tid == 0) {
      v = atomicExch(&g_slot[sm & 255], 0);
      for (int i = 0; i < 6; i++) { mbar_init(full + i * 8, 1); mbar_init(emp + i * 8, 2); }
      mbar_init(xbar, 2);
      for (int i = 0; i < 2; i++) { mbar_init(staged + i * 8, 8); mbar_init(staged + 16 + i * 8, 1); }
      FENCE_ASYNC_SMEM();
    }
    v = __shfl_sync(~0u, v, 0);
    if (!v) {
      wait_cnt(&g_fin, 128);
      for (int it = 0; !v; it++) {
        const uint4 a = ldg_rlx4(g_slot + tid * 8), b = ldg_rlx4(g_slot + tid * 8 + 4);
        const uint32_t open = __ballot_sync(~0u, a.x | a.y | a.z | a.w | b.x | b.y | b.z | b.w);
        if (!open) break;
        if (it < 16) { __nanosleep(500); continue; }
        if (tid == __ffs(open) - 1) v = atomicExch(&g_slot[tid * 8 + (a.x ? 0 : a.y ? 1 : a.z ? 2 : a.w ? 3 : b.x ? 4 : b.y ? 5 : b.z ? 6 : 7)], 0);
        v = __shfl_sync(~0u, v, __ffs(open) - 1);
      }
    }
    if (tid == 0) sts1(tile, v);
  }
  if (tid == 256) asm volatile("prefetch.tensormap [%0];" ::"l"(&mp.wo) : "memory");
  __syncthreads();
  const int bid = __shfl_sync(~0u, lds1(tile), 0) - 1;
  if (bid < 0) return;
  PH(6);
  FT(1);
  const int rb = bid >> 3, nb = bid & 7;
  unsigned* cnt = g_cnt + rb * 128;
  if (wg == 2) {
    asm volatile("setmaxnreg.dec.sync.aligned.u32 " FRP ";");
    const int pw = __shfl_sync(~0u, (tid >> 5) & 3, 0);
    uint32_t ws = emp, wp = 1, fs = full;
    auto wait_free = [&]() { mbar_wait_q(ws, wp); ws += 8; if (ws == emp + 48) { ws = emp; wp ^= 1; } };
    auto step = [&]() { fs += 8; if (fs == full + 48) fs = full; };
#define K3(c) ((0x65230 >> (c) * 4) & 7)
#define KC(k) ((k) < 2 ? nb * 2 + (k) : (k) < 9 ? ((k) - 2 + ((k) - 2 >= nb)) * 2 : ((k) - 9 + ((k) - 9 >= nb)) * 2 + 1)
    if (pw == 0) {
      uint32_t d = sb + BR + 32768;
      auto put = [&](const CUtensorMap* m, int k, int c) {
        e_expect_tma3d(d, m, k * 64, c, fs, 32768);
        step();
        d += 16384;
        if (d == sb + STG) d = sb + BR;
      };
      int n = 0;
      auto stage_free = [&]() { if (!(n & 7) && n < 56) mbar_wait_q(staged + 16 + (n & 8), (n >> 4) & 1); n++; };
      auto align = [&]() {
        if (ALN && !((n - 1) & 7) && ((ALN >> ((n - 1) >> 3)) & 1)) {
          unsigned* c = g_cnt + 64 + ((n - 1) >> 3);
          if (lane == 0) red_rlx(c);
          for (int it = 0; ldg_rlx1(c) < 128 && it < 64; it++) {}
        }
      };
      FTP(3);
#pragma unroll 1
      for (int k = 0; k < 66; k++) { wait_free(); if (k < 64) put(&mp.wo, k, nb * 2); }
#pragma unroll 1
      for (int k = 0; k < 18; k++) {
        const int u = k >= 2 ? k - 2 : k, kt = KC(u);
        const bool ea = (k & ~1) == 2;
        wait_free();
        e_expect_tma3d(sb + BR + (k & 3) * 24576, ea ? &mp.w1a : &mp.w1b, kt * 64, nb * 7 + (ea ? 3 : 0), fs, ea ? 16384 : k < 2 ? 24576 : 40960);
        step();
      }
      d = sb + BR + 49152;
#pragma unroll 1
      for (int k = 2; k < 32; k++) {
        const int kt = k < 16 ? KC(k) : k & 15;
        stage_free();
        if (k == 2 || k == 9) n++;
        if (k != 7 && k != 8) wait_free();
        align();
        put(&mp.w1a, kt, nb * 7 + 3 + (k >> 4) * 2);
      }
#pragma unroll 1
      for (int c = 0; c < 5; c++)
#pragma unroll 1
        for (int k = K3(c), i = 0; k < 56; k += c < 2 && (i ^= 1) ? 1 : c < 2 ? 6 : 7) { stage_free(); wait_free(); align(); put(&mp.w2, k, nb * 2); }
    } else if (pw == 1) {
      FTP(5);
      if (fin < 128) wait_cnt(&g_fin, 128);
      FTP(6);
      uint32_t d = sb;
      auto put = [&](const uint4* A, bool ld) {
        wait_free();
        if (ld) e_bulk_ld(d, A, 16384, fs);
        step();
        d += 16384;
        if (d == sb + BR) d = sb;
      };
      const uint4* A = g_O + rb * 65536;
#pragma unroll 1
      for (int k = 0; k < 68; k++) put(A + k * 1024, k < 64);
      A = Y_TILE(rb, 0);
      uint32_t ready = 0;
#pragma unroll 1
      for (int k = 2; k < 48; k++) {
        if (k == 16) k = 18;
        const int kt = k < 32 ? KC(k & 15) : k & 15;
        for (int it = 0; !(ready >> ((kt >> 1) + (kt & 1) * 8) & 1); it++) {
          ready = __ballot_sync(~0u, ldg_rlx1(cnt + (lane & 7)) & ((lane & 8) ? 1 : 0x10000));
          if (it > SPIN_LIMIT) __trap();
        }
        if (k == 2) FTP(75);
        put(A + kt * 1024, true);
      }
      A = U_TILE(rb, 0);
#pragma unroll 1
      for (int c = 0; c < 5; c++) {
        for (int it = 0; ldg_rlx1(cnt + 32 + c) < 8; it++) if (it > SPIN_LIMIT) __trap();
#pragma unroll 1
        for (int k = K3(c), i = 0; k < 56; k += c < 2 && (i ^= 1) ? 1 : c < 2 ? 6 : 7) put(A + k * 1024, true);
      }
    } else if (pw == 2) {
#pragma unroll 1
      for (int i = 0; i < XDL; i++) mbar_wait_q(emp, i & 1);
      if (lane == 0) {
        mbar_expect(xbar, 32768);
#pragma unroll 1
        for (int i = 0; i < 256 / XR; i++) {
          tma2d(sb + STG + i * (XR * 128), &mp.x, nb * 128 + (i * XR >> 7) * 64, rb * 128 + ((i * XR) & 127), xbar);
          const uint32_t c = clk();
          while (clk() - c < XTD) {}
        }
      }
      asm volatile("griddepcontrol.wait;" ::: "memory");
      if (lane < 16) g_modp[bid * 16 + lane] = make_uint4(0, 0, 0, 0);
      if (lane >= 16 && bid == 0) { g_hcnt = 0; g_mcnt = 0; g_hf[lane & 3] = 0; }
      if (lane == 0) {
#pragma unroll 1
        for (int g = 1; g < 9; g++) {
          if (g == 1) mbar_wait(staged + 8, 0); else { mbar_wait_q(staged + (g & 1) * 8, (g >> 1) & 1); FENCE_ASYNC_SMEM(); }
          uint4* dst = g == 1 ? Y_TILE(rb, nb * 2 + 1) : U_TILE(rb, nb * 7 + ((0x652431000ull >> g * 4) & 7));
#pragma unroll 1
          for (int i = 0; i < (g > 1 ? 4 : 1); i++) {
            bulk_st(dst + i * 256, sb + STG + (g & 1) * 16384 + i * 4096, g > 1 ? 4096 : 16384);
            const uint32_t c = clk();
            while (g > 1 && clk() - c < USD) {}
          }
          BULK_COMMIT();
          if (g != 2 && g != 4) { BULK_WAIT(0); red_rlx(g == 1 ? cnt + nb : cnt + 32 + (g < 6 ? g >> 2 : g - 4)); }
          BULK_WAIT_READ(0);
          mbar_arrive(staged + 16 + (g & 1) * 8);
        }
      }
    } else {
      const uint32_t prm = sb + PRM, pp = prm + (lane >> 3) * 64 + (lane & 1) * 32 + (lane & 6) * 2;
      const uint2 v2 = ((const uint2*)(b2 + nb * 128))[lane];
      sts1(pp + 768, v2.x); sts1(pp + 784, v2.y);
      asm volatile("griddepcontrol.wait;" ::: "memory");
      const float4* md = (const float4*)(g_mod + nb * 128) + lane;
      { const float4 ga = md[512]; sts1(pp, pk(ga.x, ga.y)); sts1(pp + 16, pk(ga.z, ga.w)); }
      { const float4 cb = md[1024]; sts1(pp + 256, pk(1.f + cb.x, 1.f + cb.y)); sts1(pp + 272, pk(1.f + cb.z, 1.f + cb.w)); }
      { const float4 gb = md[1280]; sts1(pp + 512, pk(gb.x, gb.y)); sts1(pp + 528, pk(gb.z, gb.w)); }
#pragma unroll 1
      for (int i = lane; i < 112; i += 32) { const uint4 c = g_cc[nb * 112 + i]; sts4(prm + 1024 + i * 16, c.x, c.y, c.z, c.w); }
      __syncwarp();
      if (lane == 0) {
        mbar_arrive(xbar);
        mbar_wait(staged, 0);
        bulk_st(Y_TILE(rb, nb * 2), sb + STG, 16384);
        BULK_COMMIT(); BULK_WAIT(0);
        asm volatile("red.relaxed.gpu.global.add.u32 [%0],0x10000;" ::"l"(cnt + nb) : "memory");
        mbar_arrive(staged + 16);
      }
      __syncwarp();
      mbar_wait_q(staged + 24, 0);
      mbar_wait_q(emp + 8, 1);
#pragma unroll 1
      for (int i = 0; i < 4; i++) {
        const uint4* sp = g_stat + (rb * 128 + i * 32 + lane) * 4;
        uint4 v[4];
        for (int it = 0;; it++) {
          uint32_t m = 0;
#pragma unroll
          for (int u = 0; u < 4; u++) { v[u] = ldg_rlx4(sp + u); m = max(max(m, max(v[u].x, v[u].y)), max(v[u].z, v[u].w)); }
          if (!__any_sync(~0u, m == ~0u)) break;
          if (it > SPIN_LIMIT) __trap();
        }
        float m = 0, q = 0;
#pragma unroll
        for (int u = 0; u < 4; u++) { m += F_(v[u].x) + F_(v[u].z); q += F_(v[u].y) + F_(v[u].w); }
        m *= 1.f / 1024;
        const float r = 0.5f * rsqrtf(fmaxf(q * (1.f / 1024) - m * m, 0.f) + 1e-5f);
        sts2(sb + STG + 16384 + (i * 32 + lane) * 8, U_(r), U_(-m * r));
      }
      __syncwarp();
      if (lane < 2) mbar_arrive(xbar);
    }
  } else {
    asm volatile("setmaxnreg.inc.sync.aligned.u32 " FRC ";");
    const int w = (tid >> 5) & 3, q = lane & 3;
    const uint32_t prm = sb + PRM + q * 16;
    const int row0 = wg * 64 + w * 16;
    FfnPipe p;
    p.full = full; p.emp = emp; p.ph = 0; p.aoff = wg * 8192; p.st = 0; p.sB = 2; p.prev = 0; p.leader = (tid & 127) == 0;
    FfnEpi e;
    const uint32_t stg = sb + STG + row0 * 128;
    e.st2 = stg + (lane & 15) * 128 + ((lane & 7) << 4);
    e.cc = sb + PRM + 1024 + q * 16; e.flip = 0; e.staged = staged; e.l0 = lane == 0;
    const uint32_t stw = e.st2 ^ (lane & 16);
    uint32_t x1[32];
    uint4* sp = g_stat + (rb * 128 + row0 + (lane >> 2)) * 4;
    float old[96], r0_, r1_;
    {
      float acc[64];
      p.issue<128>(acc, true); FT(8); p.next();
#pragma unroll 1
      for (int k = 1; k < 64; k++) { p.issue<128>(acc, false); FT(8 + k); p.retire(); }
      float xf[64], gf[32];
      uint32_t cb[16];
      mbar_wait(xbar, 0);
#pragma unroll
      for (int j = 0; j < 8; j++) {
        uint32_t xv[4];
        ldsm4(xv, (stw ^ ((j & 3) * 32)) + (j >> 2) * 16384);
#pragma unroll
        for (int i = 0; i < 4; i++) { xf[j * 8 + i * 2] = blo(xv[i]); xf[j * 8 + i * 2 + 1] = bhi(xv[i]); }
      }
#pragma unroll
      for (int i = 0; i < 4; i++) {
        const uint4 g = lds4(prm + i * 64), c = lds4(prm + 256 + i * 64);
        UNPK8(gf + i * 8, g);
        cb[i * 4] = c.x; cb[i * 4 + 1] = c.y; cb[i * 4 + 2] = c.z; cb[i * 4 + 3] = c.w;
      }
      acc_fence<64>(xf); acc_fence<32>(gf);
      WG_WAIT(0);
      p.release();
      acc_fence<64>(acc);
      PH(7); FT(72);
#pragma unroll
      for (int j = 0; j < 8; j++) {
        uint32_t* o = x1 + j * 4;
#pragma unroll
        for (int i = 0; i < 4; i++)
          o[i] = pk(fmaf(acc[j * 8 + i * 2], gf[j * 4 + (i & 2)], xf[j * 8 + i * 2]), fmaf(acc[j * 8 + i * 2 + 1], gf[j * 4 + (i & 2) + 1], xf[j * 8 + i * 2 + 1]));
        stsm4((stw ^ ((j & 3) * 32)) + (j >> 2) * 16384, mulbf(o[0], cb[j * 2]), mulbf(o[1], cb[j * 2]), mulbf(o[2], cb[j * 2 + 1]), mulbf(o[3], cb[j * 2 + 1]));
        if ((j & 3) == 3) { FENCE_ASYNC_SMEM(); e.flush(1); }
      }
      if (wg) BAR_SYNC(2, 128); else BAR_SYNC(3, 128);
    }
    PH(8); FT(73);
    float acc[64];
    {
      float* accC = old;
      p.sB = 0;
      p.issue<192>(accC, true, 1024 + STG); FT(80); p.next();
      p.issue<192>(accC, false, 1024 + STG + 16384); FT(81);
      FT(78);
      float s0 = 0, s1 = 0, q0 = 0, q1 = 0;
#define X1_FENCE _Pragma("unroll") for (int j = 0; j < 32; j++) asm volatile("" : "+r"(x1[j]));
      X1_FENCE
#pragma unroll
      for (int j = 0; j < 16; j++) {
        const float a = blo(x1[j * 2]), b = bhi(x1[j * 2]), c = blo(x1[j * 2 + 1]), d = bhi(x1[j * 2 + 1]);
        s0 += a + b; s1 += c + d; q0 = fmaf(a, a, fmaf(b, b, q0)); q1 = fmaf(c, c, fmaf(d, d, q1));
      }
#pragma unroll
      for (int o = 1; o < 4; o *= 2) { s0 += __shfl_xor_sync(~0u, s0, o); s1 += __shfl_xor_sync(~0u, s1, o); q0 += __shfl_xor_sync(~0u, q0, o); q1 += __shfl_xor_sync(~0u, q1, o); }
      if (q < 2) {
        uint32_t m = __float_as_uint(q ? s1 : s0), v = __float_as_uint(q ? q1 : q0);
        if (m == ~0u) m = 0x7fffffffu;
        if (v == ~0u) v = 0x7fffffffu;
        stg_rlx2((uint2*)(sp + q * 32) + nb, m, v);
      }
      X1_FENCE
      p.retire();
#pragma unroll 1
      for (int k = 0; k < 2; k++) { p.issue<128, 192>(acc, !k, 1024 + STG + k * 16384); p.retire(); }
#pragma unroll 1
      for (int k = 2; k < 15; k++) { p.issue<192>(accC, false); FT(80 + k); p.retire(); }
      p.issue<192>(accC, false); FT(95);
      mbar_wait(xbar, 1);
      const float2 u0 = lds2f(sb + STG + 16384 + (row0 + (lane >> 2)) * 8), u1 = lds2f(sb + STG + 16384 + (row0 + (lane >> 2)) * 8 + 64);
      r0_ = u0.x; e.n0 = u0.y; r1_ = u1.x; e.n1 = u1.y;
      e.c = lds2u(e.cc);
      p.retire();
      e.s0 = r0_; e.s1 = r1_;
      p.sB = 3;
    }
    PH(9);
    {
      auto pair = [&](int J, bool first, bool one, int fo) {
#pragma unroll 1
        for (int r = 0; r < 2; r++) {
          if (!(one && r)) { p.issue<128>(acc, first && !r); FT(fo + r); p.retire(); }
          acc_fence<8>(old + J * 8);
          e.half(old + J * 8, J, r);
        }
      };
#pragma unroll 1
      for (int i = 0; i < 3; i++) {
        if (i == 2) {
          e.s0 = r0_; e.s1 = r1_;
#pragma unroll
          for (int J = 8; J < 12; J++) pair(J, J == 8, false, 128 + (J - 8) * 2);
          e.cc += 512; e.c = lds2u(e.cc);
          e.s0 = e.s1 = 1.f;
        }
#pragma unroll
        for (int J = 0; J < 8; J++) pair(J, J == 0 && i == 1, !(J & 3) && !i, 96 + i * 16 + (i >> 1) * 8 + J * 2);
        if (i == 2) break;
        e.cc += i ? -768 : 256; e.c = lds2u(e.cc);
        WG_WAIT(0);
        acc_fence<64>(acc);
#pragma unroll
        for (int k = 0; k < 64; k++) old[k] = acc[k] * ((k & 2) ? r1_ : r0_);
        acc_fence<64>(old);
        e.s0 = e.s1 = 1.f;
        PH(10 + i);
      }
#pragma unroll 1
      for (int k = 24; k < 56; k++) {
        if (SKW && k == 56 - SKW && wg) BAR_SYNC(4, 256);
        p.issue<128>(acc, false); FT(128 + k);
        if (SKW && k == 55 && !wg) BAR_ARRIVE(4, 256);
        p.retire();
      }
      float xf[64], gf[32];
#pragma unroll
      for (int i = 0; i < 4; i++) {
        const uint4 g = lds4(prm + 512 + i * 64), h = lds4(prm + 768 + i * 64);
        float hf[8];
        UNPK8(gf + i * 8, g); UNPK8(hf, h);
#pragma unroll
        for (int u = 0; u < 8; u++) {
          const int c = (u >> 2) * 4 + (u & 2);
          xf[i * 16 + u * 2] = fmaf(gf[i * 8 + c], hf[c], blo(x1[i * 8 + u])); xf[i * 16 + u * 2 + 1] = fmaf(gf[i * 8 + c + 1], hf[c + 1], bhi(x1[i * 8 + u]));
        }
      }
      acc_fence<64>(xf); acc_fence<32>(gf);
      mbar_wait(staged + 24, 1);
      mbar_wait(staged + 16, 0);
      WG_WAIT(0);
      acc_fence<64>(acc);
      PH(13); FT(184);
#pragma unroll
      for (int j = 0; j < 8; j++) {
        uint32_t o[4];
#pragma unroll
        for (int i = 0; i < 4; i++)
          o[i] = pk(fmaf(acc[j * 8 + i * 2], gf[j * 4 + (i & 2)], xf[j * 8 + i * 2]), fmaf(acc[j * 8 + i * 2 + 1], gf[j * 4 + (i & 2) + 1], xf[j * 8 + i * 2 + 1]));
        stsm4((stw ^ ((j & 3) * 32)) + (j >> 2) * 16384, o[0], o[1], o[2], o[3]);
        if ((j & 3) == 3) {
          FENCE_ASYNC_SMEM();
          __syncwarp();
          if (lane == 0) { tma2d_st(&mp.out, nb * 128 + (j >> 2) * 64, rb * 128 + row0, stg + (j >> 2) * 16384); BULK_COMMIT(); }
        }
      }
      if (lane == 0) BULK_WAIT_READ(0);
      __syncwarp();
    }
  }
  PH(14); FT(185);
}

typedef CUresult (*EncFn)(CUtensorMap*, CUtensorMapDataType, cuuint32_t, void*, const cuuint64_t*, const cuuint64_t*, const cuuint32_t*,
                          const cuuint32_t*, CUtensorMapInterleave, CUtensorMapSwizzle, CUtensorMapL2promotion, CUtensorMapFloatOOBfill);
static void map2d(EncFn enc, CUtensorMap* m, const void* p, int rows, int cols, int boxRows) {
  cuuint64_t d[2] = {(cuuint64_t)cols, (cuuint64_t)rows}, s[1] = {(cuuint64_t)cols * 2};
  cuuint32_t b[2] = {64, (cuuint32_t)boxRows}, e[2] = {1, 1};
  enc(m, CU_TENSOR_MAP_DATA_TYPE_BFLOAT16, 2, (void*)p, d, s, b, e, CU_TENSOR_MAP_INTERLEAVE_NONE, CU_TENSOR_MAP_SWIZZLE_128B,
      CU_TENSOR_MAP_L2_PROMOTION_L2_128B, CU_TENSOR_MAP_FLOAT_OOB_FILL_NONE);
}
static void map3d(EncFn enc, CUtensorMap* m, const void* p, int rows, int cols, int nch) {
  cuuint64_t d[3] = {64, (cuuint64_t)rows, (cuuint64_t)(cols / 64)}, s[2] = {(cuuint64_t)cols * 2, 128};
  cuuint32_t b[3] = {64, 64, (cuuint32_t)nch}, e[3] = {1, 1, 1};
  enc(m, CU_TENSOR_MAP_DATA_TYPE_BFLOAT16, 3, (void*)p, d, s, b, e, CU_TENSOR_MAP_INTERLEAVE_NONE, CU_TENSOR_MAP_SWIZZLE_128B,
      CU_TENSOR_MAP_L2_PROMOTION_L2_128B, CU_TENSOR_MAP_FLOAT_OOB_FILL_NONE);
}

extern "C" void kernel_launch(void* const* d_in, const int* in_sizes, int n_in, void* d_out, int out_size) {
  const bf16* x = (const bf16*)d_in[0];
  const bf16* mem0 = (const bf16*)d_in[1];
  void* fn = nullptr;
  cudaDriverEntryPointQueryResult qr;
  cudaGetDriverEntryPoint("cuTensorMapEncodeTiled", &fn, cudaEnableDefault, &qr);
  EncFn enc = (EncFn)fn;
  FfnMaps fm = {};
  map3d(enc, &fm.wo, d_in[5], 4096, 1024, 2);
  map3d(enc, &fm.w1a, d_in[8], 1024, 3584, 2);
  map3d(enc, &fm.w1b, d_in[8], 1024, 3584, 3);
  map3d(enc, &fm.w2, d_in[10], 3584, 1024, 2);
  map2d(enc, &fm.x, x, 2048, 1024, XR);
  map2d(enc, &fm.out, d_out, 2048, 1024, 16);
  RecMaps rm = {};
  map2d(enc, &rm.wq, d_in[2], 1024, 4096, 128);
  map2d(enc, &rm.wk, d_in[3], 1024, 4096, 128);
  map2d(enc, &rm.wv, d_in[4], 1024, 4096, 16);
  map2d(enc, &rm.wo, d_in[5], 4096, 1024, 128);
  char* xc = nullptr;
  cudaGetSymbolAddress((void**)&xc, g_xc);
  xc += (0 - (uintptr_t)xc) & 0x1FFFFF;
  {
    cuuint64_t d[3] = {512, 6, 128}, sd[2] = {131072, 1024};
    cuuint32_t bi[3] = {64, 5, 8}, e[3] = {1, 1, 1};
    enc(&rm.ari, CU_TENSOR_MAP_DATA_TYPE_BFLOAT16, 3, xc + AR_OFF, d, sd, bi, e, CU_TENSOR_MAP_INTERLEAVE_NONE, CU_TENSOR_MAP_SWIZZLE_NONE,
        CU_TENSOR_MAP_L2_PROMOTION_NONE, CU_TENSOR_MAP_FLOAT_OOB_FILL_NONE);
  }
  {
    cuuint64_t d[5] = {256, 4, 2, 2, 2048}, sd[4] = {rec::XC, X_VX(1), X_VX(2), 4096};
    cuuint32_t bi[5] = {256, 4, 2, 2, 1}, e[5] = {1, 1, 1, 1, 1};
    enc(&rm.vx, CU_TENSOR_MAP_DATA_TYPE_BFLOAT16, 5, xc, d, sd, bi, e, CU_TENSOR_MAP_INTERLEAVE_NONE, CU_TENSOR_MAP_SWIZZLE_NONE,
        CU_TENSOR_MAP_L2_PROMOTION_NONE, CU_TENSOR_MAP_FLOAT_OOB_FILL_NONE);
  }
  cudaFuncSetAttribute(k_ffn, cudaFuncAttributeMaxDynamicSharedMemorySize, ffn::SMEM);
  cudaFuncSetAttribute(k_rec, cudaFuncAttributeMaxDynamicSharedMemorySize, rec::SMEM);
  cudaStream_t st = cudaStreamPerThread;
  int dF = 450, dA = 2700, dS = 250, dM = 120, dG = 250, dP = 24, dX = 48, dD = 350, dZ = 0, dQ = 750, dV = 370, dX2 = 0;
  k_rec<<<132, 512, rec::SMEM, st>>>(rm, mem0, x, (const bf16*)d_in[12], (const bf16*)d_in[13], (const char*)d_in[8], (const bf16*)d_in[9],
                                     (const char*)d_in[5], xc, dF, dA, dS, dM, dG, dP, dX, dD, dZ, dQ, dV, dX2);
  cudaLaunchConfig_t cfg = {};
  cfg.gridDim = dim3(132); cfg.blockDim = dim3(384); cfg.dynamicSmemBytes = ffn::SMEM; cfg.stream = st;
  cudaLaunchAttribute at[1];
  at[0].id = cudaLaunchAttributeProgrammaticStreamSerialization;
  at[0].val.programmaticStreamSerializationAllowed = 1;
  cfg.attrs = at; cfg.numAttrs = 1;
  cudaLaunchKernelEx(&cfg, k_ffn, fm, (const bf16*)d_in[11]);
}
```
